```python
import torch

def _softmax(x, axis=-1):
    return torch.softmax(x, dim=axis)
def _gelu(x):
    return torch.nn.functional.gelu(x, approximate="tanh")
def _silu(x):
    return torch.nn.functional.silu(x)
def _sigmoid(x):
    return torch.sigmoid(x)
def _layernorm(x, axis=-1, eps=1e-5):
    m = x.mean(dim=axis, keepdim=True)
    v = x.var(dim=axis, keepdim=True, unbiased=False)
    return (x - m) / torch.sqrt(v + eps)
def _scatter_add(tgt, idx, src, axis=0):
    return tgt.clone().index_add_(axis, idx, src)
def _segment_sum(src, seg, n):
    out = torch.zeros((n,) + src.shape[1:], dtype=src.dtype)
    return out.index_add_(0, seg, src)
def _pad(x, pw):
    flat = tuple(v for pair in reversed(pw) for v in pair)
    return torch.nn.functional.pad(x, flat)

kernel_name = 'parallel_sum__compressed_kv_cla__moe_arch_mod__prompt'

def setup_inputs():

    _w = (lambda a: (lambda t: t.to(torch.bfloat16) if t.is_floating_point() else t)(torch.as_tensor(a)))
    def _A_setup():
        B, H, Sq, Sk, D, M = 1, 32, 2048, 2048, 128, 640
        Dc = 4 * D
        return {
            "x": _w((lambda *s: torch.randn(*s, dtype=torch.bfloat16) * 0.05)(B, Sq, M)),
            "c_kv": _w((lambda *s: torch.randn(*s, dtype=torch.bfloat16) * 1.6)(B, Sk, Dc)),
            "w_q": _w((lambda *s: torch.randn(*s, dtype=torch.bfloat16) * 0.8)(M, H, D) * (M ** -0.5)),
            "w_uk": _w((lambda *s: torch.randn(*s, dtype=torch.bfloat16) * 0.8)(Dc, H, D) * (Dc ** -0.5)),
            "w_uv": _w((lambda *s: torch.randn(*s, dtype=torch.bfloat16) * 1.6)(Dc, H, D) * (Dc ** -0.5)),
            "w_o": _w((lambda *s: torch.randn(*s, dtype=torch.bfloat16) * 1.6)(H, D, M) * ((H * D) ** -0.5)),
        }
    _A_in = _A_setup()

    def _B_setup():
        B, S, D, F, C = 1, 2048, 640, 1728, 8
        return {
            "x": _w((lambda *s: torch.randn(*s, dtype=torch.bfloat16) * 0.05)(B, S, D)),
            "w_r": _w((lambda *s: torch.randn(*s, dtype=torch.bfloat16) * 0.05)(D)),
            "w_gate": _w((lambda *s: torch.randn(*s, dtype=torch.bfloat16) * 0.05)(D, F)),
            "w_up": _w((lambda *s: torch.randn(*s, dtype=torch.bfloat16) * 0.05)(D, F)),
            "w_down": _w((lambda *s: torch.randn(*s, dtype=torch.bfloat16) * 0.05)(F, D)),
        }
    _B_in = _B_setup()

    return {
        "A_x": _A_in["x"],
        "A_c_kv": _A_in["c_kv"],
        "A_w_q": _A_in["w_q"],
        "A_w_uk": _A_in["w_uk"],
        "A_w_uv": _A_in["w_uv"],
        "A_w_o": _A_in["w_o"],
        "B_x": _B_in["x"],
        "B_w_r": _B_in["w_r"],
        "B_w_gate": _B_in["w_gate"],
        "B_w_up": _B_in["w_up"],
        "B_w_down": _B_in["w_down"],
    }

def reference(A_x, A_c_kv, A_w_q, A_w_uk, A_w_uv, A_w_o, B_x, B_w_r, B_w_gate, B_w_up, B_w_down):
    def _A_ref(x, c_kv, w_q, w_uk, w_uv, w_o):
        B, Sq, M = x.shape[0], x.shape[1], x.shape[2]
        Sk = c_kv.shape[1]
        H, D = w_q.shape[1], w_q.shape[2]
        q = torch.einsum("bqm,mhd->bhqd", x, w_q)
        k = torch.einsum("bkc,chd->bhkd", c_kv, w_uk)
        v = torch.einsum("bkc,chd->bhkd", c_kv, w_uv)
        scores = torch.einsum("bhqd,bhkd->bhqk", q, k) * (D ** -0.5)
        off = Sk - Sq
        qi = torch.arange(Sq)[:, None]
        kj = torch.arange(Sk)[None, :]
        cmask = kj <= (qi + off)
        scores = torch.where(cmask[None, None], scores, -1e9)
        p = _softmax(scores, axis=-1)
        ctx = torch.einsum("bhqk,bhkd->bhqd", p, v)
        return torch.einsum("bhqd,hdm->bqm", ctx, w_o)

    def _B_ref(x, w_r, w_gate, w_up, w_down):
        B, S, D = x.shape
        C = 8
        r = x @ w_r
        idx = torch.argsort(-r, axis=-1)[:, :C]
        idx_e = (lambda x, n, axis: torch.repeat_interleave(x, n, dim=axis))(idx.reshape(B, C, 1), D, axis=2)
        x_sel = (lambda x, i, axis: torch.take_along_dim(x, i, dim=axis))(x, idx_e, axis=1)
        g = _silu(x_sel @ w_gate)
        u = x_sel @ w_up
        y = (g * u) @ w_down
        r_sel = _sigmoid((lambda x, i, axis: torch.take_along_dim(x, i, dim=axis))(r, idx, axis=1))
        y = y * r_sel.reshape(B, C, 1)
        b_off = (torch.arange(B) * S).reshape(B, 1)
        flat_idx = (idx + b_off).reshape(B * C)
        zero = (x * 0.0).reshape(B * S, D)
        upd = _scatter_add(zero, flat_idx, y.reshape(B * C, D), axis=0)
        return x + upd.reshape(B, S, D)

    x = A_x
    xn = _layernorm(x, axis=-1)
    return x + _A_ref(xn, A_c_kv, A_w_q, A_w_uk, A_w_uv, A_w_o) + _B_ref(xn, B_w_r, B_w_gate, B_w_up, B_w_down)
```

```cpp
#include <cuda_runtime.h>
#include <cuda_bf16.h>
#include <cuda.h>
#include <stdint.h>

namespace {

constexpr int SEQ = 2048, NH = 32, DM = 640, DC = 512, FF = 1728, TOPC = 8;
constexpr int NSLOT = 7, SLOT_BYTES = 32768;
constexpr int NST3 = 6, ST3_BYTES = 36864;
constexpr int RING_BYTES = NSLOT * SLOT_BYTES;
constexpr int SMEM_BYTES = RING_BYTES + 2048;

constexpr int BAR_FULL = 0, BAR_EMPTY = 64, BAR_FULL3 = 128, BAR_EMPTY3 = 192, BAR_EV = 256  , BAR_EPOCH = 416, MISC_EPOCH = 432;

constexpr int FL_LN = 0, FL_MOE_CNT = 1, FL_MOE_DONE = 2, FL_KV = 8  , FL_Q = 64  , FL_CTX = 320  , FL_EX = 576  , FL_TOTAL = 1600;

__device__ __align__(1024) unsigned char g_K[NH * 32 * 16384];
__device__ __align__(1024) unsigned char g_V[NH * 32 * 16384];
__device__ __align__(1024) unsigned char g_Q[NH * 32 * 16384];
__device__ __align__(1024) unsigned char g_xn[16 * 10 * 16384];
__device__ __align__(1024) float4 g_part[128 * 10 * 256];
__device__ float g_router[SEQ];
__device__ float g_moe_part[4 * TOPC * DM];
__device__ __align__(16) __nv_bfloat16 g_brow[TOPC * DM];
__device__ int g_sel[TOPC];
__device__ unsigned g_flags[FL_TOTAL * 8];
__device__ unsigned g_epoch;

struct Params {
    const __nv_bfloat16 *x, *wr, *wg, *wu, *wd, *wq, *wo;
    __nv_bfloat16* out;
};

__device__ __forceinline__ uint32_t smem_u32(const void* p) { return (uint32_t)__cvta_generic_to_shared(p); }
__device__ __forceinline__ void mbar_init(uint32_t bar, int cnt) { asm volatile("mbarrier.init.shared::cta.b64 [%0], %1;" ::"r"(bar), "r"(cnt)); }
__device__ __forceinline__ void mbar_expect_tx(uint32_t bar, uint32_t bytes) {
    asm volatile("mbarrier.arrive.expect_tx.shared::cta.b64 _, [%0], %1;" ::"r"(bar), "r"(bytes) : "memory");
}
__device__ __forceinline__ void mbar_arrive(uint32_t bar) { asm volatile("mbarrier.arrive.shared::cta.b64 _, [%0];" ::"r"(bar) : "memory"); }
__device__ __forceinline__ void mbar_arrive_cluster(uint32_t cluster_addr, uint32_t cnt) {
    asm volatile("mbarrier.arrive.shared::cluster.b64 _, [%0], %1;" ::"r"(cluster_addr), "r"(cnt) : "memory");
}
__device__ __forceinline__ uint32_t mapa(uint32_t addr, uint32_t cta) {
    uint32_t r; asm("mapa.shared::cluster.u32 %0, %1, %2;" : "=r"(r) : "r"(addr), "r"(cta)); return r;
}
__device__ __forceinline__ void mbar_wait(uint32_t bar, uint32_t parity) {
    asm volatile(
        "{\n.reg .pred p;\n.reg .u32 n;\n"
        "mbarrier.try_wait.parity.shared::cta.b64 p, [%0], %1;\n"
        "@p bra DONE;\n"
        "mov.u32 n, 0;\n"
        "LAB_WAIT:\n"
        "mbarrier.try_wait.parity.shared::cta.b64 p, [%0], %1;\n"
        "@p bra DONE;\n"
        "add.u32 n, n, 1;\n"
        "setp.lt.u32 p, n, 2000000;\n"
        "@p bra LAB_WAIT;\n"
        "trap;\n"
        "DONE:\n}\n" ::"r"(bar), "r"(parity) : "memory");
}
__device__ __forceinline__ void flag_wait(const unsigned* flag, unsigned target) {
    asm volatile(
        "{\n.reg .pred p;\n.reg .u32 n, v;\n.reg .s32 d;\n"
        "mov.u32 n, 0;\n"
        "LAB_WAIT:\n"
        "ld.acquire.gpu.global.u32 v, [%0];\n"
        "sub.s32 d, v, %1;\n"
        "setp.ge.s32 p, d, 0;\n"
        "@p bra DONE;\n"
        "nanosleep.u32 40;\n"
        "add.u32 n, n, 1;\n"
        "setp.lt.u32 p, n, 3000000;\n"
        "@p bra LAB_WAIT;\n"
        "trap;\n"
        "DONE:\n}\n" ::"l"(flag), "r"(target) : "memory");
}
__device__ __forceinline__ void flag_signal(unsigned* flag) {
    asm volatile("red.release.gpu.global.add.u32 [%0], 1;" ::"l"(flag) : "memory");
}
__device__ __forceinline__ void fence_async_global() { asm volatile("fence.proxy.async.global;" ::: "memory"); }
__device__ __forceinline__ unsigned* flag_ptr(int idx) { return g_flags + idx * 8; }

__device__ __forceinline__ void bulk_load(uint32_t dst, const void* src, uint32_t bytes, uint32_t bar) {
    asm volatile("cp.async.bulk.shared::cluster.global.mbarrier::complete_tx::bytes [%0], [%1], %2, [%3];"
                 ::"r"(dst), "l"(src), "r"(bytes), "r"(bar) : "memory");
}
__device__ __forceinline__ void bulk_load_mc(uint32_t dst, const void* src, uint32_t bytes, uint32_t bar) {
    asm volatile("cp.async.bulk.shared::cluster.global.mbarrier::complete_tx::bytes.multicast::cluster [%0], [%1], %2, [%3], %4;"
                 ::"r"(dst), "l"(src), "r"(bytes), "r"(bar), "h"((uint16_t)3) : "memory");
}
__device__ __forceinline__ void tma2d(uint32_t dst, const CUtensorMap* tm, int c0, int c1, uint32_t bar) {
    asm volatile("cp.async.bulk.tensor.2d.shared::cluster.global.mbarrier::complete_tx::bytes [%0], [%1, {%3, %4}], [%2];"
                 ::"r"(dst), "l"(tm), "r"(bar), "r"(c0), "r"(c1) : "memory");
}
__device__ __forceinline__ void tma2d_mc(uint32_t dst, const CUtensorMap* tm, int c0, int c1, uint32_t bar) {
    asm volatile("cp.async.bulk.tensor.2d.shared::cluster.global.mbarrier::complete_tx::bytes.multicast::cluster [%0], [%1, {%3, %4}], [%2], %5;"
                 ::"r"(dst), "l"(tm), "r"(bar), "r"(c0), "r"(c1), "h"((uint16_t)3) : "memory");
}
__device__ __forceinline__ void tma3d_mc(uint32_t dst, const CUtensorMap* tm, int c0, int c1, int c2, uint32_t bar) {
    asm volatile("cp.async.bulk.tensor.3d.shared::cluster.global.mbarrier::complete_tx::bytes.multicast::cluster [%0], [%1, {%3, %4, %5}], [%2], %6;"
                 ::"r"(dst), "l"(tm), "r"(bar), "r"(c0), "r"(c1), "r"(c2), "h"((uint16_t)3) : "memory");
}
__device__ __forceinline__ void l2_prefetch(const void* p, uint32_t bytes) {
    asm volatile("cp.async.bulk.prefetch.L2.global [%0], %1;" ::"l"(p), "r"(bytes) : "memory");
}
__device__ __forceinline__ void wg_fence() { asm volatile("wgmma.fence.sync.aligned;" ::: "memory"); }
__device__ __forceinline__ void wg_commit() { asm volatile("wgmma.commit_group.sync.aligned;" ::: "memory"); }
template <int N> __device__ __forceinline__ void wg_wait() { asm volatile("wgmma.wait_group.sync.aligned %0;" ::"n"(N) : "memory"); }
__device__ __forceinline__ void bar_sync(int id, int n) { asm volatile("bar.sync %0, %1;" ::"r"(id), "r"(n) : "memory"); }
__device__ __forceinline__ void bar_arrive(int id, int n) { asm volatile("bar.arrive %0, %1;" ::"r"(id), "r"(n) : "memory"); }
template <int N> __device__ __forceinline__ void fence_regs(float (&a)[N]) {
#pragma unroll
    for (int i = 0; i < N; i++) asm volatile("" : "+f"(a[i])::"memory");
}
__device__ __forceinline__ void ldsm4t(uint32_t& r0, uint32_t& r1, uint32_t& r2, uint32_t& r3, uint32_t addr) {
    asm volatile("ldmatrix.sync.aligned.m8n8.x4.trans.shared.b16 {%0,%1,%2,%3}, [%4];"
                 : "=r"(r0), "=r"(r1), "=r"(r2), "=r"(r3) : "r"(addr) : "memory");
}
__device__ __forceinline__ uint32_t pack_bf16(float lo, float hi) {
    uint32_t r; asm("cvt.rn.bf16x2.f32 %0, %1, %2;" : "=r"(r) : "f"(hi), "f"(lo)); return r;
}
__device__ __forceinline__ float bf_lo(uint32_t v) { return __uint_as_float(v << 16); }
__device__ __forceinline__ float bf_hi(uint32_t v) { return __uint_as_float(v & 0xffff0000u); }
__device__ __forceinline__ float bf_round(float v) { return __bfloat162float(__float2bfloat16_rn(v)); }
__device__ __forceinline__ float ex2(float v) { float r; asm("ex2.approx.ftz.f32 %0, %1;" : "=f"(r) : "f"(v)); return r; }
__device__ __forceinline__ void stg128(void* p, uint32_t a, uint32_t b, uint32_t c, uint32_t d) {
    asm volatile("st.global.v4.b32 [%0], {%1,%2,%3,%4};" ::"l"(p), "r"(a), "r"(b), "r"(c), "r"(d) : "memory");
}
__device__ __forceinline__ uint64_t mkdesc(uint32_t addr, uint32_t lbo, uint32_t sbo, uint32_t swz) {
    uint32_t lo = ((addr & 0x3FFFF) >> 4) | ((lbo >> 4) << 16);
    uint32_t hi = (sbo >> 4) | (swz << 30);
    return ((uint64_t)hi << 32) | lo;
}
__device__ __forceinline__ int perm32(int v) { return (v & ~30) | ((v >> 2) & 6) | ((v << 2) & 24); }

__device__ __forceinline__ void wgmma_rs_n128_ta0_tb0(float (&d)[64], uint32_t a0, uint32_t a1, uint32_t a2, uint32_t a3, uint64_t descB, int scaleD) {
  asm volatile("{\n.reg .pred p;\nsetp.ne.b32 p, %69, 0;\n"
    "wgmma.mma_async.sync.aligned.m64n128k16.f32.bf16.bf16 "
    "{%0, %1, %2, %3, %4, %5, %6, %7, %8, %9, %10, %11, %12, %13, %14, %15, %16, %17, %18, %19, %20, %21, %22, %23, %24, %25, %26, %27, %28, %29, %30, %31, %32, %33, %34, %35, %36, %37, %38, %39, %40, %41, %42, %43, %44, %45, %46, %47, %48, %49, %50, %51, %52, %53, %54, %55, %56, %57, %58, %59, %60, %61, %62, %63}, "
    "{%64, %65, %66, %67}, %68, p, 1, 1, 0;\n}\n"
    : "+f"(d[0]), "+f"(d[1]), "+f"(d[2]), "+f"(d[3]), "+f"(d[4]), "+f"(d[5]), "+f"(d[6]), "+f"(d[7]), "+f"(d[8]), "+f"(d[9]), "+f"(d[10]), "+f"(d[11]), "+f"(d[12]), "+f"(d[13]), "+f"(d[14]), "+f"(d[15]), "+f"(d[16]), "+f"(d[17]), "+f"(d[18]), "+f"(d[19]), "+f"(d[20]), "+f"(d[21]), "+f"(d[22]), "+f"(d[23]), "+f"(d[24]), "+f"(d[25]), "+f"(d[26]), "+f"(d[27]), "+f"(d[28]), "+f"(d[29]), "+f"(d[30]), "+f"(d[31]), "+f"(d[32]), "+f"(d[33]), "+f"(d[34]), "+f"(d[35]), "+f"(d[36]), "+f"(d[37]), "+f"(d[38]), "+f"(d[39]), "+f"(d[40]), "+f"(d[41]), "+f"(d[42]), "+f"(d[43]), "+f"(d[44]), "+f"(d[45]), "+f"(d[46]), "+f"(d[47]), "+f"(d[48]), "+f"(d[49]), "+f"(d[50]), "+f"(d[51]), "+f"(d[52]), "+f"(d[53]), "+f"(d[54]), "+f"(d[55]), "+f"(d[56]), "+f"(d[57]), "+f"(d[58]), "+f"(d[59]), "+f"(d[60]), "+f"(d[61]), "+f"(d[62]), "+f"(d[63])
    : "r"(a0), "r"(a1), "r"(a2), "r"(a3), "l"(descB), "r"(scaleD));
}
__device__ __forceinline__ void wgmma_rs_n128_ta0_tb1(float (&d)[64], uint32_t a0, uint32_t a1, uint32_t a2, uint32_t a3, uint64_t descB, int scaleD) {
  asm volatile("{\n.reg .pred p;\nsetp.ne.b32 p, %69, 0;\n"
    "wgmma.mma_async.sync.aligned.m64n128k16.f32.bf16.bf16 "
    "{%0, %1, %2, %3, %4, %5, %6, %7, %8, %9, %10, %11, %12, %13, %14, %15, %16, %17, %18, %19, %20, %21, %22, %23, %24, %25, %26, %27, %28, %29, %30, %31, %32, %33, %34, %35, %36, %37, %38, %39, %40, %41, %42, %43, %44, %45, %46, %47, %48, %49, %50, %51, %52, %53, %54, %55, %56, %57, %58, %59, %60, %61, %62, %63}, "
    "{%64, %65, %66, %67}, %68, p, 1, 1, 1;\n}\n"
    : "+f"(d[0]), "+f"(d[1]), "+f"(d[2]), "+f"(d[3]), "+f"(d[4]), "+f"(d[5]), "+f"(d[6]), "+f"(d[7]), "+f"(d[8]), "+f"(d[9]), "+f"(d[10]), "+f"(d[11]), "+f"(d[12]), "+f"(d[13]), "+f"(d[14]), "+f"(d[15]), "+f"(d[16]), "+f"(d[17]), "+f"(d[18]), "+f"(d[19]), "+f"(d[20]), "+f"(d[21]), "+f"(d[22]), "+f"(d[23]), "+f"(d[24]), "+f"(d[25]), "+f"(d[26]), "+f"(d[27]), "+f"(d[28]), "+f"(d[29]), "+f"(d[30]), "+f"(d[31]), "+f"(d[32]), "+f"(d[33]), "+f"(d[34]), "+f"(d[35]), "+f"(d[36]), "+f"(d[37]), "+f"(d[38]), "+f"(d[39]), "+f"(d[40]), "+f"(d[41]), "+f"(d[42]), "+f"(d[43]), "+f"(d[44]), "+f"(d[45]), "+f"(d[46]), "+f"(d[47]), "+f"(d[48]), "+f"(d[49]), "+f"(d[50]), "+f"(d[51]), "+f"(d[52]), "+f"(d[53]), "+f"(d[54]), "+f"(d[55]), "+f"(d[56]), "+f"(d[57]), "+f"(d[58]), "+f"(d[59]), "+f"(d[60]), "+f"(d[61]), "+f"(d[62]), "+f"(d[63])
    : "r"(a0), "r"(a1), "r"(a2), "r"(a3), "l"(descB), "r"(scaleD));
}
__device__ __forceinline__ void wgmma_rs_n64_ta0_tb1(float (&d)[32], uint32_t a0, uint32_t a1, uint32_t a2, uint32_t a3, uint64_t descB, int scaleD) {
  asm volatile("{\n.reg .pred p;\nsetp.ne.b32 p, %37, 0;\n"
    "wgmma.mma_async.sync.aligned.m64n64k16.f32.bf16.bf16 "
    "{%0, %1, %2, %3, %4, %5, %6, %7, %8, %9, %10, %11, %12, %13, %14, %15, %16, %17, %18, %19, %20, %21, %22, %23, %24, %25, %26, %27, %28, %29, %30, %31}, "
    "{%32, %33, %34, %35}, %36, p, 1, 1, 1;\n}\n"
    : "+f"(d[0]), "+f"(d[1]), "+f"(d[2]), "+f"(d[3]), "+f"(d[4]), "+f"(d[5]), "+f"(d[6]), "+f"(d[7]), "+f"(d[8]), "+f"(d[9]), "+f"(d[10]), "+f"(d[11]), "+f"(d[12]), "+f"(d[13]), "+f"(d[14]), "+f"(d[15]), "+f"(d[16]), "+f"(d[17]), "+f"(d[18]), "+f"(d[19]), "+f"(d[20]), "+f"(d[21]), "+f"(d[22]), "+f"(d[23]), "+f"(d[24]), "+f"(d[25]), "+f"(d[26]), "+f"(d[27]), "+f"(d[28]), "+f"(d[29]), "+f"(d[30]), "+f"(d[31])
    : "r"(a0), "r"(a1), "r"(a2), "r"(a3), "l"(descB), "r"(scaleD));
}
__device__ __forceinline__ void wgmma_ss_n128_ta1_tb0(float (&d)[64], uint64_t descA, uint64_t descB, int scaleD) {
  asm volatile("{\n.reg .pred p;\nsetp.ne.b32 p, %66, 0;\n"
    "wgmma.mma_async.sync.aligned.m64n128k16.f32.bf16.bf16 "
    "{%0, %1, %2, %3, %4, %5, %6, %7, %8, %9, %10, %11, %12, %13, %14, %15, %16, %17, %18, %19, %20, %21, %22, %23, %24, %25, %26, %27, %28, %29, %30, %31, %32, %33, %34, %35, %36, %37, %38, %39, %40, %41, %42, %43, %44, %45, %46, %47, %48, %49, %50, %51, %52, %53, %54, %55, %56, %57, %58, %59, %60, %61, %62, %63}, "
    "%64, %65, p, 1, 1, 1, 0;\n}\n"
    : "+f"(d[0]), "+f"(d[1]), "+f"(d[2]), "+f"(d[3]), "+f"(d[4]), "+f"(d[5]), "+f"(d[6]), "+f"(d[7]), "+f"(d[8]), "+f"(d[9]), "+f"(d[10]), "+f"(d[11]), "+f"(d[12]), "+f"(d[13]), "+f"(d[14]), "+f"(d[15]), "+f"(d[16]), "+f"(d[17]), "+f"(d[18]), "+f"(d[19]), "+f"(d[20]), "+f"(d[21]), "+f"(d[22]), "+f"(d[23]), "+f"(d[24]), "+f"(d[25]), "+f"(d[26]), "+f"(d[27]), "+f"(d[28]), "+f"(d[29]), "+f"(d[30]), "+f"(d[31]), "+f"(d[32]), "+f"(d[33]), "+f"(d[34]), "+f"(d[35]), "+f"(d[36]), "+f"(d[37]), "+f"(d[38]), "+f"(d[39]), "+f"(d[40]), "+f"(d[41]), "+f"(d[42]), "+f"(d[43]), "+f"(d[44]), "+f"(d[45]), "+f"(d[46]), "+f"(d[47]), "+f"(d[48]), "+f"(d[49]), "+f"(d[50]), "+f"(d[51]), "+f"(d[52]), "+f"(d[53]), "+f"(d[54]), "+f"(d[55]), "+f"(d[56]), "+f"(d[57]), "+f"(d[58]), "+f"(d[59]), "+f"(d[60]), "+f"(d[61]), "+f"(d[62]), "+f"(d[63])
    : "l"(descA), "l"(descB), "r"(scaleD));
}
__device__ __forceinline__ void wgmma_ss_n160_ta0_tb1(float (&d)[80], uint64_t descA, uint64_t descB, int scaleD) {
  asm volatile("{\n.reg .pred p;\nsetp.ne.b32 p, %82, 0;\n"
    "wgmma.mma_async.sync.aligned.m64n160k16.f32.bf16.bf16 "
    "{%0, %1, %2, %3, %4, %5, %6, %7, %8, %9, %10, %11, %12, %13, %14, %15, %16, %17, %18, %19, %20, %21, %22, %23, %24, %25, %26, %27, %28, %29, %30, %31, %32, %33, %34, %35, %36, %37, %38, %39, %40, %41, %42, %43, %44, %45, %46, %47, %48, %49, %50, %51, %52, %53, %54, %55, %56, %57, %58, %59, %60, %61, %62, %63, %64, %65, %66, %67, %68, %69, %70, %71, %72, %73, %74, %75, %76, %77, %78, %79}, "
    "%80, %81, p, 1, 1, 0, 1;\n}\n"
    : "+f"(d[0]), "+f"(d[1]), "+f"(d[2]), "+f"(d[3]), "+f"(d[4]), "+f"(d[5]), "+f"(d[6]), "+f"(d[7]), "+f"(d[8]), "+f"(d[9]), "+f"(d[10]), "+f"(d[11]), "+f"(d[12]), "+f"(d[13]), "+f"(d[14]), "+f"(d[15]), "+f"(d[16]), "+f"(d[17]), "+f"(d[18]), "+f"(d[19]), "+f"(d[20]), "+f"(d[21]), "+f"(d[22]), "+f"(d[23]), "+f"(d[24]), "+f"(d[25]), "+f"(d[26]), "+f"(d[27]), "+f"(d[28]), "+f"(d[29]), "+f"(d[30]), "+f"(d[31]), "+f"(d[32]), "+f"(d[33]), "+f"(d[34]), "+f"(d[35]), "+f"(d[36]), "+f"(d[37]), "+f"(d[38]), "+f"(d[39]), "+f"(d[40]), "+f"(d[41]), "+f"(d[42]), "+f"(d[43]), "+f"(d[44]), "+f"(d[45]), "+f"(d[46]), "+f"(d[47]), "+f"(d[48]), "+f"(d[49]), "+f"(d[50]), "+f"(d[51]), "+f"(d[52]), "+f"(d[53]), "+f"(d[54]), "+f"(d[55]), "+f"(d[56]), "+f"(d[57]), "+f"(d[58]), "+f"(d[59]), "+f"(d[60]), "+f"(d[61]), "+f"(d[62]), "+f"(d[63]), "+f"(d[64]), "+f"(d[65]), "+f"(d[66]), "+f"(d[67]), "+f"(d[68]), "+f"(d[69]), "+f"(d[70]), "+f"(d[71]), "+f"(d[72]), "+f"(d[73]), "+f"(d[74]), "+f"(d[75]), "+f"(d[76]), "+f"(d[77]), "+f"(d[78]), "+f"(d[79])
    : "l"(descA), "l"(descB), "r"(scaleD));
}

#define PROF_DECL
#define PROF_EV(tag)
#define PROF_GT(tag)

struct Cur {
    uint32_t slot, ph;
    __device__ __forceinline__ void adv() { if (++slot == NSLOT) { slot = 0; ph ^= 1; } }
};
__device__ __forceinline__ Cur cur_at(int e) { Cur c; c.slot = e % NSLOT; c.ph = (e / NSLOT) & 1; return c; }

__device__ __forceinline__ int blk_of(int a, int i) { return ((a ? 0x2516u : 0x3407u) >> (4 * i)) & 7; }
__device__ __forceinline__ int pos_of(int u) { return (0x00223311u >> (4 * u)) & 3; }

constexpr float SM_SCALE = 0.08838834764831845f * 1.4426950408889634f;

struct Ctx {
    uint32_t ring, misc;
    uint32_t rel;
    int t128, w, warp, lane;
};
__device__ __forceinline__ void release(const Ctx& c, uint32_t off, uint32_t cnt) {
    if (c.t128 < 2) mbar_arrive_cluster(c.rel + off, cnt);
}
__device__ __forceinline__ void signal_event(const Ctx& c, int ev) {
    __syncwarp();
    if (c.lane == 0) mbar_arrive(c.misc + BAR_EV + (c.w * 9 + ev) * 8);
}
template <int NK, int OFF, int N>
__device__ __forceinline__ void load_afrag(uint32_t (&a)[N], uint32_t base, const Ctx& c) {
    int r = c.lane & 7, mat = c.lane >> 3;
    uint32_t addr = base + (8 * (mat >> 1) + r) * 128 + (((2 * c.warp + (mat & 1)) ^ r) << 4);
#pragma unroll
    for (int k = 0; k < NK; k++) ldsm4t(a[OFF + 4 * k], a[OFF + 4 * k + 1], a[OFF + 4 * k + 2], a[OFF + 4 * k + 3], addr + k * 2048);
}
__device__ __forceinline__ void store_proj(const float (&acc)[64], unsigned char* dst  , const Ctx& c) {
    int g = c.lane >> 2, t = c.lane & 3;
#pragma unroll
    for (int i = 0; i < 2; i++) {
        int row = perm32(64 * c.w + 16 * c.warp + 8 * i + g);
        unsigned char* p = dst + row * 128;
#pragma unroll
        for (int q = 0; q < 4; q++) {
            int chunk = (4 * (q & 1) + t) ^ (row & 7);
            stg128(p + (q >> 1) * 16384 + chunk * 16,
                   pack_bf16(acc[16 * q + 2 * i], acc[16 * q + 2 * i + 1]), pack_bf16(acc[16 * q + 4 + 2 * i], acc[16 * q + 4 + 2 * i + 1]),
                   pack_bf16(acc[16 * q + 8 + 2 * i], acc[16 * q + 8 + 2 * i + 1]), pack_bf16(acc[16 * q + 12 + 2 * i], acc[16 * q + 12 + 2 * i + 1]));
        }
    }
}

template <int NJ, bool FIRST>
__device__ __forceinline__ void softmax_step(float (&s)[64], float (&m)[2], float (&l)[2], float (&alpha)[2]) {
#pragma unroll
    for (int i = 0; i < 2; i++) {
        float a = fmaxf(s[2 * i], s[2 * i + 1]), b = fmaxf(s[4 + 2 * i], s[4 + 2 * i + 1]);
#pragma unroll
        for (int j = 2; j < NJ; j += 2) {
            a = fmaxf(a, fmaxf(s[4 * j + 2 * i], s[4 * j + 2 * i + 1]));
            b = fmaxf(b, fmaxf(s[4 * j + 4 + 2 * i], s[4 * j + 4 + 2 * i + 1]));
        }
        a = fmaxf(a, b);
        a = fmaxf(a, __shfl_xor_sync(0xffffffffu, a, 1));
        a = fmaxf(a, __shfl_xor_sync(0xffffffffu, a, 2));
        if (!FIRST) {
            a = fmaxf(a, m[i]);
            alpha[i] = ex2((m[i] - a) * SM_SCALE);
        }
        m[i] = a;
    }
    float ms0 = m[0] * SM_SCALE, ms1 = m[1] * SM_SCALE;
    float s0 = 0.f, s1 = 0.f, s2 = 0.f, s3 = 0.f;
#pragma unroll
    for (int j = 0; j < NJ; j++) {
        s[4 * j + 0] = ex2(fmaf(s[4 * j + 0], SM_SCALE, -ms0));
        s[4 * j + 1] = ex2(fmaf(s[4 * j + 1], SM_SCALE, -ms0));
        s[4 * j + 2] = ex2(fmaf(s[4 * j + 2], SM_SCALE, -ms1));
        s[4 * j + 3] = ex2(fmaf(s[4 * j + 3], SM_SCALE, -ms1));
        s0 += s[4 * j + 0]; s1 += s[4 * j + 1]; s2 += s[4 * j + 2]; s3 += s[4 * j + 3];
    }
    if (FIRST) { l[0] = s0 + s1; l[1] = s2 + s3; }
    else { l[0] = fmaf(l[0], alpha[0], s0 + s1); l[1] = fmaf(l[1], alpha[1], s2 + s3); }
}
template <int J0>
__device__ __forceinline__ void mask_diag(float (&s)[64], const Ctx& c) {
    int g = c.lane >> 2, t = c.lane & 3;
#pragma unroll
    for (int i = 0; i < 2; i++) {
        int lim = perm32(16 * c.warp + 8 * i + g) - 8 * t;
#pragma unroll
        for (int j = 0; j < 8; j++)
#pragma unroll
            for (int e = 0; e < 2; e++)
                if (32 * (j >> 2) + 2 * (j & 3) + e > lim) s[4 * (J0 + j) + 2 * i + e] = -INFINITY;
    }
}
__device__ __forceinline__ void issue_pv(float (&o)[64], const uint32_t (&p)[32], uint32_t vaddr, int acc, bool half) {
    uint64_t d = mkdesc(vaddr, 16, 1024, 1);
    if (half) {
        wg_fence();
#pragma unroll
        for (int k = 0; k < 4; k++) wgmma_rs_n128_ta0_tb0(o, p[4 * k], p[4 * k + 1], p[4 * k + 2], p[4 * k + 3], d + 2 * k, k != 0);
        wg_commit();
    } else {
        wg_fence();
#pragma unroll
        for (int k = 0; k < 8; k++)
            wgmma_rs_n128_ta0_tb0(o, p[4 * k], p[4 * k + 1], p[4 * k + 2], p[4 * k + 3], d + (k >> 2) * 1024 + 2 * (k & 3), k ? 1 : acc);
        wg_commit();
    }
}
__device__ __forceinline__ void issue_qk(float (&s)[64], const uint32_t (&q)[32], uint32_t kaddr) {
    uint64_t d = mkdesc(kaddr, 16384, 1024, 1);
    wg_fence();
#pragma unroll
    for (int k = 0; k < 8; k++) wgmma_rs_n128_ta0_tb1(s, q[4 * k], q[4 * k + 1], q[4 * k + 2], q[4 * k + 3], d + 128 * k, k != 0);
    wg_commit();
}
__device__ __forceinline__ void issue_qk_half(float (&s)[64], const uint32_t (&q)[32], uint32_t kaddr) {
    uint64_t d = mkdesc(kaddr, 16384, 1024, 1);
    float(&s32)[32] = *reinterpret_cast<float(*)[32]>(&s[0]);
    wg_fence();
#pragma unroll
    for (int k = 0; k < 8; k++) wgmma_rs_n64_ta0_tb1(s32, q[4 * k], q[4 * k + 1], q[4 * k + 2], q[4 * k + 3], d + 128 * k, k != 0);
    wg_commit();
}
__device__ __forceinline__ void store_ctx(const float (&o)[64], const float (&l)[2], unsigned char* dst, const Ctx& c) {
    int g = c.lane >> 2, t = c.lane & 3;
#pragma unroll
    for (int i = 0; i < 2; i++) {
        float sum = l[i];
        sum += __shfl_xor_sync(0xffffffffu, sum, 1);
        sum += __shfl_xor_sync(0xffffffffu, sum, 2);
        float inv = 1.0f / sum;
        int row = perm32(16 * c.warp + 8 * i + g);
        unsigned char* p = dst + row * 128;
#pragma unroll
        for (int q = 0; q < 4; q++) {
            int chunk = (4 * (q & 1) + t) ^ (row & 7);
            stg128(p + (q >> 1) * 8192 + chunk * 16,
                   pack_bf16(o[16 * q + 2 * i] * inv, o[16 * q + 2 * i + 1] * inv), pack_bf16(o[16 * q + 4 + 2 * i] * inv, o[16 * q + 4 + 2 * i + 1] * inv),
                   pack_bf16(o[16 * q + 8 + 2 * i] * inv, o[16 * q + 8 + 2 * i + 1] * inv), pack_bf16(o[16 * q + 12 + 2 * i] * inv, o[16 * q + 12 + 2 * i + 1] * inv));
        }
    }
}

__device__ __forceinline__ const unsigned char* xn_addr(int row, int col) {
    return g_xn + ((row >> 7) * 10 + (col >> 6)) * 16384 + (row & 127) * 128 + ((((col & 63) >> 3) ^ (row & 7)) << 4);
}
__device__ __forceinline__ void gemv8(float (&acc)[64], const __nv_bfloat16* wp, int ld, const float* xs, int nk) {
#pragma unroll 1
    for (int k0 = 0; k0 < nk; k0 += 4) {
        uint4 wv[4];
#pragma unroll
        for (int u = 0; u < 4; u++) wv[u] = __ldg(reinterpret_cast<const uint4*>(wp + (size_t)(k0 + u) * ld));
#pragma unroll
        for (int u = 0; u < 4; u++) {
            float4 xa = *reinterpret_cast<const float4*>(xs + (k0 + u) * 8), xb = *reinterpret_cast<const float4*>(xs + (k0 + u) * 8 + 4);
            float xv[8] = {xa.x, xa.y, xa.z, xa.w, xb.x, xb.y, xb.z, xb.w};
            uint32_t ww[4] = {wv[u].x, wv[u].y, wv[u].z, wv[u].w};
#pragma unroll
            for (int cidx = 0; cidx < 4; cidx++) {
                float w0 = bf_lo(ww[cidx]), w1 = bf_hi(ww[cidx]);
#pragma unroll
                for (int tk = 0; tk < 8; tk++) {
                    acc[(2 * cidx) * 8 + tk] = fmaf(w0, xv[tk], acc[(2 * cidx) * 8 + tk]);
                    acc[(2 * cidx + 1) * 8 + tk] = fmaf(w1, xv[tk], acc[(2 * cidx + 1) * 8 + tk]);
                }
            }
        }
    }
}
__device__ __noinline__ void aux_cta(const Params& P, unsigned char* sm, int a) {
    const int tid = threadIdx.x;
    float* xs = reinterpret_cast<float*>(sm);
    float* hs = xs + DM * 8;
    float* red = hs + 432 * 8;
    __shared__ int s_sel[TOPC];
    __shared__ float s_r[TOPC];
    __shared__ unsigned s_epoch, s_last;
    if (tid == 0) {
        unsigned ep = *reinterpret_cast<volatile unsigned*>(&g_epoch);
        s_epoch = ep;
        flag_wait(flag_ptr(FL_LN), (ep + 1) * 384u);
    }
    __syncthreads();
    const unsigned ep = s_epoch;
    if (tid < 32) {
        uint32_t key[64];
#pragma unroll
        for (int i = 0; i < 64; i++) {
            int idx = i * 32 + tid;
            uint32_t b = __float_as_uint(__ldcg(g_router + idx)) >> 16;
            b = (b & 0x8000u) ? (~b & 0xffffu) : (b | 0x8000u);
            key[i] = (b << 16) | (uint32_t)(0xffff - idx);
        }
        uint32_t bound = 0xffffffffu;
        for (int r = 0; r < TOPC; r++) {
            uint32_t best = 0;
#pragma unroll
            for (int i = 0; i < 64; i++) best = max(best, key[i] <= bound ? key[i] : 0u);
            best = __reduce_max_sync(0xffffffffu, best);
            bound = best - 1;
            if (tid == 0) { int idx = 0xffff - (int)(best & 0xffffu); s_sel[r] = idx; s_r[r] = __ldcg(g_router + idx); }
        }
    }
    __syncthreads();
    for (int i = tid; i < TOPC * 80; i += 384) {
        int tk = i / 80, ch = i % 80;
        uint4 v = __ldcg(reinterpret_cast<const uint4*>(xn_addr(s_sel[tk], ch * 8)));
        uint32_t ww[4] = {v.x, v.y, v.z, v.w};
#pragma unroll
        for (int e = 0; e < 4; e++) { xs[(ch * 8 + 2 * e) * 8 + tk] = bf_lo(ww[e]); xs[(ch * 8 + 2 * e + 1) * 8 + tk] = bf_hi(ww[e]); }
    }
    __syncthreads();
    float acc[64];
    if (tid < 324) {
        int item = tid % 108, ks = tid / 108;
        int mat = item / 54, cg = item % 54;
        int k0 = ks * 216, nk = ks == 2 ? 208 : 216;
#pragma unroll
        for (int i = 0; i < 64; i++) acc[i] = 0.f;
        gemv8(acc, (mat ? P.wu : P.wg) + (size_t)k0 * FF + a * 432 + cg * 8, FF, xs + k0 * 8, nk);
#pragma unroll
        for (int i = 0; i < 16; i++)
            *reinterpret_cast<float4*>(red + (ks * 864 + item * 8) * 8 + i * 4) = make_float4(acc[4 * i], acc[4 * i + 1], acc[4 * i + 2], acc[4 * i + 3]);
    }
    __syncthreads();
    for (int i = tid; i < 432 * 8; i += 384) {
        float gv = bf_round(red[i] + red[864 * 8 + i] + red[2 * 864 * 8 + i]);
        float uv = bf_round(red[432 * 8 + i] + red[(864 + 432) * 8 + i] + red[(2 * 864 + 432) * 8 + i]);
        float sg = bf_round(gv / (1.0f + __expf(-gv)));
        hs[i] = bf_round(sg * uv);
    }
    __syncthreads();
    if (tid < 320) {
        int cg = tid % 80, ks = tid / 80;
#pragma unroll
        for (int i = 0; i < 64; i++) acc[i] = 0.f;
        gemv8(acc, P.wd + (size_t)(a * 432 + ks * 108) * DM + cg * 8, DM, hs + ks * 108 * 8, 108);
#pragma unroll
        for (int i = 0; i < 16; i++)
            *reinterpret_cast<float4*>(red + (ks * 640 + cg * 8) * 8 + i * 4) = make_float4(acc[4 * i], acc[4 * i + 1], acc[4 * i + 2], acc[4 * i + 3]);
    }
    __syncthreads();
    for (int i = tid; i < DM * 8; i += 384)
        g_moe_part[a * DM * 8 + i] = red[i] + red[DM * 8 + i] + red[2 * DM * 8 + i] + red[3 * DM * 8 + i];
    __syncthreads();
    if (tid == 0) {
        __threadfence();
        unsigned old = atomicAdd(flag_ptr(FL_MOE_CNT), 1u);
        s_last = (old == ep * 4u + 3u);
        __threadfence();
    }
    __syncthreads();
    if (s_last) {
        for (int i = tid; i < DM * 8; i += 384) {
            int col = i >> 3, tk = i & 7;
            float y = bf_round(__ldcg(g_moe_part + i) + __ldcg(g_moe_part + DM * 8 + i) + __ldcg(g_moe_part + 2 * DM * 8 + i) + __ldcg(g_moe_part + 3 * DM * 8 + i));
            float sg = bf_round(1.0f / (1.0f + __expf(-s_r[tk])));
            float upd = bf_round(y * sg);
            g_brow[tk * DM + col] = __float2bfloat16_rn(xs[i] + upd);
        }
        if (tid < TOPC) g_sel[tid] = s_sel[tid];
        __syncthreads();
        if (tid == 0) {
            flag_signal(flag_ptr(FL_MOE_DONE));
            *reinterpret_cast<volatile unsigned*>(&g_epoch) = ep + 1;
        }
    }
}

__global__ void __cluster_dims__(2, 1, 1) __launch_bounds__(384, 1)
fused_kernel(const __grid_constant__ CUtensorMap tmC, const __grid_constant__ CUtensorMap tmWk, const __grid_constant__ CUtensorMap tmWv,
             const __grid_constant__ CUtensorMap tmWq, const __grid_constant__ CUtensorMap tmWo, const Params P) {
    extern __shared__ unsigned char smem_raw[];
    const uint32_t ring = (smem_u32(smem_raw) + 1023u) & ~1023u;
    const uint32_t misc = ring + RING_BYTES;
    const int tid = threadIdx.x;
    const int mc = blockIdx.x >> 1, rank = blockIdx.x & 1;
    if (mc >= 64) { aux_cta(P, smem_raw + (ring - smem_u32(smem_raw)), blockIdx.x - 128); return; }
    PROF_DECL
    PROF_GT(0); PROF_EV(1);

    if (tid == 0) {
        for (int i = 0; i < NSLOT; i++) { mbar_init(misc + BAR_FULL + 8 * i, 1); mbar_init(misc + BAR_EMPTY + 8 * i, 4); }
        for (int i = 0; i < NST3; i++) { mbar_init(misc + BAR_FULL3 + 8 * i, 1); mbar_init(misc + BAR_EMPTY3 + 8 * i, 4); }
        for (int i = 0; i < 18; i++) mbar_init(misc + BAR_EV + 8 * i, 4);
        mbar_init(misc + BAR_EPOCH, 1);
        asm volatile("fence.mbarrier_init.release.cluster;" ::: "memory");
    }
    __syncthreads();
    asm volatile("barrier.cluster.arrive.relaxed.aligned;\nbarrier.cluster.wait.aligned;" ::: "memory");

    const int h = mc >> 1, a = mc & 1;
    const int rot = (mc >> 2) & 3;
    const int hq = (mc >> 2) * 2 + rank;
    const int kq = mc & 3;
    const int u3 = mc >> 3, s3 = (mc >> 1) & 3, kap = mc & 1;
    const int wg = __shfl_sync(0xffffffffu, tid >> 7, 0);

    if (wg == 0) {
        asm volatile("setmaxnreg.dec.sync.aligned.u32 40;");
        const int warp = tid >> 5, lane = tid & 31;
        if (warp == 0) {
            if (lane == 0) {
                Cur c; c.slot = 0; c.ph = 0;
                uint32_t dst, fb;
                auto acquire = [&]() {
                    mbar_wait(misc + BAR_EMPTY + 8 * c.slot, c.ph ^ 1);
                    fb = misc + BAR_FULL + 8 * c.slot; dst = ring + c.slot * SLOT_BYTES;
                    mbar_expect_tx(fb, SLOT_BYTES);
                    c.adv();
                };
                auto load_w = [&](const CUtensorMap* tm, int col, int row) {
                    acquire();
                    tma2d(dst, tm, col, row, fb); tma2d(dst + 16384, tm, col, row + 128, fb);
                };
                const CUtensorMap* tw = rank ? &tmWv : &tmWk;
                load_w(tw, h * 128, 0); load_w(tw, h * 128, 256);
                for (int t = 0; t < 8; t++) {
                    for (int ch = 0; ch < 4; ch++) {
                        acquire();
                        tma2d_mc(dst + rank * 16384, &tmC, ch * 128 + rank * 64, (a * 8 + t) * 128, fb);
                    }
                    if (t == 0) { load_w(tw, h * 128 + 64, 0); load_w(tw, h * 128 + 64, 256); }
                }
                mbar_wait(misc + BAR_EPOCH, 0);
                unsigned ep1;
                asm volatile("ld.shared.u32 %0, [%1];" : "=r"(ep1) : "r"(misc + MISC_EPOCH));
                ep1 += 1;
                load_w(&tmWq, hq * 128, 0); load_w(&tmWq, hq * 128, 256); load_w(&tmWq, hq * 128 + 64, 0);
                flag_wait(flag_ptr(FL_LN), ep1 * 384u);
                fence_async_global();
                for (int t = 0; t < 4; t++) {
                    int tile = blk_of(kq >> 1, (t + rot) & 3) * 2 + (kq & 1);
                    for (int ch = 0; ch < 5; ch++) {
                        if (t == 0 && ch == 4) load_w(&tmWq, hq * 128 + 64, 256);
                        acquire();
                        bulk_load_mc(dst + rank * 16384, g_xn + (tile * 10 + 2 * ch + rank) * 16384, 16384, fb);
                    }
                    acquire();
                    tma2d(dst, &tmWq, hq * 128, 512, fb); tma2d(dst + 16384, &tmWq, hq * 128 + 64, 512, fb);
                }
                flag_wait(flag_ptr(FL_KV + h), ep1 * 8u);
                const unsigned char* Kh = g_K + (size_t)h * 32 * 16384 + rank * 16384;
                const unsigned char* Vh = g_V + (size_t)h * 32 * 16384 + rank * 16384;
                for (int r = 0; r < 4; r++) {
                    int p = blk_of(a, (r + rot) & 3), n = 2 * p + 1;
                    flag_wait(flag_ptr(FL_Q + h * 8 + p), ep1 * 4u);
                    fence_async_global();
                    acquire();
                    int gh = 3 - rank, gl = rank;
                    bulk_load(dst, g_Q + (size_t)(h * 32 + 4 * p + ((r & 1) ? gl : gh)) * 16384, 16384, fb);
                    bulk_load(dst + 16384, g_Q + (size_t)(h * 32 + 4 * p + ((r & 1) ? gh : gl)) * 16384, 16384, fb);
                    acquire(); bulk_load_mc(dst + rank * 16384, Kh + n * 32768, 16384, fb);
                    if (r > 0) { acquire(); bulk_load_mc(dst + rank * 16384, Vh, 16384, fb); }
                    for (int j = n - 1; j >= 0; j--) {
                        acquire(); bulk_load_mc(dst + rank * 16384, Kh + j * 32768, 16384, fb);
                        acquire(); bulk_load_mc(dst + rank * 16384, Vh + (j + 1) * 32768, 16384, fb);
                    }
                }
                acquire(); bulk_load_mc(dst + rank * 16384, Vh, 16384, fb);
                mbar_wait(misc + BAR_EMPTY + 8 * c.slot, c.ph ^ 1); c.adv();
                int st = 0; uint32_t ph3 = 0;
                const int pos0 = pos_of(u3);
                for (int i = 0; i < 32; i++) {
                    int hi = i >> 1, rr = (pos0 - (hi >> 2)) & 3;
                    int head = 16 * kap + 8 * ((hi >> 1) & 1) + 2 * rr + (hi & 1);
                    if ((i & 1) == 0) { flag_wait(flag_ptr(FL_CTX + head * 8 + u3), ep1 * 4u); fence_async_global(); }
                    if (i < NST3) { mbar_wait(misc + BAR_EMPTY + 8 * c.slot, c.ph ^ 1); c.adv(); }
                    else mbar_wait(misc + BAR_EMPTY3 + 8 * st, ph3 ^ 1);
                    fb = misc + BAR_FULL3 + 8 * st; dst = ring + st * ST3_BYTES;
                    mbar_expect_tx(fb, ST3_BYTES);
                    const unsigned char* src = g_Q + (size_t)(head * 32 + 4 * u3 + 2 * rank) * 16384 + (i & 1) * 8192;
                    bulk_load(dst, src, 8192, fb);
                    bulk_load(dst + 8192, src + 16384, 8192, fb);
                    tma3d_mc(dst + 16384 + rank * 10240, &tmWo, 0, head * 128 + (i & 1) * 64 + rank * 32, 5 * s3, fb);
                    if (++st == NST3) { st = 0; ph3 ^= 1; }
                }
            }
        } else {
            unsigned ep = 0;
            if (warp == 1 && lane == 0) {
                ep = *reinterpret_cast<volatile unsigned*>(&g_epoch);
                asm volatile("st.shared.u32 [%0], %1;" ::"r"(misc + MISC_EPOCH), "r"(ep) : "memory");
                mbar_arrive(misc + BAR_EPOCH);
            }
            if (warp == 3 && lane == 0) {
                l2_prefetch(reinterpret_cast<const unsigned char*>(P.wq) + (size_t)blockIdx.x * 40960, 40960);
            }
#pragma unroll 1
            for (int rr = warp - 1; rr < 16; rr += 3) {
                int row = blockIdx.x * 16 + rr;
                uint2 v[5];
#pragma unroll
                for (int i = 0; i < 5; i++) v[i] = __ldg(reinterpret_cast<const uint2*>(P.x + (size_t)row * DM + 128 * i + 4 * lane));
                float s = 0.f;
#pragma unroll
                for (int i = 0; i < 5; i++) s += (bf_lo(v[i].x) + bf_hi(v[i].x)) + (bf_lo(v[i].y) + bf_hi(v[i].y));
#pragma unroll
                for (int o = 16; o > 0; o >>= 1) s += __shfl_xor_sync(0xffffffffu, s, o);
                float mean = s * (1.0f / DM);
                float q = 0.f;
#pragma unroll
                for (int i = 0; i < 5; i++) {
                    float d0 = bf_lo(v[i].x) - mean, d1 = bf_hi(v[i].x) - mean, d2 = bf_lo(v[i].y) - mean, d3 = bf_hi(v[i].y) - mean;
                    q = fmaf(d0, d0, q); q = fmaf(d1, d1, q); q = fmaf(d2, d2, q); q = fmaf(d3, d3, q);
                }
#pragma unroll
                for (int o = 16; o > 0; o >>= 1) q += __shfl_xor_sync(0xffffffffu, q, o);
                float mb = bf_round(mean);
                float sd = bf_round(sqrtf(bf_round(bf_round(q * (1.0f / DM)) + 1e-5f)));
                float dot = 0.f;
                unsigned char* xp = g_xn + ((row >> 7) * 10 + (lane >> 4)) * 16384 + (row & 127) * 128 + ((((lane & 15) >> 1) ^ (row & 7)) << 4) + (lane & 1) * 8;
#pragma unroll
                for (int i = 0; i < 5; i++) {
                    uint32_t d01 = pack_bf16(bf_lo(v[i].x) - mb, bf_hi(v[i].x) - mb), d23 = pack_bf16(bf_lo(v[i].y) - mb, bf_hi(v[i].y) - mb);
                    uint2 o;
                    o.x = pack_bf16(__fdiv_rn(bf_lo(d01), sd), __fdiv_rn(bf_hi(d01), sd));
                    o.y = pack_bf16(__fdiv_rn(bf_lo(d23), sd), __fdiv_rn(bf_hi(d23), sd));
                    *reinterpret_cast<uint2*>(xp + i * 32768) = o;
                    uint2 wv = __ldg(reinterpret_cast<const uint2*>(P.wr + 128 * i + 4 * lane));
                    dot = fmaf(bf_lo(o.x), bf_lo(wv.x), dot); dot = fmaf(bf_hi(o.x), bf_hi(wv.x), dot);
                    dot = fmaf(bf_lo(o.y), bf_lo(wv.y), dot); dot = fmaf(bf_hi(o.y), bf_hi(wv.y), dot);
                }
#pragma unroll
                for (int o = 16; o > 0; o >>= 1) dot += __shfl_xor_sync(0xffffffffu, dot, o);
                if (lane == 0) g_router[row] = bf_round(dot);
            }
            __syncwarp();
            if (lane == 0) {
                mbar_wait(misc + BAR_EPOCH, 0);
                flag_signal(flag_ptr(FL_LN));
                if (warp == 3) {
                    l2_prefetch(reinterpret_cast<const unsigned char*>(P.wo) + (size_t)blockIdx.x * 40960, 40960);
                } else {
                    const int w = warp - 1;
                    const uint32_t eb = misc + BAR_EV + w * 72;
                    mbar_wait(eb, 0);
                    flag_signal(flag_ptr(FL_KV + h));
                    for (int t = 0; t < 4; t++) {
                        mbar_wait(eb + 8 + 8 * t, 0);
                        flag_signal(flag_ptr(FL_Q + hq * 8 + blk_of(kq >> 1, (t + rot) & 3)));
                    }
                    for (int r = 0; r < 4; r++) {
                        mbar_wait(eb + 40 + 8 * r, 0);
                        flag_signal(flag_ptr(FL_CTX + h * 8 + blk_of(a, (r + rot) & 3)));
                    }
                }
            }
        }
    } else {
        asm volatile("setmaxnreg.inc.sync.aligned.u32 232;");
        Ctx c;
        c.ring = ring; c.misc = misc; c.w = wg - 1; c.t128 = tid & 127; c.warp = (tid >> 5) & 3; c.lane = tid & 31;
        c.rel = mapa(misc, tid & 1);
        const int w = c.w;
        const int my_bar = 1 + w, other_bar = 2 - w, wg_bar = 3 + w;
        if (w == 1) bar_arrive(1, 256);
        Cur cur;
        {
            uint32_t wf[128];
            float acc[64];
#pragma unroll
            for (int i = 0; i < 64; i++) acc[i] = 0.f;
            auto load_weights = [&](int e0, int e1) {
                Cur c0 = cur_at(e0), c1 = cur_at(e1);
                mbar_wait(misc + BAR_FULL + 8 * c0.slot, c0.ph);
                load_afrag<16, 0>(wf, ring + c0.slot * SLOT_BYTES, c);
                bar_sync(wg_bar, 128);
                release(c, BAR_EMPTY + 8 * c0.slot, 2);
                mbar_wait(misc + BAR_FULL + 8 * c1.slot, c1.ph);
                load_afrag<16, 64>(wf, ring + c1.slot * SLOT_BYTES, c);
                bar_sync(wg_bar, 128);
                release(c, BAR_EMPTY + 8 * c1.slot, 2);
            };
            auto chunks4 = [&](uint32_t& last_slot) {
#pragma unroll
                for (int ch = 0; ch < 4; ch++) {
                    mbar_wait(misc + BAR_FULL + 8 * cur.slot, cur.ph);
                    uint64_t d = mkdesc(ring + cur.slot * SLOT_BYTES, 16, 1024, 1);
                    wg_fence();
#pragma unroll
                    for (int k = 0; k < 8; k++)
                        wgmma_rs_n128_ta0_tb0(acc, wf[32 * ch + 4 * k], wf[32 * ch + 4 * k + 1], wf[32 * ch + 4 * k + 2], wf[32 * ch + 4 * k + 3],
                                              d + (k >> 2) * 1024 + (k & 3) * 2, (ch | k) != 0);
                    wg_commit();
                    if (ch > 0 && ch < 3) { wg_wait<1>(); release(c, BAR_EMPTY + 8 * last_slot, 1); }
                    if (ch < 3) { last_slot = cur.slot; cur.adv(); }
                }
            };
            load_weights(w ? 6 : 0, w ? 7 : 1);
            PROF_EV(2);
            cur = cur_at(2);
            unsigned char* kvdst = (rank ? g_V : g_K) + (size_t)(h * 32 + a * 16) * 16384;
#pragma unroll 1
            for (int t = 0; t < 8; t++) {
                uint32_t last;
                bar_sync(my_bar, 256);
                PROF_EV(10);
                chunks4(last);
                bar_arrive(other_bar, 256);
                wg_wait<1>(); release(c, BAR_EMPTY + 8 * last, 1);
                wg_wait<0>(); release(c, BAR_EMPTY + 8 * cur.slot, 1);
                PROF_EV(11);
                cur.adv();
                if (t == 0) { cur.adv(); cur.adv(); }
                fence_regs(acc);
                store_proj(acc, kvdst + t * 32768, c);
            }
            signal_event(c, 0);
            load_weights(w ? 38 : 36, w ? 43 : 37);
            cur = cur_at(39);
#pragma unroll 1
            for (int t = 0; t < 4; t++) {
                uint32_t last;
                bar_sync(my_bar, 256);
                PROF_EV(20);
                chunks4(last);
                wg_wait<1>(); release(c, BAR_EMPTY + 8 * last, 1);
                last = cur.slot; cur.adv();
                if (t == 0) cur.adv();
                Cur cx = cur; cur.adv();
                mbar_wait(misc + BAR_FULL + 8 * cx.slot, cx.ph);
                mbar_wait(misc + BAR_FULL + 8 * cur.slot, cur.ph);
                uint64_t db = mkdesc(ring + cx.slot * SLOT_BYTES, 16, 1024, 1);
                uint64_t da = mkdesc(ring + cur.slot * SLOT_BYTES + w * 16384, 16384, 1024, 1);
                wg_fence();
#pragma unroll
                for (int k = 0; k < 8; k++) wgmma_ss_n128_ta1_tb0(acc, da + 128 * k, db + (k >> 2) * 1024 + (k & 3) * 2, 1);
                wg_commit();
                bar_arrive(other_bar, 256);
                wg_wait<1>(); release(c, BAR_EMPTY + 8 * last, 1);
                wg_wait<0>(); release(c, BAR_EMPTY + 8 * cx.slot, 1); release(c, BAR_EMPTY + 8 * cur.slot, 1);
                PROF_EV(21);
                cur.adv();
                fence_regs(acc);
                int tile = blk_of(kq >> 1, (t + rot) & 3) * 2 + (kq & 1);
                store_proj(acc, g_Q + (size_t)(hq * 32 + tile * 2) * 16384, c);
                signal_event(c, 1 + t);
            }
        }
        {
            float s[64], o[64];
            uint32_t q[32], p[32];
            float m[2], l[2], alpha[2];
#pragma unroll
            for (int i = 0; i < 64; i++) { s[i] = 0.f; o[i] = 0.f; }
#pragma unroll
            for (int i = 0; i < 32; i++) p[i] = 0u;
            m[0] = m[1] = l[0] = l[1] = 0.f;
            int pv_acc = 0; bool pv_half = true; uint32_t pv_cnt = 1;
            unsigned char* ctx_dst = nullptr;
#pragma unroll 1
            for (int r = 0; r < 4; r++) {
                const int pb = blk_of(a, (r + rot) & 3);
                const bool heavy = ((r & 1) == w);
                const int grp = heavy ? 3 - rank : rank;
                const bool half = (grp & 1) == 0;
                mbar_wait(misc + BAR_FULL + 8 * cur.slot, cur.ph);
                load_afrag<8, 0>(q, ring + cur.slot * SLOT_BYTES + w * 16384, c);
                bar_sync(wg_bar, 128);
                release(c, BAR_EMPTY + 8 * cur.slot, 1);
                cur.adv();
                Cur ck = cur, cv;
                cur.adv();
                cv = cur;
                if (r > 0) cur.adv();
                if (!heavy) { ck = cur; cur.adv(); cur.adv(); }
                mbar_wait(misc + BAR_FULL + 8 * ck.slot, ck.ph);
                if (r > 0) mbar_wait(misc + BAR_FULL + 8 * cv.slot, cv.ph);
                float lprev[2] = {l[0], l[1]};
                bar_sync(my_bar, 256);
                PROF_EV(30);
                if (half) {
                    issue_qk_half(s, q, ring + ck.slot * SLOT_BYTES);
                    issue_pv(o, p, ring + cv.slot * SLOT_BYTES, pv_acc, pv_half);
                    bar_arrive(other_bar, 256);
                    wg_wait<1>();
                    release(c, BAR_EMPTY + 8 * ck.slot, heavy ? 2 : 1);
                    fence_regs(s);
                    mask_diag<0>(s, c);
                    softmax_step<8, true>(s, m, l, alpha);
                } else {
                    issue_qk(s, q, ring + ck.slot * SLOT_BYTES);
                    issue_pv(o, p, ring + cv.slot * SLOT_BYTES, pv_acc, pv_half);
                    bar_arrive(other_bar, 256);
                    wg_wait<1>();
                    release(c, BAR_EMPTY + 8 * ck.slot, heavy ? 2 : 1);
                    fence_regs(s);
                    mask_diag<8>(s, c);
                    softmax_step<16, true>(s, m, l, alpha);
                }
                wg_wait<0>();
                fence_regs(o);
                fence_regs(s);
                if (r > 0) {
                    release(c, BAR_EMPTY + 8 * cv.slot, pv_cnt);
                    store_ctx(o, lprev, ctx_dst, c);
                    signal_event(c, 4 + r);
                }
#pragma unroll
                for (int i = 0; i < 32; i++) p[i] = pack_bf16(s[2 * i], s[2 * i + 1]);
                ctx_dst = g_Q + (size_t)(h * 32 + 4 * pb + grp) * 16384;
                pv_acc = 0; pv_half = half; pv_cnt = heavy ? 2 : 1;
                const int nreg = 2 * pb + (heavy ? 1 : 0);
#pragma unroll 1
                for (int j = 0; j < nreg; j++) {
                    ck = cur; cur.adv(); cv = cur; cur.adv();
                    mbar_wait(misc + BAR_FULL + 8 * ck.slot, ck.ph);
                    mbar_wait(misc + BAR_FULL + 8 * cv.slot, cv.ph);
                    bar_sync(my_bar, 256);
                    PROF_EV(31);
                    issue_qk(s, q, ring + ck.slot * SLOT_BYTES);
                    issue_pv(o, p, ring + cv.slot * SLOT_BYTES, pv_acc, pv_half);
                    bar_arrive(other_bar, 256);
                    wg_wait<1>();
                    release(c, BAR_EMPTY + 8 * ck.slot, 1);
                    fence_regs(s);
                    softmax_step<16, false>(s, m, l, alpha);
                    wg_wait<0>();
                    release(c, BAR_EMPTY + 8 * cv.slot, pv_cnt);
                    fence_regs(o);
                    fence_regs(s);
#pragma unroll
                    for (int i = 0; i < 32; i++) p[i] = pack_bf16(s[2 * i], s[2 * i + 1]);
#pragma unroll
                    for (int i = 0; i < 64; i++) o[i] *= alpha[(i >> 1) & 1];
                    pv_acc = 1; pv_half = false; pv_cnt = 1;
                }
            }
            mbar_wait(misc + BAR_FULL + 8 * cur.slot, cur.ph);
            bar_sync(my_bar, 256);
            PROF_EV(32);
            issue_pv(o, p, ring + cur.slot * SLOT_BYTES, pv_acc, pv_half);
            if (w == 0) bar_arrive(other_bar, 256);
            wg_wait<0>();
            release(c, BAR_EMPTY + 8 * cur.slot, pv_cnt);
            fence_regs(o);
            store_ctx(o, l, ctx_dst, c);
            signal_event(c, 8);
        }
        {
            float acc[80];
#pragma unroll
            for (int i = 0; i < 80; i++) acc[i] = 0.f;
            int st = 0, prev = 0; uint32_t ph3 = 0;
            PROF_EV(40);
#pragma unroll 1
            for (int i = 0; i < 32; i++) {
                mbar_wait(misc + BAR_FULL3 + 8 * st, ph3);
                uint32_t base = ring + st * ST3_BYTES;
                uint64_t da = mkdesc(base + w * 8192, 16, 1024, 1);
                uint64_t db = mkdesc(base + 16384, 2048, 512, 2);
                wg_fence();
#pragma unroll
                for (int k = 0; k < 4; k++) wgmma_ss_n160_ta0_tb1(acc, da + 2 * k, db + (k >> 1) * 640 + (k & 1) * 64, 1);
                wg_commit();
                if (i > 0) { wg_wait<1>(); if (i <= 32 - NST3) release(c, BAR_EMPTY3 + 8 * prev, 1); }
                prev = st;
                if (++st == NST3) { st = 0; ph3 ^= 1; }
            }
            unsigned ep1;
            mbar_wait(misc + BAR_EPOCH, 0);
            asm volatile("ld.shared.u32 %0, [%1];" : "=r"(ep1) : "r"(misc + MISC_EPOCH));
            ep1 += 1;
            flag_wait(flag_ptr(FL_MOE_DONE), ep1);
            const int g = c.lane >> 2, t = c.lane & 3;
            const int row = (2 * u3 + rank) * 128 + 64 * w + 16 * c.warp + 8 * kap + g;
            const int col = 160 * s3 + 8 * t;
            int sel = -1;
#pragma unroll
            for (int i = 0; i < TOPC; i++) if (__ldcg(g_sel + i) == row) sel = i;
            uint4 xv[5], bv[5];
#pragma unroll
            for (int i = 0; i < 5; i++) {
                xv[i] = __ldg(reinterpret_cast<const uint4*>(P.x + (size_t)row * DM + col + 32 * i));
                const void* bp = sel >= 0 ? (const void*)(g_brow + sel * DM + col + 32 * i) : (const void*)xn_addr(row, col + 32 * i);
                bv[i] = __ldcg(reinterpret_cast<const uint4*>(bp));
            }
            wg_wait<0>();
            fence_regs(acc);
            PROF_EV(41);
            const int t256 = tid - 128;
            float4* sendp = g_part + (size_t)blockIdx.x * 2560 + t256;
            float keep[40];
#pragma unroll
            for (int j = 0; j < 10; j++) {
                float4 v;
                v.x = kap ? acc[8 * j + 0] : acc[8 * j + 2]; v.y = kap ? acc[8 * j + 1] : acc[8 * j + 3];
                v.z = kap ? acc[8 * j + 4] : acc[8 * j + 6]; v.w = kap ? acc[8 * j + 5] : acc[8 * j + 7];
                __stcg(sendp + j * 256, v);
                keep[4 * j + 0] = kap ? acc[8 * j + 2] : acc[8 * j + 0]; keep[4 * j + 1] = kap ? acc[8 * j + 3] : acc[8 * j + 1];
                keep[4 * j + 2] = kap ? acc[8 * j + 6] : acc[8 * j + 4]; keep[4 * j + 3] = kap ? acc[8 * j + 7] : acc[8 * j + 5];
            }
            __syncwarp();
            if (c.lane == 0) flag_signal(flag_ptr(FL_EX + blockIdx.x * 8 + (t256 >> 5)));
            flag_wait(flag_ptr(FL_EX + (blockIdx.x ^ 2) * 8 + (t256 >> 5)), ep1);
            const float4* recvp = g_part + (size_t)(blockIdx.x ^ 2) * 2560 + t256;
            uint32_t pk[20];
#pragma unroll
            for (int j = 0; j < 10; j++) {
                float4 v = __ldcg(recvp + j * 256);
                pk[2 * j] = pack_bf16(keep[4 * j] + v.x, keep[4 * j + 1] + v.y);
                pk[2 * j + 1] = pack_bf16(keep[4 * j + 2] + v.z, keep[4 * j + 3] + v.w);
            }
#pragma unroll
            for (int i = 0; i < 5; i++) {
                uint32_t a0 = pk[4 * i], a1 = pk[4 * i + 1], a2 = pk[4 * i + 2], a3 = pk[4 * i + 3];
                uint32_t x0 = (t & 1) ? a0 : a1, x1 = (t & 1) ? a2 : a3;
                x0 = __shfl_xor_sync(0xffffffffu, x0, 1); x1 = __shfl_xor_sync(0xffffffffu, x1, 1);
                if (t & 1) { a0 = x0; a2 = x1; } else { a1 = x0; a3 = x1; }
                x0 = (t & 2) ? a0 : a2; x1 = (t & 2) ? a1 : a3;
                x0 = __shfl_xor_sync(0xffffffffu, x0, 2); x1 = __shfl_xor_sync(0xffffffffu, x1, 2);
                if (t & 2) { a0 = x0; a1 = x1; } else { a2 = x0; a3 = x1; }
                uint32_t av[4] = {a0, a1, a2, a3};
                uint32_t xx[4] = {xv[i].x, xv[i].y, xv[i].z, xv[i].w}, bb[4] = {bv[i].x, bv[i].y, bv[i].z, bv[i].w};
                uint32_t ov[4];
#pragma unroll
                for (int e = 0; e < 4; e++) {
                    uint32_t t1 = pack_bf16(bf_lo(xx[e]) + bf_lo(av[e]), bf_hi(xx[e]) + bf_hi(av[e]));
                    ov[e] = pack_bf16(bf_lo(t1) + bf_lo(bb[e]), bf_hi(t1) + bf_hi(bb[e]));
                }
                stg128(P.out + (size_t)row * DM + col + 32 * i, ov[0], ov[1], ov[2], ov[3]);
            }
            PROF_EV(42); PROF_GT(43);
        }
    }
}

typedef CUresult (*EncodeFn)(CUtensorMap*, CUtensorMapDataType, cuuint32_t, void*, const cuuint64_t*, const cuuint64_t*, const cuuint32_t*,
                             const cuuint32_t*, CUtensorMapInterleave, CUtensorMapSwizzle, CUtensorMapL2promotion, CUtensorMapFloatOOBfill);

void make_map2d(EncodeFn enc, CUtensorMap* tm, const void* p, uint64_t cols, uint64_t rows) {
    cuuint64_t gd[2] = {cols, rows}, gs[1] = {cols * 2};
    cuuint32_t box[2] = {64, 128}, es[2] = {1, 1};
    enc(tm, CU_TENSOR_MAP_DATA_TYPE_BFLOAT16, 2, const_cast<void*>(p), gd, gs, box, es, CU_TENSOR_MAP_INTERLEAVE_NONE,
        CU_TENSOR_MAP_SWIZZLE_128B, CU_TENSOR_MAP_L2_PROMOTION_L2_128B, CU_TENSOR_MAP_FLOAT_OOB_FILL_NONE);
}

}

extern "C" void kernel_launch(void* const* d_in, const int* in_sizes, int n_in, void* d_out, int out_size) {
    (void)in_sizes; (void)n_in; (void)out_size;
    static EncodeFn enc = nullptr;
    if (!enc) {
        void* fn = nullptr;
        cudaDriverEntryPointQueryResult qr;
        cudaGetDriverEntryPoint("cuTensorMapEncodeTiled", &fn, cudaEnableDefault, &qr);
        enc = (EncodeFn)fn;
        cudaFuncSetAttribute(fused_kernel, cudaFuncAttributeMaxDynamicSharedMemorySize, SMEM_BYTES);
    }
    CUtensorMap tmC, tmWk, tmWv, tmWq, tmWo;
    make_map2d(enc, &tmC, d_in[1], DC, SEQ);
    make_map2d(enc, &tmWq, d_in[2], 4096, DM);
    make_map2d(enc, &tmWk, d_in[3], 4096, DC);
    make_map2d(enc, &tmWv, d_in[4], 4096, DC);
    {
        cuuint64_t gd[3] = {32, 4096, 20}, gs[2] = {DM * 2, 64};
        cuuint32_t box[3] = {32, 32, 5}, es[3] = {1, 1, 1};
        enc(&tmWo, CU_TENSOR_MAP_DATA_TYPE_BFLOAT16, 3, d_in[5], gd, gs, box, es, CU_TENSOR_MAP_INTERLEAVE_NONE,
            CU_TENSOR_MAP_SWIZZLE_64B, CU_TENSOR_MAP_L2_PROMOTION_L2_128B, CU_TENSOR_MAP_FLOAT_OOB_FILL_NONE);
    }
    Params P;
    P.x = (const __nv_bfloat16*)d_in[0];
    P.wq = (const __nv_bfloat16*)d_in[2];
    P.wo = (const __nv_bfloat16*)d_in[5];
    P.wr = (const __nv_bfloat16*)d_in[7];
    P.wg = (const __nv_bfloat16*)d_in[8];
    P.wu = (const __nv_bfloat16*)d_in[9];
    P.wd = (const __nv_bfloat16*)d_in[10];
    P.out = (__nv_bfloat16*)d_out;
    fused_kernel<<<132, 384, SMEM_BYTES>>>(tmC, tmWk, tmWv, tmWq, tmWo, P);
}
```

```cpp
#include <cuda_runtime.h>
#include <cuda_bf16.h>
#include <cuda.h>
#include <stdint.h>

namespace {

constexpr int SEQ = 2048, NH = 32, DM = 640, DC = 512, FF = 1728, TOPC = 8;
constexpr int NSLOT = 7, SLOT_BYTES = 32768;
constexpr int NST3 = 6, ST3_BYTES = 36864;
constexpr int RING_BYTES = NSLOT * SLOT_BYTES;
constexpr int SMEM_BYTES = RING_BYTES + 2048;

constexpr int BAR_FULL = 0, BAR_EMPTY = 64, BAR_FULL3 = 128, BAR_EMPTY3 = 192, BAR_EV = 256  , BAR_EPOCH = 416, BAR_LN = 424, BAR_PF = 432, BAR_SEL = 440,
              MISC_EPOCH = 448, MISC_SEL = 464;

constexpr int FL_LN = 0, FL_MOE_CNT = 1, FL_MOE_DONE = 2, FL_KV = 8  , FL_Q = 64  , FL_CTX = 320  , FL_TOTAL = 576;

__device__ __align__(1024) unsigned char g_K[NH * 32 * 16384];
__device__ __align__(1024) unsigned char g_V[NH * 32 * 16384];
__device__ __align__(1024) unsigned char g_Q[NH * 32 * 16384];
__device__ __align__(1024) unsigned char g_xn[16 * 10 * 16384];
__device__ __align__(1024) uint4 g_part[128 * 10 * 256];
__device__ float g_router[SEQ];
__device__ float g_moe_part[4 * TOPC * DM];
__device__ __align__(16) __nv_bfloat16 g_brow[TOPC * DM];
__device__ __align__(16) int g_sel[TOPC];
__device__ unsigned g_flags[FL_TOTAL * 8];
__device__ unsigned g_epoch;

struct Params {
    const __nv_bfloat16 *x, *wr, *wg, *wu, *wd, *wq, *wo;
    __nv_bfloat16* out;
};

__device__ __forceinline__ uint32_t smem_u32(const void* p) { return (uint32_t)__cvta_generic_to_shared(p); }
__device__ __forceinline__ void mbar_init(uint32_t bar, int cnt) { asm volatile("mbarrier.init.shared::cta.b64 [%0], %1;" ::"r"(bar), "r"(cnt)); }
__device__ __forceinline__ void mbar_expect_tx(uint32_t bar, uint32_t bytes) {
    asm volatile("mbarrier.arrive.expect_tx.shared::cta.b64 _, [%0], %1;" ::"r"(bar), "r"(bytes) : "memory");
}
__device__ __forceinline__ void mbar_arrive(uint32_t bar) { asm volatile("mbarrier.arrive.shared::cta.b64 _, [%0];" ::"r"(bar) : "memory"); }
__device__ __forceinline__ void mbar_arrive_cluster(uint32_t cluster_addr, uint32_t cnt) {
    asm volatile("mbarrier.arrive.shared::cluster.b64 _, [%0], %1;" ::"r"(cluster_addr), "r"(cnt) : "memory");
}
__device__ __forceinline__ uint32_t mapa(uint32_t addr, uint32_t cta) {
    uint32_t r; asm("mapa.shared::cluster.u32 %0, %1, %2;" : "=r"(r) : "r"(addr), "r"(cta)); return r;
}
__device__ __forceinline__ void mbar_wait(uint32_t bar, uint32_t parity) {
    asm volatile(
        "{\n.reg .pred p;\n.reg .u32 n;\n"
        "mbarrier.try_wait.parity.shared::cta.b64 p, [%0], %1;\n"
        "@p bra DONE;\n"
        "mov.u32 n, 0;\n"
        "LAB_WAIT:\n"
        "mbarrier.try_wait.parity.shared::cta.b64 p, [%0], %1;\n"
        "@p bra DONE;\n"
        "add.u32 n, n, 1;\n"
        "setp.lt.u32 p, n, 2000000;\n"
        "@p bra LAB_WAIT;\n"
        "trap;\n"
        "DONE:\n}\n" ::"r"(bar), "r"(parity) : "memory");
}
__device__ __forceinline__ void flag_wait(const unsigned* flag, unsigned target) {
    asm volatile(
        "{\n.reg .pred p;\n.reg .u32 n, v;\n.reg .s32 d;\n"
        "mov.u32 n, 0;\n"
        "LAB_WAIT:\n"
        "ld.acquire.gpu.global.u32 v, [%0];\n"
        "sub.s32 d, v, %1;\n"
        "setp.ge.s32 p, d, 0;\n"
        "@p bra DONE;\n"
        "nanosleep.u32 40;\n"
        "add.u32 n, n, 1;\n"
        "setp.lt.u32 p, n, 3000000;\n"
        "@p bra LAB_WAIT;\n"
        "trap;\n"
        "DONE:\n}\n" ::"l"(flag), "r"(target) : "memory");
}
__device__ __forceinline__ void flag_signal(unsigned* flag) {
    asm volatile("red.release.gpu.global.add.u32 [%0], 1;" ::"l"(flag) : "memory");
}
__device__ __forceinline__ void fence_async_global() { asm volatile("fence.proxy.async.global;" ::: "memory"); }
__device__ __forceinline__ unsigned* flag_ptr(int idx) { return g_flags + idx * 8; }

__device__ __forceinline__ void bulk_load(uint32_t dst, const void* src, uint32_t bytes, uint32_t bar) {
    asm volatile("cp.async.bulk.shared::cluster.global.mbarrier::complete_tx::bytes [%0], [%1], %2, [%3];"
                 ::"r"(dst), "l"(src), "r"(bytes), "r"(bar) : "memory");
}
__device__ __forceinline__ void bulk_load_mc(uint32_t dst, const void* src, uint32_t bytes, uint32_t bar) {
    asm volatile("cp.async.bulk.shared::cluster.global.mbarrier::complete_tx::bytes.multicast::cluster [%0], [%1], %2, [%3], %4;"
                 ::"r"(dst), "l"(src), "r"(bytes), "r"(bar), "h"((uint16_t)3) : "memory");
}
__device__ __forceinline__ void tma2d(uint32_t dst, const CUtensorMap* tm, int c0, int c1, uint32_t bar) {
    asm volatile("cp.async.bulk.tensor.2d.shared::cluster.global.mbarrier::complete_tx::bytes [%0], [%1, {%3, %4}], [%2];"
                 ::"r"(dst), "l"(tm), "r"(bar), "r"(c0), "r"(c1) : "memory");
}
__device__ __forceinline__ void tma2d_mc(uint32_t dst, const CUtensorMap* tm, int c0, int c1, uint32_t bar) {
    asm volatile("cp.async.bulk.tensor.2d.shared::cluster.global.mbarrier::complete_tx::bytes.multicast::cluster [%0], [%1, {%3, %4}], [%2], %5;"
                 ::"r"(dst), "l"(tm), "r"(bar), "r"(c0), "r"(c1), "h"((uint16_t)3) : "memory");
}
__device__ __forceinline__ void tma3d_mc(uint32_t dst, const CUtensorMap* tm, int c0, int c1, int c2, uint32_t bar) {
    asm volatile("cp.async.bulk.tensor.3d.shared::cluster.global.mbarrier::complete_tx::bytes.multicast::cluster [%0], [%1, {%3, %4, %5}], [%2], %6;"
                 ::"r"(dst), "l"(tm), "r"(bar), "r"(c0), "r"(c1), "r"(c2), "h"((uint16_t)3) : "memory");
}
__device__ __forceinline__ void l2_prefetch(const void* p, uint32_t bytes) {
    asm volatile("cp.async.bulk.prefetch.L2.global [%0], %1;" ::"l"(p), "r"(bytes) : "memory");
}
__device__ __forceinline__ void wg_fence() { asm volatile("wgmma.fence.sync.aligned;" ::: "memory"); }
__device__ __forceinline__ void wg_commit() { asm volatile("wgmma.commit_group.sync.aligned;" ::: "memory"); }
template <int N> __device__ __forceinline__ void wg_wait() { asm volatile("wgmma.wait_group.sync.aligned %0;" ::"n"(N) : "memory"); }
__device__ __forceinline__ void bar_sync(int id, int n) { asm volatile("bar.sync %0, %1;" ::"r"(id), "r"(n) : "memory"); }
__device__ __forceinline__ void bar_arrive(int id, int n) { asm volatile("bar.arrive %0, %1;" ::"r"(id), "r"(n) : "memory"); }
template <int N> __device__ __forceinline__ void fence_regs(float (&a)[N]) {
#pragma unroll
    for (int i = 0; i < N; i++) asm volatile("" : "+f"(a[i])::"memory");
}
__device__ __forceinline__ void ldsm4t(uint32_t& r0, uint32_t& r1, uint32_t& r2, uint32_t& r3, uint32_t addr) {
    asm volatile("ldmatrix.sync.aligned.m8n8.x4.trans.shared.b16 {%0,%1,%2,%3}, [%4];"
                 : "=r"(r0), "=r"(r1), "=r"(r2), "=r"(r3) : "r"(addr) : "memory");
}
__device__ __forceinline__ uint32_t pack_bf16(float lo, float hi) {
    uint32_t r; asm("cvt.rn.bf16x2.f32 %0, %1, %2;" : "=r"(r) : "f"(hi), "f"(lo)); return r;
}
__device__ __forceinline__ float bf_lo(uint32_t v) { return __uint_as_float(v << 16); }
__device__ __forceinline__ float bf_hi(uint32_t v) { return __uint_as_float(v & 0xffff0000u); }
__device__ __forceinline__ float bf_round(float v) { return __bfloat162float(__float2bfloat16_rn(v)); }
__device__ __forceinline__ float ex2(float v) { float r; asm("ex2.approx.ftz.f32 %0, %1;" : "=f"(r) : "f"(v)); return r; }
__device__ __forceinline__ void stg128(void* p, uint32_t a, uint32_t b, uint32_t c, uint32_t d) {
    asm volatile("st.global.v4.b32 [%0], {%1,%2,%3,%4};" ::"l"(p), "r"(a), "r"(b), "r"(c), "r"(d) : "memory");
}
__device__ __forceinline__ uint4 ldg128(const void* p) {
    uint4 v; asm volatile("ld.global.cg.v4.b32 {%0,%1,%2,%3}, [%4];" : "=r"(v.x), "=r"(v.y), "=r"(v.z), "=r"(v.w) : "l"(p) : "memory"); return v;
}
__device__ __forceinline__ uint64_t mkdesc(uint32_t addr, uint32_t lbo, uint32_t sbo, uint32_t swz) {
    uint32_t lo = ((addr & 0x3FFFF) >> 4) | ((lbo >> 4) << 16);
    uint32_t hi = (sbo >> 4) | (swz << 30);
    return ((uint64_t)hi << 32) | lo;
}
__device__ __forceinline__ int perm32(int v) { return (v & ~30) | ((v >> 2) & 6) | ((v << 2) & 24); }

__device__ __forceinline__ void wgmma_rs_n128_ta0_tb0(float (&d)[64], uint32_t a0, uint32_t a1, uint32_t a2, uint32_t a3, uint64_t descB, int scaleD) {
  asm volatile("{\n.reg .pred p;\nsetp.ne.b32 p, %69, 0;\n"
    "wgmma.mma_async.sync.aligned.m64n128k16.f32.bf16.bf16 "
    "{%0, %1, %2, %3, %4, %5, %6, %7, %8, %9, %10, %11, %12, %13, %14, %15, %16, %17, %18, %19, %20, %21, %22, %23, %24, %25, %26, %27, %28, %29, %30, %31, %32, %33, %34, %35, %36, %37, %38, %39, %40, %41, %42, %43, %44, %45, %46, %47, %48, %49, %50, %51, %52, %53, %54, %55, %56, %57, %58, %59, %60, %61, %62, %63}, "
    "{%64, %65, %66, %67}, %68, p, 1, 1, 0;\n}\n"
    : "+f"(d[0]), "+f"(d[1]), "+f"(d[2]), "+f"(d[3]), "+f"(d[4]), "+f"(d[5]), "+f"(d[6]), "+f"(d[7]), "+f"(d[8]), "+f"(d[9]), "+f"(d[10]), "+f"(d[11]), "+f"(d[12]), "+f"(d[13]), "+f"(d[14]), "+f"(d[15]), "+f"(d[16]), "+f"(d[17]), "+f"(d[18]), "+f"(d[19]), "+f"(d[20]), "+f"(d[21]), "+f"(d[22]), "+f"(d[23]), "+f"(d[24]), "+f"(d[25]), "+f"(d[26]), "+f"(d[27]), "+f"(d[28]), "+f"(d[29]), "+f"(d[30]), "+f"(d[31]), "+f"(d[32]), "+f"(d[33]), "+f"(d[34]), "+f"(d[35]), "+f"(d[36]), "+f"(d[37]), "+f"(d[38]), "+f"(d[39]), "+f"(d[40]), "+f"(d[41]), "+f"(d[42]), "+f"(d[43]), "+f"(d[44]), "+f"(d[45]), "+f"(d[46]), "+f"(d[47]), "+f"(d[48]), "+f"(d[49]), "+f"(d[50]), "+f"(d[51]), "+f"(d[52]), "+f"(d[53]), "+f"(d[54]), "+f"(d[55]), "+f"(d[56]), "+f"(d[57]), "+f"(d[58]), "+f"(d[59]), "+f"(d[60]), "+f"(d[61]), "+f"(d[62]), "+f"(d[63])
    : "r"(a0), "r"(a1), "r"(a2), "r"(a3), "l"(descB), "r"(scaleD));
}
__device__ __forceinline__ void wgmma_rs_n128_ta0_tb1(float (&d)[64], uint32_t a0, uint32_t a1, uint32_t a2, uint32_t a3, uint64_t descB, int scaleD) {
  asm volatile("{\n.reg .pred p;\nsetp.ne.b32 p, %69, 0;\n"
    "wgmma.mma_async.sync.aligned.m64n128k16.f32.bf16.bf16 "
    "{%0, %1, %2, %3, %4, %5, %6, %7, %8, %9, %10, %11, %12, %13, %14, %15, %16, %17, %18, %19, %20, %21, %22, %23, %24, %25, %26, %27, %28, %29, %30, %31, %32, %33, %34, %35, %36, %37, %38, %39, %40, %41, %42, %43, %44, %45, %46, %47, %48, %49, %50, %51, %52, %53, %54, %55, %56, %57, %58, %59, %60, %61, %62, %63}, "
    "{%64, %65, %66, %67}, %68, p, 1, 1, 1;\n}\n"
    : "+f"(d[0]), "+f"(d[1]), "+f"(d[2]), "+f"(d[3]), "+f"(d[4]), "+f"(d[5]), "+f"(d[6]), "+f"(d[7]), "+f"(d[8]), "+f"(d[9]), "+f"(d[10]), "+f"(d[11]), "+f"(d[12]), "+f"(d[13]), "+f"(d[14]), "+f"(d[15]), "+f"(d[16]), "+f"(d[17]), "+f"(d[18]), "+f"(d[19]), "+f"(d[20]), "+f"(d[21]), "+f"(d[22]), "+f"(d[23]), "+f"(d[24]), "+f"(d[25]), "+f"(d[26]), "+f"(d[27]), "+f"(d[28]), "+f"(d[29]), "+f"(d[30]), "+f"(d[31]), "+f"(d[32]), "+f"(d[33]), "+f"(d[34]), "+f"(d[35]), "+f"(d[36]), "+f"(d[37]), "+f"(d[38]), "+f"(d[39]), "+f"(d[40]), "+f"(d[41]), "+f"(d[42]), "+f"(d[43]), "+f"(d[44]), "+f"(d[45]), "+f"(d[46]), "+f"(d[47]), "+f"(d[48]), "+f"(d[49]), "+f"(d[50]), "+f"(d[51]), "+f"(d[52]), "+f"(d[53]), "+f"(d[54]), "+f"(d[55]), "+f"(d[56]), "+f"(d[57]), "+f"(d[58]), "+f"(d[59]), "+f"(d[60]), "+f"(d[61]), "+f"(d[62]), "+f"(d[63])
    : "r"(a0), "r"(a1), "r"(a2), "r"(a3), "l"(descB), "r"(scaleD));
}
__device__ __forceinline__ void wgmma_rs_n64_ta0_tb1(float (&d)[32], uint32_t a0, uint32_t a1, uint32_t a2, uint32_t a3, uint64_t descB, int scaleD) {
  asm volatile("{\n.reg .pred p;\nsetp.ne.b32 p, %37, 0;\n"
    "wgmma.mma_async.sync.aligned.m64n64k16.f32.bf16.bf16 "
    "{%0, %1, %2, %3, %4, %5, %6, %7, %8, %9, %10, %11, %12, %13, %14, %15, %16, %17, %18, %19, %20, %21, %22, %23, %24, %25, %26, %27, %28, %29, %30, %31}, "
    "{%32, %33, %34, %35}, %36, p, 1, 1, 1;\n}\n"
    : "+f"(d[0]), "+f"(d[1]), "+f"(d[2]), "+f"(d[3]), "+f"(d[4]), "+f"(d[5]), "+f"(d[6]), "+f"(d[7]), "+f"(d[8]), "+f"(d[9]), "+f"(d[10]), "+f"(d[11]), "+f"(d[12]), "+f"(d[13]), "+f"(d[14]), "+f"(d[15]), "+f"(d[16]), "+f"(d[17]), "+f"(d[18]), "+f"(d[19]), "+f"(d[20]), "+f"(d[21]), "+f"(d[22]), "+f"(d[23]), "+f"(d[24]), "+f"(d[25]), "+f"(d[26]), "+f"(d[27]), "+f"(d[28]), "+f"(d[29]), "+f"(d[30]), "+f"(d[31])
    : "r"(a0), "r"(a1), "r"(a2), "r"(a3), "l"(descB), "r"(scaleD));
}
__device__ __forceinline__ void wgmma_ss_n128_ta1_tb0(float (&d)[64], uint64_t descA, uint64_t descB, int scaleD) {
  asm volatile("{\n.reg .pred p;\nsetp.ne.b32 p, %66, 0;\n"
    "wgmma.mma_async.sync.aligned.m64n128k16.f32.bf16.bf16 "
    "{%0, %1, %2, %3, %4, %5, %6, %7, %8, %9, %10, %11, %12, %13, %14, %15, %16, %17, %18, %19, %20, %21, %22, %23, %24, %25, %26, %27, %28, %29, %30, %31, %32, %33, %34, %35, %36, %37, %38, %39, %40, %41, %42, %43, %44, %45, %46, %47, %48, %49, %50, %51, %52, %53, %54, %55, %56, %57, %58, %59, %60, %61, %62, %63}, "
    "%64, %65, p, 1, 1, 1, 0;\n}\n"
    : "+f"(d[0]), "+f"(d[1]), "+f"(d[2]), "+f"(d[3]), "+f"(d[4]), "+f"(d[5]), "+f"(d[6]), "+f"(d[7]), "+f"(d[8]), "+f"(d[9]), "+f"(d[10]), "+f"(d[11]), "+f"(d[12]), "+f"(d[13]), "+f"(d[14]), "+f"(d[15]), "+f"(d[16]), "+f"(d[17]), "+f"(d[18]), "+f"(d[19]), "+f"(d[20]), "+f"(d[21]), "+f"(d[22]), "+f"(d[23]), "+f"(d[24]), "+f"(d[25]), "+f"(d[26]), "+f"(d[27]), "+f"(d[28]), "+f"(d[29]), "+f"(d[30]), "+f"(d[31]), "+f"(d[32]), "+f"(d[33]), "+f"(d[34]), "+f"(d[35]), "+f"(d[36]), "+f"(d[37]), "+f"(d[38]), "+f"(d[39]), "+f"(d[40]), "+f"(d[41]), "+f"(d[42]), "+f"(d[43]), "+f"(d[44]), "+f"(d[45]), "+f"(d[46]), "+f"(d[47]), "+f"(d[48]), "+f"(d[49]), "+f"(d[50]), "+f"(d[51]), "+f"(d[52]), "+f"(d[53]), "+f"(d[54]), "+f"(d[55]), "+f"(d[56]), "+f"(d[57]), "+f"(d[58]), "+f"(d[59]), "+f"(d[60]), "+f"(d[61]), "+f"(d[62]), "+f"(d[63])
    : "l"(descA), "l"(descB), "r"(scaleD));
}
__device__ __forceinline__ void wgmma_ss_n160_ta0_tb1(float (&d)[80], uint64_t descA, uint64_t descB, int scaleD) {
  asm volatile("{\n.reg .pred p;\nsetp.ne.b32 p, %82, 0;\n"
    "wgmma.mma_async.sync.aligned.m64n160k16.f32.bf16.bf16 "
    "{%0, %1, %2, %3, %4, %5, %6, %7, %8, %9, %10, %11, %12, %13, %14, %15, %16, %17, %18, %19, %20, %21, %22, %23, %24, %25, %26, %27, %28, %29, %30, %31, %32, %33, %34, %35, %36, %37, %38, %39, %40, %41, %42, %43, %44, %45, %46, %47, %48, %49, %50, %51, %52, %53, %54, %55, %56, %57, %58, %59, %60, %61, %62, %63, %64, %65, %66, %67, %68, %69, %70, %71, %72, %73, %74, %75, %76, %77, %78, %79}, "
    "%80, %81, p, 1, 1, 0, 1;\n}\n"
    : "+f"(d[0]), "+f"(d[1]), "+f"(d[2]), "+f"(d[3]), "+f"(d[4]), "+f"(d[5]), "+f"(d[6]), "+f"(d[7]), "+f"(d[8]), "+f"(d[9]), "+f"(d[10]), "+f"(d[11]), "+f"(d[12]), "+f"(d[13]), "+f"(d[14]), "+f"(d[15]), "+f"(d[16]), "+f"(d[17]), "+f"(d[18]), "+f"(d[19]), "+f"(d[20]), "+f"(d[21]), "+f"(d[22]), "+f"(d[23]), "+f"(d[24]), "+f"(d[25]), "+f"(d[26]), "+f"(d[27]), "+f"(d[28]), "+f"(d[29]), "+f"(d[30]), "+f"(d[31]), "+f"(d[32]), "+f"(d[33]), "+f"(d[34]), "+f"(d[35]), "+f"(d[36]), "+f"(d[37]), "+f"(d[38]), "+f"(d[39]), "+f"(d[40]), "+f"(d[41]), "+f"(d[42]), "+f"(d[43]), "+f"(d[44]), "+f"(d[45]), "+f"(d[46]), "+f"(d[47]), "+f"(d[48]), "+f"(d[49]), "+f"(d[50]), "+f"(d[51]), "+f"(d[52]), "+f"(d[53]), "+f"(d[54]), "+f"(d[55]), "+f"(d[56]), "+f"(d[57]), "+f"(d[58]), "+f"(d[59]), "+f"(d[60]), "+f"(d[61]), "+f"(d[62]), "+f"(d[63]), "+f"(d[64]), "+f"(d[65]), "+f"(d[66]), "+f"(d[67]), "+f"(d[68]), "+f"(d[69]), "+f"(d[70]), "+f"(d[71]), "+f"(d[72]), "+f"(d[73]), "+f"(d[74]), "+f"(d[75]), "+f"(d[76]), "+f"(d[77]), "+f"(d[78]), "+f"(d[79])
    : "l"(descA), "l"(descB), "r"(scaleD));
}

#define PROF_DECL
#define PROF_EV(tag)
#define PROF_GT(tag)

struct Cur {
    uint32_t slot, ph;
    __device__ __forceinline__ void adv() { if (++slot == NSLOT) { slot = 0; ph ^= 1; } }
};
__device__ __forceinline__ Cur cur_at(int e) { Cur c; c.slot = e % NSLOT; c.ph = (e / NSLOT) & 1; return c; }

__device__ __forceinline__ int blk_of(int a, int i) { return ((a ? 0x2516u : 0x3407u) >> (4 * i)) & 7; }
__device__ __forceinline__ int pos_of(int u) { return (0x00223311u >> (4 * u)) & 3; }

constexpr float SM_SCALE = 0.08838834764831845f * 1.4426950408889634f;

struct Ctx {
    uint32_t ring, misc;
    uint32_t rel;
    int w, warp, lane;
};
__device__ __forceinline__ void release(const Ctx& c, uint32_t off, uint32_t cnt) {
    if (c.lane < 2) mbar_arrive_cluster(c.rel + off, cnt);
}
__device__ __forceinline__ void signal_event(const Ctx& c, int ev) {
    __syncwarp();
    if (c.lane == 0) mbar_arrive(c.misc + BAR_EV + (c.w * 9 + ev) * 8);
}
template <int NK, int OFF, int N>
__device__ __forceinline__ void load_afrag(uint32_t (&a)[N], uint32_t base, const Ctx& c) {
    int r = c.lane & 7, mat = c.lane >> 3;
    uint32_t addr = base + (8 * (mat >> 1) + r) * 128 + (((2 * c.warp + (mat & 1)) ^ r) << 4);
#pragma unroll
    for (int k = 0; k < NK; k++) ldsm4t(a[OFF + 4 * k], a[OFF + 4 * k + 1], a[OFF + 4 * k + 2], a[OFF + 4 * k + 3], addr + k * 2048);
}
__device__ __forceinline__ void store_proj(const float (&acc)[64], unsigned char* dst  , const Ctx& c) {
    int g = c.lane >> 2, t = c.lane & 3;
#pragma unroll
    for (int i = 0; i < 2; i++) {
        int row = perm32(64 * c.w + 16 * c.warp + 8 * i + g);
        unsigned char* p = dst + row * 128;
#pragma unroll
        for (int q = 0; q < 4; q++) {
            int chunk = (4 * (q & 1) + t) ^ (row & 7);
            stg128(p + (q >> 1) * 16384 + chunk * 16,
                   pack_bf16(acc[16 * q + 2 * i], acc[16 * q + 2 * i + 1]), pack_bf16(acc[16 * q + 4 + 2 * i], acc[16 * q + 4 + 2 * i + 1]),
                   pack_bf16(acc[16 * q + 8 + 2 * i], acc[16 * q + 8 + 2 * i + 1]), pack_bf16(acc[16 * q + 12 + 2 * i], acc[16 * q + 12 + 2 * i + 1]));
        }
    }
}

constexpr float SAFE_EXP = 40.0f, SAFE_SUM = 1099511627776.0f;
template <int NJ>
__device__ __forceinline__ void row_max(const float (&s)[64], float (&mx)[2]) {
#pragma unroll
    for (int i = 0; i < 2; i++) {
        float a = fmaxf(s[2 * i], s[2 * i + 1]), b = fmaxf(s[4 + 2 * i], s[4 + 2 * i + 1]);
#pragma unroll
        for (int j = 2; j < NJ; j += 2) {
            a = fmaxf(a, fmaxf(s[4 * j + 2 * i], s[4 * j + 2 * i + 1]));
            b = fmaxf(b, fmaxf(s[4 * j + 4 + 2 * i], s[4 * j + 4 + 2 * i + 1]));
        }
        a = fmaxf(a, b);
        a = fmaxf(a, __shfl_xor_sync(0xffffffffu, a, 1));
        mx[i] = fmaxf(a, __shfl_xor_sync(0xffffffffu, a, 2));
    }
}
template <int NJ, bool SHIFT>
__device__ __forceinline__ void exp_sum(float (&s)[64], const float (&m)[2], float& l0, float& l1) {
#pragma unroll
    for (int j = 0; j < NJ; j++) {
#pragma unroll
        for (int e = 0; e < 4; e++) s[4 * j + e] = ex2(SHIFT ? s[4 * j + e] - m[e >> 1] : s[4 * j + e]);
        l0 += s[4 * j + 0]; l1 += s[4 * j + 2]; l0 += s[4 * j + 1]; l1 += s[4 * j + 3];
    }
}
template <int NJ>
__device__ __forceinline__ bool softmax_first(float (&s)[64], float (&m)[2], float (&l)[2]) {
    row_max<NJ>(s, m);
    bool gen = __any_sync(0xffffffffu, !(fabsf(m[0]) <= SAFE_EXP && fabsf(m[1]) <= SAFE_EXP));
    if (!gen) m[0] = m[1] = 0.f;
    l[0] = l[1] = 0.f;
    exp_sum<NJ, true>(s, m, l[0], l[1]);
    return gen;
}
__device__ __forceinline__ void recompute_scores(float (&s)[64], const uint32_t (&q)[32], uint32_t kaddr, const Ctx& c) {
    const int r = c.lane & 7, mat = c.lane >> 3;
    const uint32_t a0 = kaddr + (8 * (mat & 1) + r) * 128 + (((mat >> 1) ^ r) << 4);
#pragma unroll
    for (int i = 0; i < 64; i++) s[i] = 0.f;
#pragma unroll
    for (int jp = 0; jp < 8; jp++) {
#pragma unroll
        for (int k = 0; k < 8; k++) {
            asm volatile(
                "{\n.reg .b32 b0, b1, b2, b3;\n"
                "ldmatrix.sync.aligned.m8n8.x4.trans.shared.b16 {b0,b1,b2,b3}, [%12];\n"
                "mma.sync.aligned.m16n8k16.row.col.f32.bf16.bf16.f32 {%0,%1,%2,%3}, {%8,%9,%10,%11}, {b0,b1}, {%0,%1,%2,%3};\n"
                "mma.sync.aligned.m16n8k16.row.col.f32.bf16.bf16.f32 {%4,%5,%6,%7}, {%8,%9,%10,%11}, {b2,b3}, {%4,%5,%6,%7};\n}\n"
                : "+f"(s[8 * jp]), "+f"(s[8 * jp + 1]), "+f"(s[8 * jp + 2]), "+f"(s[8 * jp + 3]),
                  "+f"(s[8 * jp + 4]), "+f"(s[8 * jp + 5]), "+f"(s[8 * jp + 6]), "+f"(s[8 * jp + 7])
                : "r"(q[4 * k]), "r"(q[4 * k + 1]), "r"(q[4 * k + 2]), "r"(q[4 * k + 3]),
                  "r"((a0 ^ ((jp & 3) << 5)) + (jp >> 2) * 16384 + k * 2048) : "memory");
        }
    }
}
template <int J0>
__device__ __forceinline__ void mask_diag(float (&s)[64], const Ctx& c) {
    int g = c.lane >> 2, t = c.lane & 3;
#pragma unroll
    for (int i = 0; i < 2; i++) {
        int lim = perm32(16 * c.warp + 8 * i + g) - 8 * t;
#pragma unroll
        for (int j = 0; j < 8; j++)
#pragma unroll
            for (int e = 0; e < 2; e++)
                if (32 * (j >> 2) + 2 * (j & 3) + e > lim) s[4 * (J0 + j) + 2 * i + e] = -INFINITY;
    }
}
__device__ __forceinline__ void issue_pv(float (&o)[64], const uint32_t (&p)[32], uint32_t vaddr, int acc, bool half) {
    uint64_t d = mkdesc(vaddr, 16, 1024, 1);
    if (half) {
        wg_fence();
#pragma unroll
        for (int k = 0; k < 4; k++) wgmma_rs_n128_ta0_tb0(o, p[4 * k], p[4 * k + 1], p[4 * k + 2], p[4 * k + 3], d + 2 * k, k != 0);
        wg_commit();
    } else {
        wg_fence();
#pragma unroll
        for (int k = 0; k < 8; k++)
            wgmma_rs_n128_ta0_tb0(o, p[4 * k], p[4 * k + 1], p[4 * k + 2], p[4 * k + 3], d + (k >> 2) * 1024 + 2 * (k & 3), k ? 1 : acc);
        wg_commit();
    }
}
__device__ __forceinline__ void issue_qk(float (&s)[64], const uint32_t (&q)[32], uint32_t kaddr) {
    uint64_t d = mkdesc(kaddr, 16384, 1024, 1);
    wg_fence();
#pragma unroll
    for (int k = 0; k < 8; k++) wgmma_rs_n128_ta0_tb1(s, q[4 * k], q[4 * k + 1], q[4 * k + 2], q[4 * k + 3], d + 128 * k, k != 0);
    wg_commit();
}
__device__ __forceinline__ void issue_qk_half(float (&s)[64], const uint32_t (&q)[32], uint32_t kaddr) {
    uint64_t d = mkdesc(kaddr, 16384, 1024, 1);
    float(&s32)[32] = *reinterpret_cast<float(*)[32]>(&s[0]);
    wg_fence();
#pragma unroll
    for (int k = 0; k < 8; k++) wgmma_rs_n64_ta0_tb1(s32, q[4 * k], q[4 * k + 1], q[4 * k + 2], q[4 * k + 3], d + 128 * k, k != 0);
    wg_commit();
}
__device__ __forceinline__ void store_ctx(const float (&o)[64], const float (&l)[2], unsigned char* dst, const Ctx& c) {
    int g = c.lane >> 2, t = c.lane & 3;
#pragma unroll
    for (int i = 0; i < 2; i++) {
        float sum = l[i];
        sum += __shfl_xor_sync(0xffffffffu, sum, 1);
        sum += __shfl_xor_sync(0xffffffffu, sum, 2);
        float inv = 1.0f / sum;
        int row = perm32(16 * c.warp + 8 * i + g);
        unsigned char* p = dst + row * 128;
#pragma unroll
        for (int q = 0; q < 4; q++) {
            int chunk = (4 * (q & 1) + t) ^ (row & 7);
            stg128(p + (q >> 1) * 8192 + chunk * 16,
                   pack_bf16(o[16 * q + 2 * i] * inv, o[16 * q + 2 * i + 1] * inv), pack_bf16(o[16 * q + 4 + 2 * i] * inv, o[16 * q + 4 + 2 * i + 1] * inv),
                   pack_bf16(o[16 * q + 8 + 2 * i] * inv, o[16 * q + 8 + 2 * i + 1] * inv), pack_bf16(o[16 * q + 12 + 2 * i] * inv, o[16 * q + 12 + 2 * i + 1] * inv));
        }
    }
}

__device__ __forceinline__ const unsigned char* xn_addr(int row, int col) {
    return g_xn + ((row >> 7) * 10 + (col >> 6)) * 16384 + (row & 127) * 128 + ((((col & 63) >> 3) ^ (row & 7)) << 4);
}
__device__ __forceinline__ void mma16816(float (&d)[4], uint32_t a0, uint32_t a1, uint32_t a2, uint32_t a3, uint32_t b0, uint32_t b1) {
    asm volatile("mma.sync.aligned.m16n8k16.row.col.f32.bf16.bf16.f32 {%0,%1,%2,%3}, {%4,%5,%6,%7}, {%8,%9}, {%0,%1,%2,%3};"
                 : "+f"(d[0]), "+f"(d[1]), "+f"(d[2]), "+f"(d[3]) : "r"(a0), "r"(a1), "r"(a2), "r"(a3), "r"(b0), "r"(b1));
}
__device__ __forceinline__ uint32_t lds32(uint32_t addr) { uint32_t v; asm volatile("ld.shared.u32 %0, [%1];" : "=r"(v) : "r"(addr)); return v; }

__device__ __forceinline__ void aux_cta(const Params& P, unsigned char* sm, int a) {
    constexpr int STG = 65536, XS = 3 * STG, HS = XS + 8 * 1296, MI = HS + 8 * 880;
    const int tid = threadIdx.x, warp = tid >> 5, lane = tid & 31;
    const uint32_t sb = smem_u32(sm);
    const uint32_t full = sb + MI, empty = sb + MI + 32;
    int* s_sel = reinterpret_cast<int*>(sm + MI + 64);
    float* s_r = reinterpret_cast<float*>(sm + MI + 96);
    volatile unsigned* s_misc = reinterpret_cast<volatile unsigned*>(sm + MI + 128);
    PROF_DECL
    PROF_GT(0);
    if (tid == 0) {
        for (int i = 0; i < 3; i++) { mbar_init(full + 8 * i, 1); mbar_init(empty + 8 * i, 10); }
        asm volatile("fence.mbarrier_init.release.cluster;" ::: "memory");
    }
    __syncthreads();
    if (warp == 11) {
        int st = 0; uint32_t ph = 0;
        for (int s = 0; s < 29; s++) {
            mbar_wait(empty + 8 * st, ph ^ 1);
            if (lane == 0) mbar_expect_tx(full + 8 * st, s < 20 ? 55296 : 61440);
            __syncwarp();
            uint32_t dst = sb + st * STG;
            if (s < 20) {
                size_t off = (size_t)(32 * s + lane) * FF + a * 432;
                bulk_load(dst + lane * 880, P.wg + off, 864, full + 8 * st);
                bulk_load(dst + 28160 + lane * 880, P.wu + off, 864, full + 8 * st);
            } else {
                const __nv_bfloat16* src = P.wd + (size_t)(a * 432 + (s - 20) * 48) * DM;
                bulk_load(dst + lane * 1296, src + lane * DM, 1280, full + 8 * st);
                if (lane < 16) bulk_load(dst + (32 + lane) * 1296, src + (32 + lane) * DM, 1280, full + 8 * st);
            }
            if (++st == 3) { st = 0; ph ^= 1; }
        }
        return;
    }
    if (warp == 10) return;
    if (warp == 0) {
        if (lane == 0) {
            unsigned e = *reinterpret_cast<volatile unsigned*>(&g_epoch);
            s_misc[0] = e;
            flag_wait(flag_ptr(FL_LN), (e + 1) * 128u);
        }
        __syncwarp();
        PROF_GT(50);
        uint32_t key[64];
#pragma unroll
        for (int i = 0; i < 64; i++) {
            int idx = i * 32 + lane;
            uint32_t b = __float_as_uint(__ldcg(g_router + idx)) >> 16;
            b = (b & 0x8000u) ? (~b & 0xffffu) : (b | 0x8000u);
            key[i] = (b << 16) | (uint32_t)(0xffff - idx);
        }
        uint32_t bound = 0xffffffffu;
#pragma unroll 1
        for (int r = 0; r < TOPC; r++) {
            uint32_t best = 0;
#pragma unroll
            for (int i = 0; i < 64; i++) best = max(best, key[i] <= bound ? key[i] : 0u);
            best = __reduce_max_sync(0xffffffffu, best);
            bound = best - 1;
            if (lane == 0) {
                uint32_t b = best >> 16;
                b = (b & 0x8000u) ? (b & 0x7fffu) : (~b & 0xffffu);
                s_sel[r] = 0xffff - (int)(best & 0xffffu);
                s_r[r] = __uint_as_float(b << 16);
            }
        }
    }
    bar_sync(1, 320);
    const unsigned ep = s_misc[0];
    for (int i = tid; i < TOPC * 80; i += 320) {
        int tk = i / 80, ch = i % 80;
        *reinterpret_cast<uint4*>(sm + XS + tk * 1296 + ch * 16) = __ldcg(reinterpret_cast<const uint4*>(xn_addr(s_sel[tk], ch * 8)));
    }
    bar_sync(1, 320);
    PROF_GT(51);
    const int g = lane >> 2, t = lane & 3;
    const int lrow = 8 * (lane >> 4) + (lane & 7), lcol = ((lane >> 3) & 1) * 16;
    int st = 0; uint32_t ph = 0;
    {
        float ga[3][4], ua[3][4];
#pragma unroll
        for (int i = 0; i < 3; i++)
#pragma unroll
            for (int e = 0; e < 4; e++) { ga[i][e] = 0.f; ua[i][e] = 0.f; }
#pragma unroll 1
        for (int s = 0; s < 20; s++) {
            mbar_wait(full + 8 * st, ph);
            if (warp < 9) {
#pragma unroll
                for (int kk = 0; kk < 2; kk++) {
                    uint32_t xb = sb + XS + g * 1296 + (32 * s + 16 * kk + 2 * t) * 2;
                    uint32_t b0 = lds32(xb), b1 = lds32(xb + 16);
                    uint32_t wa = sb + st * STG + (16 * kk + lrow) * 880 + lcol + warp * 96;
#pragma unroll
                    for (int i = 0; i < 3; i++) {
                        uint32_t a0, a1, a2, a3;
                        ldsm4t(a0, a1, a2, a3, wa + i * 32);
                        mma16816(ga[i], a0, a1, a2, a3, b0, b1);
                        ldsm4t(a0, a1, a2, a3, wa + 28160 + i * 32);
                        mma16816(ua[i], a0, a1, a2, a3, b0, b1);
                    }
                }
            }
            __syncwarp();
            if (lane == 0) mbar_arrive(empty + 8 * st);
            if (++st == 3) { st = 0; ph ^= 1; }
        }
        if (warp < 9) {
#pragma unroll
            for (int i = 0; i < 3; i++)
#pragma unroll
                for (int e = 0; e < 4; e++) {
                    float gv = bf_round(ga[i][e]), uv = bf_round(ua[i][e]);
                    float sg = bf_round(gv / (1.0f + __expf(-gv)));
                    int f = warp * 48 + i * 16 + g + 8 * (e >> 1), tk = 2 * t + (e & 1);
                    *reinterpret_cast<__nv_bfloat16*>(sm + HS + tk * 880 + f * 2) = __float2bfloat16_rn(sg * uv);
                }
        }
    }
    bar_sync(1, 320);
    PROF_GT(52);
    {
        float ya[4][4];
#pragma unroll
        for (int i = 0; i < 4; i++)
#pragma unroll
            for (int e = 0; e < 4; e++) ya[i][e] = 0.f;
#pragma unroll 1
        for (int s = 0; s < 9; s++) {
            mbar_wait(full + 8 * st, ph);
#pragma unroll
            for (int kk = 0; kk < 3; kk++) {
                uint32_t hb = sb + HS + g * 880 + (48 * s + 16 * kk + 2 * t) * 2;
                uint32_t b0 = lds32(hb), b1 = lds32(hb + 16);
                uint32_t wa = sb + st * STG + (16 * kk + lrow) * 1296 + lcol + warp * 128;
#pragma unroll
                for (int i = 0; i < 4; i++) {
                    uint32_t a0, a1, a2, a3;
                    ldsm4t(a0, a1, a2, a3, wa + i * 32);
                    mma16816(ya[i], a0, a1, a2, a3, b0, b1);
                }
            }
            __syncwarp();
            if (lane == 0) mbar_arrive(empty + 8 * st);
            if (++st == 3) { st = 0; ph ^= 1; }
        }
#pragma unroll
        for (int i = 0; i < 4; i++)
#pragma unroll
            for (int e = 0; e < 4; e += 2)
                *reinterpret_cast<float2*>(g_moe_part + (a * DM + warp * 64 + i * 16 + g + 4 * e) * 8 + 2 * t) = make_float2(ya[i][e], ya[i][e + 1]);
    }
    bar_sync(1, 320);
    if (tid == 0) {
        __threadfence();
        unsigned old = atomicAdd(flag_ptr(FL_MOE_CNT), 1u);
        s_misc[1] = (old == ep * 4u + 3u);
        __threadfence();
    }
    bar_sync(1, 320);
    PROF_GT(53);
    if (s_misc[1]) {
        for (int i = tid; i < DM * 8; i += 320) {
            int col = i >> 3, tk = i & 7;
            float y = bf_round(__ldcg(g_moe_part + i) + __ldcg(g_moe_part + DM * 8 + i) + __ldcg(g_moe_part + 2 * DM * 8 + i) + __ldcg(g_moe_part + 3 * DM * 8 + i));
            float sg = bf_round(1.0f / (1.0f + __expf(-s_r[tk])));
            float upd = bf_round(y * sg);
            float xn = __bfloat162float(*reinterpret_cast<const __nv_bfloat16*>(sm + XS + tk * 1296 + col * 2));
            g_brow[tk * DM + col] = __float2bfloat16_rn(xn + upd);
        }
        if (tid < TOPC) g_sel[tid] = s_sel[tid];
        bar_sync(1, 320);
        if (tid == 0) {
            flag_signal(flag_ptr(FL_MOE_DONE));
            *reinterpret_cast<volatile unsigned*>(&g_epoch) = ep + 1;
        }
        PROF_GT(54);
    }
}

__device__ __forceinline__ void layernorm4(const Params& P, int row0, int lane) {
    const int hl = lane & 15;
    uint4 v[2][5], wv[5];
#pragma unroll
    for (int b = 0; b < 2; b++)
#pragma unroll
        for (int i = 0; i < 5; i++)
            v[b][i] = __ldg(reinterpret_cast<const uint4*>(P.x + (size_t)(row0 + 2 * b + (lane >> 4)) * DM + 128 * i + 8 * hl));
#pragma unroll
    for (int i = 0; i < 5; i++) wv[i] = __ldg(reinterpret_cast<const uint4*>(P.wr + 128 * i + 8 * hl));
#pragma unroll
    for (int b = 0; b < 2; b++) {
        const int row = row0 + 2 * b + (lane >> 4);
        float f[40];
#pragma unroll
        for (int i = 0; i < 5; i++) {
            f[8 * i + 0] = bf_lo(v[b][i].x); f[8 * i + 1] = bf_hi(v[b][i].x); f[8 * i + 2] = bf_lo(v[b][i].y); f[8 * i + 3] = bf_hi(v[b][i].y);
            f[8 * i + 4] = bf_lo(v[b][i].z); f[8 * i + 5] = bf_hi(v[b][i].z); f[8 * i + 6] = bf_lo(v[b][i].w); f[8 * i + 7] = bf_hi(v[b][i].w);
        }
        float s0 = 0.f, s1 = 0.f;
#pragma unroll
        for (int i = 0; i < 40; i += 2) { s0 += f[i]; s1 += f[i + 1]; }
        s0 += s1;
#pragma unroll
        for (int o = 8; o > 0; o >>= 1) s0 += __shfl_xor_sync(0xffffffffu, s0, o);
        const float mean = s0 * (1.0f / DM);
        float q0 = 0.f, q1 = 0.f;
#pragma unroll
        for (int i = 0; i < 40; i += 2) { float d0 = f[i] - mean, d1 = f[i + 1] - mean; q0 = fmaf(d0, d0, q0); q1 = fmaf(d1, d1, q1); }
        q0 += q1;
#pragma unroll
        for (int o = 8; o > 0; o >>= 1) q0 += __shfl_xor_sync(0xffffffffu, q0, o);
        const float mb = bf_round(mean);
        const float inv = 1.0f / bf_round(sqrtf(bf_round(bf_round(q0 * (1.0f / DM)) + 1e-5f)));
        float dot = 0.f;
        unsigned char* xp = g_xn + ((row >> 7) * 10 + (hl >> 3)) * 16384 + (row & 127) * 128 + (((hl & 7) ^ (row & 7)) << 4);
#pragma unroll
        for (int i = 0; i < 5; i++) {
            uint32_t o[4], ww[4] = {wv[i].x, wv[i].y, wv[i].z, wv[i].w};
#pragma unroll
            for (int e = 0; e < 4; e++) {
                uint32_t d = pack_bf16(f[8 * i + 2 * e] - mb, f[8 * i + 2 * e + 1] - mb);
                o[e] = pack_bf16(bf_lo(d) * inv, bf_hi(d) * inv);
                dot = fmaf(bf_lo(o[e]), bf_lo(ww[e]), dot);
                dot = fmaf(bf_hi(o[e]), bf_hi(ww[e]), dot);
            }
            stg128(xp + i * 32768, o[0], o[1], o[2], o[3]);
        }
#pragma unroll
        for (int o = 8; o > 0; o >>= 1) dot += __shfl_xor_sync(0xffffffffu, dot, o);
        if (hl == 0) g_router[row] = bf_round(dot);
    }
}

__global__ void __cluster_dims__(2, 1, 1) __launch_bounds__(384, 1)
fused_kernel(const __grid_constant__ CUtensorMap tmC, const __grid_constant__ CUtensorMap tmWk, const __grid_constant__ CUtensorMap tmWv,
             const __grid_constant__ CUtensorMap tmWq, const __grid_constant__ CUtensorMap tmWo, const Params P) {
    extern __shared__ unsigned char smem_raw[];
    const uint32_t ring = (smem_u32(smem_raw) + 1023u) & ~1023u;
    const uint32_t misc = ring + RING_BYTES;
    const int tid = threadIdx.x;
    const int mc = blockIdx.x >> 1, rank = blockIdx.x & 1;
    if (mc >= 64) { aux_cta(P, smem_raw + (ring - smem_u32(smem_raw)), blockIdx.x - 128); return; }
    PROF_DECL
    PROF_GT(0); PROF_EV(1);

    if (tid == 0) {
        for (int i = 0; i < NSLOT; i++) { mbar_init(misc + BAR_FULL + 8 * i, 1); mbar_init(misc + BAR_EMPTY + 8 * i, 16); }
        for (int i = 0; i < NST3; i++) { mbar_init(misc + BAR_FULL3 + 8 * i, 1); mbar_init(misc + BAR_EMPTY3 + 8 * i, 16); }
        for (int i = 0; i < 18; i++) mbar_init(misc + BAR_EV + 8 * i, 4);
        mbar_init(misc + BAR_EPOCH, 1); mbar_init(misc + BAR_LN, 4); mbar_init(misc + BAR_PF, 1); mbar_init(misc + BAR_SEL, 1);
        asm volatile("fence.mbarrier_init.release.cluster;" ::: "memory");
        const CUtensorMap* tw = rank ? &tmWv : &tmWk;
        for (int e = 0; e < 2; e++) {
            mbar_expect_tx(misc + BAR_FULL + 8 * e, SLOT_BYTES);
            tma2d(ring + e * SLOT_BYTES, tw, (mc >> 1) * 128, e * 256, misc + BAR_FULL + 8 * e);
            tma2d(ring + e * SLOT_BYTES + 16384, tw, (mc >> 1) * 128, e * 256 + 128, misc + BAR_FULL + 8 * e);
        }
    }
    if (tid == 32) asm volatile("prefetch.tensormap [%0];" ::"l"(&tmC) : "memory");
    __syncthreads();
    asm volatile("barrier.cluster.arrive.relaxed.aligned;\nbarrier.cluster.wait.aligned;" ::: "memory");

    const int h = mc >> 1, a = mc & 1;
    const int rot = (mc >> 2) & 3;
    const int hq = (mc >> 2) * 2 + rank;
    const int kq = mc & 3;
    const int u3 = mc >> 3, s3 = (mc >> 1) & 3, kap = mc & 1;
    const int wg = __shfl_sync(0xffffffffu, tid >> 7, 0);

    if (wg == 0) {
        asm volatile("setmaxnreg.dec.sync.aligned.u32 40;");
        const int warp = tid >> 5, lane = tid & 31;
        if (warp == 0) {
            if (lane == 0) {
                Cur c; c.slot = 2; c.ph = 0;
                uint32_t dst, fb;
                auto acquire = [&]() {
                    mbar_wait(misc + BAR_EMPTY + 8 * c.slot, c.ph ^ 1);
                    fb = misc + BAR_FULL + 8 * c.slot; dst = ring + c.slot * SLOT_BYTES;
                    mbar_expect_tx(fb, SLOT_BYTES);
                    c.adv();
                };
                auto load_w = [&](const CUtensorMap* tm, int col, int row) {
                    acquire();
                    tma2d(dst, tm, col, row, fb); tma2d(dst + 16384, tm, col, row + 128, fb);
                };
                const CUtensorMap* tw = rank ? &tmWv : &tmWk;
                for (int t = 0; t < 8; t++) {
                    for (int ch = 0; ch < 4; ch++) {
                        acquire();
                        tma2d_mc(dst + rank * 16384, &tmC, ch * 128 + rank * 64, (a * 8 + t) * 128, fb);
                    }
                    if (t == 0) { load_w(tw, h * 128 + 64, 0); load_w(tw, h * 128 + 64, 256); }
                }
                mbar_wait(misc + BAR_EPOCH, 0);
                unsigned ep1;
                asm volatile("ld.shared.u32 %0, [%1];" : "=r"(ep1) : "r"(misc + MISC_EPOCH));
                ep1 += 1;
                load_w(&tmWq, hq * 128, 0); load_w(&tmWq, hq * 128, 256); load_w(&tmWq, hq * 128 + 64, 0);
                flag_wait(flag_ptr(FL_LN), ep1 * 128u);
                fence_async_global();
                for (int t = 0; t < 4; t++) {
                    int tile = blk_of(kq >> 1, (t + rot) & 3) * 2 + (kq & 1);
                    for (int ch = 0; ch < 5; ch++) {
                        if (t == 0 && ch == 4) load_w(&tmWq, hq * 128 + 64, 256);
                        acquire();
                        bulk_load_mc(dst + rank * 16384, g_xn + (tile * 10 + 2 * ch + rank) * 16384, 16384, fb);
                    }
                    acquire();
                    tma2d(dst, &tmWq, hq * 128, 512, fb); tma2d(dst + 16384, &tmWq, hq * 128 + 64, 512, fb);
                }
                flag_wait(flag_ptr(FL_KV + h), ep1 * 8u);
                const unsigned char* Kh = g_K + (size_t)h * 32 * 16384 + rank * 16384;
                const unsigned char* Vh = g_V + (size_t)h * 32 * 16384 + rank * 16384;
                for (int r = 0; r < 4; r++) {
                    int p = blk_of(a, (r + rot) & 3), n = 2 * p + 1;
                    flag_wait(flag_ptr(FL_Q + h * 8 + p), ep1 * 4u);
                    fence_async_global();
                    acquire();
                    int gh = 3 - rank, gl = rank;
                    bulk_load(dst, g_Q + (size_t)(h * 32 + 4 * p + ((r & 1) ? gl : gh)) * 16384, 16384, fb);
                    bulk_load(dst + 16384, g_Q + (size_t)(h * 32 + 4 * p + ((r & 1) ? gh : gl)) * 16384, 16384, fb);
                    acquire(); bulk_load_mc(dst + rank * 16384, Kh + n * 32768, 16384, fb);
                    if (r > 0) { acquire(); bulk_load_mc(dst + rank * 16384, Vh, 16384, fb); }
                    for (int j = n - 1; j >= 0; j--) {
                        acquire(); bulk_load_mc(dst + rank * 16384, Kh + j * 32768, 16384, fb);
                        acquire(); bulk_load_mc(dst + rank * 16384, Vh + (j + 1) * 32768, 16384, fb);
                    }
                }
                acquire(); bulk_load_mc(dst + rank * 16384, Vh, 16384, fb);
                mbar_wait(misc + BAR_EMPTY + 8 * c.slot, c.ph ^ 1); c.adv();
                int st = 0; uint32_t ph3 = 0;
                const int pos0 = pos_of(u3);
                for (int i = 0; i < 32; i++) {
                    int hi = i >> 1, rr = (pos0 - (hi >> 2)) & 3;
                    int head = 16 * kap + 8 * ((hi >> 1) & 1) + 2 * rr + (hi & 1);
                    if ((i & 1) == 0) { flag_wait(flag_ptr(FL_CTX + head * 8 + u3), ep1 * 4u); fence_async_global(); }
                    if (i < NST3) { mbar_wait(misc + BAR_EMPTY + 8 * c.slot, c.ph ^ 1); c.adv(); }
                    else mbar_wait(misc + BAR_EMPTY3 + 8 * st, ph3 ^ 1);
                    fb = misc + BAR_FULL3 + 8 * st; dst = ring + st * ST3_BYTES;
                    mbar_expect_tx(fb, ST3_BYTES);
                    const unsigned char* src = g_Q + (size_t)(head * 32 + 4 * u3 + 2 * rank) * 16384 + (i & 1) * 8192;
                    bulk_load(dst, src, 8192, fb);
                    bulk_load(dst + 8192, src + 16384, 8192, fb);
                    tma3d_mc(dst + 16384 + rank * 10240, &tmWo, 0, head * 128 + (i & 1) * 64 + rank * 32, 5 * s3, fb);
                    if (++st == NST3) { st = 0; ph3 ^= 1; }
                }
            }
        } else {
            if (lane == 0) {
                if (warp == 3) {
                    unsigned ep = *reinterpret_cast<volatile unsigned*>(&g_epoch);
                    asm volatile("st.shared.u32 [%0], %1;" ::"r"(misc + MISC_EPOCH), "r"(ep) : "memory");
                    mbar_arrive(misc + BAR_EPOCH);
                    mbar_wait(misc + BAR_LN, 0);
                    flag_signal(flag_ptr(FL_LN));
                    mbar_wait(misc + BAR_PF, 0);
                    l2_prefetch(reinterpret_cast<const unsigned char*>(P.wq) + (size_t)blockIdx.x * 40960, 40960);
                    flag_wait(flag_ptr(FL_MOE_DONE), ep + 1);
                    int4 s0 = __ldcg(reinterpret_cast<const int4*>(g_sel)), s1 = __ldcg(reinterpret_cast<const int4*>(g_sel) + 1);
                    asm volatile("st.shared.v4.u32 [%0], {%1,%2,%3,%4};" ::"r"(misc + MISC_SEL), "r"(s0.x), "r"(s0.y), "r"(s0.z), "r"(s0.w) : "memory");
                    asm volatile("st.shared.v4.u32 [%0], {%1,%2,%3,%4};" ::"r"(misc + MISC_SEL + 16), "r"(s1.x), "r"(s1.y), "r"(s1.z), "r"(s1.w) : "memory");
                    mbar_arrive(misc + BAR_SEL);
                } else {
                    const int w = warp - 1;
                    const uint32_t eb = misc + BAR_EV + w * 72;
                    mbar_wait(eb, 0);
                    flag_signal(flag_ptr(FL_KV + h));
                    for (int t = 0; t < 4; t++) {
                        mbar_wait(eb + 8 + 8 * t, 0);
                        flag_signal(flag_ptr(FL_Q + hq * 8 + blk_of(kq >> 1, (t + rot) & 3)));
                    }
                    for (int r = 0; r < 4; r++) {
                        mbar_wait(eb + 40 + 8 * r, 0);
                        flag_signal(flag_ptr(FL_CTX + h * 8 + blk_of(a, (r + rot) & 3)));
                        if (r == 1 && w == 0) l2_prefetch(reinterpret_cast<const unsigned char*>(P.wo) + (size_t)blockIdx.x * 40960, 40960);
                    }
                }
            }
        }
    } else {
        asm volatile("setmaxnreg.inc.sync.aligned.u32 232;");
        Ctx c;
        c.ring = ring; c.misc = misc; c.w = wg - 1; c.warp = (tid >> 5) & 3; c.lane = tid & 31;
        c.rel = mapa(misc, tid & 1);
        const int w = c.w;
        const int my_bar = 1 + w, other_bar = 2 - w;
        if (w == 1) {
            bar_arrive(1, 256);
            layernorm4(P, blockIdx.x * 16 + c.warp * 4, c.lane);
            __syncwarp();
            if (c.lane == 0) mbar_arrive(misc + BAR_LN);
        }
        Cur cur;
        {
            uint32_t wf[128];
            float acc[64];
#pragma unroll
            for (int i = 0; i < 64; i++) acc[i] = 0.f;
            auto load_weights = [&](int e0, int e1) {
                Cur c0 = cur_at(e0), c1 = cur_at(e1);
                mbar_wait(misc + BAR_FULL + 8 * c0.slot, c0.ph);
                load_afrag<16, 0>(wf, ring + c0.slot * SLOT_BYTES, c);
                __syncwarp();
                release(c, BAR_EMPTY + 8 * c0.slot, 2);
                mbar_wait(misc + BAR_FULL + 8 * c1.slot, c1.ph);
                load_afrag<16, 64>(wf, ring + c1.slot * SLOT_BYTES, c);
                __syncwarp();
                release(c, BAR_EMPTY + 8 * c1.slot, 2);
            };
            auto chunks4 = [&](uint32_t& last_slot) {
#pragma unroll
                for (int ch = 0; ch < 4; ch++) {
                    mbar_wait(misc + BAR_FULL + 8 * cur.slot, cur.ph);
                    uint64_t d = mkdesc(ring + cur.slot * SLOT_BYTES, 16, 1024, 1);
                    wg_fence();
#pragma unroll
                    for (int k = 0; k < 8; k++)
                        wgmma_rs_n128_ta0_tb0(acc, wf[32 * ch + 4 * k], wf[32 * ch + 4 * k + 1], wf[32 * ch + 4 * k + 2], wf[32 * ch + 4 * k + 3],
                                              d + (k >> 2) * 1024 + (k & 3) * 2, (ch | k) != 0);
                    wg_commit();
                    if (ch > 0 && ch < 3) { wg_wait<1>(); release(c, BAR_EMPTY + 8 * last_slot, 1); }
                    if (ch < 3) { last_slot = cur.slot; cur.adv(); }
                }
            };
            load_weights(w ? 6 : 0, w ? 7 : 1);
            if (tid == 256) mbar_arrive(misc + BAR_PF);
            PROF_EV(2);
            cur = cur_at(2);
            unsigned char* kvdst = (rank ? g_V : g_K) + (size_t)(h * 32 + a * 16) * 16384;
#pragma unroll 1
            for (int t = 0; t < 8; t++) {
                uint32_t last;
                bar_sync(my_bar, 256);
                PROF_EV(10);
                chunks4(last);
                bar_arrive(other_bar, 256);
                wg_wait<1>(); release(c, BAR_EMPTY + 8 * last, 1);
                wg_wait<0>(); release(c, BAR_EMPTY + 8 * cur.slot, 1);
                PROF_EV(11);
                cur.adv();
                if (t == 0) { cur.adv(); cur.adv(); }
                fence_regs(acc);
                store_proj(acc, kvdst + t * 32768, c);
            }
            signal_event(c, 0);
            load_weights(w ? 38 : 36, w ? 43 : 37);
            cur = cur_at(39);
#pragma unroll 1
            for (int t = 0; t < 4; t++) {
                uint32_t last;
                bar_sync(my_bar, 256);
                PROF_EV(20);
                chunks4(last);
                wg_wait<1>(); release(c, BAR_EMPTY + 8 * last, 1);
                last = cur.slot; cur.adv();
                if (t == 0) cur.adv();
                Cur cx = cur; cur.adv();
                mbar_wait(misc + BAR_FULL + 8 * cx.slot, cx.ph);
                mbar_wait(misc + BAR_FULL + 8 * cur.slot, cur.ph);
                uint64_t db = mkdesc(ring + cx.slot * SLOT_BYTES, 16, 1024, 1);
                uint64_t da = mkdesc(ring + cur.slot * SLOT_BYTES + w * 16384, 16384, 1024, 1);
                wg_fence();
#pragma unroll
                for (int k = 0; k < 8; k++) wgmma_ss_n128_ta1_tb0(acc, da + 128 * k, db + (k >> 2) * 1024 + (k & 3) * 2, 1);
                wg_commit();
                bar_arrive(other_bar, 256);
                wg_wait<1>(); release(c, BAR_EMPTY + 8 * last, 1);
                wg_wait<0>(); release(c, BAR_EMPTY + 8 * cx.slot, 1); release(c, BAR_EMPTY + 8 * cur.slot, 1);
                PROF_EV(21);
                cur.adv();
                fence_regs(acc);
                int tile = blk_of(kq >> 1, (t + rot) & 3) * 2 + (kq & 1);
#pragma unroll
                for (int i = 0; i < 64; i++) acc[i] *= SM_SCALE;
                store_proj(acc, g_Q + (size_t)(hq * 32 + tile * 2) * 16384, c);
                signal_event(c, 1 + t);
            }
        }
        {
            float s[64], o[64];
            uint32_t q[32], p[32];
            float m[2], l[2], alpha[2];
#pragma unroll
            for (int i = 0; i < 64; i++) { s[i] = 0.f; o[i] = 0.f; }
#pragma unroll
            for (int i = 0; i < 32; i++) p[i] = 0u;
            m[0] = m[1] = l[0] = l[1] = alpha[0] = alpha[1] = 0.f;
            bool gen = false;
            int pv_acc = 0; bool pv_half = true; uint32_t pv_cnt = 1;
            unsigned char* ctx_dst = nullptr;
#pragma unroll 1
            for (int r = 0; r < 4; r++) {
                const int pb = blk_of(a, (r + rot) & 3);
                const bool heavy = ((r & 1) == w);
                const int grp = heavy ? 3 - rank : rank;
                const bool half = (grp & 1) == 0;
                mbar_wait(misc + BAR_FULL + 8 * cur.slot, cur.ph);
                load_afrag<8, 0>(q, ring + cur.slot * SLOT_BYTES + w * 16384, c);
                __syncwarp();
                release(c, BAR_EMPTY + 8 * cur.slot, 1);
                cur.adv();
                Cur ck = cur, cv;
                cur.adv();
                cv = cur;
                if (r > 0) cur.adv();
                if (!heavy) { ck = cur; cur.adv(); cur.adv(); }
                mbar_wait(misc + BAR_FULL + 8 * ck.slot, ck.ph);
                if (r > 0) mbar_wait(misc + BAR_FULL + 8 * cv.slot, cv.ph);
                float lprev[2] = {l[0], l[1]};
                bar_sync(my_bar, 256);
                PROF_EV(30);
                if (half) {
                    issue_qk_half(s, q, ring + ck.slot * SLOT_BYTES);
                    issue_pv(o, p, ring + cv.slot * SLOT_BYTES, pv_acc, pv_half);
                    bar_arrive(other_bar, 256);
                    wg_wait<1>();
                    release(c, BAR_EMPTY + 8 * ck.slot, heavy ? 2 : 1);
                    fence_regs(s);
                    mask_diag<0>(s, c);
                    gen = softmax_first<8>(s, m, l);
                } else {
                    issue_qk(s, q, ring + ck.slot * SLOT_BYTES);
                    issue_pv(o, p, ring + cv.slot * SLOT_BYTES, pv_acc, pv_half);
                    bar_arrive(other_bar, 256);
                    wg_wait<1>();
                    release(c, BAR_EMPTY + 8 * ck.slot, heavy ? 2 : 1);
                    fence_regs(s);
                    mask_diag<8>(s, c);
                    gen = softmax_first<16>(s, m, l);
                }
                wg_wait<0>();
                fence_regs(o);
                fence_regs(s);
                if (r > 0) {
                    release(c, BAR_EMPTY + 8 * cv.slot, pv_cnt);
                    store_ctx(o, lprev, ctx_dst, c);
                    signal_event(c, 4 + r);
                }
#pragma unroll
                for (int i = 0; i < 32; i++) p[i] = pack_bf16(s[2 * i], s[2 * i + 1]);
                ctx_dst = g_Q + (size_t)(h * 32 + 4 * pb + grp) * 16384;
                pv_acc = 0; pv_half = half; pv_cnt = heavy ? 2 : 1;
                const int nreg = 2 * pb + (heavy ? 1 : 0);
#pragma unroll 1
                for (int j = 0; j < nreg; j++) {
                    ck = cur; cur.adv(); cv = cur; cur.adv();
                    mbar_wait(misc + BAR_FULL + 8 * ck.slot, ck.ph);
                    mbar_wait(misc + BAR_FULL + 8 * cv.slot, cv.ph);
                    bar_sync(my_bar, 256);
                    PROF_EV(31);
                    issue_qk(s, q, ring + ck.slot * SLOT_BYTES);
                    issue_pv(o, p, ring + cv.slot * SLOT_BYTES, pv_acc, pv_half);
                    bar_arrive(other_bar, 256);
                    wg_wait<1>();
                    fence_regs(s);
                    if (!gen) {
                        float l0 = l[0], l1 = l[1];
                        exp_sum<16, false>(s, m, l0, l1);
                        gen = __any_sync(0xffffffffu, !(l0 <= SAFE_SUM && l1 <= SAFE_SUM));
                        if (gen) recompute_scores(s, q, ring + ck.slot * SLOT_BYTES, c);
                        else { l[0] = l0; l[1] = l1; }
                    }
                    release(c, BAR_EMPTY + 8 * ck.slot, 1);
                    if (gen) {
                        float mx[2];
                        row_max<16>(s, mx);
#pragma unroll
                        for (int i = 0; i < 2; i++) {
                            mx[i] = fmaxf(mx[i], m[i]);
                            alpha[i] = ex2(m[i] - mx[i]);
                            m[i] = mx[i];
                            l[i] *= alpha[i];
                        }
                        exp_sum<16, true>(s, m, l[0], l[1]);
                    }
                    wg_wait<0>();
                    release(c, BAR_EMPTY + 8 * cv.slot, pv_cnt);
                    fence_regs(o);
                    fence_regs(s);
#pragma unroll
                    for (int i = 0; i < 32; i++) p[i] = pack_bf16(s[2 * i], s[2 * i + 1]);
                    if (gen) {
#pragma unroll
                        for (int i = 0; i < 64; i++) o[i] *= alpha[(i >> 1) & 1];
                    }
                    pv_acc = 1; pv_half = false; pv_cnt = 1;
                }
            }
            mbar_wait(misc + BAR_FULL + 8 * cur.slot, cur.ph);
            bar_sync(my_bar, 256);
            PROF_EV(32);
            issue_pv(o, p, ring + cur.slot * SLOT_BYTES, pv_acc, pv_half);
            if (w == 0) bar_arrive(other_bar, 256);
            wg_wait<0>();
            release(c, BAR_EMPTY + 8 * cur.slot, pv_cnt);
            fence_regs(o);
            store_ctx(o, l, ctx_dst, c);
            signal_event(c, 8);
        }
        {
            float acc[80];
#pragma unroll
            for (int i = 0; i < 80; i++) acc[i] = 0.f;
            int st = 0, prev = 0; uint32_t ph3 = 0;
            mbar_wait(misc + BAR_SEL, 0);
            const uint32_t tag = (lds32(misc + MISC_EPOCH) + 1) & 1;
            const int g = c.lane >> 2, t = c.lane & 3;
            const int row = (2 * u3 + rank) * 128 + 64 * w + 16 * c.warp + 8 * kap + g;
            const int col = 160 * s3 + 8 * t;
            int sel = -1;
#pragma unroll
            for (int i = 0; i < TOPC; i++) if ((int)lds32(misc + MISC_SEL + 4 * i) == row) sel = i;
            uint4 xv[5], bv[5];
#pragma unroll
            for (int i = 0; i < 5; i++) {
                xv[i] = ldg128(P.x + (size_t)row * DM + col + 32 * i);
                bv[i] = ldg128(sel >= 0 ? (const void*)(g_brow + sel * DM + col + 32 * i) : (const void*)xn_addr(row, col + 32 * i));
            }
            PROF_EV(40);
#pragma unroll 1
            for (int i = 0; i < 32; i++) {
                mbar_wait(misc + BAR_FULL3 + 8 * st, ph3);
                uint32_t base = ring + st * ST3_BYTES;
                uint64_t da = mkdesc(base + w * 8192, 16, 1024, 1);
                uint64_t db = mkdesc(base + 16384, 2048, 512, 2);
                wg_fence();
#pragma unroll
                for (int k = 0; k < 4; k++) wgmma_ss_n160_ta0_tb1(acc, da + 2 * k, db + (k >> 1) * 640 + (k & 1) * 64, 1);
                wg_commit();
                if (i > 0) { wg_wait<1>(); if (i <= 32 - NST3) release(c, BAR_EMPTY3 + 8 * prev, 1); }
                prev = st;
                if (++st == NST3) { st = 0; ph3 ^= 1; }
            }
            wg_wait<0>();
            fence_regs(acc);
            PROF_EV(41);
            const int t256 = tid - 128;
            uint4* sendp = g_part + (size_t)blockIdx.x * 2560 + t256;
            float keep[40];
#pragma unroll
            for (int j = 0; j < 10; j++) {
                uint32_t v0 = __float_as_uint(kap ? acc[8 * j + 0] : acc[8 * j + 2]), v1 = __float_as_uint(kap ? acc[8 * j + 1] : acc[8 * j + 3]);
                uint32_t v2 = __float_as_uint(kap ? acc[8 * j + 4] : acc[8 * j + 6]), v3 = __float_as_uint(kap ? acc[8 * j + 5] : acc[8 * j + 7]);
                asm volatile("st.relaxed.gpu.global.v4.b32 [%0], {%1,%2,%3,%4};" ::"l"(sendp + j * 256),
                             "r"((v0 & ~1u) | tag), "r"((v1 & ~1u) | tag), "r"((v2 & ~1u) | tag), "r"((v3 & ~1u) | tag) : "memory");
                keep[4 * j + 0] = kap ? acc[8 * j + 2] : acc[8 * j + 0]; keep[4 * j + 1] = kap ? acc[8 * j + 3] : acc[8 * j + 1];
                keep[4 * j + 2] = kap ? acc[8 * j + 6] : acc[8 * j + 4]; keep[4 * j + 3] = kap ? acc[8 * j + 7] : acc[8 * j + 5];
            }
            const uint4* recvp = g_part + (size_t)(blockIdx.x ^ 2) * 2560 + t256;
            uint4 rv[10];
            int spins = 0;
            while (true) {
                uint32_t all_and = 1u, all_or = 0u;
#pragma unroll
                for (int j = 0; j < 10; j++) {
                    asm volatile("ld.relaxed.gpu.global.v4.b32 {%0,%1,%2,%3}, [%4];"
                                 : "=r"(rv[j].x), "=r"(rv[j].y), "=r"(rv[j].z), "=r"(rv[j].w) : "l"(recvp + j * 256) : "memory");
                }
#pragma unroll
                for (int j = 0; j < 10; j++) {
                    all_and &= rv[j].x & rv[j].y & rv[j].z & rv[j].w;
                    all_or |= rv[j].x | rv[j].y | rv[j].z | rv[j].w;
                }
                bool ok = ((tag ? all_and : all_or) & 1u) == tag;
                if (__all_sync(0xffffffffu, ok) || ++spins > 2000000) break;
            }
            uint32_t pk[20];
#pragma unroll
            for (int j = 0; j < 10; j++) {
                pk[2 * j] = pack_bf16(keep[4 * j] + __uint_as_float(rv[j].x & ~1u), keep[4 * j + 1] + __uint_as_float(rv[j].y & ~1u));
                pk[2 * j + 1] = pack_bf16(keep[4 * j + 2] + __uint_as_float(rv[j].z & ~1u), keep[4 * j + 3] + __uint_as_float(rv[j].w & ~1u));
            }
#pragma unroll
            for (int i = 0; i < 5; i++) {
                uint32_t a0 = pk[4 * i], a1 = pk[4 * i + 1], a2 = pk[4 * i + 2], a3 = pk[4 * i + 3];
                uint32_t x0 = (t & 1) ? a0 : a1, x1 = (t & 1) ? a2 : a3;
                x0 = __shfl_xor_sync(0xffffffffu, x0, 1); x1 = __shfl_xor_sync(0xffffffffu, x1, 1);
                if (t & 1) { a0 = x0; a2 = x1; } else { a1 = x0; a3 = x1; }
                x0 = (t & 2) ? a0 : a2; x1 = (t & 2) ? a1 : a3;
                x0 = __shfl_xor_sync(0xffffffffu, x0, 2); x1 = __shfl_xor_sync(0xffffffffu, x1, 2);
                if (t & 2) { a0 = x0; a1 = x1; } else { a2 = x0; a3 = x1; }
                uint32_t av[4] = {a0, a1, a2, a3};
                uint32_t xx[4] = {xv[i].x, xv[i].y, xv[i].z, xv[i].w}, bb[4] = {bv[i].x, bv[i].y, bv[i].z, bv[i].w};
                uint32_t ov[4];
#pragma unroll
                for (int e = 0; e < 4; e++) {
                    uint32_t t1 = pack_bf16(bf_lo(xx[e]) + bf_lo(av[e]), bf_hi(xx[e]) + bf_hi(av[e]));
                    ov[e] = pack_bf16(bf_lo(t1) + bf_lo(bb[e]), bf_hi(t1) + bf_hi(bb[e]));
                }
                stg128(P.out + (size_t)row * DM + col + 32 * i, ov[0], ov[1], ov[2], ov[3]);
            }
            PROF_EV(42); PROF_GT(43);
        }
    }
}

typedef CUresult (*EncodeFn)(CUtensorMap*, CUtensorMapDataType, cuuint32_t, void*, const cuuint64_t*, const cuuint64_t*, const cuuint32_t*,
                             const cuuint32_t*, CUtensorMapInterleave, CUtensorMapSwizzle, CUtensorMapL2promotion, CUtensorMapFloatOOBfill);

void make_map2d(EncodeFn enc, CUtensorMap* tm, const void* p, uint64_t cols, uint64_t rows) {
    cuuint64_t gd[2] = {cols, rows}, gs[1] = {cols * 2};
    cuuint32_t box[2] = {64, 128}, es[2] = {1, 1};
    enc(tm, CU_TENSOR_MAP_DATA_TYPE_BFLOAT16, 2, const_cast<void*>(p), gd, gs, box, es, CU_TENSOR_MAP_INTERLEAVE_NONE,
        CU_TENSOR_MAP_SWIZZLE_128B, CU_TENSOR_MAP_L2_PROMOTION_L2_128B, CU_TENSOR_MAP_FLOAT_OOB_FILL_NONE);
}

}

extern "C" void kernel_launch(void* const* d_in, const int* in_sizes, int n_in, void* d_out, int out_size) {
    (void)in_sizes; (void)n_in; (void)out_size;
    static EncodeFn enc = nullptr;
    if (!enc) {
        void* fn = nullptr;
        cudaDriverEntryPointQueryResult qr;
        cudaGetDriverEntryPoint("cuTensorMapEncodeTiled", &fn, cudaEnableDefault, &qr);
        enc = (EncodeFn)fn;
        cudaFuncSetAttribute(fused_kernel, cudaFuncAttributeMaxDynamicSharedMemorySize, SMEM_BYTES);
    }
    CUtensorMap tmC, tmWk, tmWv, tmWq, tmWo;
    make_map2d(enc, &tmC, d_in[1], DC, SEQ);
    make_map2d(enc, &tmWq, d_in[2], 4096, DM);
    make_map2d(enc, &tmWk, d_in[3], 4096, DC);
    make_map2d(enc, &tmWv, d_in[4], 4096, DC);
    {
        cuuint64_t gd[3] = {32, 4096, 20}, gs[2] = {DM * 2, 64};
        cuuint32_t box[3] = {32, 32, 5}, es[3] = {1, 1, 1};
        enc(&tmWo, CU_TENSOR_MAP_DATA_TYPE_BFLOAT16, 3, d_in[5], gd, gs, box, es, CU_TENSOR_MAP_INTERLEAVE_NONE,
            CU_TENSOR_MAP_SWIZZLE_64B, CU_TENSOR_MAP_L2_PROMOTION_L2_128B, CU_TENSOR_MAP_FLOAT_OOB_FILL_NONE);
    }
    Params P;
    P.x = (const __nv_bfloat16*)d_in[0];
    P.wq = (const __nv_bfloat16*)d_in[2];
    P.wo = (const __nv_bfloat16*)d_in[5];
    P.wr = (const __nv_bfloat16*)d_in[7];
    P.wg = (const __nv_bfloat16*)d_in[8];
    P.wu = (const __nv_bfloat16*)d_in[9];
    P.wd = (const __nv_bfloat16*)d_in[10];
    P.out = (__nv_bfloat16*)d_out;
    fused_kernel<<<132, 384, SMEM_BYTES>>>(tmC, tmWk, tmWv, tmWq, tmWo, P);
}
```

```cpp
#include <cuda_runtime.h>
#include <cuda_bf16.h>
#include <cuda.h>
#include <stdint.h>

namespace {

constexpr int SEQ = 2048, NH = 32, DM = 640, DC = 512, FF = 1728, TOPC = 8;
constexpr int NSLOT = 7, SLOT_BYTES = 32768;
constexpr int NST3 = 6, ST3_BYTES = 36864;
constexpr int RING_BYTES = NSLOT * SLOT_BYTES;
constexpr int SMEM_BYTES = RING_BYTES + 2048;

constexpr int BAR_FULL = 0, BAR_EMPTY = 64, BAR_FULL3 = 128, BAR_EMPTY3 = 192, BAR_EV = 256  , BAR_LN = 424, BAR_PF = 432, BAR_SEL = 440,
              MISC_EPOCH = 448, MISC_SEL = 464, BAR_DEP = 512  , BAR_W = 672  ;

constexpr int FL_LN = 0, FL_MOE_CNT = 1, FL_MOE_DONE = 2, FL_KV = 8  , FL_Q = 64  , FL_CTX = 320  , FL_TOTAL = 576;

__device__ __align__(1024) unsigned char g_K[NH * 32 * 16384];
__device__ __align__(1024) unsigned char g_V[NH * 32 * 16384];
__device__ __align__(1024) unsigned char g_Q[NH * 32 * 16384];
__device__ __align__(1024) unsigned char g_xn[16 * 10 * 16384];
__device__ __align__(1024) uint4 g_part[128 * 10 * 256];
__device__ float g_router[SEQ];
__device__ float g_moe_part[4 * TOPC * DM];
__device__ __align__(16) __nv_bfloat16 g_brow[TOPC * DM];
__device__ __align__(16) int g_sel[TOPC];
__device__ unsigned g_flags[FL_TOTAL * 8];
__device__ unsigned g_epoch;

struct Params {
    const __nv_bfloat16 *x, *wr, *wg, *wu, *wd, *wq, *wo;
    __nv_bfloat16* out;
};

__device__ __forceinline__ uint32_t smem_u32(const void* p) { return (uint32_t)__cvta_generic_to_shared(p); }
__device__ __forceinline__ void mbar_init(uint32_t bar, int cnt) { asm volatile("mbarrier.init.shared::cta.b64 [%0], %1;" ::"r"(bar), "r"(cnt)); }
__device__ __forceinline__ void mbar_expect_tx(uint32_t bar, uint32_t bytes) {
    asm volatile("mbarrier.arrive.expect_tx.shared::cta.b64 _, [%0], %1;" ::"r"(bar), "r"(bytes) : "memory");
}
__device__ __forceinline__ void mbar_arrive(uint32_t bar) { asm volatile("mbarrier.arrive.shared::cta.b64 _, [%0];" ::"r"(bar) : "memory"); }
__device__ __forceinline__ void mbar_arrive_cluster(uint32_t cluster_addr, uint32_t cnt) {
    asm volatile("mbarrier.arrive.shared::cluster.b64 _, [%0], %1;" ::"r"(cluster_addr), "r"(cnt) : "memory");
}
__device__ __forceinline__ uint32_t mapa(uint32_t addr, uint32_t cta) {
    uint32_t r; asm("mapa.shared::cluster.u32 %0, %1, %2;" : "=r"(r) : "r"(addr), "r"(cta)); return r;
}
__device__ __forceinline__ void mbar_wait(uint32_t bar, uint32_t parity) {
    asm volatile(
        "{\n.reg .pred p;\n.reg .u32 n;\n"
        "mbarrier.try_wait.parity.shared::cta.b64 p, [%0], %1;\n"
        "@p bra DONE;\n"
        "mov.u32 n, 0;\n"
        "LAB_WAIT:\n"
        "mbarrier.try_wait.parity.shared::cta.b64 p, [%0], %1;\n"
        "@p bra DONE;\n"
        "add.u32 n, n, 1;\n"
        "setp.lt.u32 p, n, 2000000;\n"
        "@p bra LAB_WAIT;\n"
        "trap;\n"
        "DONE:\n}\n" ::"r"(bar), "r"(parity) : "memory");
}
__device__ __forceinline__ void flag_wait(const unsigned* flag, unsigned target) {
    asm volatile(
        "{\n.reg .pred p;\n.reg .u32 n, v;\n.reg .s32 d;\n"
        "mov.u32 n, 0;\n"
        "LAB_WAIT:\n"
        "ld.acquire.gpu.global.u32 v, [%0];\n"
        "sub.s32 d, v, %1;\n"
        "setp.ge.s32 p, d, 0;\n"
        "@p bra DONE;\n"
        "nanosleep.u32 40;\n"
        "add.u32 n, n, 1;\n"
        "setp.lt.u32 p, n, 3000000;\n"
        "@p bra LAB_WAIT;\n"
        "trap;\n"
        "DONE:\n}\n" ::"l"(flag), "r"(target) : "memory");
}
__device__ __forceinline__ void flag_signal(unsigned* flag) {
    asm volatile("red.release.gpu.global.add.u32 [%0], 1;" ::"l"(flag) : "memory");
}
__device__ __forceinline__ void fence_async_global() { asm volatile("fence.proxy.async.global;" ::: "memory"); }
__device__ __forceinline__ unsigned* flag_ptr(int idx) { return g_flags + idx * 8; }

__device__ __forceinline__ uint64_t policy_stream() {
    uint64_t p; asm("createpolicy.fractional.L2::evict_first.b64 %0, 1.0;" : "=l"(p)); return p;
}
__device__ __forceinline__ uint64_t policy_normal() {
    uint64_t p; asm("createpolicy.fractional.L2::evict_normal.b64 %0, 1.0;" : "=l"(p)); return p;
}
__device__ __forceinline__ void bulk_load_hint(uint32_t dst, const void* src, uint32_t bytes, uint32_t bar, uint64_t pol) {
    asm volatile("cp.async.bulk.shared::cluster.global.mbarrier::complete_tx::bytes.L2::cache_hint [%0], [%1], %2, [%3], %4;"
                 ::"r"(dst), "l"(src), "r"(bytes), "r"(bar), "l"(pol) : "memory");
}
__device__ __forceinline__ void bulk_load(uint32_t dst, const void* src, uint32_t bytes, uint32_t bar) {
    asm volatile("cp.async.bulk.shared::cluster.global.mbarrier::complete_tx::bytes [%0], [%1], %2, [%3];"
                 ::"r"(dst), "l"(src), "r"(bytes), "r"(bar) : "memory");
}
__device__ __forceinline__ void bulk_load_mc(uint32_t dst, const void* src, uint32_t bytes, uint32_t bar) {
    asm volatile("cp.async.bulk.shared::cluster.global.mbarrier::complete_tx::bytes.multicast::cluster [%0], [%1], %2, [%3], %4;"
                 ::"r"(dst), "l"(src), "r"(bytes), "r"(bar), "h"((uint16_t)3) : "memory");
}
__device__ __forceinline__ void tma2d(uint32_t dst, const CUtensorMap* tm, int c0, int c1, uint32_t bar) {
    asm volatile("cp.async.bulk.tensor.2d.shared::cluster.global.mbarrier::complete_tx::bytes.L2::cache_hint [%0], [%1, {%3, %4}], [%2], %5;"
                 ::"r"(dst), "l"(tm), "r"(bar), "r"(c0), "r"(c1), "l"(policy_stream()) : "memory");
}
__device__ __forceinline__ void tma2d_mc(uint32_t dst, const CUtensorMap* tm, int c0, int c1, uint32_t bar) {
    asm volatile("cp.async.bulk.tensor.2d.shared::cluster.global.mbarrier::complete_tx::bytes.multicast::cluster [%0], [%1, {%3, %4}], [%2], %5;"
                 ::"r"(dst), "l"(tm), "r"(bar), "r"(c0), "r"(c1), "h"((uint16_t)3) : "memory");
}
__device__ __forceinline__ void tma3d_mc(uint32_t dst, const CUtensorMap* tm, int c0, int c1, int c2, uint32_t bar) {
    asm volatile("cp.async.bulk.tensor.3d.shared::cluster.global.mbarrier::complete_tx::bytes.multicast::cluster [%0], [%1, {%3, %4, %5}], [%2], %6;"
                 ::"r"(dst), "l"(tm), "r"(bar), "r"(c0), "r"(c1), "r"(c2), "h"((uint16_t)3) : "memory");
}
__device__ __forceinline__ void l2_prefetch(const void* p, uint32_t bytes) {
    asm volatile("cp.async.bulk.prefetch.L2.global [%0], %1;" ::"l"(p), "r"(bytes) : "memory");
}
__device__ __forceinline__ bool elect_one() {
    uint32_t r; asm volatile("{\n.reg .pred p;\nelect.sync _|p, 0xffffffff;\nselp.u32 %0, 1, 0, p;\n}\n" : "=r"(r)); return r != 0;
}
__device__ __forceinline__ void wg_fence() { asm volatile("wgmma.fence.sync.aligned;" ::: "memory"); }
__device__ __forceinline__ void wg_commit() { asm volatile("wgmma.commit_group.sync.aligned;" ::: "memory"); }
template <int N> __device__ __forceinline__ void wg_wait() { asm volatile("wgmma.wait_group.sync.aligned %0;" ::"n"(N) : "memory"); }
__device__ __forceinline__ void bar_sync(int id, int n) { asm volatile("bar.sync %0, %1;" ::"r"(id), "r"(n) : "memory"); }
__device__ __forceinline__ void bar_arrive(int id, int n) { asm volatile("bar.arrive %0, %1;" ::"r"(id), "r"(n) : "memory"); }
template <int N> __device__ __forceinline__ void fence_regs(float (&a)[N]) {
#pragma unroll
    for (int i = 0; i < N; i++) asm volatile("" : "+f"(a[i])::"memory");
}
template <int N> __device__ __forceinline__ void undef_regs(float (&a)[N]) {
#pragma unroll
    for (int i = 0; i < N; i++) asm volatile("" : "=f"(a[i]));
}
__device__ __forceinline__ void ldsm4t(uint32_t& r0, uint32_t& r1, uint32_t& r2, uint32_t& r3, uint32_t addr) {
    asm volatile("ldmatrix.sync.aligned.m8n8.x4.trans.shared.b16 {%0,%1,%2,%3}, [%4];"
                 : "=r"(r0), "=r"(r1), "=r"(r2), "=r"(r3) : "r"(addr) : "memory");
}
__device__ __forceinline__ uint32_t pack_bf16(float lo, float hi) {
    uint32_t r; asm("cvt.rn.bf16x2.f32 %0, %1, %2;" : "=r"(r) : "f"(hi), "f"(lo)); return r;
}
__device__ __forceinline__ float bf_lo(uint32_t v) { return __uint_as_float(v << 16); }
__device__ __forceinline__ float bf_hi(uint32_t v) { return __uint_as_float(v & 0xffff0000u); }
__device__ __forceinline__ float bf_round(float v) { return __bfloat162float(__float2bfloat16_rn(v)); }
__device__ __forceinline__ float ex2(float v) { float r; asm("ex2.approx.ftz.f32 %0, %1;" : "=f"(r) : "f"(v)); return r; }
__device__ __forceinline__ float rcp_fast(float v) { float r; asm("rcp.approx.ftz.f32 %0, %1;" : "=f"(r) : "f"(v)); return r; }
__device__ __forceinline__ float sqrt_fast(float v) { float r; asm("sqrt.approx.ftz.f32 %0, %1;" : "=f"(r) : "f"(v)); return r; }
__device__ __forceinline__ void stg128(void* p, uint32_t a, uint32_t b, uint32_t c, uint32_t d) {
    asm volatile("st.global.v4.b32 [%0], {%1,%2,%3,%4};" ::"l"(p), "r"(a), "r"(b), "r"(c), "r"(d) : "memory");
}
__device__ __forceinline__ void stg128_hint(void* p, uint32_t a, uint32_t b, uint32_t c, uint32_t d, uint64_t pol) {
    asm volatile("st.global.L2::cache_hint.v4.b32 [%0], {%1,%2,%3,%4}, %5;" ::"l"(p), "r"(a), "r"(b), "r"(c), "r"(d), "l"(pol) : "memory");
}
__device__ __forceinline__ uint4 ldg128_stream(const void* p) {
    uint4 v; asm volatile("ld.global.nc.L2::cache_hint.v4.b32 {%0,%1,%2,%3}, [%4], %5;" : "=r"(v.x), "=r"(v.y), "=r"(v.z), "=r"(v.w) : "l"(p), "l"(policy_stream())); return v;
}
__device__ __forceinline__ uint4 ldg128(const void* p) {
    uint4 v; asm volatile("ld.global.cg.v4.b32 {%0,%1,%2,%3}, [%4];" : "=r"(v.x), "=r"(v.y), "=r"(v.z), "=r"(v.w) : "l"(p) : "memory"); return v;
}
__device__ __forceinline__ uint64_t mkdesc(uint32_t addr, uint32_t lbo, uint32_t sbo, uint32_t swz) {
    uint32_t lo = ((addr & 0x3FFFF) >> 4) | ((lbo >> 4) << 16);
    uint32_t hi = (sbo >> 4) | (swz << 30);
    return ((uint64_t)hi << 32) | lo;
}
__device__ __forceinline__ int perm32(int v) { return (v & ~30) | ((v >> 2) & 6) | ((v << 2) & 24); }

__device__ __forceinline__ void wgmma_rs_n128_ta0_tb0(float (&d)[64], uint32_t a0, uint32_t a1, uint32_t a2, uint32_t a3, uint64_t descB, int scaleD) {
  asm volatile("{\n.reg .pred p;\nsetp.ne.b32 p, %69, 0;\n"
    "wgmma.mma_async.sync.aligned.m64n128k16.f32.bf16.bf16 "
    "{%0, %1, %2, %3, %4, %5, %6, %7, %8, %9, %10, %11, %12, %13, %14, %15, %16, %17, %18, %19, %20, %21, %22, %23, %24, %25, %26, %27, %28, %29, %30, %31, %32, %33, %34, %35, %36, %37, %38, %39, %40, %41, %42, %43, %44, %45, %46, %47, %48, %49, %50, %51, %52, %53, %54, %55, %56, %57, %58, %59, %60, %61, %62, %63}, "
    "{%64, %65, %66, %67}, %68, p, 1, 1, 0;\n}\n"
    : "+f"(d[0]), "+f"(d[1]), "+f"(d[2]), "+f"(d[3]), "+f"(d[4]), "+f"(d[5]), "+f"(d[6]), "+f"(d[7]), "+f"(d[8]), "+f"(d[9]), "+f"(d[10]), "+f"(d[11]), "+f"(d[12]), "+f"(d[13]), "+f"(d[14]), "+f"(d[15]), "+f"(d[16]), "+f"(d[17]), "+f"(d[18]), "+f"(d[19]), "+f"(d[20]), "+f"(d[21]), "+f"(d[22]), "+f"(d[23]), "+f"(d[24]), "+f"(d[25]), "+f"(d[26]), "+f"(d[27]), "+f"(d[28]), "+f"(d[29]), "+f"(d[30]), "+f"(d[31]), "+f"(d[32]), "+f"(d[33]), "+f"(d[34]), "+f"(d[35]), "+f"(d[36]), "+f"(d[37]), "+f"(d[38]), "+f"(d[39]), "+f"(d[40]), "+f"(d[41]), "+f"(d[42]), "+f"(d[43]), "+f"(d[44]), "+f"(d[45]), "+f"(d[46]), "+f"(d[47]), "+f"(d[48]), "+f"(d[49]), "+f"(d[50]), "+f"(d[51]), "+f"(d[52]), "+f"(d[53]), "+f"(d[54]), "+f"(d[55]), "+f"(d[56]), "+f"(d[57]), "+f"(d[58]), "+f"(d[59]), "+f"(d[60]), "+f"(d[61]), "+f"(d[62]), "+f"(d[63])
    : "r"(a0), "r"(a1), "r"(a2), "r"(a3), "l"(descB), "r"(scaleD));
}
__device__ __forceinline__ void wgmma_rs_n128_ta0_tb1(float (&d)[64], uint32_t a0, uint32_t a1, uint32_t a2, uint32_t a3, uint64_t descB, int scaleD) {
  asm volatile("{\n.reg .pred p;\nsetp.ne.b32 p, %69, 0;\n"
    "wgmma.mma_async.sync.aligned.m64n128k16.f32.bf16.bf16 "
    "{%0, %1, %2, %3, %4, %5, %6, %7, %8, %9, %10, %11, %12, %13, %14, %15, %16, %17, %18, %19, %20, %21, %22, %23, %24, %25, %26, %27, %28, %29, %30, %31, %32, %33, %34, %35, %36, %37, %38, %39, %40, %41, %42, %43, %44, %45, %46, %47, %48, %49, %50, %51, %52, %53, %54, %55, %56, %57, %58, %59, %60, %61, %62, %63}, "
    "{%64, %65, %66, %67}, %68, p, 1, 1, 1;\n}\n"
    : "+f"(d[0]), "+f"(d[1]), "+f"(d[2]), "+f"(d[3]), "+f"(d[4]), "+f"(d[5]), "+f"(d[6]), "+f"(d[7]), "+f"(d[8]), "+f"(d[9]), "+f"(d[10]), "+f"(d[11]), "+f"(d[12]), "+f"(d[13]), "+f"(d[14]), "+f"(d[15]), "+f"(d[16]), "+f"(d[17]), "+f"(d[18]), "+f"(d[19]), "+f"(d[20]), "+f"(d[21]), "+f"(d[22]), "+f"(d[23]), "+f"(d[24]), "+f"(d[25]), "+f"(d[26]), "+f"(d[27]), "+f"(d[28]), "+f"(d[29]), "+f"(d[30]), "+f"(d[31]), "+f"(d[32]), "+f"(d[33]), "+f"(d[34]), "+f"(d[35]), "+f"(d[36]), "+f"(d[37]), "+f"(d[38]), "+f"(d[39]), "+f"(d[40]), "+f"(d[41]), "+f"(d[42]), "+f"(d[43]), "+f"(d[44]), "+f"(d[45]), "+f"(d[46]), "+f"(d[47]), "+f"(d[48]), "+f"(d[49]), "+f"(d[50]), "+f"(d[51]), "+f"(d[52]), "+f"(d[53]), "+f"(d[54]), "+f"(d[55]), "+f"(d[56]), "+f"(d[57]), "+f"(d[58]), "+f"(d[59]), "+f"(d[60]), "+f"(d[61]), "+f"(d[62]), "+f"(d[63])
    : "r"(a0), "r"(a1), "r"(a2), "r"(a3), "l"(descB), "r"(scaleD));
}
__device__ __forceinline__ void wgmma_rs_n64_ta0_tb1(float (&d)[32], uint32_t a0, uint32_t a1, uint32_t a2, uint32_t a3, uint64_t descB, int scaleD) {
  asm volatile("{\n.reg .pred p;\nsetp.ne.b32 p, %37, 0;\n"
    "wgmma.mma_async.sync.aligned.m64n64k16.f32.bf16.bf16 "
    "{%0, %1, %2, %3, %4, %5, %6, %7, %8, %9, %10, %11, %12, %13, %14, %15, %16, %17, %18, %19, %20, %21, %22, %23, %24, %25, %26, %27, %28, %29, %30, %31}, "
    "{%32, %33, %34, %35}, %36, p, 1, 1, 1;\n}\n"
    : "+f"(d[0]), "+f"(d[1]), "+f"(d[2]), "+f"(d[3]), "+f"(d[4]), "+f"(d[5]), "+f"(d[6]), "+f"(d[7]), "+f"(d[8]), "+f"(d[9]), "+f"(d[10]), "+f"(d[11]), "+f"(d[12]), "+f"(d[13]), "+f"(d[14]), "+f"(d[15]), "+f"(d[16]), "+f"(d[17]), "+f"(d[18]), "+f"(d[19]), "+f"(d[20]), "+f"(d[21]), "+f"(d[22]), "+f"(d[23]), "+f"(d[24]), "+f"(d[25]), "+f"(d[26]), "+f"(d[27]), "+f"(d[28]), "+f"(d[29]), "+f"(d[30]), "+f"(d[31])
    : "r"(a0), "r"(a1), "r"(a2), "r"(a3), "l"(descB), "r"(scaleD));
}
__device__ __forceinline__ void wgmma_ss_n128_ta1_tb0(float (&d)[64], uint64_t descA, uint64_t descB, int scaleD) {
  asm volatile("{\n.reg .pred p;\nsetp.ne.b32 p, %66, 0;\n"
    "wgmma.mma_async.sync.aligned.m64n128k16.f32.bf16.bf16 "
    "{%0, %1, %2, %3, %4, %5, %6, %7, %8, %9, %10, %11, %12, %13, %14, %15, %16, %17, %18, %19, %20, %21, %22, %23, %24, %25, %26, %27, %28, %29, %30, %31, %32, %33, %34, %35, %36, %37, %38, %39, %40, %41, %42, %43, %44, %45, %46, %47, %48, %49, %50, %51, %52, %53, %54, %55, %56, %57, %58, %59, %60, %61, %62, %63}, "
    "%64, %65, p, 1, 1, 1, 0;\n}\n"
    : "+f"(d[0]), "+f"(d[1]), "+f"(d[2]), "+f"(d[3]), "+f"(d[4]), "+f"(d[5]), "+f"(d[6]), "+f"(d[7]), "+f"(d[8]), "+f"(d[9]), "+f"(d[10]), "+f"(d[11]), "+f"(d[12]), "+f"(d[13]), "+f"(d[14]), "+f"(d[15]), "+f"(d[16]), "+f"(d[17]), "+f"(d[18]), "+f"(d[19]), "+f"(d[20]), "+f"(d[21]), "+f"(d[22]), "+f"(d[23]), "+f"(d[24]), "+f"(d[25]), "+f"(d[26]), "+f"(d[27]), "+f"(d[28]), "+f"(d[29]), "+f"(d[30]), "+f"(d[31]), "+f"(d[32]), "+f"(d[33]), "+f"(d[34]), "+f"(d[35]), "+f"(d[36]), "+f"(d[37]), "+f"(d[38]), "+f"(d[39]), "+f"(d[40]), "+f"(d[41]), "+f"(d[42]), "+f"(d[43]), "+f"(d[44]), "+f"(d[45]), "+f"(d[46]), "+f"(d[47]), "+f"(d[48]), "+f"(d[49]), "+f"(d[50]), "+f"(d[51]), "+f"(d[52]), "+f"(d[53]), "+f"(d[54]), "+f"(d[55]), "+f"(d[56]), "+f"(d[57]), "+f"(d[58]), "+f"(d[59]), "+f"(d[60]), "+f"(d[61]), "+f"(d[62]), "+f"(d[63])
    : "l"(descA), "l"(descB), "r"(scaleD));
}
__device__ __forceinline__ void wgmma_ss_n160_ta0_tb1(float (&d)[80], uint64_t descA, uint64_t descB, int scaleD) {
  asm volatile("{\n.reg .pred p;\nsetp.ne.b32 p, %82, 0;\n"
    "wgmma.mma_async.sync.aligned.m64n160k16.f32.bf16.bf16 "
    "{%0, %1, %2, %3, %4, %5, %6, %7, %8, %9, %10, %11, %12, %13, %14, %15, %16, %17, %18, %19, %20, %21, %22, %23, %24, %25, %26, %27, %28, %29, %30, %31, %32, %33, %34, %35, %36, %37, %38, %39, %40, %41, %42, %43, %44, %45, %46, %47, %48, %49, %50, %51, %52, %53, %54, %55, %56, %57, %58, %59, %60, %61, %62, %63, %64, %65, %66, %67, %68, %69, %70, %71, %72, %73, %74, %75, %76, %77, %78, %79}, "
    "%80, %81, p, 1, 1, 0, 1;\n}\n"
    : "+f"(d[0]), "+f"(d[1]), "+f"(d[2]), "+f"(d[3]), "+f"(d[4]), "+f"(d[5]), "+f"(d[6]), "+f"(d[7]), "+f"(d[8]), "+f"(d[9]), "+f"(d[10]), "+f"(d[11]), "+f"(d[12]), "+f"(d[13]), "+f"(d[14]), "+f"(d[15]), "+f"(d[16]), "+f"(d[17]), "+f"(d[18]), "+f"(d[19]), "+f"(d[20]), "+f"(d[21]), "+f"(d[22]), "+f"(d[23]), "+f"(d[24]), "+f"(d[25]), "+f"(d[26]), "+f"(d[27]), "+f"(d[28]), "+f"(d[29]), "+f"(d[30]), "+f"(d[31]), "+f"(d[32]), "+f"(d[33]), "+f"(d[34]), "+f"(d[35]), "+f"(d[36]), "+f"(d[37]), "+f"(d[38]), "+f"(d[39]), "+f"(d[40]), "+f"(d[41]), "+f"(d[42]), "+f"(d[43]), "+f"(d[44]), "+f"(d[45]), "+f"(d[46]), "+f"(d[47]), "+f"(d[48]), "+f"(d[49]), "+f"(d[50]), "+f"(d[51]), "+f"(d[52]), "+f"(d[53]), "+f"(d[54]), "+f"(d[55]), "+f"(d[56]), "+f"(d[57]), "+f"(d[58]), "+f"(d[59]), "+f"(d[60]), "+f"(d[61]), "+f"(d[62]), "+f"(d[63]), "+f"(d[64]), "+f"(d[65]), "+f"(d[66]), "+f"(d[67]), "+f"(d[68]), "+f"(d[69]), "+f"(d[70]), "+f"(d[71]), "+f"(d[72]), "+f"(d[73]), "+f"(d[74]), "+f"(d[75]), "+f"(d[76]), "+f"(d[77]), "+f"(d[78]), "+f"(d[79])
    : "l"(descA), "l"(descB), "r"(scaleD));
}

#define PROF_DECL
#define PROF_EV(tag)
#define PROF_GT(tag)

struct Cur {
    uint32_t slot, ph;
    __device__ __forceinline__ void adv() { if (++slot == NSLOT) { slot = 0; ph ^= 1; } }
};
__device__ __forceinline__ Cur cur_at(int e) { Cur c; c.slot = e % NSLOT; c.ph = (e / NSLOT) & 1; return c; }

__device__ __forceinline__ int blk_of(int a, int r, int rot) {
    uint32_t tab = rot ? (a ? 0x2156u : 0x3047u) : (a ? 0x1256u : 0x0347u);
    return (tab >> (4 * r)) & 7;
}

__device__ __forceinline__ int op_head(int i, int kap, int u) { return 16 * kap + 4 * ((i >> 1) & 3) + 2 * ((u < 2 ? 1 : 0) ^ (i >> 3)) + (i & 1); }

constexpr float SM_SCALE = 0.08838834764831845f * 1.4426950408889634f;

struct Ctx {
    uint32_t ring, misc;
    uint32_t rel;
    int w, warp, lane;
};
__device__ __forceinline__ void release(const Ctx& c, uint32_t off, uint32_t cnt) {
    if (c.lane < 2) mbar_arrive_cluster(c.rel + off, cnt);
}
__device__ __forceinline__ void signal_event(const Ctx& c, int ev) {
    __syncwarp();
    if (c.lane == 0) mbar_arrive(c.misc + BAR_EV + (c.w * 9 + ev) * 8);
}
template <int NK, int OFF, int N>
__device__ __forceinline__ uint32_t load_afrag(uint32_t (&a)[N], uint32_t base, const Ctx& c) {
    int r = c.lane & 7, mat = c.lane >> 3;
    uint32_t addr = base + (8 * (mat >> 1) + r) * 128 + (((2 * c.warp + (mat & 1)) ^ r) << 4);
#pragma unroll
    for (int k = 0; k < NK; k++) ldsm4t(a[OFF + 4 * k], a[OFF + 4 * k + 1], a[OFF + 4 * k + 2], a[OFF + 4 * k + 3], addr + k * 2048);
    uint32_t dep = 0;
#pragma unroll
    for (int k = 0; k < NK; k++) dep |= a[OFF + 4 * k];
    return dep & blockIdx.y;
}
__device__ __forceinline__ void store_proj(const float (&acc)[64], unsigned char* dst  , const Ctx& c, uint64_t pol) {
    int g = c.lane >> 2, t = c.lane & 3;
#pragma unroll
    for (int i = 0; i < 2; i++) {
        int row = perm32(64 * c.w + 16 * c.warp + 8 * i + g);
        unsigned char* p = dst + row * 128;
#pragma unroll
        for (int q = 0; q < 4; q++) {
            int chunk = (4 * (q & 1) + t) ^ (row & 7);
            stg128_hint(p + (q >> 1) * 16384 + chunk * 16,
                   pack_bf16(acc[16 * q + 2 * i], acc[16 * q + 2 * i + 1]), pack_bf16(acc[16 * q + 4 + 2 * i], acc[16 * q + 4 + 2 * i + 1]),
                   pack_bf16(acc[16 * q + 8 + 2 * i], acc[16 * q + 8 + 2 * i + 1]), pack_bf16(acc[16 * q + 12 + 2 * i], acc[16 * q + 12 + 2 * i + 1]), pol);
        }
    }
}

constexpr float SAFE_EXP = 40.0f, SAFE_SUM = 1099511627776.0f;
template <int NJ>
__device__ __forceinline__ void row_max(const float (&s)[4 * NJ], float (&mx)[2]) {
#pragma unroll
    for (int i = 0; i < 2; i++) {
        float a = fmaxf(s[2 * i], s[2 * i + 1]), b = fmaxf(s[4 + 2 * i], s[4 + 2 * i + 1]);
#pragma unroll
        for (int j = 2; j < NJ; j += 2) {
            a = fmaxf(a, fmaxf(s[4 * j + 2 * i], s[4 * j + 2 * i + 1]));
            b = fmaxf(b, fmaxf(s[4 * j + 4 + 2 * i], s[4 * j + 4 + 2 * i + 1]));
        }
        a = fmaxf(a, b);
        a = fmaxf(a, __shfl_xor_sync(0xffffffffu, a, 1));
        mx[i] = fmaxf(a, __shfl_xor_sync(0xffffffffu, a, 2));
    }
}
template <int NJ, bool SHIFT>
__device__ __forceinline__ void exp_sum(float (&s)[4 * NJ], const float (&m)[2], float& l0, float& l1) {
#pragma unroll
    for (int j = 0; j < NJ; j++) {
#pragma unroll
        for (int e = 0; e < 4; e++) s[4 * j + e] = ex2(SHIFT ? s[4 * j + e] - m[e >> 1] : s[4 * j + e]);
        l0 += s[4 * j + 0]; l1 += s[4 * j + 2]; l0 += s[4 * j + 1]; l1 += s[4 * j + 3];
    }
}
template <int NJ>
__device__ __forceinline__ bool softmax_first(float (&s)[4 * NJ], float (&m)[2], float (&l)[2]) {
    row_max<NJ>(s, m);
    bool gen = __any_sync(0xffffffffu, !(fabsf(m[0]) <= SAFE_EXP && fabsf(m[1]) <= SAFE_EXP));
    if (!gen) m[0] = m[1] = 0.f;
    l[0] = l[1] = 0.f;
    exp_sum<NJ, true>(s, m, l[0], l[1]);
    return gen;
}
__device__ __forceinline__ void recompute_scores(float (&s)[64], const uint32_t (&q)[32], uint32_t kaddr, const Ctx& c) {
    const int r = c.lane & 7, mat = c.lane >> 3;
    const uint32_t a0 = kaddr + (8 * (mat & 1) + r) * 128 + (((mat >> 1) ^ r) << 4);
#pragma unroll
    for (int i = 0; i < 64; i++) s[i] = 0.f;
#pragma unroll
    for (int jp = 0; jp < 8; jp++) {
#pragma unroll
        for (int k = 0; k < 8; k++) {
            asm volatile(
                "{\n.reg .b32 b0, b1, b2, b3;\n"
                "ldmatrix.sync.aligned.m8n8.x4.trans.shared.b16 {b0,b1,b2,b3}, [%12];\n"
                "mma.sync.aligned.m16n8k16.row.col.f32.bf16.bf16.f32 {%0,%1,%2,%3}, {%8,%9,%10,%11}, {b0,b1}, {%0,%1,%2,%3};\n"
                "mma.sync.aligned.m16n8k16.row.col.f32.bf16.bf16.f32 {%4,%5,%6,%7}, {%8,%9,%10,%11}, {b2,b3}, {%4,%5,%6,%7};\n}\n"
                : "+f"(s[8 * jp]), "+f"(s[8 * jp + 1]), "+f"(s[8 * jp + 2]), "+f"(s[8 * jp + 3]),
                  "+f"(s[8 * jp + 4]), "+f"(s[8 * jp + 5]), "+f"(s[8 * jp + 6]), "+f"(s[8 * jp + 7])
                : "r"(q[4 * k]), "r"(q[4 * k + 1]), "r"(q[4 * k + 2]), "r"(q[4 * k + 3]),
                  "r"((a0 ^ ((jp & 3) << 5)) + (jp >> 2) * 16384 + k * 2048) : "memory");
        }
    }
}
template <int J0>
__device__ __forceinline__ void mask_diag(float (&s)[4 * J0 + 32], const Ctx& c) {
    int g = c.lane >> 2, t = c.lane & 3;
#pragma unroll
    for (int i = 0; i < 2; i++) {
        int lim = perm32(16 * c.warp + 8 * i + g) - 8 * t;
#pragma unroll
        for (int j = 0; j < 8; j++)
#pragma unroll
            for (int e = 0; e < 2; e++)
                if (32 * (j >> 2) + 2 * (j & 3) + e > lim) s[4 * (J0 + j) + 2 * i + e] = -INFINITY;
    }
}
__device__ __forceinline__ void issue_pv(float (&o)[64], const uint32_t (&p)[32], uint32_t vaddr, int acc, bool half) {
    uint64_t d = mkdesc(vaddr, 16, 1024, 1);
    if (half) {
        wg_fence();
#pragma unroll
        for (int k = 0; k < 4; k++) wgmma_rs_n128_ta0_tb0(o, p[4 * k], p[4 * k + 1], p[4 * k + 2], p[4 * k + 3], d + 2 * k, k != 0);
        wg_commit();
    } else {
        wg_fence();
#pragma unroll
        for (int k = 0; k < 8; k++)
            wgmma_rs_n128_ta0_tb0(o, p[4 * k], p[4 * k + 1], p[4 * k + 2], p[4 * k + 3], d + (k >> 2) * 1024 + 2 * (k & 3), k ? 1 : acc);
        wg_commit();
    }
}
__device__ __forceinline__ void issue_qk(float (&s)[64], const uint32_t (&q)[32], uint32_t kaddr) {
    uint64_t d = mkdesc(kaddr, 16384, 1024, 1);
    wg_fence();
#pragma unroll
    for (int k = 0; k < 8; k++) wgmma_rs_n128_ta0_tb1(s, q[4 * k], q[4 * k + 1], q[4 * k + 2], q[4 * k + 3], d + 128 * k, k != 0);
    wg_commit();
}
__device__ __forceinline__ void issue_qk_half(float (&s32)[32], const uint32_t (&q)[32], uint32_t kaddr) {
    uint64_t d = mkdesc(kaddr, 16384, 1024, 1);
    wg_fence();
#pragma unroll
    for (int k = 0; k < 8; k++) wgmma_rs_n64_ta0_tb1(s32, q[4 * k], q[4 * k + 1], q[4 * k + 2], q[4 * k + 3], d + 128 * k, k != 0);
    wg_commit();
}
__device__ __forceinline__ void store_ctx(const float (&o)[64], const float (&l)[2], unsigned char* dst, const Ctx& c) {
    int g = c.lane >> 2, t = c.lane & 3;
#pragma unroll
    for (int i = 0; i < 2; i++) {
        float sum = l[i];
        sum += __shfl_xor_sync(0xffffffffu, sum, 1);
        sum += __shfl_xor_sync(0xffffffffu, sum, 2);
        float inv = rcp_fast(sum);
        int row = perm32(16 * c.warp + 8 * i + g);
        unsigned char* p = dst + row * 128;
#pragma unroll
        for (int q = 0; q < 4; q++) {
            int chunk = (4 * (q & 1) + t) ^ (row & 7);
            stg128(p + (q >> 1) * 8192 + chunk * 16,
                   pack_bf16(o[16 * q + 2 * i] * inv, o[16 * q + 2 * i + 1] * inv), pack_bf16(o[16 * q + 4 + 2 * i] * inv, o[16 * q + 4 + 2 * i + 1] * inv),
                   pack_bf16(o[16 * q + 8 + 2 * i] * inv, o[16 * q + 8 + 2 * i + 1] * inv), pack_bf16(o[16 * q + 12 + 2 * i] * inv, o[16 * q + 12 + 2 * i + 1] * inv));
        }
    }
}

__device__ __forceinline__ const unsigned char* xn_addr(int row, int col) {
    return g_xn + ((row >> 7) * 10 + (col >> 6)) * 16384 + (row & 127) * 128 + ((((col & 63) >> 3) ^ (row & 7)) << 4);
}
__device__ __forceinline__ void mma16816(float (&d)[4], uint32_t a0, uint32_t a1, uint32_t a2, uint32_t a3, uint32_t b0, uint32_t b1) {
    asm volatile("mma.sync.aligned.m16n8k16.row.col.f32.bf16.bf16.f32 {%0,%1,%2,%3}, {%4,%5,%6,%7}, {%8,%9}, {%0,%1,%2,%3};"
                 : "+f"(d[0]), "+f"(d[1]), "+f"(d[2]), "+f"(d[3]) : "r"(a0), "r"(a1), "r"(a2), "r"(a3), "r"(b0), "r"(b1));
}
__device__ __forceinline__ uint32_t lds32(uint32_t addr) { uint32_t v; asm volatile("ld.shared.u32 %0, [%1];" : "=r"(v) : "r"(addr)); return v; }

__device__ __forceinline__ void aux_cta(const Params& P, unsigned char* sm, int a) {
    constexpr int STG = 65536, XS = 3 * STG, HS = XS + 8 * 1296, MI = HS + 8 * 880;
    const int tid = threadIdx.x, warp = tid >> 5, lane = tid & 31;
    const uint32_t sb = smem_u32(sm);
    const uint32_t full = sb + MI, empty = sb + MI + 32;
    int* s_sel = reinterpret_cast<int*>(sm + MI + 64);
    float* s_r = reinterpret_cast<float*>(sm + MI + 96);
    volatile unsigned* s_misc = reinterpret_cast<volatile unsigned*>(sm + MI + 128);
    PROF_DECL
    PROF_GT(0);
    if (tid == 0) {
        for (int i = 0; i < 3; i++) { mbar_init(full + 8 * i, 1); mbar_init(empty + 8 * i, 10); }
        asm volatile("fence.mbarrier_init.release.cluster;" ::: "memory");
    }
    __syncthreads();
    if (warp == 11) {
        int st = 0; uint32_t ph = 0;
        for (int s = 0; s < 29; s++) {
            mbar_wait(empty + 8 * st, ph ^ 1);
            if (lane == 0) mbar_expect_tx(full + 8 * st, s < 20 ? 55296 : 61440);
            __syncwarp();
            uint32_t dst = sb + st * STG;
            if (s < 20) {
                size_t off = (size_t)(32 * s + lane) * FF + a * 432;
                bulk_load_hint(dst + lane * 880, P.wg + off, 864, full + 8 * st, policy_stream());
                bulk_load_hint(dst + 28160 + lane * 880, P.wu + off, 864, full + 8 * st, policy_stream());
            } else {
                const __nv_bfloat16* src = P.wd + (size_t)(a * 432 + (s - 20) * 48) * DM;
                bulk_load_hint(dst + lane * 1296, src + lane * DM, 1280, full + 8 * st, policy_stream());
                if (lane < 16) bulk_load_hint(dst + (32 + lane) * 1296, src + (32 + lane) * DM, 1280, full + 8 * st, policy_stream());
            }
            if (++st == 3) { st = 0; ph ^= 1; }
        }
        return;
    }
    if (warp == 10) return;
    if (warp == 0) {
        if (lane == 0) {
            unsigned e = *reinterpret_cast<volatile unsigned*>(&g_epoch);
            s_misc[0] = e;
            flag_wait(flag_ptr(FL_LN), (e + 1) * 128u);
        }
        __syncwarp();
        PROF_GT(50);
        uint32_t key[64];
#pragma unroll
        for (int i = 0; i < 64; i++) {
            int idx = i * 32 + lane;
            uint32_t b = __float_as_uint(__ldcg(g_router + idx)) >> 16;
            b = (b & 0x8000u) ? (~b & 0xffffu) : (b | 0x8000u);
            key[i] = (b << 16) | (uint32_t)(0xffff - idx);
        }
        uint32_t bound = 0xffffffffu;
#pragma unroll 1
        for (int r = 0; r < TOPC; r++) {
            uint32_t best = 0;
#pragma unroll
            for (int i = 0; i < 64; i++) best = max(best, key[i] <= bound ? key[i] : 0u);
            best = __reduce_max_sync(0xffffffffu, best);
            bound = best - 1;
            if (lane == 0) {
                uint32_t b = best >> 16;
                b = (b & 0x8000u) ? (b & 0x7fffu) : (~b & 0xffffu);
                s_sel[r] = 0xffff - (int)(best & 0xffffu);
                s_r[r] = __uint_as_float(b << 16);
            }
        }
    }
    bar_sync(1, 320);
    const unsigned ep = s_misc[0];
    for (int i = tid; i < TOPC * 80; i += 320) {
        int tk = i / 80, ch = i % 80;
        *reinterpret_cast<uint4*>(sm + XS + tk * 1296 + ch * 16) = __ldcg(reinterpret_cast<const uint4*>(xn_addr(s_sel[tk], ch * 8)));
    }
    bar_sync(1, 320);
    PROF_GT(51);
    const int g = lane >> 2, t = lane & 3;
    const int lrow = 8 * (lane >> 4) + (lane & 7), lcol = ((lane >> 3) & 1) * 16;
    int st = 0; uint32_t ph = 0;
    {
        float ga[3][4], ua[3][4];
#pragma unroll
        for (int i = 0; i < 3; i++)
#pragma unroll
            for (int e = 0; e < 4; e++) { ga[i][e] = 0.f; ua[i][e] = 0.f; }
#pragma unroll 1
        for (int s = 0; s < 20; s++) {
            mbar_wait(full + 8 * st, ph);
            if (warp < 9) {
#pragma unroll
                for (int kk = 0; kk < 2; kk++) {
                    uint32_t xb = sb + XS + g * 1296 + (32 * s + 16 * kk + 2 * t) * 2;
                    uint32_t b0 = lds32(xb), b1 = lds32(xb + 16);
                    uint32_t wa = sb + st * STG + (16 * kk + lrow) * 880 + lcol + warp * 96;
#pragma unroll
                    for (int i = 0; i < 3; i++) {
                        uint32_t a0, a1, a2, a3;
                        ldsm4t(a0, a1, a2, a3, wa + i * 32);
                        mma16816(ga[i], a0, a1, a2, a3, b0, b1);
                        ldsm4t(a0, a1, a2, a3, wa + 28160 + i * 32);
                        mma16816(ua[i], a0, a1, a2, a3, b0, b1);
                    }
                }
            }
            asm volatile("fence.proxy.async.shared::cta;" ::: "memory");
            __syncwarp();
            if (lane == 0) mbar_arrive(empty + 8 * st);
            if (++st == 3) { st = 0; ph ^= 1; }
        }
        if (warp < 9) {
#pragma unroll
            for (int i = 0; i < 3; i++)
#pragma unroll
                for (int e = 0; e < 4; e++) {
                    float gv = bf_round(ga[i][e]), uv = bf_round(ua[i][e]);
                    float sg = bf_round(gv / (1.0f + __expf(-gv)));
                    int f = warp * 48 + i * 16 + g + 8 * (e >> 1), tk = 2 * t + (e & 1);
                    *reinterpret_cast<__nv_bfloat16*>(sm + HS + tk * 880 + f * 2) = __float2bfloat16_rn(sg * uv);
                }
        }
    }
    bar_sync(1, 320);
    PROF_GT(52);
    {
        float ya[4][4];
#pragma unroll
        for (int i = 0; i < 4; i++)
#pragma unroll
            for (int e = 0; e < 4; e++) ya[i][e] = 0.f;
#pragma unroll 1
        for (int s = 0; s < 9; s++) {
            mbar_wait(full + 8 * st, ph);
#pragma unroll
            for (int kk = 0; kk < 3; kk++) {
                uint32_t hb = sb + HS + g * 880 + (48 * s + 16 * kk + 2 * t) * 2;
                uint32_t b0 = lds32(hb), b1 = lds32(hb + 16);
                uint32_t wa = sb + st * STG + (16 * kk + lrow) * 1296 + lcol + warp * 128;
#pragma unroll
                for (int i = 0; i < 4; i++) {
                    uint32_t a0, a1, a2, a3;
                    ldsm4t(a0, a1, a2, a3, wa + i * 32);
                    mma16816(ya[i], a0, a1, a2, a3, b0, b1);
                }
            }
            asm volatile("fence.proxy.async.shared::cta;" ::: "memory");
            __syncwarp();
            if (lane == 0) mbar_arrive(empty + 8 * st);
            if (++st == 3) { st = 0; ph ^= 1; }
        }
#pragma unroll
        for (int i = 0; i < 4; i++)
#pragma unroll
            for (int e = 0; e < 4; e += 2)
                *reinterpret_cast<float2*>(g_moe_part + (a * DM + warp * 64 + i * 16 + g + 4 * e) * 8 + 2 * t) = make_float2(ya[i][e], ya[i][e + 1]);
    }
    bar_sync(1, 320);
    if (tid == 0) {
        __threadfence();
        unsigned old = atomicAdd(flag_ptr(FL_MOE_CNT), 1u);
        s_misc[1] = (old == ep * 4u + 3u);
        __threadfence();
    }
    bar_sync(1, 320);
    PROF_GT(53);
    if (s_misc[1]) {
#pragma unroll
        for (int it = 0; it < 16; it++) {
            const int i = tid + it * 320;
            int col = i >> 3, tk = i & 7;
            float y = bf_round(__ldcg(g_moe_part + i) + __ldcg(g_moe_part + DM * 8 + i) + __ldcg(g_moe_part + 2 * DM * 8 + i) + __ldcg(g_moe_part + 3 * DM * 8 + i));
            float sg = bf_round(1.0f / (1.0f + __expf(-s_r[tk])));
            float upd = bf_round(y * sg);
            float xn = __bfloat162float(*reinterpret_cast<const __nv_bfloat16*>(sm + XS + tk * 1296 + col * 2));
            g_brow[tk * DM + col] = __float2bfloat16_rn(xn + upd);
        }
        if (tid < TOPC) g_sel[tid] = s_sel[tid];
        bar_sync(1, 320);
        if (tid == 0) {
            flag_signal(flag_ptr(FL_MOE_DONE));
            *reinterpret_cast<volatile unsigned*>(&g_epoch) = ep + 1;
        }
        PROF_GT(54);
    }
}

__device__ __forceinline__ void layernorm4(const Params& P, int row0, int lane) {
    const int hl = lane & 15;
    uint4 v[2][5], wv[5];
#pragma unroll
    for (int b = 0; b < 2; b++)
#pragma unroll
        for (int i = 0; i < 5; i++)
            v[b][i] = ldg128_stream(P.x + (size_t)(row0 + 2 * b + (lane >> 4)) * DM + 128 * i + 8 * hl);
#pragma unroll
    for (int i = 0; i < 5; i++) wv[i] = __ldg(reinterpret_cast<const uint4*>(P.wr + 128 * i + 8 * hl));
#pragma unroll
    for (int b = 0; b < 2; b++) {
        const int row = row0 + 2 * b + (lane >> 4);
        float f[40];
#pragma unroll
        for (int i = 0; i < 5; i++) {
            f[8 * i + 0] = bf_lo(v[b][i].x); f[8 * i + 1] = bf_hi(v[b][i].x); f[8 * i + 2] = bf_lo(v[b][i].y); f[8 * i + 3] = bf_hi(v[b][i].y);
            f[8 * i + 4] = bf_lo(v[b][i].z); f[8 * i + 5] = bf_hi(v[b][i].z); f[8 * i + 6] = bf_lo(v[b][i].w); f[8 * i + 7] = bf_hi(v[b][i].w);
        }
        float s0 = 0.f, s1 = 0.f;
#pragma unroll
        for (int i = 0; i < 40; i += 2) { s0 += f[i]; s1 += f[i + 1]; }
        s0 += s1;
#pragma unroll
        for (int o = 8; o > 0; o >>= 1) s0 += __shfl_xor_sync(0xffffffffu, s0, o);
        const float mean = s0 * (1.0f / DM);
        float q0 = 0.f, q1 = 0.f;
#pragma unroll
        for (int i = 0; i < 40; i += 2) { float d0 = f[i] - mean, d1 = f[i + 1] - mean; q0 = fmaf(d0, d0, q0); q1 = fmaf(d1, d1, q1); }
        q0 += q1;
#pragma unroll
        for (int o = 8; o > 0; o >>= 1) q0 += __shfl_xor_sync(0xffffffffu, q0, o);
        const float mb = bf_round(mean);
        const float inv = rcp_fast(bf_round(sqrt_fast(bf_round(bf_round(q0 * (1.0f / DM)) + 1e-5f))));
        float dot = 0.f;
        unsigned char* xp = g_xn + ((row >> 7) * 10 + (hl >> 3)) * 16384 + (row & 127) * 128 + (((hl & 7) ^ (row & 7)) << 4);
#pragma unroll
        for (int i = 0; i < 5; i++) {
            uint32_t o[4], ww[4] = {wv[i].x, wv[i].y, wv[i].z, wv[i].w};
#pragma unroll
            for (int e = 0; e < 4; e++) {
                uint32_t d = pack_bf16(f[8 * i + 2 * e] - mb, f[8 * i + 2 * e + 1] - mb);
                o[e] = pack_bf16(bf_lo(d) * inv, bf_hi(d) * inv);
                dot = fmaf(bf_lo(o[e]), bf_lo(ww[e]), dot);
                dot = fmaf(bf_hi(o[e]), bf_hi(ww[e]), dot);
            }
            stg128(xp + i * 32768, o[0], o[1], o[2], o[3]);
        }
#pragma unroll
        for (int o = 8; o > 0; o >>= 1) dot += __shfl_xor_sync(0xffffffffu, dot, o);
        if (hl == 0) g_router[row] = bf_round(dot);
    }
}

__global__ void __cluster_dims__(2, 1, 1) __launch_bounds__(384, 1)
fused_kernel(const __grid_constant__ CUtensorMap tmC, const __grid_constant__ CUtensorMap tmWk, const __grid_constant__ CUtensorMap tmWv,
             const __grid_constant__ CUtensorMap tmWq, const __grid_constant__ CUtensorMap tmWo, const Params P) {
    extern __shared__ unsigned char smem_raw[];
    const uint32_t ring = (smem_u32(smem_raw) + 1023u) & ~1023u;
    const uint32_t misc = ring + RING_BYTES;
    const int tid = threadIdx.x;
    const int mc = blockIdx.x >> 1, rank = blockIdx.x & 1;
    if (mc >= 64) { aux_cta(P, smem_raw + (ring - smem_u32(smem_raw)), blockIdx.x - 128); return; }
    PROF_DECL
    PROF_GT(0); PROF_EV(1);

    if (tid == 0) {
        for (int i = 0; i < NSLOT; i++) { mbar_init(misc + BAR_FULL + 8 * i, 1); mbar_init(misc + BAR_EMPTY + 8 * i, 16); }
        for (int i = 0; i < NST3; i++) { mbar_init(misc + BAR_FULL3 + 8 * i, 1); mbar_init(misc + BAR_EMPTY3 + 8 * i, 16); }
        for (int i = 0; i < 18; i++) mbar_init(misc + BAR_EV + 8 * i, 4);
        for (int i = 0; i < 19; i++) mbar_init(misc + BAR_DEP + 8 * i, 1);
        for (int i = 0; i < 8; i++) mbar_init(misc + BAR_W + 8 * i, 1);
        mbar_init(misc + BAR_LN, 4); mbar_init(misc + BAR_PF, 1); mbar_init(misc + BAR_SEL, 1);
        asm volatile("fence.mbarrier_init.release.cluster;" ::: "memory");
        const CUtensorMap* tw = rank ? &tmWv : &tmWk;
        for (int e = 0; e < 2; e++) {
            mbar_expect_tx(misc + BAR_W + 8 * e, SLOT_BYTES);
            tma2d(ring + e * SLOT_BYTES, tw, (mc >> 1) * 128, e * 256, misc + BAR_W + 8 * e);
            tma2d(ring + e * SLOT_BYTES + 16384, tw, (mc >> 1) * 128, e * 256 + 128, misc + BAR_W + 8 * e);
            mbar_arrive(misc + BAR_FULL + 8 * e);
        }
    }
    if (tid == 32) asm volatile("prefetch.tensormap [%0];" ::"l"(&tmC) : "memory");
    __syncthreads();
    asm volatile("barrier.cluster.arrive.relaxed.aligned;\nbarrier.cluster.wait.aligned;" ::: "memory");

    const int h = mc >> 1, a = mc & 1;
    const int rot = (mc >> 2) & 1;
    const int hq = (mc >> 2) * 2 + rank;
    const int kq = mc & 3;
    const int u3 = mc >> 3, s3 = (mc >> 1) & 3, kap = mc & 1;
    const int wg = __shfl_sync(0xffffffffu, tid >> 7, 0);

    if (wg == 0) {
        asm volatile("setmaxnreg.dec.sync.aligned.u32 24;");
        const int warp = __shfl_sync(0xffffffffu, tid >> 5, 0), lane = tid & 31;
        if (warp == 0) {
            const bool lead = elect_one();
            Cur c; c.slot = 2; c.ph = 0;
            uint32_t dst, fb;
            auto acquire = [&]() {
                mbar_wait(misc + BAR_EMPTY + 8 * c.slot, c.ph ^ 1);
                fb = misc + BAR_FULL + 8 * c.slot; dst = ring + c.slot * SLOT_BYTES;
                if (lead) mbar_expect_tx(fb, SLOT_BYTES);
                c.adv();
            };
            auto load_w = [&](int id, const CUtensorMap* tm, int col, int row) {
                mbar_wait(misc + BAR_EMPTY + 8 * c.slot, c.ph ^ 1);
                fb = misc + BAR_W + 8 * id; dst = ring + c.slot * SLOT_BYTES;
                if (lead) {
                    mbar_expect_tx(fb, SLOT_BYTES);
                    tma2d(dst, tm, col, row, fb); tma2d(dst + 16384, tm, col, row + 128, fb);
                    mbar_arrive(misc + BAR_FULL + 8 * c.slot);
                }
                c.adv();
            };
            auto load_half = [&](const unsigned char* src) {
                acquire();
                if (lead) bulk_load_mc(dst + rank * 16384, src, 16384, fb);
            };
            auto dep_wait = [&](int d) { mbar_wait(misc + BAR_DEP + 8 * d, 0); fence_async_global(); };
            const CUtensorMap* tw = rank ? &tmWv : &tmWk;
#pragma unroll 1
            for (int i = 0; i < 32; i++) {
                acquire();
                if (lead) tma2d_mc(dst + rank * 16384, &tmC, (i & 3) * 128 + rank * 64, (a * 8 + (i >> 2)) * 128, fb);
                if (i == 3) { load_w(2, tw, h * 128 + 64, 0); load_w(3, tw, h * 128 + 64, 256); }
            }
            load_w(4, &tmWq, hq * 128, 0); load_w(5, &tmWq, hq * 128, 256); load_w(6, &tmWq, hq * 128 + 64, 0);
            dep_wait(0);
#pragma unroll 1
            for (int t = 0; t < 4; t++) {
                const unsigned char* xt = g_xn + ((blk_of(kq >> 1, t, rot) * 2 + (kq & 1)) * 10 + rank) * 16384;
#pragma unroll 1
                for (int ch = 0; ch < 5; ch++) {
                    if (t == 0 && ch == 4) load_w(7, &tmWq, hq * 128 + 64, 256);
                    load_half(xt + ch * 32768);
                }
                acquire();
                if (lead) { tma2d(dst, &tmWq, hq * 128, 512, fb); tma2d(dst + 16384, &tmWq, hq * 128 + 64, 512, fb); }
            }
            const unsigned char* Kh = g_K + (size_t)h * 32 * 16384 + rank * 16384;
            const unsigned char* Vh = g_V + (size_t)h * 32 * 16384 + rank * 16384;
#pragma unroll 1
            for (int r = 0; r < 4; r++) {
                const int p = blk_of(a, r, rot), n = 2 * p + 1;
                if (r < 2) dep_wait(1 + r);
                acquire();
                if (lead) {
                    const int g0 = (r & 1) ? rank : 3 - rank;
                    bulk_load(dst, g_Q + (size_t)(h * 32 + 4 * p + g0) * 16384, 16384, fb);
                    bulk_load(dst + 16384, g_Q + (size_t)(h * 32 + 4 * p + 3 - g0) * 16384, 16384, fb);
                    if (r == 1 || r == 2) l2_prefetch(g_Q + (size_t)(h * 32 + 4 * blk_of(a, r + 1, rot) + 2 * rank) * 16384, 32768);
                }
                load_half(Kh + n * 32768);
                if (r > 0) load_half(Vh);
#pragma unroll 1
                for (int j = n - 1; j >= 0; j--) { load_half(Kh + j * 32768); load_half(Vh + (j + 1) * 32768); }
            }
            load_half(Vh);
            mbar_wait(misc + BAR_EMPTY + 8 * c.slot, c.ph ^ 1); c.adv();
            int st = 0; uint32_t ph3 = 0;
#pragma unroll 1
            for (int i = 0; i < 32; i++) {
                const int head = op_head(i >> 1, kap, u3);
                if ((i & 1) == 0) dep_wait(3 + (i >> 1));
                if (i < NST3) { mbar_wait(misc + BAR_EMPTY + 8 * c.slot, c.ph ^ 1); c.adv(); }
                else mbar_wait(misc + BAR_EMPTY3 + 8 * st, ph3 ^ 1);
                fb = misc + BAR_FULL3 + 8 * st; dst = ring + st * ST3_BYTES;
                if (lead) {
                    mbar_expect_tx(fb, ST3_BYTES);
                    const unsigned char* src = g_Q + (size_t)(head * 32 + 4 * u3 + 2 * rank) * 16384 + (i & 1) * 8192;
                    bulk_load(dst, src, 8192, fb);
                    bulk_load(dst + 8192, src + 16384, 8192, fb);
                    tma3d_mc(dst + 16384 + rank * 10240, &tmWo, 0, head * 128 + (i & 1) * 64 + rank * 32, 5 * s3, fb);
                }
                if (++st == NST3) { st = 0; ph3 ^= 1; }
            }
        } else if (warp == 3) {
            unsigned ep1 = *reinterpret_cast<volatile unsigned*>(&g_epoch) + 1;
            if (lane == 0) {
                asm volatile("st.shared.u32 [%0], %1;" ::"r"(misc + MISC_EPOCH), "r"(ep1) : "memory");
                mbar_wait(misc + BAR_LN, 0);
                flag_signal(flag_ptr(FL_LN));
                mbar_wait(misc + BAR_PF, 0);
                l2_prefetch(reinterpret_cast<const unsigned char*>(P.wq) + (size_t)blockIdx.x * 40960, 40960);
                flag_wait(flag_ptr(FL_LN), ep1 * 128u);
                mbar_arrive(misc + BAR_DEP);
                mbar_wait(misc + BAR_EV + 8, 0);
                flag_wait(flag_ptr(FL_KV + h), ep1 * 8u);
                flag_wait(flag_ptr(FL_Q + h * 8 + blk_of(a, 0, rot)), ep1 * 4u);
                mbar_arrive(misc + BAR_DEP + 8);
                mbar_wait(misc + BAR_EV + 32, 0);
                for (int r = 1; r < 4; r++) flag_wait(flag_ptr(FL_Q + h * 8 + blk_of(a, r, rot)), ep1 * 4u);
                mbar_arrive(misc + BAR_DEP + 16);
                fence_async_global();
                l2_prefetch(g_Q + (size_t)(h * 32 + 4 * blk_of(a, 1, rot) + 2 * rank) * 16384, 32768);
                flag_wait(flag_ptr(FL_MOE_DONE), ep1);
                int4 s0 = __ldcg(reinterpret_cast<const int4*>(g_sel)), s1 = __ldcg(reinterpret_cast<const int4*>(g_sel) + 1);
                asm volatile("st.shared.v4.u32 [%0], {%1,%2,%3,%4};" ::"r"(misc + MISC_SEL), "r"(s0.x), "r"(s0.y), "r"(s0.z), "r"(s0.w) : "memory");
                asm volatile("st.shared.v4.u32 [%0], {%1,%2,%3,%4};" ::"r"(misc + MISC_SEL + 16), "r"(s1.x), "r"(s1.y), "r"(s1.z), "r"(s1.w) : "memory");
                mbar_arrive(misc + BAR_SEL);
                mbar_wait(misc + BAR_EV + 48, 0);
                l2_prefetch(reinterpret_cast<const unsigned char*>(P.wo) + (size_t)blockIdx.x * 40960, 40960);
            }
            __syncwarp();
            const unsigned* cf = flag_ptr(FL_CTX + op_head(lane & 15, kap, u3) * 8 + u3);
            bool done = lane >= 16;
            for (int spin = 0; spin < 4000000; spin++) {
                if (!done) {
                    unsigned v;
                    asm volatile("ld.acquire.gpu.global.u32 %0, [%1];" : "=r"(v) : "l"(cf) : "memory");
                    if ((int)(v - ep1 * 4u) >= 0) { mbar_arrive(misc + BAR_DEP + 24 + 8 * lane); done = true; }
                }
                if (__all_sync(0xffffffffu, done)) break;
                __nanosleep(64);
            }
        } else if (lane == 0) {
            const uint32_t eb = misc + BAR_EV + (warp - 1) * 72;
            mbar_wait(eb, 0);
            flag_signal(flag_ptr(FL_KV + h));
#pragma unroll 1
            for (int t = 0; t < 4; t++) {
                mbar_wait(eb + 8 + 8 * t, 0);
                flag_signal(flag_ptr(FL_Q + hq * 8 + blk_of(kq >> 1, t, rot)));
            }
#pragma unroll 1
            for (int r = 0; r < 4; r++) {
                mbar_wait(eb + 40 + 8 * r, 0);
                flag_signal(flag_ptr(FL_CTX + h * 8 + blk_of(a, r, rot)));
            }
        }
    } else {
        asm volatile("setmaxnreg.inc.sync.aligned.u32 240;");
        Ctx c;
        c.ring = ring; c.misc = misc; c.w = wg - 1; c.warp = (tid >> 5) & 3; c.lane = tid & 31;
        c.rel = mapa(misc, tid & 1);
        const int w = c.w;
        const int my_bar = 1 + w, other_bar = 2 - w;
        if (w == 1) {
            bar_arrive(1, 256);
            layernorm4(P, blockIdx.x * 16 + c.warp * 4, c.lane);
            __syncwarp();
            if (c.lane == 0) mbar_arrive(misc + BAR_LN);
        }
        Cur cur;
        {
            uint32_t wf[128];
            float acc[64];
#pragma unroll
            for (int i = 0; i < 64; i++) acc[i] = 0.f;
            auto load_weights = [&](int id, uint32_t slot0, uint32_t slot1) {
                mbar_wait(misc + BAR_W + 8 * id, 0);
                uint32_t z = load_afrag<16, 0>(wf, ring + slot0 * SLOT_BYTES, c);
                release(c, BAR_EMPTY + 8 * slot0 + z, 2);
                mbar_wait(misc + BAR_W + 8 * id + 8, 0);
                z = load_afrag<16, 64>(wf, ring + slot1 * SLOT_BYTES, c);
                release(c, BAR_EMPTY + 8 * slot1 + z, 2);
            };
            auto chunks4 = [&](uint32_t& last_slot) {
#pragma unroll
                for (int ch = 0; ch < 4; ch++) {
                    mbar_wait(misc + BAR_FULL + 8 * cur.slot, cur.ph);
                    uint64_t d = mkdesc(ring + cur.slot * SLOT_BYTES, 16, 1024, 1);
                    wg_fence();
#pragma unroll
                    for (int k = 0; k < 8; k++)
                        wgmma_rs_n128_ta0_tb0(acc, wf[32 * ch + 4 * k], wf[32 * ch + 4 * k + 1], wf[32 * ch + 4 * k + 2], wf[32 * ch + 4 * k + 3],
                                              d + (k >> 2) * 1024 + (k & 3) * 2, (ch | k) != 0);
                    wg_commit();
                    if (ch > 0 && ch < 3) { wg_wait<1>(); release(c, BAR_EMPTY + 8 * last_slot, 1); }
                    if (ch < 3) { last_slot = cur.slot; cur.adv(); }
                }
            };
            load_weights(2 * w, w ? 6 : 0, w ? 7 % NSLOT : 1);
            if (tid == 256) mbar_arrive(misc + BAR_PF);
            PROF_EV(2);
            cur = cur_at(2);
            unsigned char* kvdst = (rank ? g_V : g_K) + (size_t)(h * 32 + a * 16) * 16384;
#pragma unroll 1
            for (int t = 0; t < 8; t++) {
                uint32_t last;
                bar_sync(my_bar, 256);
                PROF_EV(10);
                chunks4(last);
                bar_arrive(other_bar, 256);
                wg_wait<1>(); release(c, BAR_EMPTY + 8 * last, 1);
                wg_wait<0>(); release(c, BAR_EMPTY + 8 * cur.slot, 1);
                PROF_EV(11);
                cur.adv();
                if (t == 0) { cur.adv(); cur.adv(); }
                fence_regs(acc);
                store_proj(acc, kvdst + t * 32768, c, policy_normal());
            }
            signal_event(c, 0);
            load_weights(4 + 2 * w, w ? 38 % NSLOT : 36 % NSLOT, w ? 43 % NSLOT : 37 % NSLOT);
            cur = cur_at(39);
#pragma unroll 1
            for (int t = 0; t < 4; t++) {
                uint32_t last;
                bar_sync(my_bar, 256);
                PROF_EV(20);
                chunks4(last);
                wg_wait<1>(); release(c, BAR_EMPTY + 8 * last, 1);
                last = cur.slot; cur.adv();
                if (t == 0) cur.adv();
                Cur cx = cur; cur.adv();
                mbar_wait(misc + BAR_FULL + 8 * cx.slot, cx.ph);
                mbar_wait(misc + BAR_FULL + 8 * cur.slot, cur.ph);
                uint64_t db = mkdesc(ring + cx.slot * SLOT_BYTES, 16, 1024, 1);
                uint64_t da = mkdesc(ring + cur.slot * SLOT_BYTES + w * 16384, 16384, 1024, 1);
                wg_fence();
#pragma unroll
                for (int k = 0; k < 8; k++) wgmma_ss_n128_ta1_tb0(acc, da + 128 * k, db + (k >> 2) * 1024 + (k & 3) * 2, 1);
                wg_commit();
                bar_arrive(other_bar, 256);
                wg_wait<1>(); release(c, BAR_EMPTY + 8 * last, 1);
                wg_wait<0>(); release(c, BAR_EMPTY + 8 * cx.slot, 1); release(c, BAR_EMPTY + 8 * cur.slot, 1);
                PROF_EV(21);
                cur.adv();
                fence_regs(acc);
                int tile = blk_of(kq >> 1, t, rot) * 2 + (kq & 1);
#pragma unroll
                for (int i = 0; i < 64; i++) acc[i] *= SM_SCALE;
                store_proj(acc, g_Q + (size_t)(hq * 32 + tile * 2) * 16384, c, t ? policy_stream() : policy_normal());
                signal_event(c, 1 + t);
            }
        }
        {
            float o[64];
            uint32_t q[32], p[32];
            float m[2], l[2];
#pragma unroll
            for (int i = 0; i < 64; i++) o[i] = 0.f;
#pragma unroll
            for (int i = 0; i < 32; i++) p[i] = 0u;
            m[0] = m[1] = l[0] = l[1] = 0.f;
            bool gen = false;
            int pv_acc = 0; bool pv_half = true; uint32_t pv_cnt = 1;
            unsigned char* ctx_dst = nullptr;
#pragma unroll 1
            for (int r = 0; r < 4; r++) {
                const int pb = blk_of(a, r, rot);
                const bool heavy = ((r & 1) == w);
                const int grp = heavy ? 3 - rank : rank;
                const bool half = (grp & 1) == 0;
                mbar_wait(misc + BAR_FULL + 8 * cur.slot, cur.ph);
                const uint32_t z = load_afrag<8, 0>(q, ring + cur.slot * SLOT_BYTES + w * 16384, c);
                release(c, BAR_EMPTY + 8 * cur.slot + z, 1);
                cur.adv();
                Cur ck = cur, cv;
                cur.adv();
                cv = cur;
                if (r > 0) cur.adv();
                if (!heavy) { ck = cur; cur.adv(); cur.adv(); }
                mbar_wait(misc + BAR_FULL + 8 * ck.slot, ck.ph);
                if (r > 0) mbar_wait(misc + BAR_FULL + 8 * cv.slot, cv.ph);
                float lprev[2] = {l[0], l[1]};
                bar_sync(my_bar, 256);
                PROF_EV(30);
                if (half) {
                    float s[32];
                    undef_regs(s);
                    issue_qk_half(s, q, ring + ck.slot * SLOT_BYTES);
                    issue_pv(o, p, ring + cv.slot * SLOT_BYTES, pv_acc, pv_half);
                    bar_arrive(other_bar, 256);
                    wg_wait<1>();
                    release(c, BAR_EMPTY + 8 * ck.slot, heavy ? 2 : 1);
                    fence_regs(s);
                    mask_diag<0>(s, c);
                    gen = softmax_first<8>(s, m, l);
                    wg_wait<0>();
                    fence_regs(o);
                    fence_regs(s);
#pragma unroll
                    for (int i = 0; i < 16; i++) p[i] = pack_bf16(s[2 * i], s[2 * i + 1]);
                } else {
                    float s[64];
                    undef_regs(s);
                    issue_qk(s, q, ring + ck.slot * SLOT_BYTES);
                    issue_pv(o, p, ring + cv.slot * SLOT_BYTES, pv_acc, pv_half);
                    bar_arrive(other_bar, 256);
                    wg_wait<1>();
                    release(c, BAR_EMPTY + 8 * ck.slot, heavy ? 2 : 1);
                    fence_regs(s);
                    mask_diag<8>(s, c);
                    gen = softmax_first<16>(s, m, l);
                    wg_wait<0>();
                    fence_regs(o);
                    fence_regs(s);
#pragma unroll
                    for (int i = 0; i < 32; i++) p[i] = pack_bf16(s[2 * i], s[2 * i + 1]);
                }
                if (r > 0) {
                    release(c, BAR_EMPTY + 8 * cv.slot, pv_cnt);
                    store_ctx(o, lprev, ctx_dst, c);
                    signal_event(c, 4 + r);
                }
                ctx_dst = g_Q + (size_t)(h * 32 + 4 * pb + grp) * 16384;
                pv_acc = 0; pv_half = half; pv_cnt = heavy ? 2 : 1;
                const int nreg = 2 * pb + (heavy ? 1 : 0);
#pragma unroll 1
                for (int j = 0; j < nreg; j++) {
                    ck = cur; cur.adv(); cv = cur; cur.adv();
                    mbar_wait(misc + BAR_FULL + 8 * ck.slot, ck.ph);
                    mbar_wait(misc + BAR_FULL + 8 * cv.slot, cv.ph);
                    bar_sync(my_bar, 256);
                    PROF_EV(31);
                    float s[64];
                    undef_regs(s);
                    issue_qk(s, q, ring + ck.slot * SLOT_BYTES);
                    issue_pv(o, p, ring + cv.slot * SLOT_BYTES, pv_acc, pv_half);
                    bar_arrive(other_bar, 256);
                    wg_wait<1>();
                    fence_regs(s);
                    bool redo = false;
                    if (!gen) {
                        float l0 = l[0], l1 = l[1];
                        exp_sum<16, false>(s, m, l0, l1);
                        redo = __any_sync(0xffffffffu, !(l0 <= SAFE_SUM && l1 <= SAFE_SUM));
                        if (!redo) { l[0] = l0; l[1] = l1; }
                    }
                    wg_wait<0>();
                    fence_regs(o);
                    fence_regs(s);
                    if (gen | redo) {
                        if (redo) recompute_scores(s, q, ring + ck.slot * SLOT_BYTES, c);
                        gen = true;
                        float mx[2], alpha[2];
                        row_max<16>(s, mx);
#pragma unroll
                        for (int i = 0; i < 2; i++) {
                            mx[i] = fmaxf(mx[i], m[i]);
                            alpha[i] = ex2(m[i] - mx[i]);
                            m[i] = mx[i];
                            l[i] *= alpha[i];
                        }
                        exp_sum<16, true>(s, m, l[0], l[1]);
#pragma unroll
                        for (int i = 0; i < 64; i++) o[i] *= alpha[(i >> 1) & 1];
                    }
                    release(c, BAR_EMPTY + 8 * ck.slot, 1);
                    release(c, BAR_EMPTY + 8 * cv.slot, pv_cnt);
#pragma unroll
                    for (int i = 0; i < 32; i++) p[i] = pack_bf16(s[2 * i], s[2 * i + 1]);
                    pv_acc = 1; pv_half = false; pv_cnt = 1;
                }
            }
            mbar_wait(misc + BAR_FULL + 8 * cur.slot, cur.ph);
            bar_sync(my_bar, 256);
            PROF_EV(32);
            issue_pv(o, p, ring + cur.slot * SLOT_BYTES, pv_acc, pv_half);
            if (w == 0) bar_arrive(other_bar, 256);
            wg_wait<0>();
            release(c, BAR_EMPTY + 8 * cur.slot, pv_cnt);
            fence_regs(o);
            store_ctx(o, l, ctx_dst, c);
            signal_event(c, 8);
        }
        {
            float acc[80];
#pragma unroll
            for (int i = 0; i < 80; i++) acc[i] = 0.f;
            int st = 0, prev = 0; uint32_t ph3 = 0;
            mbar_wait(misc + BAR_SEL, 0);
            const uint32_t tag = lds32(misc + MISC_EPOCH) & 1;
            const int g = c.lane >> 2, t = c.lane & 3;
            const int row = (2 * u3 + rank) * 128 + 64 * w + 16 * c.warp + 8 * kap + g;
            const int col = 160 * s3 + 8 * t;
            int sel = -1;
#pragma unroll
            for (int i = 0; i < TOPC; i++) if ((int)lds32(misc + MISC_SEL + 4 * i) == row) sel = i;
            uint4 xv[5], bv[5];
#pragma unroll
            for (int i = 0; i < 5; i++) {
                xv[i] = ldg128(P.x + (size_t)row * DM + col + 32 * i);
                bv[i] = ldg128(sel >= 0 ? (const void*)(g_brow + sel * DM + col + 32 * i) : (const void*)xn_addr(row, col + 32 * i));
            }
            PROF_EV(40);
#pragma unroll 1
            for (int i = 0; i < 32; i++) {
                mbar_wait(misc + BAR_FULL3 + 8 * st, ph3);
                uint32_t base = ring + st * ST3_BYTES;
                uint64_t da = mkdesc(base + w * 8192, 16, 1024, 1);
                uint64_t db = mkdesc(base + 16384, 2048, 512, 2);
                wg_fence();
#pragma unroll
                for (int k = 0; k < 4; k++) wgmma_ss_n160_ta0_tb1(acc, da + 2 * k, db + (k >> 1) * 640 + (k & 1) * 64, 1);
                wg_commit();
                if (i > 0) { wg_wait<1>(); if (i <= 32 - NST3) release(c, BAR_EMPTY3 + 8 * prev, 1); }
                prev = st;
                if (++st == NST3) { st = 0; ph3 ^= 1; }
            }
            wg_wait<0>();
            fence_regs(acc);
            PROF_EV(41);
            const int t256 = tid - 128;
            uint4* sendp = g_part + (size_t)blockIdx.x * 2560 + t256;
            float keep[40];
#pragma unroll
            for (int j = 0; j < 10; j++) {
                uint32_t v0 = __float_as_uint(kap ? acc[8 * j + 0] : acc[8 * j + 2]), v1 = __float_as_uint(kap ? acc[8 * j + 1] : acc[8 * j + 3]);
                uint32_t v2 = __float_as_uint(kap ? acc[8 * j + 4] : acc[8 * j + 6]), v3 = __float_as_uint(kap ? acc[8 * j + 5] : acc[8 * j + 7]);
                asm volatile("st.relaxed.gpu.global.v4.b32 [%0], {%1,%2,%3,%4};" ::"l"(sendp + j * 256),
                             "r"((v0 & ~1u) | tag), "r"((v1 & ~1u) | tag), "r"((v2 & ~1u) | tag), "r"((v3 & ~1u) | tag) : "memory");
                keep[4 * j + 0] = kap ? acc[8 * j + 2] : acc[8 * j + 0]; keep[4 * j + 1] = kap ? acc[8 * j + 3] : acc[8 * j + 1];
                keep[4 * j + 2] = kap ? acc[8 * j + 6] : acc[8 * j + 4]; keep[4 * j + 3] = kap ? acc[8 * j + 7] : acc[8 * j + 5];
            }
            const uint4* recvp = g_part + (size_t)(blockIdx.x ^ 2) * 2560 + t256;
            uint4 rv[10];
            int spins = 0;
            while (true) {
                uint32_t all_and = 1u, all_or = 0u;
#pragma unroll
                for (int j = 0; j < 10; j++) {
                    asm volatile("ld.relaxed.gpu.global.v4.b32 {%0,%1,%2,%3}, [%4];"
                                 : "=r"(rv[j].x), "=r"(rv[j].y), "=r"(rv[j].z), "=r"(rv[j].w) : "l"(recvp + j * 256) : "memory");
                }
#pragma unroll
                for (int j = 0; j < 10; j++) {
                    all_and &= rv[j].x & rv[j].y & rv[j].z & rv[j].w;
                    all_or |= rv[j].x | rv[j].y | rv[j].z | rv[j].w;
                }
                bool ok = ((tag ? all_and : all_or) & 1u) == tag;
                if (__all_sync(0xffffffffu, ok) || ++spins > 2000000) break;
            }
            uint32_t pk[20];
#pragma unroll
            for (int j = 0; j < 10; j++) {
                pk[2 * j] = pack_bf16(keep[4 * j] + __uint_as_float(rv[j].x & ~1u), keep[4 * j + 1] + __uint_as_float(rv[j].y & ~1u));
                pk[2 * j + 1] = pack_bf16(keep[4 * j + 2] + __uint_as_float(rv[j].z & ~1u), keep[4 * j + 3] + __uint_as_float(rv[j].w & ~1u));
            }
#pragma unroll
            for (int i = 0; i < 5; i++) {
                uint32_t a0 = pk[4 * i], a1 = pk[4 * i + 1], a2 = pk[4 * i + 2], a3 = pk[4 * i + 3];
                uint32_t x0 = (t & 1) ? a0 : a1, x1 = (t & 1) ? a2 : a3;
                x0 = __shfl_xor_sync(0xffffffffu, x0, 1); x1 = __shfl_xor_sync(0xffffffffu, x1, 1);
                if (t & 1) { a0 = x0; a2 = x1; } else { a1 = x0; a3 = x1; }
                x0 = (t & 2) ? a0 : a2; x1 = (t & 2) ? a1 : a3;
                x0 = __shfl_xor_sync(0xffffffffu, x0, 2); x1 = __shfl_xor_sync(0xffffffffu, x1, 2);
                if (t & 2) { a0 = x0; a1 = x1; } else { a2 = x0; a3 = x1; }
                uint32_t av[4] = {a0, a1, a2, a3};
                uint32_t xx[4] = {xv[i].x, xv[i].y, xv[i].z, xv[i].w}, bb[4] = {bv[i].x, bv[i].y, bv[i].z, bv[i].w};
                uint32_t ov[4];
#pragma unroll
                for (int e = 0; e < 4; e++) {
                    uint32_t t1 = pack_bf16(bf_lo(xx[e]) + bf_lo(av[e]), bf_hi(xx[e]) + bf_hi(av[e]));
                    ov[e] = pack_bf16(bf_lo(t1) + bf_lo(bb[e]), bf_hi(t1) + bf_hi(bb[e]));
                }
                stg128(P.out + (size_t)row * DM + col + 32 * i, ov[0], ov[1], ov[2], ov[3]);
            }
            PROF_EV(42); PROF_GT(43);
        }
    }
}

typedef CUresult (*EncodeFn)(CUtensorMap*, CUtensorMapDataType, cuuint32_t, void*, const cuuint64_t*, const cuuint64_t*, const cuuint32_t*,
                             const cuuint32_t*, CUtensorMapInterleave, CUtensorMapSwizzle, CUtensorMapL2promotion, CUtensorMapFloatOOBfill);

void make_map2d(EncodeFn enc, CUtensorMap* tm, const void* p, uint64_t cols, uint64_t rows) {
    cuuint64_t gd[2] = {cols, rows}, gs[1] = {cols * 2};
    cuuint32_t box[2] = {64, 128}, es[2] = {1, 1};
    enc(tm, CU_TENSOR_MAP_DATA_TYPE_BFLOAT16, 2, const_cast<void*>(p), gd, gs, box, es, CU_TENSOR_MAP_INTERLEAVE_NONE,
        CU_TENSOR_MAP_SWIZZLE_128B, CU_TENSOR_MAP_L2_PROMOTION_L2_128B, CU_TENSOR_MAP_FLOAT_OOB_FILL_NONE);
}

}

extern "C" void kernel_launch(void* const* d_in, const int* in_sizes, int n_in, void* d_out, int out_size) {
    (void)in_sizes; (void)n_in; (void)out_size;
    static EncodeFn enc = nullptr;
    if (!enc) {
        void* fn = nullptr;
        cudaDriverEntryPointQueryResult qr;
        cudaGetDriverEntryPoint("cuTensorMapEncodeTiled", &fn, cudaEnableDefault, &qr);
        enc = (EncodeFn)fn;
        cudaFuncSetAttribute(fused_kernel, cudaFuncAttributeMaxDynamicSharedMemorySize, SMEM_BYTES);
    }
    CUtensorMap tmC, tmWk, tmWv, tmWq, tmWo;
    make_map2d(enc, &tmC, d_in[1], DC, SEQ);
    make_map2d(enc, &tmWq, d_in[2], 4096, DM);
    make_map2d(enc, &tmWk, d_in[3], 4096, DC);
    make_map2d(enc, &tmWv, d_in[4], 4096, DC);
    {
        cuuint64_t gd[3] = {32, 4096, 20}, gs[2] = {DM * 2, 64};
        cuuint32_t box[3] = {32, 32, 5}, es[3] = {1, 1, 1};
        enc(&tmWo, CU_TENSOR_MAP_DATA_TYPE_BFLOAT16, 3, d_in[5], gd, gs, box, es, CU_TENSOR_MAP_INTERLEAVE_NONE,
            CU_TENSOR_MAP_SWIZZLE_64B, CU_TENSOR_MAP_L2_PROMOTION_L2_128B, CU_TENSOR_MAP_FLOAT_OOB_FILL_NONE);
    }
    Params P;
    P.x = (const __nv_bfloat16*)d_in[0];
    P.wq = (const __nv_bfloat16*)d_in[2];
    P.wo = (const __nv_bfloat16*)d_in[5];
    P.wr = (const __nv_bfloat16*)d_in[7];
    P.wg = (const __nv_bfloat16*)d_in[8];
    P.wu = (const __nv_bfloat16*)d_in[9];
    P.wd = (const __nv_bfloat16*)d_in[10];
    P.out = (__nv_bfloat16*)d_out;
    fused_kernel<<<132, 384, SMEM_BYTES>>>(tmC, tmWk, tmWv, tmWq, tmWo, P);
}
```

```cpp
#include <cuda_runtime.h>
#include <cuda_bf16.h>
#include <cuda.h>
#include <stdint.h>

namespace {

constexpr int SEQ = 2048, NH = 32, DM = 640, DC = 512, FF = 1728, TOPC = 8;
constexpr int NSLOT = 7, SLOT_BYTES = 32768;
constexpr int NST3 = 6, ST3_BYTES = 36864;
constexpr int RING_BYTES = NSLOT * SLOT_BYTES;
constexpr int SMEM_BYTES = RING_BYTES + 3072;

constexpr int BAR_FULL = 0, BAR_EMPTY = 64, BAR_FULL3 = 128, BAR_EMPTY3 = 192, BAR_EV = 256  , BAR_LN = 416, BAR_PF = 424  , BAR_SEL = 440,
              MISC_EPOCH = 448, MISC_SEL = 464, BAR_DEP = 512  , BAR_W = 672  , MISC_WR = 768  ;

constexpr int FL_LN = 0, FL_MOE_CNT = 1, FL_MOE_DONE = 2, FL_KV = 8  , FL_Q = 64  , FL_CTX = 320  , FL_TOTAL = 576;

__device__ __align__(1024) unsigned char g_K[NH * 32 * 16384];
__device__ __align__(1024) unsigned char g_V[NH * 32 * 16384];
__device__ __align__(1024) unsigned char g_Q[NH * 32 * 16384];
__device__ __align__(1024) unsigned char g_xn[16 * 10 * 16384];
__device__ __align__(1024) uint4 g_part[128 * 10 * 256];
__device__ float g_router[SEQ];
__device__ __align__(16) float g_moe_part[4 * TOPC * DM];
__device__ __align__(16) __nv_bfloat16 g_brow[TOPC * DM];
__device__ __align__(16) int g_sel[TOPC];
__device__ unsigned g_flags[FL_TOTAL * 8];
__device__ unsigned g_epoch;

struct Params {
    const __nv_bfloat16 *x, *wr, *wq, *wo;
    __nv_bfloat16* out;
};

__device__ __forceinline__ uint32_t smem_u32(const void* p) { return (uint32_t)__cvta_generic_to_shared(p); }
__device__ __forceinline__ void mbar_init(uint32_t bar, int cnt) { asm volatile("mbarrier.init.shared::cta.b64 [%0], %1;" ::"r"(bar), "r"(cnt)); }
__device__ __forceinline__ void mbar_expect_tx(uint32_t bar, uint32_t bytes) {
    asm volatile("mbarrier.arrive.expect_tx.shared::cta.b64 _, [%0], %1;" ::"r"(bar), "r"(bytes) : "memory");
}
__device__ __forceinline__ void mbar_arrive(uint32_t bar) { asm volatile("mbarrier.arrive.shared::cta.b64 _, [%0];" ::"r"(bar) : "memory"); }
__device__ __forceinline__ void mbar_arrive_cluster(uint32_t cluster_addr, uint32_t cnt) {
    asm volatile("mbarrier.arrive.shared::cluster.b64 _, [%0], %1;" ::"r"(cluster_addr), "r"(cnt) : "memory");
}
__device__ __forceinline__ uint32_t mapa(uint32_t addr, uint32_t cta) {
    uint32_t r; asm("mapa.shared::cluster.u32 %0, %1, %2;" : "=r"(r) : "r"(addr), "r"(cta)); return r;
}
__device__ __forceinline__ void mbar_wait(uint32_t bar, uint32_t parity) {
    asm volatile(
        "{\n.reg .pred p;\n.reg .u32 n;\n"
        "mbarrier.try_wait.parity.shared::cta.b64 p, [%0], %1;\n"
        "@p bra DONE;\n"
        "mov.u32 n, 0;\n"
        "LAB_WAIT:\n"
        "mbarrier.try_wait.parity.shared::cta.b64 p, [%0], %1;\n"
        "@p bra DONE;\n"
        "add.u32 n, n, 1;\n"
        "setp.lt.u32 p, n, 2000000;\n"
        "@p bra LAB_WAIT;\n"
        "trap;\n"
        "DONE:\n}\n" ::"r"(bar), "r"(parity) : "memory");
}
__device__ __forceinline__ void flag_wait(const unsigned* flag, unsigned target) {
    asm volatile(
        "{\n.reg .pred p;\n.reg .u32 n, v;\n.reg .s32 d;\n"
        "mov.u32 n, 0;\n"
        "LAB_WAIT:\n"
        "ld.acquire.gpu.global.u32 v, [%0];\n"
        "sub.s32 d, v, %1;\n"
        "setp.ge.s32 p, d, 0;\n"
        "@p bra DONE;\n"
        "nanosleep.u32 40;\n"
        "add.u32 n, n, 1;\n"
        "setp.lt.u32 p, n, 3000000;\n"
        "@p bra LAB_WAIT;\n"
        "trap;\n"
        "DONE:\n}\n" ::"l"(flag), "r"(target) : "memory");
}
__device__ __forceinline__ void flag_signal(unsigned* flag) {
    asm volatile("red.release.gpu.global.add.u32 [%0], 1;" ::"l"(flag) : "memory");
}
__device__ __forceinline__ void fence_async_global() { asm volatile("fence.proxy.async.global;" ::: "memory"); }
__device__ __forceinline__ unsigned* flag_ptr(int idx) { return g_flags + idx * 8; }

__device__ __forceinline__ uint64_t policy_stream() {
    uint64_t p; asm("createpolicy.fractional.L2::evict_first.b64 %0, 1.0;" : "=l"(p)); return p;
}
__device__ __forceinline__ uint64_t policy_normal() {
    uint64_t p; asm("createpolicy.fractional.L2::evict_normal.b64 %0, 1.0;" : "=l"(p)); return p;
}
__device__ __forceinline__ void bulk_load(uint32_t dst, const void* src, uint32_t bytes, uint32_t bar) {
    asm volatile("cp.async.bulk.shared::cluster.global.mbarrier::complete_tx::bytes [%0], [%1], %2, [%3];"
                 ::"r"(dst), "l"(src), "r"(bytes), "r"(bar) : "memory");
}
__device__ __forceinline__ void bulk_load_mc(uint32_t dst, const void* src, uint32_t bytes, uint32_t bar) {
    asm volatile("cp.async.bulk.shared::cluster.global.mbarrier::complete_tx::bytes.multicast::cluster [%0], [%1], %2, [%3], %4;"
                 ::"r"(dst), "l"(src), "r"(bytes), "r"(bar), "h"((uint16_t)3) : "memory");
}
__device__ __forceinline__ void tma2d(uint32_t dst, const CUtensorMap* tm, int c0, int c1, uint32_t bar) {
    asm volatile("cp.async.bulk.tensor.2d.shared::cluster.global.mbarrier::complete_tx::bytes [%0], [%1, {%3, %4}], [%2];"
                 ::"r"(dst), "l"(tm), "r"(bar), "r"(c0), "r"(c1) : "memory");
}
__device__ __forceinline__ void tma2d_mc(uint32_t dst, const CUtensorMap* tm, int c0, int c1, uint32_t bar) {
    asm volatile("cp.async.bulk.tensor.2d.shared::cluster.global.mbarrier::complete_tx::bytes.multicast::cluster [%0], [%1, {%3, %4}], [%2], %5;"
                 ::"r"(dst), "l"(tm), "r"(bar), "r"(c0), "r"(c1), "h"((uint16_t)3) : "memory");
}
__device__ __forceinline__ void tma3d_mc(uint32_t dst, const CUtensorMap* tm, int c0, int c1, int c2, uint32_t bar) {
    asm volatile("cp.async.bulk.tensor.3d.shared::cluster.global.mbarrier::complete_tx::bytes.multicast::cluster [%0], [%1, {%3, %4, %5}], [%2], %6;"
                 ::"r"(dst), "l"(tm), "r"(bar), "r"(c0), "r"(c1), "r"(c2), "h"((uint16_t)3) : "memory");
}
__device__ __forceinline__ void tma3d(uint32_t dst, const CUtensorMap* tm, int c0, int c1, int c2, uint32_t bar) {
    asm volatile("cp.async.bulk.tensor.3d.shared::cluster.global.mbarrier::complete_tx::bytes.L2::cache_hint [%0], [%1, {%3, %4, %5}], [%2], %6;"
                 ::"r"(dst), "l"(tm), "r"(bar), "r"(c0), "r"(c1), "r"(c2), "l"(policy_stream()) : "memory");
}
__device__ __forceinline__ void tma3d_prefetch(const CUtensorMap* tm, int c0, int c1, int c2) {
    asm volatile("cp.async.bulk.prefetch.tensor.3d.L2.global [%0, {%1, %2, %3}];" ::"l"(tm), "r"(c0), "r"(c1), "r"(c2) : "memory");
}
__device__ __forceinline__ void l2_prefetch(const void* p, uint32_t bytes) {
    asm volatile("cp.async.bulk.prefetch.L2.global [%0], %1;" ::"l"(p), "r"(bytes) : "memory");
}
__device__ __forceinline__ bool elect_one() {
    uint32_t r; asm volatile("{\n.reg .pred p;\nelect.sync _|p, 0xffffffff;\nselp.u32 %0, 1, 0, p;\n}\n" : "=r"(r)); return r != 0;
}
__device__ __forceinline__ void wg_fence() { asm volatile("wgmma.fence.sync.aligned;" ::: "memory"); }
__device__ __forceinline__ void wg_commit() { asm volatile("wgmma.commit_group.sync.aligned;" ::: "memory"); }
template <int N> __device__ __forceinline__ void wg_wait() { asm volatile("wgmma.wait_group.sync.aligned %0;" ::"n"(N) : "memory"); }
__device__ __forceinline__ void bar_sync(int id, int n) { asm volatile("bar.sync %0, %1;" ::"r"(id), "r"(n) : "memory"); }
__device__ __forceinline__ void bar_arrive(int id, int n) { asm volatile("bar.arrive %0, %1;" ::"r"(id), "r"(n) : "memory"); }
template <int N> __device__ __forceinline__ void fence_regs(float (&a)[N]) {
#pragma unroll
    for (int i = 0; i < N; i++) asm volatile("" : "+f"(a[i])::"memory");
}
template <int N> __device__ __forceinline__ void undef_regs(float (&a)[N]) {
#pragma unroll
    for (int i = 0; i < N; i++) asm volatile("" : "=f"(a[i]));
}
__device__ __forceinline__ void ldsm4t(uint32_t& r0, uint32_t& r1, uint32_t& r2, uint32_t& r3, uint32_t addr) {
    asm volatile("ldmatrix.sync.aligned.m8n8.x4.trans.shared.b16 {%0,%1,%2,%3}, [%4];"
                 : "=r"(r0), "=r"(r1), "=r"(r2), "=r"(r3) : "r"(addr) : "memory");
}
__device__ __forceinline__ uint32_t pack_bf16(float lo, float hi) {
    uint32_t r; asm("cvt.rn.bf16x2.f32 %0, %1, %2;" : "=r"(r) : "f"(hi), "f"(lo)); return r;
}
__device__ __forceinline__ float bf_lo(uint32_t v) { return __uint_as_float(v << 16); }
__device__ __forceinline__ float bf_hi(uint32_t v) { return __uint_as_float(v & 0xffff0000u); }
__device__ __forceinline__ float bf_round(float v) { return __bfloat162float(__float2bfloat16_rn(v)); }
__device__ __forceinline__ float ex2(float v) { float r; asm("ex2.approx.ftz.f32 %0, %1;" : "=f"(r) : "f"(v)); return r; }
__device__ __forceinline__ float rcp_fast(float v) { float r; asm("rcp.approx.ftz.f32 %0, %1;" : "=f"(r) : "f"(v)); return r; }
__device__ __forceinline__ float sqrt_fast(float v) { float r; asm("sqrt.approx.ftz.f32 %0, %1;" : "=f"(r) : "f"(v)); return r; }
__device__ __forceinline__ void stg128(void* p, uint32_t a, uint32_t b, uint32_t c, uint32_t d) {
    asm volatile("st.global.v4.b32 [%0], {%1,%2,%3,%4};" ::"l"(p), "r"(a), "r"(b), "r"(c), "r"(d) : "memory");
}
__device__ __forceinline__ void stg128_hint(void* p, uint32_t a, uint32_t b, uint32_t c, uint32_t d, uint64_t pol) {
    asm volatile("st.global.L2::cache_hint.v4.b32 [%0], {%1,%2,%3,%4}, %5;" ::"l"(p), "r"(a), "r"(b), "r"(c), "r"(d), "l"(pol) : "memory");
}
__device__ __forceinline__ uint4 ldg128(const void* p) {
    uint4 v; asm volatile("ld.global.cg.v4.b32 {%0,%1,%2,%3}, [%4];" : "=r"(v.x), "=r"(v.y), "=r"(v.z), "=r"(v.w) : "l"(p) : "memory"); return v;
}
__device__ __forceinline__ uint64_t mkdesc(uint32_t addr, uint32_t lbo, uint32_t sbo, uint32_t swz) {
    uint32_t lo = ((addr & 0x3FFFF) >> 4) | ((lbo >> 4) << 16);
    uint32_t hi = (sbo >> 4) | (swz << 30);
    return ((uint64_t)hi << 32) | lo;
}
__device__ __forceinline__ int perm32(int v) { return (v & ~30) | ((v >> 2) & 6) | ((v << 2) & 24); }

__device__ __forceinline__ void wgmma_rs_n128_ta0_tb0(float (&d)[64], uint32_t a0, uint32_t a1, uint32_t a2, uint32_t a3, uint64_t descB, int scaleD) {
  asm volatile("{\n.reg .pred p;\nsetp.ne.b32 p, %69, 0;\n"
    "wgmma.mma_async.sync.aligned.m64n128k16.f32.bf16.bf16 "
    "{%0, %1, %2, %3, %4, %5, %6, %7, %8, %9, %10, %11, %12, %13, %14, %15, %16, %17, %18, %19, %20, %21, %22, %23, %24, %25, %26, %27, %28, %29, %30, %31, %32, %33, %34, %35, %36, %37, %38, %39, %40, %41, %42, %43, %44, %45, %46, %47, %48, %49, %50, %51, %52, %53, %54, %55, %56, %57, %58, %59, %60, %61, %62, %63}, "
    "{%64, %65, %66, %67}, %68, p, 1, 1, 0;\n}\n"
    : "+f"(d[0]), "+f"(d[1]), "+f"(d[2]), "+f"(d[3]), "+f"(d[4]), "+f"(d[5]), "+f"(d[6]), "+f"(d[7]), "+f"(d[8]), "+f"(d[9]), "+f"(d[10]), "+f"(d[11]), "+f"(d[12]), "+f"(d[13]), "+f"(d[14]), "+f"(d[15]), "+f"(d[16]), "+f"(d[17]), "+f"(d[18]), "+f"(d[19]), "+f"(d[20]), "+f"(d[21]), "+f"(d[22]), "+f"(d[23]), "+f"(d[24]), "+f"(d[25]), "+f"(d[26]), "+f"(d[27]), "+f"(d[28]), "+f"(d[29]), "+f"(d[30]), "+f"(d[31]), "+f"(d[32]), "+f"(d[33]), "+f"(d[34]), "+f"(d[35]), "+f"(d[36]), "+f"(d[37]), "+f"(d[38]), "+f"(d[39]), "+f"(d[40]), "+f"(d[41]), "+f"(d[42]), "+f"(d[43]), "+f"(d[44]), "+f"(d[45]), "+f"(d[46]), "+f"(d[47]), "+f"(d[48]), "+f"(d[49]), "+f"(d[50]), "+f"(d[51]), "+f"(d[52]), "+f"(d[53]), "+f"(d[54]), "+f"(d[55]), "+f"(d[56]), "+f"(d[57]), "+f"(d[58]), "+f"(d[59]), "+f"(d[60]), "+f"(d[61]), "+f"(d[62]), "+f"(d[63])
    : "r"(a0), "r"(a1), "r"(a2), "r"(a3), "l"(descB), "r"(scaleD));
}
__device__ __forceinline__ void wgmma_rs_n128_ta0_tb1(float (&d)[64], uint32_t a0, uint32_t a1, uint32_t a2, uint32_t a3, uint64_t descB, int scaleD) {
  asm volatile("{\n.reg .pred p;\nsetp.ne.b32 p, %69, 0;\n"
    "wgmma.mma_async.sync.aligned.m64n128k16.f32.bf16.bf16 "
    "{%0, %1, %2, %3, %4, %5, %6, %7, %8, %9, %10, %11, %12, %13, %14, %15, %16, %17, %18, %19, %20, %21, %22, %23, %24, %25, %26, %27, %28, %29, %30, %31, %32, %33, %34, %35, %36, %37, %38, %39, %40, %41, %42, %43, %44, %45, %46, %47, %48, %49, %50, %51, %52, %53, %54, %55, %56, %57, %58, %59, %60, %61, %62, %63}, "
    "{%64, %65, %66, %67}, %68, p, 1, 1, 1;\n}\n"
    : "+f"(d[0]), "+f"(d[1]), "+f"(d[2]), "+f"(d[3]), "+f"(d[4]), "+f"(d[5]), "+f"(d[6]), "+f"(d[7]), "+f"(d[8]), "+f"(d[9]), "+f"(d[10]), "+f"(d[11]), "+f"(d[12]), "+f"(d[13]), "+f"(d[14]), "+f"(d[15]), "+f"(d[16]), "+f"(d[17]), "+f"(d[18]), "+f"(d[19]), "+f"(d[20]), "+f"(d[21]), "+f"(d[22]), "+f"(d[23]), "+f"(d[24]), "+f"(d[25]), "+f"(d[26]), "+f"(d[27]), "+f"(d[28]), "+f"(d[29]), "+f"(d[30]), "+f"(d[31]), "+f"(d[32]), "+f"(d[33]), "+f"(d[34]), "+f"(d[35]), "+f"(d[36]), "+f"(d[37]), "+f"(d[38]), "+f"(d[39]), "+f"(d[40]), "+f"(d[41]), "+f"(d[42]), "+f"(d[43]), "+f"(d[44]), "+f"(d[45]), "+f"(d[46]), "+f"(d[47]), "+f"(d[48]), "+f"(d[49]), "+f"(d[50]), "+f"(d[51]), "+f"(d[52]), "+f"(d[53]), "+f"(d[54]), "+f"(d[55]), "+f"(d[56]), "+f"(d[57]), "+f"(d[58]), "+f"(d[59]), "+f"(d[60]), "+f"(d[61]), "+f"(d[62]), "+f"(d[63])
    : "r"(a0), "r"(a1), "r"(a2), "r"(a3), "l"(descB), "r"(scaleD));
}
__device__ __forceinline__ void wgmma_rs_n64_ta0_tb1(float (&d)[32], uint32_t a0, uint32_t a1, uint32_t a2, uint32_t a3, uint64_t descB, int scaleD) {
  asm volatile("{\n.reg .pred p;\nsetp.ne.b32 p, %37, 0;\n"
    "wgmma.mma_async.sync.aligned.m64n64k16.f32.bf16.bf16 "
    "{%0, %1, %2, %3, %4, %5, %6, %7, %8, %9, %10, %11, %12, %13, %14, %15, %16, %17, %18, %19, %20, %21, %22, %23, %24, %25, %26, %27, %28, %29, %30, %31}, "
    "{%32, %33, %34, %35}, %36, p, 1, 1, 1;\n}\n"
    : "+f"(d[0]), "+f"(d[1]), "+f"(d[2]), "+f"(d[3]), "+f"(d[4]), "+f"(d[5]), "+f"(d[6]), "+f"(d[7]), "+f"(d[8]), "+f"(d[9]), "+f"(d[10]), "+f"(d[11]), "+f"(d[12]), "+f"(d[13]), "+f"(d[14]), "+f"(d[15]), "+f"(d[16]), "+f"(d[17]), "+f"(d[18]), "+f"(d[19]), "+f"(d[20]), "+f"(d[21]), "+f"(d[22]), "+f"(d[23]), "+f"(d[24]), "+f"(d[25]), "+f"(d[26]), "+f"(d[27]), "+f"(d[28]), "+f"(d[29]), "+f"(d[30]), "+f"(d[31])
    : "r"(a0), "r"(a1), "r"(a2), "r"(a3), "l"(descB), "r"(scaleD));
}
__device__ __forceinline__ void wgmma_ss_n128_ta1_tb0(float (&d)[64], uint64_t descA, uint64_t descB, int scaleD) {
  asm volatile("{\n.reg .pred p;\nsetp.ne.b32 p, %66, 0;\n"
    "wgmma.mma_async.sync.aligned.m64n128k16.f32.bf16.bf16 "
    "{%0, %1, %2, %3, %4, %5, %6, %7, %8, %9, %10, %11, %12, %13, %14, %15, %16, %17, %18, %19, %20, %21, %22, %23, %24, %25, %26, %27, %28, %29, %30, %31, %32, %33, %34, %35, %36, %37, %38, %39, %40, %41, %42, %43, %44, %45, %46, %47, %48, %49, %50, %51, %52, %53, %54, %55, %56, %57, %58, %59, %60, %61, %62, %63}, "
    "%64, %65, p, 1, 1, 1, 0;\n}\n"
    : "+f"(d[0]), "+f"(d[1]), "+f"(d[2]), "+f"(d[3]), "+f"(d[4]), "+f"(d[5]), "+f"(d[6]), "+f"(d[7]), "+f"(d[8]), "+f"(d[9]), "+f"(d[10]), "+f"(d[11]), "+f"(d[12]), "+f"(d[13]), "+f"(d[14]), "+f"(d[15]), "+f"(d[16]), "+f"(d[17]), "+f"(d[18]), "+f"(d[19]), "+f"(d[20]), "+f"(d[21]), "+f"(d[22]), "+f"(d[23]), "+f"(d[24]), "+f"(d[25]), "+f"(d[26]), "+f"(d[27]), "+f"(d[28]), "+f"(d[29]), "+f"(d[30]), "+f"(d[31]), "+f"(d[32]), "+f"(d[33]), "+f"(d[34]), "+f"(d[35]), "+f"(d[36]), "+f"(d[37]), "+f"(d[38]), "+f"(d[39]), "+f"(d[40]), "+f"(d[41]), "+f"(d[42]), "+f"(d[43]), "+f"(d[44]), "+f"(d[45]), "+f"(d[46]), "+f"(d[47]), "+f"(d[48]), "+f"(d[49]), "+f"(d[50]), "+f"(d[51]), "+f"(d[52]), "+f"(d[53]), "+f"(d[54]), "+f"(d[55]), "+f"(d[56]), "+f"(d[57]), "+f"(d[58]), "+f"(d[59]), "+f"(d[60]), "+f"(d[61]), "+f"(d[62]), "+f"(d[63])
    : "l"(descA), "l"(descB), "r"(scaleD));
}
__device__ __forceinline__ void wgmma_ss_n160_ta0_tb1(float (&d)[80], uint64_t descA, uint64_t descB, int scaleD) {
  asm volatile("{\n.reg .pred p;\nsetp.ne.b32 p, %82, 0;\n"
    "wgmma.mma_async.sync.aligned.m64n160k16.f32.bf16.bf16 "
    "{%0, %1, %2, %3, %4, %5, %6, %7, %8, %9, %10, %11, %12, %13, %14, %15, %16, %17, %18, %19, %20, %21, %22, %23, %24, %25, %26, %27, %28, %29, %30, %31, %32, %33, %34, %35, %36, %37, %38, %39, %40, %41, %42, %43, %44, %45, %46, %47, %48, %49, %50, %51, %52, %53, %54, %55, %56, %57, %58, %59, %60, %61, %62, %63, %64, %65, %66, %67, %68, %69, %70, %71, %72, %73, %74, %75, %76, %77, %78, %79}, "
    "%80, %81, p, 1, 1, 0, 1;\n}\n"
    : "+f"(d[0]), "+f"(d[1]), "+f"(d[2]), "+f"(d[3]), "+f"(d[4]), "+f"(d[5]), "+f"(d[6]), "+f"(d[7]), "+f"(d[8]), "+f"(d[9]), "+f"(d[10]), "+f"(d[11]), "+f"(d[12]), "+f"(d[13]), "+f"(d[14]), "+f"(d[15]), "+f"(d[16]), "+f"(d[17]), "+f"(d[18]), "+f"(d[19]), "+f"(d[20]), "+f"(d[21]), "+f"(d[22]), "+f"(d[23]), "+f"(d[24]), "+f"(d[25]), "+f"(d[26]), "+f"(d[27]), "+f"(d[28]), "+f"(d[29]), "+f"(d[30]), "+f"(d[31]), "+f"(d[32]), "+f"(d[33]), "+f"(d[34]), "+f"(d[35]), "+f"(d[36]), "+f"(d[37]), "+f"(d[38]), "+f"(d[39]), "+f"(d[40]), "+f"(d[41]), "+f"(d[42]), "+f"(d[43]), "+f"(d[44]), "+f"(d[45]), "+f"(d[46]), "+f"(d[47]), "+f"(d[48]), "+f"(d[49]), "+f"(d[50]), "+f"(d[51]), "+f"(d[52]), "+f"(d[53]), "+f"(d[54]), "+f"(d[55]), "+f"(d[56]), "+f"(d[57]), "+f"(d[58]), "+f"(d[59]), "+f"(d[60]), "+f"(d[61]), "+f"(d[62]), "+f"(d[63]), "+f"(d[64]), "+f"(d[65]), "+f"(d[66]), "+f"(d[67]), "+f"(d[68]), "+f"(d[69]), "+f"(d[70]), "+f"(d[71]), "+f"(d[72]), "+f"(d[73]), "+f"(d[74]), "+f"(d[75]), "+f"(d[76]), "+f"(d[77]), "+f"(d[78]), "+f"(d[79])
    : "l"(descA), "l"(descB), "r"(scaleD));
}

#define PROF_DECL
#define PROF_EV(tag)
#define PROF_GT(tag)

struct Cur {
    uint32_t slot, ph;
    __device__ __forceinline__ void adv() { if (++slot == NSLOT) { slot = 0; ph ^= 1; } }
};
constexpr int E0 = 3;
__host__ __device__ constexpr uint32_t slot_of(int e) { return (e + E0) % NSLOT; }
__device__ __forceinline__ Cur cur_at(int e) { Cur c; c.slot = (e + E0) % NSLOT; c.ph = ((e + E0) / NSLOT) & 1; return c; }

__device__ __forceinline__ int blk_of(int a, int r, int rot) {
    uint32_t tab = rot ? (a ? 0x2156u : 0x3047u) : (a ? 0x1256u : 0x0347u);
    return (tab >> (4 * r)) & 7;
}

__device__ __forceinline__ int op_head(int i, int kap, int u) { return 16 * kap + 4 * ((i >> 1) & 3) + 2 * ((u < 2 ? 1 : 0) ^ (i >> 3)) + (i & 1); }

constexpr float SM_SCALE = 0.08838834764831845f * 1.4426950408889634f;

struct Ctx {
    uint32_t ring, misc;
    uint32_t rel;
    int w, warp, lane;
};
__device__ __forceinline__ void release(const Ctx& c, uint32_t off, uint32_t cnt) {
    if (c.lane < 2) mbar_arrive_cluster(c.rel + off, cnt);
}
__device__ __forceinline__ void signal_event(const Ctx& c, int ev) {
    __syncwarp();
    if (c.lane == 0) mbar_arrive(c.misc + BAR_EV + (c.w * 9 + ev) * 8);
}
template <int NK, int OFF, int N>
__device__ __forceinline__ uint32_t load_afrag(uint32_t (&a)[N], uint32_t base, const Ctx& c) {
    int r = c.lane & 7, mat = c.lane >> 3;
    uint32_t addr = base + (8 * (mat >> 1) + r) * 128 + (((2 * c.warp + (mat & 1)) ^ r) << 4);
#pragma unroll
    for (int k = 0; k < NK; k++) ldsm4t(a[OFF + 4 * k], a[OFF + 4 * k + 1], a[OFF + 4 * k + 2], a[OFF + 4 * k + 3], addr + k * 2048);
    uint32_t dep = 0;
#pragma unroll
    for (int k = 0; k < NK; k++) dep |= a[OFF + 4 * k];
    return dep & blockIdx.y;
}
__device__ __forceinline__ void store_proj(const float (&acc)[64], unsigned char* dst  , const Ctx& c, uint64_t pol) {
    int g = c.lane >> 2, t = c.lane & 3;
#pragma unroll
    for (int i = 0; i < 2; i++) {
        int row = perm32(64 * c.w + 16 * c.warp + 8 * i + g);
        unsigned char* p = dst + row * 128;
#pragma unroll
        for (int q = 0; q < 4; q++) {
            int chunk = (4 * (q & 1) + t) ^ (row & 7);
            stg128_hint(p + (q >> 1) * 16384 + chunk * 16,
                   pack_bf16(acc[16 * q + 2 * i], acc[16 * q + 2 * i + 1]), pack_bf16(acc[16 * q + 4 + 2 * i], acc[16 * q + 4 + 2 * i + 1]),
                   pack_bf16(acc[16 * q + 8 + 2 * i], acc[16 * q + 8 + 2 * i + 1]), pack_bf16(acc[16 * q + 12 + 2 * i], acc[16 * q + 12 + 2 * i + 1]), pol);
        }
    }
}

constexpr float SAFE_EXP = 40.0f, SAFE_SUM = 1099511627776.0f;
template <int NJ>
__device__ __forceinline__ void row_max(const float (&s)[4 * NJ], float (&mx)[2]) {
#pragma unroll
    for (int i = 0; i < 2; i++) {
        float a = fmaxf(s[2 * i], s[2 * i + 1]), b = fmaxf(s[4 + 2 * i], s[4 + 2 * i + 1]);
#pragma unroll
        for (int j = 2; j < NJ; j += 2) {
            a = fmaxf(a, fmaxf(s[4 * j + 2 * i], s[4 * j + 2 * i + 1]));
            b = fmaxf(b, fmaxf(s[4 * j + 4 + 2 * i], s[4 * j + 4 + 2 * i + 1]));
        }
        a = fmaxf(a, b);
        a = fmaxf(a, __shfl_xor_sync(0xffffffffu, a, 1));
        mx[i] = fmaxf(a, __shfl_xor_sync(0xffffffffu, a, 2));
    }
}
template <int NJ, bool SHIFT>
__device__ __forceinline__ void exp_sum(float (&s)[4 * NJ], const float (&m)[2], float& l0, float& l1) {
#pragma unroll
    for (int j = 0; j < NJ; j++) {
#pragma unroll
        for (int e = 0; e < 4; e++) s[4 * j + e] = ex2(SHIFT ? s[4 * j + e] - m[e >> 1] : s[4 * j + e]);
        l0 += s[4 * j + 0]; l1 += s[4 * j + 2]; l0 += s[4 * j + 1]; l1 += s[4 * j + 3];
    }
}
template <int NJ>
__device__ __forceinline__ bool softmax_first(float (&s)[4 * NJ], float (&m)[2], float (&l)[2]) {
    row_max<NJ>(s, m);
    bool gen = __any_sync(0xffffffffu, !(fabsf(m[0]) <= SAFE_EXP && fabsf(m[1]) <= SAFE_EXP));
    if (!gen) m[0] = m[1] = 0.f;
    l[0] = l[1] = 0.f;
    exp_sum<NJ, true>(s, m, l[0], l[1]);
    return gen;
}
__device__ __forceinline__ void recompute_scores(float (&s)[64], const uint32_t (&q)[32], uint32_t kaddr, const Ctx& c) {
    const int r = c.lane & 7, mat = c.lane >> 3;
    const uint32_t a0 = kaddr + (8 * (mat & 1) + r) * 128 + (((mat >> 1) ^ r) << 4);
#pragma unroll
    for (int i = 0; i < 64; i++) s[i] = 0.f;
#pragma unroll
    for (int jp = 0; jp < 8; jp++) {
#pragma unroll
        for (int k = 0; k < 8; k++) {
            asm volatile(
                "{\n.reg .b32 b0, b1, b2, b3;\n"
                "ldmatrix.sync.aligned.m8n8.x4.trans.shared.b16 {b0,b1,b2,b3}, [%12];\n"
                "mma.sync.aligned.m16n8k16.row.col.f32.bf16.bf16.f32 {%0,%1,%2,%3}, {%8,%9,%10,%11}, {b0,b1}, {%0,%1,%2,%3};\n"
                "mma.sync.aligned.m16n8k16.row.col.f32.bf16.bf16.f32 {%4,%5,%6,%7}, {%8,%9,%10,%11}, {b2,b3}, {%4,%5,%6,%7};\n}\n"
                : "+f"(s[8 * jp]), "+f"(s[8 * jp + 1]), "+f"(s[8 * jp + 2]), "+f"(s[8 * jp + 3]),
                  "+f"(s[8 * jp + 4]), "+f"(s[8 * jp + 5]), "+f"(s[8 * jp + 6]), "+f"(s[8 * jp + 7])
                : "r"(q[4 * k]), "r"(q[4 * k + 1]), "r"(q[4 * k + 2]), "r"(q[4 * k + 3]),
                  "r"((a0 ^ ((jp & 3) << 5)) + (jp >> 2) * 16384 + k * 2048) : "memory");
        }
    }
}
template <int J0>
__device__ __forceinline__ void mask_diag(float (&s)[4 * J0 + 32], const Ctx& c) {
    int g = c.lane >> 2, t = c.lane & 3;
#pragma unroll
    for (int i = 0; i < 2; i++) {
        int lim = perm32(16 * c.warp + 8 * i + g) - 8 * t;
#pragma unroll
        for (int j = 0; j < 8; j++)
#pragma unroll
            for (int e = 0; e < 2; e++)
                if (32 * (j >> 2) + 2 * (j & 3) + e > lim) s[4 * (J0 + j) + 2 * i + e] = -INFINITY;
    }
}
__device__ __forceinline__ void issue_pv(float (&o)[64], const uint32_t (&p)[32], uint32_t vaddr, int acc, bool half) {
    uint64_t d = mkdesc(vaddr, 16, 1024, 1);
    if (half) {
        wg_fence();
#pragma unroll
        for (int k = 0; k < 4; k++) wgmma_rs_n128_ta0_tb0(o, p[4 * k], p[4 * k + 1], p[4 * k + 2], p[4 * k + 3], d + 2 * k, k != 0);
        wg_commit();
    } else {
        wg_fence();
#pragma unroll
        for (int k = 0; k < 8; k++)
            wgmma_rs_n128_ta0_tb0(o, p[4 * k], p[4 * k + 1], p[4 * k + 2], p[4 * k + 3], d + (k >> 2) * 1024 + 2 * (k & 3), k ? 1 : acc);
        wg_commit();
    }
}
__device__ __forceinline__ void issue_qk(float (&s)[64], const uint32_t (&q)[32], uint32_t kaddr) {
    uint64_t d = mkdesc(kaddr, 16384, 1024, 1);
    wg_fence();
#pragma unroll
    for (int k = 0; k < 8; k++) wgmma_rs_n128_ta0_tb1(s, q[4 * k], q[4 * k + 1], q[4 * k + 2], q[4 * k + 3], d + 128 * k, k != 0);
    wg_commit();
}
__device__ __forceinline__ void issue_qk_half(float (&s32)[32], const uint32_t (&q)[32], uint32_t kaddr) {
    uint64_t d = mkdesc(kaddr, 16384, 1024, 1);
    wg_fence();
#pragma unroll
    for (int k = 0; k < 8; k++) wgmma_rs_n64_ta0_tb1(s32, q[4 * k], q[4 * k + 1], q[4 * k + 2], q[4 * k + 3], d + 128 * k, k != 0);
    wg_commit();
}
__device__ __forceinline__ void stage_ctx(const float (&o)[64], const float (&l)[2], Cur ce, int ev, const Ctx& c) {
    const int g = c.lane >> 2, t = c.lane & 3, r7 = ((g & 1) << 2) | (g >> 1);
    const uint32_t base = c.ring + ce.slot * SLOT_BYTES + c.w * 16384 + (16 * c.warp + r7) * 128 + ((t ^ r7) << 4);
    float inv[2];
#pragma unroll
    for (int i = 0; i < 2; i++) {
        float sum = l[i];
        sum += __shfl_xor_sync(0xffffffffu, sum, 1);
        sum += __shfl_xor_sync(0xffffffffu, sum, 2);
        inv[i] = rcp_fast(sum);
    }
    mbar_wait(c.misc + BAR_FULL + 8 * ce.slot, ce.ph);
#pragma unroll
    for (int i = 0; i < 2; i++)
#pragma unroll
        for (int q = 0; q < 4; q++)
            asm volatile("st.shared.v4.b32 [%0], {%1,%2,%3,%4};" ::"r"((base ^ ((q & 1) << 6)) + (q >> 1) * 8192 + i * 1024),
                         "r"(pack_bf16(o[16 * q + 2 * i] * inv[i], o[16 * q + 2 * i + 1] * inv[i])),
                         "r"(pack_bf16(o[16 * q + 4 + 2 * i] * inv[i], o[16 * q + 4 + 2 * i + 1] * inv[i])),
                         "r"(pack_bf16(o[16 * q + 8 + 2 * i] * inv[i], o[16 * q + 8 + 2 * i + 1] * inv[i])),
                         "r"(pack_bf16(o[16 * q + 12 + 2 * i] * inv[i], o[16 * q + 12 + 2 * i + 1] * inv[i])) : "memory");
    asm volatile("fence.proxy.async.shared::cta;" ::: "memory");
    signal_event(c, ev);
}

__device__ __forceinline__ const unsigned char* xn_addr(int row, int col) {
    return g_xn + ((row >> 7) * 10 + (col >> 6)) * 16384 + (row & 127) * 128 + ((((col & 63) >> 3) ^ (row & 7)) << 4);
}
__device__ __forceinline__ void mma16816(float (&d)[4], uint32_t a0, uint32_t a1, uint32_t a2, uint32_t a3, uint32_t b0, uint32_t b1) {
    asm volatile("mma.sync.aligned.m16n8k16.row.col.f32.bf16.bf16.f32 {%0,%1,%2,%3}, {%4,%5,%6,%7}, {%8,%9}, {%0,%1,%2,%3};"
                 : "+f"(d[0]), "+f"(d[1]), "+f"(d[2]), "+f"(d[3]) : "r"(a0), "r"(a1), "r"(a2), "r"(a3), "r"(b0), "r"(b1));
}
__device__ __forceinline__ uint32_t lds32(uint32_t addr) { uint32_t v; asm volatile("ld.shared.u32 %0, [%1];" : "=r"(v) : "r"(addr)); return v; }

__device__ __forceinline__ void aux_cta(const CUtensorMap* tmG, const CUtensorMap* tmU, const CUtensorMap* tmD, unsigned char* sm, int a) {
    constexpr int STG = 57344, XS = 3 * STG, HS = XS + 8 * 1296, KEY = HS + 8 * 912, MI = KEY + 8192;
    const int tid = threadIdx.x, warp = __shfl_sync(0xffffffffu, tid >> 5, 0), lane = tid & 31;
    const uint32_t sb = smem_u32(sm);
    const uint32_t full = sb + MI, empty = sb + MI + 32;
    int* s_sel = reinterpret_cast<int*>(sm + MI + 64);
    float* s_r = reinterpret_cast<float*>(sm + MI + 96);
    volatile unsigned* s_misc = reinterpret_cast<volatile unsigned*>(sm + MI + 128);
    uint32_t* s_key = reinterpret_cast<uint32_t*>(sm + KEY);
    PROF_DECL
    PROF_GT(0);
    if (tid == 0) {
        for (int i = 0; i < 3; i++) { mbar_init(full + 8 * i, 1); mbar_init(empty + 8 * i, 10); }
        asm volatile("fence.mbarrier_init.release.cluster;" ::: "memory");
    }
    __syncthreads();
    if (warp == 11) {
        if (elect_one()) {
            int st = 0; uint32_t ph = 0;
#pragma unroll 1
            for (int s = 0; s < 34; s++) {
                mbar_wait(empty + 8 * st, ph ^ 1);
                const uint32_t dst = sb + st * STG, fb = full + 8 * st;
                if (s < 20) {
                    mbar_expect_tx(fb, 57344);
                    tma3d(dst, tmG, 0, 32 * s, 7 * a, fb);
                    tma3d(dst + 28672, tmU, 0, 32 * s, 7 * a, fb);
                } else {
                    mbar_expect_tx(fb, 40960);
                    tma3d(dst, tmD, 0, 448 * a + 32 * (s - 20), 0, fb);
                }
                if (s >= 3) {
#pragma unroll 1
                    for (int f = (s == 3 ? 4 : s + 6); f <= s + 6 && f < 34; f++) {
                        if (f < 20) { tma3d_prefetch(tmG, 0, 32 * f, 7 * a); tma3d_prefetch(tmU, 0, 32 * f, 7 * a); }
                        else tma3d_prefetch(tmD, 0, 448 * a + 32 * (f - 20), 0);
                    }
                }
                if (++st == 3) { st = 0; ph ^= 1; }
            }
        }
        return;
    }
    if (warp == 10) return;
    if (tid == 0) {
        unsigned e = *reinterpret_cast<volatile unsigned*>(&g_epoch);
        s_misc[0] = e;
        flag_wait(flag_ptr(FL_LN), (e + 1) * 128u);
    }
    bar_sync(1, 320);
    PROF_GT(50);
    const unsigned ep = s_misc[0];
    auto top8 = [&](uint32_t (&key)[8]) {
        uint32_t mine = 0;
#pragma unroll 1
        for (int r = 0; r < TOPC; r++) {
            uint32_t best = 0;
#pragma unroll
            for (int i = 0; i < 8; i++) best = max(best, key[i]);
            best = __reduce_max_sync(0xffffffffu, best);
#pragma unroll
            for (int i = 0; i < 8; i++) if (key[i] == best) key[i] = 0;
            if (lane == r) mine = best;
        }
        return mine;
    };
#pragma unroll 1
    for (int pass = 0; pass < 2; pass++) {
        if (warp < (pass ? 1 : 8)) {
            uint32_t key[8];
#pragma unroll
            for (int i = 0; i < 8; i++) {
                if (pass == 0) {
                    int idx = warp * 256 + i * 32 + lane;
                    uint32_t b = __float_as_uint(__ldcg(g_router + idx)) >> 16;
                    b = (b & 0x8000u) ? (~b & 0xffffu) : (b | 0x8000u);
                    key[i] = (b << 16) | (uint32_t)(0xffff - idx);
                } else key[i] = i < 2 ? s_key[i * 32 + lane] : 0u;
            }
            uint32_t best = top8(key);
            if (lane < TOPC) {
                if (pass == 0) s_key[warp * 8 + lane] = best;
                else {
                    uint32_t b = best >> 16;
                    b = (b & 0x8000u) ? (b & 0x7fffu) : (~b & 0xffffu);
                    s_sel[lane] = 0xffff - (int)(best & 0xffffu);
                    s_r[lane] = __uint_as_float(b << 16);
                }
            }
        }
        bar_sync(1, 320);
    }
#pragma unroll
    for (int it = 0; it < 2; it++) {
        int i = tid + it * 320, tk = i / 80, ch = i % 80;
        *reinterpret_cast<uint4*>(sm + XS + tk * 1296 + ch * 16) = __ldcg(reinterpret_cast<const uint4*>(xn_addr(s_sel[tk], ch * 8)));
    }
    bar_sync(1, 320);
    PROF_GT(51);
    const int g = lane >> 2, t = lane & 3;
    const uint32_t woff = warp * 4096 + (8 * (lane >> 4) + (lane & 7)) * 128 + ((((lane >> 3) & 1) ^ (lane & 7)) << 4);
    int st = 0; uint32_t ph = 0;
    float ga[4][4], ua[4][4];
#pragma unroll
    for (int i = 0; i < 4; i++)
#pragma unroll
        for (int e = 0; e < 4; e++) { ga[i][e] = 0.f; ua[i][e] = 0.f; }
#pragma unroll 1
    for (int s = 0; s < 34; s++) {
        if (s == 20) {
            if (warp < 7) {
#pragma unroll
                for (int i = 0; i < 4; i++)
#pragma unroll
                    for (int e = 0; e < 4; e++) {
                        float gv = bf_round(ga[i][e]), uv = bf_round(ua[i][e]);
                        float sg = bf_round(__fdividef(gv, 1.0f + __expf(fminf(-gv, 80.f))));
                        int f = warp * 64 + i * 16 + g + 8 * (e >> 1), tk = 2 * t + (e & 1);
                        *reinterpret_cast<__nv_bfloat16*>(sm + HS + tk * 912 + f * 2) = __float2bfloat16_rn(sg * uv);
                        ga[i][e] = 0.f;
                    }
            }
            bar_sync(1, 320);
            PROF_GT(52);
        }
        mbar_wait(full + 8 * st, ph);
        if (s >= 20 || warp < 7) {
#pragma unroll
            for (int kk = 0; kk < 2; kk++) {
                uint32_t xb = sb + (s < 20 ? XS + g * 1296 + s * 64 : HS + g * 912 + (s - 20) * 64) + 32 * kk + 4 * t;
                uint32_t b0 = lds32(xb), b1 = lds32(xb + 16);
                uint32_t wa = sb + st * STG + woff + kk * 2048;
#pragma unroll
                for (int i = 0; i < 4; i++) {
                    uint32_t a0, a1, a2, a3;
                    ldsm4t(a0, a1, a2, a3, wa ^ (i << 5));
                    mma16816(ga[i], a0, a1, a2, a3, b0, b1);
                    if (s < 20) {
                        ldsm4t(a0, a1, a2, a3, (wa ^ (i << 5)) + 28672);
                        mma16816(ua[i], a0, a1, a2, a3, b0, b1);
                    }
                }
            }
        }
        asm volatile("fence.proxy.async.shared::cta;" ::: "memory");
        __syncwarp();
        if (lane == 0) mbar_arrive(empty + 8 * st);
        if (++st == 3) { st = 0; ph ^= 1; }
    }
#pragma unroll
    for (int i = 0; i < 4; i++)
#pragma unroll
        for (int e = 0; e < 4; e += 2)
            *reinterpret_cast<float2*>(g_moe_part + (a * DM + warp * 64 + i * 16 + g + 4 * e) * 8 + 2 * t) = make_float2(ga[i][e], ga[i][e + 1]);
    bar_sync(1, 320);
    if (tid == 0) {
        __threadfence();
        unsigned old = atomicAdd(flag_ptr(FL_MOE_CNT), 1u);
        s_misc[1] = (old == ep * 4u + 3u);
        __threadfence();
    }
    bar_sync(1, 320);
    PROF_GT(53);
    if (s_misc[1]) {
        const float4* pp = reinterpret_cast<const float4*>(g_moe_part);
#pragma unroll 2
        for (int i = tid; i < DM * 2; i += 320) {
            float4 v0 = __ldcg(pp + i), v1 = __ldcg(pp + DM * 2 + i), v2 = __ldcg(pp + DM * 4 + i), v3 = __ldcg(pp + DM * 6 + i);
            float y[4] = {v0.x + v1.x + v2.x + v3.x, v0.y + v1.y + v2.y + v3.y, v0.z + v1.z + v2.z + v3.z, v0.w + v1.w + v2.w + v3.w};
#pragma unroll
            for (int e = 0; e < 4; e++) {
                int col = i >> 1, tk = (i & 1) * 4 + e;
                float sg = bf_round(__fdividef(1.0f, 1.0f + __expf(fminf(-s_r[tk], 80.f))));
                float upd = bf_round(bf_round(y[e]) * sg);
                float xn = __bfloat162float(*reinterpret_cast<const __nv_bfloat16*>(sm + XS + tk * 1296 + col * 2));
                g_brow[tk * DM + col] = __float2bfloat16_rn(xn + upd);
            }
        }
        if (tid < TOPC) g_sel[tid] = s_sel[tid];
        bar_sync(1, 320);
        if (tid == 0) {
            flag_signal(flag_ptr(FL_MOE_DONE));
            *reinterpret_cast<volatile unsigned*>(&g_epoch) = ep + 1;
        }
        PROF_GT(54);
    }
}

__device__ __forceinline__ void ln_rows(const Params& P, int row0, int lane, uint32_t wr_s) {
    const int hl = lane & 15, row = row0 + (lane >> 4);
    uint32_t v[20];
#pragma unroll
    for (int i = 0; i < 5; i++) {
        uint4 u = __ldg(reinterpret_cast<const uint4*>(P.x + (size_t)row * DM + 128 * i + 8 * hl));
        v[4 * i] = u.x; v[4 * i + 1] = u.y; v[4 * i + 2] = u.z; v[4 * i + 3] = u.w;
    }
    float mean = 0.f, m2 = 0.f;
#pragma unroll
    for (int i = 0; i < 20; i++) { mean += bf_lo(v[i]); mean += bf_hi(v[i]); }
    mean *= (1.0f / 40);
#pragma unroll
    for (int i = 0; i < 20; i++) {
        float d0 = __uint_as_float(__byte_perm(v[i], 0, 0x1044)) - mean, d1 = __uint_as_float(__byte_perm(v[i], 0, 0x3244)) - mean;
        m2 = fmaf(d0, d0, m2); m2 = fmaf(d1, d1, m2);
    }
#pragma unroll
    for (int o = 1; o < 16; o <<= 1) {
        float mo = __shfl_xor_sync(0xffffffffu, mean, o), qo = __shfl_xor_sync(0xffffffffu, m2, o), d = mo - mean;
        m2 = fmaf(d * d, 20.0f * o, m2 + qo);
        mean = 0.5f * (mean + mo);
    }
    const uint32_t mb2 = pack_bf16(mean, mean);
    const float inv = rcp_fast(bf_round(sqrt_fast(bf_round(bf_round(m2 * (1.0f / DM)) + 1e-5f))));
    float dot = 0.f;
    unsigned char* xp = g_xn + ((row >> 7) * 10 + (hl >> 3)) * 16384 + (row & 127) * 128 + (((hl & 7) ^ (row & 7)) << 4);
#pragma unroll
    for (int i = 0; i < 5; i++) {
        uint32_t ww[4];
        asm volatile("ld.shared.v4.b32 {%0,%1,%2,%3}, [%4];" : "=r"(ww[0]), "=r"(ww[1]), "=r"(ww[2]), "=r"(ww[3]) : "r"(wr_s + 256 * i + 16 * hl) : "memory");
#pragma unroll
        for (int e = 0; e < 4; e++) {
            uint32_t d;
            asm("sub.rn.bf16x2 %0, %1, %2;" : "=r"(d) : "r"(v[4 * i + e]), "r"(mb2));
            d = pack_bf16(bf_lo(d) * inv, bf_hi(d) * inv);
            v[4 * i + e] = d;
            dot = fmaf(bf_lo(d), bf_lo(ww[e]), dot);
            dot = fmaf(bf_hi(d), bf_hi(ww[e]), dot);
        }
        stg128(xp + i * 32768, v[4 * i], v[4 * i + 1], v[4 * i + 2], v[4 * i + 3]);
    }
#pragma unroll
    for (int o = 8; o > 0; o >>= 1) dot += __shfl_xor_sync(0xffffffffu, dot, o);
    if (hl == 0) g_router[row] = bf_round(dot);
}

__global__ void __cluster_dims__(2, 1, 1) __launch_bounds__(384, 1)
fused_kernel(const __grid_constant__ CUtensorMap tmC, const __grid_constant__ CUtensorMap tmWk, const __grid_constant__ CUtensorMap tmWv,
             const __grid_constant__ CUtensorMap tmWq, const __grid_constant__ CUtensorMap tmWo,
             const __grid_constant__ CUtensorMap tmG, const __grid_constant__ CUtensorMap tmU, const __grid_constant__ CUtensorMap tmD, const Params P) {
    extern __shared__ unsigned char smem_raw[];
    const uint32_t ring = (smem_u32(smem_raw) + 1023u) & ~1023u;
    const uint32_t misc = ring + RING_BYTES;
    const int tid = threadIdx.x;
    const int mc = blockIdx.x >> 1, rank = blockIdx.x & 1;
    if (mc >= 64) { aux_cta(&tmG, &tmU, &tmD, smem_raw + (ring - smem_u32(smem_raw)), blockIdx.x - 128); return; }
    PROF_DECL
    PROF_GT(0); PROF_EV(1);

    if (tid == 0) {
        for (int i = 0; i < 8; i++) mbar_init(misc + BAR_W + 8 * i, 1);
        asm volatile("fence.mbarrier_init.release.cluster;" ::: "memory");
        const CUtensorMap* tw = rank ? &tmWv : &tmWk;
        for (int e = 0; e < 2; e++) {
            mbar_expect_tx(misc + BAR_W + 8 * e, SLOT_BYTES);
            tma2d(ring + (E0 + e) * SLOT_BYTES, tw, (mc >> 1) * 128, e * 256, misc + BAR_W + 8 * e);
            tma2d(ring + (E0 + e) * SLOT_BYTES + 16384, tw, (mc >> 1) * 128, e * 256 + 128, misc + BAR_W + 8 * e);
        }
        for (int i = 0; i < NSLOT; i++) { mbar_init(misc + BAR_FULL + 8 * i, 1); mbar_init(misc + BAR_EMPTY + 8 * i, 16); }
        for (int i = 0; i < NST3; i++) { mbar_init(misc + BAR_FULL3 + 8 * i, 1); mbar_init(misc + BAR_EMPTY3 + 8 * i, 16); }
        for (int i = 0; i < 18; i++) mbar_init(misc + BAR_EV + 8 * i, 4);
        for (int i = 0; i < 19; i++) mbar_init(misc + BAR_DEP + 8 * i, 1);
        mbar_init(misc + BAR_LN, 2); mbar_init(misc + BAR_PF, 1); mbar_init(misc + BAR_PF + 8, 1); mbar_init(misc + BAR_SEL, 1);
        for (int i = 0; i < E0 + 2; i++) mbar_arrive(misc + BAR_FULL + 8 * i);
        for (int i = 0; i < E0; i++) mbar_arrive_cluster(misc + BAR_EMPTY + 8 * i, 16);
        asm volatile("fence.mbarrier_init.release.cluster;" ::: "memory");
    }
    if (tid == 32) asm volatile("prefetch.tensormap [%0];" ::"l"(&tmC) : "memory");
    __syncthreads();
    asm volatile("barrier.cluster.arrive.relaxed.aligned;\nbarrier.cluster.wait.aligned;" ::: "memory");

    PROF_EV(5);
    const int h = mc >> 1, a = mc & 1;
    const int rot = (mc >> 2) & 1;
    const int hq = (mc >> 2) * 2 + rank;
    const int kq = mc & 3;
    const int u3 = mc >> 3, s3 = (mc >> 1) & 3, kap = mc & 1;
    const int wg = __shfl_sync(0xffffffffu, tid >> 7, 0);

    if (wg == 0) {
        asm volatile("setmaxnreg.dec.sync.aligned.u32 40;");
        const int warp = __shfl_sync(0xffffffffu, tid >> 5, 0), lane = tid & 31;
        if (warp == 0) {
            const bool lead = elect_one();
            Cur c = cur_at(2);
            uint32_t dst, fb;
            auto acquire = [&]() {
                mbar_wait(misc + BAR_EMPTY + 8 * c.slot, c.ph ^ 1);
                fb = misc + BAR_FULL + 8 * c.slot; dst = ring + c.slot * SLOT_BYTES;
                if (lead) mbar_expect_tx(fb, SLOT_BYTES);
                c.adv();
            };
            auto load_w = [&](int id, const CUtensorMap* tm, int col, int row) {
                mbar_wait(misc + BAR_EMPTY + 8 * c.slot, c.ph ^ 1);
                fb = misc + BAR_W + 8 * id; dst = ring + c.slot * SLOT_BYTES;
                if (lead) {
                    mbar_expect_tx(fb, SLOT_BYTES);
                    tma2d(dst, tm, col, row, fb); tma2d(dst + 16384, tm, col, row + 128, fb);
                    mbar_arrive(misc + BAR_FULL + 8 * c.slot);
                }
                c.adv();
            };
            auto load_half = [&](const unsigned char* src) {
                acquire();
                if (lead) bulk_load_mc(dst + rank * 16384, src, 16384, fb);
            };
            auto staging = [&]() {
                mbar_wait(misc + BAR_EMPTY + 8 * c.slot, c.ph ^ 1);
                if (lead) mbar_arrive(misc + BAR_FULL + 8 * c.slot);
                c.adv();
            };
            auto dep_wait = [&](int d) { mbar_wait(misc + BAR_DEP + 8 * d, 0); fence_async_global(); };
            const CUtensorMap* tw = rank ? &tmWv : &tmWk;
#pragma unroll 1
            for (int i = 0; i < 32; i++) {
                acquire();
                if (lead) tma2d_mc(dst + rank * 16384, &tmC, (i & 3) * 128 + rank * 64, (a * 8 + (i >> 2)) * 128, fb);
                if (i == 3) { load_w(2, tw, h * 128 + 64, 0); load_w(3, tw, h * 128 + 64, 256); }
            }
            load_w(4, &tmWq, hq * 128, 0); load_w(5, &tmWq, hq * 128, 256); load_w(6, &tmWq, hq * 128 + 64, 0);
            dep_wait(0);
#pragma unroll 1
            for (int t = 0; t < 4; t++) {
                const unsigned char* xt = g_xn + ((blk_of(kq >> 1, t, rot) * 2 + (kq & 1)) * 10 + rank) * 16384;
#pragma unroll 1
                for (int ch = 0; ch < 5; ch++) {
                    if (t == 0 && ch == 4) load_w(7, &tmWq, hq * 128 + 64, 256);
                    load_half(xt + ch * 32768);
                }
                acquire();
                if (lead) { tma2d(dst, &tmWq, hq * 128, 512, fb); tma2d(dst + 16384, &tmWq, hq * 128 + 64, 512, fb); }
            }
            const unsigned char* Kh = g_K + (size_t)h * 32 * 16384 + rank * 16384;
            const unsigned char* Vh = g_V + (size_t)h * 32 * 16384 + rank * 16384;
#pragma unroll 1
            for (int r = 0; r < 4; r++) {
                const int p = blk_of(a, r, rot), n = 2 * p + 1;
                if (r < 2) dep_wait(1 + r);
                acquire();
                if (lead) {
                    const int g0 = (r & 1) ? rank : 3 - rank;
                    bulk_load(dst, g_Q + (size_t)(h * 32 + 4 * p + g0) * 16384, 16384, fb);
                    bulk_load(dst + 16384, g_Q + (size_t)(h * 32 + 4 * p + 3 - g0) * 16384, 16384, fb);
                }
                load_half(Kh + n * 32768);
                if (r > 0) { load_half(Vh); staging(); }
#pragma unroll 1
                for (int j = n - 1; j >= 0; j--) { load_half(Kh + j * 32768); load_half(Vh + (j + 1) * 32768); }
            }
            load_half(Vh);
            staging();
            mbar_wait(misc + BAR_EMPTY + 8 * c.slot, c.ph ^ 1); c.adv();
            int st = 0; uint32_t ph3 = 0;
#pragma unroll 1
            for (int i = 0; i < 32; i++) {
                const int head = op_head(i >> 1, kap, u3);
                if ((i & 1) == 0) dep_wait(3 + (i >> 1));
                if (i < NST3) { mbar_wait(misc + BAR_EMPTY + 8 * c.slot, c.ph ^ 1); c.adv(); }
                else mbar_wait(misc + BAR_EMPTY3 + 8 * st, ph3 ^ 1);
                fb = misc + BAR_FULL3 + 8 * st; dst = ring + st * ST3_BYTES;
                if (lead) {
                    mbar_expect_tx(fb, ST3_BYTES);
                    const unsigned char* src = g_Q + (size_t)(head * 32 + 4 * u3 + 2 * rank) * 16384 + (i & 1) * 8192;
                    bulk_load(dst, src, 8192, fb);
                    bulk_load(dst + 8192, src + 16384, 8192, fb);
                    tma3d_mc(dst + 16384 + rank * 10240, &tmWo, 0, head * 128 + (i & 1) * 64 + rank * 32, 5 * s3, fb);
                }
                if (++st == NST3) { st = 0; ph3 ^= 1; }
            }
        } else if (warp == 3) {
            unsigned ep1 = *reinterpret_cast<volatile unsigned*>(&g_epoch) + 1;
            if (lane == 0) {
                asm volatile("st.shared.u32 [%0], %1;" ::"r"(misc + MISC_EPOCH), "r"(ep1) : "memory");
                mbar_wait(misc + BAR_LN, 0);
                flag_signal(flag_ptr(FL_LN));
                mbar_wait(misc + BAR_PF + 8, 0);
                l2_prefetch(reinterpret_cast<const unsigned char*>(P.wq) + (size_t)blockIdx.x * 40960, 40960);
                flag_wait(flag_ptr(FL_LN), ep1 * 128u);
                mbar_arrive(misc + BAR_DEP);
                mbar_wait(misc + BAR_EV + 8, 0);
                flag_wait(flag_ptr(FL_KV + h), ep1 * 8u);
                flag_wait(flag_ptr(FL_Q + h * 8 + blk_of(a, 0, rot)), ep1 * 4u);
                mbar_arrive(misc + BAR_DEP + 8);
                mbar_wait(misc + BAR_EV + 32, 0);
                for (int r = 1; r < 4; r++) flag_wait(flag_ptr(FL_Q + h * 8 + blk_of(a, r, rot)), ep1 * 4u);
                mbar_arrive(misc + BAR_DEP + 16);
                flag_wait(flag_ptr(FL_MOE_DONE), ep1);
                int4 s0 = __ldcg(reinterpret_cast<const int4*>(g_sel)), s1 = __ldcg(reinterpret_cast<const int4*>(g_sel) + 1);
                asm volatile("st.shared.v4.u32 [%0], {%1,%2,%3,%4};" ::"r"(misc + MISC_SEL), "r"(s0.x), "r"(s0.y), "r"(s0.z), "r"(s0.w) : "memory");
                asm volatile("st.shared.v4.u32 [%0], {%1,%2,%3,%4};" ::"r"(misc + MISC_SEL + 16), "r"(s1.x), "r"(s1.y), "r"(s1.z), "r"(s1.w) : "memory");
                mbar_arrive(misc + BAR_SEL);
                mbar_wait(misc + BAR_EV + 48, 0);
                l2_prefetch(reinterpret_cast<const unsigned char*>(P.wo) + (size_t)blockIdx.x * 40960, 40960);
            }
            __syncwarp();
            const unsigned* cf = flag_ptr(FL_CTX + op_head(lane & 15, kap, u3) * 8 + u3);
            bool done = lane >= 16;
            for (int spin = 0; spin < 4000000; spin++) {
                if (!done) {
                    unsigned v;
                    asm volatile("ld.acquire.gpu.global.u32 %0, [%1];" : "=r"(v) : "l"(cf) : "memory");
                    if ((int)(v - ep1 * 4u) >= 0) {
                        mbar_arrive(misc + BAR_DEP + 24 + 8 * lane);
                        done = true;
                        fence_async_global();
                        l2_prefetch(g_Q + (size_t)(op_head(lane, kap, u3) * 32 + 4 * u3 + 2 * rank) * 16384 + s3 * 8192, 8192);
                    }
                }
                if (__all_sync(0xffffffffu, done)) break;
                __nanosleep(64);
            }
        } else {
            if (lane < 20) {
#pragma unroll
                for (int i = 0; i < 2; i++) {
                    const int ch = (warp - 1) * 40 + i * 20 + lane;
                    uint4 u = __ldg(reinterpret_cast<const uint4*>(P.wr) + ch);
                    asm volatile("st.shared.v4.b32 [%0], {%1,%2,%3,%4};" ::"r"(misc + MISC_WR + 16 * ch), "r"(u.x), "r"(u.y), "r"(u.z), "r"(u.w) : "memory");
                }
            }
            bar_sync(3, 64);
            mbar_wait(misc + BAR_PF, 0);
            if (lane == 0) l2_prefetch(P.x + (size_t)(blockIdx.x * 16 + (warp - 1) * 8) * DM, 8 * DM * 2);
#pragma unroll 1
            for (int i = 0; i < 8; i += 2) ln_rows(P, blockIdx.x * 16 + (warp - 1) * 8 + i, lane, misc + MISC_WR);
            __syncwarp();
            if (lane == 0) {
            mbar_arrive(misc + BAR_LN);
            const uint32_t eb = misc + BAR_EV + (warp - 1) * 72;
            mbar_wait(eb, 0);
            flag_signal(flag_ptr(FL_KV + h));
#pragma unroll 1
            for (int t = 0; t < 4; t++) {
                mbar_wait(eb + 8 + 8 * t, 0);
                flag_signal(flag_ptr(FL_Q + hq * 8 + blk_of(kq >> 1, t, rot)));
            }
            int e = 64;
#pragma unroll 1
            for (int r = 0; r < 4; r++) {
                const int p = blk_of(a, r, rot);
                e += 4 * p + 4 + (r > 0 ? 2 : 0);
                const uint32_t slot = (e + (r < 3 ? 3 : 1) + E0) % NSLOT;
                const int grp = ((r & 1) == warp - 1) ? 3 - rank : rank;
                mbar_wait(eb + 40 + 8 * r, 0);
                asm volatile("cp.async.bulk.global.shared::cta.bulk_group [%0], [%1], 16384;"
                             ::"l"(g_Q + (size_t)(h * 32 + 4 * p + grp) * 16384), "r"(ring + slot * SLOT_BYTES + (warp - 1) * 16384) : "memory");
                asm volatile("cp.async.bulk.commit_group;" ::: "memory");
                asm volatile("cp.async.bulk.wait_group.read 0;" ::: "memory");
                mbar_arrive_cluster(mapa(misc + BAR_EMPTY + 8 * slot, 0), 4);
                mbar_arrive_cluster(mapa(misc + BAR_EMPTY + 8 * slot, 1), 4);
                asm volatile("cp.async.bulk.wait_group 0;" ::: "memory");
                fence_async_global();
                flag_signal(flag_ptr(FL_CTX + h * 8 + p));
            }
            }
        }
    } else {
        asm volatile("setmaxnreg.inc.sync.aligned.u32 232;");
        Ctx c;
        c.ring = ring; c.misc = misc; c.w = wg - 1; c.warp = (tid >> 5) & 3; c.lane = tid & 31;
        c.rel = mapa(misc, tid & 1);
        const int w = c.w;
        const int my_bar = 1 + w, other_bar = 2 - w;
        if (w == 1) bar_arrive(1, 256);
        Cur cur;
        {
            uint32_t wf[128];
            float acc[64];
#pragma unroll
            for (int i = 0; i < 64; i++) acc[i] = 0.f;
            auto load_weights = [&](int id, uint32_t slot0, uint32_t slot1) {
                mbar_wait(misc + BAR_W + 8 * id, 0);
                uint32_t z = load_afrag<16, 0>(wf, ring + slot0 * SLOT_BYTES, c);
                release(c, BAR_EMPTY + 8 * slot0 + z, 2);
                mbar_wait(misc + BAR_W + 8 * id + 8, 0);
                z = load_afrag<16, 64>(wf, ring + slot1 * SLOT_BYTES, c);
                release(c, BAR_EMPTY + 8 * slot1 + z, 2);
            };
            auto chunks4 = [&](uint32_t& last_slot) {
#pragma unroll
                for (int ch = 0; ch < 4; ch++) {
                    mbar_wait(misc + BAR_FULL + 8 * cur.slot, cur.ph);
                    uint64_t d = mkdesc(ring + cur.slot * SLOT_BYTES, 16, 1024, 1);
                    wg_fence();
#pragma unroll
                    for (int k = 0; k < 8; k++)
                        wgmma_rs_n128_ta0_tb0(acc, wf[32 * ch + 4 * k], wf[32 * ch + 4 * k + 1], wf[32 * ch + 4 * k + 2], wf[32 * ch + 4 * k + 3],
                                              d + (k >> 2) * 1024 + (k & 3) * 2, (ch | k) != 0);
                    wg_commit();
                    if (ch > 0 && ch < 3) { wg_wait<1>(); release(c, BAR_EMPTY + 8 * last_slot, 1); }
                    if (ch < 3) { last_slot = cur.slot; cur.adv(); }
                }
            };
            load_weights(2 * w, w ? slot_of(6) : slot_of(0), w ? slot_of(7) : slot_of(1));
            if (tid == 256) mbar_arrive(misc + BAR_PF);
            PROF_EV(2);
            cur = cur_at(2);
            unsigned char* kvdst = (rank ? g_V : g_K) + (size_t)(h * 32 + a * 16) * 16384;
#pragma unroll 1
            for (int t = 0; t < 8; t++) {
                uint32_t last;
                bar_sync(my_bar, 256);
                PROF_EV(10);
                chunks4(last);
                bar_arrive(other_bar, 256);
                wg_wait<1>(); release(c, BAR_EMPTY + 8 * last, 1);
                wg_wait<0>(); release(c, BAR_EMPTY + 8 * cur.slot, 1);
                PROF_EV(11);
                cur.adv();
                if (t == 0) { cur.adv(); cur.adv(); }
                fence_regs(acc);
                if (t == 5 && tid == 128) mbar_arrive(misc + BAR_PF + 8);
                if (t == 7) load_weights(4 + 2 * w, w ? slot_of(38) : slot_of(36), w ? slot_of(43) : slot_of(37));
                store_proj(acc, kvdst + t * 32768, c, policy_normal());
            }
            signal_event(c, 0);
            cur = cur_at(39);
#pragma unroll 1
            for (int t = 0; t < 4; t++) {
                uint32_t last;
                bar_sync(my_bar, 256);
                PROF_EV(20);
                chunks4(last);
                wg_wait<1>(); release(c, BAR_EMPTY + 8 * last, 1);
                last = cur.slot; cur.adv();
                if (t == 0) cur.adv();
                Cur cx = cur; cur.adv();
                mbar_wait(misc + BAR_FULL + 8 * cx.slot, cx.ph);
                mbar_wait(misc + BAR_FULL + 8 * cur.slot, cur.ph);
                uint64_t db = mkdesc(ring + cx.slot * SLOT_BYTES, 16, 1024, 1);
                uint64_t da = mkdesc(ring + cur.slot * SLOT_BYTES + w * 16384, 16384, 1024, 1);
                wg_fence();
#pragma unroll
                for (int k = 0; k < 8; k++) wgmma_ss_n128_ta1_tb0(acc, da + 128 * k, db + (k >> 2) * 1024 + (k & 3) * 2, 1);
                wg_commit();
                bar_arrive(other_bar, 256);
                wg_wait<1>(); release(c, BAR_EMPTY + 8 * last, 1);
                wg_wait<0>(); release(c, BAR_EMPTY + 8 * cx.slot, 1); release(c, BAR_EMPTY + 8 * cur.slot, 1);
                PROF_EV(21);
                cur.adv();
                fence_regs(acc);
                int tile = blk_of(kq >> 1, t, rot) * 2 + (kq & 1);
#pragma unroll
                for (int i = 0; i < 64; i++) acc[i] *= SM_SCALE;
                store_proj(acc, g_Q + (size_t)(hq * 32 + tile * 2) * 16384, c, policy_normal());
                signal_event(c, 1 + t);
            }
        }
        float o[64], l[2];
        {
            uint32_t q[32], p[32];
            float m[2], lprev[2];
#pragma unroll
            for (int i = 0; i < 64; i++) o[i] = 0.f;
#pragma unroll
            for (int i = 0; i < 32; i++) p[i] = 0u;
            m[0] = m[1] = l[0] = l[1] = lprev[0] = lprev[1] = 0.f;
            bool gen = false;
            int pv_acc = 0; bool pv_half = true; uint32_t pv_cnt = 0;
            int pending = 0; Cur ce = cur;
#pragma unroll 1
            for (int r = 0; r < 4; r++) {
                const int pb = blk_of(a, r, rot);
                const bool heavy = ((r & 1) == w);
                const bool half = (((heavy ? 3 - rank : rank)) & 1) == 0;
                mbar_wait(misc + BAR_FULL + 8 * cur.slot, cur.ph);
                const uint32_t z = load_afrag<8, 0>(q, ring + cur.slot * SLOT_BYTES + w * 16384, c);
                release(c, BAR_EMPTY + 8 * cur.slot + z, 1);
                cur.adv();
                Cur ck = cur; cur.adv();
                Cur cv = ck, cen = cur;
                if (r > 0) { cv = cur; cur.adv(); cen = cur; cur.adv(); }
                if (!heavy) { ck = cur; cur.adv(); cur.adv(); if (r == 0) cv = ck; }
                const int nsteps = 2 * pb + (heavy ? 2 : 1);
                int j = 0;
                if (half) {
                    mbar_wait(misc + BAR_FULL + 8 * ck.slot, ck.ph);
                    mbar_wait(misc + BAR_FULL + 8 * cv.slot, cv.ph);
                    bar_sync(my_bar, 256);
                    PROF_EV(30);
                    float s[32];
                    undef_regs(s);
                    issue_qk_half(s, q, ring + ck.slot * SLOT_BYTES);
                    if (pending) stage_ctx(o, lprev, ce, pending, c);
                    issue_pv(o, p, ring + cv.slot * SLOT_BYTES, pv_acc, pv_half);
                    bar_arrive(other_bar, 256);
                    wg_wait<1>();
                    fence_regs(s);
                    lprev[0] = l[0]; lprev[1] = l[1];
                    mask_diag<0>(s, c);
                    gen = softmax_first<8>(s, m, l);
                    wg_wait<0>();
                    fence_regs(o);
                    fence_regs(s);
                    release(c, BAR_EMPTY + 8 * ck.slot, heavy ? 2 : 1);
                    if (pv_cnt) release(c, BAR_EMPTY + 8 * cv.slot, pv_cnt);
#pragma unroll
                    for (int i = 0; i < 16; i++) p[i] = pack_bf16(s[2 * i], s[2 * i + 1]);
                    pv_acc = 0; pv_half = true; pv_cnt = heavy ? 2 : 1;
                    pending = r ? 4 + r : 0; ce = cen;
                    j = 1;
                }
#pragma unroll 1
                for (; j < nsteps; j++) {
                    const bool first = j == 0;
                    if (!first) { ck = cur; cur.adv(); cv = cur; cur.adv(); }
                    mbar_wait(misc + BAR_FULL + 8 * ck.slot, ck.ph);
                    mbar_wait(misc + BAR_FULL + 8 * cv.slot, cv.ph);
                    bar_sync(my_bar, 256);
                    PROF_EV(first ? 30 : 31);
                    float s[64];
                    undef_regs(s);
                    issue_qk(s, q, ring + ck.slot * SLOT_BYTES);
                    if (pending) stage_ctx(o, lprev, ce, pending, c);
                    issue_pv(o, p, ring + cv.slot * SLOT_BYTES, pv_acc, pv_half);
                    bar_arrive(other_bar, 256);
                    wg_wait<1>();
                    fence_regs(s);
                    if (first) {
                        lprev[0] = l[0]; lprev[1] = l[1];
                        l[0] = l[1] = m[0] = m[1] = 0.f;
                        gen = false;
                        mask_diag<8>(s, c);
                    }
                    bool redo = false;
                    if (!gen) {
                        float l0 = l[0], l1 = l[1];
                        exp_sum<16, false>(s, m, l0, l1);
                        const float lo = first ? 1.0f / SAFE_SUM : 0.f;
                        redo = __any_sync(0xffffffffu, !(l0 <= SAFE_SUM && l1 <= SAFE_SUM && l0 >= lo && l1 >= lo));
                        if (!redo) { l[0] = l0; l[1] = l1; }
                    }
                    wg_wait<0>();
                    fence_regs(o);
                    fence_regs(s);
                    if (gen | redo) {
                        if (redo) {
                            recompute_scores(s, q, ring + ck.slot * SLOT_BYTES, c);
                            if (first) { mask_diag<8>(s, c); m[0] = m[1] = -INFINITY; }
                        }
                        gen = true;
                        float mx[2], alpha[2];
                        row_max<16>(s, mx);
#pragma unroll
                        for (int i = 0; i < 2; i++) {
                            mx[i] = fmaxf(mx[i], m[i]);
                            alpha[i] = first ? 1.0f : ex2(m[i] - mx[i]);
                            m[i] = mx[i];
                            l[i] *= alpha[i];
                        }
                        exp_sum<16, true>(s, m, l[0], l[1]);
#pragma unroll
                        for (int i = 0; i < 64; i++) o[i] *= alpha[(i >> 1) & 1];
                    }
                    release(c, BAR_EMPTY + 8 * ck.slot, first && heavy ? 2 : 1);
                    if (pv_cnt) release(c, BAR_EMPTY + 8 * cv.slot, pv_cnt);
#pragma unroll
                    for (int i = 0; i < 32; i++) p[i] = pack_bf16(s[2 * i], s[2 * i + 1]);
                    pv_acc = first ? 0 : 1; pv_half = false; pv_cnt = first && heavy ? 2 : 1;
                    pending = first && r ? 4 + r : 0; ce = cen;
                }
            }
            if (pending) stage_ctx(o, lprev, ce, pending, c);
            mbar_wait(misc + BAR_FULL + 8 * cur.slot, cur.ph);
            bar_sync(my_bar, 256);
            PROF_EV(32);
            issue_pv(o, p, ring + cur.slot * SLOT_BYTES, pv_acc, pv_half);
            if (w == 0) bar_arrive(other_bar, 256);
            wg_wait<0>();
            release(c, BAR_EMPTY + 8 * cur.slot, pv_cnt);
            fence_regs(o);
            cur.adv();
        }
        {
            float acc[80];
            undef_regs(acc);
            int st = 0, prev = 0; uint32_t ph3 = 0;
            auto op_stage = [&](int i) {
                mbar_wait(misc + BAR_FULL3 + 8 * st, ph3);
                uint32_t base = ring + st * ST3_BYTES;
                uint64_t da = mkdesc(base + w * 8192, 16, 1024, 1);
                uint64_t db = mkdesc(base + 16384, 2048, 512, 2);
                wg_fence();
#pragma unroll
                for (int k = 0; k < 4; k++) wgmma_ss_n160_ta0_tb1(acc, da + 2 * k, db + (k >> 1) * 640 + (k & 1) * 64, k ? 1 : i);
                wg_commit();
                if (i > 0) { wg_wait<1>(); if (i <= 32 - NST3) release(c, BAR_EMPTY3 + 8 * prev, 1); }
                prev = st;
                if (++st == NST3) { st = 0; ph3 ^= 1; }
            };
            PROF_EV(40);
            op_stage(0);
            stage_ctx(o, l, cur, 8, c);
#pragma unroll 1
            for (int i = 1; i < 22; i++) op_stage(i);
            mbar_wait(misc + BAR_SEL, 0);
            const uint32_t tag = lds32(misc + MISC_EPOCH) & 1;
            const int g = c.lane >> 2, t = c.lane & 3;
            const int row = (2 * u3 + rank) * 128 + 64 * w + perm32(16 * c.warp + 8 * kap + (((g & 3) << 1) | (g >> 2)));
            const int col = 160 * s3 + 8 * t;
            int sel = -1;
#pragma unroll
            for (int i = 0; i < TOPC; i++) if ((int)lds32(misc + MISC_SEL + 4 * i) == row) sel = i;
            uint4 xv[5], bv[5];
#pragma unroll
            for (int i = 0; i < 5; i++) {
                xv[i] = ldg128(P.x + (size_t)row * DM + col + 32 * i);
                bv[i] = ldg128(sel >= 0 ? (const void*)(g_brow + sel * DM + col + 32 * i) : (const void*)xn_addr(row, col + 32 * i));
            }
#pragma unroll 1
            for (int i = 22; i < 32; i++) op_stage(i);
            wg_wait<0>();
            fence_regs(acc);
            PROF_EV(41);
            const int t256 = tid - 128;
            uint4* sendp = g_part + (size_t)blockIdx.x * 2560 + t256;
            float keep[40];
#pragma unroll
            for (int j = 0; j < 10; j++) {
                uint32_t v0 = __float_as_uint(kap ? acc[8 * j + 0] : acc[8 * j + 2]), v1 = __float_as_uint(kap ? acc[8 * j + 1] : acc[8 * j + 3]);
                uint32_t v2 = __float_as_uint(kap ? acc[8 * j + 4] : acc[8 * j + 6]), v3 = __float_as_uint(kap ? acc[8 * j + 5] : acc[8 * j + 7]);
                asm volatile("st.relaxed.gpu.global.v4.b32 [%0], {%1,%2,%3,%4};" ::"l"(sendp + j * 256),
                             "r"((v0 & ~1u) | tag), "r"((v1 & ~1u) | tag), "r"((v2 & ~1u) | tag), "r"((v3 & ~1u) | tag) : "memory");
                keep[4 * j + 0] = kap ? acc[8 * j + 2] : acc[8 * j + 0]; keep[4 * j + 1] = kap ? acc[8 * j + 3] : acc[8 * j + 1];
                keep[4 * j + 2] = kap ? acc[8 * j + 6] : acc[8 * j + 4]; keep[4 * j + 3] = kap ? acc[8 * j + 7] : acc[8 * j + 5];
            }
            const uint4* recvp = g_part + (size_t)(blockIdx.x ^ 2) * 2560 + t256;
            uint4 rv[10];
            int spins = 0;
            while (true) {
                uint32_t v;
                asm volatile("ld.relaxed.gpu.global.b32 %0, [%1];" : "=r"(v) : "l"(recvp + 9 * 256) : "memory");
                if (__all_sync(0xffffffffu, (v & 1u) == tag) || ++spins > 2000000) break;
                __nanosleep(20);
            }
            while (true) {
                uint32_t all_and = 1u, all_or = 0u;
#pragma unroll
                for (int j = 0; j < 10; j++) {
                    asm volatile("ld.relaxed.gpu.global.v4.b32 {%0,%1,%2,%3}, [%4];"
                                 : "=r"(rv[j].x), "=r"(rv[j].y), "=r"(rv[j].z), "=r"(rv[j].w) : "l"(recvp + j * 256) : "memory");
                }
#pragma unroll
                for (int j = 0; j < 10; j++) {
                    all_and &= rv[j].x & rv[j].y & rv[j].z & rv[j].w;
                    all_or |= rv[j].x | rv[j].y | rv[j].z | rv[j].w;
                }
                bool ok = ((tag ? all_and : all_or) & 1u) == tag;
                if (__all_sync(0xffffffffu, ok) || ++spins > 2000000) break;
            }
            uint32_t pk[20];
#pragma unroll
            for (int j = 0; j < 10; j++) {
                pk[2 * j] = pack_bf16(keep[4 * j] + __uint_as_float(rv[j].x & ~1u), keep[4 * j + 1] + __uint_as_float(rv[j].y & ~1u));
                pk[2 * j + 1] = pack_bf16(keep[4 * j + 2] + __uint_as_float(rv[j].z & ~1u), keep[4 * j + 3] + __uint_as_float(rv[j].w & ~1u));
            }
#pragma unroll
            for (int i = 0; i < 5; i++) {
                uint32_t a0 = pk[4 * i], a1 = pk[4 * i + 1], a2 = pk[4 * i + 2], a3 = pk[4 * i + 3];
                uint32_t x0 = (t & 1) ? a0 : a1, x1 = (t & 1) ? a2 : a3;
                x0 = __shfl_xor_sync(0xffffffffu, x0, 1); x1 = __shfl_xor_sync(0xffffffffu, x1, 1);
                if (t & 1) { a0 = x0; a2 = x1; } else { a1 = x0; a3 = x1; }
                x0 = (t & 2) ? a0 : a2; x1 = (t & 2) ? a1 : a3;
                x0 = __shfl_xor_sync(0xffffffffu, x0, 2); x1 = __shfl_xor_sync(0xffffffffu, x1, 2);
                if (t & 2) { a0 = x0; a1 = x1; } else { a2 = x0; a3 = x1; }
                uint32_t av[4] = {a0, a1, a2, a3};
                uint32_t xx[4] = {xv[i].x, xv[i].y, xv[i].z, xv[i].w}, bb[4] = {bv[i].x, bv[i].y, bv[i].z, bv[i].w};
                uint32_t ov[4];
#pragma unroll
                for (int e = 0; e < 4; e++) {
                    uint32_t t1 = pack_bf16(bf_lo(xx[e]) + bf_lo(av[e]), bf_hi(xx[e]) + bf_hi(av[e]));
                    ov[e] = pack_bf16(bf_lo(t1) + bf_lo(bb[e]), bf_hi(t1) + bf_hi(bb[e]));
                }
                stg128(P.out + (size_t)row * DM + col + 32 * i, ov[0], ov[1], ov[2], ov[3]);
            }
            PROF_EV(42); PROF_GT(43);
        }
    }
}

typedef CUresult (*EncodeFn)(CUtensorMap*, CUtensorMapDataType, cuuint32_t, void*, const cuuint64_t*, const cuuint64_t*, const cuuint32_t*,
                             const cuuint32_t*, CUtensorMapInterleave, CUtensorMapSwizzle, CUtensorMapL2promotion, CUtensorMapFloatOOBfill);

void make_map2d(EncodeFn enc, CUtensorMap* tm, const void* p, uint64_t cols, uint64_t rows) {
    cuuint64_t gd[2] = {cols, rows}, gs[1] = {cols * 2};
    cuuint32_t box[2] = {64, 128}, es[2] = {1, 1};
    enc(tm, CU_TENSOR_MAP_DATA_TYPE_BFLOAT16, 2, const_cast<void*>(p), gd, gs, box, es, CU_TENSOR_MAP_INTERLEAVE_NONE,
        CU_TENSOR_MAP_SWIZZLE_128B, CU_TENSOR_MAP_L2_PROMOTION_L2_128B, CU_TENSOR_MAP_FLOAT_OOB_FILL_NONE);
}

void make_map3d(EncodeFn enc, CUtensorMap* tm, const void* p, uint64_t cols, uint64_t rows, uint32_t bw, uint32_t nb) {
    cuuint64_t gd[3] = {bw, rows, cols / bw}, gs[2] = {cols * 2, bw * 2};
    cuuint32_t box[3] = {bw, 32, nb}, es[3] = {1, 1, 1};
    enc(tm, CU_TENSOR_MAP_DATA_TYPE_BFLOAT16, 3, const_cast<void*>(p), gd, gs, box, es, CU_TENSOR_MAP_INTERLEAVE_NONE,
        bw == 64 ? CU_TENSOR_MAP_SWIZZLE_128B : CU_TENSOR_MAP_SWIZZLE_64B, CU_TENSOR_MAP_L2_PROMOTION_L2_128B, CU_TENSOR_MAP_FLOAT_OOB_FILL_NONE);
}

}

extern "C" void kernel_launch(void* const* d_in, const int* in_sizes, int n_in, void* d_out, int out_size) {
    (void)in_sizes; (void)n_in; (void)out_size;
    static EncodeFn enc = nullptr;
    if (!enc) {
        void* fn = nullptr;
        cudaDriverEntryPointQueryResult qr;
        cudaGetDriverEntryPoint("cuTensorMapEncodeTiled", &fn, cudaEnableDefault, &qr);
        enc = (EncodeFn)fn;
        cudaFuncSetAttribute(fused_kernel, cudaFuncAttributeMaxDynamicSharedMemorySize, SMEM_BYTES);
    }
    CUtensorMap tmC, tmWk, tmWv, tmWq, tmWo, tmG, tmU, tmD;
    make_map2d(enc, &tmC, d_in[1], DC, SEQ);
    make_map2d(enc, &tmWq, d_in[2], 4096, DM);
    make_map2d(enc, &tmWk, d_in[3], 4096, DC);
    make_map2d(enc, &tmWv, d_in[4], 4096, DC);
    make_map3d(enc, &tmWo, d_in[5], DM, 4096, 32, 5);
    make_map3d(enc, &tmG, d_in[8], FF, DM, 64, 7);
    make_map3d(enc, &tmU, d_in[9], FF, DM, 64, 7);
    make_map3d(enc, &tmD, d_in[10], DM, FF, 64, 10);
    Params P;
    P.x = (const __nv_bfloat16*)d_in[0];
    P.wq = (const __nv_bfloat16*)d_in[2];
    P.wo = (const __nv_bfloat16*)d_in[5];
    P.wr = (const __nv_bfloat16*)d_in[7];
    P.out = (__nv_bfloat16*)d_out;
    fused_kernel<<<132, 384, SMEM_BYTES>>>(tmC, tmWk, tmWv, tmWq, tmWo, tmG, tmU, tmD, P);
}
```

```cpp
#include <cuda_runtime.h>
#include <cuda_bf16.h>
#include <cuda.h>
#include <stdint.h>

namespace {

constexpr int SEQ = 2048, NH = 32, DM = 640, DC = 512, FF = 1728, TOPC = 8;
constexpr int NSLOT = 7, SLOT_BYTES = 32768;
constexpr int NST3 = 6, ST3_BYTES = 36864;
constexpr int RING_BYTES = NSLOT * SLOT_BYTES;
constexpr int SMEM_BYTES = RING_BYTES + 3072;

constexpr int BAR_FULL = 0, BAR_EMPTY = 64, BAR_FULL3 = 128, BAR_EMPTY3 = 192, BAR_EV = 256  , BAR_LN = 416, BAR_PF = 424  , BAR_SEL = 440,
              MISC_EPOCH = 448, MISC_SEL = 464, BAR_DEP = 512  , BAR_W = 672  , MISC_WR = 768  ;

constexpr int FL_LN = 0, FL_MOE_CNT = 1, FL_MOE_DONE = 2, FL_KV = 8  , FL_Q = 64  , FL_CTX = 320  , FL_TOTAL = 576;

__device__ __align__(1024) unsigned char g_K[NH * 32 * 16384];
__device__ __align__(1024) unsigned char g_V[NH * 32 * 16384];
__device__ __align__(1024) unsigned char g_Q[NH * 32 * 16384];
__device__ __align__(1024) unsigned char g_xn[16 * 10 * 16384];
__device__ __align__(1024) uint4 g_part[128 * 10 * 256];
__device__ float g_router[SEQ];
__device__ __align__(16) float g_moe_part[4 * TOPC * DM];
__device__ __align__(16) __nv_bfloat16 g_brow[TOPC * DM];
__device__ __align__(16) int g_sel[TOPC];
__device__ unsigned g_flags[FL_TOTAL * 8];
__device__ unsigned g_epoch;

struct Params {
    const __nv_bfloat16 *x, *wr, *wq, *wo;
    __nv_bfloat16* out;
};

__device__ __forceinline__ uint32_t smem_u32(const void* p) { return (uint32_t)__cvta_generic_to_shared(p); }
__device__ __forceinline__ void mbar_init(uint32_t bar, int cnt) { asm volatile("mbarrier.init.shared::cta.b64 [%0], %1;" ::"r"(bar), "r"(cnt)); }
__device__ __forceinline__ void mbar_expect_tx(uint32_t bar, uint32_t bytes) {
    asm volatile("mbarrier.arrive.expect_tx.shared::cta.b64 _, [%0], %1;" ::"r"(bar), "r"(bytes) : "memory");
}
__device__ __forceinline__ void mbar_arrive(uint32_t bar) { asm volatile("mbarrier.arrive.shared::cta.b64 _, [%0];" ::"r"(bar) : "memory"); }
__device__ __forceinline__ void mbar_arrive_cluster(uint32_t cluster_addr, uint32_t cnt) {
    asm volatile("mbarrier.arrive.shared::cluster.b64 _, [%0], %1;" ::"r"(cluster_addr), "r"(cnt) : "memory");
}
__device__ __forceinline__ uint32_t mapa(uint32_t addr, uint32_t cta) {
    uint32_t r; asm("mapa.shared::cluster.u32 %0, %1, %2;" : "=r"(r) : "r"(addr), "r"(cta)); return r;
}
__device__ __forceinline__ void mbar_wait(uint32_t bar, uint32_t parity) {
    asm volatile(
        "{\n.reg .pred p;\n.reg .u32 n;\n"
        "mbarrier.try_wait.parity.shared::cta.b64 p, [%0], %1;\n"
        "@p bra DONE;\n"
        "mov.u32 n, 0;\n"
        "LAB_WAIT:\n"
        "mbarrier.try_wait.parity.shared::cta.b64 p, [%0], %1, 100000;\n"
        "@p bra DONE;\n"
        "add.u32 n, n, 1;\n"
        "setp.lt.u32 p, n, 200000;\n"
        "@p bra LAB_WAIT;\n"
        "trap;\n"
        "DONE:\n}\n" ::"r"(bar), "r"(parity) : "memory");
}
__device__ __forceinline__ void mbar_wait_hot(uint32_t bar, uint32_t parity) {
    asm volatile("{\n.reg .pred p;\nLAB_WAIT:\nmbarrier.try_wait.parity.shared::cta.b64 p, [%0], %1;\n@!p bra LAB_WAIT;\n}\n" ::"r"(bar), "r"(parity) : "memory");
}
__device__ __forceinline__ void flag_wait(const unsigned* flag, unsigned target) {
    asm volatile(
        "{\n.reg .pred p;\n.reg .u32 n, v;\n.reg .s32 d;\n"
        "mov.u32 n, 0;\n"
        "LAB_WAIT:\n"
        "ld.acquire.gpu.global.u32 v, [%0];\n"
        "sub.s32 d, v, %1;\n"
        "setp.ge.s32 p, d, 0;\n"
        "@p bra DONE;\n"
        "nanosleep.u32 40;\n"
        "add.u32 n, n, 1;\n"
        "setp.lt.u32 p, n, 3000000;\n"
        "@p bra LAB_WAIT;\n"
        "trap;\n"
        "DONE:\n}\n" ::"l"(flag), "r"(target) : "memory");
}
__device__ __forceinline__ void flag_signal(unsigned* flag) {
    asm volatile("red.release.gpu.global.add.u32 [%0], 1;" ::"l"(flag) : "memory");
}
__device__ __forceinline__ void fence_async_global() { asm volatile("fence.proxy.async.global;" ::: "memory"); }
__device__ __forceinline__ unsigned* flag_ptr(int idx) { return g_flags + idx * 8; }

__device__ __forceinline__ uint64_t policy_stream() {
    uint64_t p; asm("createpolicy.fractional.L2::evict_first.b64 %0, 1.0;" : "=l"(p)); return p;
}
__device__ __forceinline__ uint64_t policy_normal() {
    uint64_t p; asm("createpolicy.fractional.L2::evict_normal.b64 %0, 1.0;" : "=l"(p)); return p;
}
__device__ __forceinline__ void bulk_load(uint32_t dst, const void* src, uint32_t bytes, uint32_t bar) {
    asm volatile("cp.async.bulk.shared::cluster.global.mbarrier::complete_tx::bytes [%0], [%1], %2, [%3];"
                 ::"r"(dst), "l"(src), "r"(bytes), "r"(bar) : "memory");
}
__device__ __forceinline__ void bulk_load_mc(uint32_t dst, const void* src, uint32_t bytes, uint32_t bar) {
    asm volatile("cp.async.bulk.shared::cluster.global.mbarrier::complete_tx::bytes.multicast::cluster [%0], [%1], %2, [%3], %4;"
                 ::"r"(dst), "l"(src), "r"(bytes), "r"(bar), "h"((uint16_t)3) : "memory");
}
__device__ __forceinline__ void tma2d(uint32_t dst, const CUtensorMap* tm, int c0, int c1, uint32_t bar) {
    asm volatile("cp.async.bulk.tensor.2d.shared::cluster.global.mbarrier::complete_tx::bytes [%0], [%1, {%3, %4}], [%2];"
                 ::"r"(dst), "l"(tm), "r"(bar), "r"(c0), "r"(c1) : "memory");
}
__device__ __forceinline__ void tma2d_mc(uint32_t dst, const CUtensorMap* tm, int c0, int c1, uint32_t bar) {
    asm volatile("cp.async.bulk.tensor.2d.shared::cluster.global.mbarrier::complete_tx::bytes.multicast::cluster [%0], [%1, {%3, %4}], [%2], %5;"
                 ::"r"(dst), "l"(tm), "r"(bar), "r"(c0), "r"(c1), "h"((uint16_t)3) : "memory");
}
__device__ __forceinline__ void tma3d_mc(uint32_t dst, const CUtensorMap* tm, int c0, int c1, int c2, uint32_t bar) {
    asm volatile("cp.async.bulk.tensor.3d.shared::cluster.global.mbarrier::complete_tx::bytes.multicast::cluster [%0], [%1, {%3, %4, %5}], [%2], %6;"
                 ::"r"(dst), "l"(tm), "r"(bar), "r"(c0), "r"(c1), "r"(c2), "h"((uint16_t)3) : "memory");
}
__device__ __forceinline__ void tma3d(uint32_t dst, const CUtensorMap* tm, int c0, int c1, int c2, uint32_t bar) {
    asm volatile("cp.async.bulk.tensor.3d.shared::cluster.global.mbarrier::complete_tx::bytes.L2::cache_hint [%0], [%1, {%3, %4, %5}], [%2], %6;"
                 ::"r"(dst), "l"(tm), "r"(bar), "r"(c0), "r"(c1), "r"(c2), "l"(policy_stream()) : "memory");
}
__device__ __forceinline__ void tma3d_prefetch(const CUtensorMap* tm, int c0, int c1, int c2) {
    asm volatile("cp.async.bulk.prefetch.tensor.3d.L2.global [%0, {%1, %2, %3}];" ::"l"(tm), "r"(c0), "r"(c1), "r"(c2) : "memory");
}
__device__ __forceinline__ void l2_prefetch(const void* p, uint32_t bytes) {
    asm volatile("cp.async.bulk.prefetch.L2.global [%0], %1;" ::"l"(p), "r"(bytes) : "memory");
}
__device__ __forceinline__ bool elect_one() {
    uint32_t r; asm volatile("{\n.reg .pred p;\nelect.sync _|p, 0xffffffff;\nselp.u32 %0, 1, 0, p;\n}\n" : "=r"(r)); return r != 0;
}
__device__ __forceinline__ void wg_fence() { asm volatile("wgmma.fence.sync.aligned;" ::: "memory"); }
__device__ __forceinline__ void wg_commit() { asm volatile("wgmma.commit_group.sync.aligned;" ::: "memory"); }
template <int N> __device__ __forceinline__ void wg_wait() { asm volatile("wgmma.wait_group.sync.aligned %0;" ::"n"(N) : "memory"); }
__device__ __forceinline__ void bar_sync(int id, int n) { asm volatile("bar.sync %0, %1;" ::"r"(id), "r"(n) : "memory"); }
__device__ __forceinline__ void bar_arrive(int id, int n) { asm volatile("bar.arrive %0, %1;" ::"r"(id), "r"(n) : "memory"); }
template <int N> __device__ __forceinline__ void fence_regs(float (&a)[N]) {
#pragma unroll
    for (int i = 0; i < N; i++) asm volatile("" : "+f"(a[i])::"memory");
}
template <int N> __device__ __forceinline__ void undef_regs(float (&a)[N]) {
#pragma unroll
    for (int i = 0; i < N; i++) asm volatile("" : "=f"(a[i]));
}
__device__ __forceinline__ void ldsm4t(uint32_t& r0, uint32_t& r1, uint32_t& r2, uint32_t& r3, uint32_t addr) {
    asm volatile("ldmatrix.sync.aligned.m8n8.x4.trans.shared.b16 {%0,%1,%2,%3}, [%4];"
                 : "=r"(r0), "=r"(r1), "=r"(r2), "=r"(r3) : "r"(addr) : "memory");
}
__device__ __forceinline__ uint32_t pack_bf16(float lo, float hi) {
    uint32_t r; asm("cvt.rn.bf16x2.f32 %0, %1, %2;" : "=r"(r) : "f"(hi), "f"(lo)); return r;
}
__device__ __forceinline__ float bf_lo(uint32_t v) { return __uint_as_float(v << 16); }
__device__ __forceinline__ float bf_hi(uint32_t v) { return __uint_as_float(v & 0xffff0000u); }
__device__ __forceinline__ float bf_round(float v) { return __bfloat162float(__float2bfloat16_rn(v)); }
__device__ __forceinline__ float ex2(float v) { float r; asm("ex2.approx.ftz.f32 %0, %1;" : "=f"(r) : "f"(v)); return r; }
__device__ __forceinline__ void ex2v(float& v) { asm volatile("ex2.approx.ftz.f32 %0, %0;" : "+f"(v)); }
__device__ __forceinline__ float rcp_fast(float v) { float r; asm("rcp.approx.ftz.f32 %0, %1;" : "=f"(r) : "f"(v)); return r; }
__device__ __forceinline__ float sqrt_fast(float v) { float r; asm("sqrt.approx.ftz.f32 %0, %1;" : "=f"(r) : "f"(v)); return r; }
__device__ __forceinline__ void stg128(void* p, uint32_t a, uint32_t b, uint32_t c, uint32_t d) {
    asm volatile("st.global.v4.b32 [%0], {%1,%2,%3,%4};" ::"l"(p), "r"(a), "r"(b), "r"(c), "r"(d) : "memory");
}
__device__ __forceinline__ void stg128_hint(void* p, uint32_t a, uint32_t b, uint32_t c, uint32_t d, uint64_t pol) {
    asm volatile("st.global.L2::cache_hint.v4.b32 [%0], {%1,%2,%3,%4}, %5;" ::"l"(p), "r"(a), "r"(b), "r"(c), "r"(d), "l"(pol) : "memory");
}
__device__ __forceinline__ uint4 ldg128(const void* p) {
    uint4 v; asm volatile("ld.global.cg.v4.b32 {%0,%1,%2,%3}, [%4];" : "=r"(v.x), "=r"(v.y), "=r"(v.z), "=r"(v.w) : "l"(p) : "memory"); return v;
}
__device__ __forceinline__ uint64_t mkdesc(uint32_t addr, uint32_t lbo, uint32_t sbo, uint32_t swz) {
    uint32_t lo = ((addr & 0x3FFFF) >> 4) | ((lbo >> 4) << 16);
    uint32_t hi = (sbo >> 4) | (swz << 30);
    return ((uint64_t)hi << 32) | lo;
}
__device__ __forceinline__ int perm32(int v) { return (v & ~30) | ((v >> 2) & 6) | ((v << 2) & 24); }

__device__ __forceinline__ void wgmma_rs_n128_ta0_tb0(float (&d)[64], uint32_t a0, uint32_t a1, uint32_t a2, uint32_t a3, uint64_t descB, int scaleD) {
  asm volatile("{\n.reg .pred p;\nsetp.ne.b32 p, %69, 0;\n"
    "wgmma.mma_async.sync.aligned.m64n128k16.f32.bf16.bf16 "
    "{%0, %1, %2, %3, %4, %5, %6, %7, %8, %9, %10, %11, %12, %13, %14, %15, %16, %17, %18, %19, %20, %21, %22, %23, %24, %25, %26, %27, %28, %29, %30, %31, %32, %33, %34, %35, %36, %37, %38, %39, %40, %41, %42, %43, %44, %45, %46, %47, %48, %49, %50, %51, %52, %53, %54, %55, %56, %57, %58, %59, %60, %61, %62, %63}, "
    "{%64, %65, %66, %67}, %68, p, 1, 1, 0;\n}\n"
    : "+f"(d[0]), "+f"(d[1]), "+f"(d[2]), "+f"(d[3]), "+f"(d[4]), "+f"(d[5]), "+f"(d[6]), "+f"(d[7]), "+f"(d[8]), "+f"(d[9]), "+f"(d[10]), "+f"(d[11]), "+f"(d[12]), "+f"(d[13]), "+f"(d[14]), "+f"(d[15]), "+f"(d[16]), "+f"(d[17]), "+f"(d[18]), "+f"(d[19]), "+f"(d[20]), "+f"(d[21]), "+f"(d[22]), "+f"(d[23]), "+f"(d[24]), "+f"(d[25]), "+f"(d[26]), "+f"(d[27]), "+f"(d[28]), "+f"(d[29]), "+f"(d[30]), "+f"(d[31]), "+f"(d[32]), "+f"(d[33]), "+f"(d[34]), "+f"(d[35]), "+f"(d[36]), "+f"(d[37]), "+f"(d[38]), "+f"(d[39]), "+f"(d[40]), "+f"(d[41]), "+f"(d[42]), "+f"(d[43]), "+f"(d[44]), "+f"(d[45]), "+f"(d[46]), "+f"(d[47]), "+f"(d[48]), "+f"(d[49]), "+f"(d[50]), "+f"(d[51]), "+f"(d[52]), "+f"(d[53]), "+f"(d[54]), "+f"(d[55]), "+f"(d[56]), "+f"(d[57]), "+f"(d[58]), "+f"(d[59]), "+f"(d[60]), "+f"(d[61]), "+f"(d[62]), "+f"(d[63])
    : "r"(a0), "r"(a1), "r"(a2), "r"(a3), "l"(descB), "r"(scaleD));
}
__device__ __forceinline__ void wgmma_rs_n128_ta0_tb1(float (&d)[64], uint32_t a0, uint32_t a1, uint32_t a2, uint32_t a3, uint64_t descB, int scaleD) {
  asm volatile("{\n.reg .pred p;\nsetp.ne.b32 p, %69, 0;\n"
    "wgmma.mma_async.sync.aligned.m64n128k16.f32.bf16.bf16 "
    "{%0, %1, %2, %3, %4, %5, %6, %7, %8, %9, %10, %11, %12, %13, %14, %15, %16, %17, %18, %19, %20, %21, %22, %23, %24, %25, %26, %27, %28, %29, %30, %31, %32, %33, %34, %35, %36, %37, %38, %39, %40, %41, %42, %43, %44, %45, %46, %47, %48, %49, %50, %51, %52, %53, %54, %55, %56, %57, %58, %59, %60, %61, %62, %63}, "
    "{%64, %65, %66, %67}, %68, p, 1, 1, 1;\n}\n"
    : "+f"(d[0]), "+f"(d[1]), "+f"(d[2]), "+f"(d[3]), "+f"(d[4]), "+f"(d[5]), "+f"(d[6]), "+f"(d[7]), "+f"(d[8]), "+f"(d[9]), "+f"(d[10]), "+f"(d[11]), "+f"(d[12]), "+f"(d[13]), "+f"(d[14]), "+f"(d[15]), "+f"(d[16]), "+f"(d[17]), "+f"(d[18]), "+f"(d[19]), "+f"(d[20]), "+f"(d[21]), "+f"(d[22]), "+f"(d[23]), "+f"(d[24]), "+f"(d[25]), "+f"(d[26]), "+f"(d[27]), "+f"(d[28]), "+f"(d[29]), "+f"(d[30]), "+f"(d[31]), "+f"(d[32]), "+f"(d[33]), "+f"(d[34]), "+f"(d[35]), "+f"(d[36]), "+f"(d[37]), "+f"(d[38]), "+f"(d[39]), "+f"(d[40]), "+f"(d[41]), "+f"(d[42]), "+f"(d[43]), "+f"(d[44]), "+f"(d[45]), "+f"(d[46]), "+f"(d[47]), "+f"(d[48]), "+f"(d[49]), "+f"(d[50]), "+f"(d[51]), "+f"(d[52]), "+f"(d[53]), "+f"(d[54]), "+f"(d[55]), "+f"(d[56]), "+f"(d[57]), "+f"(d[58]), "+f"(d[59]), "+f"(d[60]), "+f"(d[61]), "+f"(d[62]), "+f"(d[63])
    : "r"(a0), "r"(a1), "r"(a2), "r"(a3), "l"(descB), "r"(scaleD));
}
__device__ __forceinline__ void wgmma_rs_n64_ta0_tb1(float (&d)[32], uint32_t a0, uint32_t a1, uint32_t a2, uint32_t a3, uint64_t descB, int scaleD) {
  asm volatile("{\n.reg .pred p;\nsetp.ne.b32 p, %37, 0;\n"
    "wgmma.mma_async.sync.aligned.m64n64k16.f32.bf16.bf16 "
    "{%0, %1, %2, %3, %4, %5, %6, %7, %8, %9, %10, %11, %12, %13, %14, %15, %16, %17, %18, %19, %20, %21, %22, %23, %24, %25, %26, %27, %28, %29, %30, %31}, "
    "{%32, %33, %34, %35}, %36, p, 1, 1, 1;\n}\n"
    : "+f"(d[0]), "+f"(d[1]), "+f"(d[2]), "+f"(d[3]), "+f"(d[4]), "+f"(d[5]), "+f"(d[6]), "+f"(d[7]), "+f"(d[8]), "+f"(d[9]), "+f"(d[10]), "+f"(d[11]), "+f"(d[12]), "+f"(d[13]), "+f"(d[14]), "+f"(d[15]), "+f"(d[16]), "+f"(d[17]), "+f"(d[18]), "+f"(d[19]), "+f"(d[20]), "+f"(d[21]), "+f"(d[22]), "+f"(d[23]), "+f"(d[24]), "+f"(d[25]), "+f"(d[26]), "+f"(d[27]), "+f"(d[28]), "+f"(d[29]), "+f"(d[30]), "+f"(d[31])
    : "r"(a0), "r"(a1), "r"(a2), "r"(a3), "l"(descB), "r"(scaleD));
}
__device__ __forceinline__ void wgmma_ss_n128_ta1_tb0(float (&d)[64], uint64_t descA, uint64_t descB, int scaleD) {
  asm volatile("{\n.reg .pred p;\nsetp.ne.b32 p, %66, 0;\n"
    "wgmma.mma_async.sync.aligned.m64n128k16.f32.bf16.bf16 "
    "{%0, %1, %2, %3, %4, %5, %6, %7, %8, %9, %10, %11, %12, %13, %14, %15, %16, %17, %18, %19, %20, %21, %22, %23, %24, %25, %26, %27, %28, %29, %30, %31, %32, %33, %34, %35, %36, %37, %38, %39, %40, %41, %42, %43, %44, %45, %46, %47, %48, %49, %50, %51, %52, %53, %54, %55, %56, %57, %58, %59, %60, %61, %62, %63}, "
    "%64, %65, p, 1, 1, 1, 0;\n}\n"
    : "+f"(d[0]), "+f"(d[1]), "+f"(d[2]), "+f"(d[3]), "+f"(d[4]), "+f"(d[5]), "+f"(d[6]), "+f"(d[7]), "+f"(d[8]), "+f"(d[9]), "+f"(d[10]), "+f"(d[11]), "+f"(d[12]), "+f"(d[13]), "+f"(d[14]), "+f"(d[15]), "+f"(d[16]), "+f"(d[17]), "+f"(d[18]), "+f"(d[19]), "+f"(d[20]), "+f"(d[21]), "+f"(d[22]), "+f"(d[23]), "+f"(d[24]), "+f"(d[25]), "+f"(d[26]), "+f"(d[27]), "+f"(d[28]), "+f"(d[29]), "+f"(d[30]), "+f"(d[31]), "+f"(d[32]), "+f"(d[33]), "+f"(d[34]), "+f"(d[35]), "+f"(d[36]), "+f"(d[37]), "+f"(d[38]), "+f"(d[39]), "+f"(d[40]), "+f"(d[41]), "+f"(d[42]), "+f"(d[43]), "+f"(d[44]), "+f"(d[45]), "+f"(d[46]), "+f"(d[47]), "+f"(d[48]), "+f"(d[49]), "+f"(d[50]), "+f"(d[51]), "+f"(d[52]), "+f"(d[53]), "+f"(d[54]), "+f"(d[55]), "+f"(d[56]), "+f"(d[57]), "+f"(d[58]), "+f"(d[59]), "+f"(d[60]), "+f"(d[61]), "+f"(d[62]), "+f"(d[63])
    : "l"(descA), "l"(descB), "r"(scaleD));
}
__device__ __forceinline__ void wgmma_ss_n160_ta0_tb1(float (&d)[80], uint64_t descA, uint64_t descB, int scaleD) {
  asm volatile("{\n.reg .pred p;\nsetp.ne.b32 p, %82, 0;\n"
    "wgmma.mma_async.sync.aligned.m64n160k16.f32.bf16.bf16 "
    "{%0, %1, %2, %3, %4, %5, %6, %7, %8, %9, %10, %11, %12, %13, %14, %15, %16, %17, %18, %19, %20, %21, %22, %23, %24, %25, %26, %27, %28, %29, %30, %31, %32, %33, %34, %35, %36, %37, %38, %39, %40, %41, %42, %43, %44, %45, %46, %47, %48, %49, %50, %51, %52, %53, %54, %55, %56, %57, %58, %59, %60, %61, %62, %63, %64, %65, %66, %67, %68, %69, %70, %71, %72, %73, %74, %75, %76, %77, %78, %79}, "
    "%80, %81, p, 1, 1, 0, 1;\n}\n"
    : "+f"(d[0]), "+f"(d[1]), "+f"(d[2]), "+f"(d[3]), "+f"(d[4]), "+f"(d[5]), "+f"(d[6]), "+f"(d[7]), "+f"(d[8]), "+f"(d[9]), "+f"(d[10]), "+f"(d[11]), "+f"(d[12]), "+f"(d[13]), "+f"(d[14]), "+f"(d[15]), "+f"(d[16]), "+f"(d[17]), "+f"(d[18]), "+f"(d[19]), "+f"(d[20]), "+f"(d[21]), "+f"(d[22]), "+f"(d[23]), "+f"(d[24]), "+f"(d[25]), "+f"(d[26]), "+f"(d[27]), "+f"(d[28]), "+f"(d[29]), "+f"(d[30]), "+f"(d[31]), "+f"(d[32]), "+f"(d[33]), "+f"(d[34]), "+f"(d[35]), "+f"(d[36]), "+f"(d[37]), "+f"(d[38]), "+f"(d[39]), "+f"(d[40]), "+f"(d[41]), "+f"(d[42]), "+f"(d[43]), "+f"(d[44]), "+f"(d[45]), "+f"(d[46]), "+f"(d[47]), "+f"(d[48]), "+f"(d[49]), "+f"(d[50]), "+f"(d[51]), "+f"(d[52]), "+f"(d[53]), "+f"(d[54]), "+f"(d[55]), "+f"(d[56]), "+f"(d[57]), "+f"(d[58]), "+f"(d[59]), "+f"(d[60]), "+f"(d[61]), "+f"(d[62]), "+f"(d[63]), "+f"(d[64]), "+f"(d[65]), "+f"(d[66]), "+f"(d[67]), "+f"(d[68]), "+f"(d[69]), "+f"(d[70]), "+f"(d[71]), "+f"(d[72]), "+f"(d[73]), "+f"(d[74]), "+f"(d[75]), "+f"(d[76]), "+f"(d[77]), "+f"(d[78]), "+f"(d[79])
    : "l"(descA), "l"(descB), "r"(scaleD));
}

#define PROF_DECL
#define PROF_EV(tag)
#define PROF_GT(tag)

struct Cur {
    uint32_t slot, ph;
    __device__ __forceinline__ void adv() { if (++slot == NSLOT) { slot = 0; ph ^= 1; } }
};
constexpr int E0 = 3;
__host__ __device__ constexpr uint32_t slot_of(int e) { return (e + E0) % NSLOT; }
__device__ __forceinline__ Cur cur_at(int e) { Cur c; c.slot = (e + E0) % NSLOT; c.ph = ((e + E0) / NSLOT) & 1; return c; }

__device__ __forceinline__ int blk_of(int a, int r, int rot) {
    uint32_t tab = rot ? (a ? 0x2156u : 0x3047u) : (a ? 0x1256u : 0x0347u);
    return (tab >> (4 * r)) & 7;
}

__device__ __forceinline__ int op_head(int i, int kap, int u) { return 16 * kap + 4 * ((i >> 1) & 3) + 2 * ((u < 2 ? 1 : 0) ^ (i >> 3)) + (i & 1); }

constexpr float SM_SCALE = 0.08838834764831845f * 1.4426950408889634f;

struct Ctx {
    uint32_t ring, misc;
    uint32_t rel;
    int w, warp, lane;
};
__device__ __forceinline__ void release(const Ctx& c, uint32_t off, uint32_t cnt) {
    if (c.lane < 2) mbar_arrive_cluster(c.rel + off, cnt);
}
__device__ __forceinline__ void signal_event(const Ctx& c, int ev) {
    __syncwarp();
    if (c.lane == 0) mbar_arrive(c.misc + BAR_EV + (c.w * 9 + ev) * 8);
}
template <int NK, int OFF, int N>
__device__ __forceinline__ uint32_t load_afrag(uint32_t (&a)[N], uint32_t base, const Ctx& c) {
    int r = c.lane & 7, mat = c.lane >> 3;
    uint32_t addr = base + (8 * (mat >> 1) + r) * 128 + (((2 * c.warp + (mat & 1)) ^ r) << 4);
#pragma unroll
    for (int k = 0; k < NK; k++) ldsm4t(a[OFF + 4 * k], a[OFF + 4 * k + 1], a[OFF + 4 * k + 2], a[OFF + 4 * k + 3], addr + k * 2048);
    uint32_t dep = 0;
#pragma unroll
    for (int k = 0; k < NK; k++) dep |= a[OFF + 4 * k];
    return dep & blockIdx.y;
}
__device__ __forceinline__ void store_proj(const float (&acc)[64], unsigned char* dst  , const Ctx& c, uint64_t pol) {
    int g = c.lane >> 2, t = c.lane & 3;
#pragma unroll
    for (int i = 0; i < 2; i++) {
        int row = perm32(64 * c.w + 16 * c.warp + 8 * i + g);
        unsigned char* p = dst + row * 128;
#pragma unroll
        for (int q = 0; q < 4; q++) {
            int chunk = (4 * (q & 1) + t) ^ (row & 7);
            stg128_hint(p + (q >> 1) * 16384 + chunk * 16,
                   pack_bf16(acc[16 * q + 2 * i], acc[16 * q + 2 * i + 1]), pack_bf16(acc[16 * q + 4 + 2 * i], acc[16 * q + 4 + 2 * i + 1]),
                   pack_bf16(acc[16 * q + 8 + 2 * i], acc[16 * q + 8 + 2 * i + 1]), pack_bf16(acc[16 * q + 12 + 2 * i], acc[16 * q + 12 + 2 * i + 1]), pol);
        }
    }
}

constexpr float SAFE_EXP = 40.0f, SAFE_SUM = 1099511627776.0f;
template <int NJ>
__device__ __forceinline__ void row_max(const float (&s)[4 * NJ], float (&mx)[2]) {
#pragma unroll
    for (int i = 0; i < 2; i++) {
        float a = fmaxf(s[2 * i], s[2 * i + 1]), b = fmaxf(s[4 + 2 * i], s[4 + 2 * i + 1]);
#pragma unroll
        for (int j = 2; j < NJ; j += 2) {
            a = fmaxf(a, fmaxf(s[4 * j + 2 * i], s[4 * j + 2 * i + 1]));
            b = fmaxf(b, fmaxf(s[4 * j + 4 + 2 * i], s[4 * j + 4 + 2 * i + 1]));
        }
        a = fmaxf(a, b);
        a = fmaxf(a, __shfl_xor_sync(0xffffffffu, a, 1));
        mx[i] = fmaxf(a, __shfl_xor_sync(0xffffffffu, a, 2));
    }
}
template <int NJ, bool SHIFT>
__device__ __forceinline__ void exp_sum(float (&s)[4 * NJ], const float (&m)[2], float& l0, float& l1) {
#pragma unroll
    for (int j = 0; j < NJ; j++) {
#pragma unroll
        for (int e = 0; e < 4; e++) s[4 * j + e] = ex2(SHIFT ? s[4 * j + e] - m[e >> 1] : s[4 * j + e]);
        l0 += s[4 * j + 0] + s[4 * j + 1]; l1 += s[4 * j + 2] + s[4 * j + 3];
    }
}
template <int NJ>
__device__ __forceinline__ bool softmax_first(float (&s)[4 * NJ], float (&m)[2], float (&l)[2]) {
    row_max<NJ>(s, m);
    bool gen = __any_sync(0xffffffffu, !(fabsf(m[0]) <= SAFE_EXP && fabsf(m[1]) <= SAFE_EXP));
    if (!gen) m[0] = m[1] = 0.f;
    l[0] = l[1] = 0.f;
    exp_sum<NJ, true>(s, m, l[0], l[1]);
    return gen;
}
__device__ __forceinline__ void recompute_scores(float (&s)[64], const uint32_t (&q)[32], uint32_t kaddr, const Ctx& c) {
    const int r = c.lane & 7, mat = c.lane >> 3;
    const uint32_t a0 = kaddr + (8 * (mat & 1) + r) * 128 + (((mat >> 1) ^ r) << 4);
#pragma unroll
    for (int i = 0; i < 64; i++) s[i] = 0.f;
#pragma unroll
    for (int jp = 0; jp < 8; jp++) {
#pragma unroll
        for (int k = 0; k < 8; k++) {
            asm volatile(
                "{\n.reg .b32 b0, b1, b2, b3;\n"
                "ldmatrix.sync.aligned.m8n8.x4.trans.shared.b16 {b0,b1,b2,b3}, [%12];\n"
                "mma.sync.aligned.m16n8k16.row.col.f32.bf16.bf16.f32 {%0,%1,%2,%3}, {%8,%9,%10,%11}, {b0,b1}, {%0,%1,%2,%3};\n"
                "mma.sync.aligned.m16n8k16.row.col.f32.bf16.bf16.f32 {%4,%5,%6,%7}, {%8,%9,%10,%11}, {b2,b3}, {%4,%5,%6,%7};\n}\n"
                : "+f"(s[8 * jp]), "+f"(s[8 * jp + 1]), "+f"(s[8 * jp + 2]), "+f"(s[8 * jp + 3]),
                  "+f"(s[8 * jp + 4]), "+f"(s[8 * jp + 5]), "+f"(s[8 * jp + 6]), "+f"(s[8 * jp + 7])
                : "r"(q[4 * k]), "r"(q[4 * k + 1]), "r"(q[4 * k + 2]), "r"(q[4 * k + 3]),
                  "r"((a0 ^ ((jp & 3) << 5)) + (jp >> 2) * 16384 + k * 2048) : "memory");
        }
    }
}
template <int J0>
__device__ __forceinline__ void mask_diag(float (&s)[4 * J0 + 32], const Ctx& c) {
    int g = c.lane >> 2, t = c.lane & 3;
#pragma unroll
    for (int i = 0; i < 2; i++) {
        int lim = perm32(16 * c.warp + 8 * i + g) - 8 * t;
#pragma unroll
        for (int j = 0; j < 8; j++)
#pragma unroll
            for (int e = 0; e < 2; e++)
                if (32 * (j >> 2) + 2 * (j & 3) + e > lim) s[4 * (J0 + j) + 2 * i + e] = -INFINITY;
    }
}
__device__ __forceinline__ void issue_pv(float (&o)[64], const uint32_t (&p)[32], uint32_t vaddr, int acc, bool half) {
    uint64_t d = mkdesc(vaddr, 16, 1024, 1);
    if (half) {
        wg_fence();
#pragma unroll
        for (int k = 0; k < 4; k++) wgmma_rs_n128_ta0_tb0(o, p[4 * k], p[4 * k + 1], p[4 * k + 2], p[4 * k + 3], d + 2 * k, k != 0);
        wg_commit();
    } else {
        wg_fence();
#pragma unroll
        for (int k = 0; k < 8; k++)
            wgmma_rs_n128_ta0_tb0(o, p[4 * k], p[4 * k + 1], p[4 * k + 2], p[4 * k + 3], d + (k >> 2) * 1024 + 2 * (k & 3), k ? 1 : acc);
        wg_commit();
    }
}
__device__ __forceinline__ void issue_qk(float (&s)[64], const uint32_t (&q)[32], uint32_t kaddr) {
    uint64_t d = mkdesc(kaddr, 16384, 1024, 1);
    wg_fence();
#pragma unroll
    for (int k = 0; k < 8; k++) wgmma_rs_n128_ta0_tb1(s, q[4 * k], q[4 * k + 1], q[4 * k + 2], q[4 * k + 3], d + 128 * k, k != 0);
    wg_commit();
}
__device__ __forceinline__ void issue_qk_half(float (&s32)[32], const uint32_t (&q)[32], uint32_t kaddr) {
    uint64_t d = mkdesc(kaddr, 16384, 1024, 1);
    wg_fence();
#pragma unroll
    for (int k = 0; k < 8; k++) wgmma_rs_n64_ta0_tb1(s32, q[4 * k], q[4 * k + 1], q[4 * k + 2], q[4 * k + 3], d + 128 * k, k != 0);
    wg_commit();
}
__device__ __forceinline__ void row_inv(const float (&l)[2], float (&inv)[2]) {
#pragma unroll
    for (int i = 0; i < 2; i++) {
        float sum = l[i];
        sum += __shfl_xor_sync(0xffffffffu, sum, 1);
        sum += __shfl_xor_sync(0xffffffffu, sum, 2);
        inv[i] = rcp_fast(sum);
    }
}
__device__ __forceinline__ void stage_ctx(float (&o)[64], const float (&inv)[2], Cur ce, const Ctx& c) {
    const int g = c.lane >> 2, t = c.lane & 3, r7 = ((g & 1) << 2) | (g >> 1);
    const uint32_t base = c.ring + ce.slot * SLOT_BYTES + c.w * 16384 + (16 * c.warp + r7) * 128 + ((t ^ r7) << 4);
    mbar_wait_hot(c.misc + BAR_FULL + 8 * ce.slot, ce.ph);
#pragma unroll
    for (int q = 0; q < 4; q++) {
        uint32_t v[8];
#pragma unroll
        for (int i = 0; i < 2; i++)
#pragma unroll
            for (int j = 0; j < 4; j++) v[4 * i + j] = pack_bf16(o[16 * q + 4 * j + 2 * i] * inv[i], o[16 * q + 4 * j + 2 * i + 1] * inv[i]);
#pragma unroll
        for (int i = 0; i < 8; i++) { o[16 * q + i] = __uint_as_float(v[i]); asm volatile("" : "=f"(o[16 * q + 8 + i])); }
#pragma unroll
        for (int i = 0; i < 2; i++)
            asm volatile("st.shared.v4.b32 [%0], {%1,%2,%3,%4};" ::"r"((base ^ ((q & 1) << 6)) + (q >> 1) * 8192 + i * 1024),
                         "r"(v[4 * i]), "r"(v[4 * i + 1]), "r"(v[4 * i + 2]), "r"(v[4 * i + 3]) : "memory");
    }
}
__device__ __forceinline__ void publish_ctx(int ev, const Ctx& c) {
    asm volatile("fence.proxy.async.shared::cta;" ::: "memory");
    signal_event(c, ev);
}

__device__ __forceinline__ const unsigned char* xn_addr(int row, int col) {
    return g_xn + ((row >> 7) * 10 + (col >> 6)) * 16384 + (row & 127) * 128 + ((((col & 63) >> 3) ^ (row & 7)) << 4);
}
__device__ __forceinline__ void mma16816(float (&d)[4], uint32_t a0, uint32_t a1, uint32_t a2, uint32_t a3, uint32_t b0, uint32_t b1) {
    asm volatile("mma.sync.aligned.m16n8k16.row.col.f32.bf16.bf16.f32 {%0,%1,%2,%3}, {%4,%5,%6,%7}, {%8,%9}, {%0,%1,%2,%3};"
                 : "+f"(d[0]), "+f"(d[1]), "+f"(d[2]), "+f"(d[3]) : "r"(a0), "r"(a1), "r"(a2), "r"(a3), "r"(b0), "r"(b1));
}
__device__ __forceinline__ uint32_t lds32(uint32_t addr) { uint32_t v; asm volatile("ld.shared.u32 %0, [%1];" : "=r"(v) : "r"(addr)); return v; }

__device__ __forceinline__ void aux_cta(const CUtensorMap* tmG, const CUtensorMap* tmU, const CUtensorMap* tmD, unsigned char* sm, int a) {
    constexpr int STG = 57344, XS = 3 * STG, HS = XS + 8 * 1296, KEY = HS + 8 * 912, MI = KEY + 8192;
    const int tid = threadIdx.x, warp = __shfl_sync(0xffffffffu, tid >> 5, 0), lane = tid & 31;
    const uint32_t sb = smem_u32(sm);
    const uint32_t full = sb + MI, empty = sb + MI + 32;
    int* s_sel = reinterpret_cast<int*>(sm + MI + 64);
    float* s_r = reinterpret_cast<float*>(sm + MI + 96);
    volatile unsigned* s_misc = reinterpret_cast<volatile unsigned*>(sm + MI + 128);
    uint32_t* s_key = reinterpret_cast<uint32_t*>(sm + KEY);
    PROF_DECL
    PROF_GT(0);
    if (tid == 0) {
        for (int i = 0; i < 3; i++) { mbar_init(full + 8 * i, 1); mbar_init(empty + 8 * i, 10); }
        asm volatile("fence.mbarrier_init.release.cluster;" ::: "memory");
    }
    __syncthreads();
    if (warp == 11) {
        if (elect_one()) {
            int st = 0; uint32_t ph = 0;
#pragma unroll 1
            for (int s = 0; s < 34; s++) {
                mbar_wait(empty + 8 * st, ph ^ 1);
                const uint32_t dst = sb + st * STG, fb = full + 8 * st;
                if (s < 20) {
                    mbar_expect_tx(fb, 57344);
                    tma3d(dst, tmG, 0, 32 * s, 7 * a, fb);
                    tma3d(dst + 28672, tmU, 0, 32 * s, 7 * a, fb);
                } else {
                    mbar_expect_tx(fb, 40960);
                    tma3d(dst, tmD, 0, 448 * a + 32 * (s - 20), 0, fb);
                }
                if (s >= 3) {
#pragma unroll 1
                    for (int f = (s == 3 ? 4 : s + 6); f <= s + 6 && f < 34; f++) {
                        if (f < 20) { tma3d_prefetch(tmG, 0, 32 * f, 7 * a); tma3d_prefetch(tmU, 0, 32 * f, 7 * a); }
                        else tma3d_prefetch(tmD, 0, 448 * a + 32 * (f - 20), 0);
                    }
                }
                if (++st == 3) { st = 0; ph ^= 1; }
            }
        }
        return;
    }
    if (warp == 10) return;
    if (tid == 0) {
        unsigned e = *reinterpret_cast<volatile unsigned*>(&g_epoch);
        s_misc[0] = e;
        flag_wait(flag_ptr(FL_LN), (e + 1) * 128u);
    }
    bar_sync(1, 320);
    PROF_GT(50);
    const unsigned ep = s_misc[0];
    auto top8 = [&](uint32_t (&key)[8]) {
        uint32_t mine = 0;
#pragma unroll 1
        for (int r = 0; r < TOPC; r++) {
            uint32_t best = 0;
#pragma unroll
            for (int i = 0; i < 8; i++) best = max(best, key[i]);
            best = __reduce_max_sync(0xffffffffu, best);
#pragma unroll
            for (int i = 0; i < 8; i++) if (key[i] == best) key[i] = 0;
            if (lane == r) mine = best;
        }
        return mine;
    };
#pragma unroll 1
    for (int pass = 0; pass < 2; pass++) {
        if (warp < (pass ? 1 : 8)) {
            uint32_t key[8];
#pragma unroll
            for (int i = 0; i < 8; i++) {
                if (pass == 0) {
                    int idx = warp * 256 + i * 32 + lane;
                    uint32_t b = __float_as_uint(__ldcg(g_router + idx)) >> 16;
                    b = (b & 0x8000u) ? (~b & 0xffffu) : (b | 0x8000u);
                    key[i] = (b << 16) | (uint32_t)(0xffff - idx);
                } else key[i] = i < 2 ? s_key[i * 32 + lane] : 0u;
            }
            uint32_t best = top8(key);
            if (lane < TOPC) {
                if (pass == 0) s_key[warp * 8 + lane] = best;
                else {
                    uint32_t b = best >> 16;
                    b = (b & 0x8000u) ? (b & 0x7fffu) : (~b & 0xffffu);
                    s_sel[lane] = 0xffff - (int)(best & 0xffffu);
                    s_r[lane] = __uint_as_float(b << 16);
                }
            }
        }
        bar_sync(1, 320);
    }
#pragma unroll
    for (int it = 0; it < 2; it++) {
        int i = tid + it * 320, tk = i / 80, ch = i % 80;
        *reinterpret_cast<uint4*>(sm + XS + tk * 1296 + ch * 16) = __ldcg(reinterpret_cast<const uint4*>(xn_addr(s_sel[tk], ch * 8)));
    }
    bar_sync(1, 320);
    PROF_GT(51);
    const int g = lane >> 2, t = lane & 3;
    const uint32_t woff = warp * 4096 + (8 * (lane >> 4) + (lane & 7)) * 128 + ((((lane >> 3) & 1) ^ (lane & 7)) << 4);
    int st = 0; uint32_t ph = 0;
    float ga[4][4], ua[4][4];
#pragma unroll
    for (int i = 0; i < 4; i++)
#pragma unroll
        for (int e = 0; e < 4; e++) { ga[i][e] = 0.f; ua[i][e] = 0.f; }
#pragma unroll 1
    for (int s = 0; s < 34; s++) {
        if (s == 20) {
            if (warp < 7) {
#pragma unroll
                for (int i = 0; i < 4; i++)
#pragma unroll
                    for (int e = 0; e < 4; e++) {
                        float gv = bf_round(ga[i][e]), uv = bf_round(ua[i][e]);
                        float sg = bf_round(__fdividef(gv, 1.0f + __expf(fminf(-gv, 80.f))));
                        int f = warp * 64 + i * 16 + g + 8 * (e >> 1), tk = 2 * t + (e & 1);
                        *reinterpret_cast<__nv_bfloat16*>(sm + HS + tk * 912 + f * 2) = __float2bfloat16_rn(sg * uv);
                        ga[i][e] = 0.f;
                    }
            }
            bar_sync(1, 320);
            PROF_GT(52);
        }
        mbar_wait(full + 8 * st, ph);
        if (s >= 20 || warp < 7) {
#pragma unroll
            for (int kk = 0; kk < 2; kk++) {
                uint32_t xb = sb + (s < 20 ? XS + g * 1296 + s * 64 : HS + g * 912 + (s - 20) * 64) + 32 * kk + 4 * t;
                uint32_t b0 = lds32(xb), b1 = lds32(xb + 16);
                uint32_t wa = sb + st * STG + woff + kk * 2048;
#pragma unroll
                for (int i = 0; i < 4; i++) {
                    uint32_t a0, a1, a2, a3;
                    ldsm4t(a0, a1, a2, a3, wa ^ (i << 5));
                    mma16816(ga[i], a0, a1, a2, a3, b0, b1);
                    if (s < 20) {
                        ldsm4t(a0, a1, a2, a3, (wa ^ (i << 5)) + 28672);
                        mma16816(ua[i], a0, a1, a2, a3, b0, b1);
                    }
                }
            }
        }
        asm volatile("fence.proxy.async.shared::cta;" ::: "memory");
        __syncwarp();
        if (lane == 0) mbar_arrive(empty + 8 * st);
        if (++st == 3) { st = 0; ph ^= 1; }
    }
#pragma unroll
    for (int i = 0; i < 4; i++)
#pragma unroll
        for (int e = 0; e < 4; e += 2)
            *reinterpret_cast<float2*>(g_moe_part + (a * DM + warp * 64 + i * 16 + g + 4 * e) * 8 + 2 * t) = make_float2(ga[i][e], ga[i][e + 1]);
    bar_sync(1, 320);
    if (tid == 0) {
        __threadfence();
        unsigned old = atomicAdd(flag_ptr(FL_MOE_CNT), 1u);
        s_misc[1] = (old == ep * 4u + 3u);
        __threadfence();
    }
    bar_sync(1, 320);
    PROF_GT(53);
    if (s_misc[1]) {
        const float4* pp = reinterpret_cast<const float4*>(g_moe_part);
#pragma unroll 2
        for (int i = tid; i < DM * 2; i += 320) {
            float4 v0 = __ldcg(pp + i), v1 = __ldcg(pp + DM * 2 + i), v2 = __ldcg(pp + DM * 4 + i), v3 = __ldcg(pp + DM * 6 + i);
            float y[4] = {v0.x + v1.x + v2.x + v3.x, v0.y + v1.y + v2.y + v3.y, v0.z + v1.z + v2.z + v3.z, v0.w + v1.w + v2.w + v3.w};
#pragma unroll
            for (int e = 0; e < 4; e++) {
                int col = i >> 1, tk = (i & 1) * 4 + e;
                float sg = bf_round(__fdividef(1.0f, 1.0f + __expf(fminf(-s_r[tk], 80.f))));
                float upd = bf_round(bf_round(y[e]) * sg);
                float xn = __bfloat162float(*reinterpret_cast<const __nv_bfloat16*>(sm + XS + tk * 1296 + col * 2));
                g_brow[tk * DM + col] = __float2bfloat16_rn(xn + upd);
            }
        }
        if (tid < TOPC) g_sel[tid] = s_sel[tid];
        bar_sync(1, 320);
        if (tid == 0) {
            flag_signal(flag_ptr(FL_MOE_DONE));
            *reinterpret_cast<volatile unsigned*>(&g_epoch) = ep + 1;
        }
        PROF_GT(54);
    }
}

__device__ __forceinline__ void ln_rows(const Params& P, int row0, int lane, uint32_t wr_s) {
    const int hl = lane & 15, row = row0 + (lane >> 4);
    uint32_t v[20];
#pragma unroll
    for (int i = 0; i < 5; i++) {
        uint4 u = __ldg(reinterpret_cast<const uint4*>(P.x + (size_t)row * DM + 128 * i + 8 * hl));
        v[4 * i] = u.x; v[4 * i + 1] = u.y; v[4 * i + 2] = u.z; v[4 * i + 3] = u.w;
    }
    float mean = 0.f, m2 = 0.f;
#pragma unroll
    for (int i = 0; i < 20; i++) { mean += bf_lo(v[i]); mean += bf_hi(v[i]); }
    mean *= (1.0f / 40);
#pragma unroll
    for (int i = 0; i < 20; i++) {
        float d0 = __uint_as_float(__byte_perm(v[i], 0, 0x1044)) - mean, d1 = __uint_as_float(__byte_perm(v[i], 0, 0x3244)) - mean;
        m2 = fmaf(d0, d0, m2); m2 = fmaf(d1, d1, m2);
    }
#pragma unroll
    for (int o = 1; o < 16; o <<= 1) {
        float mo = __shfl_xor_sync(0xffffffffu, mean, o), qo = __shfl_xor_sync(0xffffffffu, m2, o), d = mo - mean;
        m2 = fmaf(d * d, 20.0f * o, m2 + qo);
        mean = 0.5f * (mean + mo);
    }
    const uint32_t mb2 = pack_bf16(mean, mean);
    const float inv = rcp_fast(bf_round(sqrt_fast(bf_round(bf_round(m2 * (1.0f / DM)) + 1e-5f))));
    float dot = 0.f;
    unsigned char* xp = g_xn + ((row >> 7) * 10 + (hl >> 3)) * 16384 + (row & 127) * 128 + (((hl & 7) ^ (row & 7)) << 4);
#pragma unroll
    for (int i = 0; i < 5; i++) {
        uint32_t ww[4];
        asm volatile("ld.shared.v4.b32 {%0,%1,%2,%3}, [%4];" : "=r"(ww[0]), "=r"(ww[1]), "=r"(ww[2]), "=r"(ww[3]) : "r"(wr_s + 256 * i + 16 * hl) : "memory");
#pragma unroll
        for (int e = 0; e < 4; e++) {
            uint32_t d;
            asm("sub.rn.bf16x2 %0, %1, %2;" : "=r"(d) : "r"(v[4 * i + e]), "r"(mb2));
            d = pack_bf16(bf_lo(d) * inv, bf_hi(d) * inv);
            v[4 * i + e] = d;
            dot = fmaf(bf_lo(d), bf_lo(ww[e]), dot);
            dot = fmaf(bf_hi(d), bf_hi(ww[e]), dot);
        }
        stg128(xp + i * 32768, v[4 * i], v[4 * i + 1], v[4 * i + 2], v[4 * i + 3]);
    }
#pragma unroll
    for (int o = 8; o > 0; o >>= 1) dot += __shfl_xor_sync(0xffffffffu, dot, o);
    if (hl == 0) g_router[row] = bf_round(dot);
}

__global__ void __cluster_dims__(2, 1, 1) __launch_bounds__(384, 1)
fused_kernel(const __grid_constant__ CUtensorMap tmC, const __grid_constant__ CUtensorMap tmWk, const __grid_constant__ CUtensorMap tmWv,
             const __grid_constant__ CUtensorMap tmWq, const __grid_constant__ CUtensorMap tmWo,
             const __grid_constant__ CUtensorMap tmG, const __grid_constant__ CUtensorMap tmU, const __grid_constant__ CUtensorMap tmD, const Params P) {
    extern __shared__ unsigned char smem_raw[];
    const uint32_t ring = (smem_u32(smem_raw) + 1023u) & ~1023u;
    const uint32_t misc = ring + RING_BYTES;
    const int tid = threadIdx.x;
    const int mc = blockIdx.x >> 1, rank = blockIdx.x & 1;
    if (mc >= 64) { aux_cta(&tmG, &tmU, &tmD, smem_raw + (ring - smem_u32(smem_raw)), blockIdx.x - 128); return; }
    PROF_DECL
    PROF_GT(0); PROF_EV(1);

    if (tid == 0) {
        for (int i = 0; i < 8; i++) mbar_init(misc + BAR_W + 8 * i, 1);
        asm volatile("fence.mbarrier_init.release.cluster;" ::: "memory");
        const CUtensorMap* tw = rank ? &tmWv : &tmWk;
        for (int e = 0; e < 2; e++) {
            mbar_expect_tx(misc + BAR_W + 8 * e, SLOT_BYTES);
            tma2d(ring + (E0 + e) * SLOT_BYTES, tw, (mc >> 1) * 128, e * 256, misc + BAR_W + 8 * e);
            tma2d(ring + (E0 + e) * SLOT_BYTES + 16384, tw, (mc >> 1) * 128, e * 256 + 128, misc + BAR_W + 8 * e);
        }
        for (int i = 0; i < NSLOT; i++) { mbar_init(misc + BAR_FULL + 8 * i, 1); mbar_init(misc + BAR_EMPTY + 8 * i, 16); }
        for (int i = 0; i < NST3; i++) { mbar_init(misc + BAR_FULL3 + 8 * i, 1); mbar_init(misc + BAR_EMPTY3 + 8 * i, 16); }
        for (int i = 0; i < 18; i++) mbar_init(misc + BAR_EV + 8 * i, 4);
        for (int i = 0; i < 19; i++) mbar_init(misc + BAR_DEP + 8 * i, 1);
        mbar_init(misc + BAR_LN, 2); mbar_init(misc + BAR_PF, 1); mbar_init(misc + BAR_PF + 8, 1); mbar_init(misc + BAR_SEL, 1);
        for (int i = 0; i < E0 + 2; i++) mbar_arrive(misc + BAR_FULL + 8 * i);
        for (int i = 0; i < E0; i++) mbar_arrive_cluster(misc + BAR_EMPTY + 8 * i, 16);
        asm volatile("fence.mbarrier_init.release.cluster;" ::: "memory");
    }
    if (tid == 32) asm volatile("prefetch.tensormap [%0];" ::"l"(&tmC) : "memory");
    __syncthreads();
    asm volatile("barrier.cluster.arrive.relaxed.aligned;\nbarrier.cluster.wait.aligned;" ::: "memory");

    PROF_EV(5);
    const int h = mc >> 1, a = mc & 1;
    const int rot = (mc >> 2) & 1;
    const int hq = (mc >> 2) * 2 + rank;
    const int kq = mc & 3;
    const int u3 = mc >> 3, s3 = (mc >> 1) & 3, kap = mc & 1;
    const int wg = __shfl_sync(0xffffffffu, tid >> 7, 0);

    if (wg == 0) {
        asm volatile("setmaxnreg.dec.sync.aligned.u32 40;");
        const int warp = __shfl_sync(0xffffffffu, tid >> 5, 0), lane = tid & 31;
        if (warp == 0) {
            const bool lead = elect_one();
            Cur c = cur_at(2);
            uint32_t dst, fb;
            auto acquire = [&]() {
                mbar_wait(misc + BAR_EMPTY + 8 * c.slot, c.ph ^ 1);
                fb = misc + BAR_FULL + 8 * c.slot; dst = ring + c.slot * SLOT_BYTES;
                if (lead) mbar_expect_tx(fb, SLOT_BYTES);
                c.adv();
            };
            auto load_w = [&](int id, const CUtensorMap* tm, int col, int row) {
                mbar_wait(misc + BAR_EMPTY + 8 * c.slot, c.ph ^ 1);
                fb = misc + BAR_W + 8 * id; dst = ring + c.slot * SLOT_BYTES;
                if (lead) {
                    mbar_expect_tx(fb, SLOT_BYTES);
                    tma2d(dst, tm, col, row, fb); tma2d(dst + 16384, tm, col, row + 128, fb);
                    mbar_arrive(misc + BAR_FULL + 8 * c.slot);
                }
                c.adv();
            };
            auto load_half = [&](const unsigned char* src) {
                acquire();
                if (lead) bulk_load_mc(dst + rank * 16384, src, 16384, fb);
            };
            auto staging = [&]() {
                mbar_wait(misc + BAR_EMPTY + 8 * c.slot, c.ph ^ 1);
                if (lead) mbar_arrive(misc + BAR_FULL + 8 * c.slot);
                c.adv();
            };
            auto dep_wait = [&](int d) { mbar_wait(misc + BAR_DEP + 8 * d, 0); fence_async_global(); };
            const CUtensorMap* tw = rank ? &tmWv : &tmWk;
#pragma unroll 1
            for (int i = 0; i < 32; i++) {
                acquire();
                if (lead) tma2d_mc(dst + rank * 16384, &tmC, (i & 3) * 128 + rank * 64, (a * 8 + (i >> 2)) * 128, fb);
                if (i == 3) { load_w(2, tw, h * 128 + 64, 0); load_w(3, tw, h * 128 + 64, 256); }
            }
            load_w(4, &tmWq, hq * 128, 0); load_w(5, &tmWq, hq * 128, 256); load_w(6, &tmWq, hq * 128 + 64, 0);
            dep_wait(0);
#pragma unroll 1
            for (int t = 0; t < 4; t++) {
                const unsigned char* xt = g_xn + ((blk_of(kq >> 1, t, rot) * 2 + (kq & 1)) * 10 + rank) * 16384;
#pragma unroll 1
                for (int ch = 0; ch < 5; ch++) {
                    if (t == 0 && ch == 4) load_w(7, &tmWq, hq * 128 + 64, 256);
                    load_half(xt + ch * 32768);
                }
                acquire();
                if (lead) { tma2d(dst, &tmWq, hq * 128, 512, fb); tma2d(dst + 16384, &tmWq, hq * 128 + 64, 512, fb); }
            }
            const unsigned char* Kh = g_K + (size_t)h * 32 * 16384 + rank * 16384;
            const unsigned char* Vh = g_V + (size_t)h * 32 * 16384 + rank * 16384;
#pragma unroll 1
            for (int r = 0; r < 4; r++) {
                const int p = blk_of(a, r, rot), n = 2 * p + 1;
                if (r < 2) dep_wait(1 + r);
                acquire();
                if (lead) {
                    const int g0 = (r & 1) ? rank : 3 - rank;
                    bulk_load(dst, g_Q + (size_t)(h * 32 + 4 * p + g0) * 16384, 16384, fb);
                    bulk_load(dst + 16384, g_Q + (size_t)(h * 32 + 4 * p + 3 - g0) * 16384, 16384, fb);
                }
                load_half(Kh + n * 32768);
                if (r > 0) { load_half(Vh); staging(); }
#pragma unroll 1
                for (int j = n - 1; j >= 0; j--) { load_half(Kh + j * 32768); load_half(Vh + (j + 1) * 32768); }
            }
            load_half(Vh);
            staging();
            mbar_wait(misc + BAR_EMPTY + 8 * c.slot, c.ph ^ 1); c.adv();
            int st = 0; uint32_t ph3 = 0;
#pragma unroll 1
            for (int i = 0; i < 32; i++) {
                const int head = op_head(i >> 1, kap, u3);
                if ((i & 1) == 0) dep_wait(3 + (i >> 1));
                if (i < NST3) { mbar_wait(misc + BAR_EMPTY + 8 * c.slot, c.ph ^ 1); c.adv(); }
                else mbar_wait(misc + BAR_EMPTY3 + 8 * st, ph3 ^ 1);
                fb = misc + BAR_FULL3 + 8 * st; dst = ring + st * ST3_BYTES;
                if (lead) {
                    mbar_expect_tx(fb, ST3_BYTES);
                    const unsigned char* src = g_Q + (size_t)(head * 32 + 4 * u3 + 2 * rank) * 16384 + (i & 1) * 8192;
                    bulk_load(dst, src, 8192, fb);
                    bulk_load(dst + 8192, src + 16384, 8192, fb);
                    tma3d_mc(dst + 16384 + rank * 10240, &tmWo, 0, head * 128 + (i & 1) * 64 + rank * 32, 5 * s3, fb);
                }
                if (++st == NST3) { st = 0; ph3 ^= 1; }
            }
        } else if (warp == 3) {
            unsigned ep1 = *reinterpret_cast<volatile unsigned*>(&g_epoch) + 1;
            if (lane == 0) {
                asm volatile("st.shared.u32 [%0], %1;" ::"r"(misc + MISC_EPOCH), "r"(ep1) : "memory");
                mbar_wait(misc + BAR_LN, 0);
                flag_signal(flag_ptr(FL_LN));
                mbar_wait(misc + BAR_PF + 8, 0);
                l2_prefetch(reinterpret_cast<const unsigned char*>(P.wq) + (size_t)blockIdx.x * 40960, 40960);
                flag_wait(flag_ptr(FL_LN), ep1 * 128u);
                mbar_arrive(misc + BAR_DEP);
                mbar_wait(misc + BAR_EV + 8, 0);
                flag_wait(flag_ptr(FL_KV + h), ep1 * 8u);
                flag_wait(flag_ptr(FL_Q + h * 8 + blk_of(a, 0, rot)), ep1 * 4u);
                mbar_arrive(misc + BAR_DEP + 8);
                mbar_wait(misc + BAR_EV + 32, 0);
                for (int r = 1; r < 4; r++) flag_wait(flag_ptr(FL_Q + h * 8 + blk_of(a, r, rot)), ep1 * 4u);
                mbar_arrive(misc + BAR_DEP + 16);
                flag_wait(flag_ptr(FL_MOE_DONE), ep1);
                int4 s0 = __ldcg(reinterpret_cast<const int4*>(g_sel)), s1 = __ldcg(reinterpret_cast<const int4*>(g_sel) + 1);
                asm volatile("st.shared.v4.u32 [%0], {%1,%2,%3,%4};" ::"r"(misc + MISC_SEL), "r"(s0.x), "r"(s0.y), "r"(s0.z), "r"(s0.w) : "memory");
                asm volatile("st.shared.v4.u32 [%0], {%1,%2,%3,%4};" ::"r"(misc + MISC_SEL + 16), "r"(s1.x), "r"(s1.y), "r"(s1.z), "r"(s1.w) : "memory");
                mbar_arrive(misc + BAR_SEL);
                mbar_wait(misc + BAR_EV + 48, 0);
                l2_prefetch(reinterpret_cast<const unsigned char*>(P.wo) + (size_t)blockIdx.x * 40960, 40960);
            }
            __syncwarp();
            const unsigned* cf = flag_ptr(FL_CTX + op_head(lane & 15, kap, u3) * 8 + u3);
            bool done = lane >= 16;
            for (int spin = 0; spin < 4000000; spin++) {
                if (!done) {
                    unsigned v;
                    asm volatile("ld.acquire.gpu.global.u32 %0, [%1];" : "=r"(v) : "l"(cf) : "memory");
                    if ((int)(v - ep1 * 4u) >= 0) {
                        mbar_arrive(misc + BAR_DEP + 24 + 8 * lane);
                        done = true;
                        fence_async_global();
                        l2_prefetch(g_Q + (size_t)(op_head(lane, kap, u3) * 32 + 4 * u3 + 2 * rank) * 16384 + s3 * 8192, 8192);
                    }
                }
                if (__all_sync(0xffffffffu, done)) break;
                __nanosleep(64);
            }
        } else {
            if (lane < 20) {
#pragma unroll
                for (int i = 0; i < 2; i++) {
                    const int ch = (warp - 1) * 40 + i * 20 + lane;
                    uint4 u = __ldg(reinterpret_cast<const uint4*>(P.wr) + ch);
                    asm volatile("st.shared.v4.b32 [%0], {%1,%2,%3,%4};" ::"r"(misc + MISC_WR + 16 * ch), "r"(u.x), "r"(u.y), "r"(u.z), "r"(u.w) : "memory");
                }
            }
            bar_sync(3, 64);
            mbar_wait(misc + BAR_PF, 0);
            if (lane == 0) l2_prefetch(P.x + (size_t)(blockIdx.x * 16 + (warp - 1) * 8) * DM, 8 * DM * 2);
#pragma unroll 1
            for (int i = 0; i < 8; i += 2) ln_rows(P, blockIdx.x * 16 + (warp - 1) * 8 + i, lane, misc + MISC_WR);
            __syncwarp();
            if (lane == 0) {
            mbar_arrive(misc + BAR_LN);
            const uint32_t eb = misc + BAR_EV + (warp - 1) * 72;
            mbar_wait(eb, 0);
            flag_signal(flag_ptr(FL_KV + h));
#pragma unroll 1
            for (int t = 0; t < 4; t++) {
                mbar_wait(eb + 8 + 8 * t, 0);
                flag_signal(flag_ptr(FL_Q + hq * 8 + blk_of(kq >> 1, t, rot)));
            }
            int e = 64;
#pragma unroll 1
            for (int r = 0; r < 4; r++) {
                const int p = blk_of(a, r, rot);
                e += 4 * p + 4 + (r > 0 ? 2 : 0);
                const uint32_t slot = (e + (r < 3 ? 3 : 1) + E0) % NSLOT;
                const int grp = ((r & 1) == warp - 1) ? 3 - rank : rank;
                mbar_wait(eb + 40 + 8 * r, 0);
                asm volatile("cp.async.bulk.global.shared::cta.bulk_group [%0], [%1], 16384;"
                             ::"l"(g_Q + (size_t)(h * 32 + 4 * p + grp) * 16384), "r"(ring + slot * SLOT_BYTES + (warp - 1) * 16384) : "memory");
                asm volatile("cp.async.bulk.commit_group;" ::: "memory");
                asm volatile("cp.async.bulk.wait_group.read 0;" ::: "memory");
                mbar_arrive_cluster(mapa(misc + BAR_EMPTY + 8 * slot, 0), 4);
                mbar_arrive_cluster(mapa(misc + BAR_EMPTY + 8 * slot, 1), 4);
                asm volatile("cp.async.bulk.wait_group 0;" ::: "memory");
                fence_async_global();
                flag_signal(flag_ptr(FL_CTX + h * 8 + p));
            }
            }
        }
    } else {
        asm volatile("setmaxnreg.inc.sync.aligned.u32 232;");
        Ctx c;
        c.ring = ring; c.misc = misc; c.w = wg - 1; c.warp = (tid >> 5) & 3; c.lane = tid & 31;
        c.rel = mapa(misc, tid & 1);
        const int w = c.w;
        const int my_bar = 1 + w, other_bar = 2 - w;
        if (w == 1) bar_arrive(1, 256);
        Cur cur;
        {
            uint32_t wf[128];
            float acc[64];
#pragma unroll
            for (int i = 0; i < 64; i++) acc[i] = 0.f;
            auto load_weights = [&](int id, uint32_t slot0, uint32_t slot1) {
                mbar_wait(misc + BAR_W + 8 * id, 0);
                uint32_t z = load_afrag<16, 0>(wf, ring + slot0 * SLOT_BYTES, c);
                release(c, BAR_EMPTY + 8 * slot0 + z, 2);
                mbar_wait(misc + BAR_W + 8 * id + 8, 0);
                z = load_afrag<16, 64>(wf, ring + slot1 * SLOT_BYTES, c);
                release(c, BAR_EMPTY + 8 * slot1 + z, 2);
            };
            auto chunks4 = [&](uint32_t& last_slot) {
#pragma unroll
                for (int ch = 0; ch < 4; ch++) {
                    mbar_wait(misc + BAR_FULL + 8 * cur.slot, cur.ph);
                    uint64_t d = mkdesc(ring + cur.slot * SLOT_BYTES, 16, 1024, 1);
                    wg_fence();
#pragma unroll
                    for (int k = 0; k < 8; k++)
                        wgmma_rs_n128_ta0_tb0(acc, wf[32 * ch + 4 * k], wf[32 * ch + 4 * k + 1], wf[32 * ch + 4 * k + 2], wf[32 * ch + 4 * k + 3],
                                              d + (k >> 2) * 1024 + (k & 3) * 2, (ch | k) != 0);
                    wg_commit();
                    if (ch > 0 && ch < 3) { wg_wait<1>(); release(c, BAR_EMPTY + 8 * last_slot, 1); }
                    if (ch < 3) { last_slot = cur.slot; cur.adv(); }
                }
            };
            load_weights(2 * w, w ? slot_of(6) : slot_of(0), w ? slot_of(7) : slot_of(1));
            if (tid == 256) mbar_arrive(misc + BAR_PF);
            PROF_EV(2); PROF_GT(60);
            cur = cur_at(2);
            unsigned char* kvdst = (rank ? g_V : g_K) + (size_t)(h * 32 + a * 16) * 16384;
#pragma unroll 1
            for (int t = 0; t < 8; t++) {
                uint32_t last;
                bar_sync(my_bar, 256);
                PROF_EV(10);
                chunks4(last);
                bar_arrive(other_bar, 256);
                wg_wait<1>(); release(c, BAR_EMPTY + 8 * last, 1);
                wg_wait<0>(); release(c, BAR_EMPTY + 8 * cur.slot, 1);
                PROF_EV(11);
                cur.adv();
                if (t == 0) { cur.adv(); cur.adv(); }
                fence_regs(acc);
                if (t == 5 && tid == 128) mbar_arrive(misc + BAR_PF + 8);
                if (t == 7) load_weights(4 + 2 * w, w ? slot_of(38) : slot_of(36), w ? slot_of(43) : slot_of(37));
                store_proj(acc, kvdst + t * 32768, c, policy_normal());
            }
            signal_event(c, 0);
            PROF_EV(61); PROF_GT(62);
            cur = cur_at(39);
#pragma unroll 1
            for (int t = 0; t < 4; t++) {
                uint32_t last;
                bar_sync(my_bar, 256);
                PROF_EV(20);
                chunks4(last);
                wg_wait<1>(); release(c, BAR_EMPTY + 8 * last, 1);
                last = cur.slot; cur.adv();
                if (t == 0) cur.adv();
                Cur cx = cur; cur.adv();
                mbar_wait(misc + BAR_FULL + 8 * cx.slot, cx.ph);
                mbar_wait(misc + BAR_FULL + 8 * cur.slot, cur.ph);
                uint64_t db = mkdesc(ring + cx.slot * SLOT_BYTES, 16, 1024, 1);
                uint64_t da = mkdesc(ring + cur.slot * SLOT_BYTES + w * 16384, 16384, 1024, 1);
                wg_fence();
#pragma unroll
                for (int k = 0; k < 8; k++) wgmma_ss_n128_ta1_tb0(acc, da + 128 * k, db + (k >> 2) * 1024 + (k & 3) * 2, 1);
                wg_commit();
                bar_arrive(other_bar, 256);
                wg_wait<1>(); release(c, BAR_EMPTY + 8 * last, 1);
                wg_wait<0>(); release(c, BAR_EMPTY + 8 * cx.slot, 1); release(c, BAR_EMPTY + 8 * cur.slot, 1);
                PROF_EV(21);
                cur.adv();
                fence_regs(acc);
                int tile = blk_of(kq >> 1, t, rot) * 2 + (kq & 1);
#pragma unroll
                for (int i = 0; i < 64; i++) acc[i] *= SM_SCALE;
                store_proj(acc, g_Q + (size_t)(hq * 32 + tile * 2) * 16384, c, policy_normal());
                signal_event(c, 1 + t);
            }
        }
        PROF_EV(63); PROF_GT(64);
        float o[64], inv[2];
        {
            uint32_t q[32], p[32];
            float m[2], l[2];
#pragma unroll
            for (int i = 0; i < 64; i++) o[i] = 0.f;
#pragma unroll
            for (int i = 0; i < 32; i++) p[i] = 0u;
            m[0] = m[1] = inv[0] = inv[1] = 0.f;
            l[0] = l[1] = 1.f;
            int gen = 0;
            Cur ck = cur, cv = cur, cq, ce, cen;
            int r = 0, left;
            int first = 1, half, heavy;
            int pv_acc = 0, pv_half = 1; uint32_t pv_cnt = 0;
            int pending = 0;
            Cur nck, ncv;
            auto next_task = [&](int rr) {
                heavy = 1 ^ (rr & 1) ^ w;
                half = 1 ^ heavy ^ rank;
                left = 2 * blk_of(a, rr, rot) + 1 + heavy;
                cq = cur; cur.adv();
                nck = cur; cur.adv();
                if (rr > 0) { ncv = cur; cur.adv(); cen = cur; cur.adv(); }
                if (!heavy) { nck = cur; cur.adv(); cur.adv(); }
                if (rr == 0) { ncv = nck; cen = nck; }
            };
            next_task(0);
            ce = cen;
            mbar_wait(misc + BAR_FULL + 8 * cq.slot, cq.ph);
            load_afrag<8, 0>(q, ring + cq.slot * SLOT_BYTES + w * 16384, c);
            uint32_t k_cnt = 1; int last = 0, was_first = 0, publish = 0;
            auto window = [&]() {
                publish = pending;
                if (pending) stage_ctx(o, inv, ce, c);
                pending = 0;
                k_cnt = 1;
                was_first = first;
                if (first) {
                    release(c, BAR_EMPTY + 8 * cq.slot, 1);
                    pending = r ? 4 + r : 0; ce = cen;
                    k_cnt = 1 + heavy;
                }
                last = --left == 0 ? 1 : 0;
                first = last;
                if (!last) { nck = cur; cur.adv(); ncv = cur; cur.adv(); half = 0; }
                else if (++r < 4) next_task(r);
                mbar_wait_hot(misc + BAR_FULL + 8 * cv.slot, cv.ph);
            };
            auto next_q = [&]() {
                if (last && r < 4) {
                    mbar_wait_hot(misc + BAR_FULL + 8 * cq.slot, cq.ph);
                    load_afrag<8, 0>(q, ring + cq.slot * SLOT_BYTES + w * 16384, c);
                }
            };
#pragma unroll 1
            while (r < 4) {
                ck = nck; cv = ncv;
                mbar_wait_hot(misc + BAR_FULL + 8 * ck.slot, ck.ph);
                if (half) {
                    bar_sync(my_bar, 256);
                    PROF_EV(30);
                    float s[32];
                    undef_regs(s);
                    issue_qk_half(s, q, ring + ck.slot * SLOT_BYTES);
                    window();
                    issue_pv(o, p, ring + cv.slot * SLOT_BYTES, pv_acc, pv_half);
                    bar_arrive(other_bar, 256);
                    if (publish) publish_ctx(publish, c);
                    wg_wait<1>();
                    PROF_EV(34);
                    fence_regs(s);
                    row_inv(l, inv);
                    mask_diag<0>(s, c);
                    gen = softmax_first<8>(s, m, l);
                    next_q();
                    wg_wait<0>();
                    fence_regs(o);
                    fence_regs(s);
                    release(c, BAR_EMPTY + 8 * ck.slot, k_cnt);
                    if (pv_cnt) release(c, BAR_EMPTY + 8 * cv.slot, pv_cnt);
#pragma unroll
                    for (int i = 0; i < 16; i++) p[i] = pack_bf16(s[2 * i], s[2 * i + 1]);
                    pv_acc = 0; pv_half = 1; pv_cnt = k_cnt;
                    continue;
                }
                float s[64];
                int redo;
#pragma unroll 1
                while (true) {
                    bar_sync(my_bar, 256);
                    PROF_EV(first ? 30 : 31);
                    undef_regs(s);
                    issue_qk(s, q, ring + ck.slot * SLOT_BYTES);
                    const bool special = first > 0 || pv_acc == 0 || left == 1;
                    if (special) window();
                    else {
                        nck = cur; cur.adv(); ncv = cur; cur.adv();
                        --left;
                        mbar_wait_hot(misc + BAR_FULL + 8 * cv.slot, cv.ph);
                    }
                    issue_pv(o, p, ring + cv.slot * SLOT_BYTES, pv_acc, special && pv_half);
                    bar_arrive(other_bar, 256);
                    wg_wait<1>();
                    PROF_EV(33);
                    fence_regs(s);
                    float lo = 0.f;
                    if (special) {
                        if (publish) publish_ctx(publish, c);
                        if (was_first) {
                            row_inv(l, inv);
                            l[0] = l[1] = m[0] = m[1] = 0.f;
                            gen = 0;
                            lo = 1.0f / SAFE_SUM;
                            mask_diag<8>(s, c);
                        }
                    }
                    constexpr int JB = 11;
                    float l0 = l[0], l1 = l[1];
                    if (!gen) {
#pragma unroll
                        for (int j = 0; j < JB; j++) {
#pragma unroll
                            for (int e = 0; e < 4; e++) ex2v(s[4 * j + e]);
                            if (j < JB - 1) { l0 += s[4 * j] + s[4 * j + 1]; l1 += s[4 * j + 2] + s[4 * j + 3]; }
                        }
                    }
                    wg_wait<0>();
                    fence_regs(o);
                    redo = 0;
                    if (gen) break;
#pragma unroll
                    for (int j = JB - 1; j < 16; j++) {
                        if (j >= JB) {
#pragma unroll
                            for (int e = 0; e < 4; e++) ex2v(s[4 * j + e]);
                        }
                        l0 += s[4 * j] + s[4 * j + 1]; l1 += s[4 * j + 2] + s[4 * j + 3];
                    }
#pragma unroll
                    for (int i = 0; i < 32; i++) p[i] = pack_bf16(s[2 * i], s[2 * i + 1]);
                    redo = 1;
                    if (__any_sync(0xffffffffu, !(l0 <= SAFE_SUM && l1 <= SAFE_SUM && l0 >= lo && l1 >= lo))) break;
                    l[0] = l0; l[1] = l1;
                    redo = 0;
                    if (last) break;
                    release(c, BAR_EMPTY + 8 * ck.slot, k_cnt);
                    if (pv_cnt) release(c, BAR_EMPTY + 8 * cv.slot, pv_cnt);
                    pv_acc = was_first ^ 1; pv_half = 0; pv_cnt = k_cnt;
                    ck = nck; cv = ncv;
                    mbar_wait_hot(misc + BAR_FULL + 8 * ck.slot, ck.ph);
                }
                if (gen | redo) {
                    if (redo) {
                        recompute_scores(s, q, ring + ck.slot * SLOT_BYTES, c);
                        if (was_first) { mask_diag<8>(s, c); m[0] = m[1] = -INFINITY; }
                    }
                    gen = 1;
                    float mx[2], alpha[2];
                    row_max<16>(s, mx);
#pragma unroll
                    for (int i = 0; i < 2; i++) {
                        mx[i] = fmaxf(mx[i], m[i]);
                        alpha[i] = was_first ? 1.0f : ex2(m[i] - mx[i]);
                        m[i] = mx[i];
                        l[i] *= alpha[i];
                    }
                    exp_sum<16, true>(s, m, l[0], l[1]);
#pragma unroll
                    for (int i = 0; i < 64; i++) o[i] *= alpha[(i >> 1) & 1];
#pragma unroll
                    for (int i = 0; i < 32; i++) p[i] = pack_bf16(s[2 * i], s[2 * i + 1]);
                }
                next_q();
                release(c, BAR_EMPTY + 8 * ck.slot, k_cnt);
                if (pv_cnt) release(c, BAR_EMPTY + 8 * cv.slot, pv_cnt);
                pv_acc = was_first ^ 1; pv_half = 0; pv_cnt = k_cnt;
            }
            if (pending) { stage_ctx(o, inv, ce, c); publish_ctx(pending, c); }
            mbar_wait(misc + BAR_FULL + 8 * cur.slot, cur.ph);
            bar_sync(my_bar, 256);
            PROF_EV(32);
            issue_pv(o, p, ring + cur.slot * SLOT_BYTES, pv_acc, pv_half);
            if (w == 0) bar_arrive(other_bar, 256);
            row_inv(l, inv);
            wg_wait<0>();
            release(c, BAR_EMPTY + 8 * cur.slot, pv_cnt);
            fence_regs(o);
            cur.adv();
        }
        {
            float acc[80];
            undef_regs(acc);
            int st = 0, prev = 0; uint32_t ph3 = 0;
            auto op_stage = [&](int i) {
                mbar_wait(misc + BAR_FULL3 + 8 * st, ph3);
                uint32_t base = ring + st * ST3_BYTES;
                uint64_t da = mkdesc(base + w * 8192, 16, 1024, 1);
                uint64_t db = mkdesc(base + 16384, 2048, 512, 2);
                wg_fence();
#pragma unroll
                for (int k = 0; k < 4; k++) wgmma_ss_n160_ta0_tb1(acc, da + 2 * k, db + (k >> 1) * 640 + (k & 1) * 64, k ? 1 : i);
                wg_commit();
                if (i > 0) { wg_wait<1>(); if (i <= 32 - NST3) release(c, BAR_EMPTY3 + 8 * prev, 1); }
                prev = st;
                if (++st == NST3) { st = 0; ph3 ^= 1; }
            };
            PROF_EV(40); PROF_GT(65);
            op_stage(0);
            stage_ctx(o, inv, cur, c);
            publish_ctx(8, c);
#pragma unroll 1
            for (int i = 1; i < 22; i++) op_stage(i);
            mbar_wait(misc + BAR_SEL, 0);
            const uint32_t tag = lds32(misc + MISC_EPOCH) & 1;
            const int g = c.lane >> 2, t = c.lane & 3;
            const int row = (2 * u3 + rank) * 128 + 64 * w + perm32(16 * c.warp + 8 * kap + (((g & 3) << 1) | (g >> 2)));
            const int col = 160 * s3 + 8 * t;
            int sel = -1;
#pragma unroll
            for (int i = 0; i < TOPC; i++) if ((int)lds32(misc + MISC_SEL + 4 * i) == row) sel = i;
            uint4 xv[5], bv[5];
#pragma unroll
            for (int i = 0; i < 5; i++) {
                xv[i] = ldg128(P.x + (size_t)row * DM + col + 32 * i);
                bv[i] = ldg128(sel >= 0 ? (const void*)(g_brow + sel * DM + col + 32 * i) : (const void*)xn_addr(row, col + 32 * i));
            }
#pragma unroll 1
            for (int i = 22; i < 32; i++) op_stage(i);
            wg_wait<0>();
            fence_regs(acc);
            PROF_EV(41); PROF_GT(66);
            const int t256 = tid - 128;
            uint4* sendp = g_part + (size_t)blockIdx.x * 2560 + t256;
            float keep[40];
#pragma unroll
            for (int j = 0; j < 10; j++) {
                uint32_t v0 = __float_as_uint(kap ? acc[8 * j + 0] : acc[8 * j + 2]), v1 = __float_as_uint(kap ? acc[8 * j + 1] : acc[8 * j + 3]);
                uint32_t v2 = __float_as_uint(kap ? acc[8 * j + 4] : acc[8 * j + 6]), v3 = __float_as_uint(kap ? acc[8 * j + 5] : acc[8 * j + 7]);
                asm volatile("st.relaxed.gpu.global.v4.b32 [%0], {%1,%2,%3,%4};" ::"l"(sendp + j * 256),
                             "r"((v0 & ~1u) | tag), "r"((v1 & ~1u) | tag), "r"((v2 & ~1u) | tag), "r"((v3 & ~1u) | tag) : "memory");
                keep[4 * j + 0] = kap ? acc[8 * j + 2] : acc[8 * j + 0]; keep[4 * j + 1] = kap ? acc[8 * j + 3] : acc[8 * j + 1];
                keep[4 * j + 2] = kap ? acc[8 * j + 6] : acc[8 * j + 4]; keep[4 * j + 3] = kap ? acc[8 * j + 7] : acc[8 * j + 5];
            }
            const uint4* recvp = g_part + (size_t)(blockIdx.x ^ 2) * 2560 + t256;
            uint4 rv[10];
            int spins = 0;
            while (true) {
                uint32_t v;
                asm volatile("ld.relaxed.gpu.global.b32 %0, [%1];" : "=r"(v) : "l"(recvp + 9 * 256) : "memory");
                if (__all_sync(0xffffffffu, (v & 1u) == tag) || ++spins > 2000000) break;
                __nanosleep(20);
            }
            while (true) {
                uint32_t all_and = 1u, all_or = 0u;
#pragma unroll
                for (int j = 0; j < 10; j++) {
                    asm volatile("ld.relaxed.gpu.global.v4.b32 {%0,%1,%2,%3}, [%4];"
                                 : "=r"(rv[j].x), "=r"(rv[j].y), "=r"(rv[j].z), "=r"(rv[j].w) : "l"(recvp + j * 256) : "memory");
                }
#pragma unroll
                for (int j = 0; j < 10; j++) {
                    all_and &= rv[j].x & rv[j].y & rv[j].z & rv[j].w;
                    all_or |= rv[j].x | rv[j].y | rv[j].z | rv[j].w;
                }
                bool ok = ((tag ? all_and : all_or) & 1u) == tag;
                if (__all_sync(0xffffffffu, ok) || ++spins > 2000000) break;
            }
            uint32_t pk[20];
#pragma unroll
            for (int j = 0; j < 10; j++) {
                pk[2 * j] = pack_bf16(keep[4 * j] + __uint_as_float(rv[j].x & ~1u), keep[4 * j + 1] + __uint_as_float(rv[j].y & ~1u));
                pk[2 * j + 1] = pack_bf16(keep[4 * j + 2] + __uint_as_float(rv[j].z & ~1u), keep[4 * j + 3] + __uint_as_float(rv[j].w & ~1u));
            }
#pragma unroll
            for (int i = 0; i < 5; i++) {
                uint32_t a0 = pk[4 * i], a1 = pk[4 * i + 1], a2 = pk[4 * i + 2], a3 = pk[4 * i + 3];
                uint32_t x0 = (t & 1) ? a0 : a1, x1 = (t & 1) ? a2 : a3;
                x0 = __shfl_xor_sync(0xffffffffu, x0, 1); x1 = __shfl_xor_sync(0xffffffffu, x1, 1);
                if (t & 1) { a0 = x0; a2 = x1; } else { a1 = x0; a3 = x1; }
                x0 = (t & 2) ? a0 : a2; x1 = (t & 2) ? a1 : a3;
                x0 = __shfl_xor_sync(0xffffffffu, x0, 2); x1 = __shfl_xor_sync(0xffffffffu, x1, 2);
                if (t & 2) { a0 = x0; a1 = x1; } else { a2 = x0; a3 = x1; }
                uint32_t av[4] = {a0, a1, a2, a3};
                uint32_t xx[4] = {xv[i].x, xv[i].y, xv[i].z, xv[i].w}, bb[4] = {bv[i].x, bv[i].y, bv[i].z, bv[i].w};
                uint32_t ov[4];
#pragma unroll
                for (int e = 0; e < 4; e++) {
                    uint32_t t1 = pack_bf16(bf_lo(xx[e]) + bf_lo(av[e]), bf_hi(xx[e]) + bf_hi(av[e]));
                    ov[e] = pack_bf16(bf_lo(t1) + bf_lo(bb[e]), bf_hi(t1) + bf_hi(bb[e]));
                }
                stg128(P.out + (size_t)row * DM + col + 32 * i, ov[0], ov[1], ov[2], ov[3]);
            }
            PROF_EV(42); PROF_GT(43);
        }
    }
}

typedef CUresult (*EncodeFn)(CUtensorMap*, CUtensorMapDataType, cuuint32_t, void*, const cuuint64_t*, const cuuint64_t*, const cuuint32_t*,
                             const cuuint32_t*, CUtensorMapInterleave, CUtensorMapSwizzle, CUtensorMapL2promotion, CUtensorMapFloatOOBfill);

void make_map2d(EncodeFn enc, CUtensorMap* tm, const void* p, uint64_t cols, uint64_t rows) {
    cuuint64_t gd[2] = {cols, rows}, gs[1] = {cols * 2};
    cuuint32_t box[2] = {64, 128}, es[2] = {1, 1};
    enc(tm, CU_TENSOR_MAP_DATA_TYPE_BFLOAT16, 2, const_cast<void*>(p), gd, gs, box, es, CU_TENSOR_MAP_INTERLEAVE_NONE,
        CU_TENSOR_MAP_SWIZZLE_128B, CU_TENSOR_MAP_L2_PROMOTION_L2_128B, CU_TENSOR_MAP_FLOAT_OOB_FILL_NONE);
}

void make_map3d(EncodeFn enc, CUtensorMap* tm, const void* p, uint64_t cols, uint64_t rows, uint32_t bw, uint32_t nb) {
    cuuint64_t gd[3] = {bw, rows, cols / bw}, gs[2] = {cols * 2, bw * 2};
    cuuint32_t box[3] = {bw, 32, nb}, es[3] = {1, 1, 1};
    enc(tm, CU_TENSOR_MAP_DATA_TYPE_BFLOAT16, 3, const_cast<void*>(p), gd, gs, box, es, CU_TENSOR_MAP_INTERLEAVE_NONE,
        bw == 64 ? CU_TENSOR_MAP_SWIZZLE_128B : CU_TENSOR_MAP_SWIZZLE_64B, CU_TENSOR_MAP_L2_PROMOTION_L2_128B, CU_TENSOR_MAP_FLOAT_OOB_FILL_NONE);
}

}

extern "C" void kernel_launch(void* const* d_in, const int* in_sizes, int n_in, void* d_out, int out_size) {
    (void)in_sizes; (void)n_in; (void)out_size;
    static EncodeFn enc = nullptr;
    if (!enc) {
        void* fn = nullptr;
        cudaDriverEntryPointQueryResult qr;
        cudaGetDriverEntryPoint("cuTensorMapEncodeTiled", &fn, cudaEnableDefault, &qr);
        enc = (EncodeFn)fn;
        cudaFuncSetAttribute(fused_kernel, cudaFuncAttributeMaxDynamicSharedMemorySize, SMEM_BYTES);
    }
    CUtensorMap tmC, tmWk, tmWv, tmWq, tmWo, tmG, tmU, tmD;
    make_map2d(enc, &tmC, d_in[1], DC, SEQ);
    make_map2d(enc, &tmWq, d_in[2], 4096, DM);
    make_map2d(enc, &tmWk, d_in[3], 4096, DC);
    make_map2d(enc, &tmWv, d_in[4], 4096, DC);
    make_map3d(enc, &tmWo, d_in[5], DM, 4096, 32, 5);
    make_map3d(enc, &tmG, d_in[8], FF, DM, 64, 7);
    make_map3d(enc, &tmU, d_in[9], FF, DM, 64, 7);
    make_map3d(enc, &tmD, d_in[10], DM, FF, 64, 10);
    Params P;
    P.x = (const __nv_bfloat16*)d_in[0];
    P.wq = (const __nv_bfloat16*)d_in[2];
    P.wo = (const __nv_bfloat16*)d_in[5];
    P.wr = (const __nv_bfloat16*)d_in[7];
    P.out = (__nv_bfloat16*)d_out;
    fused_kernel<<<132, 384, SMEM_BYTES>>>(tmC, tmWk, tmWv, tmWq, tmWo, tmG, tmU, tmD, P);
}
```

```cpp
#include <cuda_runtime.h>
#include <cuda_bf16.h>
#include <cuda.h>
#include <stdint.h>

namespace {

constexpr int SEQ = 2048, NH = 32, DM = 640, DC = 512, FF = 1728, TOPC = 8;
constexpr int NSLOT = 7, SLOT_BYTES = 32768;
constexpr int NST3 = 6, ST3_BYTES = 36864;
constexpr int RING_BYTES = NSLOT * SLOT_BYTES;
constexpr int SMEM_BYTES = RING_BYTES + 3072;

constexpr int BAR_FULL = 96  , BAR_FULL3 = 152  , BAR_DEP = 200  , BAR_PF = 456, BAR_SEL = 464,
              BAR_LN = 472  , BAR_EV = 504  , BAR_EMPTY = 760  , BAR_EMPTY3 = 816  ,
              BAR_PROG = 864  , MISC_EPOCH = 880, MISC_SEL = 896, MISC_WR = 1024  ;
constexpr int D_LN = 0  , D_KV = 4  , D_Q = 12  , D_WAR = 14  , D_CTX = 16  ;
constexpr int EV_KV = 0  , EV_Q = 8  , EV_CTX = 12  ;

constexpr int FL_MOE_CNT = 0, FL_MOE_DONE = 1, FL_LN = 16  , FL_KV = 32  , FL_Q = 160  , FL_CTX = 416  , FL_WAR = 672  , FL_TOTAL = 704;

__device__ __align__(1024) unsigned char g_K[16 * 32 * 16384];
__device__ __align__(1024) unsigned char g_V[16 * 32 * 16384];
__device__ __align__(1024) unsigned char g_Q[NH * 32 * 16384];
__device__ __align__(1024) unsigned char g_xn[16 * 10 * 16384];
__device__ __align__(1024) uint4 g_part[128 * 10 * 256];
__device__ float g_router[SEQ];
__device__ __align__(16) float g_moe_part[4 * TOPC * DM];
__device__ __align__(16) __nv_bfloat16 g_brow[TOPC * DM];
__device__ __align__(16) int g_sel[TOPC];
__device__ unsigned g_flags[FL_TOTAL * 8];
__device__ unsigned g_epoch;

struct Params {
    const __nv_bfloat16 *x, *c, *wr, *wq, *wo;
    __nv_bfloat16* out;
};

__device__ __forceinline__ uint32_t smem_u32(const void* p) { return (uint32_t)__cvta_generic_to_shared(p); }
__device__ __forceinline__ void mbar_init(uint32_t bar, int cnt) { asm volatile("mbarrier.init.shared::cta.b64 [%0], %1;" ::"r"(bar), "r"(cnt)); }
__device__ __forceinline__ void mbar_expect_tx(uint32_t bar, uint32_t bytes) {
    asm volatile("mbarrier.arrive.expect_tx.shared::cta.b64 _, [%0], %1;" ::"r"(bar), "r"(bytes) : "memory");
}
__device__ __forceinline__ void mbar_arrive(uint32_t bar) { asm volatile("mbarrier.arrive.shared::cta.b64 _, [%0];" ::"r"(bar) : "memory"); }
__device__ __forceinline__ void mbar_arrive_cluster(uint32_t cluster_addr, uint32_t cnt) {
    asm volatile("mbarrier.arrive.shared::cluster.b64 _, [%0], %1;" ::"r"(cluster_addr), "r"(cnt) : "memory");
}
__device__ __forceinline__ uint32_t mapa(uint32_t addr, uint32_t cta) {
    uint32_t r; asm("mapa.shared::cluster.u32 %0, %1, %2;" : "=r"(r) : "r"(addr), "r"(cta)); return r;
}
__device__ __forceinline__ void mbar_wait(uint32_t bar, uint32_t parity) {
    asm volatile(
        "{\n.reg .pred p;\n.reg .u32 n;\n"
        "mbarrier.try_wait.parity.shared::cta.b64 p, [%0], %1;\n"
        "@p bra DONE;\n"
        "mov.u32 n, 0;\n"
        "LAB_WAIT:\n"
        "mbarrier.try_wait.parity.shared::cta.b64 p, [%0], %1, 100000;\n"
        "@p bra DONE;\n"
        "add.u32 n, n, 1;\n"
        "setp.lt.u32 p, n, 200000;\n"
        "@p bra LAB_WAIT;\n"
        "trap;\n"
        "DONE:\n}\n" ::"r"(bar), "r"(parity) : "memory");
}
__device__ __forceinline__ void mbar_wait_hot(uint32_t bar, uint32_t parity) {
    asm volatile("{\n.reg .pred p;\nLAB_WAIT:\nmbarrier.try_wait.parity.shared::cta.b64 p, [%0], %1;\n@!p bra LAB_WAIT;\n}\n" ::"r"(bar), "r"(parity) : "memory");
}
__device__ __forceinline__ void flag_wait(const unsigned* flag, unsigned target) {
    asm volatile(
        "{\n.reg .pred p;\n.reg .u32 n, v;\n.reg .s32 d;\n"
        "mov.u32 n, 0;\n"
        "LAB_WAIT:\n"
        "ld.acquire.gpu.global.u32 v, [%0];\n"
        "sub.s32 d, v, %1;\n"
        "setp.ge.s32 p, d, 0;\n"
        "@p bra DONE;\n"
        "nanosleep.u32 40;\n"
        "add.u32 n, n, 1;\n"
        "setp.lt.u32 p, n, 3000000;\n"
        "@p bra LAB_WAIT;\n"
        "trap;\n"
        "DONE:\n}\n" ::"l"(flag), "r"(target) : "memory");
}
__device__ __forceinline__ void flag_signal(unsigned* flag) {
    asm volatile("red.release.gpu.global.add.u32 [%0], 1;" ::"l"(flag) : "memory");
}
__device__ __forceinline__ void fence_async_global() { asm volatile("fence.proxy.async.global;" ::: "memory"); }
__device__ __forceinline__ unsigned* flag_ptr(int idx) { return g_flags + idx * 8; }

__device__ __forceinline__ uint64_t policy_stream() {
    uint64_t p; asm("createpolicy.fractional.L2::evict_first.b64 %0, 1.0;" : "=l"(p)); return p;
}
__device__ __forceinline__ uint64_t policy_normal() {
    uint64_t p; asm("createpolicy.fractional.L2::evict_normal.b64 %0, 1.0;" : "=l"(p)); return p;
}
__device__ __forceinline__ void bulk_load(uint32_t dst, const void* src, uint32_t bytes, uint32_t bar) {
    asm volatile("cp.async.bulk.shared::cluster.global.mbarrier::complete_tx::bytes [%0], [%1], %2, [%3];"
                 ::"r"(dst), "l"(src), "r"(bytes), "r"(bar) : "memory");
}
__device__ __forceinline__ void bulk_load_mc(uint32_t dst, const void* src, uint32_t bytes, uint32_t bar) {
    asm volatile("cp.async.bulk.shared::cluster.global.mbarrier::complete_tx::bytes.multicast::cluster [%0], [%1], %2, [%3], %4;"
                 ::"r"(dst), "l"(src), "r"(bytes), "r"(bar), "h"((uint16_t)3) : "memory");
}
__device__ __forceinline__ void tma2d(uint32_t dst, const CUtensorMap* tm, int c0, int c1, uint32_t bar) {
    asm volatile("cp.async.bulk.tensor.2d.shared::cluster.global.mbarrier::complete_tx::bytes [%0], [%1, {%3, %4}], [%2];"
                 ::"r"(dst), "l"(tm), "r"(bar), "r"(c0), "r"(c1) : "memory");
}
__device__ __forceinline__ void tma2d_mc(uint32_t dst, const CUtensorMap* tm, int c0, int c1, uint32_t bar) {
    asm volatile("cp.async.bulk.tensor.2d.shared::cluster.global.mbarrier::complete_tx::bytes.multicast::cluster [%0], [%1, {%3, %4}], [%2], %5;"
                 ::"r"(dst), "l"(tm), "r"(bar), "r"(c0), "r"(c1), "h"((uint16_t)3) : "memory");
}
__device__ __forceinline__ void tma3d_mc(uint32_t dst, const CUtensorMap* tm, int c0, int c1, int c2, uint32_t bar) {
    asm volatile("cp.async.bulk.tensor.3d.shared::cluster.global.mbarrier::complete_tx::bytes.multicast::cluster [%0], [%1, {%3, %4, %5}], [%2], %6;"
                 ::"r"(dst), "l"(tm), "r"(bar), "r"(c0), "r"(c1), "r"(c2), "h"((uint16_t)3) : "memory");
}
__device__ __forceinline__ void tma3d(uint32_t dst, const CUtensorMap* tm, int c0, int c1, int c2, uint32_t bar) {
    asm volatile("cp.async.bulk.tensor.3d.shared::cluster.global.mbarrier::complete_tx::bytes.L2::cache_hint [%0], [%1, {%3, %4, %5}], [%2], %6;"
                 ::"r"(dst), "l"(tm), "r"(bar), "r"(c0), "r"(c1), "r"(c2), "l"(policy_stream()) : "memory");
}
__device__ __forceinline__ void tma2d_prefetch(const CUtensorMap* tm, int c0, int c1) {
    asm volatile("cp.async.bulk.prefetch.tensor.2d.L2.global [%0, {%1, %2}];" ::"l"(tm), "r"(c0), "r"(c1) : "memory");
}
__device__ __forceinline__ void tma3d_prefetch(const CUtensorMap* tm, int c0, int c1, int c2) {
    asm volatile("cp.async.bulk.prefetch.tensor.3d.L2.global [%0, {%1, %2, %3}];" ::"l"(tm), "r"(c0), "r"(c1), "r"(c2) : "memory");
}
__device__ __forceinline__ void l2_prefetch(const void* p, uint32_t bytes) {
    asm volatile("cp.async.bulk.prefetch.L2.global [%0], %1;" ::"l"(p), "r"(bytes) : "memory");
}
__device__ __forceinline__ bool elect_one() {
    uint32_t r; asm volatile("{\n.reg .pred p;\nelect.sync _|p, 0xffffffff;\nselp.u32 %0, 1, 0, p;\n}\n" : "=r"(r)); return r != 0;
}
__device__ __forceinline__ void wg_fence() { asm volatile("wgmma.fence.sync.aligned;" ::: "memory"); }
__device__ __forceinline__ void wg_commit() { asm volatile("wgmma.commit_group.sync.aligned;" ::: "memory"); }
template <int N> __device__ __forceinline__ void wg_wait() { asm volatile("wgmma.wait_group.sync.aligned %0;" ::"n"(N) : "memory"); }
__device__ __forceinline__ void bar_sync(int id, int n) { asm volatile("bar.sync %0, %1;" ::"r"(id), "r"(n) : "memory"); }
__device__ __forceinline__ void bar_arrive(int id, int n) { asm volatile("bar.arrive %0, %1;" ::"r"(id), "r"(n) : "memory"); }
template <int N> __device__ __forceinline__ void fence_regs(float (&a)[N]) {
#pragma unroll
    for (int i = 0; i < N; i++) asm volatile("" : "+f"(a[i])::"memory");
}
template <int N> __device__ __forceinline__ void undef_regs(float (&a)[N]) {
#pragma unroll
    for (int i = 0; i < N; i++) asm volatile("" : "=f"(a[i]));
}
__device__ __forceinline__ void ldsm4t(uint32_t& r0, uint32_t& r1, uint32_t& r2, uint32_t& r3, uint32_t addr) {
    asm volatile("ldmatrix.sync.aligned.m8n8.x4.trans.shared.b16 {%0,%1,%2,%3}, [%4];"
                 : "=r"(r0), "=r"(r1), "=r"(r2), "=r"(r3) : "r"(addr) : "memory");
}
__device__ __forceinline__ uint32_t pack_bf16(float lo, float hi) {
    uint32_t r; asm("cvt.rn.bf16x2.f32 %0, %1, %2;" : "=r"(r) : "f"(hi), "f"(lo)); return r;
}
__device__ __forceinline__ float bf_lo(uint32_t v) { return __uint_as_float(v << 16); }
__device__ __forceinline__ float bf_hi(uint32_t v) { return __uint_as_float(v & 0xffff0000u); }
__device__ __forceinline__ float bf_round(float v) { return __bfloat162float(__float2bfloat16_rn(v)); }
__device__ __forceinline__ float ex2(float v) { float r; asm("ex2.approx.ftz.f32 %0, %1;" : "=f"(r) : "f"(v)); return r; }
__device__ __forceinline__ void ex2v(float& v) { asm volatile("ex2.approx.ftz.f32 %0, %0;" : "+f"(v)); }
__device__ __forceinline__ float rcp_fast(float v) { float r; asm("rcp.approx.ftz.f32 %0, %1;" : "=f"(r) : "f"(v)); return r; }
__device__ __forceinline__ float sqrt_fast(float v) { float r; asm("sqrt.approx.ftz.f32 %0, %1;" : "=f"(r) : "f"(v)); return r; }
__device__ __forceinline__ void stg128(void* p, uint32_t a, uint32_t b, uint32_t c, uint32_t d) {
    asm volatile("st.global.v4.b32 [%0], {%1,%2,%3,%4};" ::"l"(p), "r"(a), "r"(b), "r"(c), "r"(d) : "memory");
}
__device__ __forceinline__ void stg128_hint(void* p, uint32_t a, uint32_t b, uint32_t c, uint32_t d, uint64_t pol) {
    asm volatile("st.global.L2::cache_hint.v4.b32 [%0], {%1,%2,%3,%4}, %5;" ::"l"(p), "r"(a), "r"(b), "r"(c), "r"(d), "l"(pol) : "memory");
}
__device__ __forceinline__ uint4 ldg128(const void* p) {
    uint4 v; asm volatile("ld.global.cg.v4.b32 {%0,%1,%2,%3}, [%4];" : "=r"(v.x), "=r"(v.y), "=r"(v.z), "=r"(v.w) : "l"(p) : "memory"); return v;
}
__device__ __forceinline__ uint64_t mkdesc(uint32_t addr, uint32_t lbo, uint32_t sbo, uint32_t swz) {
    uint32_t lo = ((addr & 0x3FFFF) >> 4) | ((lbo >> 4) << 16);
    uint32_t hi = (sbo >> 4) | (swz << 30);
    return ((uint64_t)hi << 32) | lo;
}
__device__ __forceinline__ int perm32(int v) { return (v & ~30) | ((v >> 2) & 6) | ((v << 2) & 24); }

__device__ __forceinline__ void wgmma_rs_n128_ta0_tb0(float (&d)[64], uint32_t a0, uint32_t a1, uint32_t a2, uint32_t a3, uint64_t descB, int scaleD) {
  asm volatile("{\n.reg .pred p;\nsetp.ne.b32 p, %69, 0;\n"
    "wgmma.mma_async.sync.aligned.m64n128k16.f32.bf16.bf16 "
    "{%0, %1, %2, %3, %4, %5, %6, %7, %8, %9, %10, %11, %12, %13, %14, %15, %16, %17, %18, %19, %20, %21, %22, %23, %24, %25, %26, %27, %28, %29, %30, %31, %32, %33, %34, %35, %36, %37, %38, %39, %40, %41, %42, %43, %44, %45, %46, %47, %48, %49, %50, %51, %52, %53, %54, %55, %56, %57, %58, %59, %60, %61, %62, %63}, "
    "{%64, %65, %66, %67}, %68, p, 1, 1, 0;\n}\n"
    : "+f"(d[0]), "+f"(d[1]), "+f"(d[2]), "+f"(d[3]), "+f"(d[4]), "+f"(d[5]), "+f"(d[6]), "+f"(d[7]), "+f"(d[8]), "+f"(d[9]), "+f"(d[10]), "+f"(d[11]), "+f"(d[12]), "+f"(d[13]), "+f"(d[14]), "+f"(d[15]), "+f"(d[16]), "+f"(d[17]), "+f"(d[18]), "+f"(d[19]), "+f"(d[20]), "+f"(d[21]), "+f"(d[22]), "+f"(d[23]), "+f"(d[24]), "+f"(d[25]), "+f"(d[26]), "+f"(d[27]), "+f"(d[28]), "+f"(d[29]), "+f"(d[30]), "+f"(d[31]), "+f"(d[32]), "+f"(d[33]), "+f"(d[34]), "+f"(d[35]), "+f"(d[36]), "+f"(d[37]), "+f"(d[38]), "+f"(d[39]), "+f"(d[40]), "+f"(d[41]), "+f"(d[42]), "+f"(d[43]), "+f"(d[44]), "+f"(d[45]), "+f"(d[46]), "+f"(d[47]), "+f"(d[48]), "+f"(d[49]), "+f"(d[50]), "+f"(d[51]), "+f"(d[52]), "+f"(d[53]), "+f"(d[54]), "+f"(d[55]), "+f"(d[56]), "+f"(d[57]), "+f"(d[58]), "+f"(d[59]), "+f"(d[60]), "+f"(d[61]), "+f"(d[62]), "+f"(d[63])
    : "r"(a0), "r"(a1), "r"(a2), "r"(a3), "l"(descB), "r"(scaleD));
}
__device__ __forceinline__ void wgmma_rs_n128_ta0_tb1(float (&d)[64], uint32_t a0, uint32_t a1, uint32_t a2, uint32_t a3, uint64_t descB, int scaleD) {
  asm volatile("{\n.reg .pred p;\nsetp.ne.b32 p, %69, 0;\n"
    "wgmma.mma_async.sync.aligned.m64n128k16.f32.bf16.bf16 "
    "{%0, %1, %2, %3, %4, %5, %6, %7, %8, %9, %10, %11, %12, %13, %14, %15, %16, %17, %18, %19, %20, %21, %22, %23, %24, %25, %26, %27, %28, %29, %30, %31, %32, %33, %34, %35, %36, %37, %38, %39, %40, %41, %42, %43, %44, %45, %46, %47, %48, %49, %50, %51, %52, %53, %54, %55, %56, %57, %58, %59, %60, %61, %62, %63}, "
    "{%64, %65, %66, %67}, %68, p, 1, 1, 1;\n}\n"
    : "+f"(d[0]), "+f"(d[1]), "+f"(d[2]), "+f"(d[3]), "+f"(d[4]), "+f"(d[5]), "+f"(d[6]), "+f"(d[7]), "+f"(d[8]), "+f"(d[9]), "+f"(d[10]), "+f"(d[11]), "+f"(d[12]), "+f"(d[13]), "+f"(d[14]), "+f"(d[15]), "+f"(d[16]), "+f"(d[17]), "+f"(d[18]), "+f"(d[19]), "+f"(d[20]), "+f"(d[21]), "+f"(d[22]), "+f"(d[23]), "+f"(d[24]), "+f"(d[25]), "+f"(d[26]), "+f"(d[27]), "+f"(d[28]), "+f"(d[29]), "+f"(d[30]), "+f"(d[31]), "+f"(d[32]), "+f"(d[33]), "+f"(d[34]), "+f"(d[35]), "+f"(d[36]), "+f"(d[37]), "+f"(d[38]), "+f"(d[39]), "+f"(d[40]), "+f"(d[41]), "+f"(d[42]), "+f"(d[43]), "+f"(d[44]), "+f"(d[45]), "+f"(d[46]), "+f"(d[47]), "+f"(d[48]), "+f"(d[49]), "+f"(d[50]), "+f"(d[51]), "+f"(d[52]), "+f"(d[53]), "+f"(d[54]), "+f"(d[55]), "+f"(d[56]), "+f"(d[57]), "+f"(d[58]), "+f"(d[59]), "+f"(d[60]), "+f"(d[61]), "+f"(d[62]), "+f"(d[63])
    : "r"(a0), "r"(a1), "r"(a2), "r"(a3), "l"(descB), "r"(scaleD));
}
__device__ __forceinline__ void wgmma_rs_n64_ta0_tb1(float (&d)[32], uint32_t a0, uint32_t a1, uint32_t a2, uint32_t a3, uint64_t descB, int scaleD) {
  asm volatile("{\n.reg .pred p;\nsetp.ne.b32 p, %37, 0;\n"
    "wgmma.mma_async.sync.aligned.m64n64k16.f32.bf16.bf16 "
    "{%0, %1, %2, %3, %4, %5, %6, %7, %8, %9, %10, %11, %12, %13, %14, %15, %16, %17, %18, %19, %20, %21, %22, %23, %24, %25, %26, %27, %28, %29, %30, %31}, "
    "{%32, %33, %34, %35}, %36, p, 1, 1, 1;\n}\n"
    : "+f"(d[0]), "+f"(d[1]), "+f"(d[2]), "+f"(d[3]), "+f"(d[4]), "+f"(d[5]), "+f"(d[6]), "+f"(d[7]), "+f"(d[8]), "+f"(d[9]), "+f"(d[10]), "+f"(d[11]), "+f"(d[12]), "+f"(d[13]), "+f"(d[14]), "+f"(d[15]), "+f"(d[16]), "+f"(d[17]), "+f"(d[18]), "+f"(d[19]), "+f"(d[20]), "+f"(d[21]), "+f"(d[22]), "+f"(d[23]), "+f"(d[24]), "+f"(d[25]), "+f"(d[26]), "+f"(d[27]), "+f"(d[28]), "+f"(d[29]), "+f"(d[30]), "+f"(d[31])
    : "r"(a0), "r"(a1), "r"(a2), "r"(a3), "l"(descB), "r"(scaleD));
}
__device__ __forceinline__ void wgmma_ss_n128_ta1_tb0(float (&d)[64], uint64_t descA, uint64_t descB, int scaleD) {
  asm volatile("{\n.reg .pred p;\nsetp.ne.b32 p, %66, 0;\n"
    "wgmma.mma_async.sync.aligned.m64n128k16.f32.bf16.bf16 "
    "{%0, %1, %2, %3, %4, %5, %6, %7, %8, %9, %10, %11, %12, %13, %14, %15, %16, %17, %18, %19, %20, %21, %22, %23, %24, %25, %26, %27, %28, %29, %30, %31, %32, %33, %34, %35, %36, %37, %38, %39, %40, %41, %42, %43, %44, %45, %46, %47, %48, %49, %50, %51, %52, %53, %54, %55, %56, %57, %58, %59, %60, %61, %62, %63}, "
    "%64, %65, p, 1, 1, 1, 0;\n}\n"
    : "+f"(d[0]), "+f"(d[1]), "+f"(d[2]), "+f"(d[3]), "+f"(d[4]), "+f"(d[5]), "+f"(d[6]), "+f"(d[7]), "+f"(d[8]), "+f"(d[9]), "+f"(d[10]), "+f"(d[11]), "+f"(d[12]), "+f"(d[13]), "+f"(d[14]), "+f"(d[15]), "+f"(d[16]), "+f"(d[17]), "+f"(d[18]), "+f"(d[19]), "+f"(d[20]), "+f"(d[21]), "+f"(d[22]), "+f"(d[23]), "+f"(d[24]), "+f"(d[25]), "+f"(d[26]), "+f"(d[27]), "+f"(d[28]), "+f"(d[29]), "+f"(d[30]), "+f"(d[31]), "+f"(d[32]), "+f"(d[33]), "+f"(d[34]), "+f"(d[35]), "+f"(d[36]), "+f"(d[37]), "+f"(d[38]), "+f"(d[39]), "+f"(d[40]), "+f"(d[41]), "+f"(d[42]), "+f"(d[43]), "+f"(d[44]), "+f"(d[45]), "+f"(d[46]), "+f"(d[47]), "+f"(d[48]), "+f"(d[49]), "+f"(d[50]), "+f"(d[51]), "+f"(d[52]), "+f"(d[53]), "+f"(d[54]), "+f"(d[55]), "+f"(d[56]), "+f"(d[57]), "+f"(d[58]), "+f"(d[59]), "+f"(d[60]), "+f"(d[61]), "+f"(d[62]), "+f"(d[63])
    : "l"(descA), "l"(descB), "r"(scaleD));
}
__device__ __forceinline__ void wgmma_ss_n160_ta0_tb1(float (&d)[80], uint64_t descA, uint64_t descB, int scaleD) {
  asm volatile("{\n.reg .pred p;\nsetp.ne.b32 p, %82, 0;\n"
    "wgmma.mma_async.sync.aligned.m64n160k16.f32.bf16.bf16 "
    "{%0, %1, %2, %3, %4, %5, %6, %7, %8, %9, %10, %11, %12, %13, %14, %15, %16, %17, %18, %19, %20, %21, %22, %23, %24, %25, %26, %27, %28, %29, %30, %31, %32, %33, %34, %35, %36, %37, %38, %39, %40, %41, %42, %43, %44, %45, %46, %47, %48, %49, %50, %51, %52, %53, %54, %55, %56, %57, %58, %59, %60, %61, %62, %63, %64, %65, %66, %67, %68, %69, %70, %71, %72, %73, %74, %75, %76, %77, %78, %79}, "
    "%80, %81, p, 1, 1, 0, 1;\n}\n"
    : "+f"(d[0]), "+f"(d[1]), "+f"(d[2]), "+f"(d[3]), "+f"(d[4]), "+f"(d[5]), "+f"(d[6]), "+f"(d[7]), "+f"(d[8]), "+f"(d[9]), "+f"(d[10]), "+f"(d[11]), "+f"(d[12]), "+f"(d[13]), "+f"(d[14]), "+f"(d[15]), "+f"(d[16]), "+f"(d[17]), "+f"(d[18]), "+f"(d[19]), "+f"(d[20]), "+f"(d[21]), "+f"(d[22]), "+f"(d[23]), "+f"(d[24]), "+f"(d[25]), "+f"(d[26]), "+f"(d[27]), "+f"(d[28]), "+f"(d[29]), "+f"(d[30]), "+f"(d[31]), "+f"(d[32]), "+f"(d[33]), "+f"(d[34]), "+f"(d[35]), "+f"(d[36]), "+f"(d[37]), "+f"(d[38]), "+f"(d[39]), "+f"(d[40]), "+f"(d[41]), "+f"(d[42]), "+f"(d[43]), "+f"(d[44]), "+f"(d[45]), "+f"(d[46]), "+f"(d[47]), "+f"(d[48]), "+f"(d[49]), "+f"(d[50]), "+f"(d[51]), "+f"(d[52]), "+f"(d[53]), "+f"(d[54]), "+f"(d[55]), "+f"(d[56]), "+f"(d[57]), "+f"(d[58]), "+f"(d[59]), "+f"(d[60]), "+f"(d[61]), "+f"(d[62]), "+f"(d[63]), "+f"(d[64]), "+f"(d[65]), "+f"(d[66]), "+f"(d[67]), "+f"(d[68]), "+f"(d[69]), "+f"(d[70]), "+f"(d[71]), "+f"(d[72]), "+f"(d[73]), "+f"(d[74]), "+f"(d[75]), "+f"(d[76]), "+f"(d[77]), "+f"(d[78]), "+f"(d[79])
    : "l"(descA), "l"(descB), "r"(scaleD));
}

#define PROF_DECL
#define PROF_EV(tag)
#define PROF_GT(tag)

template <int N> struct IC { static constexpr int value = N; };
struct Cur {
    uint32_t slot, ph;
    __device__ __forceinline__ void adv() { if (++slot == NSLOT) { slot = 0; ph ^= 1; } }
};
constexpr int E0 = 6, E_ATT0 = 48, E_ATT1 = 108;
__host__ __device__ constexpr uint32_t slot_of(int e) { return (e + E0) % NSLOT; }
__device__ __forceinline__ Cur cur_at(int e) { Cur c; c.slot = (e + E0) % NSLOT; c.ph = ((e + E0) / NSLOT) & 1; return c; }

__device__ __forceinline__ int q_tile(int k, int t) { return (t < 2 ? 14 - 2 * k : 2 * k) + (t & 1); }
__device__ __forceinline__ int op_head(int i, int kap) { return 16 * kap + 2 * (i & 7) + (i >> 3); }

constexpr float SM_SCALE = 0.08838834764831845f * 1.4426950408889634f;

struct Ctx {
    uint32_t ring, misc;
    uint32_t rel;
    int w, warp, lane;
};
__device__ __forceinline__ void release(const Ctx& c, uint32_t off, uint32_t cnt) {
    if (c.lane < 2) mbar_arrive_cluster(c.rel + off, cnt);
}
__device__ __forceinline__ void signal_event(const Ctx& c, int ev) {
    __syncwarp();
    if (c.lane == 0) mbar_arrive(c.misc + BAR_EV + (c.w * 16 + ev) * 8);
}
template <int NK, int OFF, int N>
__device__ __forceinline__ uint32_t load_afrag(uint32_t (&a)[N], uint32_t base, const Ctx& c) {
    int r = c.lane & 7, mat = c.lane >> 3;
    uint32_t addr = base + (8 * (mat >> 1) + r) * 128 + (((2 * c.warp + (mat & 1)) ^ r) << 4);
#pragma unroll
    for (int k = 0; k < NK; k++) ldsm4t(a[OFF + 4 * k], a[OFF + 4 * k + 1], a[OFF + 4 * k + 2], a[OFF + 4 * k + 3], addr + k * 2048);
    uint32_t dep = 0;
#pragma unroll
    for (int k = 0; k < NK; k++) dep |= a[OFF + 4 * k];
    return dep & blockIdx.y;
}
__device__ __forceinline__ void store_proj(const float (&acc)[64], unsigned char* dst  , const Ctx& c, uint64_t pol) {
    int g = c.lane >> 2, t = c.lane & 3;
#pragma unroll
    for (int i = 0; i < 2; i++) {
        int row = perm32(64 * c.w + 16 * c.warp + 8 * i + g);
        unsigned char* p = dst + row * 128;
#pragma unroll
        for (int q = 0; q < 4; q++) {
            int chunk = (4 * (q & 1) + t) ^ (row & 7);
            stg128_hint(p + (q >> 1) * 16384 + chunk * 16,
                   pack_bf16(acc[16 * q + 2 * i], acc[16 * q + 2 * i + 1]), pack_bf16(acc[16 * q + 4 + 2 * i], acc[16 * q + 4 + 2 * i + 1]),
                   pack_bf16(acc[16 * q + 8 + 2 * i], acc[16 * q + 8 + 2 * i + 1]), pack_bf16(acc[16 * q + 12 + 2 * i], acc[16 * q + 12 + 2 * i + 1]), pol);
        }
    }
}

constexpr float SAFE_EXP = 40.0f, SAFE_SUM = 1099511627776.0f;
template <int NJ>
__device__ __forceinline__ void row_max(const float (&s)[4 * NJ], float (&mx)[2]) {
#pragma unroll
    for (int i = 0; i < 2; i++) {
        float a = fmaxf(s[2 * i], s[2 * i + 1]), b = fmaxf(s[4 + 2 * i], s[4 + 2 * i + 1]);
#pragma unroll
        for (int j = 2; j < NJ; j += 2) {
            a = fmaxf(a, fmaxf(s[4 * j + 2 * i], s[4 * j + 2 * i + 1]));
            b = fmaxf(b, fmaxf(s[4 * j + 4 + 2 * i], s[4 * j + 4 + 2 * i + 1]));
        }
        a = fmaxf(a, b);
        a = fmaxf(a, __shfl_xor_sync(0xffffffffu, a, 1));
        mx[i] = fmaxf(a, __shfl_xor_sync(0xffffffffu, a, 2));
    }
}
template <int NJ, bool SHIFT>
__device__ __forceinline__ void exp_sum(float (&s)[4 * NJ], const float (&m)[2], float& l0, float& l1) {
#pragma unroll
    for (int j = 0; j < NJ; j++) {
#pragma unroll
        for (int e = 0; e < 4; e++) s[4 * j + e] = ex2(SHIFT ? s[4 * j + e] - m[e >> 1] : s[4 * j + e]);
        l0 += s[4 * j + 0] + s[4 * j + 1]; l1 += s[4 * j + 2] + s[4 * j + 3];
    }
}
template <int NJ>
__device__ __forceinline__ bool softmax_first(float (&s)[4 * NJ], float (&m)[2], float (&l)[2]) {
    row_max<NJ>(s, m);
    bool gen = __any_sync(0xffffffffu, !(fabsf(m[0]) <= SAFE_EXP && fabsf(m[1]) <= SAFE_EXP));
    if (!gen) m[0] = m[1] = 0.f;
    l[0] = l[1] = 0.f;
    exp_sum<NJ, true>(s, m, l[0], l[1]);
    return gen;
}
__device__ __forceinline__ void recompute_scores(float (&s)[64], const uint32_t (&q)[32], uint32_t kaddr, const Ctx& c) {
    const int r = c.lane & 7, mat = c.lane >> 3;
    const uint32_t a0 = kaddr + (8 * (mat & 1) + r) * 128 + (((mat >> 1) ^ r) << 4);
#pragma unroll
    for (int i = 0; i < 64; i++) s[i] = 0.f;
#pragma unroll
    for (int jp = 0; jp < 8; jp++) {
#pragma unroll
        for (int k = 0; k < 8; k++) {
            asm volatile(
                "{\n.reg .b32 b0, b1, b2, b3;\n"
                "ldmatrix.sync.aligned.m8n8.x4.trans.shared.b16 {b0,b1,b2,b3}, [%12];\n"
                "mma.sync.aligned.m16n8k16.row.col.f32.bf16.bf16.f32 {%0,%1,%2,%3}, {%8,%9,%10,%11}, {b0,b1}, {%0,%1,%2,%3};\n"
                "mma.sync.aligned.m16n8k16.row.col.f32.bf16.bf16.f32 {%4,%5,%6,%7}, {%8,%9,%10,%11}, {b2,b3}, {%4,%5,%6,%7};\n}\n"
                : "+f"(s[8 * jp]), "+f"(s[8 * jp + 1]), "+f"(s[8 * jp + 2]), "+f"(s[8 * jp + 3]),
                  "+f"(s[8 * jp + 4]), "+f"(s[8 * jp + 5]), "+f"(s[8 * jp + 6]), "+f"(s[8 * jp + 7])
                : "r"(q[4 * k]), "r"(q[4 * k + 1]), "r"(q[4 * k + 2]), "r"(q[4 * k + 3]),
                  "r"((a0 ^ ((jp & 3) << 5)) + (jp >> 2) * 16384 + k * 2048) : "memory");
        }
    }
}
template <int J0>
__device__ __forceinline__ void mask_diag(float (&s)[4 * J0 + 32], const Ctx& c) {
    int g = c.lane >> 2, t = c.lane & 3;
#pragma unroll
    for (int i = 0; i < 2; i++) {
        int lim = perm32(16 * c.warp + 8 * i + g) - 8 * t;
#pragma unroll
        for (int j = 0; j < 8; j++)
#pragma unroll
            for (int e = 0; e < 2; e++)
                if (32 * (j >> 2) + 2 * (j & 3) + e > lim) s[4 * (J0 + j) + 2 * i + e] = -INFINITY;
    }
}
__device__ __forceinline__ void issue_pv(float (&o)[64], const uint32_t (&p)[32], uint32_t vaddr, int acc, bool half) {
    uint64_t d = mkdesc(vaddr, 16, 1024, 1);
    if (half) {
        wg_fence();
#pragma unroll
        for (int k = 0; k < 4; k++) wgmma_rs_n128_ta0_tb0(o, p[4 * k], p[4 * k + 1], p[4 * k + 2], p[4 * k + 3], d + 2 * k, k != 0);
        wg_commit();
    } else {
        wg_fence();
#pragma unroll
        for (int k = 0; k < 8; k++)
            wgmma_rs_n128_ta0_tb0(o, p[4 * k], p[4 * k + 1], p[4 * k + 2], p[4 * k + 3], d + (k >> 2) * 1024 + 2 * (k & 3), k ? 1 : acc);
        wg_commit();
    }
}
__device__ __forceinline__ void issue_qk(float (&s)[64], const uint32_t (&q)[32], uint32_t kaddr) {
    uint64_t d = mkdesc(kaddr, 16384, 1024, 1);
    wg_fence();
#pragma unroll
    for (int k = 0; k < 8; k++) wgmma_rs_n128_ta0_tb1(s, q[4 * k], q[4 * k + 1], q[4 * k + 2], q[4 * k + 3], d + 128 * k, k != 0);
    wg_commit();
}
__device__ __forceinline__ void issue_qk_half(float (&s32)[32], const uint32_t (&q)[32], uint32_t kaddr) {
    uint64_t d = mkdesc(kaddr, 16384, 1024, 1);
    wg_fence();
#pragma unroll
    for (int k = 0; k < 8; k++) wgmma_rs_n64_ta0_tb1(s32, q[4 * k], q[4 * k + 1], q[4 * k + 2], q[4 * k + 3], d + 128 * k, k != 0);
    wg_commit();
}
__device__ __forceinline__ void row_inv(const float (&l)[2], float (&inv)[2]) {
#pragma unroll
    for (int i = 0; i < 2; i++) {
        float sum = l[i];
        sum += __shfl_xor_sync(0xffffffffu, sum, 1);
        sum += __shfl_xor_sync(0xffffffffu, sum, 2);
        inv[i] = rcp_fast(sum);
    }
}
__device__ __forceinline__ void stage_ctx(float (&o)[64], const float (&inv)[2], Cur ce, const Ctx& c) {
    const int g = c.lane >> 2, t = c.lane & 3, r7 = ((g & 1) << 2) | (g >> 1);
    const uint32_t base = c.ring + ce.slot * SLOT_BYTES + c.w * 16384 + (16 * c.warp + r7) * 128 + ((t ^ r7) << 4);
    mbar_wait_hot(c.misc + BAR_FULL + 8 * ce.slot, ce.ph);
#pragma unroll
    for (int q = 0; q < 4; q++) {
        uint32_t v[8];
#pragma unroll
        for (int i = 0; i < 2; i++)
#pragma unroll
            for (int j = 0; j < 4; j++) v[4 * i + j] = pack_bf16(o[16 * q + 4 * j + 2 * i] * inv[i], o[16 * q + 4 * j + 2 * i + 1] * inv[i]);
#pragma unroll
        for (int i = 0; i < 8; i++) { o[16 * q + i] = __uint_as_float(v[i]); asm volatile("" : "=f"(o[16 * q + 8 + i])); }
#pragma unroll
        for (int i = 0; i < 2; i++)
            asm volatile("st.shared.v4.b32 [%0], {%1,%2,%3,%4};" ::"r"((base ^ ((q & 1) << 6)) + (q >> 1) * 8192 + i * 1024),
                         "r"(v[4 * i]), "r"(v[4 * i + 1]), "r"(v[4 * i + 2]), "r"(v[4 * i + 3]) : "memory");
    }
}
__device__ __forceinline__ void publish_ctx(int ev, const Ctx& c) {
    asm volatile("fence.proxy.async.shared::cta;" ::: "memory");
    signal_event(c, ev);
}

__device__ __forceinline__ const unsigned char* xn_addr(int row, int col) {
    return g_xn + ((row >> 7) * 10 + (col >> 6)) * 16384 + (row & 127) * 128 + ((((col & 63) >> 3) ^ (row & 7)) << 4);
}
__device__ __forceinline__ void mma16816(float (&d)[4], uint32_t a0, uint32_t a1, uint32_t a2, uint32_t a3, uint32_t b0, uint32_t b1) {
    asm volatile("mma.sync.aligned.m16n8k16.row.col.f32.bf16.bf16.f32 {%0,%1,%2,%3}, {%4,%5,%6,%7}, {%8,%9}, {%0,%1,%2,%3};"
                 : "+f"(d[0]), "+f"(d[1]), "+f"(d[2]), "+f"(d[3]) : "r"(a0), "r"(a1), "r"(a2), "r"(a3), "r"(b0), "r"(b1));
}
__device__ __forceinline__ uint32_t lds32(uint32_t addr) { uint32_t v; asm volatile("ld.shared.u32 %0, [%1];" : "=r"(v) : "r"(addr)); return v; }

__device__ __forceinline__ void aux_cta(const CUtensorMap* tmG, const CUtensorMap* tmU, const CUtensorMap* tmD, unsigned char* sm, int a) {
    constexpr int STG = 57344, XS = 3 * STG, HS = XS + 8 * 1296, KEY = HS + 8 * 912, MI = KEY + 8192;
    const int tid = threadIdx.x, warp = __shfl_sync(0xffffffffu, tid >> 5, 0), lane = tid & 31;
    const uint32_t sb = smem_u32(sm);
    const uint32_t full = sb + MI, empty = sb + MI + 32;
    int* s_sel = reinterpret_cast<int*>(sm + MI + 64);
    float* s_r = reinterpret_cast<float*>(sm + MI + 96);
    volatile unsigned* s_misc = reinterpret_cast<volatile unsigned*>(sm + MI + 128);
    uint32_t* s_key = reinterpret_cast<uint32_t*>(sm + KEY);
    PROF_DECL
    PROF_GT(0);
    if (tid == 0) {
        for (int i = 0; i < 3; i++) { mbar_init(full + 8 * i, 1); mbar_init(empty + 8 * i, 10); }
        asm volatile("fence.mbarrier_init.release.cluster;" ::: "memory");
    }
    __syncthreads();
    if (warp == 11) {
        if (elect_one()) {
            int st = 0; uint32_t ph = 0;
#pragma unroll 1
            for (int s = 0; s < 34; s++) {
                mbar_wait(empty + 8 * st, ph ^ 1);
                const uint32_t dst = sb + st * STG, fb = full + 8 * st;
                if (s < 20) {
                    mbar_expect_tx(fb, 57344);
                    tma3d(dst, tmG, 0, 32 * s, 7 * a, fb);
                    tma3d(dst + 28672, tmU, 0, 32 * s, 7 * a, fb);
                } else {
                    mbar_expect_tx(fb, 40960);
                    tma3d(dst, tmD, 0, 448 * a + 32 * (s - 20), 0, fb);
                }
                if (s >= 3) {
#pragma unroll 1
                    for (int f = (s == 3 ? 4 : s + 6); f <= s + 6 && f < 34; f++) {
                        if (f < 20) { tma3d_prefetch(tmG, 0, 32 * f, 7 * a); tma3d_prefetch(tmU, 0, 32 * f, 7 * a); }
                        else tma3d_prefetch(tmD, 0, 448 * a + 32 * (f - 20), 0);
                    }
                }
                if (++st == 3) { st = 0; ph ^= 1; }
            }
        }
        return;
    }
    if (warp == 10) return;
    if (tid < 16) {
        unsigned e = *reinterpret_cast<volatile unsigned*>(&g_epoch);
        if (tid == 0) s_misc[0] = e;
        flag_wait(flag_ptr(FL_LN + tid), (e + 1) * 32u);
    }
    bar_sync(1, 320);
    PROF_GT(50);
    const unsigned ep = s_misc[0];
    auto top8 = [&](uint32_t (&key)[8]) {
        uint32_t mine = 0;
#pragma unroll 1
        for (int r = 0; r < TOPC; r++) {
            uint32_t best = 0;
#pragma unroll
            for (int i = 0; i < 8; i++) best = max(best, key[i]);
            best = __reduce_max_sync(0xffffffffu, best);
#pragma unroll
            for (int i = 0; i < 8; i++) if (key[i] == best) key[i] = 0;
            if (lane == r) mine = best;
        }
        return mine;
    };
#pragma unroll 1
    for (int pass = 0; pass < 2; pass++) {
        if (warp < (pass ? 1 : 8)) {
            uint32_t key[8];
#pragma unroll
            for (int i = 0; i < 8; i++) {
                if (pass == 0) {
                    int idx = warp * 256 + i * 32 + lane;
                    uint32_t b = __float_as_uint(__ldcg(g_router + idx)) >> 16;
                    b = (b & 0x8000u) ? (~b & 0xffffu) : (b | 0x8000u);
                    key[i] = (b << 16) | (uint32_t)(0xffff - idx);
                } else key[i] = i < 2 ? s_key[i * 32 + lane] : 0u;
            }
            uint32_t best = top8(key);
            if (lane < TOPC) {
                if (pass == 0) s_key[warp * 8 + lane] = best;
                else {
                    uint32_t b = best >> 16;
                    b = (b & 0x8000u) ? (b & 0x7fffu) : (~b & 0xffffu);
                    s_sel[lane] = 0xffff - (int)(best & 0xffffu);
                    s_r[lane] = __uint_as_float(b << 16);
                }
            }
        }
        bar_sync(1, 320);
    }
#pragma unroll
    for (int it = 0; it < 2; it++) {
        int i = tid + it * 320, tk = i / 80, ch = i % 80;
        *reinterpret_cast<uint4*>(sm + XS + tk * 1296 + ch * 16) = __ldcg(reinterpret_cast<const uint4*>(xn_addr(s_sel[tk], ch * 8)));
    }
    bar_sync(1, 320);
    PROF_GT(51);
    const int g = lane >> 2, t = lane & 3;
    const uint32_t woff = warp * 4096 + (8 * (lane >> 4) + (lane & 7)) * 128 + ((((lane >> 3) & 1) ^ (lane & 7)) << 4);
    int st = 0; uint32_t ph = 0;
    float ga[4][4], ua[4][4];
#pragma unroll
    for (int i = 0; i < 4; i++)
#pragma unroll
        for (int e = 0; e < 4; e++) { ga[i][e] = 0.f; ua[i][e] = 0.f; }
#pragma unroll 1
    for (int s = 0; s < 34; s++) {
        if (s == 20) {
            if (warp < 7) {
#pragma unroll
                for (int i = 0; i < 4; i++)
#pragma unroll
                    for (int e = 0; e < 4; e++) {
                        float gv = bf_round(ga[i][e]), uv = bf_round(ua[i][e]);
                        float sg = bf_round(__fdividef(gv, 1.0f + __expf(fminf(-gv, 80.f))));
                        int f = warp * 64 + i * 16 + g + 8 * (e >> 1), tk = 2 * t + (e & 1);
                        *reinterpret_cast<__nv_bfloat16*>(sm + HS + tk * 912 + f * 2) = __float2bfloat16_rn(sg * uv);
                        ga[i][e] = 0.f;
                    }
            }
            bar_sync(1, 320);
            PROF_GT(52);
        }
        mbar_wait(full + 8 * st, ph);
        if (s >= 20 || warp < 7) {
#pragma unroll
            for (int kk = 0; kk < 2; kk++) {
                uint32_t xb = sb + (s < 20 ? XS + g * 1296 + s * 64 : HS + g * 912 + (s - 20) * 64) + 32 * kk + 4 * t;
                uint32_t b0 = lds32(xb), b1 = lds32(xb + 16);
                uint32_t wa = sb + st * STG + woff + kk * 2048;
#pragma unroll
                for (int i = 0; i < 4; i++) {
                    uint32_t a0, a1, a2, a3;
                    ldsm4t(a0, a1, a2, a3, wa ^ (i << 5));
                    mma16816(ga[i], a0, a1, a2, a3, b0, b1);
                    if (s < 20) {
                        ldsm4t(a0, a1, a2, a3, (wa ^ (i << 5)) + 28672);
                        mma16816(ua[i], a0, a1, a2, a3, b0, b1);
                    }
                }
            }
        }
        asm volatile("fence.proxy.async.shared::cta;" ::: "memory");
        __syncwarp();
        if (lane == 0) mbar_arrive(empty + 8 * st);
        if (++st == 3) { st = 0; ph ^= 1; }
    }
#pragma unroll
    for (int i = 0; i < 4; i++)
#pragma unroll
        for (int e = 0; e < 4; e += 2)
            *reinterpret_cast<float2*>(g_moe_part + (a * DM + warp * 64 + i * 16 + g + 4 * e) * 8 + 2 * t) = make_float2(ga[i][e], ga[i][e + 1]);
    bar_sync(1, 320);
    if (tid == 0) {
        __threadfence();
        unsigned old = atomicAdd(flag_ptr(FL_MOE_CNT), 1u);
        s_misc[1] = (old == ep * 4u + 3u);
        __threadfence();
    }
    bar_sync(1, 320);
    PROF_GT(53);
    if (s_misc[1]) {
        const float4* pp = reinterpret_cast<const float4*>(g_moe_part);
#pragma unroll 2
        for (int i = tid; i < DM * 2; i += 320) {
            float4 v0 = __ldcg(pp + i), v1 = __ldcg(pp + DM * 2 + i), v2 = __ldcg(pp + DM * 4 + i), v3 = __ldcg(pp + DM * 6 + i);
            float y[4] = {v0.x + v1.x + v2.x + v3.x, v0.y + v1.y + v2.y + v3.y, v0.z + v1.z + v2.z + v3.z, v0.w + v1.w + v2.w + v3.w};
#pragma unroll
            for (int e = 0; e < 4; e++) {
                int col = i >> 1, tk = (i & 1) * 4 + e;
                float sg = bf_round(__fdividef(1.0f, 1.0f + __expf(fminf(-s_r[tk], 80.f))));
                float upd = bf_round(bf_round(y[e]) * sg);
                float xn = __bfloat162float(*reinterpret_cast<const __nv_bfloat16*>(sm + XS + tk * 1296 + col * 2));
                g_brow[tk * DM + col] = __float2bfloat16_rn(xn + upd);
            }
        }
        if (tid < TOPC) g_sel[tid] = s_sel[tid];
        bar_sync(1, 320);
        if (tid == 0) {
            flag_signal(flag_ptr(FL_MOE_DONE));
            *reinterpret_cast<volatile unsigned*>(&g_epoch) = ep + 1;
        }
        PROF_GT(54);
    }
}

__device__ __forceinline__ void ln_rows(const Params& P, int row0, int lane, uint32_t wr_s) {
    const int hl = lane & 15, row = row0 + (lane >> 4);
    uint32_t v[20];
#pragma unroll
    for (int i = 0; i < 5; i++) {
        uint4 u = __ldg(reinterpret_cast<const uint4*>(P.x + (size_t)row * DM + 128 * i + 8 * hl));
        v[4 * i] = u.x; v[4 * i + 1] = u.y; v[4 * i + 2] = u.z; v[4 * i + 3] = u.w;
    }
    float mean = 0.f, m2 = 0.f;
#pragma unroll
    for (int i = 0; i < 20; i++) { mean += bf_lo(v[i]); mean += bf_hi(v[i]); }
    mean *= (1.0f / 40);
#pragma unroll
    for (int i = 0; i < 20; i++) {
        float d0 = __uint_as_float(__byte_perm(v[i], 0, 0x1044)) - mean, d1 = __uint_as_float(__byte_perm(v[i], 0, 0x3244)) - mean;
        m2 = fmaf(d0, d0, m2); m2 = fmaf(d1, d1, m2);
    }
#pragma unroll
    for (int o = 1; o < 16; o <<= 1) {
        float mo = __shfl_xor_sync(0xffffffffu, mean, o), qo = __shfl_xor_sync(0xffffffffu, m2, o), d = mo - mean;
        m2 = fmaf(d * d, 20.0f * o, m2 + qo);
        mean = 0.5f * (mean + mo);
    }
    const uint32_t mb2 = pack_bf16(mean, mean);
    const float inv = rcp_fast(bf_round(sqrt_fast(bf_round(bf_round(m2 * (1.0f / DM)) + 1e-5f))));
    float dot = 0.f;
    unsigned char* xp = g_xn + ((row >> 7) * 10 + (hl >> 3)) * 16384 + (row & 127) * 128 + (((hl & 7) ^ (row & 7)) << 4);
#pragma unroll
    for (int i = 0; i < 5; i++) {
        uint32_t ww[4];
        asm volatile("ld.shared.v4.b32 {%0,%1,%2,%3}, [%4];" : "=r"(ww[0]), "=r"(ww[1]), "=r"(ww[2]), "=r"(ww[3]) : "r"(wr_s + 256 * i + 16 * hl) : "memory");
#pragma unroll
        for (int e = 0; e < 4; e++) {
            uint32_t d;
            asm("sub.rn.bf16x2 %0, %1, %2;" : "=r"(d) : "r"(v[4 * i + e]), "r"(mb2));
            d = pack_bf16(bf_lo(d) * inv, bf_hi(d) * inv);
            v[4 * i + e] = d;
            dot = fmaf(bf_lo(d), bf_lo(ww[e]), dot);
            dot = fmaf(bf_hi(d), bf_hi(ww[e]), dot);
        }
        stg128(xp + i * 32768, v[4 * i], v[4 * i + 1], v[4 * i + 2], v[4 * i + 3]);
    }
#pragma unroll
    for (int o = 8; o > 0; o >>= 1) dot += __shfl_xor_sync(0xffffffffu, dot, o);
    if (hl == 0) g_router[row] = bf_round(dot);
}

__global__ void __cluster_dims__(2, 1, 1) __launch_bounds__(384, 1)
fused_kernel(const __grid_constant__ CUtensorMap tmC, const __grid_constant__ CUtensorMap tmWk, const __grid_constant__ CUtensorMap tmWv,
             const __grid_constant__ CUtensorMap tmWq, const __grid_constant__ CUtensorMap tmWo,
             const __grid_constant__ CUtensorMap tmG, const __grid_constant__ CUtensorMap tmU, const __grid_constant__ CUtensorMap tmD, const Params P) {
    extern __shared__ __align__(1024) unsigned char smem_raw[];
    const uint32_t ring = smem_u32(smem_raw);
    const uint32_t misc = ring + RING_BYTES;
    const int tid = threadIdx.x;
    const int mc = blockIdx.x >> 1, rank = blockIdx.x & 1;
    if (mc >= 64) { aux_cta(&tmG, &tmU, &tmD, smem_raw, blockIdx.x - 128); return; }
    PROF_DECL
    PROF_GT(0); PROF_EV(1);
    const int team = mc >> 2, k = mc & 3;
    const int u3 = mc >> 3, s3 = (mc >> 1) & 3, kap = mc & 1;

    if (tid == 0) {
#pragma unroll
        for (int i = 0; i < NSLOT; i++) mbar_init(misc + BAR_FULL + 8 * i, 1);
#pragma unroll
        for (int i = 0; i < E0; i++) mbar_arrive(misc + BAR_FULL + 8 * i);
        asm volatile("fence.mbarrier_init.release.cluster;" ::: "memory");
        const CUtensorMap* tw = rank ? &tmWv : &tmWk;
        mbar_expect_tx(misc + BAR_FULL + 8 * slot_of(0), SLOT_BYTES);
        tma2d(ring + slot_of(0) * SLOT_BYTES, tw, team * 256, 0, misc + BAR_FULL + 8 * slot_of(0));
        tma2d(ring + slot_of(0) * SLOT_BYTES + 16384, tw, team * 256 + 64, 0, misc + BAR_FULL + 8 * slot_of(0));
    }
    if (tid == 32) {
        asm volatile("prefetch.tensormap [%0];" ::"l"(&tmC) : "memory");
#pragma unroll
        for (int i = 0; i < NSLOT; i++) mbar_init(misc + BAR_EMPTY + 8 * i, 16);
#pragma unroll
        for (int i = 0; i < E0; i++) mbar_arrive_cluster(misc + BAR_EMPTY + 8 * i, 16);
        asm volatile("fence.mbarrier_init.release.cluster;" ::: "memory");
    }
    if (tid == 64) {
#pragma unroll
        for (int i = 0; i < NST3; i++) { mbar_init(misc + BAR_FULL3 + 8 * i, 1); mbar_init(misc + BAR_EMPTY3 + 8 * i, 16); }
#pragma unroll
        for (int i = 0; i < 4; i++) mbar_init(misc + BAR_LN + 8 * i, 2);
        mbar_init(misc + BAR_PROG, 1); mbar_init(misc + BAR_PROG + 8, 1);
        asm volatile("fence.mbarrier_init.release.cluster;" ::: "memory");
    }
    if (tid == 96) {
#pragma unroll
        for (int i = 0; i < 34; i++) mbar_init(misc + BAR_DEP + 8 * i, 1);
    }
    if (tid == 128) {
#pragma unroll
        for (int i = 0; i < 32; i++) mbar_init(misc + BAR_EV + 8 * i, 4);
    }
    __syncthreads();
    asm volatile("barrier.cluster.arrive.relaxed.aligned;\nbarrier.cluster.wait.aligned;" ::: "memory");
    PROF_EV(5);
    const int wg = __shfl_sync(0xffffffffu, tid >> 7, 0);

    if (wg == 0) {
        asm volatile("setmaxnreg.dec.sync.aligned.u32 40;");
        const int warp = __shfl_sync(0xffffffffu, tid >> 5, 0), lane = tid & 31;
        if (warp == 0) {
            const bool lead = elect_one();
            Cur c = cur_at(1);
            uint32_t dst, fb;
            auto acquire = [&]() {
                mbar_wait(misc + BAR_EMPTY + 8 * c.slot, c.ph ^ 1);
                fb = misc + BAR_FULL + 8 * c.slot; dst = ring + c.slot * SLOT_BYTES;
                if (lead) mbar_expect_tx(fb, SLOT_BYTES);
                c.adv();
            };
            auto load_w = [&](const CUtensorMap* tm, int col, int row) {
                acquire();
                if (lead) { tma2d(dst, tm, col, row, fb); tma2d(dst + 16384, tm, col + 64, row, fb); }
            };
            auto load_half = [&](const unsigned char* src) {
                acquire();
                if (lead) bulk_load_mc(dst + rank * 16384, src, 16384, fb);
            };
            auto staging = [&]() {
                mbar_wait(misc + BAR_EMPTY + 8 * c.slot, c.ph ^ 1);
                if (lead) mbar_arrive(misc + BAR_FULL + 8 * c.slot);
                c.adv();
            };
            auto dep_wait = [&](int d) { mbar_wait(misc + BAR_DEP + 8 * d, 0); fence_async_global(); };
            constexpr int OP_PF = 4;
            auto op_prefetch = [&](int i) {
                const int head = op_head(i, kap);
                l2_prefetch(reinterpret_cast<const unsigned char*>(P.wo) + head * 163840 + (u3 * 8 + s3 * 2 + rank) * 2560, 2560);
                if (i < 8) l2_prefetch(g_Q + (size_t)(head * 32 + 4 * u3 + 2 * rank) * 16384 + s3 * 8192, 8192);
            };
            const CUtensorMap* tw = rank ? &tmWv : &tmWk;
            const unsigned char* Kh = g_K + (size_t)team * 32 * 16384 + rank * 16384;
            const unsigned char* Vh = g_V + (size_t)team * 32 * 16384 + rank * 16384;
#pragma unroll 1
            for (int v = 0; v < 2; v++) {
                const int h = 2 * team + v;
#pragma unroll 1
                for (int i = 0; i < 16; i++) {
                    if (i < 4 && (v | i)) load_w(tw, h * 128, i * 128);
                    if (v && (i & 7) == 3) dep_wait(D_WAR + (i >> 3));
                    acquire();
                    if (lead) tma2d_mc(dst + rank * 16384, &tmC, (i & 3) * 128 + rank * 64, (12 - (i & 12) + k) * 128, fb);
                    if (v && i == 2 && lead) mbar_arrive(misc + BAR_PROG + 8);
                }
                if (v == 0) {
                    const int cq = (h + rank) * 128;
                    load_w(&tmWq, cq, 0); load_w(&tmWq, cq, 128); load_w(&tmWq, cq, 256);
#pragma unroll 1
                    for (int t = 0; t < 4; t++) {
                        const unsigned char* xt = g_xn + (q_tile(k, t) * 10 + rank) * 16384;
                        dep_wait(D_LN + t);
                        if (t == 3 && lead) l2_prefetch((rank ? Vh - 16384 : Kh) + (13 - 2 * k) * 32768, 3 * 32768);
#pragma unroll 1
                        for (int ch = 0; ch < 5; ch++) {
                            load_half(xt + ch * 32768);
                            if (t == 0 && ch == 0) load_w(&tmWq, cq, 384);
                        }
                        load_w(&tmWq, cq, 512);
                    }
                }
                int togo = v ? 13 : 11;
#pragma unroll 1
                for (int r = 0; r < 2; r++) {
                    const int p = r ? k : 7 - k, n = 2 * p + 1;
                    if (v == 0) dep_wait(D_Q + r);
                    acquire();
                    if (lead) {
                        const int g0 = r ? rank : 3 - rank;
                        bulk_load(dst, g_Q + (size_t)(h * 32 + 4 * p + g0) * 16384, 16384, fb);
                        bulk_load(dst + 16384, g_Q + (size_t)(h * 32 + 4 * p + 3 - g0) * 16384, 16384, fb);
                    }
                    if (v && r == 0) dep_wait(D_KV + 4 + (k >> 1));
                    load_half(Kh + n * 32768);
                    if (r) { load_half(Vh); staging(); }
#pragma unroll 1
                    for (int j = n - 1; j >= 0; j--) {
                        if (v && r == 0 && (j & 3) == 3) dep_wait(D_KV + 7 - (j >> 2));
                        load_half(Kh + j * 32768); load_half(Vh + (j + 1) * 32768);
                        if (v == 0 && r == 0 && j == 3 && lead) mbar_arrive(misc + BAR_PROG);
                        if (--togo == 0 && lead) {
                            if (v == 0) {
                                tma2d_prefetch(tw, h * 128 + 128, k * 128); tma2d_prefetch(tw, h * 128 + 192, k * 128);
                                l2_prefetch(reinterpret_cast<const unsigned char*>(P.c) + (size_t)blockIdx.x * 16384, 16384);
                            } else {
#pragma unroll
                                for (int i = 0; i < OP_PF; i++) op_prefetch(i);
                            }
                        }
                    }
                }
                load_half(Vh);
                staging();
                if (v == 0 && lead) l2_prefetch(g_Q + (size_t)((h + 1) * 32 + 8 * k + 4 * rank) * 16384, 65536);
            }
            mbar_wait(misc + BAR_EMPTY + 8 * c.slot, c.ph ^ 1); c.adv();
            int st = 0; uint32_t ph3 = 0;
#pragma unroll 1
            for (int i = 0; i < 32; i++) {
                const int head = op_head(i >> 1, kap);
                if ((i & 1) == 0) dep_wait(D_CTX + (i >> 1));
                if (i < NST3) { mbar_wait(misc + BAR_EMPTY + 8 * c.slot, c.ph ^ 1); c.adv(); }
                else mbar_wait(misc + BAR_EMPTY3 + 8 * st, ph3 ^ 1);
                fb = misc + BAR_FULL3 + 8 * st; dst = ring + st * ST3_BYTES;
                if (lead) {
                    mbar_expect_tx(fb, ST3_BYTES);
                    const unsigned char* src = g_Q + (size_t)(head * 32 + 4 * u3 + 2 * rank) * 16384 + (i & 1) * 8192;
                    bulk_load(dst, src, 8192, fb);
                    bulk_load(dst + 8192, src + 16384, 8192, fb);
                    tma3d_mc(dst + 16384 + rank * 10240, &tmWo, 0, head * 128 + (i & 1) * 64 + rank * 32, 5 * s3, fb);
                    if ((i & 1) && (i >> 1) + OP_PF < 16) op_prefetch((i >> 1) + OP_PF);
                }
                if (++st == NST3) { st = 0; ph3 ^= 1; }
            }
        } else if (warp == 3) {
            const unsigned ep1 = *reinterpret_cast<volatile unsigned*>(&g_epoch) + 1;
            if (lane == 0) {
                asm volatile("st.shared.u32 [%0], %1;" ::"r"(misc + MISC_EPOCH), "r"(ep1) : "memory");
                l2_prefetch(reinterpret_cast<const unsigned char*>(P.c) + (size_t)blockIdx.x * 12288, 12288);
#pragma unroll 1
                for (int t = 0; t < 4; t++) {
                    if (t == 1) {
                        mbar_wait(misc + BAR_PF, 0);
                        l2_prefetch(reinterpret_cast<const unsigned char*>(P.wq) + (size_t)blockIdx.x * 40960, 40960);
                    }
                    mbar_wait(misc + BAR_LN + 8 * t, 0);
                    flag_signal(flag_ptr(FL_LN + q_tile(blockIdx.x >> 5, t)));
                    flag_wait(flag_ptr(FL_LN + q_tile(k, t)), ep1 * 32u);
                    mbar_arrive(misc + BAR_DEP + 8 * (D_LN + t));
                }
                mbar_wait(misc + BAR_EV + 8 * (16 + EV_KV + 3), 0);
                flag_wait(flag_ptr(FL_KV + team * 8), ep1 * 16u);
#pragma unroll 1
                for (int i = 0; i < 2; i++) {
                    mbar_wait(misc + BAR_EV + 8 * (16 + EV_Q + 1 + 2 * i), 0);
                    flag_wait(flag_ptr(FL_Q + team * 8 + (i ? k : 7 - k)), ep1 * 4u);
                    mbar_arrive(misc + BAR_DEP + 8 * (D_Q + i));
                }
#pragma unroll 1
                for (int i = 0; i < 2; i++) {
                    mbar_wait(misc + BAR_PROG + 8 * i, 0);
                    flag_signal(flag_ptr(FL_WAR + 2 * team + i));
                    flag_wait(flag_ptr(FL_WAR + 2 * team + i), ep1 * 8u);
                    mbar_arrive(misc + BAR_DEP + 8 * (D_WAR + i));
                }
#pragma unroll 1
                for (int i = 4; i < 8; i++) {
                    mbar_wait(misc + BAR_EV + 8 * (16 + EV_KV + i), 0);
                    flag_wait(flag_ptr(FL_KV + team * 8 + i), ep1 * 16u);
                    mbar_arrive(misc + BAR_DEP + 8 * (D_KV + i));
                }
                flag_wait(flag_ptr(FL_MOE_DONE), ep1);
                int4 s0 = __ldcg(reinterpret_cast<const int4*>(g_sel)), s1 = __ldcg(reinterpret_cast<const int4*>(g_sel) + 1);
                asm volatile("st.shared.v4.u32 [%0], {%1,%2,%3,%4};" ::"r"(misc + MISC_SEL), "r"(s0.x), "r"(s0.y), "r"(s0.z), "r"(s0.w) : "memory");
                asm volatile("st.shared.v4.u32 [%0], {%1,%2,%3,%4};" ::"r"(misc + MISC_SEL + 16), "r"(s1.x), "r"(s1.y), "r"(s1.z), "r"(s1.w) : "memory");
                mbar_arrive(misc + BAR_SEL);
            }
            __syncwarp();
            const unsigned* cf = flag_ptr(FL_CTX + op_head(lane & 15, kap) * 8 + u3);
#pragma unroll 1
            for (int half = 0; half < 2; half++) {
                if (half) mbar_wait(misc + BAR_EV + 8 * (EV_CTX + 3), 0);
                bool done = (lane >> 3) != half;
                for (int spin = 0; spin < 4000000; spin++) {
                    if (!done) {
                        unsigned v;
                        asm volatile("ld.acquire.gpu.global.u32 %0, [%1];" : "=r"(v) : "l"(cf) : "memory");
                        if ((int)(v - ep1 * 4u) >= 0) { mbar_arrive(misc + BAR_DEP + 8 * (D_CTX + lane)); done = true; }
                    }
                    if (__all_sync(0xffffffffu, done)) break;
                    __nanosleep(64);
                }
            }
        } else {
            const int w = warp - 1;
            if (lane < 20) {
#pragma unroll
                for (int i = 0; i < 2; i++) {
                    const int ch = w * 40 + i * 20 + lane;
                    uint4 u = __ldg(reinterpret_cast<const uint4*>(P.wr) + ch);
                    asm volatile("st.shared.v4.b32 [%0], {%1,%2,%3,%4};" ::"r"(misc + MISC_WR + 16 * ch), "r"(u.x), "r"(u.y), "r"(u.z), "r"(u.w) : "memory");
                }
            }
            const int rsub = (blockIdx.x & 31) * 4 + 2 * w;
            if (lane < 3) l2_prefetch(P.x + (size_t)(q_tile(blockIdx.x >> 5, lane + 1) * 128 + rsub) * DM, 2 * DM * 2);
            bar_sync(3, 64);
#pragma unroll 1
            for (int t = 0; t < 4; t++) {
                ln_rows(P, q_tile(blockIdx.x >> 5, t) * 128 + rsub, lane, misc + MISC_WR);
                __syncwarp();
                if (lane == 0) mbar_arrive(misc + BAR_LN + 8 * t);
            }
            if (lane == 0) {
                const uint32_t eb = misc + BAR_EV + w * 128;
#pragma unroll 1
                for (int v = 0; v < 2; v++) {
#pragma unroll 1
                    for (int i = 0; i < (v ? 4 : 3); i++) {
                        mbar_wait(eb + 8 * (v ? EV_KV + 4 + i : i ? EV_Q + 2 * i - 1 : EV_KV + 3), 0);
                        flag_signal(flag_ptr(v ? FL_KV + team * 8 + 4 + i : i ? FL_Q + team * 8 + (i == 1 ? 7 - k : k) : FL_KV + team * 8));
                    }
#pragma unroll 1
                    for (int r = 0; r < 2; r++) {
                        const int p = r ? k : 7 - k;
                        const uint32_t slot = ((v ? E_ATT1 : E_ATT0) + (r ? 39 : 4 * p + 7) + E0) % NSLOT;
                        const int grp = (r == w) ? 3 - rank : rank;
                        mbar_wait(eb + 8 * (EV_CTX + 2 * v + r), 0);
                        asm volatile("cp.async.bulk.global.shared::cta.bulk_group [%0], [%1], 16384;"
                                     ::"l"(g_Q + (size_t)((2 * team + v) * 32 + 4 * p + grp) * 16384), "r"(ring + slot * SLOT_BYTES + w * 16384) : "memory");
                        asm volatile("cp.async.bulk.commit_group;" ::: "memory");
                        asm volatile("cp.async.bulk.wait_group.read 0;" ::: "memory");
                        mbar_arrive_cluster(mapa(misc + BAR_EMPTY + 8 * slot, 0), 4);
                        mbar_arrive_cluster(mapa(misc + BAR_EMPTY + 8 * slot, 1), 4);
                        asm volatile("cp.async.bulk.wait_group 0;" ::: "memory");
                        fence_async_global();
                        flag_signal(flag_ptr(FL_CTX + (2 * team + v) * 8 + p));
                    }
                }
            }
        }
    } else {
        asm volatile("setmaxnreg.inc.sync.aligned.u32 232;");
        Ctx c;
        c.ring = ring; c.misc = misc; c.w = wg - 1; c.warp = (tid >> 5) & 3; c.lane = tid & 31;
        c.rel = mapa(misc, tid & 1);
        const int w = c.w;
        const int my_bar = 1 + w, other_bar = 2 - w;
        if (w == 1) bar_arrive(1, 256);
        Cur cur = cur_at(0);
        float o[64], inv[2];
#pragma unroll 1
        for (int v = 0; v < 2; v++) {
        {
            uint32_t wf[128];
            float acc[64];
#pragma unroll
            for (int i = 32; i < 128; i++) wf[i] = 0u;
            Cur cw = cur;
            int wstep = 2;
            auto load_wchunk = [&](auto CH) {
                constexpr int ch = decltype(CH)::value;
                mbar_wait_hot(misc + BAR_FULL + 8 * cw.slot, cw.ph);
                const uint32_t z = load_afrag<8, 32 * ch>(wf, ring + cw.slot * SLOT_BYTES + w * 16384, c);
                release(c, BAR_EMPTY + 8 * cw.slot + z, 1);
                cw.adv();
                if (wstep == 2 || ch == 2) cw.adv();
            };
            load_wchunk(IC<0>{});
            cur.adv();
            int nload = 1;
            PROF_EV(2); PROF_GT(60);
#pragma unroll 1
            for (int t = 0; t < (v ? 4 : 8); t++) {
                uint32_t last = 0;
                bar_sync(my_bar, 256);
                PROF_EV(t < 4 ? 10 : 20);
                undef_regs(acc);
                auto chunk = [&](auto CH) {
                    constexpr int ch = decltype(CH)::value;
                    mbar_wait_hot(misc + BAR_FULL + 8 * cur.slot, cur.ph);
                    uint64_t d = mkdesc(ring + cur.slot * SLOT_BYTES, 16, 1024, 1);
                    wg_fence();
#pragma unroll
                    for (int ks = 0; ks < 8; ks++)
                        wgmma_rs_n128_ta0_tb0(acc, wf[32 * ch + 4 * ks], wf[32 * ch + 4 * ks + 1], wf[32 * ch + 4 * ks + 2], wf[32 * ch + 4 * ks + 3],
                                              d + (ks >> 2) * 1024 + (ks & 3) * 2, (ch | ks) != 0);
                    wg_commit();
                    const bool swap = (ch < 2 && t == 0) || (ch == 3 && t < 4);
                    if (swap) bar_arrive(other_bar, 256);
                    if constexpr (ch < 3) { if (nload == ch + 1) { load_wchunk(IC<ch + 1>{}); nload++; } }
                    if (ch > 0) { wg_wait<1>(); release(c, BAR_EMPTY + 8 * last, 1); }
                    last = cur.slot;
                    cur.adv();
                    if ((ch < 3 && t == 0) || (ch == 0 && t == 4)) cur.adv();
                    if (ch < 2 && swap) bar_sync(my_bar, 256);
                };
                chunk(IC<0>{}); chunk(IC<1>{}); chunk(IC<2>{}); chunk(IC<3>{});
                if (t < 4) {
                    wg_wait<0>();
                    release(c, BAR_EMPTY + 8 * last, 1);
                } else {
                    Cur cx = cur; cur.adv();
                    mbar_wait_hot(misc + BAR_FULL + 8 * cx.slot, cx.ph);
                    mbar_wait_hot(misc + BAR_FULL + 8 * cur.slot, cur.ph);
                    uint64_t db = mkdesc(ring + cx.slot * SLOT_BYTES, 16, 1024, 1);
                    uint64_t da = mkdesc(ring + cur.slot * SLOT_BYTES + w * 16384, 16384, 1024, 1);
                    wg_fence();
#pragma unroll
                    for (int ks = 0; ks < 8; ks++) wgmma_ss_n128_ta1_tb0(acc, da + 128 * ks, db + (ks >> 2) * 1024 + (ks & 3) * 2, 1);
                    wg_commit();
                    bar_arrive(other_bar, 256);
                    wg_wait<1>(); release(c, BAR_EMPTY + 8 * last, 1);
                    wg_wait<0>(); release(c, BAR_EMPTY + 8 * cx.slot, 1); release(c, BAR_EMPTY + 8 * cur.slot, 1);
                    cur.adv();
                    fence_regs(acc);
#pragma unroll
                    for (int i = 0; i < 64; i++) acc[i] *= SM_SCALE;
                }
                PROF_EV(t < 4 ? 11 : 21);
                fence_regs(acc);
                if (t == 0 && v == 0 && tid == 128) mbar_arrive(misc + BAR_PF);
                const bool wswitch = t == 3 && v == 0;
                if (wswitch) {
                    cw = cur; wstep = 1; nload = 0;
                    cur.adv(); cur.adv(); cur.adv();
                    if (w) { load_wchunk(IC<0>{}); load_wchunk(IC<1>{}); load_wchunk(IC<2>{}); nload = 3; }
                }
                unsigned char* dst = t < 4 ? (rank ? g_V : g_K) + (size_t)(team * 32 + 24 + 2 * k - 8 * t) * 16384
                                           : g_Q + (size_t)((2 * team + rank) * 32 + q_tile(k, t & 3) * 2) * 16384;
                store_proj(acc, dst, c, policy_normal());
                signal_event(c, t < 4 ? EV_KV + 4 * v + t : EV_Q + t - 4);
                if (wswitch) {
                    if (w) { load_wchunk(IC<3>{}); nload = 4; }
                    else { load_wchunk(IC<0>{}); load_wchunk(IC<1>{}); nload = 2; }
                }
                if (t == 3) { PROF_EV(61); PROF_GT(62); }
            }
        }
        PROF_EV(63); PROF_GT(64);
        {
            uint32_t q[32], p[32];
            float m[2], l[2];
#pragma unroll
            for (int i = 0; i < 64; i++) o[i] = 0.f;
#pragma unroll
            for (int i = 0; i < 32; i++) p[i] = 0u;
            m[0] = m[1] = inv[0] = inv[1] = 0.f;
            l[0] = l[1] = 1.f;
            int gen = 0;
            Cur ck = cur, cv = cur, cq, ce, cen;
            int r = 0, left;
            int first = 1, half, heavy;
            int pv_acc = 0, pv_half = 1; uint32_t pv_cnt = 0;
            int pending = 0;
            Cur nck, ncv;
            auto next_task = [&](int rr) {
                heavy = 1 ^ (rr & 1) ^ w;
                half = 1 ^ heavy ^ rank;
                left = 2 * (rr ? k : 7 - k) + 1 + heavy;
                cq = cur; cur.adv();
                nck = cur; cur.adv();
                if (rr > 0) { ncv = cur; cur.adv(); cen = cur; cur.adv(); }
                if (!heavy) { nck = cur; cur.adv(); cur.adv(); }
                if (rr == 0) { ncv = nck; cen = nck; }
            };
            next_task(0);
            ce = cen;
            mbar_wait(misc + BAR_FULL + 8 * cq.slot, cq.ph);
            load_afrag<8, 0>(q, ring + cq.slot * SLOT_BYTES + w * 16384, c);
            uint32_t k_cnt = 1; int last = 0, was_first = 0, publish = 0;
            auto window = [&]() {
                publish = pending;
                if (pending) stage_ctx(o, inv, ce, c);
                pending = 0;
                k_cnt = 1;
                was_first = first;
                if (first) {
                    release(c, BAR_EMPTY + 8 * cq.slot, 1);
                    pending = r ? EV_CTX + 2 * v : 0; ce = cen;
                    k_cnt = 1 + heavy;
                }
                last = --left == 0 ? 1 : 0;
                first = last;
                if (!last) { nck = cur; cur.adv(); ncv = cur; cur.adv(); half = 0; }
                else if (++r < 2) next_task(r);
                mbar_wait_hot(misc + BAR_FULL + 8 * cv.slot, cv.ph);
            };
            auto next_q = [&]() {
                if (last && r < 2) {
                    mbar_wait_hot(misc + BAR_FULL + 8 * cq.slot, cq.ph);
                    load_afrag<8, 0>(q, ring + cq.slot * SLOT_BYTES + w * 16384, c);
                }
            };
#pragma unroll 1
            while (r < 2) {
                ck = nck; cv = ncv;
                mbar_wait_hot(misc + BAR_FULL + 8 * ck.slot, ck.ph);
                if (half) {
                    bar_sync(my_bar, 256);
                    PROF_EV(30);
                    float s[32];
                    undef_regs(s);
                    issue_qk_half(s, q, ring + ck.slot * SLOT_BYTES);
                    window();
                    issue_pv(o, p, ring + cv.slot * SLOT_BYTES, pv_acc, pv_half);
                    bar_arrive(other_bar, 256);
                    if (publish) publish_ctx(publish, c);
                    wg_wait<1>();
                    PROF_EV(34);
                    fence_regs(s);
                    row_inv(l, inv);
                    mask_diag<0>(s, c);
                    gen = softmax_first<8>(s, m, l);
                    next_q();
                    wg_wait<0>();
                    fence_regs(o);
                    fence_regs(s);
                    release(c, BAR_EMPTY + 8 * ck.slot, k_cnt);
                    if (pv_cnt) release(c, BAR_EMPTY + 8 * cv.slot, pv_cnt);
#pragma unroll
                    for (int i = 0; i < 16; i++) p[i] = pack_bf16(s[2 * i], s[2 * i + 1]);
                    pv_acc = 0; pv_half = 1; pv_cnt = k_cnt;
                    continue;
                }
                float s[64];
                int redo;
#pragma unroll 1
                while (true) {
                    bar_sync(my_bar, 256);
                    PROF_EV(first ? 30 : 31);
                    undef_regs(s);
                    issue_qk(s, q, ring + ck.slot * SLOT_BYTES);
                    const bool special = first > 0 || pv_acc == 0 || left == 1;
                    if (special) window();
                    else {
                        nck = cur; cur.adv(); ncv = cur; cur.adv();
                        --left;
                        mbar_wait_hot(misc + BAR_FULL + 8 * cv.slot, cv.ph);
                    }
                    issue_pv(o, p, ring + cv.slot * SLOT_BYTES, pv_acc, special && pv_half);
                    bar_arrive(other_bar, 256);
                    wg_wait<1>();
                    PROF_EV(33);
                    fence_regs(s);
                    float lo = 0.f;
                    if (special) {
                        if (publish) publish_ctx(publish, c);
                        if (was_first) {
                            row_inv(l, inv);
                            l[0] = l[1] = m[0] = m[1] = 0.f;
                            gen = 0;
                            lo = 1.0f / SAFE_SUM;
                            mask_diag<8>(s, c);
                        }
                    }
                    constexpr int JB = 11;
                    float l0 = l[0], l1 = l[1];
                    if (!gen) {
#pragma unroll
                        for (int j = 0; j < JB; j++) {
#pragma unroll
                            for (int e = 0; e < 4; e++) ex2v(s[4 * j + e]);
                            if (j < JB - 1) { l0 += s[4 * j] + s[4 * j + 1]; l1 += s[4 * j + 2] + s[4 * j + 3]; }
                        }
                    }
                    wg_wait<0>();
                    fence_regs(o);
                    redo = 0;
                    if (gen) break;
#pragma unroll
                    for (int j = JB - 1; j < 16; j++) {
                        if (j >= JB) {
#pragma unroll
                            for (int e = 0; e < 4; e++) ex2v(s[4 * j + e]);
                        }
                        l0 += s[4 * j] + s[4 * j + 1]; l1 += s[4 * j + 2] + s[4 * j + 3];
                    }
#pragma unroll
                    for (int i = 0; i < 32; i++) p[i] = pack_bf16(s[2 * i], s[2 * i + 1]);
                    redo = 1;
                    if (__any_sync(0xffffffffu, !(l0 <= SAFE_SUM && l1 <= SAFE_SUM && l0 >= lo && l1 >= lo))) break;
                    l[0] = l0; l[1] = l1;
                    redo = 0;
                    if (last) break;
                    release(c, BAR_EMPTY + 8 * ck.slot, k_cnt);
                    if (pv_cnt) release(c, BAR_EMPTY + 8 * cv.slot, pv_cnt);
                    pv_acc = was_first ^ 1; pv_half = 0; pv_cnt = k_cnt;
                    ck = nck; cv = ncv;
                    mbar_wait_hot(misc + BAR_FULL + 8 * ck.slot, ck.ph);
                }
                if (gen | redo) {
                    if (redo) {
                        recompute_scores(s, q, ring + ck.slot * SLOT_BYTES, c);
                        if (was_first) { mask_diag<8>(s, c); m[0] = m[1] = -INFINITY; }
                    }
                    gen = 1;
                    float mx[2], alpha[2];
                    row_max<16>(s, mx);
#pragma unroll
                    for (int i = 0; i < 2; i++) {
                        mx[i] = fmaxf(mx[i], m[i]);
                        alpha[i] = was_first ? 1.0f : ex2(m[i] - mx[i]);
                        m[i] = mx[i];
                        l[i] *= alpha[i];
                    }
                    exp_sum<16, true>(s, m, l[0], l[1]);
#pragma unroll
                    for (int i = 0; i < 64; i++) o[i] *= alpha[(i >> 1) & 1];
#pragma unroll
                    for (int i = 0; i < 32; i++) p[i] = pack_bf16(s[2 * i], s[2 * i + 1]);
                }
                next_q();
                release(c, BAR_EMPTY + 8 * ck.slot, k_cnt);
                if (pv_cnt) release(c, BAR_EMPTY + 8 * cv.slot, pv_cnt);
                pv_acc = was_first ^ 1; pv_half = 0; pv_cnt = k_cnt;
            }
            if (pending) { stage_ctx(o, inv, ce, c); publish_ctx(pending, c); }
            mbar_wait(misc + BAR_FULL + 8 * cur.slot, cur.ph);
            bar_sync(my_bar, 256);
            PROF_EV(32);
            issue_pv(o, p, ring + cur.slot * SLOT_BYTES, pv_acc, pv_half);
            if (w == 0 || v == 0) bar_arrive(other_bar, 256);
            row_inv(l, inv);
            wg_wait<0>();
            release(c, BAR_EMPTY + 8 * cur.slot, pv_cnt);
            fence_regs(o);
            cur.adv();
            if (v == 0) { stage_ctx(o, inv, cur, c); publish_ctx(EV_CTX + 1, c); cur.adv(); }
        }
        }
        {
            float acc[80];
            undef_regs(acc);
            int st = 0, prev = 0; uint32_t ph3 = 0;
            auto op_stage = [&](int i) {
                mbar_wait(misc + BAR_FULL3 + 8 * st, ph3);
                uint32_t base = ring + st * ST3_BYTES;
                uint64_t da = mkdesc(base + w * 8192, 16, 1024, 1);
                uint64_t db = mkdesc(base + 16384, 2048, 512, 2);
                wg_fence();
#pragma unroll
                for (int k = 0; k < 4; k++) wgmma_ss_n160_ta0_tb1(acc, da + 2 * k, db + (k >> 1) * 640 + (k & 1) * 64, k ? 1 : i);
                wg_commit();
                if (i > 0) { wg_wait<1>(); if (i <= 32 - NST3) release(c, BAR_EMPTY3 + 8 * prev, 1); }
                prev = st;
                if (++st == NST3) { st = 0; ph3 ^= 1; }
            };
            PROF_EV(40); PROF_GT(65);
            op_stage(0);
            stage_ctx(o, inv, cur, c);
            publish_ctx(EV_CTX + 3, c);
#pragma unroll 1
            for (int i = 1; i < 22; i++) op_stage(i);
            mbar_wait(misc + BAR_SEL, 0);
            const uint32_t tag = lds32(misc + MISC_EPOCH) & 1;
            const int g = c.lane >> 2, t = c.lane & 3;
            const int row = (2 * u3 + rank) * 128 + 64 * w + perm32(16 * c.warp + 8 * kap + (((g & 3) << 1) | (g >> 2)));
            const int col = 160 * s3 + 8 * t;
            int sel = -1;
#pragma unroll
            for (int i = 0; i < TOPC; i++) if ((int)lds32(misc + MISC_SEL + 4 * i) == row) sel = i;
            uint4 xv[5], bv[5];
#pragma unroll
            for (int i = 0; i < 5; i++) {
                xv[i] = ldg128(P.x + (size_t)row * DM + col + 32 * i);
                bv[i] = ldg128(sel >= 0 ? (const void*)(g_brow + sel * DM + col + 32 * i) : (const void*)xn_addr(row, col + 32 * i));
            }
#pragma unroll 1
            for (int i = 22; i < 32; i++) op_stage(i);
            wg_wait<0>();
            fence_regs(acc);
            PROF_EV(41); PROF_GT(66);
            const int t256 = tid - 128;
            uint4* sendp = g_part + (size_t)blockIdx.x * 2560 + t256;
            float keep[40];
#pragma unroll
            for (int j = 0; j < 10; j++) {
                uint32_t v0 = __float_as_uint(kap ? acc[8 * j + 0] : acc[8 * j + 2]), v1 = __float_as_uint(kap ? acc[8 * j + 1] : acc[8 * j + 3]);
                uint32_t v2 = __float_as_uint(kap ? acc[8 * j + 4] : acc[8 * j + 6]), v3 = __float_as_uint(kap ? acc[8 * j + 5] : acc[8 * j + 7]);
                asm volatile("st.relaxed.gpu.global.v4.b32 [%0], {%1,%2,%3,%4};" ::"l"(sendp + j * 256),
                             "r"((v0 & ~1u) | tag), "r"((v1 & ~1u) | tag), "r"((v2 & ~1u) | tag), "r"((v3 & ~1u) | tag) : "memory");
                keep[4 * j + 0] = kap ? acc[8 * j + 2] : acc[8 * j + 0]; keep[4 * j + 1] = kap ? acc[8 * j + 3] : acc[8 * j + 1];
                keep[4 * j + 2] = kap ? acc[8 * j + 6] : acc[8 * j + 4]; keep[4 * j + 3] = kap ? acc[8 * j + 7] : acc[8 * j + 5];
            }
            const uint4* recvp = g_part + (size_t)(blockIdx.x ^ 2) * 2560 + t256;
            uint4 rv[10];
            int spins = 0;
            while (true) {
                uint32_t v;
                asm volatile("ld.relaxed.gpu.global.b32 %0, [%1];" : "=r"(v) : "l"(recvp + 9 * 256) : "memory");
                if (__all_sync(0xffffffffu, (v & 1u) == tag) || ++spins > 2000000) break;
                __nanosleep(20);
            }
            while (true) {
                uint32_t all_and = 1u, all_or = 0u;
#pragma unroll
                for (int j = 0; j < 10; j++) {
                    asm volatile("ld.relaxed.gpu.global.v4.b32 {%0,%1,%2,%3}, [%4];"
                                 : "=r"(rv[j].x), "=r"(rv[j].y), "=r"(rv[j].z), "=r"(rv[j].w) : "l"(recvp + j * 256) : "memory");
                }
#pragma unroll
                for (int j = 0; j < 10; j++) {
                    all_and &= rv[j].x & rv[j].y & rv[j].z & rv[j].w;
                    all_or |= rv[j].x | rv[j].y | rv[j].z | rv[j].w;
                }
                bool ok = ((tag ? all_and : all_or) & 1u) == tag;
                if (__all_sync(0xffffffffu, ok) || ++spins > 2000000) break;
            }
            uint32_t pk[20];
#pragma unroll
            for (int j = 0; j < 10; j++) {
                pk[2 * j] = pack_bf16(keep[4 * j] + __uint_as_float(rv[j].x & ~1u), keep[4 * j + 1] + __uint_as_float(rv[j].y & ~1u));
                pk[2 * j + 1] = pack_bf16(keep[4 * j + 2] + __uint_as_float(rv[j].z & ~1u), keep[4 * j + 3] + __uint_as_float(rv[j].w & ~1u));
            }
#pragma unroll
            for (int i = 0; i < 5; i++) {
                uint32_t a0 = pk[4 * i], a1 = pk[4 * i + 1], a2 = pk[4 * i + 2], a3 = pk[4 * i + 3];
                uint32_t x0 = (t & 1) ? a0 : a1, x1 = (t & 1) ? a2 : a3;
                x0 = __shfl_xor_sync(0xffffffffu, x0, 1); x1 = __shfl_xor_sync(0xffffffffu, x1, 1);
                if (t & 1) { a0 = x0; a2 = x1; } else { a1 = x0; a3 = x1; }
                x0 = (t & 2) ? a0 : a2; x1 = (t & 2) ? a1 : a3;
                x0 = __shfl_xor_sync(0xffffffffu, x0, 2); x1 = __shfl_xor_sync(0xffffffffu, x1, 2);
                if (t & 2) { a0 = x0; a1 = x1; } else { a2 = x0; a3 = x1; }
                uint32_t av[4] = {a0, a1, a2, a3};
                uint32_t xx[4] = {xv[i].x, xv[i].y, xv[i].z, xv[i].w}, bb[4] = {bv[i].x, bv[i].y, bv[i].z, bv[i].w};
                uint32_t ov[4];
#pragma unroll
                for (int e = 0; e < 4; e++) {
                    uint32_t t1 = pack_bf16(bf_lo(xx[e]) + bf_lo(av[e]), bf_hi(xx[e]) + bf_hi(av[e]));
                    ov[e] = pack_bf16(bf_lo(t1) + bf_lo(bb[e]), bf_hi(t1) + bf_hi(bb[e]));
                }
                stg128(P.out + (size_t)row * DM + col + 32 * i, ov[0], ov[1], ov[2], ov[3]);
            }
            PROF_EV(42); PROF_GT(43);
        }
    }
}

typedef CUresult (*EncodeFn)(CUtensorMap*, CUtensorMapDataType, cuuint32_t, void*, const cuuint64_t*, const cuuint64_t*, const cuuint32_t*,
                             const cuuint32_t*, CUtensorMapInterleave, CUtensorMapSwizzle, CUtensorMapL2promotion, CUtensorMapFloatOOBfill);

void make_map2d(EncodeFn enc, CUtensorMap* tm, const void* p, uint64_t cols, uint64_t rows) {
    cuuint64_t gd[2] = {cols, rows}, gs[1] = {cols * 2};
    cuuint32_t box[2] = {64, 128}, es[2] = {1, 1};
    enc(tm, CU_TENSOR_MAP_DATA_TYPE_BFLOAT16, 2, const_cast<void*>(p), gd, gs, box, es, CU_TENSOR_MAP_INTERLEAVE_NONE,
        CU_TENSOR_MAP_SWIZZLE_128B, CU_TENSOR_MAP_L2_PROMOTION_L2_128B, CU_TENSOR_MAP_FLOAT_OOB_FILL_NONE);
}

void make_map3d(EncodeFn enc, CUtensorMap* tm, const void* p, uint64_t cols, uint64_t rows, uint32_t bw, uint32_t nb) {
    cuuint64_t gd[3] = {bw, rows, cols / bw}, gs[2] = {cols * 2, bw * 2};
    cuuint32_t box[3] = {bw, 32, nb}, es[3] = {1, 1, 1};
    enc(tm, CU_TENSOR_MAP_DATA_TYPE_BFLOAT16, 3, const_cast<void*>(p), gd, gs, box, es, CU_TENSOR_MAP_INTERLEAVE_NONE,
        bw == 64 ? CU_TENSOR_MAP_SWIZZLE_128B : CU_TENSOR_MAP_SWIZZLE_64B, CU_TENSOR_MAP_L2_PROMOTION_L2_128B, CU_TENSOR_MAP_FLOAT_OOB_FILL_NONE);
}

}

extern "C" void kernel_launch(void* const* d_in, const int* in_sizes, int n_in, void* d_out, int out_size) {
    (void)in_sizes; (void)n_in; (void)out_size;
    static EncodeFn enc = nullptr;
    if (!enc) {
        void* fn = nullptr;
        cudaDriverEntryPointQueryResult qr;
        cudaGetDriverEntryPoint("cuTensorMapEncodeTiled", &fn, cudaEnableDefault, &qr);
        enc = (EncodeFn)fn;
        cudaFuncSetAttribute(fused_kernel, cudaFuncAttributeMaxDynamicSharedMemorySize, SMEM_BYTES);
    }
    CUtensorMap tmC, tmWk, tmWv, tmWq, tmWo, tmG, tmU, tmD;
    make_map2d(enc, &tmC, d_in[1], DC, SEQ);
    make_map2d(enc, &tmWq, d_in[2], 4096, DM);
    make_map2d(enc, &tmWk, d_in[3], 4096, DC);
    make_map2d(enc, &tmWv, d_in[4], 4096, DC);
    make_map3d(enc, &tmWo, d_in[5], DM, 4096, 32, 5);
    make_map3d(enc, &tmG, d_in[8], FF, DM, 64, 7);
    make_map3d(enc, &tmU, d_in[9], FF, DM, 64, 7);
    make_map3d(enc, &tmD, d_in[10], DM, FF, 64, 10);
    Params P;
    P.x = (const __nv_bfloat16*)d_in[0];
    P.c = (const __nv_bfloat16*)d_in[1];
    P.wq = (const __nv_bfloat16*)d_in[2];
    P.wo = (const __nv_bfloat16*)d_in[5];
    P.wr = (const __nv_bfloat16*)d_in[7];
    P.out = (__nv_bfloat16*)d_out;
    fused_kernel<<<132, 384, SMEM_BYTES>>>(tmC, tmWk, tmWv, tmWq, tmWo, tmG, tmU, tmD, P);
}
```

```cpp
#include <cuda_runtime.h>
#include <cuda_bf16.h>
#include <cuda.h>
#include <stdint.h>

#define HM 960
#define POLL1 1
#define OP_PF 8
#define PF_START 9
#define LATE_AT 18
#define MAP 2
namespace {

constexpr int SEQ = 2048, NH = 32, DM = 640, DC = 512, FF = 1728, TOPC = 8;
constexpr int NSLOT = 7, SLOT_BYTES = 32768;
constexpr int NST3 = 6, ST3_BYTES = 36864;
constexpr int RING_BYTES = NSLOT * SLOT_BYTES;
constexpr int SMEM_BYTES = RING_BYTES + 3072;

constexpr int BAR_FULL = 96  , BAR_FULL3 = 152  , BAR_DEP = 200  , BAR_PF = 456, BAR_SEL = 464,
              BAR_LN = 472  , BAR_EV = 504  , BAR_EMPTY = 760  , BAR_EMPTY3 = 816  ,
              BAR_PROG = 864  , MISC_EPOCH = 896, MISC_SEL = 912, MISC_WR = 1024  ;
constexpr int D_LN = 0  , D_KV = 4  , D_Q = 12  , D_WAR = 14  , D_CTX = 16  ;
constexpr int EV_KV = 0  , EV_Q = 8  , EV_CTX = 12  ;

constexpr int FL_MOE_CNT = 0, FL_MOE_DONE = 1, FL_LN = 16  , FL_KV = 32  , FL_Q = 160  , FL_CTX = 416  , FL_WAR = 672  , FL_TOTAL = 704;

__device__ __align__(1024) unsigned char g_K[16 * 32 * 16384];
__device__ __align__(1024) unsigned char g_V[16 * 32 * 16384];
__device__ __align__(1024) unsigned char g_Q[NH * 32 * 16384];
__device__ __align__(1024) unsigned char g_xn[16 * 10 * 16384];
__device__ __align__(1024) uint4 g_part[128 * 10 * 256];
__device__ float g_router[SEQ];
__device__ uint2 g_stats[SEQ];
__device__ __align__(16) float g_moe_part[4 * TOPC * DM];
__device__ __align__(16) __nv_bfloat16 g_brow[TOPC * DM];
__device__ __align__(16) int g_sel[TOPC];
__device__ unsigned g_flags[FL_TOTAL * 8];
__device__ unsigned g_epoch;

struct Params {
    const __nv_bfloat16 *x, *c, *wr, *wq, *wk, *wv, *wo;
    __nv_bfloat16* out;
};

__device__ __forceinline__ uint32_t smem_u32(const void* p) { return (uint32_t)__cvta_generic_to_shared(p); }
__device__ __forceinline__ void mbar_init(uint32_t bar, int cnt) { asm volatile("mbarrier.init.shared::cta.b64 [%0], %1;" ::"r"(bar), "r"(cnt)); }
__device__ __forceinline__ void mbar_expect_tx(uint32_t bar, uint32_t bytes) {
    asm volatile("mbarrier.arrive.expect_tx.shared::cta.b64 _, [%0], %1;" ::"r"(bar), "r"(bytes) : "memory");
}
__device__ __forceinline__ void mbar_arrive(uint32_t bar) { asm volatile("mbarrier.arrive.shared::cta.b64 _, [%0];" ::"r"(bar) : "memory"); }
__device__ __forceinline__ void mbar_arrive_cluster(uint32_t cluster_addr, uint32_t cnt) {
    asm volatile("mbarrier.arrive.shared::cluster.b64 _, [%0], %1;" ::"r"(cluster_addr), "r"(cnt) : "memory");
}
__device__ __forceinline__ uint32_t mapa(uint32_t addr, uint32_t cta) {
    uint32_t r; asm("mapa.shared::cluster.u32 %0, %1, %2;" : "=r"(r) : "r"(addr), "r"(cta)); return r;
}
__device__ __forceinline__ void mbar_wait(uint32_t bar, uint32_t parity) {
    asm volatile(
        "{\n.reg .pred p;\n.reg .u32 n;\n"
        "mbarrier.try_wait.parity.shared::cta.b64 p, [%0], %1;\n"
        "@p bra DONE;\n"
        "mov.u32 n, 0;\n"
        "LAB_WAIT:\n"
        "mbarrier.try_wait.parity.shared::cta.b64 p, [%0], %1, 100000;\n"
        "@p bra DONE;\n"
        "add.u32 n, n, 1;\n"
        "setp.lt.u32 p, n, 200000;\n"
        "@p bra LAB_WAIT;\n"
        "trap;\n"
        "DONE:\n}\n" ::"r"(bar), "r"(parity) : "memory");
}
__device__ __forceinline__ void mbar_wait_hot(uint32_t bar, uint32_t parity) {
    asm volatile("{\n.reg .pred p;\nLAB_WAIT:\nmbarrier.try_wait.parity.shared::cta.b64 p, [%0], %1;\n@!p bra LAB_WAIT;\n}\n" ::"r"(bar), "r"(parity) : "memory");
}
__device__ __forceinline__ void flag_wait(const unsigned* flag, unsigned target) {
    asm volatile(
        "{\n.reg .pred p;\n.reg .u32 n, v;\n.reg .s32 d;\n"
        "mov.u32 n, 0;\n"
        "LAB_WAIT:\n"
        "ld.acquire.gpu.global.u32 v, [%0];\n"
        "sub.s32 d, v, %1;\n"
        "setp.ge.s32 p, d, 0;\n"
        "@p bra DONE;\n"
        "nanosleep.u32 40;\n"
        "add.u32 n, n, 1;\n"
        "setp.lt.u32 p, n, 3000000;\n"
        "@p bra LAB_WAIT;\n"
        "trap;\n"
        "DONE:\n}\n" ::"l"(flag), "r"(target) : "memory");
}
__device__ __forceinline__ void flag_signal(unsigned* flag) {
    asm volatile("red.release.gpu.global.add.u32 [%0], 1;" ::"l"(flag) : "memory");
}
__device__ __forceinline__ void fence_async_global() { asm volatile("fence.proxy.async.global;" ::: "memory"); }
__device__ __forceinline__ unsigned* flag_ptr(int idx) { return g_flags + idx * 8; }

__device__ __forceinline__ uint64_t policy_stream() {
    uint64_t p; asm("createpolicy.fractional.L2::evict_first.b64 %0, 1.0;" : "=l"(p)); return p;
}
__device__ __forceinline__ uint64_t policy_normal() { return 0x1000000000000000ull; }
__device__ __forceinline__ uint64_t policy(bool stream) { return stream ? policy_stream() : policy_normal(); }
__device__ __forceinline__ void bulk_load(uint32_t dst, const void* src, uint32_t bytes, uint32_t bar, uint64_t pol) {
    asm volatile("cp.async.bulk.shared::cluster.global.mbarrier::complete_tx::bytes.L2::cache_hint [%0], [%1], %2, [%3], %4;"
                 ::"r"(dst), "l"(src), "r"(bytes), "r"(bar), "l"(pol) : "memory");
}
__device__ __forceinline__ void bulk_load_mc(uint32_t dst, const void* src, uint32_t bytes, uint32_t bar, uint64_t pol) {
    asm volatile("cp.async.bulk.shared::cluster.global.mbarrier::complete_tx::bytes.multicast::cluster.L2::cache_hint [%0], [%1], %2, [%3], %4, %5;"
                 ::"r"(dst), "l"(src), "r"(bytes), "r"(bar), "h"((uint16_t)3), "l"(pol) : "memory");
}
__device__ __forceinline__ void tma2d(uint32_t dst, const CUtensorMap* tm, int c0, int c1, uint32_t bar, uint64_t pol) {
    asm volatile("cp.async.bulk.tensor.2d.shared::cluster.global.mbarrier::complete_tx::bytes.L2::cache_hint [%0], [%1, {%3, %4}], [%2], %5;"
                 ::"r"(dst), "l"(tm), "r"(bar), "r"(c0), "r"(c1), "l"(pol) : "memory");
}
__device__ __forceinline__ void tma2d_mc(uint32_t dst, const CUtensorMap* tm, int c0, int c1, uint32_t bar, uint64_t pol) {
    asm volatile("cp.async.bulk.tensor.2d.shared::cluster.global.mbarrier::complete_tx::bytes.multicast::cluster.L2::cache_hint [%0], [%1, {%3, %4}], [%2], %5, %6;"
                 ::"r"(dst), "l"(tm), "r"(bar), "r"(c0), "r"(c1), "h"((uint16_t)3), "l"(pol) : "memory");
}
__device__ __forceinline__ void tma3d_mc(uint32_t dst, const CUtensorMap* tm, int c0, int c1, int c2, uint32_t bar, uint64_t pol) {
    asm volatile("cp.async.bulk.tensor.3d.shared::cluster.global.mbarrier::complete_tx::bytes.multicast::cluster.L2::cache_hint [%0], [%1, {%3, %4, %5}], [%2], %6, %7;"
                 ::"r"(dst), "l"(tm), "r"(bar), "r"(c0), "r"(c1), "r"(c2), "h"((uint16_t)3), "l"(pol) : "memory");
}
__device__ __forceinline__ void tma3d(uint32_t dst, const CUtensorMap* tm, int c0, int c1, int c2, uint32_t bar) {
    asm volatile("cp.async.bulk.tensor.3d.shared::cluster.global.mbarrier::complete_tx::bytes.L2::cache_hint [%0], [%1, {%3, %4, %5}], [%2], %6;"
                 ::"r"(dst), "l"(tm), "r"(bar), "r"(c0), "r"(c1), "r"(c2), "l"(policy_stream()) : "memory");
}
__device__ __forceinline__ void tma2d_prefetch(const CUtensorMap* tm, int c0, int c1) {
    asm volatile("cp.async.bulk.prefetch.tensor.2d.L2.global [%0, {%1, %2}];" ::"l"(tm), "r"(c0), "r"(c1) : "memory");
}
__device__ __forceinline__ void tma3d_prefetch(const CUtensorMap* tm, int c0, int c1, int c2) {
    asm volatile("cp.async.bulk.prefetch.tensor.3d.L2.global [%0, {%1, %2, %3}];" ::"l"(tm), "r"(c0), "r"(c1), "r"(c2) : "memory");
}
__device__ __forceinline__ void l2_prefetch(const void* p, uint32_t bytes) {
    asm volatile("cp.async.bulk.prefetch.L2.global [%0], %1;" ::"l"(p), "r"(bytes) : "memory");
}
__device__ __forceinline__ bool elect_one() {
    uint32_t r; asm volatile("{\n.reg .pred p;\nelect.sync _|p, 0xffffffff;\nselp.u32 %0, 1, 0, p;\n}\n" : "=r"(r)); return r != 0;
}
__device__ __forceinline__ void wg_fence() { asm volatile("wgmma.fence.sync.aligned;" ::: "memory"); }
__device__ __forceinline__ void wg_commit() { asm volatile("wgmma.commit_group.sync.aligned;" ::: "memory"); }
template <int N> __device__ __forceinline__ void wg_wait() { asm volatile("wgmma.wait_group.sync.aligned %0;" ::"n"(N) : "memory"); }
__device__ __forceinline__ void bar_sync(int id, int n) { asm volatile("bar.sync %0, %1;" ::"r"(id), "r"(n) : "memory"); }
__device__ __forceinline__ void bar_arrive(int id, int n) { asm volatile("bar.arrive %0, %1;" ::"r"(id), "r"(n) : "memory"); }
__device__ __forceinline__ void token_wait(int w) {
    asm volatile("{\n.reg .pred p;\nsetp.eq.u32 p, %0, 0;\n@p bar.sync 1, 256;\n@!p bar.sync 2, 256;\n}\n" ::"r"(w) : "memory");
}
__device__ __forceinline__ void token_pass(int w) {
    asm volatile("{\n.reg .pred p;\nsetp.eq.u32 p, %0, 0;\n@p bar.arrive 2, 256;\n@!p bar.arrive 1, 256;\n}\n" ::"r"(w) : "memory");
}
template <int N> __device__ __forceinline__ void fence_regs(float (&a)[N]) {
#pragma unroll
    for (int i = 0; i < N; i++) asm volatile("" : "+f"(a[i])::"memory");
}
template <int N> __device__ __forceinline__ void undef_regs(float (&a)[N]) {
#pragma unroll
    for (int i = 0; i < N; i++) asm volatile("" : "=f"(a[i]));
}
__device__ __forceinline__ void ldsm4t(uint32_t& r0, uint32_t& r1, uint32_t& r2, uint32_t& r3, uint32_t addr) {
    asm volatile("ldmatrix.sync.aligned.m8n8.x4.trans.shared.b16 {%0,%1,%2,%3}, [%4];"
                 : "=r"(r0), "=r"(r1), "=r"(r2), "=r"(r3) : "r"(addr) : "memory");
}
__device__ __forceinline__ uint32_t pack_bf16(float lo, float hi) {
    uint32_t r; asm("cvt.rn.bf16x2.f32 %0, %1, %2;" : "=r"(r) : "f"(hi), "f"(lo)); return r;
}
__device__ __forceinline__ float bf_lo(uint32_t v) { return __uint_as_float(v << 16); }
__device__ __forceinline__ float bf_hi(uint32_t v) { return __uint_as_float(v & 0xffff0000u); }
__device__ __forceinline__ float bf_round(float v) { return __bfloat162float(__float2bfloat16_rn(v)); }
__device__ __forceinline__ float ex2(float v) { float r; asm("ex2.approx.ftz.f32 %0, %1;" : "=f"(r) : "f"(v)); return r; }
__device__ __forceinline__ void ex2v(float& v) { asm volatile("ex2.approx.ftz.f32 %0, %0;" : "+f"(v)); }
__device__ __forceinline__ float rcp_fast(float v) { float r; asm("rcp.approx.ftz.f32 %0, %1;" : "=f"(r) : "f"(v)); return r; }
__device__ __forceinline__ float sqrt_fast(float v) { float r; asm("sqrt.approx.ftz.f32 %0, %1;" : "=f"(r) : "f"(v)); return r; }
__device__ __forceinline__ void stg128(void* p, uint32_t a, uint32_t b, uint32_t c, uint32_t d) {
    asm volatile("st.global.v4.b32 [%0], {%1,%2,%3,%4};" ::"l"(p), "r"(a), "r"(b), "r"(c), "r"(d) : "memory");
}
__device__ __forceinline__ void stg128_hint(void* p, uint32_t a, uint32_t b, uint32_t c, uint32_t d, uint64_t pol) {
    asm volatile("st.global.L2::cache_hint.v4.b32 [%0], {%1,%2,%3,%4}, %5;" ::"l"(p), "r"(a), "r"(b), "r"(c), "r"(d), "l"(pol) : "memory");
}
__device__ __forceinline__ uint4 ldg128(const void* p) {
    uint4 v; asm volatile("ld.global.cg.v4.b32 {%0,%1,%2,%3}, [%4];" : "=r"(v.x), "=r"(v.y), "=r"(v.z), "=r"(v.w) : "l"(p) : "memory"); return v;
}
__device__ __forceinline__ uint64_t mkdesc(uint32_t addr, uint32_t lbo, uint32_t sbo, uint32_t swz) {
    uint32_t lo = ((addr & 0x3FFFF) >> 4) | ((lbo >> 4) << 16);
    uint32_t hi = (sbo >> 4) | (swz << 30);
    return ((uint64_t)hi << 32) | lo;
}
__device__ __forceinline__ int perm32(int v) { return (v & ~30) | ((v >> 2) & 6) | ((v << 2) & 24); }

__device__ __forceinline__ void wgmma_rs_n128_ta0_tb0(float (&d)[64], uint32_t a0, uint32_t a1, uint32_t a2, uint32_t a3, uint64_t descB, int scaleD) {
  asm volatile("{\n.reg .pred p;\nsetp.ne.b32 p, %69, 0;\n"
    "wgmma.mma_async.sync.aligned.m64n128k16.f32.bf16.bf16 "
    "{%0, %1, %2, %3, %4, %5, %6, %7, %8, %9, %10, %11, %12, %13, %14, %15, %16, %17, %18, %19, %20, %21, %22, %23, %24, %25, %26, %27, %28, %29, %30, %31, %32, %33, %34, %35, %36, %37, %38, %39, %40, %41, %42, %43, %44, %45, %46, %47, %48, %49, %50, %51, %52, %53, %54, %55, %56, %57, %58, %59, %60, %61, %62, %63}, "
    "{%64, %65, %66, %67}, %68, p, 1, 1, 0;\n}\n"
    : "+f"(d[0]), "+f"(d[1]), "+f"(d[2]), "+f"(d[3]), "+f"(d[4]), "+f"(d[5]), "+f"(d[6]), "+f"(d[7]), "+f"(d[8]), "+f"(d[9]), "+f"(d[10]), "+f"(d[11]), "+f"(d[12]), "+f"(d[13]), "+f"(d[14]), "+f"(d[15]), "+f"(d[16]), "+f"(d[17]), "+f"(d[18]), "+f"(d[19]), "+f"(d[20]), "+f"(d[21]), "+f"(d[22]), "+f"(d[23]), "+f"(d[24]), "+f"(d[25]), "+f"(d[26]), "+f"(d[27]), "+f"(d[28]), "+f"(d[29]), "+f"(d[30]), "+f"(d[31]), "+f"(d[32]), "+f"(d[33]), "+f"(d[34]), "+f"(d[35]), "+f"(d[36]), "+f"(d[37]), "+f"(d[38]), "+f"(d[39]), "+f"(d[40]), "+f"(d[41]), "+f"(d[42]), "+f"(d[43]), "+f"(d[44]), "+f"(d[45]), "+f"(d[46]), "+f"(d[47]), "+f"(d[48]), "+f"(d[49]), "+f"(d[50]), "+f"(d[51]), "+f"(d[52]), "+f"(d[53]), "+f"(d[54]), "+f"(d[55]), "+f"(d[56]), "+f"(d[57]), "+f"(d[58]), "+f"(d[59]), "+f"(d[60]), "+f"(d[61]), "+f"(d[62]), "+f"(d[63])
    : "r"(a0), "r"(a1), "r"(a2), "r"(a3), "l"(descB), "r"(scaleD));
}
__device__ __forceinline__ void wgmma_rs_n128_ta0_tb1(float (&d)[64], uint32_t a0, uint32_t a1, uint32_t a2, uint32_t a3, uint64_t descB, int scaleD) {
  asm volatile("{\n.reg .pred p;\nsetp.ne.b32 p, %69, 0;\n"
    "wgmma.mma_async.sync.aligned.m64n128k16.f32.bf16.bf16 "
    "{%0, %1, %2, %3, %4, %5, %6, %7, %8, %9, %10, %11, %12, %13, %14, %15, %16, %17, %18, %19, %20, %21, %22, %23, %24, %25, %26, %27, %28, %29, %30, %31, %32, %33, %34, %35, %36, %37, %38, %39, %40, %41, %42, %43, %44, %45, %46, %47, %48, %49, %50, %51, %52, %53, %54, %55, %56, %57, %58, %59, %60, %61, %62, %63}, "
    "{%64, %65, %66, %67}, %68, p, 1, 1, 1;\n}\n"
    : "+f"(d[0]), "+f"(d[1]), "+f"(d[2]), "+f"(d[3]), "+f"(d[4]), "+f"(d[5]), "+f"(d[6]), "+f"(d[7]), "+f"(d[8]), "+f"(d[9]), "+f"(d[10]), "+f"(d[11]), "+f"(d[12]), "+f"(d[13]), "+f"(d[14]), "+f"(d[15]), "+f"(d[16]), "+f"(d[17]), "+f"(d[18]), "+f"(d[19]), "+f"(d[20]), "+f"(d[21]), "+f"(d[22]), "+f"(d[23]), "+f"(d[24]), "+f"(d[25]), "+f"(d[26]), "+f"(d[27]), "+f"(d[28]), "+f"(d[29]), "+f"(d[30]), "+f"(d[31]), "+f"(d[32]), "+f"(d[33]), "+f"(d[34]), "+f"(d[35]), "+f"(d[36]), "+f"(d[37]), "+f"(d[38]), "+f"(d[39]), "+f"(d[40]), "+f"(d[41]), "+f"(d[42]), "+f"(d[43]), "+f"(d[44]), "+f"(d[45]), "+f"(d[46]), "+f"(d[47]), "+f"(d[48]), "+f"(d[49]), "+f"(d[50]), "+f"(d[51]), "+f"(d[52]), "+f"(d[53]), "+f"(d[54]), "+f"(d[55]), "+f"(d[56]), "+f"(d[57]), "+f"(d[58]), "+f"(d[59]), "+f"(d[60]), "+f"(d[61]), "+f"(d[62]), "+f"(d[63])
    : "r"(a0), "r"(a1), "r"(a2), "r"(a3), "l"(descB), "r"(scaleD));
}
__device__ __forceinline__ void wgmma_rs_n64_ta0_tb1(float (&d)[32], uint32_t a0, uint32_t a1, uint32_t a2, uint32_t a3, uint64_t descB, int scaleD) {
  asm volatile("{\n.reg .pred p;\nsetp.ne.b32 p, %37, 0;\n"
    "wgmma.mma_async.sync.aligned.m64n64k16.f32.bf16.bf16 "
    "{%0, %1, %2, %3, %4, %5, %6, %7, %8, %9, %10, %11, %12, %13, %14, %15, %16, %17, %18, %19, %20, %21, %22, %23, %24, %25, %26, %27, %28, %29, %30, %31}, "
    "{%32, %33, %34, %35}, %36, p, 1, 1, 1;\n}\n"
    : "+f"(d[0]), "+f"(d[1]), "+f"(d[2]), "+f"(d[3]), "+f"(d[4]), "+f"(d[5]), "+f"(d[6]), "+f"(d[7]), "+f"(d[8]), "+f"(d[9]), "+f"(d[10]), "+f"(d[11]), "+f"(d[12]), "+f"(d[13]), "+f"(d[14]), "+f"(d[15]), "+f"(d[16]), "+f"(d[17]), "+f"(d[18]), "+f"(d[19]), "+f"(d[20]), "+f"(d[21]), "+f"(d[22]), "+f"(d[23]), "+f"(d[24]), "+f"(d[25]), "+f"(d[26]), "+f"(d[27]), "+f"(d[28]), "+f"(d[29]), "+f"(d[30]), "+f"(d[31])
    : "r"(a0), "r"(a1), "r"(a2), "r"(a3), "l"(descB), "r"(scaleD));
}
__device__ __forceinline__ void wgmma_ss_n128_ta1_tb0(float (&d)[64], uint64_t descA, uint64_t descB, int scaleD) {
  asm volatile("{\n.reg .pred p;\nsetp.ne.b32 p, %66, 0;\n"
    "wgmma.mma_async.sync.aligned.m64n128k16.f32.bf16.bf16 "
    "{%0, %1, %2, %3, %4, %5, %6, %7, %8, %9, %10, %11, %12, %13, %14, %15, %16, %17, %18, %19, %20, %21, %22, %23, %24, %25, %26, %27, %28, %29, %30, %31, %32, %33, %34, %35, %36, %37, %38, %39, %40, %41, %42, %43, %44, %45, %46, %47, %48, %49, %50, %51, %52, %53, %54, %55, %56, %57, %58, %59, %60, %61, %62, %63}, "
    "%64, %65, p, 1, 1, 1, 0;\n}\n"
    : "+f"(d[0]), "+f"(d[1]), "+f"(d[2]), "+f"(d[3]), "+f"(d[4]), "+f"(d[5]), "+f"(d[6]), "+f"(d[7]), "+f"(d[8]), "+f"(d[9]), "+f"(d[10]), "+f"(d[11]), "+f"(d[12]), "+f"(d[13]), "+f"(d[14]), "+f"(d[15]), "+f"(d[16]), "+f"(d[17]), "+f"(d[18]), "+f"(d[19]), "+f"(d[20]), "+f"(d[21]), "+f"(d[22]), "+f"(d[23]), "+f"(d[24]), "+f"(d[25]), "+f"(d[26]), "+f"(d[27]), "+f"(d[28]), "+f"(d[29]), "+f"(d[30]), "+f"(d[31]), "+f"(d[32]), "+f"(d[33]), "+f"(d[34]), "+f"(d[35]), "+f"(d[36]), "+f"(d[37]), "+f"(d[38]), "+f"(d[39]), "+f"(d[40]), "+f"(d[41]), "+f"(d[42]), "+f"(d[43]), "+f"(d[44]), "+f"(d[45]), "+f"(d[46]), "+f"(d[47]), "+f"(d[48]), "+f"(d[49]), "+f"(d[50]), "+f"(d[51]), "+f"(d[52]), "+f"(d[53]), "+f"(d[54]), "+f"(d[55]), "+f"(d[56]), "+f"(d[57]), "+f"(d[58]), "+f"(d[59]), "+f"(d[60]), "+f"(d[61]), "+f"(d[62]), "+f"(d[63])
    : "l"(descA), "l"(descB), "r"(scaleD));
}
__device__ __forceinline__ void wgmma_ss_n160_ta0_tb1(float (&d)[80], uint64_t descA, uint64_t descB, int scaleD) {
  asm volatile("{\n.reg .pred p;\nsetp.ne.b32 p, %82, 0;\n"
    "wgmma.mma_async.sync.aligned.m64n160k16.f32.bf16.bf16 "
    "{%0, %1, %2, %3, %4, %5, %6, %7, %8, %9, %10, %11, %12, %13, %14, %15, %16, %17, %18, %19, %20, %21, %22, %23, %24, %25, %26, %27, %28, %29, %30, %31, %32, %33, %34, %35, %36, %37, %38, %39, %40, %41, %42, %43, %44, %45, %46, %47, %48, %49, %50, %51, %52, %53, %54, %55, %56, %57, %58, %59, %60, %61, %62, %63, %64, %65, %66, %67, %68, %69, %70, %71, %72, %73, %74, %75, %76, %77, %78, %79}, "
    "%80, %81, p, 1, 1, 0, 1;\n}\n"
    : "+f"(d[0]), "+f"(d[1]), "+f"(d[2]), "+f"(d[3]), "+f"(d[4]), "+f"(d[5]), "+f"(d[6]), "+f"(d[7]), "+f"(d[8]), "+f"(d[9]), "+f"(d[10]), "+f"(d[11]), "+f"(d[12]), "+f"(d[13]), "+f"(d[14]), "+f"(d[15]), "+f"(d[16]), "+f"(d[17]), "+f"(d[18]), "+f"(d[19]), "+f"(d[20]), "+f"(d[21]), "+f"(d[22]), "+f"(d[23]), "+f"(d[24]), "+f"(d[25]), "+f"(d[26]), "+f"(d[27]), "+f"(d[28]), "+f"(d[29]), "+f"(d[30]), "+f"(d[31]), "+f"(d[32]), "+f"(d[33]), "+f"(d[34]), "+f"(d[35]), "+f"(d[36]), "+f"(d[37]), "+f"(d[38]), "+f"(d[39]), "+f"(d[40]), "+f"(d[41]), "+f"(d[42]), "+f"(d[43]), "+f"(d[44]), "+f"(d[45]), "+f"(d[46]), "+f"(d[47]), "+f"(d[48]), "+f"(d[49]), "+f"(d[50]), "+f"(d[51]), "+f"(d[52]), "+f"(d[53]), "+f"(d[54]), "+f"(d[55]), "+f"(d[56]), "+f"(d[57]), "+f"(d[58]), "+f"(d[59]), "+f"(d[60]), "+f"(d[61]), "+f"(d[62]), "+f"(d[63]), "+f"(d[64]), "+f"(d[65]), "+f"(d[66]), "+f"(d[67]), "+f"(d[68]), "+f"(d[69]), "+f"(d[70]), "+f"(d[71]), "+f"(d[72]), "+f"(d[73]), "+f"(d[74]), "+f"(d[75]), "+f"(d[76]), "+f"(d[77]), "+f"(d[78]), "+f"(d[79])
    : "l"(descA), "l"(descB), "r"(scaleD));
}

#define PROF_DECL(b)
#define PROF_EV(tag)
#define PROF_GT(tag)

template <int N> struct IC { static constexpr int value = N; };
struct Cur {
    uint32_t slot, ph;
    __device__ __forceinline__ void adv() { if (++slot == NSLOT) { slot = 0; ph ^= 1; } }
};
constexpr int E0 = 6, E_ATT0 = 48, E_ATT1 = 108;
__host__ __device__ constexpr uint32_t slot_of(int e) { return (e + E0) % NSLOT; }
__device__ __forceinline__ Cur cur_at(int e) { Cur c; c.slot = (e + E0) % NSLOT; c.ph = ((e + E0) / NSLOT) & 1; return c; }

__device__ __forceinline__ int q_tile(int k, int t) { return (t < 2 ? 14 - 2 * k : 2 * k) + (t & 1); }
__device__ __forceinline__ int op_head(int i, int kap) { return 16 * kap + 2 * (i & 7) + (i >> 3); }

constexpr float SM_SCALE = 0.08838834764831845f * 1.4426950408889634f;

struct Ctx {
    uint32_t ring, misc;
    uint32_t rel;
    int w, warp, lane;
};
__device__ __forceinline__ void release(const Ctx& c, uint32_t off, uint32_t cnt) {
    if (c.lane < 2) mbar_arrive_cluster(c.rel + off, cnt);
}
__device__ __forceinline__ void signal_event(const Ctx& c, int ev) {
    __syncwarp();
    if (c.lane == 0) mbar_arrive(c.misc + BAR_EV + (c.w * 16 + ev) * 8);
}
template <int NK, int OFF, int N>
__device__ __forceinline__ uint32_t load_afrag(uint32_t (&a)[N], uint32_t base, const Ctx& c) {
    int r = c.lane & 7, mat = c.lane >> 3;
    uint32_t addr = base + (8 * (mat >> 1) + r) * 128 + (((2 * c.warp + (mat & 1)) ^ r) << 4);
#pragma unroll
    for (int k = 0; k < NK; k++) ldsm4t(a[OFF + 4 * k], a[OFF + 4 * k + 1], a[OFF + 4 * k + 2], a[OFF + 4 * k + 3], addr + k * 2048);
    uint32_t dep = 0;
#pragma unroll
    for (int k = 0; k < NK; k++) dep |= a[OFF + 4 * k];
    return dep & blockIdx.y;
}
__device__ __forceinline__ void store_proj(const float (&acc)[64], unsigned char* dst  , const Ctx& c, uint64_t pol) {
    int g = c.lane >> 2, t = c.lane & 3;
#pragma unroll
    for (int i = 0; i < 2; i++) {
        int row = perm32(64 * c.w + 16 * c.warp + 8 * i + g);
        unsigned char* p = dst + row * 128;
#pragma unroll
        for (int q = 0; q < 4; q++) {
            int chunk = (4 * (q & 1) + t) ^ (row & 7);
            stg128_hint(p + (q >> 1) * 16384 + chunk * 16,
                   pack_bf16(acc[16 * q + 2 * i], acc[16 * q + 2 * i + 1]), pack_bf16(acc[16 * q + 4 + 2 * i], acc[16 * q + 4 + 2 * i + 1]),
                   pack_bf16(acc[16 * q + 8 + 2 * i], acc[16 * q + 8 + 2 * i + 1]), pack_bf16(acc[16 * q + 12 + 2 * i], acc[16 * q + 12 + 2 * i + 1]), pol);
        }
    }
}

constexpr float SAFE_EXP = 40.0f, SAFE_SUM = 1099511627776.0f;
template <int NJ>
__device__ __forceinline__ void row_max(const float (&s)[4 * NJ], float (&mx)[2]) {
#pragma unroll
    for (int i = 0; i < 2; i++) {
        float a = fmaxf(s[2 * i], s[2 * i + 1]), b = fmaxf(s[4 + 2 * i], s[4 + 2 * i + 1]);
#pragma unroll
        for (int j = 2; j < NJ; j += 2) {
            a = fmaxf(a, fmaxf(s[4 * j + 2 * i], s[4 * j + 2 * i + 1]));
            b = fmaxf(b, fmaxf(s[4 * j + 4 + 2 * i], s[4 * j + 4 + 2 * i + 1]));
        }
        a = fmaxf(a, b);
        a = fmaxf(a, __shfl_xor_sync(0xffffffffu, a, 1));
        mx[i] = fmaxf(a, __shfl_xor_sync(0xffffffffu, a, 2));
    }
}
template <int NJ, bool SHIFT>
__device__ __forceinline__ void exp_sum(float (&s)[4 * NJ], const float (&m)[2], float& l0, float& l1) {
#pragma unroll
    for (int j = 0; j < NJ; j++) {
#pragma unroll
        for (int e = 0; e < 4; e++) s[4 * j + e] = ex2(SHIFT ? s[4 * j + e] - m[e >> 1] : s[4 * j + e]);
        l0 += s[4 * j + 0] + s[4 * j + 1]; l1 += s[4 * j + 2] + s[4 * j + 3];
    }
}
template <int NJ>
__device__ __forceinline__ bool softmax_first(float (&s)[4 * NJ], float (&m)[2], float (&l)[2]) {
    row_max<NJ>(s, m);
    bool gen = __any_sync(0xffffffffu, !(fabsf(m[0]) <= SAFE_EXP && fabsf(m[1]) <= SAFE_EXP));
    if (!gen) m[0] = m[1] = 0.f;
    l[0] = l[1] = 0.f;
    exp_sum<NJ, true>(s, m, l[0], l[1]);
    return gen;
}
__device__ __forceinline__ void recompute_scores(float (&s)[64], const uint32_t (&q)[32], uint32_t kaddr, const Ctx& c) {
    const int r = c.lane & 7, mat = c.lane >> 3;
    const uint32_t a0 = kaddr + (8 * (mat & 1) + r) * 128 + (((mat >> 1) ^ r) << 4);
#pragma unroll
    for (int i = 0; i < 64; i++) s[i] = 0.f;
#pragma unroll
    for (int jp = 0; jp < 8; jp++) {
#pragma unroll
        for (int k = 0; k < 8; k++) {
            asm volatile(
                "{\n.reg .b32 b0, b1, b2, b3;\n"
                "ldmatrix.sync.aligned.m8n8.x4.trans.shared.b16 {b0,b1,b2,b3}, [%12];\n"
                "mma.sync.aligned.m16n8k16.row.col.f32.bf16.bf16.f32 {%0,%1,%2,%3}, {%8,%9,%10,%11}, {b0,b1}, {%0,%1,%2,%3};\n"
                "mma.sync.aligned.m16n8k16.row.col.f32.bf16.bf16.f32 {%4,%5,%6,%7}, {%8,%9,%10,%11}, {b2,b3}, {%4,%5,%6,%7};\n}\n"
                : "+f"(s[8 * jp]), "+f"(s[8 * jp + 1]), "+f"(s[8 * jp + 2]), "+f"(s[8 * jp + 3]),
                  "+f"(s[8 * jp + 4]), "+f"(s[8 * jp + 5]), "+f"(s[8 * jp + 6]), "+f"(s[8 * jp + 7])
                : "r"(q[4 * k]), "r"(q[4 * k + 1]), "r"(q[4 * k + 2]), "r"(q[4 * k + 3]),
                  "r"((a0 ^ ((jp & 3) << 5)) + (jp >> 2) * 16384 + k * 2048) : "memory");
        }
    }
}
template <int J0>
__device__ __forceinline__ void mask_diag(float (&s)[4 * J0 + 32], const Ctx& c) {
    int g = c.lane >> 2, t = c.lane & 3;
#pragma unroll
    for (int i = 0; i < 2; i++) {
        int lim = perm32(16 * c.warp + 8 * i + g) - 8 * t;
#pragma unroll
        for (int j = 0; j < 8; j++)
#pragma unroll
            for (int e = 0; e < 2; e++)
                if (32 * (j >> 2) + 2 * (j & 3) + e > lim) s[4 * (J0 + j) + 2 * i + e] = -INFINITY;
    }
}
__device__ __forceinline__ void issue_pv(float (&o)[64], const uint32_t (&p)[32], uint32_t vaddr, int acc, bool half) {
    uint64_t d = mkdesc(vaddr, 16, 1024, 1);
    if (half) {
        wg_fence();
#pragma unroll
        for (int k = 0; k < 4; k++) wgmma_rs_n128_ta0_tb0(o, p[4 * k], p[4 * k + 1], p[4 * k + 2], p[4 * k + 3], d + 2 * k, k != 0);
        wg_commit();
    } else {
        wg_fence();
#pragma unroll
        for (int k = 0; k < 8; k++)
            wgmma_rs_n128_ta0_tb0(o, p[4 * k], p[4 * k + 1], p[4 * k + 2], p[4 * k + 3], d + (k >> 2) * 1024 + 2 * (k & 3), k ? 1 : acc);
        wg_commit();
    }
}
__device__ __forceinline__ void issue_qk(float (&s)[64], const uint32_t (&q)[32], uint32_t kaddr) {
    uint64_t d = mkdesc(kaddr, 16384, 1024, 1);
    wg_fence();
#pragma unroll
    for (int k = 0; k < 8; k++) wgmma_rs_n128_ta0_tb1(s, q[4 * k], q[4 * k + 1], q[4 * k + 2], q[4 * k + 3], d + 128 * k, k != 0);
    wg_commit();
}
__device__ __forceinline__ void issue_qk_half(float (&s32)[32], const uint32_t (&q)[32], uint32_t kaddr) {
    uint64_t d = mkdesc(kaddr, 16384, 1024, 1);
    wg_fence();
#pragma unroll
    for (int k = 0; k < 8; k++) wgmma_rs_n64_ta0_tb1(s32, q[4 * k], q[4 * k + 1], q[4 * k + 2], q[4 * k + 3], d + 128 * k, k != 0);
    wg_commit();
}
__device__ __forceinline__ void row_inv(const float (&l)[2], float (&inv)[2]) {
#pragma unroll
    for (int i = 0; i < 2; i++) {
        float sum = l[i];
        sum += __shfl_xor_sync(0xffffffffu, sum, 1);
        sum += __shfl_xor_sync(0xffffffffu, sum, 2);
        inv[i] = rcp_fast(sum);
    }
}
__device__ __forceinline__ void stage_ctx(float (&o)[64], const float (&inv)[2], Cur ce, const Ctx& c) {
    const int g = c.lane >> 2, t = c.lane & 3, r7 = ((g & 1) << 2) | (g >> 1);
    const uint32_t base = c.ring + ce.slot * SLOT_BYTES + c.w * 16384 + (16 * c.warp + r7) * 128 + ((t ^ r7) << 4);
    mbar_wait_hot(c.misc + BAR_FULL + 8 * ce.slot, ce.ph);
#pragma unroll
    for (int q = 0; q < 4; q++) {
        uint32_t v[8];
#pragma unroll
        for (int i = 0; i < 2; i++)
#pragma unroll
            for (int j = 0; j < 4; j++) v[4 * i + j] = pack_bf16(o[16 * q + 4 * j + 2 * i] * inv[i], o[16 * q + 4 * j + 2 * i + 1] * inv[i]);
#pragma unroll
        for (int i = 0; i < 8; i++) { o[16 * q + i] = __uint_as_float(v[i]); asm volatile("" : "=f"(o[16 * q + 8 + i])); }
#pragma unroll
        for (int i = 0; i < 2; i++)
            asm volatile("st.shared.v4.b32 [%0], {%1,%2,%3,%4};" ::"r"((base ^ ((q & 1) << 6)) + (q >> 1) * 8192 + i * 1024),
                         "r"(v[4 * i]), "r"(v[4 * i + 1]), "r"(v[4 * i + 2]), "r"(v[4 * i + 3]) : "memory");
    }
}
__device__ __forceinline__ void publish_ctx(int ev, const Ctx& c) {
    asm volatile("fence.proxy.async.shared::cta;" ::: "memory");
    signal_event(c, ev);
}

__device__ __forceinline__ const unsigned char* xn_addr(int row, int col) {
    return g_xn + ((row >> 7) * 10 + (col >> 6)) * 16384 + (row & 127) * 128 + ((((col & 63) >> 3) ^ (row & 7)) << 4);
}
__device__ __forceinline__ void mma16816(float (&d)[4], uint32_t a0, uint32_t a1, uint32_t a2, uint32_t a3, uint32_t b0, uint32_t b1) {
    asm volatile("mma.sync.aligned.m16n8k16.row.col.f32.bf16.bf16.f32 {%0,%1,%2,%3}, {%4,%5,%6,%7}, {%8,%9}, {%0,%1,%2,%3};"
                 : "+f"(d[0]), "+f"(d[1]), "+f"(d[2]), "+f"(d[3]) : "r"(a0), "r"(a1), "r"(a2), "r"(a3), "r"(b0), "r"(b1));
}
__device__ __forceinline__ uint32_t lds32(uint32_t addr) { uint32_t v; asm volatile("ld.shared.u32 %0, [%1];" : "=r"(v) : "r"(addr)); return v; }

__device__ __forceinline__ void aux_cta(const CUtensorMap* tmG, const CUtensorMap* tmU, const CUtensorMap* tmD, unsigned char* sm, int a) {
    constexpr int STG = 57344, XS = 3 * STG, HS = XS + 8 * 1296, KEY = HS + 8 * 912, MI = KEY + 8192;
    const int tid = threadIdx.x, warp = __shfl_sync(0xffffffffu, tid >> 5, 0), lane = tid & 31;
    const uint32_t sb = smem_u32(sm);
    const uint32_t full = sb + MI, empty = sb + MI + 32;
    int* s_sel = reinterpret_cast<int*>(sm + MI + 64);
    float* s_r = reinterpret_cast<float*>(sm + MI + 96);
    volatile unsigned* s_misc = reinterpret_cast<volatile unsigned*>(sm + MI + 128);
    uint32_t* s_key = reinterpret_cast<uint32_t*>(sm + KEY);
    PROF_DECL(128 + a)
    PROF_GT(0);
    if (tid == 0) {
        for (int i = 0; i < 3; i++) { mbar_init(full + 8 * i, 1); mbar_init(empty + 8 * i, 10); }
        asm volatile("fence.mbarrier_init.release.cluster;" ::: "memory");
    }
    __syncthreads();
    if (warp == 11) {
        if (elect_one()) {
            int st = 0; uint32_t ph = 0;
#pragma unroll 1
            for (int s = 0; s < 34; s++) {
                mbar_wait(empty + 8 * st, ph ^ 1);
                const uint32_t dst = sb + st * STG, fb = full + 8 * st;
                if (s < 20) {
                    mbar_expect_tx(fb, 57344);
                    tma3d(dst, tmG, 0, 32 * s, 7 * a, fb);
                    tma3d(dst + 28672, tmU, 0, 32 * s, 7 * a, fb);
                } else {
                    mbar_expect_tx(fb, 40960);
                    tma3d(dst, tmD, 0, 448 * a + 32 * (s - 20), 0, fb);
                }
                if (s >= 3) {
#pragma unroll 1
                    for (int f = (s == 3 ? 4 : s + 6); f <= s + 6 && f < 34; f++) {
                        if (f < 20) { tma3d_prefetch(tmG, 0, 32 * f, 7 * a); tma3d_prefetch(tmU, 0, 32 * f, 7 * a); }
                        else tma3d_prefetch(tmD, 0, 448 * a + 32 * (f - 20), 0);
                    }
                }
                if (++st == 3) { st = 0; ph ^= 1; }
            }
        }
        return;
    }
    if (warp == 10) return;
    if (tid < 16) {
        unsigned e = *reinterpret_cast<volatile unsigned*>(&g_epoch);
        if (tid == 0) s_misc[0] = e;
        flag_wait(flag_ptr(FL_LN + tid), (e + 1) * 32u);
    }
    bar_sync(1, 320);
    PROF_GT(50);
    const unsigned ep = s_misc[0];
    auto top8 = [&](uint32_t (&key)[8]) {
        uint32_t mine = 0;
#pragma unroll 1
        for (int r = 0; r < TOPC; r++) {
            uint32_t best = 0;
#pragma unroll
            for (int i = 0; i < 8; i++) best = max(best, key[i]);
            best = __reduce_max_sync(0xffffffffu, best);
#pragma unroll
            for (int i = 0; i < 8; i++) if (key[i] == best) key[i] = 0;
            if (lane == r) mine = best;
        }
        return mine;
    };
#pragma unroll 1
    for (int pass = 0; pass < 2; pass++) {
        if (warp < (pass ? 1 : 8)) {
            uint32_t key[8];
#pragma unroll
            for (int i = 0; i < 8; i++) {
                if (pass == 0) {
                    int idx = warp * 256 + i * 32 + lane;
                    uint32_t b = __float_as_uint(__ldcg(g_router + idx)) >> 16;
                    b = (b & 0x8000u) ? (~b & 0xffffu) : (b | 0x8000u);
                    key[i] = (b << 16) | (uint32_t)(0xffff - idx);
                } else key[i] = i < 2 ? s_key[i * 32 + lane] : 0u;
            }
            uint32_t best = top8(key);
            if (lane < TOPC) {
                if (pass == 0) s_key[warp * 8 + lane] = best;
                else {
                    uint32_t b = best >> 16;
                    b = (b & 0x8000u) ? (b & 0x7fffu) : (~b & 0xffffu);
                    s_sel[lane] = 0xffff - (int)(best & 0xffffu);
                    s_r[lane] = __uint_as_float(b << 16);
                }
            }
        }
        bar_sync(1, 320);
    }
#pragma unroll
    for (int it = 0; it < 2; it++) {
        int i = tid + it * 320, tk = i / 80, ch = i % 80;
        *reinterpret_cast<uint4*>(sm + XS + tk * 1296 + ch * 16) = __ldcg(reinterpret_cast<const uint4*>(xn_addr(s_sel[tk], ch * 8)));
    }
    bar_sync(1, 320);
    PROF_GT(51);
    const int g = lane >> 2, t = lane & 3;
    const uint32_t woff = warp * 4096 + (8 * (lane >> 4) + (lane & 7)) * 128 + ((((lane >> 3) & 1) ^ (lane & 7)) << 4);
    int st = 0; uint32_t ph = 0;
    float ga[4][4], ua[4][4];
#pragma unroll
    for (int i = 0; i < 4; i++)
#pragma unroll
        for (int e = 0; e < 4; e++) { ga[i][e] = 0.f; ua[i][e] = 0.f; }
#pragma unroll 1
    for (int s = 0; s < 34; s++) {
        if (s == 20) {
            if (warp < 7) {
#pragma unroll
                for (int i = 0; i < 4; i++)
#pragma unroll
                    for (int e = 0; e < 4; e++) {
                        float gv = bf_round(ga[i][e]), uv = bf_round(ua[i][e]);
                        float sg = bf_round(__fdividef(gv, 1.0f + __expf(fminf(-gv, 80.f))));
                        int f = warp * 64 + i * 16 + g + 8 * (e >> 1), tk = 2 * t + (e & 1);
                        *reinterpret_cast<__nv_bfloat16*>(sm + HS + tk * 912 + f * 2) = __float2bfloat16_rn(sg * uv);
                        ga[i][e] = 0.f;
                    }
            }
            bar_sync(1, 320);
            PROF_GT(52);
        }
        mbar_wait(full + 8 * st, ph);
        if (s >= 20 || warp < 7) {
#pragma unroll
            for (int kk = 0; kk < 2; kk++) {
                uint32_t xb = sb + (s < 20 ? XS + g * 1296 + s * 64 : HS + g * 912 + (s - 20) * 64) + 32 * kk + 4 * t;
                uint32_t b0 = lds32(xb), b1 = lds32(xb + 16);
                uint32_t wa = sb + st * STG + woff + kk * 2048;
#pragma unroll
                for (int i = 0; i < 4; i++) {
                    uint32_t a0, a1, a2, a3;
                    ldsm4t(a0, a1, a2, a3, wa ^ (i << 5));
                    mma16816(ga[i], a0, a1, a2, a3, b0, b1);
                    if (s < 20) {
                        ldsm4t(a0, a1, a2, a3, (wa ^ (i << 5)) + 28672);
                        mma16816(ua[i], a0, a1, a2, a3, b0, b1);
                    }
                }
            }
        }
        asm volatile("fence.proxy.async.shared::cta;" ::: "memory");
        __syncwarp();
        if (lane == 0) mbar_arrive(empty + 8 * st);
        if (++st == 3) { st = 0; ph ^= 1; }
    }
#pragma unroll
    for (int i = 0; i < 4; i++)
#pragma unroll
        for (int e = 0; e < 4; e += 2)
            *reinterpret_cast<float2*>(g_moe_part + (a * DM + warp * 64 + i * 16 + g + 4 * e) * 8 + 2 * t) = make_float2(ga[i][e], ga[i][e + 1]);
    bar_sync(1, 320);
    if (tid == 0) {
        __threadfence();
        unsigned old = atomicAdd(flag_ptr(FL_MOE_CNT), 1u);
        s_misc[1] = (old == ep * 4u + 3u);
        __threadfence();
    }
    bar_sync(1, 320);
    PROF_GT(53);
    if (s_misc[1]) {
        const float4* pp = reinterpret_cast<const float4*>(g_moe_part);
#pragma unroll 2
        for (int i = tid; i < DM * 2; i += 320) {
            float4 v0 = __ldcg(pp + i), v1 = __ldcg(pp + DM * 2 + i), v2 = __ldcg(pp + DM * 4 + i), v3 = __ldcg(pp + DM * 6 + i);
            float y[4] = {v0.x + v1.x + v2.x + v3.x, v0.y + v1.y + v2.y + v3.y, v0.z + v1.z + v2.z + v3.z, v0.w + v1.w + v2.w + v3.w};
#pragma unroll
            for (int e = 0; e < 4; e++) {
                int col = i >> 1, tk = (i & 1) * 4 + e;
                float sg = bf_round(__fdividef(1.0f, 1.0f + __expf(fminf(-s_r[tk], 80.f))));
                float upd = bf_round(bf_round(y[e]) * sg);
                float xn = __bfloat162float(*reinterpret_cast<const __nv_bfloat16*>(sm + XS + tk * 1296 + col * 2));
                g_brow[tk * DM + col] = __float2bfloat16_rn(xn + upd);
            }
        }
        if (tid < TOPC) g_sel[tid] = s_sel[tid];
        bar_sync(1, 320);
        if (tid == 0) {
            flag_signal(flag_ptr(FL_MOE_DONE));
            *reinterpret_cast<volatile unsigned*>(&g_epoch) = ep + 1;
        }
        PROF_GT(54);
    }
}

__device__ __forceinline__ void ln_rows(const Params& P, int row0, int lane, uint32_t wr_s) {
    const int hl = lane & 15, row = row0 + (lane >> 4);
    uint32_t v[20];
#pragma unroll
    for (int i = 0; i < 5; i++) {
        uint4 u;
        asm("ld.global.nc.L2::cache_hint.v4.b32 {%0,%1,%2,%3}, [%4], %5;" : "=r"(u.x), "=r"(u.y), "=r"(u.z), "=r"(u.w)
            : "l"(P.x + (size_t)row * DM + 128 * i + 8 * hl), "l"(policy(HM & 512)));
        v[4 * i] = u.x; v[4 * i + 1] = u.y; v[4 * i + 2] = u.z; v[4 * i + 3] = u.w;
    }
    float mean = 0.f, m2 = 0.f;
#pragma unroll
    for (int i = 0; i < 20; i++) { mean += bf_lo(v[i]); mean += bf_hi(v[i]); }
    mean *= (1.0f / 40);
#pragma unroll
    for (int i = 0; i < 20; i++) {
        float d0 = __uint_as_float(__byte_perm(v[i], 0, 0x1044)) - mean, d1 = __uint_as_float(__byte_perm(v[i], 0, 0x3244)) - mean;
        m2 = fmaf(d0, d0, m2); m2 = fmaf(d1, d1, m2);
    }
#pragma unroll
    for (int o = 1; o < 16; o <<= 1) {
        float mo = __shfl_xor_sync(0xffffffffu, mean, o), qo = __shfl_xor_sync(0xffffffffu, m2, o), d = mo - mean;
        m2 = fmaf(d * d, 20.0f * o, m2 + qo);
        mean = 0.5f * (mean + mo);
    }
    const uint32_t mb2 = pack_bf16(mean, mean);
    const float inv = rcp_fast(bf_round(sqrt_fast(bf_round(bf_round(m2 * (1.0f / DM)) + 1e-5f))));
    float dot = 0.f;
    unsigned char* xp = g_xn + ((row >> 7) * 10 + (hl >> 3)) * 16384 + (row & 127) * 128 + (((hl & 7) ^ (row & 7)) << 4);
#pragma unroll
    for (int i = 0; i < 5; i++) {
        uint32_t ww[4];
        asm volatile("ld.shared.v4.b32 {%0,%1,%2,%3}, [%4];" : "=r"(ww[0]), "=r"(ww[1]), "=r"(ww[2]), "=r"(ww[3]) : "r"(wr_s + 256 * i + 16 * hl) : "memory");
#pragma unroll
        for (int e = 0; e < 4; e++) {
            uint32_t d;
            asm("sub.rn.bf16x2 %0, %1, %2;" : "=r"(d) : "r"(v[4 * i + e]), "r"(mb2));
            d = pack_bf16(bf_lo(d) * inv, bf_hi(d) * inv);
            v[4 * i + e] = d;
            dot = fmaf(bf_lo(d), bf_lo(ww[e]), dot);
            dot = fmaf(bf_hi(d), bf_hi(ww[e]), dot);
        }
        stg128(xp + i * 32768, v[4 * i], v[4 * i + 1], v[4 * i + 2], v[4 * i + 3]);
    }
#pragma unroll
    for (int o = 8; o > 0; o >>= 1) dot += __shfl_xor_sync(0xffffffffu, dot, o);
    if (hl == 0) { g_router[row] = bf_round(dot); g_stats[row] = make_uint2(mb2, __float_as_uint(inv)); }
}

__global__ void __cluster_dims__(2, 1, 1) __launch_bounds__(384, 1)
fused_kernel(const __grid_constant__ CUtensorMap tmC, const __grid_constant__ CUtensorMap tmWk, const __grid_constant__ CUtensorMap tmWv,
             const __grid_constant__ CUtensorMap tmWq, const __grid_constant__ CUtensorMap tmWo,
             const __grid_constant__ CUtensorMap tmG, const __grid_constant__ CUtensorMap tmU, const __grid_constant__ CUtensorMap tmD, const Params P) {
    extern __shared__ __align__(1024) unsigned char smem_raw[];
    const uint32_t ring = smem_u32(smem_raw);
    const uint32_t misc = ring + RING_BYTES;
    const int tid = threadIdx.x;
    const int rank = blockIdx.x & 1;
    uint32_t smid; asm("mov.u32 %0, %%smid;" : "=r"(smid));
    const int tpc = smid >> 1;
    const int mc = tpc < 32 ? (tpc & 7) * 8 + (tpc >> 3) : tpc < 60 ? (1 + (tpc - 32) % 7) * 8 + 4 + (tpc - 32) / 7 : tpc < 64 ? tpc - 56 : tpc;
    const int cta = mc * 2 + rank;
    if (mc >= 64) { aux_cta(&tmG, &tmU, &tmD, smem_raw, cta - 128); return; }
    PROF_DECL(cta)
    PROF_GT(0); PROF_EV(1);
    const int team = mc >> 2, k = mc & 3;
    const int u3 = (mc >> 4) * 2 + (team & 1), s3 = k, kap = (mc >> 3) & 1;
    const int partner = cta ^ 16;

    if (tid >= 128) {
        const int i = tid - 128;
        asm volatile("prefetch.global.L2 [%0];" ::"l"((rank ? P.wv : P.wk) + (size_t)(k * 128 + (i >> 1)) * 4096 + team * 256 + (i & 1) * 64));
        if (i < 32) asm volatile("prefetch.global.L2 [%0];" ::"l"(P.c + (size_t)((12 + k) * 128 + (team * 2 + rank) * 4) * DC + i * 64));
    }
    if (tid == 0) {
#pragma unroll
        for (int i = 0; i < NSLOT; i++) mbar_init(misc + BAR_FULL + 8 * i, 1);
#pragma unroll
        for (int i = 0; i < E0; i++) mbar_arrive(misc + BAR_FULL + 8 * i);
        asm volatile("fence.mbarrier_init.release.cluster;" ::: "memory");
        const CUtensorMap* tw = rank ? &tmWv : &tmWk;
        mbar_expect_tx(misc + BAR_FULL + 8 * slot_of(0), SLOT_BYTES);
        tma2d(ring + slot_of(0) * SLOT_BYTES, tw, team * 256, 0, misc + BAR_FULL + 8 * slot_of(0), policy(HM & 1));
        tma2d(ring + slot_of(0) * SLOT_BYTES + 16384, tw, team * 256 + 64, 0, misc + BAR_FULL + 8 * slot_of(0), policy(HM & 1));
    }
    if (tid == 32) {
        asm volatile("prefetch.tensormap [%0];" ::"l"(&tmC) : "memory");
#pragma unroll
        for (int i = 0; i < NSLOT; i++) mbar_init(misc + BAR_EMPTY + 8 * i, 16);
#pragma unroll
        for (int i = 0; i < E0; i++) mbar_arrive_cluster(misc + BAR_EMPTY + 8 * i, 16);
        asm volatile("fence.mbarrier_init.release.cluster;" ::: "memory");
    }
    if (tid == 64) {
#pragma unroll
        for (int i = 0; i < NST3; i++) { mbar_init(misc + BAR_FULL3 + 8 * i, 1); mbar_init(misc + BAR_EMPTY3 + 8 * i, 16); }
#pragma unroll
        for (int i = 0; i < 4; i++) mbar_init(misc + BAR_LN + 8 * i, 2);
        mbar_init(misc + BAR_PROG, 1); mbar_init(misc + BAR_PROG + 8, 1); mbar_init(misc + BAR_PROG + 16, 1);
        asm volatile("fence.mbarrier_init.release.cluster;" ::: "memory");
    }
    if (tid == 96) {
#pragma unroll
        for (int i = 0; i < 34; i++) mbar_init(misc + BAR_DEP + 8 * i, 1);
    }
    if (tid == 128) {
#pragma unroll
        for (int i = 0; i < 32; i++) mbar_init(misc + BAR_EV + 8 * i, 4);
    }
    __syncthreads();
    asm volatile("barrier.cluster.arrive.relaxed.aligned;\nbarrier.cluster.wait.aligned;" ::: "memory");
    PROF_EV(5);
    const int wg = __shfl_sync(0xffffffffu, tid >> 7, 0);

    if (wg == 0) {
        asm volatile("setmaxnreg.dec.sync.aligned.u32 40;");
        const int warp = __shfl_sync(0xffffffffu, tid >> 5, 0), lane = tid & 31;
        if (warp == 0) {
            const bool lead = elect_one();
            Cur c = cur_at(1);
            uint32_t dst, fb;
            auto acquire = [&]() {
                mbar_wait(misc + BAR_EMPTY + 8 * c.slot, c.ph ^ 1);
                fb = misc + BAR_FULL + 8 * c.slot; dst = ring + c.slot * SLOT_BYTES;
                if (lead) mbar_expect_tx(fb, SLOT_BYTES);
                c.adv();
            };
            auto load_w = [&](const CUtensorMap* tm, int col, int row, bool stream) {
                acquire();
                if (lead) { tma2d(dst, tm, col, row, fb, policy(stream)); tma2d(dst + 16384, tm, col + 64, row, fb, policy(stream)); }
            };
            auto load_half = [&](const unsigned char* src, bool stream) {
                acquire();
                if (lead) bulk_load_mc(dst + rank * 16384, src, 16384, fb, policy(stream));
            };
            auto staging = [&]() {
                mbar_wait(misc + BAR_EMPTY + 8 * c.slot, c.ph ^ 1);
                if (lead) mbar_arrive(misc + BAR_FULL + 8 * c.slot);
                c.adv();
            };
            auto dep_wait = [&](int d) { mbar_wait(misc + BAR_DEP + 8 * d, 0); fence_async_global(); };
            auto op_prefetch = [&](int i) {
                const int head = op_head(i, kap);
                l2_prefetch(reinterpret_cast<const unsigned char*>(P.wo) + head * 163840 + (u3 * 8 + s3 * 2 + rank) * 2560, 2560);
                if (i < 8) l2_prefetch(g_Q + (size_t)(head * 32 + 4 * u3 + 2 * rank) * 16384 + s3 * 8192, 8192);
            };
            const CUtensorMap* tw = rank ? &tmWv : &tmWk;
            const unsigned char* Kh = g_K + (size_t)team * 32 * 16384 + rank * 16384;
            const unsigned char* Vh = g_V + (size_t)team * 32 * 16384 + rank * 16384;
#pragma unroll 1
            for (int v = 0; v < 2; v++) {
                const int h = 2 * team + v;
#pragma unroll 1
                for (int i = 0; i < 16; i++) {
                    if (i < 4 && (v | i)) load_w(tw, h * 128, i * 128, HM & 1);
                    if (v && (i & 7) == 3) dep_wait(D_WAR + (i >> 3));
                    acquire();
                    if (lead) tma2d_mc(dst + rank * 16384, &tmC, (i & 3) * 128 + rank * 64, (12 - (i & 12) + k) * 128, fb, policy(HM & 2));
                    if (v && i == 2 && lead) mbar_arrive(misc + BAR_PROG + 8);
                }
                if (v == 0) {
                    const int cq = (h + rank) * 128;
                    load_w(&tmWq, cq, 0, HM & 1); load_w(&tmWq, cq, 128, HM & 1); load_w(&tmWq, cq, 256, HM & 1);
#pragma unroll 1
                    for (int t = 0; t < 4; t++) {
                        const unsigned char* xt = g_xn + (q_tile(k, t) * 10 + rank) * 16384;
                        dep_wait(D_LN + t);
                        if (t == 3 && lead) l2_prefetch((rank ? Vh - 16384 : Kh) + (13 - 2 * k) * 32768, 3 * 32768);
#pragma unroll 1
                        for (int ch = 0; ch < 5; ch++) {
                            load_half(xt + ch * 32768, HM & 4);
                            if (t == 0 && ch == 0) load_w(&tmWq, cq, 384, HM & 1);
                        }
                        load_w(&tmWq, cq, 512, (HM & 1) && t == 3);
                    }
                }
                int togo = v ? PF_START : 11;
#pragma unroll 1
                for (int r = 0; r < 2; r++) {
                    const int p = r ? k : 7 - k, n = 2 * p + 1;
                    if (v == 0) dep_wait(D_Q + r);
                    acquire();
                    if (lead) {
                        const int g0 = r ? rank : 3 - rank;
                        bulk_load(dst, g_Q + (size_t)(h * 32 + 4 * p + g0) * 16384, 16384, fb, policy(HM & 8));
                        bulk_load(dst + 16384, g_Q + (size_t)(h * 32 + 4 * p + 3 - g0) * 16384, 16384, fb, policy(HM & 8));
                    }
                    if (v && r == 0) dep_wait(D_KV + 4 + (k >> 1));
                    load_half(Kh + n * 32768, HM & 16);
                    if (r) { load_half(Vh, HM & 16); staging(); }
#pragma unroll 1
                    for (int j = n - 1; j >= 0; j--) {
                        if (v && r == 0 && (j & 3) == 3) dep_wait(D_KV + 7 - (j >> 2));
                        load_half(Kh + j * 32768, HM & 16); load_half(Vh + (j + 1) * 32768, HM & 16);
                        if (v == 0 && r == 0 && j == 3 && lead) mbar_arrive(misc + BAR_PROG);
                        --togo;
                        if (v == 0 && togo == 0 && lead) {
                            tma2d_prefetch(tw, h * 128 + 128, k * 128); tma2d_prefetch(tw, h * 128 + 192, k * 128);
                            l2_prefetch(reinterpret_cast<const unsigned char*>(P.c) + (size_t)cta * 16384, 16384);
                        }
                        if (v && togo <= 0 && togo > -OP_PF && lead) op_prefetch(-togo);
                    }
                }
                load_half(Vh, HM & 16);
                staging();
                if (v == 0 && lead) l2_prefetch(g_Q + (size_t)((h + 1) * 32 + 8 * k + 4 * rank) * 16384, 65536);
            }
            mbar_wait(misc + BAR_EMPTY + 8 * c.slot, c.ph ^ 1); c.adv();
            int st = 0; uint32_t ph3 = 0;
#pragma unroll 1
            for (int i = 0; i < 32; i++) {
                const int head = op_head(i >> 1, kap);
                if ((i & 1) == 0) dep_wait(D_CTX + (i >> 1));
                if (i < NST3) { mbar_wait(misc + BAR_EMPTY + 8 * c.slot, c.ph ^ 1); c.adv(); }
                else mbar_wait(misc + BAR_EMPTY3 + 8 * st, ph3 ^ 1);
                fb = misc + BAR_FULL3 + 8 * st; dst = ring + st * ST3_BYTES;
                if (i == LATE_AT && lead) mbar_arrive(misc + BAR_PROG + 16);
                if (lead) {
                    mbar_expect_tx(fb, ST3_BYTES);
                    const unsigned char* src = g_Q + (size_t)(head * 32 + 4 * u3 + 2 * rank) * 16384 + (i & 1) * 8192;
                    bulk_load(dst, src, 8192, fb, policy(HM & 32));
                    bulk_load(dst + 8192, src + 16384, 8192, fb, policy(HM & 32));
                    tma3d_mc(dst + 16384 + rank * 10240, &tmWo, 0, head * 128 + (i & 1) * 64 + rank * 32, 5 * s3, fb, policy(HM & 32));
                    if ((i & 1) && (i >> 1) + OP_PF < 16) op_prefetch((i >> 1) + OP_PF);
                }
                if (++st == NST3) { st = 0; ph3 ^= 1; }
            }
        } else if (warp == 3) {
            const unsigned ep1 = *reinterpret_cast<volatile unsigned*>(&g_epoch) + 1;
            if (lane == 0) {
                asm volatile("st.shared.u32 [%0], %1;" ::"r"(misc + MISC_EPOCH), "r"(ep1) : "memory");
                l2_prefetch(reinterpret_cast<const unsigned char*>(P.c) + (size_t)cta * 12288, 12288);
#pragma unroll 1
                for (int t = 0; t < 4; t++) {
                    if (t == 1) {
                        mbar_wait(misc + BAR_PF, 0);
                        l2_prefetch(reinterpret_cast<const unsigned char*>(P.wq) + (size_t)cta * 40960, 40960);
                    }
                    mbar_wait(misc + BAR_LN + 8 * t, 0);
                    flag_signal(flag_ptr(FL_LN + q_tile(cta >> 5, t)));
                    flag_wait(flag_ptr(FL_LN + q_tile(k, t)), ep1 * 32u);
                    mbar_arrive(misc + BAR_DEP + 8 * (D_LN + t));
                }
                mbar_wait(misc + BAR_EV + 8 * (16 + EV_KV + 3), 0);
                flag_wait(flag_ptr(FL_KV + team * 8), ep1 * 16u);
#pragma unroll 1
                for (int i = 0; i < 2; i++) {
                    mbar_wait(misc + BAR_EV + 8 * (16 + EV_Q + 1 + 2 * i), 0);
                    flag_wait(flag_ptr(FL_Q + team * 8 + (i ? k : 7 - k)), ep1 * 4u);
                    mbar_arrive(misc + BAR_DEP + 8 * (D_Q + i));
                }
#pragma unroll 1
                for (int i = 0; i < 2; i++) {
                    mbar_wait(misc + BAR_PROG + 8 * i, 0);
                    flag_signal(flag_ptr(FL_WAR + 2 * team + i));
                    flag_wait(flag_ptr(FL_WAR + 2 * team + i), ep1 * 8u);
                    mbar_arrive(misc + BAR_DEP + 8 * (D_WAR + i));
                }
#pragma unroll 1
                for (int i = 4; i < 8; i++) {
                    mbar_wait(misc + BAR_EV + 8 * (16 + EV_KV + i), 0);
                    flag_wait(flag_ptr(FL_KV + team * 8 + i), ep1 * 16u);
                    mbar_arrive(misc + BAR_DEP + 8 * (D_KV + i));
                }
                flag_wait(flag_ptr(FL_MOE_DONE), ep1);
                int4 s0 = __ldcg(reinterpret_cast<const int4*>(g_sel)), s1 = __ldcg(reinterpret_cast<const int4*>(g_sel) + 1);
                asm volatile("st.shared.v4.u32 [%0], {%1,%2,%3,%4};" ::"r"(misc + MISC_SEL), "r"(s0.x), "r"(s0.y), "r"(s0.z), "r"(s0.w) : "memory");
                asm volatile("st.shared.v4.u32 [%0], {%1,%2,%3,%4};" ::"r"(misc + MISC_SEL + 16), "r"(s1.x), "r"(s1.y), "r"(s1.z), "r"(s1.w) : "memory");
                mbar_arrive(misc + BAR_SEL);
            }
            __syncwarp();
            const unsigned* cf = flag_ptr(FL_CTX + op_head(lane & 15, kap) * 8 + u3);
#pragma unroll 1
            for (int half = 0; half < 2; half++) {
                if (half) mbar_wait(misc + BAR_EV + 8 * (EV_CTX + 3), 0);
                bool done = (lane >> 3) != half;
                for (int spin = 0; spin < 4000000; spin++) {
                    if (!done) {
                        unsigned v;
                        asm volatile("ld.acquire.gpu.global.u32 %0, [%1];" : "=r"(v) : "l"(cf) : "memory");
                        if ((int)(v - ep1 * 4u) >= 0) { mbar_arrive(misc + BAR_DEP + 8 * (D_CTX + lane)); done = true; }
                    }
                    if (__all_sync(0xffffffffu, done)) break;
                    __nanosleep(64);
                }
            }
        } else {
            const int w = warp - 1;
            if (lane < 20) {
#pragma unroll
                for (int i = 0; i < 2; i++) {
                    const int ch = w * 40 + i * 20 + lane;
                    uint4 u = __ldg(reinterpret_cast<const uint4*>(P.wr) + ch);
                    asm volatile("st.shared.v4.b32 [%0], {%1,%2,%3,%4};" ::"r"(misc + MISC_WR + 16 * ch), "r"(u.x), "r"(u.y), "r"(u.z), "r"(u.w) : "memory");
                }
            }
            const int rsub = (cta & 31) * 4 + 2 * w;
            if (lane < 3) l2_prefetch(P.x + (size_t)(q_tile(cta >> 5, lane + 1) * 128 + rsub) * DM, 2 * DM * 2);
            bar_sync(3, 64);
#pragma unroll 1
            for (int t = 0; t < 4; t++) {
                ln_rows(P, q_tile(cta >> 5, t) * 128 + rsub, lane, misc + MISC_WR);
                __syncwarp();
                if (lane == 0) mbar_arrive(misc + BAR_LN + 8 * t);
            }
            if (lane == 0) {
                const uint32_t eb = misc + BAR_EV + w * 128;
#pragma unroll 1
                for (int v = 0; v < 2; v++) {
#pragma unroll 1
                    for (int i = 0; i < (v ? 4 : 3); i++) {
                        mbar_wait(eb + 8 * (v ? EV_KV + 4 + i : i ? EV_Q + 2 * i - 1 : EV_KV + 3), 0);
                        flag_signal(flag_ptr(v ? FL_KV + team * 8 + 4 + i : i ? FL_Q + team * 8 + (i == 1 ? 7 - k : k) : FL_KV + team * 8));
                    }
#pragma unroll 1
                    for (int r = 0; r < 2; r++) {
                        const int p = r ? k : 7 - k;
                        const uint32_t slot = ((v ? E_ATT1 : E_ATT0) + (r ? 39 : 4 * p + 7) + E0) % NSLOT;
                        const int grp = (r == w) ? 3 - rank : rank;
                        mbar_wait(eb + 8 * (EV_CTX + 2 * v + r), 0);
                        asm volatile("cp.async.bulk.global.shared::cta.bulk_group.L2::cache_hint [%0], [%1], 16384, %2;"
                                     ::"l"(g_Q + (size_t)((2 * team + v) * 32 + 4 * p + grp) * 16384), "r"(ring + slot * SLOT_BYTES + w * 16384),
                                       "l"(policy((HM & 256) && v == 0)) : "memory");
                        asm volatile("cp.async.bulk.commit_group;" ::: "memory");
                        asm volatile("cp.async.bulk.wait_group.read 0;" ::: "memory");
                        mbar_arrive_cluster(mapa(misc + BAR_EMPTY + 8 * slot, 0), 4);
                        mbar_arrive_cluster(mapa(misc + BAR_EMPTY + 8 * slot, 1), 4);
                        asm volatile("cp.async.bulk.wait_group 0;" ::: "memory");
                        fence_async_global();
                        flag_signal(flag_ptr(FL_CTX + (2 * team + v) * 8 + p));
                    }
                }
            }
            __syncwarp();
            mbar_wait(misc + BAR_PROG + 16, 0);
            const int row = (2 * u3 + rank) * 128 + 64 * w + perm32(16 * (lane >> 3) + 8 * kap + (lane & 7));
#pragma unroll
            for (int i = 0; i < 10; i++) asm volatile("prefetch.global.L2 [%0];" ::"l"(P.x + (size_t)row * DM + 160 * s3 + 16 * i));
            asm volatile("prefetch.global.L2 [%0];" ::"l"(g_stats + row));
        }
    } else {
        asm volatile("setmaxnreg.inc.sync.aligned.u32 232;");
        Ctx c;
        c.ring = ring; c.misc = misc; c.w = wg - 1; c.warp = (tid >> 5) & 3; c.lane = tid & 31;
        c.rel = mapa(misc, tid & 1);
        const int w = c.w;
        if (w == 1) bar_arrive(1, 256);
        Cur cur = cur_at(0);
        float o[64], inv[2];
#pragma unroll 1
        for (int v = 0; v < 2; v++) {
        {
            uint32_t wf[128];
            float acc[64];
#pragma unroll
            for (int i = 32; i < 128; i++) wf[i] = 0u;
            Cur cw = cur;
            int wstep = 2;
            auto load_wchunk = [&](auto CH) {
                constexpr int ch = decltype(CH)::value;
                mbar_wait_hot(misc + BAR_FULL + 8 * cw.slot, cw.ph);
                const uint32_t z = load_afrag<8, 32 * ch>(wf, ring + cw.slot * SLOT_BYTES + w * 16384, c);
                release(c, BAR_EMPTY + 8 * cw.slot + z, 1);
                cw.adv();
                if (wstep == 2 || ch == 2) cw.adv();
            };
            load_wchunk(IC<0>{});
            cur.adv();
            int nload = 1;
            PROF_EV(2); PROF_GT(60);
#pragma unroll 1
            for (int t = 0; t < (v ? 4 : 8); t++) {
                uint32_t last = 0;
                token_wait(w);
                PROF_EV(t < 4 ? 10 : 20);
                undef_regs(acc);
                auto chunk = [&](auto CH) {
                    constexpr int ch = decltype(CH)::value;
                    mbar_wait_hot(misc + BAR_FULL + 8 * cur.slot, cur.ph);
                    if (t == 0 || t == 4) { PROF_EV(12 + ch); }
                    uint64_t d = mkdesc(ring + cur.slot * SLOT_BYTES, 16, 1024, 1);
                    wg_fence();
#pragma unroll
                    for (int ks = 0; ks < 8; ks++)
                        wgmma_rs_n128_ta0_tb0(acc, wf[32 * ch + 4 * ks], wf[32 * ch + 4 * ks + 1], wf[32 * ch + 4 * ks + 2], wf[32 * ch + 4 * ks + 3],
                                              d + (ks >> 2) * 1024 + (ks & 3) * 2, (ch | ks) != 0);
                    wg_commit();
                    const bool swap = (ch < 2 && t == 0) || (ch == 3 && t < 4);
                    if (swap) token_pass(w);
                    if constexpr (ch < 3) { if (nload == ch + 1) { load_wchunk(IC<ch + 1>{}); nload++; } }
                    if (ch > 0) { wg_wait<1>(); release(c, BAR_EMPTY + 8 * last, 1); }
                    last = cur.slot;
                    cur.adv();
                    if ((ch < 3 && t == 0) || (ch == 0 && t == 4)) cur.adv();
                    if (ch < 2 && swap) token_wait(w);
                };
                chunk(IC<0>{}); chunk(IC<1>{}); chunk(IC<2>{}); chunk(IC<3>{});
                if (t < 4) {
                    wg_wait<0>();
                    release(c, BAR_EMPTY + 8 * last, 1);
                } else {
                    Cur cx = cur; cur.adv();
                    mbar_wait_hot(misc + BAR_FULL + 8 * cx.slot, cx.ph);
                    mbar_wait_hot(misc + BAR_FULL + 8 * cur.slot, cur.ph);
                    uint64_t db = mkdesc(ring + cx.slot * SLOT_BYTES, 16, 1024, 1);
                    uint64_t da = mkdesc(ring + cur.slot * SLOT_BYTES + w * 16384, 16384, 1024, 1);
                    wg_fence();
#pragma unroll
                    for (int ks = 0; ks < 8; ks++) wgmma_ss_n128_ta1_tb0(acc, da + 128 * ks, db + (ks >> 2) * 1024 + (ks & 3) * 2, 1);
                    wg_commit();
                    token_pass(w);
                    wg_wait<1>(); release(c, BAR_EMPTY + 8 * last, 1);
                    wg_wait<0>(); release(c, BAR_EMPTY + 8 * cx.slot, 1); release(c, BAR_EMPTY + 8 * cur.slot, 1);
                    cur.adv();
                    fence_regs(acc);
#pragma unroll
                    for (int i = 0; i < 64; i++) acc[i] *= SM_SCALE;
                }
                PROF_EV(t < 4 ? 11 : 21);
                fence_regs(acc);
                if (t == 0 && v == 0 && tid == 128) mbar_arrive(misc + BAR_PF);
                const bool wswitch = t == 3 && v == 0;
                if (wswitch) {
                    cw = cur; wstep = 1; nload = 0;
                    cur.adv(); cur.adv(); cur.adv();
                    if (w) { load_wchunk(IC<0>{}); load_wchunk(IC<1>{}); load_wchunk(IC<2>{}); nload = 3; }
                }
                unsigned char* dst = t < 4 ? (rank ? g_V : g_K) + (size_t)(team * 32 + 24 + 2 * k - 8 * t) * 16384
                                           : g_Q + (size_t)((2 * team + rank) * 32 + q_tile(k, t & 3) * 2) * 16384;
                store_proj(acc, dst, c, policy(((HM & 64) && t >= 4 && rank) || ((HM & 128) && t >= 6)));
                signal_event(c, t < 4 ? EV_KV + 4 * v + t : EV_Q + t - 4);
                if (wswitch) {
                    if (w) { load_wchunk(IC<3>{}); nload = 4; }
                    else { load_wchunk(IC<0>{}); load_wchunk(IC<1>{}); nload = 2; }
                }
                if (t == 3) { PROF_EV(61); PROF_GT(62); }
            }
        }
        PROF_EV(63); PROF_GT(64);
        {
            uint32_t q[32], p[32];
            float m[2], l[2];
#pragma unroll
            for (int i = 0; i < 64; i++) o[i] = 0.f;
#pragma unroll
            for (int i = 0; i < 32; i++) p[i] = 0u;
            m[0] = m[1] = inv[0] = inv[1] = 0.f;
            l[0] = l[1] = 1.f;
            int gen = 0;
            Cur ck = cur, cv = cur, cq, ce, cen;
            int r = 0, left;
            int first = 1, half, heavy;
            int pv_acc = 0, pv_half = 1; uint32_t pv_cnt = 0;
            int pending = 0;
            Cur nck, ncv;
            auto next_task = [&](int rr) {
                heavy = 1 ^ (rr & 1) ^ w;
                half = 1 ^ heavy ^ rank;
                left = 2 * (rr ? k : 7 - k) + 1 + heavy;
                cq = cur; cur.adv();
                nck = cur; cur.adv();
                if (rr > 0) { ncv = cur; cur.adv(); cen = cur; cur.adv(); }
                if (!heavy) { nck = cur; cur.adv(); cur.adv(); }
                if (rr == 0) { ncv = nck; cen = nck; }
            };
            next_task(0);
            ce = cen;
            mbar_wait(misc + BAR_FULL + 8 * cq.slot, cq.ph);
            load_afrag<8, 0>(q, ring + cq.slot * SLOT_BYTES + w * 16384, c);
            uint32_t k_cnt = 1; int last = 0, was_first = 0, publish = 0;
            auto window = [&]() {
                publish = pending;
                if (pending) stage_ctx(o, inv, ce, c);
                pending = 0;
                k_cnt = 1;
                was_first = first;
                if (first) {
                    release(c, BAR_EMPTY + 8 * cq.slot, 1);
                    pending = r ? EV_CTX + 2 * v : 0; ce = cen;
                    k_cnt = 1 + heavy;
                }
                last = --left == 0 ? 1 : 0;
                first = last;
                if (!last) { nck = cur; cur.adv(); ncv = cur; cur.adv(); half = 0; }
                else if (++r < 2) next_task(r);
                mbar_wait_hot(misc + BAR_FULL + 8 * cv.slot, cv.ph);
            };
            auto next_q = [&]() {
                if (last && r < 2) {
                    mbar_wait_hot(misc + BAR_FULL + 8 * cq.slot, cq.ph);
                    load_afrag<8, 0>(q, ring + cq.slot * SLOT_BYTES + w * 16384, c);
                }
            };
#pragma unroll 1
            while (r < 2) {
                ck = nck; cv = ncv;
                mbar_wait_hot(misc + BAR_FULL + 8 * ck.slot, ck.ph);
                if (half) {
                    token_wait(w);
                    PROF_EV(30);
                    float s[32];
                    undef_regs(s);
                    issue_qk_half(s, q, ring + ck.slot * SLOT_BYTES);
                    window();
                    issue_pv(o, p, ring + cv.slot * SLOT_BYTES, pv_acc, pv_half);
                    token_pass(w);
                    if (publish) publish_ctx(publish, c);
                    wg_wait<1>();
                    PROF_EV(34);
                    fence_regs(s);
                    row_inv(l, inv);
                    mask_diag<0>(s, c);
                    gen = softmax_first<8>(s, m, l);
                    next_q();
                    wg_wait<0>();
                    fence_regs(o);
                    fence_regs(s);
                    release(c, BAR_EMPTY + 8 * ck.slot, k_cnt);
                    if (pv_cnt) release(c, BAR_EMPTY + 8 * cv.slot, pv_cnt);
#pragma unroll
                    for (int i = 0; i < 16; i++) p[i] = pack_bf16(s[2 * i], s[2 * i + 1]);
                    pv_acc = 0; pv_half = 1; pv_cnt = k_cnt;
                    continue;
                }
                float s[64];
                int redo;
#pragma unroll 1
                while (true) {
                    token_wait(w);
                    PROF_EV(first ? 30 : 31);
                    undef_regs(s);
                    issue_qk(s, q, ring + ck.slot * SLOT_BYTES);
                    const bool special = first > 0 || pv_acc == 0 || left == 1;
                    if (special) window();
                    else {
                        nck = cur; cur.adv(); ncv = cur; cur.adv();
                        --left;
                        mbar_wait_hot(misc + BAR_FULL + 8 * cv.slot, cv.ph);
                    }
                    issue_pv(o, p, ring + cv.slot * SLOT_BYTES, pv_acc, special && pv_half);
                    token_pass(w);
                    wg_wait<1>();
                    PROF_EV(33);
                    fence_regs(s);
                    float lo = 0.f;
                    if (special) {
                        if (publish) publish_ctx(publish, c);
                        if (was_first) {
                            row_inv(l, inv);
                            l[0] = l[1] = m[0] = m[1] = 0.f;
                            gen = 0;
                            lo = 1.0f / SAFE_SUM;
                            mask_diag<8>(s, c);
                        }
                    }
                    constexpr int JB = 11;
                    float l0 = l[0], l1 = l[1];
                    if (!gen) {
#pragma unroll
                        for (int j = 0; j < JB; j++) {
#pragma unroll
                            for (int e = 0; e < 4; e++) ex2v(s[4 * j + e]);
                            if (j < JB - 1) { l0 += s[4 * j] + s[4 * j + 1]; l1 += s[4 * j + 2] + s[4 * j + 3]; }
                        }
                    }
                    wg_wait<0>();
                    fence_regs(o);
                    redo = 0;
                    if (gen) break;
#pragma unroll
                    for (int j = JB - 1; j < 16; j++) {
                        if (j >= JB) {
#pragma unroll
                            for (int e = 0; e < 4; e++) ex2v(s[4 * j + e]);
                        }
                        l0 += s[4 * j] + s[4 * j + 1]; l1 += s[4 * j + 2] + s[4 * j + 3];
                    }
#pragma unroll
                    for (int i = 0; i < 32; i++) p[i] = pack_bf16(s[2 * i], s[2 * i + 1]);
                    redo = 1;
                    if (__any_sync(0xffffffffu, !(l0 <= SAFE_SUM && l1 <= SAFE_SUM && l0 >= lo && l1 >= lo))) break;
                    l[0] = l0; l[1] = l1;
                    redo = 0;
                    if (last) break;
                    release(c, BAR_EMPTY + 8 * ck.slot, k_cnt);
                    if (pv_cnt) release(c, BAR_EMPTY + 8 * cv.slot, pv_cnt);
                    pv_acc = was_first ^ 1; pv_half = 0; pv_cnt = k_cnt;
                    ck = nck; cv = ncv;
                    mbar_wait_hot(misc + BAR_FULL + 8 * ck.slot, ck.ph);
                }
                if (gen | redo) {
                    if (redo) {
                        recompute_scores(s, q, ring + ck.slot * SLOT_BYTES, c);
                        if (was_first) { mask_diag<8>(s, c); m[0] = m[1] = -INFINITY; }
                    }
                    gen = 1;
                    float mx[2], alpha[2];
                    row_max<16>(s, mx);
#pragma unroll
                    for (int i = 0; i < 2; i++) {
                        mx[i] = fmaxf(mx[i], m[i]);
                        alpha[i] = was_first ? 1.0f : ex2(m[i] - mx[i]);
                        m[i] = mx[i];
                        l[i] *= alpha[i];
                    }
                    exp_sum<16, true>(s, m, l[0], l[1]);
#pragma unroll
                    for (int i = 0; i < 64; i++) o[i] *= alpha[(i >> 1) & 1];
#pragma unroll
                    for (int i = 0; i < 32; i++) p[i] = pack_bf16(s[2 * i], s[2 * i + 1]);
                }
                next_q();
                release(c, BAR_EMPTY + 8 * ck.slot, k_cnt);
                if (pv_cnt) release(c, BAR_EMPTY + 8 * cv.slot, pv_cnt);
                pv_acc = was_first ^ 1; pv_half = 0; pv_cnt = k_cnt;
            }
            if (pending) { stage_ctx(o, inv, ce, c); publish_ctx(pending, c); }
            mbar_wait(misc + BAR_FULL + 8 * cur.slot, cur.ph);
            token_wait(w);
            PROF_EV(32);
            issue_pv(o, p, ring + cur.slot * SLOT_BYTES, pv_acc, pv_half);
            if (w == 0 || v == 0) token_pass(w);
            row_inv(l, inv);
            wg_wait<0>();
            release(c, BAR_EMPTY + 8 * cur.slot, pv_cnt);
            fence_regs(o);
            cur.adv();
            if (v == 0) { stage_ctx(o, inv, cur, c); publish_ctx(EV_CTX + 1, c); cur.adv(); }
        }
        }
        {
            float acc[80];
            undef_regs(acc);
            int st = 0, prev = 0; uint32_t ph3 = 0;
            auto op_stage = [&](int i) {
                mbar_wait(misc + BAR_FULL3 + 8 * st, ph3);
                PROF_EV(44);
                uint32_t base = ring + st * ST3_BYTES;
                uint64_t da = mkdesc(base + w * 8192, 16, 1024, 1);
                uint64_t db = mkdesc(base + 16384, 2048, 512, 2);
                wg_fence();
#pragma unroll
                for (int k = 0; k < 4; k++) wgmma_ss_n160_ta0_tb1(acc, da + 2 * k, db + (k >> 1) * 640 + (k & 1) * 64, k ? 1 : i);
                wg_commit();
                if (i > 0) { wg_wait<1>(); if (i <= 32 - NST3) release(c, BAR_EMPTY3 + 8 * prev, 1); }
                prev = st;
                if (++st == NST3) { st = 0; ph3 ^= 1; }
            };
            PROF_EV(40); PROF_GT(65);
            op_stage(0);
            stage_ctx(o, inv, cur, c);
            publish_ctx(EV_CTX + 3, c);
#pragma unroll 1
            for (int i = 1; i < 12; i++) op_stage(i);
            mbar_wait(misc + BAR_SEL, 0);
            const uint32_t tag = lds32(misc + MISC_EPOCH) & 1;
            const int g = c.lane >> 2, t = c.lane & 3;
            const int row = (2 * u3 + rank) * 128 + 64 * w + perm32(16 * c.warp + 8 * kap + (((g & 3) << 1) | (g >> 2)));
            const int col = 160 * s3 + 8 * t;
            int sel = -1;
#pragma unroll
            for (int i = 0; i < TOPC; i++) if ((int)lds32(misc + MISC_SEL + 4 * i) == row) sel = i;
            const int t256 = tid - 128;
            uint4* sendp = g_part + (size_t)cta * 2560 + t256;
            if (c.lane >= 30) stg128(sendp + 9 * 256, tag ^ 1, tag ^ 1, tag ^ 1, tag ^ 1);
#pragma unroll 1
            for (int i = 12; i < 32; i++) op_stage(i);
            uint4 xv[5], bv[5];
#pragma unroll
            for (int i = 0; i < 5; i++) xv[i] = ldg128(P.x + (size_t)row * DM + col + 32 * i);
            uint2 stat;
            asm volatile("ld.global.cg.v2.b32 {%0,%1}, [%2];" : "=r"(stat.x), "=r"(stat.y) : "l"(g_stats + row) : "memory");
            wg_wait<0>();
            fence_regs(acc);
            PROF_EV(41); PROF_GT(66);
            float keep[40];
#pragma unroll
            for (int j = 0; j < 10; j++) {
                uint32_t v0 = __float_as_uint(kap ? acc[8 * j + 0] : acc[8 * j + 2]), v1 = __float_as_uint(kap ? acc[8 * j + 1] : acc[8 * j + 3]);
                uint32_t v2 = __float_as_uint(kap ? acc[8 * j + 4] : acc[8 * j + 6]), v3 = __float_as_uint(kap ? acc[8 * j + 5] : acc[8 * j + 7]);
                asm volatile("st.relaxed.gpu.global.v4.b32 [%0], {%1,%2,%3,%4};" ::"l"(sendp + j * 256),
                             "r"((v0 & ~1u) | tag), "r"((v1 & ~1u) | tag), "r"((v2 & ~1u) | tag), "r"((v3 & ~1u) | tag) : "memory");
                keep[4 * j + 0] = kap ? acc[8 * j + 2] : acc[8 * j + 0]; keep[4 * j + 1] = kap ? acc[8 * j + 3] : acc[8 * j + 1];
                keep[4 * j + 2] = kap ? acc[8 * j + 6] : acc[8 * j + 4]; keep[4 * j + 3] = kap ? acc[8 * j + 7] : acc[8 * j + 5];
            }
            PROF_GT(67);
#pragma unroll
            for (int i = 0; i < 5; i++) {
                uint32_t xx[4] = {xv[i].x, xv[i].y, xv[i].z, xv[i].w};
#pragma unroll
                for (int e = 0; e < 4; e++) {
                    asm("sub.rn.bf16x2 %0, %0, %1;" : "+r"(xx[e]) : "r"(stat.x));
                    xx[e] = pack_bf16(bf_lo(xx[e]) * __uint_as_float(stat.y), bf_hi(xx[e]) * __uint_as_float(stat.y));
                }
                bv[i] = make_uint4(xx[0], xx[1], xx[2], xx[3]);
            }
            if (sel >= 0) {
#pragma unroll
                for (int i = 0; i < 5; i++) bv[i] = ldg128(g_brow + sel * DM + col + 32 * i);
            }
            const uint4* recvp = g_part + (size_t)partner * 2560 + t256;
            uint4 rv[10];
            int spins = 0;
            while (POLL1) {
                uint32_t v;
                asm volatile("ld.relaxed.gpu.global.b32 %0, [%1];" : "=r"(v) : "l"(recvp + 9 * 256 + (31 - c.lane)) : "memory");
                if (__all_sync(0xffffffffu, (v & 1u) == tag) || ++spins > 2000000) break;
            }
            PROF_GT(68);
            while (true) {
                uint32_t bad = 0u;
#pragma unroll
                for (int j = 0; j < 10; j++) {
                    asm volatile("ld.relaxed.gpu.global.v4.b32 {%0,%1,%2,%3}, [%4];"
                                 : "=r"(rv[j].x), "=r"(rv[j].y), "=r"(rv[j].z), "=r"(rv[j].w) : "l"(recvp + j * 256) : "memory");
                }
#pragma unroll
                for (int j = 0; j < 10; j++) {
                    rv[j].x ^= tag; rv[j].y ^= tag; rv[j].z ^= tag; rv[j].w ^= tag;
                    bad |= rv[j].x | rv[j].y | rv[j].z | rv[j].w;
                }
                if (__all_sync(0xffffffffu, (bad & 1u) == 0) || ++spins > 2000000) break;
            }
            PROF_GT(69);
            uint32_t pk[20];
#pragma unroll
            for (int j = 0; j < 10; j++) {
                pk[2 * j] = pack_bf16(keep[4 * j] + __uint_as_float(rv[j].x), keep[4 * j + 1] + __uint_as_float(rv[j].y));
                pk[2 * j + 1] = pack_bf16(keep[4 * j + 2] + __uint_as_float(rv[j].z), keep[4 * j + 3] + __uint_as_float(rv[j].w));
            }
#pragma unroll
            for (int i = 0; i < 5; i++) {
                uint32_t a0 = pk[4 * i], a1 = pk[4 * i + 1], a2 = pk[4 * i + 2], a3 = pk[4 * i + 3];
                uint32_t x0 = (t & 1) ? a0 : a1, x1 = (t & 1) ? a2 : a3;
                x0 = __shfl_xor_sync(0xffffffffu, x0, 1); x1 = __shfl_xor_sync(0xffffffffu, x1, 1);
                if (t & 1) { a0 = x0; a2 = x1; } else { a1 = x0; a3 = x1; }
                x0 = (t & 2) ? a0 : a2; x1 = (t & 2) ? a1 : a3;
                x0 = __shfl_xor_sync(0xffffffffu, x0, 2); x1 = __shfl_xor_sync(0xffffffffu, x1, 2);
                if (t & 2) { a0 = x0; a1 = x1; } else { a2 = x0; a3 = x1; }
                uint32_t av[4] = {a0, a1, a2, a3};
                uint32_t xx[4] = {xv[i].x, xv[i].y, xv[i].z, xv[i].w}, bb[4] = {bv[i].x, bv[i].y, bv[i].z, bv[i].w};
                uint32_t ov[4];
#pragma unroll
                for (int e = 0; e < 4; e++) {
                    asm("add.rn.bf16x2 %0, %1, %2;" : "=r"(ov[e]) : "r"(xx[e]), "r"(av[e]));
                    asm("add.rn.bf16x2 %0, %0, %1;" : "+r"(ov[e]) : "r"(bb[e]));
                }
                stg128(P.out + (size_t)row * DM + col + 32 * i, ov[0], ov[1], ov[2], ov[3]);
            }
            PROF_EV(42); PROF_GT(43);
        }
    }
}

typedef CUresult (*EncodeFn)(CUtensorMap*, CUtensorMapDataType, cuuint32_t, void*, const cuuint64_t*, const cuuint64_t*, const cuuint32_t*,
                             const cuuint32_t*, CUtensorMapInterleave, CUtensorMapSwizzle, CUtensorMapL2promotion, CUtensorMapFloatOOBfill);

void make_map2d(EncodeFn enc, CUtensorMap* tm, const void* p, uint64_t cols, uint64_t rows) {
    cuuint64_t gd[2] = {cols, rows}, gs[1] = {cols * 2};
    cuuint32_t box[2] = {64, 128}, es[2] = {1, 1};
    enc(tm, CU_TENSOR_MAP_DATA_TYPE_BFLOAT16, 2, const_cast<void*>(p), gd, gs, box, es, CU_TENSOR_MAP_INTERLEAVE_NONE,
        CU_TENSOR_MAP_SWIZZLE_128B, CU_TENSOR_MAP_L2_PROMOTION_L2_128B, CU_TENSOR_MAP_FLOAT_OOB_FILL_NONE);
}

void make_map3d(EncodeFn enc, CUtensorMap* tm, const void* p, uint64_t cols, uint64_t rows, uint32_t bw, uint32_t nb) {
    cuuint64_t gd[3] = {bw, rows, cols / bw}, gs[2] = {cols * 2, bw * 2};
    cuuint32_t box[3] = {bw, 32, nb}, es[3] = {1, 1, 1};
    enc(tm, CU_TENSOR_MAP_DATA_TYPE_BFLOAT16, 3, const_cast<void*>(p), gd, gs, box, es, CU_TENSOR_MAP_INTERLEAVE_NONE,
        bw == 64 ? CU_TENSOR_MAP_SWIZZLE_128B : CU_TENSOR_MAP_SWIZZLE_64B, CU_TENSOR_MAP_L2_PROMOTION_L2_128B, CU_TENSOR_MAP_FLOAT_OOB_FILL_NONE);
}

}

extern "C" void kernel_launch(void* const* d_in, const int* in_sizes, int n_in, void* d_out, int out_size) {
    (void)in_sizes; (void)n_in; (void)out_size;
    static EncodeFn enc = nullptr;
    if (!enc) {
        void* fn = nullptr;
        cudaDriverEntryPointQueryResult qr;
        cudaGetDriverEntryPoint("cuTensorMapEncodeTiled", &fn, cudaEnableDefault, &qr);
        enc = (EncodeFn)fn;
        cudaFuncSetAttribute(fused_kernel, cudaFuncAttributeMaxDynamicSharedMemorySize, SMEM_BYTES);
    }
    CUtensorMap tmC, tmWk, tmWv, tmWq, tmWo, tmG, tmU, tmD;
    make_map2d(enc, &tmC, d_in[1], DC, SEQ);
    make_map2d(enc, &tmWq, d_in[2], 4096, DM);
    make_map2d(enc, &tmWk, d_in[3], 4096, DC);
    make_map2d(enc, &tmWv, d_in[4], 4096, DC);
    make_map3d(enc, &tmWo, d_in[5], DM, 4096, 32, 5);
    make_map3d(enc, &tmG, d_in[8], FF, DM, 64, 7);
    make_map3d(enc, &tmU, d_in[9], FF, DM, 64, 7);
    make_map3d(enc, &tmD, d_in[10], DM, FF, 64, 10);
    Params P;
    P.x = (const __nv_bfloat16*)d_in[0];
    P.c = (const __nv_bfloat16*)d_in[1];
    P.wq = (const __nv_bfloat16*)d_in[2];
    P.wk = (const __nv_bfloat16*)d_in[3];
    P.wv = (const __nv_bfloat16*)d_in[4];
    P.wo = (const __nv_bfloat16*)d_in[5];
    P.wr = (const __nv_bfloat16*)d_in[7];
    P.out = (__nv_bfloat16*)d_out;
    fused_kernel<<<132, 384, SMEM_BYTES>>>(tmC, tmWk, tmWv, tmWq, tmWo, tmG, tmU, tmD, P);
}
```

```cpp
#include <cuda_runtime.h>
#include <cuda_bf16.h>
#include <cuda.h>
#include <stdint.h>

#define HM 960
#define POLL1 1
#define OP_PF 8
#define PF_START 9
#define LATE_AT 18
#define MAP 2
namespace {

constexpr int SEQ = 2048, NH = 32, DM = 640, DC = 512, FF = 1728, TOPC = 8;
constexpr int NSLOT = 7, SLOT_BYTES = 32768;
constexpr int NST3 = 6, ST3_BYTES = 36864;
constexpr int RING_BYTES = NSLOT * SLOT_BYTES;
constexpr int SMEM_BYTES = RING_BYTES + 3072;

constexpr int BAR_FULL = 96  , BAR_FULL3 = 152  , BAR_DEP = 200  , BAR_PF = 456, BAR_SEL = 464,
              BAR_LN = 472  , BAR_EV = 504  , BAR_EMPTY = 760  , BAR_EMPTY3 = 816  ,
              BAR_PROG = 864  , MISC_EPOCH = 896, MISC_SEL = 912, MISC_WR = 1024  ;
constexpr int D_LN = 0  , D_KV = 4  , D_Q = 12  , D_WAR = 14  , D_CTX = 16  ;
constexpr int EV_KV = 0  , EV_Q = 8  , EV_CTX = 12  ;

constexpr int FL_MOE_CNT = 0, FL_MOE_DONE = 1, FL_LN = 16  , FL_KV = 32  , FL_Q = 160  , FL_CTX = 416  , FL_WAR = 672  , FL_TOTAL = 704;

__device__ __align__(1024) unsigned char g_K[16 * 32 * 16384];
__device__ __align__(1024) unsigned char g_V[16 * 32 * 16384];
__device__ __align__(1024) unsigned char g_Q[NH * 32 * 16384];
__device__ __align__(1024) unsigned char g_xn[16 * 10 * 16384];
__device__ __align__(1024) uint4 g_part[128 * 10 * 256];
__device__ float g_router[SEQ];
__device__ uint2 g_stats[SEQ];
__device__ __align__(16) float g_moe_part[4 * TOPC * DM];
__device__ __align__(16) __nv_bfloat16 g_brow[TOPC * DM];
__device__ __align__(16) int g_sel[TOPC];
__device__ unsigned g_flags[FL_TOTAL * 8];
__device__ unsigned g_epoch;

struct Params {
    const __nv_bfloat16 *x, *c, *wr, *wq, *wk, *wv, *wo;
    __nv_bfloat16* out;
};

__device__ __forceinline__ uint32_t smem_u32(const void* p) { return (uint32_t)__cvta_generic_to_shared(p); }
__device__ __forceinline__ void mbar_init(uint32_t bar, int cnt) { asm volatile("mbarrier.init.shared::cta.b64 [%0], %1;" ::"r"(bar), "r"(cnt)); }
__device__ __forceinline__ void mbar_expect_tx(uint32_t bar, uint32_t bytes) {
    asm volatile("mbarrier.arrive.expect_tx.shared::cta.b64 _, [%0], %1;" ::"r"(bar), "r"(bytes) : "memory");
}
__device__ __forceinline__ void mbar_arrive(uint32_t bar) { asm volatile("mbarrier.arrive.shared::cta.b64 _, [%0];" ::"r"(bar) : "memory"); }
__device__ __forceinline__ void mbar_arrive_cluster(uint32_t cluster_addr, uint32_t cnt) {
    asm volatile("mbarrier.arrive.shared::cluster.b64 _, [%0], %1;" ::"r"(cluster_addr), "r"(cnt) : "memory");
}
__device__ __forceinline__ uint32_t mapa(uint32_t addr, uint32_t cta) {
    uint32_t r; asm("mapa.shared::cluster.u32 %0, %1, %2;" : "=r"(r) : "r"(addr), "r"(cta)); return r;
}
__device__ __forceinline__ void mbar_wait(uint32_t bar, uint32_t parity) {
    asm volatile(
        "{\n.reg .pred p;\n.reg .u32 n;\n"
        "mbarrier.try_wait.parity.shared::cta.b64 p, [%0], %1;\n"
        "@p bra DONE;\n"
        "mov.u32 n, 0;\n"
        "LAB_WAIT:\n"
        "mbarrier.try_wait.parity.shared::cta.b64 p, [%0], %1, 100000;\n"
        "@p bra DONE;\n"
        "add.u32 n, n, 1;\n"
        "setp.lt.u32 p, n, 200000;\n"
        "@p bra LAB_WAIT;\n"
        "trap;\n"
        "DONE:\n}\n" ::"r"(bar), "r"(parity) : "memory");
}
__device__ __forceinline__ void mbar_wait_hot(uint32_t bar, uint32_t parity) {
    asm volatile("{\n.reg .pred p;\nLAB_WAIT:\nmbarrier.try_wait.parity.shared::cta.b64 p, [%0], %1;\n@!p bra LAB_WAIT;\n}\n" ::"r"(bar), "r"(parity) : "memory");
}
__device__ __forceinline__ void flag_wait(const unsigned* flag, unsigned target) {
    asm volatile(
        "{\n.reg .pred p;\n.reg .u32 n, v;\n.reg .s32 d;\n"
        "mov.u32 n, 0;\n"
        "LAB_WAIT:\n"
        "ld.acquire.gpu.global.u32 v, [%0];\n"
        "sub.s32 d, v, %1;\n"
        "setp.ge.s32 p, d, 0;\n"
        "@p bra DONE;\n"
        "nanosleep.u32 40;\n"
        "add.u32 n, n, 1;\n"
        "setp.lt.u32 p, n, 3000000;\n"
        "@p bra LAB_WAIT;\n"
        "trap;\n"
        "DONE:\n}\n" ::"l"(flag), "r"(target) : "memory");
}
__device__ __forceinline__ void flag_signal(unsigned* flag) {
    asm volatile("red.release.gpu.global.add.u32 [%0], 1;" ::"l"(flag) : "memory");
}
__device__ __forceinline__ void fence_async_global() { asm volatile("fence.proxy.async.global;" ::: "memory"); }
__device__ __forceinline__ unsigned* flag_ptr(int idx) { return g_flags + idx * 8; }

__device__ __forceinline__ uint64_t policy_stream() {
    uint64_t p; asm("createpolicy.fractional.L2::evict_first.b64 %0, 1.0;" : "=l"(p)); return p;
}
__device__ __forceinline__ uint64_t policy_normal() { return 0x1000000000000000ull; }
__device__ __forceinline__ uint64_t policy(bool stream) { return stream ? policy_stream() : policy_normal(); }
__device__ __forceinline__ void bulk_load(uint32_t dst, const void* src, uint32_t bytes, uint32_t bar, uint64_t pol) {
    asm volatile("cp.async.bulk.shared::cluster.global.mbarrier::complete_tx::bytes.L2::cache_hint [%0], [%1], %2, [%3], %4;"
                 ::"r"(dst), "l"(src), "r"(bytes), "r"(bar), "l"(pol) : "memory");
}
__device__ __forceinline__ void bulk_load_mc(uint32_t dst, const void* src, uint32_t bytes, uint32_t bar, uint64_t pol) {
    asm volatile("cp.async.bulk.shared::cluster.global.mbarrier::complete_tx::bytes.multicast::cluster.L2::cache_hint [%0], [%1], %2, [%3], %4, %5;"
                 ::"r"(dst), "l"(src), "r"(bytes), "r"(bar), "h"((uint16_t)3), "l"(pol) : "memory");
}
__device__ __forceinline__ void tma2d(uint32_t dst, const CUtensorMap* tm, int c0, int c1, uint32_t bar, uint64_t pol) {
    asm volatile("cp.async.bulk.tensor.2d.shared::cluster.global.mbarrier::complete_tx::bytes.L2::cache_hint [%0], [%1, {%3, %4}], [%2], %5;"
                 ::"r"(dst), "l"(tm), "r"(bar), "r"(c0), "r"(c1), "l"(pol) : "memory");
}
__device__ __forceinline__ void tma2d_mc(uint32_t dst, const CUtensorMap* tm, int c0, int c1, uint32_t bar, uint64_t pol) {
    asm volatile("cp.async.bulk.tensor.2d.shared::cluster.global.mbarrier::complete_tx::bytes.multicast::cluster.L2::cache_hint [%0], [%1, {%3, %4}], [%2], %5, %6;"
                 ::"r"(dst), "l"(tm), "r"(bar), "r"(c0), "r"(c1), "h"((uint16_t)3), "l"(pol) : "memory");
}
__device__ __forceinline__ void tma3d_mc(uint32_t dst, const CUtensorMap* tm, int c0, int c1, int c2, uint32_t bar, uint64_t pol) {
    asm volatile("cp.async.bulk.tensor.3d.shared::cluster.global.mbarrier::complete_tx::bytes.multicast::cluster.L2::cache_hint [%0], [%1, {%3, %4, %5}], [%2], %6, %7;"
                 ::"r"(dst), "l"(tm), "r"(bar), "r"(c0), "r"(c1), "r"(c2), "h"((uint16_t)3), "l"(pol) : "memory");
}
__device__ __forceinline__ void tma3d(uint32_t dst, const CUtensorMap* tm, int c0, int c1, int c2, uint32_t bar) {
    asm volatile("cp.async.bulk.tensor.3d.shared::cluster.global.mbarrier::complete_tx::bytes.L2::cache_hint [%0], [%1, {%3, %4, %5}], [%2], %6;"
                 ::"r"(dst), "l"(tm), "r"(bar), "r"(c0), "r"(c1), "r"(c2), "l"(policy_stream()) : "memory");
}
__device__ __forceinline__ void tma2d_prefetch(const CUtensorMap* tm, int c0, int c1) {
    asm volatile("cp.async.bulk.prefetch.tensor.2d.L2.global [%0, {%1, %2}];" ::"l"(tm), "r"(c0), "r"(c1) : "memory");
}
__device__ __forceinline__ void tma3d_prefetch(const CUtensorMap* tm, int c0, int c1, int c2) {
    asm volatile("cp.async.bulk.prefetch.tensor.3d.L2.global [%0, {%1, %2, %3}];" ::"l"(tm), "r"(c0), "r"(c1), "r"(c2) : "memory");
}
__device__ __forceinline__ void l2_prefetch(const void* p, uint32_t bytes) {
    asm volatile("cp.async.bulk.prefetch.L2.global [%0], %1;" ::"l"(p), "r"(bytes) : "memory");
}
__device__ __forceinline__ bool elect_one() {
    uint32_t r; asm volatile("{\n.reg .pred p;\nelect.sync _|p, 0xffffffff;\nselp.u32 %0, 1, 0, p;\n}\n" : "=r"(r)); return r != 0;
}
__device__ __forceinline__ void wg_fence() { asm volatile("wgmma.fence.sync.aligned;" ::: "memory"); }
__device__ __forceinline__ void wg_commit() { asm volatile("wgmma.commit_group.sync.aligned;" ::: "memory"); }
template <int N> __device__ __forceinline__ void wg_wait() { asm volatile("wgmma.wait_group.sync.aligned %0;" ::"n"(N) : "memory"); }
__device__ __forceinline__ void bar_sync(int id, int n) { asm volatile("bar.sync %0, %1;" ::"r"(id), "r"(n) : "memory"); }
__device__ __forceinline__ void bar_arrive(int id, int n) { asm volatile("bar.arrive %0, %1;" ::"r"(id), "r"(n) : "memory"); }
__device__ __forceinline__ void token_wait(int w) {
    asm volatile("{\n.reg .pred p;\nsetp.eq.u32 p, %0, 0;\n@p bar.sync 1, 256;\n@!p bar.sync 2, 256;\n}\n" ::"r"(w) : "memory");
}
__device__ __forceinline__ void token_pass(int w) {
    asm volatile("{\n.reg .pred p;\nsetp.eq.u32 p, %0, 0;\n@p bar.arrive 2, 256;\n@!p bar.arrive 1, 256;\n}\n" ::"r"(w) : "memory");
}
template <int N> __device__ __forceinline__ void fence_regs(float (&a)[N]) {
#pragma unroll
    for (int i = 0; i < N; i++) asm volatile("" : "+f"(a[i])::"memory");
}
template <int N> __device__ __forceinline__ void undef_regs(float (&a)[N]) {
#pragma unroll
    for (int i = 0; i < N; i++) asm volatile("" : "=f"(a[i]));
}
__device__ __forceinline__ void ldsm4t(uint32_t& r0, uint32_t& r1, uint32_t& r2, uint32_t& r3, uint32_t addr) {
    asm volatile("ldmatrix.sync.aligned.m8n8.x4.trans.shared.b16 {%0,%1,%2,%3}, [%4];"
                 : "=r"(r0), "=r"(r1), "=r"(r2), "=r"(r3) : "r"(addr) : "memory");
}
__device__ __forceinline__ uint32_t pack_bf16(float lo, float hi) {
    uint32_t r; asm("cvt.rn.bf16x2.f32 %0, %1, %2;" : "=r"(r) : "f"(hi), "f"(lo)); return r;
}
__device__ __forceinline__ float bf_lo(uint32_t v) { return __uint_as_float(v << 16); }
__device__ __forceinline__ float bf_hi(uint32_t v) { return __uint_as_float(v & 0xffff0000u); }
__device__ __forceinline__ float bf_round(float v) { return __bfloat162float(__float2bfloat16_rn(v)); }
__device__ __forceinline__ float ex2(float v) { float r; asm("ex2.approx.ftz.f32 %0, %1;" : "=f"(r) : "f"(v)); return r; }
__device__ __forceinline__ void ex2v(float& v) { asm volatile("ex2.approx.ftz.f32 %0, %0;" : "+f"(v)); }
__device__ __forceinline__ float rcp_fast(float v) { float r; asm("rcp.approx.ftz.f32 %0, %1;" : "=f"(r) : "f"(v)); return r; }
__device__ __forceinline__ float sqrt_fast(float v) { float r; asm("sqrt.approx.ftz.f32 %0, %1;" : "=f"(r) : "f"(v)); return r; }
__device__ __forceinline__ void stg128(void* p, uint32_t a, uint32_t b, uint32_t c, uint32_t d) {
    asm volatile("st.global.v4.b32 [%0], {%1,%2,%3,%4};" ::"l"(p), "r"(a), "r"(b), "r"(c), "r"(d) : "memory");
}
__device__ __forceinline__ void stg128_hint(void* p, uint32_t a, uint32_t b, uint32_t c, uint32_t d, uint64_t pol) {
    asm volatile("st.global.L2::cache_hint.v4.b32 [%0], {%1,%2,%3,%4}, %5;" ::"l"(p), "r"(a), "r"(b), "r"(c), "r"(d), "l"(pol) : "memory");
}
__device__ __forceinline__ uint4 ldg128(const void* p) {
    uint4 v; asm volatile("ld.global.cg.v4.b32 {%0,%1,%2,%3}, [%4];" : "=r"(v.x), "=r"(v.y), "=r"(v.z), "=r"(v.w) : "l"(p) : "memory"); return v;
}
__device__ __forceinline__ uint64_t mkdesc(uint32_t addr, uint32_t lbo, uint32_t sbo, uint32_t swz) {
    uint32_t lo = ((addr & 0x3FFFF) >> 4) | ((lbo >> 4) << 16);
    uint32_t hi = (sbo >> 4) | (swz << 30);
    return ((uint64_t)hi << 32) | lo;
}
__device__ __forceinline__ int perm32(int v) { return (v & ~30) | ((v >> 2) & 6) | ((v << 2) & 24); }

__device__ __forceinline__ void wgmma_rs_n128_ta0_tb0(float (&d)[64], uint32_t a0, uint32_t a1, uint32_t a2, uint32_t a3, uint64_t descB, int scaleD) {
  asm volatile("{\n.reg .pred p;\nsetp.ne.b32 p, %69, 0;\n"
    "wgmma.mma_async.sync.aligned.m64n128k16.f32.bf16.bf16 "
    "{%0, %1, %2, %3, %4, %5, %6, %7, %8, %9, %10, %11, %12, %13, %14, %15, %16, %17, %18, %19, %20, %21, %22, %23, %24, %25, %26, %27, %28, %29, %30, %31, %32, %33, %34, %35, %36, %37, %38, %39, %40, %41, %42, %43, %44, %45, %46, %47, %48, %49, %50, %51, %52, %53, %54, %55, %56, %57, %58, %59, %60, %61, %62, %63}, "
    "{%64, %65, %66, %67}, %68, p, 1, 1, 0;\n}\n"
    : "+f"(d[0]), "+f"(d[1]), "+f"(d[2]), "+f"(d[3]), "+f"(d[4]), "+f"(d[5]), "+f"(d[6]), "+f"(d[7]), "+f"(d[8]), "+f"(d[9]), "+f"(d[10]), "+f"(d[11]), "+f"(d[12]), "+f"(d[13]), "+f"(d[14]), "+f"(d[15]), "+f"(d[16]), "+f"(d[17]), "+f"(d[18]), "+f"(d[19]), "+f"(d[20]), "+f"(d[21]), "+f"(d[22]), "+f"(d[23]), "+f"(d[24]), "+f"(d[25]), "+f"(d[26]), "+f"(d[27]), "+f"(d[28]), "+f"(d[29]), "+f"(d[30]), "+f"(d[31]), "+f"(d[32]), "+f"(d[33]), "+f"(d[34]), "+f"(d[35]), "+f"(d[36]), "+f"(d[37]), "+f"(d[38]), "+f"(d[39]), "+f"(d[40]), "+f"(d[41]), "+f"(d[42]), "+f"(d[43]), "+f"(d[44]), "+f"(d[45]), "+f"(d[46]), "+f"(d[47]), "+f"(d[48]), "+f"(d[49]), "+f"(d[50]), "+f"(d[51]), "+f"(d[52]), "+f"(d[53]), "+f"(d[54]), "+f"(d[55]), "+f"(d[56]), "+f"(d[57]), "+f"(d[58]), "+f"(d[59]), "+f"(d[60]), "+f"(d[61]), "+f"(d[62]), "+f"(d[63])
    : "r"(a0), "r"(a1), "r"(a2), "r"(a3), "l"(descB), "r"(scaleD));
}
__device__ __forceinline__ void wgmma_rs_n128_ta0_tb1(float (&d)[64], uint32_t a0, uint32_t a1, uint32_t a2, uint32_t a3, uint64_t descB, int scaleD) {
  asm volatile("{\n.reg .pred p;\nsetp.ne.b32 p, %69, 0;\n"
    "wgmma.mma_async.sync.aligned.m64n128k16.f32.bf16.bf16 "
    "{%0, %1, %2, %3, %4, %5, %6, %7, %8, %9, %10, %11, %12, %13, %14, %15, %16, %17, %18, %19, %20, %21, %22, %23, %24, %25, %26, %27, %28, %29, %30, %31, %32, %33, %34, %35, %36, %37, %38, %39, %40, %41, %42, %43, %44, %45, %46, %47, %48, %49, %50, %51, %52, %53, %54, %55, %56, %57, %58, %59, %60, %61, %62, %63}, "
    "{%64, %65, %66, %67}, %68, p, 1, 1, 1;\n}\n"
    : "+f"(d[0]), "+f"(d[1]), "+f"(d[2]), "+f"(d[3]), "+f"(d[4]), "+f"(d[5]), "+f"(d[6]), "+f"(d[7]), "+f"(d[8]), "+f"(d[9]), "+f"(d[10]), "+f"(d[11]), "+f"(d[12]), "+f"(d[13]), "+f"(d[14]), "+f"(d[15]), "+f"(d[16]), "+f"(d[17]), "+f"(d[18]), "+f"(d[19]), "+f"(d[20]), "+f"(d[21]), "+f"(d[22]), "+f"(d[23]), "+f"(d[24]), "+f"(d[25]), "+f"(d[26]), "+f"(d[27]), "+f"(d[28]), "+f"(d[29]), "+f"(d[30]), "+f"(d[31]), "+f"(d[32]), "+f"(d[33]), "+f"(d[34]), "+f"(d[35]), "+f"(d[36]), "+f"(d[37]), "+f"(d[38]), "+f"(d[39]), "+f"(d[40]), "+f"(d[41]), "+f"(d[42]), "+f"(d[43]), "+f"(d[44]), "+f"(d[45]), "+f"(d[46]), "+f"(d[47]), "+f"(d[48]), "+f"(d[49]), "+f"(d[50]), "+f"(d[51]), "+f"(d[52]), "+f"(d[53]), "+f"(d[54]), "+f"(d[55]), "+f"(d[56]), "+f"(d[57]), "+f"(d[58]), "+f"(d[59]), "+f"(d[60]), "+f"(d[61]), "+f"(d[62]), "+f"(d[63])
    : "r"(a0), "r"(a1), "r"(a2), "r"(a3), "l"(descB), "r"(scaleD));
}
__device__ __forceinline__ void wgmma_rs_n64_ta0_tb1(float (&d)[32], uint32_t a0, uint32_t a1, uint32_t a2, uint32_t a3, uint64_t descB, int scaleD) {
  asm volatile("{\n.reg .pred p;\nsetp.ne.b32 p, %37, 0;\n"
    "wgmma.mma_async.sync.aligned.m64n64k16.f32.bf16.bf16 "
    "{%0, %1, %2, %3, %4, %5, %6, %7, %8, %9, %10, %11, %12, %13, %14, %15, %16, %17, %18, %19, %20, %21, %22, %23, %24, %25, %26, %27, %28, %29, %30, %31}, "
    "{%32, %33, %34, %35}, %36, p, 1, 1, 1;\n}\n"
    : "+f"(d[0]), "+f"(d[1]), "+f"(d[2]), "+f"(d[3]), "+f"(d[4]), "+f"(d[5]), "+f"(d[6]), "+f"(d[7]), "+f"(d[8]), "+f"(d[9]), "+f"(d[10]), "+f"(d[11]), "+f"(d[12]), "+f"(d[13]), "+f"(d[14]), "+f"(d[15]), "+f"(d[16]), "+f"(d[17]), "+f"(d[18]), "+f"(d[19]), "+f"(d[20]), "+f"(d[21]), "+f"(d[22]), "+f"(d[23]), "+f"(d[24]), "+f"(d[25]), "+f"(d[26]), "+f"(d[27]), "+f"(d[28]), "+f"(d[29]), "+f"(d[30]), "+f"(d[31])
    : "r"(a0), "r"(a1), "r"(a2), "r"(a3), "l"(descB), "r"(scaleD));
}
__device__ __forceinline__ void wgmma_ss_n128_ta1_tb0(float (&d)[64], uint64_t descA, uint64_t descB, int scaleD) {
  asm volatile("{\n.reg .pred p;\nsetp.ne.b32 p, %66, 0;\n"
    "wgmma.mma_async.sync.aligned.m64n128k16.f32.bf16.bf16 "
    "{%0, %1, %2, %3, %4, %5, %6, %7, %8, %9, %10, %11, %12, %13, %14, %15, %16, %17, %18, %19, %20, %21, %22, %23, %24, %25, %26, %27, %28, %29, %30, %31, %32, %33, %34, %35, %36, %37, %38, %39, %40, %41, %42, %43, %44, %45, %46, %47, %48, %49, %50, %51, %52, %53, %54, %55, %56, %57, %58, %59, %60, %61, %62, %63}, "
    "%64, %65, p, 1, 1, 1, 0;\n}\n"
    : "+f"(d[0]), "+f"(d[1]), "+f"(d[2]), "+f"(d[3]), "+f"(d[4]), "+f"(d[5]), "+f"(d[6]), "+f"(d[7]), "+f"(d[8]), "+f"(d[9]), "+f"(d[10]), "+f"(d[11]), "+f"(d[12]), "+f"(d[13]), "+f"(d[14]), "+f"(d[15]), "+f"(d[16]), "+f"(d[17]), "+f"(d[18]), "+f"(d[19]), "+f"(d[20]), "+f"(d[21]), "+f"(d[22]), "+f"(d[23]), "+f"(d[24]), "+f"(d[25]), "+f"(d[26]), "+f"(d[27]), "+f"(d[28]), "+f"(d[29]), "+f"(d[30]), "+f"(d[31]), "+f"(d[32]), "+f"(d[33]), "+f"(d[34]), "+f"(d[35]), "+f"(d[36]), "+f"(d[37]), "+f"(d[38]), "+f"(d[39]), "+f"(d[40]), "+f"(d[41]), "+f"(d[42]), "+f"(d[43]), "+f"(d[44]), "+f"(d[45]), "+f"(d[46]), "+f"(d[47]), "+f"(d[48]), "+f"(d[49]), "+f"(d[50]), "+f"(d[51]), "+f"(d[52]), "+f"(d[53]), "+f"(d[54]), "+f"(d[55]), "+f"(d[56]), "+f"(d[57]), "+f"(d[58]), "+f"(d[59]), "+f"(d[60]), "+f"(d[61]), "+f"(d[62]), "+f"(d[63])
    : "l"(descA), "l"(descB), "r"(scaleD));
}
__device__ __forceinline__ void wgmma_ss_n160_ta0_tb1(float (&d)[80], uint64_t descA, uint64_t descB, int scaleD) {
  asm volatile("{\n.reg .pred p;\nsetp.ne.b32 p, %82, 0;\n"
    "wgmma.mma_async.sync.aligned.m64n160k16.f32.bf16.bf16 "
    "{%0, %1, %2, %3, %4, %5, %6, %7, %8, %9, %10, %11, %12, %13, %14, %15, %16, %17, %18, %19, %20, %21, %22, %23, %24, %25, %26, %27, %28, %29, %30, %31, %32, %33, %34, %35, %36, %37, %38, %39, %40, %41, %42, %43, %44, %45, %46, %47, %48, %49, %50, %51, %52, %53, %54, %55, %56, %57, %58, %59, %60, %61, %62, %63, %64, %65, %66, %67, %68, %69, %70, %71, %72, %73, %74, %75, %76, %77, %78, %79}, "
    "%80, %81, p, 1, 1, 0, 1;\n}\n"
    : "+f"(d[0]), "+f"(d[1]), "+f"(d[2]), "+f"(d[3]), "+f"(d[4]), "+f"(d[5]), "+f"(d[6]), "+f"(d[7]), "+f"(d[8]), "+f"(d[9]), "+f"(d[10]), "+f"(d[11]), "+f"(d[12]), "+f"(d[13]), "+f"(d[14]), "+f"(d[15]), "+f"(d[16]), "+f"(d[17]), "+f"(d[18]), "+f"(d[19]), "+f"(d[20]), "+f"(d[21]), "+f"(d[22]), "+f"(d[23]), "+f"(d[24]), "+f"(d[25]), "+f"(d[26]), "+f"(d[27]), "+f"(d[28]), "+f"(d[29]), "+f"(d[30]), "+f"(d[31]), "+f"(d[32]), "+f"(d[33]), "+f"(d[34]), "+f"(d[35]), "+f"(d[36]), "+f"(d[37]), "+f"(d[38]), "+f"(d[39]), "+f"(d[40]), "+f"(d[41]), "+f"(d[42]), "+f"(d[43]), "+f"(d[44]), "+f"(d[45]), "+f"(d[46]), "+f"(d[47]), "+f"(d[48]), "+f"(d[49]), "+f"(d[50]), "+f"(d[51]), "+f"(d[52]), "+f"(d[53]), "+f"(d[54]), "+f"(d[55]), "+f"(d[56]), "+f"(d[57]), "+f"(d[58]), "+f"(d[59]), "+f"(d[60]), "+f"(d[61]), "+f"(d[62]), "+f"(d[63]), "+f"(d[64]), "+f"(d[65]), "+f"(d[66]), "+f"(d[67]), "+f"(d[68]), "+f"(d[69]), "+f"(d[70]), "+f"(d[71]), "+f"(d[72]), "+f"(d[73]), "+f"(d[74]), "+f"(d[75]), "+f"(d[76]), "+f"(d[77]), "+f"(d[78]), "+f"(d[79])
    : "l"(descA), "l"(descB), "r"(scaleD));
}

#define PROF_DECL(b)
#define PROF_EV(tag)
#define PROF_GT(tag)

template <int N> struct IC { static constexpr int value = N; };
struct Cur {
    uint32_t slot, ph;
    __device__ __forceinline__ void adv() { if (++slot == NSLOT) { slot = 0; ph ^= 1; } }
};
constexpr int E0 = 6, E_ATT0 = 48, E_ATT1 = 108;
__host__ __device__ constexpr uint32_t slot_of(int e) { return (e + E0) % NSLOT; }
__device__ __forceinline__ Cur cur_at(int e) { Cur c; c.slot = (e + E0) % NSLOT; c.ph = ((e + E0) / NSLOT) & 1; return c; }

__device__ __forceinline__ int q_tile(int k, int t) { return (t < 2 ? 14 - 2 * k : 2 * k) + (t & 1); }
__device__ __forceinline__ int op_head(int i, int kap) { return 16 * kap + 2 * (i & 7) + (i >> 3); }

constexpr float SM_SCALE = 0.08838834764831845f * 1.4426950408889634f;

struct Ctx {
    uint32_t ring, misc;
    uint32_t rel;
    int w, warp, lane;
};
__device__ __forceinline__ void release(const Ctx& c, uint32_t off, uint32_t cnt) {
    if (c.lane < 2) mbar_arrive_cluster(c.rel + off, cnt);
}
__device__ __forceinline__ void signal_event(const Ctx& c, int ev) {
    __syncwarp();
    if (c.lane == 0) mbar_arrive(c.misc + BAR_EV + (c.w * 16 + ev) * 8);
}
template <int NK, int OFF, int N>
__device__ __forceinline__ uint32_t load_afrag(uint32_t (&a)[N], uint32_t base, const Ctx& c) {
    int r = c.lane & 7, mat = c.lane >> 3;
    uint32_t addr = base + (8 * (mat >> 1) + r) * 128 + (((2 * c.warp + (mat & 1)) ^ r) << 4);
#pragma unroll
    for (int k = 0; k < NK; k++) ldsm4t(a[OFF + 4 * k], a[OFF + 4 * k + 1], a[OFF + 4 * k + 2], a[OFF + 4 * k + 3], addr + k * 2048);
    uint32_t dep = 0;
#pragma unroll
    for (int k = 0; k < NK; k++) dep |= a[OFF + 4 * k];
    return dep & blockIdx.y;
}
__device__ __forceinline__ void store_proj(const float (&acc)[64], unsigned char* dst  , const Ctx& c, uint64_t pol) {
    int g = c.lane >> 2, t = c.lane & 3;
#pragma unroll
    for (int i = 0; i < 2; i++) {
        int row = perm32(64 * c.w + 16 * c.warp + 8 * i + g);
        unsigned char* p = dst + row * 128;
#pragma unroll
        for (int q = 0; q < 4; q++) {
            int chunk = (4 * (q & 1) + t) ^ (row & 7);
            stg128_hint(p + (q >> 1) * 16384 + chunk * 16,
                   pack_bf16(acc[16 * q + 2 * i], acc[16 * q + 2 * i + 1]), pack_bf16(acc[16 * q + 4 + 2 * i], acc[16 * q + 4 + 2 * i + 1]),
                   pack_bf16(acc[16 * q + 8 + 2 * i], acc[16 * q + 8 + 2 * i + 1]), pack_bf16(acc[16 * q + 12 + 2 * i], acc[16 * q + 12 + 2 * i + 1]), pol);
        }
    }
}

constexpr float SAFE_SUM = 1099511627776.0f;
template <int NJ>
__device__ __forceinline__ void row_max(const float (&s)[4 * NJ], float (&mx)[2]) {
#pragma unroll
    for (int i = 0; i < 2; i++) {
        float a = fmaxf(s[2 * i], s[2 * i + 1]), b = fmaxf(s[4 + 2 * i], s[4 + 2 * i + 1]);
#pragma unroll
        for (int j = 2; j < NJ; j += 2) {
            a = fmaxf(a, fmaxf(s[4 * j + 2 * i], s[4 * j + 2 * i + 1]));
            b = fmaxf(b, fmaxf(s[4 * j + 4 + 2 * i], s[4 * j + 4 + 2 * i + 1]));
        }
        a = fmaxf(a, b);
        a = fmaxf(a, __shfl_xor_sync(0xffffffffu, a, 1));
        mx[i] = fmaxf(a, __shfl_xor_sync(0xffffffffu, a, 2));
    }
}
template <int NJ, bool SHIFT>
__device__ __forceinline__ void exp_sum(float (&s)[4 * NJ], const float (&m)[2], float& l0, float& l1) {
#pragma unroll
    for (int j = 0; j < NJ; j++) {
#pragma unroll
        for (int e = 0; e < 4; e++) s[4 * j + e] = ex2(SHIFT ? s[4 * j + e] - m[e >> 1] : s[4 * j + e]);
        l0 += s[4 * j + 0] + s[4 * j + 1]; l1 += s[4 * j + 2] + s[4 * j + 3];
    }
}
__device__ __forceinline__ void recompute_scores(float (&s)[64], const unsigned char* qh, uint32_t kaddr, const Ctx& c) {
    const int r = c.lane & 7, mat = c.lane >> 3, g = c.lane >> 2, t = c.lane & 3;
    const uint32_t a0 = kaddr + (8 * (mat & 1) + r) * 128 + (((mat >> 1) ^ r) << 4);
    uint32_t q[32];
#pragma unroll
    for (int i = 0; i < 32; i++) {
        const uint32_t v = __ldcg(reinterpret_cast<const uint32_t*>(qh + (8 * (i >> 1) + g) * 128 + (((2 * c.warp + (i & 1)) ^ g) << 4) + 4 * t));
        asm volatile("movmatrix.sync.aligned.m8n8.trans.b16 %0, %1;" : "=r"(q[i]) : "r"(v));
    }
#pragma unroll
    for (int i = 0; i < 64; i++) s[i] = 0.f;
#pragma unroll
    for (int jp = 0; jp < 8; jp++) {
#pragma unroll
        for (int k = 0; k < 8; k++) {
            asm volatile(
                "{\n.reg .b32 b0, b1, b2, b3;\n"
                "ldmatrix.sync.aligned.m8n8.x4.trans.shared.b16 {b0,b1,b2,b3}, [%12];\n"
                "mma.sync.aligned.m16n8k16.row.col.f32.bf16.bf16.f32 {%0,%1,%2,%3}, {%8,%9,%10,%11}, {b0,b1}, {%0,%1,%2,%3};\n"
                "mma.sync.aligned.m16n8k16.row.col.f32.bf16.bf16.f32 {%4,%5,%6,%7}, {%8,%9,%10,%11}, {b2,b3}, {%4,%5,%6,%7};\n}\n"
                : "+f"(s[8 * jp]), "+f"(s[8 * jp + 1]), "+f"(s[8 * jp + 2]), "+f"(s[8 * jp + 3]),
                  "+f"(s[8 * jp + 4]), "+f"(s[8 * jp + 5]), "+f"(s[8 * jp + 6]), "+f"(s[8 * jp + 7])
                : "r"(q[4 * k]), "r"(q[4 * k + 1]), "r"(q[4 * k + 2]), "r"(q[4 * k + 3]),
                  "r"((a0 ^ ((jp & 3) << 5)) + (jp >> 2) * 16384 + k * 2048) : "memory");
        }
    }
}
__device__ __forceinline__ int mask_lim(const Ctx& c) { return perm32(16 * c.warp + (c.lane >> 2)) - 8 * (c.lane & 3); }
template <int J0>
__device__ __forceinline__ void mask_diag(float (&s)[4 * J0 + 32], const Ctx& c) {
    const int lim = mask_lim(c);
    if (c.warp < 2) {
#pragma unroll
        for (int x = 0; x < 16; x++) {
            if (2 * (x >> 2) + (x & 1) - (x & 2) > lim) s[4 * J0 + x] = -INFINITY;
            s[4 * J0 + 16 + x] = -INFINITY;
        }
    } else {
#pragma unroll
        for (int x = 0; x < 16; x++)
            if (32 + 2 * (x >> 2) + (x & 1) - (x & 2) > lim) s[4 * J0 + 16 + x] = -INFINITY;
    }
}
__device__ __forceinline__ void mask_any(float (&s)[64], int hh, const Ctx& c) {
    const int lim = mask_lim(c) + 64 * hh;
#pragma unroll
    for (int x = 0; x < 64; x++)
        if (32 * (x >> 4) + 2 * ((x >> 2) & 3) + (x & 1) - (x & 2) > lim) s[x] = -INFINITY;
}
__device__ __forceinline__ void issue_pv(float (&o)[64], const uint32_t (&p)[32], uint32_t vaddr, int acc, int mode  ) {
    uint64_t d = mkdesc(vaddr, 16, 1024, 1);
    if (mode == 0) {
        wg_fence();
#pragma unroll
        for (int k = 0; k < 8; k++)
            wgmma_rs_n128_ta0_tb0(o, p[4 * k], p[4 * k + 1], p[4 * k + 2], p[4 * k + 3], d + (k >> 2) * 1024 + 2 * (k & 3), k ? 1 : acc);
        wg_commit();
    } else if (mode == 1) {
        wg_fence();
#pragma unroll
        for (int k = 0; k < 4; k++) wgmma_rs_n128_ta0_tb0(o, p[4 * k], p[4 * k + 1], p[4 * k + 2], p[4 * k + 3], d + 2 * k, k != 0);
        wg_commit();
    } else {
        wg_fence();
        wgmma_rs_n128_ta0_tb0(o, p[0], p[1], p[2], p[3], d, 0);
        wg_commit();
    }
}
__device__ __forceinline__ void issue_qk(float (&s)[64], const uint32_t (&q)[32], uint32_t kaddr) {
    uint64_t d = mkdesc(kaddr, 16384, 1024, 1);
    wg_fence();
#pragma unroll
    for (int k = 0; k < 8; k++) wgmma_rs_n128_ta0_tb1(s, q[4 * k], q[4 * k + 1], q[4 * k + 2], q[4 * k + 3], d + 128 * k, k != 0);
    wg_commit();
}
__device__ __forceinline__ void issue_qk_half(float (&s32)[32], const uint32_t (&q)[32], uint32_t kaddr) {
    uint64_t d = mkdesc(kaddr, 16384, 1024, 1);
    wg_fence();
#pragma unroll
    for (int k = 0; k < 8; k++) wgmma_rs_n64_ta0_tb1(s32, q[4 * k], q[4 * k + 1], q[4 * k + 2], q[4 * k + 3], d + 128 * k, k != 0);
    wg_commit();
}
template <int Q0, int Q1>
__device__ __forceinline__ void stage_ctx(float (&o)[64], const float (&inv)[2], Cur ce, const Ctx& c) {
    const int g = c.lane >> 2, t = c.lane & 3, r7 = ((g & 1) << 2) | (g >> 1);
    const uint32_t base = c.ring + ce.slot * SLOT_BYTES + c.w * 16384 + (16 * c.warp + r7) * 128 + ((t ^ r7) << 4);
    if (Q0 == 0) mbar_wait_hot(c.misc + BAR_FULL + 8 * ce.slot, ce.ph);
#pragma unroll
    for (int q = Q0; q < Q1; q++) {
        uint32_t v[8];
#pragma unroll
        for (int i = 0; i < 2; i++)
#pragma unroll
            for (int j = 0; j < 4; j++) v[4 * i + j] = pack_bf16(o[16 * q + 4 * j + 2 * i] * inv[i], o[16 * q + 4 * j + 2 * i + 1] * inv[i]);
#pragma unroll
        for (int i = 0; i < 8; i++) { o[16 * q + i] = __uint_as_float(v[i]); asm volatile("" : "=f"(o[16 * q + 8 + i])); }
#pragma unroll
        for (int i = 0; i < 2; i++)
            asm volatile("st.shared.v4.b32 [%0], {%1,%2,%3,%4};" ::"r"((base ^ ((q & 1) << 6)) + (q >> 1) * 8192 + i * 1024),
                         "r"(v[4 * i]), "r"(v[4 * i + 1]), "r"(v[4 * i + 2]), "r"(v[4 * i + 3]) : "memory");
    }
}
__device__ __forceinline__ void publish_ctx(int ev, const Ctx& c) {
    asm volatile("fence.proxy.async.shared::cta;" ::: "memory");
    signal_event(c, ev);
}

__device__ __forceinline__ const unsigned char* xn_addr(int row, int col) {
    return g_xn + ((row >> 7) * 10 + (col >> 6)) * 16384 + (row & 127) * 128 + ((((col & 63) >> 3) ^ (row & 7)) << 4);
}
__device__ __forceinline__ void mma16816(float (&d)[4], uint32_t a0, uint32_t a1, uint32_t a2, uint32_t a3, uint32_t b0, uint32_t b1) {
    asm volatile("mma.sync.aligned.m16n8k16.row.col.f32.bf16.bf16.f32 {%0,%1,%2,%3}, {%4,%5,%6,%7}, {%8,%9}, {%0,%1,%2,%3};"
                 : "+f"(d[0]), "+f"(d[1]), "+f"(d[2]), "+f"(d[3]) : "r"(a0), "r"(a1), "r"(a2), "r"(a3), "r"(b0), "r"(b1));
}
__device__ __forceinline__ uint32_t lds32(uint32_t addr) { uint32_t v; asm volatile("ld.shared.u32 %0, [%1];" : "=r"(v) : "r"(addr)); return v; }

__device__ __forceinline__ void aux_cta(const CUtensorMap* tmG, const CUtensorMap* tmU, const CUtensorMap* tmD, unsigned char* sm, int a) {
    constexpr int STG = 57344, XS = 3 * STG, HS = XS + 8 * 1296, KEY = HS + 8 * 912, MI = KEY + 8192;
    const int tid = threadIdx.x, warp = __shfl_sync(0xffffffffu, tid >> 5, 0), lane = tid & 31;
    const uint32_t sb = smem_u32(sm);
    const uint32_t full = sb + MI, empty = sb + MI + 32;
    int* s_sel = reinterpret_cast<int*>(sm + MI + 64);
    float* s_r = reinterpret_cast<float*>(sm + MI + 96);
    volatile unsigned* s_misc = reinterpret_cast<volatile unsigned*>(sm + MI + 128);
    uint32_t* s_key = reinterpret_cast<uint32_t*>(sm + KEY);
    PROF_DECL(128 + a)
    PROF_GT(0);
    if (tid == 0) {
        for (int i = 0; i < 3; i++) { mbar_init(full + 8 * i, 1); mbar_init(empty + 8 * i, 10); }
        asm volatile("fence.mbarrier_init.release.cluster;" ::: "memory");
    }
    __syncthreads();
    if (warp == 11) {
        if (elect_one()) {
            int st = 0; uint32_t ph = 0;
#pragma unroll 1
            for (int s = 0; s < 34; s++) {
                mbar_wait(empty + 8 * st, ph ^ 1);
                const uint32_t dst = sb + st * STG, fb = full + 8 * st;
                if (s < 20) {
                    mbar_expect_tx(fb, 57344);
                    tma3d(dst, tmG, 0, 32 * s, 7 * a, fb);
                    tma3d(dst + 28672, tmU, 0, 32 * s, 7 * a, fb);
                } else {
                    mbar_expect_tx(fb, 40960);
                    tma3d(dst, tmD, 0, 448 * a + 32 * (s - 20), 0, fb);
                }
                if (s >= 3) {
#pragma unroll 1
                    for (int f = (s == 3 ? 4 : s + 6); f <= s + 6 && f < 34; f++) {
                        if (f < 20) { tma3d_prefetch(tmG, 0, 32 * f, 7 * a); tma3d_prefetch(tmU, 0, 32 * f, 7 * a); }
                        else tma3d_prefetch(tmD, 0, 448 * a + 32 * (f - 20), 0);
                    }
                }
                if (++st == 3) { st = 0; ph ^= 1; }
            }
        }
        return;
    }
    if (warp == 10) return;
    if (tid < 16) {
        unsigned e = *reinterpret_cast<volatile unsigned*>(&g_epoch);
        if (tid == 0) s_misc[0] = e;
        flag_wait(flag_ptr(FL_LN + tid), (e + 1) * 32u);
    }
    bar_sync(1, 320);
    PROF_GT(50);
    const unsigned ep = s_misc[0];
    auto top8 = [&](uint32_t (&key)[8]) {
        uint32_t mine = 0;
#pragma unroll 1
        for (int r = 0; r < TOPC; r++) {
            uint32_t best = 0;
#pragma unroll
            for (int i = 0; i < 8; i++) best = max(best, key[i]);
            best = __reduce_max_sync(0xffffffffu, best);
#pragma unroll
            for (int i = 0; i < 8; i++) if (key[i] == best) key[i] = 0;
            if (lane == r) mine = best;
        }
        return mine;
    };
#pragma unroll 1
    for (int pass = 0; pass < 2; pass++) {
        if (warp < (pass ? 1 : 8)) {
            uint32_t key[8];
#pragma unroll
            for (int i = 0; i < 8; i++) {
                if (pass == 0) {
                    int idx = warp * 256 + i * 32 + lane;
                    uint32_t b = __float_as_uint(__ldcg(g_router + idx)) >> 16;
                    b = (b & 0x8000u) ? (~b & 0xffffu) : (b | 0x8000u);
                    key[i] = (b << 16) | (uint32_t)(0xffff - idx);
                } else key[i] = i < 2 ? s_key[i * 32 + lane] : 0u;
            }
            uint32_t best = top8(key);
            if (lane < TOPC) {
                if (pass == 0) s_key[warp * 8 + lane] = best;
                else {
                    uint32_t b = best >> 16;
                    b = (b & 0x8000u) ? (b & 0x7fffu) : (~b & 0xffffu);
                    s_sel[lane] = 0xffff - (int)(best & 0xffffu);
                    s_r[lane] = __uint_as_float(b << 16);
                }
            }
        }
        bar_sync(1, 320);
    }
#pragma unroll
    for (int it = 0; it < 2; it++) {
        int i = tid + it * 320, tk = i / 80, ch = i % 80;
        *reinterpret_cast<uint4*>(sm + XS + tk * 1296 + ch * 16) = __ldcg(reinterpret_cast<const uint4*>(xn_addr(s_sel[tk], ch * 8)));
    }
    bar_sync(1, 320);
    PROF_GT(51);
    const int g = lane >> 2, t = lane & 3;
    const uint32_t woff = warp * 4096 + (8 * (lane >> 4) + (lane & 7)) * 128 + ((((lane >> 3) & 1) ^ (lane & 7)) << 4);
    int st = 0; uint32_t ph = 0;
    float ga[4][4], ua[4][4];
#pragma unroll
    for (int i = 0; i < 4; i++)
#pragma unroll
        for (int e = 0; e < 4; e++) { ga[i][e] = 0.f; ua[i][e] = 0.f; }
#pragma unroll 1
    for (int s = 0; s < 34; s++) {
        if (s == 20) {
            if (warp < 7) {
#pragma unroll
                for (int i = 0; i < 4; i++)
#pragma unroll
                    for (int e = 0; e < 4; e++) {
                        float gv = bf_round(ga[i][e]), uv = bf_round(ua[i][e]);
                        float sg = bf_round(__fdividef(gv, 1.0f + __expf(fminf(-gv, 80.f))));
                        int f = warp * 64 + i * 16 + g + 8 * (e >> 1), tk = 2 * t + (e & 1);
                        *reinterpret_cast<__nv_bfloat16*>(sm + HS + tk * 912 + f * 2) = __float2bfloat16_rn(sg * uv);
                        ga[i][e] = 0.f;
                    }
            }
            bar_sync(1, 320);
            PROF_GT(52);
        }
        mbar_wait(full + 8 * st, ph);
        if (s >= 20 || warp < 7) {
#pragma unroll
            for (int kk = 0; kk < 2; kk++) {
                uint32_t xb = sb + (s < 20 ? XS + g * 1296 + s * 64 : HS + g * 912 + (s - 20) * 64) + 32 * kk + 4 * t;
                uint32_t b0 = lds32(xb), b1 = lds32(xb + 16);
                uint32_t wa = sb + st * STG + woff + kk * 2048;
#pragma unroll
                for (int i = 0; i < 4; i++) {
                    uint32_t a0, a1, a2, a3;
                    ldsm4t(a0, a1, a2, a3, wa ^ (i << 5));
                    mma16816(ga[i], a0, a1, a2, a3, b0, b1);
                    if (s < 20) {
                        ldsm4t(a0, a1, a2, a3, (wa ^ (i << 5)) + 28672);
                        mma16816(ua[i], a0, a1, a2, a3, b0, b1);
                    }
                }
            }
        }
        asm volatile("fence.proxy.async.shared::cta;" ::: "memory");
        __syncwarp();
        if (lane == 0) mbar_arrive(empty + 8 * st);
        if (++st == 3) { st = 0; ph ^= 1; }
    }
#pragma unroll
    for (int i = 0; i < 4; i++)
#pragma unroll
        for (int e = 0; e < 4; e += 2)
            *reinterpret_cast<float2*>(g_moe_part + (a * DM + warp * 64 + i * 16 + g + 4 * e) * 8 + 2 * t) = make_float2(ga[i][e], ga[i][e + 1]);
    bar_sync(1, 320);
    if (tid == 0) {
        __threadfence();
        unsigned old = atomicAdd(flag_ptr(FL_MOE_CNT), 1u);
        s_misc[1] = (old == ep * 4u + 3u);
        __threadfence();
    }
    bar_sync(1, 320);
    PROF_GT(53);
    if (s_misc[1]) {
        const float4* pp = reinterpret_cast<const float4*>(g_moe_part);
#pragma unroll 2
        for (int i = tid; i < DM * 2; i += 320) {
            float4 v0 = __ldcg(pp + i), v1 = __ldcg(pp + DM * 2 + i), v2 = __ldcg(pp + DM * 4 + i), v3 = __ldcg(pp + DM * 6 + i);
            float y[4] = {v0.x + v1.x + v2.x + v3.x, v0.y + v1.y + v2.y + v3.y, v0.z + v1.z + v2.z + v3.z, v0.w + v1.w + v2.w + v3.w};
#pragma unroll
            for (int e = 0; e < 4; e++) {
                int col = i >> 1, tk = (i & 1) * 4 + e;
                float sg = bf_round(__fdividef(1.0f, 1.0f + __expf(fminf(-s_r[tk], 80.f))));
                float upd = bf_round(bf_round(y[e]) * sg);
                float xn = __bfloat162float(*reinterpret_cast<const __nv_bfloat16*>(sm + XS + tk * 1296 + col * 2));
                g_brow[tk * DM + col] = __float2bfloat16_rn(xn + upd);
            }
        }
        if (tid < TOPC) g_sel[tid] = s_sel[tid];
        bar_sync(1, 320);
        if (tid == 0) {
            flag_signal(flag_ptr(FL_MOE_DONE));
            *reinterpret_cast<volatile unsigned*>(&g_epoch) = ep + 1;
        }
        PROF_GT(54);
    }
}

__device__ __forceinline__ void ln_rows(const Params& P, int row0, int lane, uint32_t wr_s) {
    const int hl = lane & 15, row = row0 + (lane >> 4);
    uint32_t v[20];
#pragma unroll
    for (int i = 0; i < 5; i++) {
        uint4 u;
        asm("ld.global.nc.L2::cache_hint.v4.b32 {%0,%1,%2,%3}, [%4], %5;" : "=r"(u.x), "=r"(u.y), "=r"(u.z), "=r"(u.w)
            : "l"(P.x + (size_t)row * DM + 128 * i + 8 * hl), "l"(policy(HM & 512)));
        v[4 * i] = u.x; v[4 * i + 1] = u.y; v[4 * i + 2] = u.z; v[4 * i + 3] = u.w;
    }
    float mean = 0.f, m2 = 0.f;
#pragma unroll
    for (int i = 0; i < 20; i++) { mean += bf_lo(v[i]); mean += bf_hi(v[i]); }
    mean *= (1.0f / 40);
#pragma unroll
    for (int i = 0; i < 20; i++) {
        float d0 = __uint_as_float(__byte_perm(v[i], 0, 0x1044)) - mean, d1 = __uint_as_float(__byte_perm(v[i], 0, 0x3244)) - mean;
        m2 = fmaf(d0, d0, m2); m2 = fmaf(d1, d1, m2);
    }
#pragma unroll
    for (int o = 1; o < 16; o <<= 1) {
        float mo = __shfl_xor_sync(0xffffffffu, mean, o), qo = __shfl_xor_sync(0xffffffffu, m2, o), d = mo - mean;
        m2 = fmaf(d * d, 20.0f * o, m2 + qo);
        mean = 0.5f * (mean + mo);
    }
    const uint32_t mb2 = pack_bf16(mean, mean);
    const float inv = rcp_fast(bf_round(sqrt_fast(bf_round(bf_round(m2 * (1.0f / DM)) + 1e-5f))));
    float dot = 0.f;
    unsigned char* xp = g_xn + ((row >> 7) * 10 + (hl >> 3)) * 16384 + (row & 127) * 128 + (((hl & 7) ^ (row & 7)) << 4);
#pragma unroll
    for (int i = 0; i < 5; i++) {
        uint32_t ww[4];
        asm volatile("ld.shared.v4.b32 {%0,%1,%2,%3}, [%4];" : "=r"(ww[0]), "=r"(ww[1]), "=r"(ww[2]), "=r"(ww[3]) : "r"(wr_s + 256 * i + 16 * hl) : "memory");
#pragma unroll
        for (int e = 0; e < 4; e++) {
            uint32_t d;
            asm("sub.rn.bf16x2 %0, %1, %2;" : "=r"(d) : "r"(v[4 * i + e]), "r"(mb2));
            d = pack_bf16(bf_lo(d) * inv, bf_hi(d) * inv);
            v[4 * i + e] = d;
            dot = fmaf(bf_lo(d), bf_lo(ww[e]), dot);
            dot = fmaf(bf_hi(d), bf_hi(ww[e]), dot);
        }
        stg128(xp + i * 32768, v[4 * i], v[4 * i + 1], v[4 * i + 2], v[4 * i + 3]);
    }
#pragma unroll
    for (int o = 8; o > 0; o >>= 1) dot += __shfl_xor_sync(0xffffffffu, dot, o);
    if (hl == 0) { g_router[row] = bf_round(dot); g_stats[row] = make_uint2(mb2, __float_as_uint(inv)); }
}

__global__ void __cluster_dims__(2, 1, 1) __launch_bounds__(384, 1)
fused_kernel(const __grid_constant__ CUtensorMap tmC, const __grid_constant__ CUtensorMap tmWk, const __grid_constant__ CUtensorMap tmWv,
             const __grid_constant__ CUtensorMap tmWq, const __grid_constant__ CUtensorMap tmWo,
             const __grid_constant__ CUtensorMap tmG, const __grid_constant__ CUtensorMap tmU, const __grid_constant__ CUtensorMap tmD, const Params P) {
    extern __shared__ __align__(1024) unsigned char smem_raw[];
    const uint32_t ring = smem_u32(smem_raw);
    const uint32_t misc = ring + RING_BYTES;
    const int tid = threadIdx.x;
    const int rank = blockIdx.x & 1;
    uint32_t smid; asm("mov.u32 %0, %%smid;" : "=r"(smid));
    const int tpc = smid >> 1;
    const int mc = tpc < 32 ? (tpc & 7) * 8 + (tpc >> 3) : tpc < 60 ? (1 + (tpc - 32) % 7) * 8 + 4 + (tpc - 32) / 7 : tpc < 64 ? tpc - 56 : tpc;
    const int cta = mc * 2 + rank;
    if (mc >= 64) { aux_cta(&tmG, &tmU, &tmD, smem_raw, cta - 128); return; }
    PROF_DECL(cta)
    PROF_GT(0); PROF_EV(1);
    const int team = mc >> 2, k = mc & 3;
    const int u3 = (mc >> 4) * 2 + (team & 1), s3 = k, kap = (mc >> 3) & 1;
    const int partner = cta ^ 16;

    if (tid >= 128) {
        const int i = tid - 128;
        asm volatile("prefetch.global.L2 [%0];" ::"l"((rank ? P.wv : P.wk) + (size_t)(k * 128 + (i >> 1)) * 4096 + team * 256 + (i & 1) * 64));
        if (i < 32) asm volatile("prefetch.global.L2 [%0];" ::"l"(P.c + (size_t)((12 + k) * 128 + (team * 2 + rank) * 4) * DC + i * 64));
    }
    if (tid == 0) {
#pragma unroll
        for (int i = 0; i < NSLOT; i++) mbar_init(misc + BAR_FULL + 8 * i, 1);
#pragma unroll
        for (int i = 0; i < E0; i++) mbar_arrive(misc + BAR_FULL + 8 * i);
        asm volatile("fence.mbarrier_init.release.cluster;" ::: "memory");
        const CUtensorMap* tw = rank ? &tmWv : &tmWk;
        mbar_expect_tx(misc + BAR_FULL + 8 * slot_of(0), SLOT_BYTES);
        tma2d(ring + slot_of(0) * SLOT_BYTES, tw, team * 256, 0, misc + BAR_FULL + 8 * slot_of(0), policy(HM & 1));
        tma2d(ring + slot_of(0) * SLOT_BYTES + 16384, tw, team * 256 + 64, 0, misc + BAR_FULL + 8 * slot_of(0), policy(HM & 1));
    }
    if (tid == 32) {
        asm volatile("prefetch.tensormap [%0];" ::"l"(&tmC) : "memory");
#pragma unroll
        for (int i = 0; i < NSLOT; i++) mbar_init(misc + BAR_EMPTY + 8 * i, 16);
#pragma unroll
        for (int i = 0; i < E0; i++) mbar_arrive_cluster(misc + BAR_EMPTY + 8 * i, 16);
        asm volatile("fence.mbarrier_init.release.cluster;" ::: "memory");
    }
    if (tid == 64) {
#pragma unroll
        for (int i = 0; i < NST3; i++) { mbar_init(misc + BAR_FULL3 + 8 * i, 1); mbar_init(misc + BAR_EMPTY3 + 8 * i, 16); }
#pragma unroll
        for (int i = 0; i < 4; i++) mbar_init(misc + BAR_LN + 8 * i, 2);
        mbar_init(misc + BAR_PROG, 1); mbar_init(misc + BAR_PROG + 8, 1); mbar_init(misc + BAR_PROG + 16, 1);
        asm volatile("fence.mbarrier_init.release.cluster;" ::: "memory");
    }
    if (tid == 96) {
#pragma unroll
        for (int i = 0; i < 34; i++) mbar_init(misc + BAR_DEP + 8 * i, 1);
    }
    if (tid == 128) {
#pragma unroll
        for (int i = 0; i < 32; i++) mbar_init(misc + BAR_EV + 8 * i, 4);
    }
    __syncthreads();
    asm volatile("barrier.cluster.arrive.relaxed.aligned;\nbarrier.cluster.wait.aligned;" ::: "memory");
    PROF_EV(5);
    const int wg = __shfl_sync(0xffffffffu, tid >> 7, 0);

    if (wg == 0) {
        asm volatile("setmaxnreg.dec.sync.aligned.u32 40;");
        const int warp = __shfl_sync(0xffffffffu, tid >> 5, 0), lane = tid & 31;
        if (warp == 0) {
            const bool lead = elect_one();
            Cur c = cur_at(1);
            uint32_t dst, fb;
            auto acquire = [&]() {
                mbar_wait(misc + BAR_EMPTY + 8 * c.slot, c.ph ^ 1);
                fb = misc + BAR_FULL + 8 * c.slot; dst = ring + c.slot * SLOT_BYTES;
                if (lead) mbar_expect_tx(fb, SLOT_BYTES);
                c.adv();
            };
            auto load_w = [&](const CUtensorMap* tm, int col, int row, bool stream) {
                acquire();
                if (lead) { tma2d(dst, tm, col, row, fb, policy(stream)); tma2d(dst + 16384, tm, col + 64, row, fb, policy(stream)); }
            };
            auto load_half = [&](const unsigned char* src, bool stream) {
                acquire();
                if (lead) bulk_load_mc(dst + rank * 16384, src, 16384, fb, policy(stream));
            };
            auto staging = [&]() {
                mbar_wait(misc + BAR_EMPTY + 8 * c.slot, c.ph ^ 1);
                if (lead) mbar_arrive(misc + BAR_FULL + 8 * c.slot);
                c.adv();
            };
            auto dep_wait = [&](int d) { mbar_wait(misc + BAR_DEP + 8 * d, 0); fence_async_global(); };
            auto op_prefetch = [&](int i) {
                const int head = op_head(i, kap);
                l2_prefetch(reinterpret_cast<const unsigned char*>(P.wo) + head * 163840 + (u3 * 8 + s3 * 2 + rank) * 2560, 2560);
                if (i < 8) l2_prefetch(g_Q + (size_t)(head * 32 + 4 * u3 + 2 * rank) * 16384 + s3 * 8192, 8192);
            };
            const CUtensorMap* tw = rank ? &tmWv : &tmWk;
            const unsigned char* Kh = g_K + (size_t)team * 32 * 16384 + rank * 16384;
            const unsigned char* Vh = g_V + (size_t)team * 32 * 16384 + rank * 16384;
#pragma unroll 1
            for (int v = 0; v < 2; v++) {
                const int h = 2 * team + v;
#pragma unroll 1
                for (int i = 0; i < 16; i++) {
                    if (i < 4 && (v | i)) load_w(tw, h * 128, i * 128, HM & 1);
                    if (v && (i & 7) == 3) dep_wait(D_WAR + (i >> 3));
                    acquire();
                    if (lead) tma2d_mc(dst + rank * 16384, &tmC, (i & 3) * 128 + rank * 64, (12 - (i & 12) + k) * 128, fb, policy(HM & 2));
                    if (v && i == 2 && lead) mbar_arrive(misc + BAR_PROG + 8);
                }
                if (v == 0) {
                    const int cq = (h + rank) * 128;
                    load_w(&tmWq, cq, 0, HM & 1); load_w(&tmWq, cq, 128, HM & 1); load_w(&tmWq, cq, 256, HM & 1);
#pragma unroll 1
                    for (int t = 0; t < 4; t++) {
                        const unsigned char* xt = g_xn + (q_tile(k, t) * 10 + rank) * 16384;
                        dep_wait(D_LN + t);
                        if (t == 3 && lead) l2_prefetch((rank ? Vh - 16384 : Kh) + (13 - 2 * k) * 32768, 3 * 32768);
#pragma unroll 1
                        for (int ch = 0; ch < 5; ch++) {
                            load_half(xt + ch * 32768, HM & 4);
                            if (t == 0 && ch == 0) load_w(&tmWq, cq, 384, HM & 1);
                        }
                        load_w(&tmWq, cq, 512, (HM & 1) && t == 3);
                    }
                }
                int togo = v ? PF_START : 11;
#pragma unroll 1
                for (int r = 0; r < 2; r++) {
                    const int p = r ? k : 7 - k, n = 2 * p + 1;
                    if (v == 0) dep_wait(D_Q + r);
                    acquire();
                    if (lead) {
                        const int g0 = r ? rank : 3 - rank;
                        bulk_load(dst, g_Q + (size_t)(h * 32 + 4 * p + g0) * 16384, 16384, fb, policy(HM & 8));
                        bulk_load(dst + 16384, g_Q + (size_t)(h * 32 + 4 * p + 3 - g0) * 16384, 16384, fb, policy(HM & 8));
                    }
                    if (v && r == 0) dep_wait(D_KV + 4 + (k >> 1));
                    load_half(Kh + n * 32768, HM & 16);
                    if (r) { load_half(Vh, HM & 16); staging(); }
#pragma unroll 1
                    for (int j = n - 1; j >= 0; j--) {
                        if (v && r == 0 && (j & 3) == 3) dep_wait(D_KV + 7 - (j >> 2));
                        load_half(Kh + j * 32768, HM & 16); load_half(Vh + (j + 1) * 32768, HM & 16);
                        if (v == 0 && r == 0 && j == 3 && lead) mbar_arrive(misc + BAR_PROG);
                        --togo;
                        if (v == 0 && togo == 0 && lead) {
                            tma2d_prefetch(tw, h * 128 + 128, k * 128); tma2d_prefetch(tw, h * 128 + 192, k * 128);
                            l2_prefetch(reinterpret_cast<const unsigned char*>(P.c) + (size_t)cta * 16384, 16384);
                        }
                        if (v && togo <= 0 && togo > -OP_PF && lead) op_prefetch(-togo);
                    }
                }
                load_half(Vh, HM & 16);
                staging();
                if (v == 0 && lead) l2_prefetch(g_Q + (size_t)((h + 1) * 32 + 8 * k + 4 * rank) * 16384, 65536);
            }
            mbar_wait(misc + BAR_EMPTY + 8 * c.slot, c.ph ^ 1); c.adv();
            int st = 0; uint32_t ph3 = 0;
#pragma unroll 1
            for (int i = 0; i < 32; i++) {
                const int head = op_head(i >> 1, kap);
                if ((i & 1) == 0) dep_wait(D_CTX + (i >> 1));
                if (i < NST3) { mbar_wait(misc + BAR_EMPTY + 8 * c.slot, c.ph ^ 1); c.adv(); }
                else mbar_wait(misc + BAR_EMPTY3 + 8 * st, ph3 ^ 1);
                fb = misc + BAR_FULL3 + 8 * st; dst = ring + st * ST3_BYTES;
                if (i == LATE_AT && lead) mbar_arrive(misc + BAR_PROG + 16);
                if (lead) {
                    mbar_expect_tx(fb, ST3_BYTES);
                    const unsigned char* src = g_Q + (size_t)(head * 32 + 4 * u3 + 2 * rank) * 16384 + (i & 1) * 8192;
                    bulk_load(dst, src, 8192, fb, policy(HM & 32));
                    bulk_load(dst + 8192, src + 16384, 8192, fb, policy(HM & 32));
                    tma3d_mc(dst + 16384 + rank * 10240, &tmWo, 0, head * 128 + (i & 1) * 64 + rank * 32, 5 * s3, fb, policy(HM & 32));
                    if ((i & 1) && (i >> 1) + OP_PF < 16) op_prefetch((i >> 1) + OP_PF);
                }
                if (++st == NST3) { st = 0; ph3 ^= 1; }
            }
        } else if (warp == 3) {
            const unsigned ep1 = *reinterpret_cast<volatile unsigned*>(&g_epoch) + 1;
            if (lane == 0) {
                asm volatile("st.shared.u32 [%0], %1;" ::"r"(misc + MISC_EPOCH), "r"(ep1) : "memory");
                l2_prefetch(reinterpret_cast<const unsigned char*>(P.c) + (size_t)cta * 12288, 12288);
#pragma unroll 1
                for (int t = 0; t < 4; t++) {
                    if (t == 1) {
                        mbar_wait(misc + BAR_PF, 0);
                        l2_prefetch(reinterpret_cast<const unsigned char*>(P.wq) + (size_t)cta * 40960, 40960);
                    }
                    mbar_wait(misc + BAR_LN + 8 * t, 0);
                    flag_signal(flag_ptr(FL_LN + q_tile(cta >> 5, t)));
                    flag_wait(flag_ptr(FL_LN + q_tile(k, t)), ep1 * 32u);
                    mbar_arrive(misc + BAR_DEP + 8 * (D_LN + t));
                }
                mbar_wait(misc + BAR_EV + 8 * (16 + EV_KV + 3), 0);
                flag_wait(flag_ptr(FL_KV + team * 8), ep1 * 16u);
#pragma unroll 1
                for (int i = 0; i < 2; i++) {
                    mbar_wait(misc + BAR_EV + 8 * (16 + EV_Q + 1 + 2 * i), 0);
                    flag_wait(flag_ptr(FL_Q + team * 8 + (i ? k : 7 - k)), ep1 * 4u);
                    mbar_arrive(misc + BAR_DEP + 8 * (D_Q + i));
                }
#pragma unroll 1
                for (int i = 0; i < 2; i++) {
                    mbar_wait(misc + BAR_PROG + 8 * i, 0);
                    flag_signal(flag_ptr(FL_WAR + 2 * team + i));
                    flag_wait(flag_ptr(FL_WAR + 2 * team + i), ep1 * 8u);
                    mbar_arrive(misc + BAR_DEP + 8 * (D_WAR + i));
                }
#pragma unroll 1
                for (int i = 4; i < 8; i++) {
                    mbar_wait(misc + BAR_EV + 8 * (16 + EV_KV + i), 0);
                    flag_wait(flag_ptr(FL_KV + team * 8 + i), ep1 * 16u);
                    mbar_arrive(misc + BAR_DEP + 8 * (D_KV + i));
                }
                flag_wait(flag_ptr(FL_MOE_DONE), ep1);
                int4 s0 = __ldcg(reinterpret_cast<const int4*>(g_sel)), s1 = __ldcg(reinterpret_cast<const int4*>(g_sel) + 1);
                asm volatile("st.shared.v4.u32 [%0], {%1,%2,%3,%4};" ::"r"(misc + MISC_SEL), "r"(s0.x), "r"(s0.y), "r"(s0.z), "r"(s0.w) : "memory");
                asm volatile("st.shared.v4.u32 [%0], {%1,%2,%3,%4};" ::"r"(misc + MISC_SEL + 16), "r"(s1.x), "r"(s1.y), "r"(s1.z), "r"(s1.w) : "memory");
                mbar_arrive(misc + BAR_SEL);
            }
            __syncwarp();
            const unsigned* cf = flag_ptr(FL_CTX + op_head(lane & 15, kap) * 8 + u3);
#pragma unroll 1
            for (int half = 0; half < 2; half++) {
                if (half) mbar_wait(misc + BAR_EV + 8 * (EV_CTX + 3), 0);
                bool done = (lane >> 3) != half;
                for (int spin = 0; spin < 4000000; spin++) {
                    if (!done) {
                        unsigned v;
                        asm volatile("ld.acquire.gpu.global.u32 %0, [%1];" : "=r"(v) : "l"(cf) : "memory");
                        if ((int)(v - ep1 * 4u) >= 0) { mbar_arrive(misc + BAR_DEP + 8 * (D_CTX + lane)); done = true; }
                    }
                    if (__all_sync(0xffffffffu, done)) break;
                    __nanosleep(64);
                }
            }
        } else {
            const int w = warp - 1;
            if (lane < 20) {
#pragma unroll
                for (int i = 0; i < 2; i++) {
                    const int ch = w * 40 + i * 20 + lane;
                    uint4 u = __ldg(reinterpret_cast<const uint4*>(P.wr) + ch);
                    asm volatile("st.shared.v4.b32 [%0], {%1,%2,%3,%4};" ::"r"(misc + MISC_WR + 16 * ch), "r"(u.x), "r"(u.y), "r"(u.z), "r"(u.w) : "memory");
                }
            }
            const int rsub = (cta & 31) * 4 + 2 * w;
            if (lane < 3) l2_prefetch(P.x + (size_t)(q_tile(cta >> 5, lane + 1) * 128 + rsub) * DM, 2 * DM * 2);
            bar_sync(3, 64);
#pragma unroll 1
            for (int t = 0; t < 4; t++) {
                ln_rows(P, q_tile(cta >> 5, t) * 128 + rsub, lane, misc + MISC_WR);
                __syncwarp();
                if (lane == 0) mbar_arrive(misc + BAR_LN + 8 * t);
            }
            if (lane == 0) {
                const uint32_t eb = misc + BAR_EV + w * 128;
#pragma unroll 1
                for (int v = 0; v < 2; v++) {
#pragma unroll 1
                    for (int i = 0; i < (v ? 4 : 3); i++) {
                        mbar_wait(eb + 8 * (v ? EV_KV + 4 + i : i ? EV_Q + 2 * i - 1 : EV_KV + 3), 0);
                        flag_signal(flag_ptr(v ? FL_KV + team * 8 + 4 + i : i ? FL_Q + team * 8 + (i == 1 ? 7 - k : k) : FL_KV + team * 8));
                    }
#pragma unroll 1
                    for (int r = 0; r < 2; r++) {
                        const int p = r ? k : 7 - k;
                        const uint32_t slot = ((v ? E_ATT1 : E_ATT0) + (r ? 39 : 4 * p + 7) + E0) % NSLOT;
                        const int grp = (r == w) ? 3 - rank : rank;
                        mbar_wait(eb + 8 * (EV_CTX + 2 * v + r), 0);
                        asm volatile("cp.async.bulk.global.shared::cta.bulk_group.L2::cache_hint [%0], [%1], 16384, %2;"
                                     ::"l"(g_Q + (size_t)((2 * team + v) * 32 + 4 * p + grp) * 16384), "r"(ring + slot * SLOT_BYTES + w * 16384),
                                       "l"(policy((HM & 256) && v == 0)) : "memory");
                        asm volatile("cp.async.bulk.commit_group;" ::: "memory");
                        asm volatile("cp.async.bulk.wait_group.read 0;" ::: "memory");
                        mbar_arrive_cluster(mapa(misc + BAR_EMPTY + 8 * slot, 0), 4);
                        mbar_arrive_cluster(mapa(misc + BAR_EMPTY + 8 * slot, 1), 4);
                        asm volatile("cp.async.bulk.wait_group 0;" ::: "memory");
                        fence_async_global();
                        flag_signal(flag_ptr(FL_CTX + (2 * team + v) * 8 + p));
                    }
                }
            }
            __syncwarp();
            mbar_wait(misc + BAR_PROG + 16, 0);
            const int row = (2 * u3 + rank) * 128 + 64 * w + perm32(16 * (lane >> 3) + 8 * kap + (lane & 7));
#pragma unroll
            for (int i = 0; i < 10; i++) asm volatile("prefetch.global.L2 [%0];" ::"l"(P.x + (size_t)row * DM + 160 * s3 + 16 * i));
            asm volatile("prefetch.global.L2 [%0];" ::"l"(g_stats + row));
        }
    } else {
        asm volatile("setmaxnreg.inc.sync.aligned.u32 232;");
        Ctx c;
        c.ring = ring; c.misc = misc; c.w = wg - 1; c.warp = __shfl_sync(0xffffffffu, (tid >> 5) & 3, 0); c.lane = tid & 31;
        c.rel = mapa(misc, tid & 1);
        const int w = c.w;
        if (w == 1) bar_arrive(1, 256);
        Cur cur = cur_at(0);
        float o[64], inv[2];
#pragma unroll 1
        for (int v = 0; v < 2; v++) {
        {
            uint32_t wf[128];
            float acc[64];
#pragma unroll
            for (int i = 32; i < 128; i++) wf[i] = 0u;
            Cur cw = cur;
            int wstep = 2;
            auto load_wchunk = [&](auto CH) {
                constexpr int ch = decltype(CH)::value;
                mbar_wait_hot(misc + BAR_FULL + 8 * cw.slot, cw.ph);
                const uint32_t z = load_afrag<8, 32 * ch>(wf, ring + cw.slot * SLOT_BYTES + w * 16384, c);
                release(c, BAR_EMPTY + 8 * cw.slot + z, 1);
                cw.adv();
                if (wstep == 2 || ch == 2) cw.adv();
            };
            load_wchunk(IC<0>{});
            cur.adv();
            int nload = 1;
            PROF_EV(2); PROF_GT(60);
#pragma unroll 1
            for (int t = 0; t < (v ? 4 : 8); t++) {
                uint32_t last = 0;
                token_wait(w);
                PROF_EV(t < 4 ? 10 : 20);
                undef_regs(acc);
                auto chunk = [&](auto CH) {
                    constexpr int ch = decltype(CH)::value;
                    mbar_wait_hot(misc + BAR_FULL + 8 * cur.slot, cur.ph);
                    if (t == 0 || t == 4) { PROF_EV(12 + ch); }
                    uint64_t d = mkdesc(ring + cur.slot * SLOT_BYTES, 16, 1024, 1);
                    wg_fence();
#pragma unroll
                    for (int ks = 0; ks < 8; ks++)
                        wgmma_rs_n128_ta0_tb0(acc, wf[32 * ch + 4 * ks], wf[32 * ch + 4 * ks + 1], wf[32 * ch + 4 * ks + 2], wf[32 * ch + 4 * ks + 3],
                                              d + (ks >> 2) * 1024 + (ks & 3) * 2, (ch | ks) != 0);
                    wg_commit();
                    const bool swap = (ch < 2 && t == 0) || (ch == 3 && t < 4);
                    if (swap) token_pass(w);
                    if constexpr (ch < 3) { if (nload == ch + 1) { load_wchunk(IC<ch + 1>{}); nload++; } }
                    if (ch > 0) { wg_wait<1>(); release(c, BAR_EMPTY + 8 * last, 1); }
                    last = cur.slot;
                    cur.adv();
                    if ((ch < 3 && t == 0) || (ch == 0 && t == 4)) cur.adv();
                    if (ch < 2 && swap) token_wait(w);
                };
                chunk(IC<0>{}); chunk(IC<1>{}); chunk(IC<2>{}); chunk(IC<3>{});
                if (t < 4) {
                    wg_wait<0>();
                    release(c, BAR_EMPTY + 8 * last, 1);
                } else {
                    Cur cx = cur; cur.adv();
                    mbar_wait_hot(misc + BAR_FULL + 8 * cx.slot, cx.ph);
                    mbar_wait_hot(misc + BAR_FULL + 8 * cur.slot, cur.ph);
                    uint64_t db = mkdesc(ring + cx.slot * SLOT_BYTES, 16, 1024, 1);
                    uint64_t da = mkdesc(ring + cur.slot * SLOT_BYTES + w * 16384, 16384, 1024, 1);
                    wg_fence();
#pragma unroll
                    for (int ks = 0; ks < 8; ks++) wgmma_ss_n128_ta1_tb0(acc, da + 128 * ks, db + (ks >> 2) * 1024 + (ks & 3) * 2, 1);
                    wg_commit();
                    token_pass(w);
                    wg_wait<1>(); release(c, BAR_EMPTY + 8 * last, 1);
                    wg_wait<0>(); release(c, BAR_EMPTY + 8 * cx.slot, 1); release(c, BAR_EMPTY + 8 * cur.slot, 1);
                    cur.adv();
                    fence_regs(acc);
#pragma unroll
                    for (int i = 0; i < 64; i++) acc[i] *= SM_SCALE;
                }
                PROF_EV(t < 4 ? 11 : 21);
                fence_regs(acc);
                if (t == 0 && v == 0 && tid == 128) mbar_arrive(misc + BAR_PF);
                const bool wswitch = t == 3 && v == 0;
                if (wswitch) {
                    cw = cur; wstep = 1; nload = 0;
                    cur.adv(); cur.adv(); cur.adv();
                    if (w) { load_wchunk(IC<0>{}); load_wchunk(IC<1>{}); load_wchunk(IC<2>{}); nload = 3; }
                }
                unsigned char* dst = t < 4 ? (rank ? g_V : g_K) + (size_t)(team * 32 + 24 + 2 * k - 8 * t) * 16384
                                           : g_Q + (size_t)((2 * team + rank) * 32 + q_tile(k, t & 3) * 2) * 16384;
                store_proj(acc, dst, c, policy(((HM & 64) && t >= 4 && rank) || ((HM & 128) && t >= 6)));
                signal_event(c, t < 4 ? EV_KV + 4 * v + t : EV_Q + t - 4);
                if (wswitch) {
                    if (w) { load_wchunk(IC<3>{}); nload = 4; }
                    else { load_wchunk(IC<0>{}); load_wchunk(IC<1>{}); nload = 2; }
                }
                if (t == 3) { PROF_EV(61); PROF_GT(62); }
            }
        }
        PROF_EV(63); PROF_GT(64);
        {
            uint32_t q[32], p[32];
            float m[2], l[2], tq[2];
#pragma unroll
            for (int i = 0; i < 64; i++) o[i] = 0.f;
#pragma unroll
            for (int i = 0; i < 32; i++) p[i] = 0u;
            m[0] = m[1] = inv[0] = inv[1] = 0.f;
            l[0] = l[1] = tq[0] = tq[1] = 1.f;
            int gen = 0;
            Cur ck = cur, cv = cur, cq, ce;
            int r = 0, left;
            int first = 1, half, heavy;
            int pv_acc = 0, pv_mode = 2; uint32_t pv_cnt = 0;
            int pending = 0;
            Cur nck, ncv;
            auto next_task = [&](int rr) {
                heavy = 1 ^ rr ^ w;
                half = 1 ^ heavy ^ rank;
                left = 2 * (rr ? k : 7 - k) + 1 + heavy;
                cq = cur; cur.adv();
                nck = cur; cur.adv();
                if (rr) { ncv = cur; cur.adv(); ce = cur; cur.adv(); }
                if (!heavy) { nck = cur; cur.adv(); cur.adv(); }
                if (!rr) { ncv = nck; ce = nck; }
            };
            auto load_q = [&]() {
                mbar_wait_hot(misc + BAR_FULL + 8 * cq.slot, cq.ph);
                load_afrag<8, 0>(q, ring + cq.slot * SLOT_BYTES + w * 16384, c);
            };
            next_task(0);
            load_q();
            uint32_t k_cnt = 1; int last = 0, was_first = 0, was_half = 0, publish = 0;
            auto window = [&]() {
                publish = pending;
                if (pending) stage_ctx<2, 4>(o, inv, ce, c);
                pending = 0;
                k_cnt = 1;
                was_first = first; was_half = half;
                if (first) {
                    release(c, BAR_EMPTY + 8 * cq.slot, 1);
                    l[0] += tq[0]; l[1] += tq[1];
                    tq[0] = __shfl_xor_sync(0xffffffffu, l[0], 2); tq[1] = __shfl_xor_sync(0xffffffffu, l[1], 2);
                    pending = r;
                    k_cnt = 1 + heavy;
                }
                last = --left == 0 ? 1 : 0;
                first = last;
                if (!last) { nck = cur; cur.adv(); ncv = cur; cur.adv(); half = 0; }
                else if (++r < 2) next_task(1);
                mbar_wait_hot(misc + BAR_FULL + 8 * cv.slot, cv.ph);
            };
            auto new_rows = [&]() {
                inv[0] = rcp_fast(l[0] + tq[0]); inv[1] = rcp_fast(l[1] + tq[1]);
                l[0] = l[1] = m[0] = m[1] = 0.f;
                gen = 0;
            };
#pragma unroll 1
            while (r < 2) {
                float s[64];
                ck = nck; cv = ncv;
                mbar_wait_hot(misc + BAR_FULL + 8 * ck.slot, ck.ph);
                if (half) {
                    token_wait(w);
                    PROF_EV(30);
                    float sh[32];
                    undef_regs(sh);
                    issue_qk_half(sh, q, ring + ck.slot * SLOT_BYTES);
                    window();
                    issue_pv(o, p, ring + cv.slot * SLOT_BYTES, pv_acc, pv_mode);
                    token_pass(w);
                    wg_wait<1>();
                    PROF_EV(34);
                    fence_regs(sh);
                    new_rows();
                    mask_diag<0>(sh, c);
                    float l0 = 0.f, l1 = 0.f;
#pragma unroll
                    for (int j = 0; j < 8; j++) {
#pragma unroll
                        for (int e = 0; e < 4; e++) ex2v(sh[4 * j + e]);
                        l0 += sh[4 * j] + sh[4 * j + 1]; l1 += sh[4 * j + 2] + sh[4 * j + 3];
                    }
                    const int lim = mask_lim(c);
                    const bool bad = __any_sync(0xffffffffu, !(l0 <= SAFE_SUM && l1 <= SAFE_SUM && (l0 >= 1.0f / SAFE_SUM || lim < 0) &&
                                                               (l1 >= 1.0f / SAFE_SUM || lim < -2)));
                    if (!bad) { l[0] = l0; l[1] = l1; asm volatile("" ::: "memory"); }
                    wg_wait<0>();
                    fence_regs(o);
                    fence_regs(sh);
                    if (bad) goto redo;
#pragma unroll
                    for (int i = 0; i < 16; i++) p[i] = pack_bf16(sh[2 * i], sh[2 * i + 1]);
                    goto tail;
                }
#pragma unroll 1
                while (true) {
                    token_wait(w);
                    PROF_EV(first ? 30 : 31);
                    undef_regs(s);
                    issue_qk(s, q, ring + ck.slot * SLOT_BYTES);
                    const bool special = first > 0 || pv_acc == 0 || left == 1;
                    if (special) window();
                    else {
                        nck = cur; cur.adv(); ncv = cur; cur.adv();
                        --left;
                        mbar_wait_hot(misc + BAR_FULL + 8 * cv.slot, cv.ph);
                    }
                    issue_pv(o, p, ring + cv.slot * SLOT_BYTES, pv_acc, pv_mode);
                    token_pass(w);
                    wg_wait<1>();
                    PROF_EV(33);
                    fence_regs(s);
                    float lo = 0.f;
                    if (special) {
                        if (last && r < 2) load_q();
                        if (publish) publish_ctx(EV_CTX + 2 * v, c);
                        if (was_first) {
                            new_rows();
                            lo = 1.0f / SAFE_SUM;
                            mask_diag<8>(s, c);
                        }
                    }
                    constexpr int JB = 11;
                    float l0 = l[0], l1 = l[1];
                    if (!gen) {
#pragma unroll
                        for (int j = 0; j < JB; j++) {
#pragma unroll
                            for (int e = 0; e < 4; e++) ex2v(s[4 * j + e]);
                            if (j < JB - 1) { l0 += s[4 * j] + s[4 * j + 1]; l1 += s[4 * j + 2] + s[4 * j + 3]; }
                        }
                    }
                    wg_wait<0>();
                    fence_regs(o);
                    if (gen) goto general;
#pragma unroll
                    for (int j = JB - 1; j < 16; j++) {
                        if (j >= JB) {
#pragma unroll
                            for (int e = 0; e < 4; e++) ex2v(s[4 * j + e]);
                        }
                        l0 += s[4 * j] + s[4 * j + 1]; l1 += s[4 * j + 2] + s[4 * j + 3];
                    }
#pragma unroll
                    for (int i = 0; i < 32; i++) p[i] = pack_bf16(s[2 * i], s[2 * i + 1]);
                    if (__any_sync(0xffffffffu, !(l0 <= SAFE_SUM && l1 <= SAFE_SUM && l0 >= lo && l1 >= lo))) goto redo;
                    l[0] = l0; l[1] = l1;
                    if (special) goto tail;
                    release(c, BAR_EMPTY + 8 * ck.slot, 1);
                    release(c, BAR_EMPTY + 8 * cv.slot, 1);
                    ck = nck; cv = ncv;
                    mbar_wait_hot(misc + BAR_FULL + 8 * ck.slot, ck.ph);
                }
            redo:
                {
                    const int rr = r - last;
                    const int grp = (rr == w) ? 3 - rank : rank;
                    recompute_scores(s, g_Q + (size_t)((2 * team + v) * 32 + 4 * (rr ? k : 7 - k) + grp) * 16384, ring + ck.slot * SLOT_BYTES, c);
                    if (was_first) { mask_any(s, was_half ^ 1, c); m[0] = m[1] = -INFINITY; }
                    gen = 1;
                }
            general:
                {
                    float mx[2], alpha[2];
                    row_max<16>(s, mx);
#pragma unroll
                    for (int i = 0; i < 2; i++) {
                        mx[i] = fmaxf(mx[i], m[i]);
                        alpha[i] = was_first ? 1.0f : ex2(m[i] - mx[i]);
                        m[i] = mx[i];
                        l[i] *= alpha[i];
                    }
                    exp_sum<16, true>(s, m, l[0], l[1]);
#pragma unroll
                    for (int i = 0; i < 64; i++) o[i] *= alpha[(i >> 1) & 1];
#pragma unroll
                    for (int i = 0; i < 32; i++) p[i] = pack_bf16(s[2 * i], s[2 * i + 1]);
                }
            tail:
                release(c, BAR_EMPTY + 8 * ck.slot, k_cnt);
                if (pv_cnt) release(c, BAR_EMPTY + 8 * cv.slot, pv_cnt);
                pv_acc = was_first ^ 1; pv_mode = was_half; pv_cnt = k_cnt;
                if (last) { tq[0] = __shfl_xor_sync(0xffffffffu, l[0], 1); tq[1] = __shfl_xor_sync(0xffffffffu, l[1], 1); }
                if (pending) stage_ctx<0, 2>(o, inv, ce, c);
            }
            if (pending) { stage_ctx<2, 4>(o, inv, ce, c); publish_ctx(EV_CTX + 2 * v, c); }
            mbar_wait_hot(misc + BAR_FULL + 8 * cur.slot, cur.ph);
            token_wait(w);
            PROF_EV(32);
            issue_pv(o, p, ring + cur.slot * SLOT_BYTES, pv_acc, pv_mode);
            if (w == 0 || v == 0) token_pass(w);
            l[0] += tq[0]; l[1] += tq[1];
            inv[0] = rcp_fast(l[0] + __shfl_xor_sync(0xffffffffu, l[0], 2));
            inv[1] = rcp_fast(l[1] + __shfl_xor_sync(0xffffffffu, l[1], 2));
            wg_wait<0>();
            release(c, BAR_EMPTY + 8 * cur.slot, pv_cnt);
            fence_regs(o);
            cur.adv();
            if (v == 0) { stage_ctx<0, 4>(o, inv, cur, c); publish_ctx(EV_CTX + 1, c); cur.adv(); }
        }
        }
        {
            float acc[80];
            undef_regs(acc);
            int st = 0, prev = 0; uint32_t ph3 = 0;
            auto op_stage = [&](int i) {
                mbar_wait(misc + BAR_FULL3 + 8 * st, ph3);
                PROF_EV(44);
                uint32_t base = ring + st * ST3_BYTES;
                uint64_t da = mkdesc(base + w * 8192, 16, 1024, 1);
                uint64_t db = mkdesc(base + 16384, 2048, 512, 2);
                wg_fence();
#pragma unroll
                for (int k = 0; k < 4; k++) wgmma_ss_n160_ta0_tb1(acc, da + 2 * k, db + (k >> 1) * 640 + (k & 1) * 64, k ? 1 : i);
                wg_commit();
                if (i > 0) { wg_wait<1>(); if (i <= 32 - NST3) release(c, BAR_EMPTY3 + 8 * prev, 1); }
                prev = st;
                if (++st == NST3) { st = 0; ph3 ^= 1; }
            };
            PROF_EV(40); PROF_GT(65);
            op_stage(0);
            stage_ctx<0, 4>(o, inv, cur, c);
            publish_ctx(EV_CTX + 3, c);
#pragma unroll 1
            for (int i = 1; i < 12; i++) op_stage(i);
            mbar_wait(misc + BAR_SEL, 0);
            const uint32_t tag = lds32(misc + MISC_EPOCH) & 1;
            const int g = c.lane >> 2, t = c.lane & 3;
            const int row = (2 * u3 + rank) * 128 + 64 * w + perm32(16 * c.warp + 8 * kap + (((g & 3) << 1) | (g >> 2)));
            const int col = 160 * s3 + 8 * t;
            int sel = -1;
#pragma unroll
            for (int i = 0; i < TOPC; i++) if ((int)lds32(misc + MISC_SEL + 4 * i) == row) sel = i;
            const int t256 = tid - 128;
            uint4* sendp = g_part + (size_t)cta * 2560 + t256;
            if (c.lane >= 30) stg128(sendp + 9 * 256, tag ^ 1, tag ^ 1, tag ^ 1, tag ^ 1);
#pragma unroll 1
            for (int i = 12; i < 32; i++) op_stage(i);
            uint4 xv[5], bv[5];
#pragma unroll
            for (int i = 0; i < 5; i++) xv[i] = ldg128(P.x + (size_t)row * DM + col + 32 * i);
            uint2 stat;
            asm volatile("ld.global.cg.v2.b32 {%0,%1}, [%2];" : "=r"(stat.x), "=r"(stat.y) : "l"(g_stats + row) : "memory");
            wg_wait<0>();
            fence_regs(acc);
            PROF_EV(41); PROF_GT(66);
            float keep[40];
#pragma unroll
            for (int j = 0; j < 10; j++) {
                uint32_t v0 = __float_as_uint(kap ? acc[8 * j + 0] : acc[8 * j + 2]), v1 = __float_as_uint(kap ? acc[8 * j + 1] : acc[8 * j + 3]);
                uint32_t v2 = __float_as_uint(kap ? acc[8 * j + 4] : acc[8 * j + 6]), v3 = __float_as_uint(kap ? acc[8 * j + 5] : acc[8 * j + 7]);
                asm volatile("st.relaxed.gpu.global.v4.b32 [%0], {%1,%2,%3,%4};" ::"l"(sendp + j * 256),
                             "r"((v0 & ~1u) | tag), "r"((v1 & ~1u) | tag), "r"((v2 & ~1u) | tag), "r"((v3 & ~1u) | tag) : "memory");
                keep[4 * j + 0] = kap ? acc[8 * j + 2] : acc[8 * j + 0]; keep[4 * j + 1] = kap ? acc[8 * j + 3] : acc[8 * j + 1];
                keep[4 * j + 2] = kap ? acc[8 * j + 6] : acc[8 * j + 4]; keep[4 * j + 3] = kap ? acc[8 * j + 7] : acc[8 * j + 5];
            }
            PROF_GT(67);
#pragma unroll
            for (int i = 0; i < 5; i++) {
                uint32_t xx[4] = {xv[i].x, xv[i].y, xv[i].z, xv[i].w};
#pragma unroll
                for (int e = 0; e < 4; e++) {
                    asm("sub.rn.bf16x2 %0, %0, %1;" : "+r"(xx[e]) : "r"(stat.x));
                    xx[e] = pack_bf16(bf_lo(xx[e]) * __uint_as_float(stat.y), bf_hi(xx[e]) * __uint_as_float(stat.y));
                }
                bv[i] = make_uint4(xx[0], xx[1], xx[2], xx[3]);
            }
            if (sel >= 0) {
#pragma unroll
                for (int i = 0; i < 5; i++) bv[i] = ldg128(g_brow + sel * DM + col + 32 * i);
            }
            const uint4* recvp = g_part + (size_t)partner * 2560 + t256;
            uint4 rv[10];
            int spins = 0;
            while (POLL1) {
                uint32_t v;
                asm volatile("ld.relaxed.gpu.global.b32 %0, [%1];" : "=r"(v) : "l"(recvp + 9 * 256 + (31 - c.lane)) : "memory");
                if (__all_sync(0xffffffffu, (v & 1u) == tag) || ++spins > 2000000) break;
            }
            PROF_GT(68);
            while (true) {
                uint32_t bad = 0u;
#pragma unroll
                for (int j = 0; j < 10; j++) {
                    asm volatile("ld.relaxed.gpu.global.v4.b32 {%0,%1,%2,%3}, [%4];"
                                 : "=r"(rv[j].x), "=r"(rv[j].y), "=r"(rv[j].z), "=r"(rv[j].w) : "l"(recvp + j * 256) : "memory");
                }
#pragma unroll
                for (int j = 0; j < 10; j++) {
                    rv[j].x ^= tag; rv[j].y ^= tag; rv[j].z ^= tag; rv[j].w ^= tag;
                    bad |= rv[j].x | rv[j].y | rv[j].z | rv[j].w;
                }
                if (__all_sync(0xffffffffu, (bad & 1u) == 0) || ++spins > 2000000) break;
            }
            PROF_GT(69);
            uint32_t pk[20];
#pragma unroll
            for (int j = 0; j < 10; j++) {
                pk[2 * j] = pack_bf16(keep[4 * j] + __uint_as_float(rv[j].x), keep[4 * j + 1] + __uint_as_float(rv[j].y));
                pk[2 * j + 1] = pack_bf16(keep[4 * j + 2] + __uint_as_float(rv[j].z), keep[4 * j + 3] + __uint_as_float(rv[j].w));
            }
#pragma unroll
            for (int i = 0; i < 5; i++) {
                uint32_t a0 = pk[4 * i], a1 = pk[4 * i + 1], a2 = pk[4 * i + 2], a3 = pk[4 * i + 3];
                uint32_t x0 = (t & 1) ? a0 : a1, x1 = (t & 1) ? a2 : a3;
                x0 = __shfl_xor_sync(0xffffffffu, x0, 1); x1 = __shfl_xor_sync(0xffffffffu, x1, 1);
                if (t & 1) { a0 = x0; a2 = x1; } else { a1 = x0; a3 = x1; }
                x0 = (t & 2) ? a0 : a2; x1 = (t & 2) ? a1 : a3;
                x0 = __shfl_xor_sync(0xffffffffu, x0, 2); x1 = __shfl_xor_sync(0xffffffffu, x1, 2);
                if (t & 2) { a0 = x0; a1 = x1; } else { a2 = x0; a3 = x1; }
                uint32_t av[4] = {a0, a1, a2, a3};
                uint32_t xx[4] = {xv[i].x, xv[i].y, xv[i].z, xv[i].w}, bb[4] = {bv[i].x, bv[i].y, bv[i].z, bv[i].w};
                uint32_t ov[4];
#pragma unroll
                for (int e = 0; e < 4; e++) {
                    asm("add.rn.bf16x2 %0, %1, %2;" : "=r"(ov[e]) : "r"(xx[e]), "r"(av[e]));
                    asm("add.rn.bf16x2 %0, %0, %1;" : "+r"(ov[e]) : "r"(bb[e]));
                }
                stg128(P.out + (size_t)row * DM + col + 32 * i, ov[0], ov[1], ov[2], ov[3]);
            }
            PROF_EV(42); PROF_GT(43);
        }
    }
}

typedef CUresult (*EncodeFn)(CUtensorMap*, CUtensorMapDataType, cuuint32_t, void*, const cuuint64_t*, const cuuint64_t*, const cuuint32_t*,
                             const cuuint32_t*, CUtensorMapInterleave, CUtensorMapSwizzle, CUtensorMapL2promotion, CUtensorMapFloatOOBfill);

void make_map2d(EncodeFn enc, CUtensorMap* tm, const void* p, uint64_t cols, uint64_t rows) {
    cuuint64_t gd[2] = {cols, rows}, gs[1] = {cols * 2};
    cuuint32_t box[2] = {64, 128}, es[2] = {1, 1};
    enc(tm, CU_TENSOR_MAP_DATA_TYPE_BFLOAT16, 2, const_cast<void*>(p), gd, gs, box, es, CU_TENSOR_MAP_INTERLEAVE_NONE,
        CU_TENSOR_MAP_SWIZZLE_128B, CU_TENSOR_MAP_L2_PROMOTION_L2_128B, CU_TENSOR_MAP_FLOAT_OOB_FILL_NONE);
}

void make_map3d(EncodeFn enc, CUtensorMap* tm, const void* p, uint64_t cols, uint64_t rows, uint32_t bw, uint32_t nb) {
    cuuint64_t gd[3] = {bw, rows, cols / bw}, gs[2] = {cols * 2, bw * 2};
    cuuint32_t box[3] = {bw, 32, nb}, es[3] = {1, 1, 1};
    enc(tm, CU_TENSOR_MAP_DATA_TYPE_BFLOAT16, 3, const_cast<void*>(p), gd, gs, box, es, CU_TENSOR_MAP_INTERLEAVE_NONE,
        bw == 64 ? CU_TENSOR_MAP_SWIZZLE_128B : CU_TENSOR_MAP_SWIZZLE_64B, CU_TENSOR_MAP_L2_PROMOTION_L2_128B, CU_TENSOR_MAP_FLOAT_OOB_FILL_NONE);
}

}

extern "C" void kernel_launch(void* const* d_in, const int* in_sizes, int n_in, void* d_out, int out_size) {
    (void)in_sizes; (void)n_in; (void)out_size;
    static EncodeFn enc = nullptr;
    if (!enc) {
        void* fn = nullptr;
        cudaDriverEntryPointQueryResult qr;
        cudaGetDriverEntryPoint("cuTensorMapEncodeTiled", &fn, cudaEnableDefault, &qr);
        enc = (EncodeFn)fn;
        cudaFuncSetAttribute(fused_kernel, cudaFuncAttributeMaxDynamicSharedMemorySize, SMEM_BYTES);
    }
    CUtensorMap tmC, tmWk, tmWv, tmWq, tmWo, tmG, tmU, tmD;
    make_map2d(enc, &tmC, d_in[1], DC, SEQ);
    make_map2d(enc, &tmWq, d_in[2], 4096, DM);
    make_map2d(enc, &tmWk, d_in[3], 4096, DC);
    make_map2d(enc, &tmWv, d_in[4], 4096, DC);
    make_map3d(enc, &tmWo, d_in[5], DM, 4096, 32, 5);
    make_map3d(enc, &tmG, d_in[8], FF, DM, 64, 7);
    make_map3d(enc, &tmU, d_in[9], FF, DM, 64, 7);
    make_map3d(enc, &tmD, d_in[10], DM, FF, 64, 10);
    Params P;
    P.x = (const __nv_bfloat16*)d_in[0];
    P.c = (const __nv_bfloat16*)d_in[1];
    P.wq = (const __nv_bfloat16*)d_in[2];
    P.wk = (const __nv_bfloat16*)d_in[3];
    P.wv = (const __nv_bfloat16*)d_in[4];
    P.wo = (const __nv_bfloat16*)d_in[5];
    P.wr = (const __nv_bfloat16*)d_in[7];
    P.out = (__nv_bfloat16*)d_out;
    fused_kernel<<<132, 384, SMEM_BYTES>>>(tmC, tmWk, tmWv, tmWq, tmWo, tmG, tmU, tmD, P);
}
```

```cpp
#include <cuda_runtime.h>
#include <cuda_bf16.h>
#include <cuda.h>
#include <stdint.h>

#define HM 960
#define POLL1 1
#define OP_PF 8
#define PF_START 9
#define LATE_AT 18
#define PFV 21
#define CDELAY 2000
#define LNDELAY 0
#define AUXDELAY 3000
#define MAP 2
namespace {

constexpr int SEQ = 2048, NH = 32, DM = 640, DC = 512, FF = 1728, TOPC = 8;
constexpr int NSLOT = 7, SLOT_BYTES = 32768;
constexpr int NST3 = 6, ST3_BYTES = 36864;
constexpr int RING_BYTES = NSLOT * SLOT_BYTES;
constexpr int SMEM_BYTES = RING_BYTES + 3072;

constexpr int BAR_FULL = 96  , BAR_FULL3 = 152  , BAR_DEP = 200  , BAR_PF = 456, BAR_SEL = 464,
              BAR_LN = 472  , BAR_EV = 504  , BAR_EMPTY = 760  , BAR_EMPTY3 = 816  ,
              BAR_PROG = 864  , MISC_EPOCH = 896, MISC_SEL = 912, MISC_WR = 1024  ;
constexpr int D_LN = 0  , D_KV = 4  , D_Q = 12  , D_WAR = 14  , D_CTX = 16  ;
constexpr int EV_KV = 0  , EV_Q = 8  , EV_CTX = 12  ;

constexpr int FL_MOE_CNT = 0, FL_MOE_DONE = 1, FL_LN = 16  , FL_KV = 32  , FL_Q = 160  , FL_CTX = 416  , FL_WAR = 672  , FL_TOTAL = 704;

__device__ __align__(1024) unsigned char g_K[16 * 32 * 16384];
__device__ __align__(1024) unsigned char g_V[16 * 32 * 16384];
__device__ __align__(1024) unsigned char g_Q[NH * 32 * 16384];
__device__ __align__(1024) unsigned char g_xn[16 * 10 * 16384];
__device__ __align__(1024) uint4 g_part[128 * 10 * 256];
__device__ float g_router[SEQ];
__device__ uint2 g_stats[SEQ];
__device__ __align__(16) float g_moe_part[4 * TOPC * DM];
__device__ __align__(16) __nv_bfloat16 g_brow[TOPC * DM];
__device__ __align__(16) int g_sel[TOPC];
__device__ unsigned g_flags[FL_TOTAL * 8];
__device__ unsigned g_epoch;

struct Params {
    const __nv_bfloat16 *x, *c, *wr, *wq, *wk, *wv, *wo;
    __nv_bfloat16* out;
};

__device__ __forceinline__ uint32_t smem_u32(const void* p) { return (uint32_t)__cvta_generic_to_shared(p); }
__device__ __forceinline__ void mbar_init(uint32_t bar, int cnt) { asm volatile("mbarrier.init.shared::cta.b64 [%0], %1;" ::"r"(bar), "r"(cnt)); }
__device__ __forceinline__ void mbar_expect_tx(uint32_t bar, uint32_t bytes) {
    asm volatile("mbarrier.arrive.expect_tx.shared::cta.b64 _, [%0], %1;" ::"r"(bar), "r"(bytes) : "memory");
}
__device__ __forceinline__ void mbar_arrive(uint32_t bar) { asm volatile("mbarrier.arrive.shared::cta.b64 _, [%0];" ::"r"(bar) : "memory"); }
__device__ __forceinline__ void mbar_arrive_cluster(uint32_t cluster_addr, uint32_t cnt) {
    asm volatile("mbarrier.arrive.shared::cluster.b64 _, [%0], %1;" ::"r"(cluster_addr), "r"(cnt) : "memory");
}
__device__ __forceinline__ uint32_t mapa(uint32_t addr, uint32_t cta) {
    uint32_t r; asm("mapa.shared::cluster.u32 %0, %1, %2;" : "=r"(r) : "r"(addr), "r"(cta)); return r;
}
__device__ __forceinline__ void mbar_wait(uint32_t bar, uint32_t parity) {
    asm volatile(
        "{\n.reg .pred p;\n.reg .u32 n;\n"
        "mbarrier.try_wait.parity.shared::cta.b64 p, [%0], %1;\n"
        "@p bra DONE;\n"
        "mov.u32 n, 0;\n"
        "LAB_WAIT:\n"
        "mbarrier.try_wait.parity.shared::cta.b64 p, [%0], %1, 100000;\n"
        "@p bra DONE;\n"
        "add.u32 n, n, 1;\n"
        "setp.lt.u32 p, n, 200000;\n"
        "@p bra LAB_WAIT;\n"
        "trap;\n"
        "DONE:\n}\n" ::"r"(bar), "r"(parity) : "memory");
}
__device__ __forceinline__ void mbar_wait_hot(uint32_t bar, uint32_t parity) {
    asm volatile("{\n.reg .pred p;\nLAB_WAIT:\nmbarrier.try_wait.parity.shared::cta.b64 p, [%0], %1;\n@!p bra LAB_WAIT;\n}\n" ::"r"(bar), "r"(parity) : "memory");
}
__device__ __forceinline__ void flag_wait(const unsigned* flag, unsigned target) {
    asm volatile(
        "{\n.reg .pred p;\n.reg .u32 n, v;\n.reg .s32 d;\n"
        "mov.u32 n, 0;\n"
        "LAB_WAIT:\n"
        "ld.acquire.gpu.global.u32 v, [%0];\n"
        "sub.s32 d, v, %1;\n"
        "setp.ge.s32 p, d, 0;\n"
        "@p bra DONE;\n"
        "nanosleep.u32 40;\n"
        "add.u32 n, n, 1;\n"
        "setp.lt.u32 p, n, 3000000;\n"
        "@p bra LAB_WAIT;\n"
        "trap;\n"
        "DONE:\n}\n" ::"l"(flag), "r"(target) : "memory");
}
__device__ __forceinline__ void flag_signal(unsigned* flag) {
    asm volatile("red.release.gpu.global.add.u32 [%0], 1;" ::"l"(flag) : "memory");
}
__device__ __forceinline__ void fence_async_global() { asm volatile("fence.proxy.async.global;" ::: "memory"); }
__device__ __forceinline__ unsigned* flag_ptr(int idx) { return g_flags + idx * 8; }

__device__ __forceinline__ uint64_t policy_stream() {
    uint64_t p; asm("createpolicy.fractional.L2::evict_first.b64 %0, 1.0;" : "=l"(p)); return p;
}
__device__ __forceinline__ uint64_t policy_normal() { return 0x1000000000000000ull; }
__device__ __forceinline__ uint64_t policy(bool stream) { return stream ? policy_stream() : policy_normal(); }
__device__ __forceinline__ void bulk_load(uint32_t dst, const void* src, uint32_t bytes, uint32_t bar, uint64_t pol) {
    asm volatile("cp.async.bulk.shared::cluster.global.mbarrier::complete_tx::bytes.L2::cache_hint [%0], [%1], %2, [%3], %4;"
                 ::"r"(dst), "l"(src), "r"(bytes), "r"(bar), "l"(pol) : "memory");
}
__device__ __forceinline__ void bulk_load_mc(uint32_t dst, const void* src, uint32_t bytes, uint32_t bar, uint64_t pol) {
    asm volatile("cp.async.bulk.shared::cluster.global.mbarrier::complete_tx::bytes.multicast::cluster.L2::cache_hint [%0], [%1], %2, [%3], %4, %5;"
                 ::"r"(dst), "l"(src), "r"(bytes), "r"(bar), "h"((uint16_t)3), "l"(pol) : "memory");
}
__device__ __forceinline__ void tma2d(uint32_t dst, const CUtensorMap* tm, int c0, int c1, uint32_t bar, uint64_t pol) {
    asm volatile("cp.async.bulk.tensor.2d.shared::cluster.global.mbarrier::complete_tx::bytes.L2::cache_hint [%0], [%1, {%3, %4}], [%2], %5;"
                 ::"r"(dst), "l"(tm), "r"(bar), "r"(c0), "r"(c1), "l"(pol) : "memory");
}
__device__ __forceinline__ void tma2d_mc(uint32_t dst, const CUtensorMap* tm, int c0, int c1, uint32_t bar, uint64_t pol) {
    asm volatile("cp.async.bulk.tensor.2d.shared::cluster.global.mbarrier::complete_tx::bytes.multicast::cluster.L2::cache_hint [%0], [%1, {%3, %4}], [%2], %5, %6;"
                 ::"r"(dst), "l"(tm), "r"(bar), "r"(c0), "r"(c1), "h"((uint16_t)3), "l"(pol) : "memory");
}
__device__ __forceinline__ void tma3d_mc(uint32_t dst, const CUtensorMap* tm, int c0, int c1, int c2, uint32_t bar, uint64_t pol) {
    asm volatile("cp.async.bulk.tensor.3d.shared::cluster.global.mbarrier::complete_tx::bytes.multicast::cluster.L2::cache_hint [%0], [%1, {%3, %4, %5}], [%2], %6, %7;"
                 ::"r"(dst), "l"(tm), "r"(bar), "r"(c0), "r"(c1), "r"(c2), "h"((uint16_t)3), "l"(pol) : "memory");
}
__device__ __forceinline__ void tma3d(uint32_t dst, const CUtensorMap* tm, int c0, int c1, int c2, uint32_t bar) {
    asm volatile("cp.async.bulk.tensor.3d.shared::cluster.global.mbarrier::complete_tx::bytes.L2::cache_hint [%0], [%1, {%3, %4, %5}], [%2], %6;"
                 ::"r"(dst), "l"(tm), "r"(bar), "r"(c0), "r"(c1), "r"(c2), "l"(policy_stream()) : "memory");
}
__device__ __forceinline__ void tma2d_prefetch(const CUtensorMap* tm, int c0, int c1) {
    asm volatile("cp.async.bulk.prefetch.tensor.2d.L2.global [%0, {%1, %2}];" ::"l"(tm), "r"(c0), "r"(c1) : "memory");
}
__device__ __forceinline__ void tma3d_prefetch(const CUtensorMap* tm, int c0, int c1, int c2) {
    asm volatile("cp.async.bulk.prefetch.tensor.3d.L2.global [%0, {%1, %2, %3}];" ::"l"(tm), "r"(c0), "r"(c1), "r"(c2) : "memory");
}
__device__ __forceinline__ void l2_prefetch(const void* p, uint32_t bytes) {
    asm volatile("cp.async.bulk.prefetch.L2.global [%0], %1;" ::"l"(p), "r"(bytes) : "memory");
}
__device__ __forceinline__ bool elect_one() {
    uint32_t r; asm volatile("{\n.reg .pred p;\nelect.sync _|p, 0xffffffff;\nselp.u32 %0, 1, 0, p;\n}\n" : "=r"(r)); return r != 0;
}
__device__ __forceinline__ void wg_fence() { asm volatile("wgmma.fence.sync.aligned;" ::: "memory"); }
__device__ __forceinline__ void wg_commit() { asm volatile("wgmma.commit_group.sync.aligned;" ::: "memory"); }
template <int N> __device__ __forceinline__ void wg_wait() { asm volatile("wgmma.wait_group.sync.aligned %0;" ::"n"(N) : "memory"); }
__device__ __forceinline__ void bar_sync(int id, int n) { asm volatile("bar.sync %0, %1;" ::"r"(id), "r"(n) : "memory"); }
__device__ __forceinline__ void bar_arrive(int id, int n) { asm volatile("bar.arrive %0, %1;" ::"r"(id), "r"(n) : "memory"); }
__device__ __forceinline__ void token_wait(int w) {
    asm volatile("{\n.reg .pred p;\nsetp.eq.u32 p, %0, 0;\n@p bar.sync 1, 256;\n@!p bar.sync 2, 256;\n}\n" ::"r"(w) : "memory");
}
__device__ __forceinline__ void token_pass(int w) {
    asm volatile("{\n.reg .pred p;\nsetp.eq.u32 p, %0, 0;\n@p bar.arrive 2, 256;\n@!p bar.arrive 1, 256;\n}\n" ::"r"(w) : "memory");
}
template <int N> __device__ __forceinline__ void fence_regs(float (&a)[N]) {
#pragma unroll
    for (int i = 0; i < N; i++) asm volatile("" : "+f"(a[i])::"memory");
}
template <int N> __device__ __forceinline__ void undef_regs(float (&a)[N]) {
#pragma unroll
    for (int i = 0; i < N; i++) asm volatile("" : "=f"(a[i]));
}
__device__ __forceinline__ void ldsm4t(uint32_t& r0, uint32_t& r1, uint32_t& r2, uint32_t& r3, uint32_t addr) {
    asm volatile("ldmatrix.sync.aligned.m8n8.x4.trans.shared.b16 {%0,%1,%2,%3}, [%4];"
                 : "=r"(r0), "=r"(r1), "=r"(r2), "=r"(r3) : "r"(addr) : "memory");
}
__device__ __forceinline__ uint32_t pack_bf16(float lo, float hi) {
    uint32_t r; asm("cvt.rn.bf16x2.f32 %0, %1, %2;" : "=r"(r) : "f"(hi), "f"(lo)); return r;
}
__device__ __forceinline__ float bf_lo(uint32_t v) { return __uint_as_float(v << 16); }
__device__ __forceinline__ float bf_hi(uint32_t v) { return __uint_as_float(v & 0xffff0000u); }
__device__ __forceinline__ float bf_round(float v) { return __bfloat162float(__float2bfloat16_rn(v)); }
__device__ __forceinline__ float ex2(float v) { float r; asm("ex2.approx.ftz.f32 %0, %1;" : "=f"(r) : "f"(v)); return r; }
__device__ __forceinline__ void ex2v(float& v) { asm volatile("ex2.approx.ftz.f32 %0, %0;" : "+f"(v)); }
__device__ __forceinline__ float rcp_fast(float v) { float r; asm("rcp.approx.ftz.f32 %0, %1;" : "=f"(r) : "f"(v)); return r; }
__device__ __forceinline__ float sqrt_fast(float v) { float r; asm("sqrt.approx.ftz.f32 %0, %1;" : "=f"(r) : "f"(v)); return r; }
__device__ __forceinline__ void stg128(void* p, uint32_t a, uint32_t b, uint32_t c, uint32_t d) {
    asm volatile("st.global.v4.b32 [%0], {%1,%2,%3,%4};" ::"l"(p), "r"(a), "r"(b), "r"(c), "r"(d) : "memory");
}
__device__ __forceinline__ void stg128_hint(void* p, uint32_t a, uint32_t b, uint32_t c, uint32_t d, uint64_t pol) {
    asm volatile("st.global.L2::cache_hint.v4.b32 [%0], {%1,%2,%3,%4}, %5;" ::"l"(p), "r"(a), "r"(b), "r"(c), "r"(d), "l"(pol) : "memory");
}
__device__ __forceinline__ uint4 ldg128(const void* p) {
    uint4 v; asm volatile("ld.global.cg.v4.b32 {%0,%1,%2,%3}, [%4];" : "=r"(v.x), "=r"(v.y), "=r"(v.z), "=r"(v.w) : "l"(p) : "memory"); return v;
}
__device__ __forceinline__ uint64_t mkdesc(uint32_t addr, uint32_t lbo, uint32_t sbo, uint32_t swz) {
    uint32_t lo = ((addr & 0x3FFFF) >> 4) | ((lbo >> 4) << 16);
    uint32_t hi = (sbo >> 4) | (swz << 30);
    return ((uint64_t)hi << 32) | lo;
}
__device__ __forceinline__ int perm32(int v) { return (v & ~30) | ((v >> 2) & 6) | ((v << 2) & 24); }

__device__ __forceinline__ void wgmma_rs_n128_ta0_tb0(float (&d)[64], uint32_t a0, uint32_t a1, uint32_t a2, uint32_t a3, uint64_t descB, int scaleD) {
  asm volatile("{\n.reg .pred p;\nsetp.ne.b32 p, %69, 0;\n"
    "wgmma.mma_async.sync.aligned.m64n128k16.f32.bf16.bf16 "
    "{%0, %1, %2, %3, %4, %5, %6, %7, %8, %9, %10, %11, %12, %13, %14, %15, %16, %17, %18, %19, %20, %21, %22, %23, %24, %25, %26, %27, %28, %29, %30, %31, %32, %33, %34, %35, %36, %37, %38, %39, %40, %41, %42, %43, %44, %45, %46, %47, %48, %49, %50, %51, %52, %53, %54, %55, %56, %57, %58, %59, %60, %61, %62, %63}, "
    "{%64, %65, %66, %67}, %68, p, 1, 1, 0;\n}\n"
    : "+f"(d[0]), "+f"(d[1]), "+f"(d[2]), "+f"(d[3]), "+f"(d[4]), "+f"(d[5]), "+f"(d[6]), "+f"(d[7]), "+f"(d[8]), "+f"(d[9]), "+f"(d[10]), "+f"(d[11]), "+f"(d[12]), "+f"(d[13]), "+f"(d[14]), "+f"(d[15]), "+f"(d[16]), "+f"(d[17]), "+f"(d[18]), "+f"(d[19]), "+f"(d[20]), "+f"(d[21]), "+f"(d[22]), "+f"(d[23]), "+f"(d[24]), "+f"(d[25]), "+f"(d[26]), "+f"(d[27]), "+f"(d[28]), "+f"(d[29]), "+f"(d[30]), "+f"(d[31]), "+f"(d[32]), "+f"(d[33]), "+f"(d[34]), "+f"(d[35]), "+f"(d[36]), "+f"(d[37]), "+f"(d[38]), "+f"(d[39]), "+f"(d[40]), "+f"(d[41]), "+f"(d[42]), "+f"(d[43]), "+f"(d[44]), "+f"(d[45]), "+f"(d[46]), "+f"(d[47]), "+f"(d[48]), "+f"(d[49]), "+f"(d[50]), "+f"(d[51]), "+f"(d[52]), "+f"(d[53]), "+f"(d[54]), "+f"(d[55]), "+f"(d[56]), "+f"(d[57]), "+f"(d[58]), "+f"(d[59]), "+f"(d[60]), "+f"(d[61]), "+f"(d[62]), "+f"(d[63])
    : "r"(a0), "r"(a1), "r"(a2), "r"(a3), "l"(descB), "r"(scaleD));
}
__device__ __forceinline__ void wgmma_rs_n128_ta0_tb1(float (&d)[64], uint32_t a0, uint32_t a1, uint32_t a2, uint32_t a3, uint64_t descB, int scaleD) {
  asm volatile("{\n.reg .pred p;\nsetp.ne.b32 p, %69, 0;\n"
    "wgmma.mma_async.sync.aligned.m64n128k16.f32.bf16.bf16 "
    "{%0, %1, %2, %3, %4, %5, %6, %7, %8, %9, %10, %11, %12, %13, %14, %15, %16, %17, %18, %19, %20, %21, %22, %23, %24, %25, %26, %27, %28, %29, %30, %31, %32, %33, %34, %35, %36, %37, %38, %39, %40, %41, %42, %43, %44, %45, %46, %47, %48, %49, %50, %51, %52, %53, %54, %55, %56, %57, %58, %59, %60, %61, %62, %63}, "
    "{%64, %65, %66, %67}, %68, p, 1, 1, 1;\n}\n"
    : "+f"(d[0]), "+f"(d[1]), "+f"(d[2]), "+f"(d[3]), "+f"(d[4]), "+f"(d[5]), "+f"(d[6]), "+f"(d[7]), "+f"(d[8]), "+f"(d[9]), "+f"(d[10]), "+f"(d[11]), "+f"(d[12]), "+f"(d[13]), "+f"(d[14]), "+f"(d[15]), "+f"(d[16]), "+f"(d[17]), "+f"(d[18]), "+f"(d[19]), "+f"(d[20]), "+f"(d[21]), "+f"(d[22]), "+f"(d[23]), "+f"(d[24]), "+f"(d[25]), "+f"(d[26]), "+f"(d[27]), "+f"(d[28]), "+f"(d[29]), "+f"(d[30]), "+f"(d[31]), "+f"(d[32]), "+f"(d[33]), "+f"(d[34]), "+f"(d[35]), "+f"(d[36]), "+f"(d[37]), "+f"(d[38]), "+f"(d[39]), "+f"(d[40]), "+f"(d[41]), "+f"(d[42]), "+f"(d[43]), "+f"(d[44]), "+f"(d[45]), "+f"(d[46]), "+f"(d[47]), "+f"(d[48]), "+f"(d[49]), "+f"(d[50]), "+f"(d[51]), "+f"(d[52]), "+f"(d[53]), "+f"(d[54]), "+f"(d[55]), "+f"(d[56]), "+f"(d[57]), "+f"(d[58]), "+f"(d[59]), "+f"(d[60]), "+f"(d[61]), "+f"(d[62]), "+f"(d[63])
    : "r"(a0), "r"(a1), "r"(a2), "r"(a3), "l"(descB), "r"(scaleD));
}
__device__ __forceinline__ void wgmma_rs_n64_ta0_tb1(float (&d)[32], uint32_t a0, uint32_t a1, uint32_t a2, uint32_t a3, uint64_t descB, int scaleD) {
  asm volatile("{\n.reg .pred p;\nsetp.ne.b32 p, %37, 0;\n"
    "wgmma.mma_async.sync.aligned.m64n64k16.f32.bf16.bf16 "
    "{%0, %1, %2, %3, %4, %5, %6, %7, %8, %9, %10, %11, %12, %13, %14, %15, %16, %17, %18, %19, %20, %21, %22, %23, %24, %25, %26, %27, %28, %29, %30, %31}, "
    "{%32, %33, %34, %35}, %36, p, 1, 1, 1;\n}\n"
    : "+f"(d[0]), "+f"(d[1]), "+f"(d[2]), "+f"(d[3]), "+f"(d[4]), "+f"(d[5]), "+f"(d[6]), "+f"(d[7]), "+f"(d[8]), "+f"(d[9]), "+f"(d[10]), "+f"(d[11]), "+f"(d[12]), "+f"(d[13]), "+f"(d[14]), "+f"(d[15]), "+f"(d[16]), "+f"(d[17]), "+f"(d[18]), "+f"(d[19]), "+f"(d[20]), "+f"(d[21]), "+f"(d[22]), "+f"(d[23]), "+f"(d[24]), "+f"(d[25]), "+f"(d[26]), "+f"(d[27]), "+f"(d[28]), "+f"(d[29]), "+f"(d[30]), "+f"(d[31])
    : "r"(a0), "r"(a1), "r"(a2), "r"(a3), "l"(descB), "r"(scaleD));
}
__device__ __forceinline__ void wgmma_ss_n128_ta1_tb0(float (&d)[64], uint64_t descA, uint64_t descB, int scaleD) {
  asm volatile("{\n.reg .pred p;\nsetp.ne.b32 p, %66, 0;\n"
    "wgmma.mma_async.sync.aligned.m64n128k16.f32.bf16.bf16 "
    "{%0, %1, %2, %3, %4, %5, %6, %7, %8, %9, %10, %11, %12, %13, %14, %15, %16, %17, %18, %19, %20, %21, %22, %23, %24, %25, %26, %27, %28, %29, %30, %31, %32, %33, %34, %35, %36, %37, %38, %39, %40, %41, %42, %43, %44, %45, %46, %47, %48, %49, %50, %51, %52, %53, %54, %55, %56, %57, %58, %59, %60, %61, %62, %63}, "
    "%64, %65, p, 1, 1, 1, 0;\n}\n"
    : "+f"(d[0]), "+f"(d[1]), "+f"(d[2]), "+f"(d[3]), "+f"(d[4]), "+f"(d[5]), "+f"(d[6]), "+f"(d[7]), "+f"(d[8]), "+f"(d[9]), "+f"(d[10]), "+f"(d[11]), "+f"(d[12]), "+f"(d[13]), "+f"(d[14]), "+f"(d[15]), "+f"(d[16]), "+f"(d[17]), "+f"(d[18]), "+f"(d[19]), "+f"(d[20]), "+f"(d[21]), "+f"(d[22]), "+f"(d[23]), "+f"(d[24]), "+f"(d[25]), "+f"(d[26]), "+f"(d[27]), "+f"(d[28]), "+f"(d[29]), "+f"(d[30]), "+f"(d[31]), "+f"(d[32]), "+f"(d[33]), "+f"(d[34]), "+f"(d[35]), "+f"(d[36]), "+f"(d[37]), "+f"(d[38]), "+f"(d[39]), "+f"(d[40]), "+f"(d[41]), "+f"(d[42]), "+f"(d[43]), "+f"(d[44]), "+f"(d[45]), "+f"(d[46]), "+f"(d[47]), "+f"(d[48]), "+f"(d[49]), "+f"(d[50]), "+f"(d[51]), "+f"(d[52]), "+f"(d[53]), "+f"(d[54]), "+f"(d[55]), "+f"(d[56]), "+f"(d[57]), "+f"(d[58]), "+f"(d[59]), "+f"(d[60]), "+f"(d[61]), "+f"(d[62]), "+f"(d[63])
    : "l"(descA), "l"(descB), "r"(scaleD));
}
__device__ __forceinline__ void wgmma_ss_n160_ta0_tb1(float (&d)[80], uint64_t descA, uint64_t descB, int scaleD) {
  asm volatile("{\n.reg .pred p;\nsetp.ne.b32 p, %82, 0;\n"
    "wgmma.mma_async.sync.aligned.m64n160k16.f32.bf16.bf16 "
    "{%0, %1, %2, %3, %4, %5, %6, %7, %8, %9, %10, %11, %12, %13, %14, %15, %16, %17, %18, %19, %20, %21, %22, %23, %24, %25, %26, %27, %28, %29, %30, %31, %32, %33, %34, %35, %36, %37, %38, %39, %40, %41, %42, %43, %44, %45, %46, %47, %48, %49, %50, %51, %52, %53, %54, %55, %56, %57, %58, %59, %60, %61, %62, %63, %64, %65, %66, %67, %68, %69, %70, %71, %72, %73, %74, %75, %76, %77, %78, %79}, "
    "%80, %81, p, 1, 1, 0, 1;\n}\n"
    : "+f"(d[0]), "+f"(d[1]), "+f"(d[2]), "+f"(d[3]), "+f"(d[4]), "+f"(d[5]), "+f"(d[6]), "+f"(d[7]), "+f"(d[8]), "+f"(d[9]), "+f"(d[10]), "+f"(d[11]), "+f"(d[12]), "+f"(d[13]), "+f"(d[14]), "+f"(d[15]), "+f"(d[16]), "+f"(d[17]), "+f"(d[18]), "+f"(d[19]), "+f"(d[20]), "+f"(d[21]), "+f"(d[22]), "+f"(d[23]), "+f"(d[24]), "+f"(d[25]), "+f"(d[26]), "+f"(d[27]), "+f"(d[28]), "+f"(d[29]), "+f"(d[30]), "+f"(d[31]), "+f"(d[32]), "+f"(d[33]), "+f"(d[34]), "+f"(d[35]), "+f"(d[36]), "+f"(d[37]), "+f"(d[38]), "+f"(d[39]), "+f"(d[40]), "+f"(d[41]), "+f"(d[42]), "+f"(d[43]), "+f"(d[44]), "+f"(d[45]), "+f"(d[46]), "+f"(d[47]), "+f"(d[48]), "+f"(d[49]), "+f"(d[50]), "+f"(d[51]), "+f"(d[52]), "+f"(d[53]), "+f"(d[54]), "+f"(d[55]), "+f"(d[56]), "+f"(d[57]), "+f"(d[58]), "+f"(d[59]), "+f"(d[60]), "+f"(d[61]), "+f"(d[62]), "+f"(d[63]), "+f"(d[64]), "+f"(d[65]), "+f"(d[66]), "+f"(d[67]), "+f"(d[68]), "+f"(d[69]), "+f"(d[70]), "+f"(d[71]), "+f"(d[72]), "+f"(d[73]), "+f"(d[74]), "+f"(d[75]), "+f"(d[76]), "+f"(d[77]), "+f"(d[78]), "+f"(d[79])
    : "l"(descA), "l"(descB), "r"(scaleD));
}

#define PROF_DECL(b)
#define PROF_EV(tag)
#define PROF_GT(tag)

template <int N> struct IC { static constexpr int value = N; };
struct Cur {
    uint32_t slot, ph;
    __device__ __forceinline__ void adv() { if (++slot == NSLOT) { slot = 0; ph ^= 1; } }
};
constexpr int E0 = 6, E_ATT0 = 48, E_ATT1 = 108;
__host__ __device__ constexpr uint32_t slot_of(int e) { return (e + E0) % NSLOT; }
__device__ __forceinline__ Cur cur_at(int e) { Cur c; c.slot = (e + E0) % NSLOT; c.ph = ((e + E0) / NSLOT) & 1; return c; }

__device__ __forceinline__ int q_tile(int k, int t) { return (t < 2 ? 14 - 2 * k : 2 * k) + (t & 1); }
__device__ __forceinline__ int op_head(int i, int kap) { return 16 * kap + 2 * (i & 7) + (i >> 3); }

constexpr float SM_SCALE = 0.08838834764831845f * 1.4426950408889634f;

struct Ctx {
    uint32_t ring, misc;
    uint32_t rel;
    int w, warp, lane;
};
__device__ __forceinline__ void release(const Ctx& c, uint32_t off, uint32_t cnt) {
    if (c.lane < 2) mbar_arrive_cluster(c.rel + off, cnt);
}
__device__ __forceinline__ void signal_event(const Ctx& c, int ev) {
    __syncwarp();
    if (c.lane == 0) mbar_arrive(c.misc + BAR_EV + (c.w * 16 + ev) * 8);
}
template <int NK, int OFF, int N>
__device__ __forceinline__ uint32_t load_afrag(uint32_t (&a)[N], uint32_t base, const Ctx& c) {
    int r = c.lane & 7, mat = c.lane >> 3;
    uint32_t addr = base + (8 * (mat >> 1) + r) * 128 + (((2 * c.warp + (mat & 1)) ^ r) << 4);
#pragma unroll
    for (int k = 0; k < NK; k++) ldsm4t(a[OFF + 4 * k], a[OFF + 4 * k + 1], a[OFF + 4 * k + 2], a[OFF + 4 * k + 3], addr + k * 2048);
    uint32_t dep = 0;
#pragma unroll
    for (int k = 0; k < NK; k++) dep |= a[OFF + 4 * k];
    return dep & blockIdx.y;
}
__device__ __forceinline__ void store_proj(const float (&acc)[64], unsigned char* dst  , const Ctx& c, uint64_t pol) {
    int g = c.lane >> 2, t = c.lane & 3;
#pragma unroll
    for (int i = 0; i < 2; i++) {
        int row = perm32(64 * c.w + 16 * c.warp + 8 * i + g);
        unsigned char* p = dst + row * 128;
#pragma unroll
        for (int q = 0; q < 4; q++) {
            int chunk = (4 * (q & 1) + t) ^ (row & 7);
            stg128_hint(p + (q >> 1) * 16384 + chunk * 16,
                   pack_bf16(acc[16 * q + 2 * i], acc[16 * q + 2 * i + 1]), pack_bf16(acc[16 * q + 4 + 2 * i], acc[16 * q + 4 + 2 * i + 1]),
                   pack_bf16(acc[16 * q + 8 + 2 * i], acc[16 * q + 8 + 2 * i + 1]), pack_bf16(acc[16 * q + 12 + 2 * i], acc[16 * q + 12 + 2 * i + 1]), pol);
        }
    }
}

constexpr float SAFE_SUM = 1099511627776.0f;
template <int NJ>
__device__ __forceinline__ void row_max(const float (&s)[4 * NJ], float (&mx)[2]) {
#pragma unroll
    for (int i = 0; i < 2; i++) {
        float a = fmaxf(s[2 * i], s[2 * i + 1]), b = fmaxf(s[4 + 2 * i], s[4 + 2 * i + 1]);
#pragma unroll
        for (int j = 2; j < NJ; j += 2) {
            a = fmaxf(a, fmaxf(s[4 * j + 2 * i], s[4 * j + 2 * i + 1]));
            b = fmaxf(b, fmaxf(s[4 * j + 4 + 2 * i], s[4 * j + 4 + 2 * i + 1]));
        }
        a = fmaxf(a, b);
        a = fmaxf(a, __shfl_xor_sync(0xffffffffu, a, 1));
        mx[i] = fmaxf(a, __shfl_xor_sync(0xffffffffu, a, 2));
    }
}
template <int NJ, bool SHIFT>
__device__ __forceinline__ void exp_sum(float (&s)[4 * NJ], const float (&m)[2], float& l0, float& l1) {
#pragma unroll
    for (int j = 0; j < NJ; j++) {
#pragma unroll
        for (int e = 0; e < 4; e++) s[4 * j + e] = ex2(SHIFT ? s[4 * j + e] - m[e >> 1] : s[4 * j + e]);
        l0 += s[4 * j + 0] + s[4 * j + 1]; l1 += s[4 * j + 2] + s[4 * j + 3];
    }
}
__device__ __forceinline__ void recompute_scores(float (&s)[64], const unsigned char* qh, uint32_t kaddr, const Ctx& c) {
    const int r = c.lane & 7, mat = c.lane >> 3, g = c.lane >> 2, t = c.lane & 3;
    const uint32_t a0 = kaddr + (8 * (mat & 1) + r) * 128 + (((mat >> 1) ^ r) << 4);
    uint32_t q[32];
#pragma unroll
    for (int i = 0; i < 32; i++) {
        const uint32_t v = __ldcg(reinterpret_cast<const uint32_t*>(qh + (8 * (i >> 1) + g) * 128 + (((2 * c.warp + (i & 1)) ^ g) << 4) + 4 * t));
        asm volatile("movmatrix.sync.aligned.m8n8.trans.b16 %0, %1;" : "=r"(q[i]) : "r"(v));
    }
#pragma unroll
    for (int i = 0; i < 64; i++) s[i] = 0.f;
#pragma unroll
    for (int jp = 0; jp < 8; jp++) {
#pragma unroll
        for (int k = 0; k < 8; k++) {
            asm volatile(
                "{\n.reg .b32 b0, b1, b2, b3;\n"
                "ldmatrix.sync.aligned.m8n8.x4.trans.shared.b16 {b0,b1,b2,b3}, [%12];\n"
                "mma.sync.aligned.m16n8k16.row.col.f32.bf16.bf16.f32 {%0,%1,%2,%3}, {%8,%9,%10,%11}, {b0,b1}, {%0,%1,%2,%3};\n"
                "mma.sync.aligned.m16n8k16.row.col.f32.bf16.bf16.f32 {%4,%5,%6,%7}, {%8,%9,%10,%11}, {b2,b3}, {%4,%5,%6,%7};\n}\n"
                : "+f"(s[8 * jp]), "+f"(s[8 * jp + 1]), "+f"(s[8 * jp + 2]), "+f"(s[8 * jp + 3]),
                  "+f"(s[8 * jp + 4]), "+f"(s[8 * jp + 5]), "+f"(s[8 * jp + 6]), "+f"(s[8 * jp + 7])
                : "r"(q[4 * k]), "r"(q[4 * k + 1]), "r"(q[4 * k + 2]), "r"(q[4 * k + 3]),
                  "r"((a0 ^ ((jp & 3) << 5)) + (jp >> 2) * 16384 + k * 2048) : "memory");
        }
    }
}
__device__ __forceinline__ int mask_lim(const Ctx& c) { return perm32(16 * c.warp + (c.lane >> 2)) - 8 * (c.lane & 3); }
template <int J0>
__device__ __forceinline__ void mask_diag(float (&s)[4 * J0 + 32], const Ctx& c) {
    const int lim = mask_lim(c);
    if (c.warp < 2) {
#pragma unroll
        for (int x = 0; x < 16; x++) {
            if (2 * (x >> 2) + (x & 1) - (x & 2) > lim) s[4 * J0 + x] = -INFINITY;
            s[4 * J0 + 16 + x] = -INFINITY;
        }
    } else {
#pragma unroll
        for (int x = 0; x < 16; x++)
            if (32 + 2 * (x >> 2) + (x & 1) - (x & 2) > lim) s[4 * J0 + 16 + x] = -INFINITY;
    }
}
__device__ __forceinline__ void mask_any(float (&s)[64], int hh, const Ctx& c) {
    const int lim = mask_lim(c) + 64 * hh;
#pragma unroll
    for (int x = 0; x < 64; x++)
        if (32 * (x >> 4) + 2 * ((x >> 2) & 3) + (x & 1) - (x & 2) > lim) s[x] = -INFINITY;
}
__device__ __forceinline__ void issue_pv(float (&o)[64], const uint32_t (&p)[32], uint32_t vaddr, int acc, int mode  ) {
    uint64_t d = mkdesc(vaddr, 16, 1024, 1);
    if (mode == 0) {
        wg_fence();
#pragma unroll
        for (int k = 0; k < 8; k++)
            wgmma_rs_n128_ta0_tb0(o, p[4 * k], p[4 * k + 1], p[4 * k + 2], p[4 * k + 3], d + (k >> 2) * 1024 + 2 * (k & 3), k ? 1 : acc);
        wg_commit();
    } else if (mode == 1) {
        wg_fence();
#pragma unroll
        for (int k = 0; k < 4; k++) wgmma_rs_n128_ta0_tb0(o, p[4 * k], p[4 * k + 1], p[4 * k + 2], p[4 * k + 3], d + 2 * k, k != 0);
        wg_commit();
    } else {
        wg_fence();
        wgmma_rs_n128_ta0_tb0(o, p[0], p[1], p[2], p[3], d, 0);
        wg_commit();
    }
}
__device__ __forceinline__ void issue_qk(float (&s)[64], const uint32_t (&q)[32], uint32_t kaddr) {
    uint64_t d = mkdesc(kaddr, 16384, 1024, 1);
    wg_fence();
#pragma unroll
    for (int k = 0; k < 8; k++) wgmma_rs_n128_ta0_tb1(s, q[4 * k], q[4 * k + 1], q[4 * k + 2], q[4 * k + 3], d + 128 * k, k != 0);
    wg_commit();
}
__device__ __forceinline__ void issue_qk_half(float (&s32)[32], const uint32_t (&q)[32], uint32_t kaddr) {
    uint64_t d = mkdesc(kaddr, 16384, 1024, 1);
    wg_fence();
#pragma unroll
    for (int k = 0; k < 8; k++) wgmma_rs_n64_ta0_tb1(s32, q[4 * k], q[4 * k + 1], q[4 * k + 2], q[4 * k + 3], d + 128 * k, k != 0);
    wg_commit();
}
template <int Q0, int Q1>
__device__ __forceinline__ void stage_ctx(float (&o)[64], const float (&inv)[2], Cur ce, const Ctx& c) {
    const int g = c.lane >> 2, t = c.lane & 3, r7 = ((g & 1) << 2) | (g >> 1);
    const uint32_t base = c.ring + ce.slot * SLOT_BYTES + c.w * 16384 + (16 * c.warp + r7) * 128 + ((t ^ r7) << 4);
    if (Q0 == 0) mbar_wait_hot(c.misc + BAR_FULL + 8 * ce.slot, ce.ph);
#pragma unroll
    for (int q = Q0; q < Q1; q++) {
        uint32_t v[8];
#pragma unroll
        for (int i = 0; i < 2; i++)
#pragma unroll
            for (int j = 0; j < 4; j++) v[4 * i + j] = pack_bf16(o[16 * q + 4 * j + 2 * i] * inv[i], o[16 * q + 4 * j + 2 * i + 1] * inv[i]);
#pragma unroll
        for (int i = 0; i < 8; i++) { o[16 * q + i] = __uint_as_float(v[i]); asm volatile("" : "=f"(o[16 * q + 8 + i])); }
#pragma unroll
        for (int i = 0; i < 2; i++)
            asm volatile("st.shared.v4.b32 [%0], {%1,%2,%3,%4};" ::"r"((base ^ ((q & 1) << 6)) + (q >> 1) * 8192 + i * 1024),
                         "r"(v[4 * i]), "r"(v[4 * i + 1]), "r"(v[4 * i + 2]), "r"(v[4 * i + 3]) : "memory");
    }
}
__device__ __forceinline__ void publish_ctx(int ev, const Ctx& c) {
    asm volatile("fence.proxy.async.shared::cta;" ::: "memory");
    signal_event(c, ev);
}

__device__ __forceinline__ const unsigned char* xn_addr(int row, int col) {
    return g_xn + ((row >> 7) * 10 + (col >> 6)) * 16384 + (row & 127) * 128 + ((((col & 63) >> 3) ^ (row & 7)) << 4);
}
__device__ __forceinline__ void mma16816(float (&d)[4], uint32_t a0, uint32_t a1, uint32_t a2, uint32_t a3, uint32_t b0, uint32_t b1) {
    asm volatile("mma.sync.aligned.m16n8k16.row.col.f32.bf16.bf16.f32 {%0,%1,%2,%3}, {%4,%5,%6,%7}, {%8,%9}, {%0,%1,%2,%3};"
                 : "+f"(d[0]), "+f"(d[1]), "+f"(d[2]), "+f"(d[3]) : "r"(a0), "r"(a1), "r"(a2), "r"(a3), "r"(b0), "r"(b1));
}
__device__ __forceinline__ uint32_t lds32(uint32_t addr) { uint32_t v; asm volatile("ld.shared.u32 %0, [%1];" : "=r"(v) : "r"(addr)); return v; }

__device__ __forceinline__ void ln_rows(const Params& P, int row0, int lane, uint32_t wr_s) {
    const int hl = lane & 15, row = row0 + (lane >> 4);
    uint32_t v[20];
#pragma unroll
    for (int i = 0; i < 5; i++) {
        uint4 u;
        asm("ld.global.nc.L2::cache_hint.v4.b32 {%0,%1,%2,%3}, [%4], %5;" : "=r"(u.x), "=r"(u.y), "=r"(u.z), "=r"(u.w)
            : "l"(P.x + (size_t)row * DM + 128 * i + 8 * hl), "l"(policy(HM & 512)));
        v[4 * i] = u.x; v[4 * i + 1] = u.y; v[4 * i + 2] = u.z; v[4 * i + 3] = u.w;
    }
    float mean = 0.f, m2 = 0.f, acc2 = 0.f;
#pragma unroll
    for (int i = 0; i < 20; i++) { mean += bf_lo(v[i]); acc2 += bf_hi(v[i]); }
    mean = (mean + acc2) * (1.0f / 40);
    acc2 = 0.f;
#pragma unroll
    for (int i = 0; i < 20; i++) {
        float d0 = __uint_as_float(__byte_perm(v[i], 0, 0x1044)) - mean, d1 = __uint_as_float(__byte_perm(v[i], 0, 0x3244)) - mean;
        m2 = fmaf(d0, d0, m2); acc2 = fmaf(d1, d1, acc2);
    }
    m2 += acc2;
    acc2 = 0.f;
#pragma unroll
    for (int o = 1; o < 16; o <<= 1) {
        float mo = __shfl_xor_sync(0xffffffffu, mean, o), qo = __shfl_xor_sync(0xffffffffu, m2, o), d = mo - mean;
        m2 = fmaf(d * d, 20.0f * o, m2 + qo);
        mean = 0.5f * (mean + mo);
    }
    const uint32_t mb2 = pack_bf16(mean, mean);
    const float inv = rcp_fast(bf_round(sqrt_fast(bf_round(bf_round(m2 * (1.0f / DM)) + 1e-5f))));
    float dot = 0.f;
    unsigned char* xp = g_xn + ((row >> 7) * 10 + (hl >> 3)) * 16384 + (row & 127) * 128 + (((hl & 7) ^ (row & 7)) << 4);
#pragma unroll
    for (int i = 0; i < 5; i++) {
        uint32_t ww[4];
        asm volatile("ld.shared.v4.b32 {%0,%1,%2,%3}, [%4];" : "=r"(ww[0]), "=r"(ww[1]), "=r"(ww[2]), "=r"(ww[3]) : "r"(wr_s + 256 * i + 16 * hl) : "memory");
#pragma unroll
        for (int e = 0; e < 4; e++) {
            uint32_t d;
            asm("sub.rn.bf16x2 %0, %1, %2;" : "=r"(d) : "r"(v[4 * i + e]), "r"(mb2));
            d = pack_bf16(bf_lo(d) * inv, bf_hi(d) * inv);
            v[4 * i + e] = d;
            dot = fmaf(bf_lo(d), bf_lo(ww[e]), dot);
            acc2 = fmaf(bf_hi(d), bf_hi(ww[e]), acc2);
        }
        stg128(xp + i * 32768, v[4 * i], v[4 * i + 1], v[4 * i + 2], v[4 * i + 3]);
    }
    dot += acc2;
#pragma unroll
    for (int o = 8; o > 0; o >>= 1) dot += __shfl_xor_sync(0xffffffffu, dot, o);
    if (hl == 0) { g_router[row] = bf_round(dot); g_stats[row] = make_uint2(mb2, __float_as_uint(inv)); }
}

__device__ __forceinline__ void aux_cta(const Params& P, const CUtensorMap* tmG, const CUtensorMap* tmU, const CUtensorMap* tmD, unsigned char* sm, int a) {
    constexpr int STG = 57344, XS = 3 * STG, HS = XS + 8 * 1296, KEY = HS + 8 * 912, MI = KEY + 8192;
    const int tid = threadIdx.x, warp = __shfl_sync(0xffffffffu, tid >> 5, 0), lane = tid & 31;
    const uint32_t sb = smem_u32(sm);
    const uint32_t full = sb + MI, empty = sb + MI + 32;
    int* s_sel = reinterpret_cast<int*>(sm + MI + 64);
    float* s_r = reinterpret_cast<float*>(sm + MI + 96);
    volatile unsigned* s_misc = reinterpret_cast<volatile unsigned*>(sm + MI + 128);
    uint32_t* s_key = reinterpret_cast<uint32_t*>(sm + KEY);
    PROF_DECL(128 + a)
    PROF_GT(0);
    if (tid == 0) {
        for (int i = 0; i < 3; i++) { mbar_init(full + 8 * i, 1); mbar_init(empty + 8 * i, 10); }
        asm volatile("fence.mbarrier_init.release.cluster;" ::: "memory");
    }
    __syncthreads();
    if (warp == 11) {
        if (elect_one()) {
            int st = 0; uint32_t ph = 0;
#pragma unroll 1
            for (int s = 0; s < 34; s++) {
                mbar_wait(empty + 8 * st, ph ^ 1);
                const uint32_t dst = sb + st * STG, fb = full + 8 * st;
                if (s < 20) {
                    mbar_expect_tx(fb, 57344);
                    tma3d(dst, tmG, 0, 32 * s, 7 * a, fb);
                    tma3d(dst + 28672, tmU, 0, 32 * s, 7 * a, fb);
                } else {
                    mbar_expect_tx(fb, 40960);
                    tma3d(dst, tmD, 0, 448 * a + 32 * (s - 20), 0, fb);
                }
                if (s >= 3) {
#pragma unroll 1
                    for (int f = (s == 3 ? 4 : s + 6); f <= s + 6 && f < 34; f++) {
                        if (f < 20) { tma3d_prefetch(tmG, 0, 32 * f, 7 * a); tma3d_prefetch(tmU, 0, 32 * f, 7 * a); }
                        else tma3d_prefetch(tmD, 0, 448 * a + 32 * (f - 20), 0);
                    }
                }
                if (++st == 3) { st = 0; ph ^= 1; }
            }
        }
        return;
    }
    if (tid < 80) *reinterpret_cast<uint4*>(sm + KEY + 1024 + tid * 16) = __ldg(reinterpret_cast<const uint4*>(P.wr) + tid);
    __nanosleep(AUXDELAY);
#pragma unroll 1
    for (int i = tid; i < 128 * 40; i += 352) asm volatile("prefetch.global.L2 [%0];" ::"l"(P.x + (size_t)(2 * a + 1) * 128 * DM + i * 16));
    bar_sync(2, 352);
#pragma unroll 1
    for (int i = warp; i < 64; i += 11) ln_rows(P, (2 * a + 1) * 128 + 2 * i, lane, sb + KEY + 1024);
    bar_sync(2, 352);
    if (tid == 320) asm volatile("red.release.gpu.global.add.u32 [%0], 32;" ::"l"(flag_ptr(FL_LN + 2 * a + 1)) : "memory");
    PROF_GT(49);
    if (warp == 10) return;
    if (tid < 16) {
        unsigned e = *reinterpret_cast<volatile unsigned*>(&g_epoch);
        if (tid == 0) s_misc[0] = e;
        flag_wait(flag_ptr(FL_LN + tid), (e + 1) * 32u);
    }
    bar_sync(1, 320);
    PROF_GT(50);
    const unsigned ep = s_misc[0];
    auto top8 = [&](uint32_t (&key)[8]) {
        uint32_t mine = 0;
#pragma unroll 1
        for (int r = 0; r < TOPC; r++) {
            uint32_t best = 0;
#pragma unroll
            for (int i = 0; i < 8; i++) best = max(best, key[i]);
            best = __reduce_max_sync(0xffffffffu, best);
#pragma unroll
            for (int i = 0; i < 8; i++) if (key[i] == best) key[i] = 0;
            if (lane == r) mine = best;
        }
        return mine;
    };
#pragma unroll 1
    for (int pass = 0; pass < 2; pass++) {
        if (warp < (pass ? 1 : 8)) {
            uint32_t key[8];
#pragma unroll
            for (int i = 0; i < 8; i++) {
                if (pass == 0) {
                    int idx = warp * 256 + i * 32 + lane;
                    uint32_t b = __float_as_uint(__ldcg(g_router + idx)) >> 16;
                    b = (b & 0x8000u) ? (~b & 0xffffu) : (b | 0x8000u);
                    key[i] = (b << 16) | (uint32_t)(0xffff - idx);
                } else key[i] = i < 2 ? s_key[i * 32 + lane] : 0u;
            }
            uint32_t best = top8(key);
            if (lane < TOPC) {
                if (pass == 0) s_key[warp * 8 + lane] = best;
                else {
                    uint32_t b = best >> 16;
                    b = (b & 0x8000u) ? (b & 0x7fffu) : (~b & 0xffffu);
                    s_sel[lane] = 0xffff - (int)(best & 0xffffu);
                    s_r[lane] = __uint_as_float(b << 16);
                }
            }
        }
        bar_sync(1, 320);
    }
#pragma unroll
    for (int it = 0; it < 2; it++) {
        int i = tid + it * 320, tk = i / 80, ch = i % 80;
        *reinterpret_cast<uint4*>(sm + XS + tk * 1296 + ch * 16) = __ldcg(reinterpret_cast<const uint4*>(xn_addr(s_sel[tk], ch * 8)));
    }
    bar_sync(1, 320);
    PROF_GT(51);
    const int g = lane >> 2, t = lane & 3;
    const uint32_t woff = warp * 4096 + (8 * (lane >> 4) + (lane & 7)) * 128 + ((((lane >> 3) & 1) ^ (lane & 7)) << 4);
    int st = 0; uint32_t ph = 0;
    float ga[4][4], ua[4][4];
#pragma unroll
    for (int i = 0; i < 4; i++)
#pragma unroll
        for (int e = 0; e < 4; e++) { ga[i][e] = 0.f; ua[i][e] = 0.f; }
#pragma unroll 1
    for (int s = 0; s < 34; s++) {
        if (s == 20) {
            if (warp < 7) {
#pragma unroll
                for (int i = 0; i < 4; i++)
#pragma unroll
                    for (int e = 0; e < 4; e++) {
                        float gv = bf_round(ga[i][e]), uv = bf_round(ua[i][e]);
                        float sg = bf_round(__fdividef(gv, 1.0f + __expf(fminf(-gv, 80.f))));
                        int f = warp * 64 + i * 16 + g + 8 * (e >> 1), tk = 2 * t + (e & 1);
                        *reinterpret_cast<__nv_bfloat16*>(sm + HS + tk * 912 + f * 2) = __float2bfloat16_rn(sg * uv);
                        ga[i][e] = 0.f;
                    }
            }
            bar_sync(1, 320);
            PROF_GT(52);
        }
        mbar_wait(full + 8 * st, ph);
        if (s >= 20 || warp < 7) {
#pragma unroll
            for (int kk = 0; kk < 2; kk++) {
                uint32_t xb = sb + (s < 20 ? XS + g * 1296 + s * 64 : HS + g * 912 + (s - 20) * 64) + 32 * kk + 4 * t;
                uint32_t b0 = lds32(xb), b1 = lds32(xb + 16);
                uint32_t wa = sb + st * STG + woff + kk * 2048;
#pragma unroll
                for (int i = 0; i < 4; i++) {
                    uint32_t a0, a1, a2, a3;
                    ldsm4t(a0, a1, a2, a3, wa ^ (i << 5));
                    mma16816(ga[i], a0, a1, a2, a3, b0, b1);
                    if (s < 20) {
                        ldsm4t(a0, a1, a2, a3, (wa ^ (i << 5)) + 28672);
                        mma16816(ua[i], a0, a1, a2, a3, b0, b1);
                    }
                }
            }
        }
        asm volatile("fence.proxy.async.shared::cta;" ::: "memory");
        __syncwarp();
        if (lane == 0) mbar_arrive(empty + 8 * st);
        if (++st == 3) { st = 0; ph ^= 1; }
    }
#pragma unroll
    for (int i = 0; i < 4; i++)
#pragma unroll
        for (int e = 0; e < 4; e += 2)
            *reinterpret_cast<float2*>(g_moe_part + (a * DM + warp * 64 + i * 16 + g + 4 * e) * 8 + 2 * t) = make_float2(ga[i][e], ga[i][e + 1]);
    bar_sync(1, 320);
    if (tid == 0) {
        __threadfence();
        unsigned old = atomicAdd(flag_ptr(FL_MOE_CNT), 1u);
        s_misc[1] = (old == ep * 4u + 3u);
        __threadfence();
    }
    bar_sync(1, 320);
    PROF_GT(53);
    if (s_misc[1]) {
        const float4* pp = reinterpret_cast<const float4*>(g_moe_part);
#pragma unroll 2
        for (int i = tid; i < DM * 2; i += 320) {
            float4 v0 = __ldcg(pp + i), v1 = __ldcg(pp + DM * 2 + i), v2 = __ldcg(pp + DM * 4 + i), v3 = __ldcg(pp + DM * 6 + i);
            float y[4] = {v0.x + v1.x + v2.x + v3.x, v0.y + v1.y + v2.y + v3.y, v0.z + v1.z + v2.z + v3.z, v0.w + v1.w + v2.w + v3.w};
#pragma unroll
            for (int e = 0; e < 4; e++) {
                int col = i >> 1, tk = (i & 1) * 4 + e;
                float sg = bf_round(__fdividef(1.0f, 1.0f + __expf(fminf(-s_r[tk], 80.f))));
                float upd = bf_round(bf_round(y[e]) * sg);
                float xn = __bfloat162float(*reinterpret_cast<const __nv_bfloat16*>(sm + XS + tk * 1296 + col * 2));
                g_brow[tk * DM + col] = __float2bfloat16_rn(xn + upd);
            }
        }
        if (tid < TOPC) g_sel[tid] = s_sel[tid];
        bar_sync(1, 320);
        if (tid == 0) {
            flag_signal(flag_ptr(FL_MOE_DONE));
            *reinterpret_cast<volatile unsigned*>(&g_epoch) = ep + 1;
        }
        PROF_GT(54);
    }
}

__global__ void __cluster_dims__(2, 1, 1) __launch_bounds__(384, 1)
fused_kernel(const __grid_constant__ CUtensorMap tmC, const __grid_constant__ CUtensorMap tmWk, const __grid_constant__ CUtensorMap tmWv,
             const __grid_constant__ CUtensorMap tmWq, const __grid_constant__ CUtensorMap tmWo,
             const __grid_constant__ CUtensorMap tmG, const __grid_constant__ CUtensorMap tmU, const __grid_constant__ CUtensorMap tmD, const Params P) {
    extern __shared__ __align__(1024) unsigned char smem_raw[];
    const uint32_t ring = smem_u32(smem_raw);
    const uint32_t misc = ring + RING_BYTES;
    const int tid = threadIdx.x;
    const int rank = blockIdx.x & 1;
    uint32_t smid; asm("mov.u32 %0, %%smid;" : "=r"(smid));
    const int tpc = smid >> 1;
    const int mc = tpc < 32 ? (tpc & 7) * 8 + (tpc >> 3) : tpc < 60 ? (1 + (tpc - 32) % 7) * 8 + 4 + (tpc - 32) / 7 : tpc < 64 ? tpc - 56 : tpc;
    const int cta = mc * 2 + rank;
    if (mc >= 64) { aux_cta(P, &tmG, &tmU, &tmD, smem_raw, cta - 128); return; }
    PROF_DECL(cta)
    PROF_GT(0); PROF_EV(1);
    const int team = mc >> 2, k = mc & 3;
    const int u3 = (mc >> 4) * 2 + (team & 1), s3 = k, kap = (mc >> 3) & 1;
    const int partner = cta ^ 16;

    if (tid >= 128) {
        const int i = tid - 128;
        if (i < 128) asm volatile("prefetch.global.L2 [%0];" ::"l"(P.c + (size_t)((12 + k) * 128 + (team * 2 + rank) * 4) * DC + i * 16));
    }
    auto prefetch_w = [&](int ch) {
        const int i = tid - 128;
        asm volatile("prefetch.global.L2 [%0];" ::"l"((rank ? P.wv : P.wk) + (size_t)(ch * 128 + k * 32 + (i >> 3)) * 4096 + team * 256 + (i & 7) * 16));
    };
    if (tid >= 128) { if (PFV & 1) prefetch_w(0); if (PFV & 2) prefetch_w(1); }
    if (tid == 0) {
#pragma unroll
        for (int i = 0; i < NSLOT; i++) mbar_init(misc + BAR_FULL + 8 * i, 1);
#pragma unroll
        for (int i = 0; i < E0; i++) mbar_arrive(misc + BAR_FULL + 8 * i);
        asm volatile("fence.mbarrier_init.release.cluster;" ::: "memory");
        const CUtensorMap* tw = rank ? &tmWv : &tmWk;
        mbar_expect_tx(misc + BAR_FULL + 8 * slot_of(0), SLOT_BYTES);
        tma2d(ring + slot_of(0) * SLOT_BYTES, tw, team * 256, 0, misc + BAR_FULL + 8 * slot_of(0), policy(HM & 1));
        tma2d(ring + slot_of(0) * SLOT_BYTES + 16384, tw, team * 256 + 64, 0, misc + BAR_FULL + 8 * slot_of(0), policy(HM & 1));
    }
    if (tid == 32) {
        asm volatile("prefetch.tensormap [%0];" ::"l"(&tmC) : "memory");
#pragma unroll
        for (int i = 0; i < NSLOT; i++) mbar_init(misc + BAR_EMPTY + 8 * i, 16);
#pragma unroll
        for (int i = 0; i < E0; i++) mbar_arrive_cluster(misc + BAR_EMPTY + 8 * i, 16);
        asm volatile("fence.mbarrier_init.release.cluster;" ::: "memory");
    }
    if (tid == 64) {
#pragma unroll
        for (int i = 0; i < NST3; i++) { mbar_init(misc + BAR_FULL3 + 8 * i, 1); mbar_init(misc + BAR_EMPTY3 + 8 * i, 16); }
#pragma unroll
        for (int i = 0; i < 4; i++) mbar_init(misc + BAR_LN + 8 * i, 2);
        mbar_init(misc + BAR_PROG, 1); mbar_init(misc + BAR_PROG + 8, 1); mbar_init(misc + BAR_PROG + 16, 1);
        asm volatile("fence.mbarrier_init.release.cluster;" ::: "memory");
    }
    if (tid == 96) {
#pragma unroll
        for (int i = 0; i < 34; i++) mbar_init(misc + BAR_DEP + 8 * i, 1);
    }
    if (tid == 128) {
#pragma unroll
        for (int i = 0; i < 32; i++) mbar_init(misc + BAR_EV + 8 * i, 4);
    }
    __syncthreads();
    asm volatile("barrier.cluster.arrive.relaxed.aligned;\nbarrier.cluster.wait.aligned;" ::: "memory");
    if (tid >= 128) { if (PFV & 4) prefetch_w(1); if (PFV & 8) prefetch_w(2); }
    if (tid == 256) {
        const CUtensorMap* tw = rank ? &tmWv : &tmWk;
#pragma unroll
        for (int e = 1; e < NSLOT; e++) {
            const uint32_t fb = misc + BAR_FULL + 8 * slot_of(e), dst = ring + slot_of(e) * SLOT_BYTES;
            mbar_expect_tx(fb, SLOT_BYTES);
            if (e & 1) tma2d_mc(dst + rank * 16384, &tmC, (e >> 1) * 128 + rank * 64, (12 + k) * 128, fb, policy(false));
            else { tma2d(dst, tw, team * 256, e * 64, fb, policy(false)); tma2d(dst + 16384, tw, team * 256 + 64, e * 64, fb, policy(false)); }
        }
    }
    PROF_EV(5);
    const int wg = __shfl_sync(0xffffffffu, tid >> 7, 0);

    if (wg == 0) {
        asm volatile("setmaxnreg.dec.sync.aligned.u32 40;");
        const int warp = __shfl_sync(0xffffffffu, tid >> 5, 0), lane = tid & 31;
        if (warp == 0) {
            const bool lead = elect_one();
            Cur c = cur_at(NSLOT);
            uint32_t dst, fb;
            auto acquire = [&]() {
                mbar_wait(misc + BAR_EMPTY + 8 * c.slot, c.ph ^ 1);
                fb = misc + BAR_FULL + 8 * c.slot; dst = ring + c.slot * SLOT_BYTES;
                if (lead) mbar_expect_tx(fb, SLOT_BYTES);
                c.adv();
            };
            auto load_w = [&](const CUtensorMap* tm, int col, int row, bool stream) {
                acquire();
                if (lead) { tma2d(dst, tm, col, row, fb, policy(stream)); tma2d(dst + 16384, tm, col + 64, row, fb, policy(stream)); }
            };
            auto load_half = [&](const unsigned char* src, bool stream) {
                acquire();
                if (lead) bulk_load_mc(dst + rank * 16384, src, 16384, fb, policy(stream));
            };
            auto staging = [&]() {
                mbar_wait(misc + BAR_EMPTY + 8 * c.slot, c.ph ^ 1);
                if (lead) mbar_arrive(misc + BAR_FULL + 8 * c.slot);
                c.adv();
            };
            auto dep_wait = [&](int d) { mbar_wait(misc + BAR_DEP + 8 * d, 0); fence_async_global(); };
            auto op_prefetch = [&](int i) {
                const int head = op_head(i, kap);
                l2_prefetch(reinterpret_cast<const unsigned char*>(P.wo) + head * 163840 + (u3 * 8 + s3 * 2 + rank) * 2560, 2560);
                if (i < 8) l2_prefetch(g_Q + (size_t)(head * 32 + 4 * u3 + 2 * rank) * 16384 + s3 * 8192, 8192);
            };
            const CUtensorMap* tw = rank ? &tmWv : &tmWk;
            const unsigned char* Kh = g_K + (size_t)team * 32 * 16384 + rank * 16384;
            const unsigned char* Vh = g_V + (size_t)team * 32 * 16384 + rank * 16384;
#pragma unroll 1
            for (int v = 0; v < 2; v++) {
                const int h = 2 * team + v;
#pragma unroll 1
                for (int i = v ? 0 : 3; i < 16; i++) {
                    if (i < 4 && v) load_w(tw, h * 128, i * 128, HM & 1);
                    if (v && (i & 7) == 3) dep_wait(D_WAR + (i >> 3));
                    acquire();
                    if (lead) tma2d_mc(dst + rank * 16384, &tmC, (i & 3) * 128 + rank * 64, (12 - (i & 12) + k) * 128, fb, policy(HM & 2));
                    if (v && i == 2 && lead) mbar_arrive(misc + BAR_PROG + 8);
                }
                if (v == 0) {
                    const int cq = (h + rank) * 128;
                    load_w(&tmWq, cq, 0, HM & 1); load_w(&tmWq, cq, 128, HM & 1); load_w(&tmWq, cq, 256, HM & 1);
#pragma unroll 1
                    for (int t = 0; t < 4; t++) {
                        const unsigned char* xt = g_xn + (q_tile(k, t) * 10 + rank) * 16384;
                        dep_wait(D_LN + t);
                        if (t == 3 && lead) l2_prefetch((rank ? Vh - 16384 : Kh) + (13 - 2 * k) * 32768, 3 * 32768);
#pragma unroll 1
                        for (int ch = 0; ch < 5; ch++) {
                            load_half(xt + ch * 32768, HM & 4);
                            if (t == 0 && ch == 0) load_w(&tmWq, cq, 384, HM & 1);
                        }
                        load_w(&tmWq, cq, 512, (HM & 1) && t == 3);
                    }
                }
                int togo = v ? PF_START : 11;
#pragma unroll 1
                for (int r = 0; r < 2; r++) {
                    const int p = r ? k : 7 - k, n = 2 * p + 1;
                    if (v == 0) dep_wait(D_Q + r);
                    acquire();
                    if (lead) {
                        const int g0 = r ? rank : 3 - rank;
                        bulk_load(dst, g_Q + (size_t)(h * 32 + 4 * p + g0) * 16384, 16384, fb, policy(HM & 8));
                        bulk_load(dst + 16384, g_Q + (size_t)(h * 32 + 4 * p + 3 - g0) * 16384, 16384, fb, policy(HM & 8));
                    }
                    if (v && r == 0) dep_wait(D_KV + 4 + (k >> 1));
                    load_half(Kh + n * 32768, HM & 16);
                    if (r) { load_half(Vh, HM & 16); staging(); }
#pragma unroll 1
                    for (int j = n - 1; j >= 0; j--) {
                        if (v && r == 0 && (j & 3) == 3) dep_wait(D_KV + 7 - (j >> 2));
                        load_half(Kh + j * 32768, HM & 16); load_half(Vh + (j + 1) * 32768, HM & 16);
                        if (v == 0 && r == 0 && j == 3 && lead) mbar_arrive(misc + BAR_PROG);
                        --togo;
                        if (v == 0 && togo == 0 && lead) {
                            tma2d_prefetch(tw, h * 128 + 128, k * 128); tma2d_prefetch(tw, h * 128 + 192, k * 128);
                            l2_prefetch(reinterpret_cast<const unsigned char*>(P.c) + (size_t)cta * 16384, 16384);
                        }
                        if (v && togo <= 0 && togo > -OP_PF && lead) op_prefetch(-togo);
                    }
                }
                load_half(Vh, HM & 16);
                staging();
                if (v == 0 && lead) l2_prefetch(g_Q + (size_t)((h + 1) * 32 + 8 * k + 4 * rank) * 16384, 65536);
            }
            mbar_wait(misc + BAR_EMPTY + 8 * c.slot, c.ph ^ 1); c.adv();
            int st = 0; uint32_t ph3 = 0;
#pragma unroll 1
            for (int i = 0; i < 32; i++) {
                const int head = op_head(i >> 1, kap);
                if ((i & 1) == 0) dep_wait(D_CTX + (i >> 1));
                if (i < NST3) { mbar_wait(misc + BAR_EMPTY + 8 * c.slot, c.ph ^ 1); c.adv(); }
                else mbar_wait(misc + BAR_EMPTY3 + 8 * st, ph3 ^ 1);
                fb = misc + BAR_FULL3 + 8 * st; dst = ring + st * ST3_BYTES;
                if (i == LATE_AT && lead) mbar_arrive(misc + BAR_PROG + 16);
                if (lead) {
                    mbar_expect_tx(fb, ST3_BYTES);
                    const unsigned char* src = g_Q + (size_t)(head * 32 + 4 * u3 + 2 * rank) * 16384 + (i & 1) * 8192;
                    bulk_load(dst, src, 8192, fb, policy(HM & 32));
                    bulk_load(dst + 8192, src + 16384, 8192, fb, policy(HM & 32));
                    tma3d_mc(dst + 16384 + rank * 10240, &tmWo, 0, head * 128 + (i & 1) * 64 + rank * 32, 5 * s3, fb, policy(HM & 32));
                    if ((i & 1) && (i >> 1) + OP_PF < 16) op_prefetch((i >> 1) + OP_PF);
                }
                if (++st == NST3) { st = 0; ph3 ^= 1; }
            }
        } else if (warp == 3) {
            const unsigned ep1 = *reinterpret_cast<volatile unsigned*>(&g_epoch) + 1;
            if (lane == 0) {
                asm volatile("st.shared.u32 [%0], %1;" ::"r"(misc + MISC_EPOCH), "r"(ep1) : "memory");
                if (CDELAY) __nanosleep(CDELAY);
                l2_prefetch(reinterpret_cast<const unsigned char*>(P.c) + (size_t)cta * 12288, 12288);
#pragma unroll 1
                for (int t = 0; t < 4; t++) {
                    if (t == 1) {
                        mbar_wait(misc + BAR_PF, 0);
                        l2_prefetch(reinterpret_cast<const unsigned char*>(P.wq) + (size_t)cta * 40960, 40960);
                    }
                    if (t < 3) {
                        mbar_wait(misc + BAR_LN + 8 * t, 0);
                        flag_signal(flag_ptr(FL_LN + q_tile(cta >> 5, t)));
                    }
                    flag_wait(flag_ptr(FL_LN + q_tile(k, t)), ep1 * 32u);
                    mbar_arrive(misc + BAR_DEP + 8 * (D_LN + t));
                }
                mbar_wait(misc + BAR_EV + 8 * (16 + EV_KV + 3), 0);
                flag_wait(flag_ptr(FL_KV + team * 8), ep1 * 16u);
#pragma unroll 1
                for (int i = 0; i < 2; i++) {
                    mbar_wait(misc + BAR_EV + 8 * (16 + EV_Q + 1 + 2 * i), 0);
                    flag_wait(flag_ptr(FL_Q + team * 8 + (i ? k : 7 - k)), ep1 * 4u);
                    mbar_arrive(misc + BAR_DEP + 8 * (D_Q + i));
                }
#pragma unroll 1
                for (int i = 0; i < 2; i++) {
                    mbar_wait(misc + BAR_PROG + 8 * i, 0);
                    flag_signal(flag_ptr(FL_WAR + 2 * team + i));
                    flag_wait(flag_ptr(FL_WAR + 2 * team + i), ep1 * 8u);
                    mbar_arrive(misc + BAR_DEP + 8 * (D_WAR + i));
                }
#pragma unroll 1
                for (int i = 4; i < 8; i++) {
                    mbar_wait(misc + BAR_EV + 8 * (16 + EV_KV + i), 0);
                    flag_wait(flag_ptr(FL_KV + team * 8 + i), ep1 * 16u);
                    mbar_arrive(misc + BAR_DEP + 8 * (D_KV + i));
                }
                flag_wait(flag_ptr(FL_MOE_DONE), ep1);
                int4 s0 = __ldcg(reinterpret_cast<const int4*>(g_sel)), s1 = __ldcg(reinterpret_cast<const int4*>(g_sel) + 1);
                asm volatile("st.shared.v4.u32 [%0], {%1,%2,%3,%4};" ::"r"(misc + MISC_SEL), "r"(s0.x), "r"(s0.y), "r"(s0.z), "r"(s0.w) : "memory");
                asm volatile("st.shared.v4.u32 [%0], {%1,%2,%3,%4};" ::"r"(misc + MISC_SEL + 16), "r"(s1.x), "r"(s1.y), "r"(s1.z), "r"(s1.w) : "memory");
                mbar_arrive(misc + BAR_SEL);
            }
            __syncwarp();
            const unsigned* cf = flag_ptr(FL_CTX + op_head(lane & 15, kap) * 8 + u3);
#pragma unroll 1
            for (int half = 0; half < 2; half++) {
                if (half) mbar_wait(misc + BAR_EV + 8 * (EV_CTX + 3), 0);
                bool done = (lane >> 3) != half;
                for (int spin = 0; spin < 4000000; spin++) {
                    if (!done) {
                        unsigned v;
                        asm volatile("ld.acquire.gpu.global.u32 %0, [%1];" : "=r"(v) : "l"(cf) : "memory");
                        if ((int)(v - ep1 * 4u) >= 0) { mbar_arrive(misc + BAR_DEP + 8 * (D_CTX + lane)); done = true; }
                    }
                    if (__all_sync(0xffffffffu, done)) break;
                    __nanosleep(64);
                }
            }
        } else {
            const int w = warp - 1;
            if (lane < 20) {
#pragma unroll
                for (int i = 0; i < 2; i++) {
                    const int ch = w * 40 + i * 20 + lane;
                    uint4 u = __ldg(reinterpret_cast<const uint4*>(P.wr) + ch);
                    asm volatile("st.shared.v4.b32 [%0], {%1,%2,%3,%4};" ::"r"(misc + MISC_WR + 16 * ch), "r"(u.x), "r"(u.y), "r"(u.z), "r"(u.w) : "memory");
                }
            }
            const int rsub = (cta & 31) * 4 + 2 * w;
            if (LNDELAY) __nanosleep(LNDELAY);
            bar_sync(3, 64);
#pragma unroll 1
            for (int t = 0; t < 3; t++) {
                if (t < 2) {
#pragma unroll
                    for (int i = 0; i < 3; i++)
                        if (i * 32 + lane < 80) asm volatile("prefetch.global.L2 [%0];" ::"l"(P.x + (size_t)(q_tile(cta >> 5, t + 1) * 128 + rsub) * DM + (i * 32 + lane) * 16));
                }
                ln_rows(P, q_tile(cta >> 5, t) * 128 + rsub, lane, misc + MISC_WR);
                __syncwarp();
                if (lane == 0) mbar_arrive(misc + BAR_LN + 8 * t);
            }
            if (lane == 0) {
                const uint32_t eb = misc + BAR_EV + w * 128;
#pragma unroll 1
                for (int v = 0; v < 2; v++) {
#pragma unroll 1
                    for (int i = 0; i < (v ? 4 : 3); i++) {
                        mbar_wait(eb + 8 * (v ? EV_KV + 4 + i : i ? EV_Q + 2 * i - 1 : EV_KV + 3), 0);
                        flag_signal(flag_ptr(v ? FL_KV + team * 8 + 4 + i : i ? FL_Q + team * 8 + (i == 1 ? 7 - k : k) : FL_KV + team * 8));
                    }
#pragma unroll 1
                    for (int r = 0; r < 2; r++) {
                        const int p = r ? k : 7 - k;
                        const uint32_t slot = ((v ? E_ATT1 : E_ATT0) + (r ? 39 : 4 * p + 7) + E0) % NSLOT;
                        const int grp = (r == w) ? 3 - rank : rank;
                        mbar_wait(eb + 8 * (EV_CTX + 2 * v + r), 0);
                        asm volatile("cp.async.bulk.global.shared::cta.bulk_group.L2::cache_hint [%0], [%1], 16384, %2;"
                                     ::"l"(g_Q + (size_t)((2 * team + v) * 32 + 4 * p + grp) * 16384), "r"(ring + slot * SLOT_BYTES + w * 16384),
                                       "l"(policy((HM & 256) && v == 0)) : "memory");
                        asm volatile("cp.async.bulk.commit_group;" ::: "memory");
                        asm volatile("cp.async.bulk.wait_group.read 0;" ::: "memory");
                        mbar_arrive_cluster(mapa(misc + BAR_EMPTY + 8 * slot, 0), 4);
                        mbar_arrive_cluster(mapa(misc + BAR_EMPTY + 8 * slot, 1), 4);
                        asm volatile("cp.async.bulk.wait_group 0;" ::: "memory");
                        fence_async_global();
                        flag_signal(flag_ptr(FL_CTX + (2 * team + v) * 8 + p));
                    }
                }
            }
            __syncwarp();
            mbar_wait(misc + BAR_PROG + 16, 0);
            const int row = (2 * u3 + rank) * 128 + 64 * w + perm32(16 * (lane >> 3) + 8 * kap + (lane & 7));
#pragma unroll
            for (int i = 0; i < 10; i++) asm volatile("prefetch.global.L2 [%0];" ::"l"(P.x + (size_t)row * DM + 160 * s3 + 16 * i));
            asm volatile("prefetch.global.L2 [%0];" ::"l"(g_stats + row));
        }
    } else {
        asm volatile("setmaxnreg.inc.sync.aligned.u32 232;");
        Ctx c;
        c.ring = ring; c.misc = misc; c.w = wg - 1; c.warp = __shfl_sync(0xffffffffu, (tid >> 5) & 3, 0); c.lane = tid & 31;
        c.rel = mapa(misc, tid & 1);
        const int w = c.w;
        if (w == 1) bar_arrive(1, 256);
        if (PFV & 16) prefetch_w(2);
        prefetch_w(3);
        Cur cur = cur_at(0);
        float o[64], inv[2];
#pragma unroll 1
        for (int v = 0; v < 2; v++) {
        {
            uint32_t wf[128];
            float acc[64];
#pragma unroll
            for (int i = 32; i < 128; i++) wf[i] = 0u;
            Cur cw = cur;
            int wstep = 2;
            auto load_wchunk = [&](auto CH) {
                constexpr int ch = decltype(CH)::value;
                mbar_wait_hot(misc + BAR_FULL + 8 * cw.slot, cw.ph);
                const uint32_t z = load_afrag<8, 32 * ch>(wf, ring + cw.slot * SLOT_BYTES + w * 16384, c);
                release(c, BAR_EMPTY + 8 * cw.slot + z, 1);
                cw.adv();
                if (wstep == 2 || ch == 2) cw.adv();
            };
            load_wchunk(IC<0>{});
            cur.adv();
            int nload = 1;
            PROF_EV(2); PROF_GT(60);
#pragma unroll 1
            for (int t = 0; t < (v ? 4 : 8); t++) {
                uint32_t last = 0;
                token_wait(w);
                PROF_EV(t < 4 ? 10 : 20);
                undef_regs(acc);
                auto chunk = [&](auto CH) {
                    constexpr int ch = decltype(CH)::value;
                    mbar_wait_hot(misc + BAR_FULL + 8 * cur.slot, cur.ph);
                    if (t == 0 || t == 4) { PROF_EV(12 + ch); }
                    uint64_t d = mkdesc(ring + cur.slot * SLOT_BYTES, 16, 1024, 1);
                    wg_fence();
#pragma unroll
                    for (int ks = 0; ks < 8; ks++)
                        wgmma_rs_n128_ta0_tb0(acc, wf[32 * ch + 4 * ks], wf[32 * ch + 4 * ks + 1], wf[32 * ch + 4 * ks + 2], wf[32 * ch + 4 * ks + 3],
                                              d + (ks >> 2) * 1024 + (ks & 3) * 2, (ch | ks) != 0);
                    wg_commit();
                    const bool swap = (ch < 2 && t == 0) || (ch == 3 && t < 4);
                    if (swap) token_pass(w);
                    if constexpr (ch < 3) { if (nload == ch + 1) { load_wchunk(IC<ch + 1>{}); nload++; } }
                    if (ch > 0) { wg_wait<1>(); release(c, BAR_EMPTY + 8 * last, 1); }
                    last = cur.slot;
                    cur.adv();
                    if ((ch < 3 && t == 0) || (ch == 0 && t == 4)) cur.adv();
                    if (ch < 2 && swap) token_wait(w);
                };
                chunk(IC<0>{}); chunk(IC<1>{}); chunk(IC<2>{}); chunk(IC<3>{});
                if (t < 4) {
                    wg_wait<0>();
                    release(c, BAR_EMPTY + 8 * last, 1);
                } else {
                    Cur cx = cur; cur.adv();
                    mbar_wait_hot(misc + BAR_FULL + 8 * cx.slot, cx.ph);
                    mbar_wait_hot(misc + BAR_FULL + 8 * cur.slot, cur.ph);
                    uint64_t db = mkdesc(ring + cx.slot * SLOT_BYTES, 16, 1024, 1);
                    uint64_t da = mkdesc(ring + cur.slot * SLOT_BYTES + w * 16384, 16384, 1024, 1);
                    wg_fence();
#pragma unroll
                    for (int ks = 0; ks < 8; ks++) wgmma_ss_n128_ta1_tb0(acc, da + 128 * ks, db + (ks >> 2) * 1024 + (ks & 3) * 2, 1);
                    wg_commit();
                    token_pass(w);
                    wg_wait<1>(); release(c, BAR_EMPTY + 8 * last, 1);
                    wg_wait<0>(); release(c, BAR_EMPTY + 8 * cx.slot, 1); release(c, BAR_EMPTY + 8 * cur.slot, 1);
                    cur.adv();
                    fence_regs(acc);
#pragma unroll
                    for (int i = 0; i < 64; i++) acc[i] *= SM_SCALE;
                }
                PROF_EV(t < 4 ? 11 : 21);
                fence_regs(acc);
                if (t == 0 && v == 0 && tid == 128) mbar_arrive(misc + BAR_PF);
                const bool wswitch = t == 3 && v == 0;
                if (wswitch) {
                    cw = cur; wstep = 1; nload = 0;
                    cur.adv(); cur.adv(); cur.adv();
                    if (w) { load_wchunk(IC<0>{}); load_wchunk(IC<1>{}); load_wchunk(IC<2>{}); nload = 3; }
                }
                unsigned char* dst = t < 4 ? (rank ? g_V : g_K) + (size_t)(team * 32 + 24 + 2 * k - 8 * t) * 16384
                                           : g_Q + (size_t)((2 * team + rank) * 32 + q_tile(k, t & 3) * 2) * 16384;
                store_proj(acc, dst, c, policy(((HM & 64) && t >= 4 && rank) || ((HM & 128) && t >= 6)));
                signal_event(c, t < 4 ? EV_KV + 4 * v + t : EV_Q + t - 4);
                if (wswitch) {
                    if (w) { load_wchunk(IC<3>{}); nload = 4; }
                    else { load_wchunk(IC<0>{}); load_wchunk(IC<1>{}); nload = 2; }
                }
                if (t == 3) { PROF_EV(61); PROF_GT(62); }
            }
        }
        PROF_EV(63); PROF_GT(64);
        {
            uint32_t q[32], p[32];
            float m[2], l[2], tq[2];
#pragma unroll
            for (int i = 0; i < 64; i++) o[i] = 0.f;
#pragma unroll
            for (int i = 0; i < 32; i++) p[i] = 0u;
            m[0] = m[1] = inv[0] = inv[1] = 0.f;
            l[0] = l[1] = tq[0] = tq[1] = 1.f;
            int gen = 0;
            Cur ck = cur, cv = cur, cq, ce;
            int r = 0, left;
            int first = 1, half, heavy;
            int pv_acc = 0, pv_mode = 2; uint32_t pv_cnt = 0;
            int pending = 0;
            Cur nck, ncv;
            auto next_task = [&](int rr) {
                heavy = 1 ^ rr ^ w;
                half = 1 ^ heavy ^ rank;
                left = 2 * (rr ? k : 7 - k) + 1 + heavy;
                cq = cur; cur.adv();
                nck = cur; cur.adv();
                if (rr) { ncv = cur; cur.adv(); ce = cur; cur.adv(); }
                if (!heavy) { nck = cur; cur.adv(); cur.adv(); }
                if (!rr) { ncv = nck; ce = nck; }
            };
            auto load_q = [&]() {
                mbar_wait_hot(misc + BAR_FULL + 8 * cq.slot, cq.ph);
                load_afrag<8, 0>(q, ring + cq.slot * SLOT_BYTES + w * 16384, c);
            };
            next_task(0);
            load_q();
            uint32_t k_cnt = 1; int last = 0, was_first = 0, was_half = 0, publish = 0;
            auto window = [&]() {
                mbar_wait_hot(misc + BAR_FULL + 8 * cv.slot, cv.ph);
                publish = pending;
                if (pending) stage_ctx<2, 4>(o, inv, ce, c);
                pending = 0;
                k_cnt = 1;
                was_first = first; was_half = half;
                if (first) {
                    release(c, BAR_EMPTY + 8 * cq.slot, 1);
                    l[0] += tq[0]; l[1] += tq[1];
                    tq[0] = __shfl_xor_sync(0xffffffffu, l[0], 2); tq[1] = __shfl_xor_sync(0xffffffffu, l[1], 2);
                    pending = r;
                    k_cnt = 1 + heavy;
                }
                last = --left == 0 ? 1 : 0;
                first = last;
                if (!last) { nck = cur; cur.adv(); ncv = cur; cur.adv(); half = 0; }
                else if (++r < 2) next_task(1);
            };
            auto new_rows = [&]() {
                inv[0] = rcp_fast(l[0] + tq[0]); inv[1] = rcp_fast(l[1] + tq[1]);
                l[0] = l[1] = m[0] = m[1] = 0.f;
                gen = 0;
            };
            ck = nck; cv = ncv;
            mbar_wait_hot(misc + BAR_FULL + 8 * ck.slot, ck.ph);
            uint32_t qaddr1 = ring + (((v ? E_ATT1 : E_ATT0) + 32 - 4 * k + E0) % NSLOT) * SLOT_BYTES + w * 16384 +
                              (8 * (c.lane >> 4) + (c.lane & 7)) * 128 + (((2 * c.warp + ((c.lane >> 3) & 1)) ^ (c.lane & 7)) << 4);
            qaddr1 = __shfl_sync(0xffffffffu, qaddr1, c.lane);
#pragma unroll 1
            while (r < 2) {
                float s[64];
                if (half) {
                    token_wait(w);
                    PROF_EV(30);
                    float sh[32];
                    undef_regs(sh);
                    issue_qk_half(sh, q, ring + ck.slot * SLOT_BYTES);
                    window();
                    issue_pv(o, p, ring + cv.slot * SLOT_BYTES, pv_acc, pv_mode);
                    token_pass(w);
                    wg_wait<1>();
                    PROF_EV(34);
                    fence_regs(sh);
                    new_rows();
                    mask_diag<0>(sh, c);
                    float l0 = 0.f, l1 = 0.f;
                    if (blockIdx.y == 0) {
#pragma unroll
                        for (int j = 0; j < 8; j++) {
#pragma unroll
                            for (int e = 0; e < 4; e++) ex2v(sh[4 * j + e]);
                            l0 += sh[4 * j] + sh[4 * j + 1]; l1 += sh[4 * j + 2] + sh[4 * j + 3];
                        }
                    }
                    const int lim = mask_lim(c);
                    const bool bad = __any_sync(0xffffffffu, !(l0 <= SAFE_SUM && l1 <= SAFE_SUM && (l0 >= 1.0f / SAFE_SUM || lim < 0) &&
                                                               (l1 >= 1.0f / SAFE_SUM || lim < -2)));
                    if (!bad) { l[0] = l0; l[1] = l1; asm volatile("" ::: "memory"); }
                    wg_wait<0>();
                    fence_regs(o);
                    fence_regs(sh);
                    if (bad) goto redo;
#pragma unroll
                    for (int i = 0; i < 16; i++) p[i] = pack_bf16(sh[2 * i], sh[2 * i + 1]);
                    goto tail;
                }
#pragma unroll 1
                while (true) {
                    token_wait(w);
                    PROF_EV(first ? 30 : 31);
                    undef_regs(s);
                    issue_qk(s, q, ring + ck.slot * SLOT_BYTES);
                    const bool special = first > 0 || pv_acc == 0 || left == 1;
                    if (special) window();
                    else {
                        nck = cur; cur.adv(); ncv = cur; cur.adv();
                        --left;
                        mbar_wait_hot(misc + BAR_FULL + 8 * cv.slot, cv.ph);
                    }
                    issue_pv(o, p, ring + cv.slot * SLOT_BYTES, pv_acc, pv_mode);
                    token_pass(w);
                    wg_wait<1>();
                    PROF_EV(33);
                    fence_regs(s);
                    float lo = 0.f;
                    if (special) {
                        if (last && r < 2) {
                            mbar_wait_hot(misc + BAR_FULL + 8 * cq.slot, cq.ph);
#pragma unroll
                            for (int ks = 0; ks < 8; ks++) ldsm4t(q[4 * ks], q[4 * ks + 1], q[4 * ks + 2], q[4 * ks + 3], qaddr1 + ks * 2048);
                        }
                        if (publish) publish_ctx(EV_CTX + 2 * v, c);
                        if (was_first) {
                            new_rows();
                            lo = 1.0f / SAFE_SUM;
                            mask_diag<8>(s, c);
                        }
                    }
                    constexpr int JB = 11;
                    float l0 = l[0], l1 = l[1];
                    if (!gen) {
#pragma unroll
                        for (int j = 0; j < JB; j++) {
#pragma unroll
                            for (int e = 0; e < 4; e++) ex2v(s[4 * j + e]);
                            if (j < JB - 1) { l0 += s[4 * j] + s[4 * j + 1]; l1 += s[4 * j + 2] + s[4 * j + 3]; }
                        }
                    }
                    wg_wait<0>();
                    fence_regs(o);
                    if (gen) goto general;
#pragma unroll
                    for (int j = JB - 1; j < 16; j++) {
                        if (j >= JB) {
#pragma unroll
                            for (int e = 0; e < 4; e++) ex2v(s[4 * j + e]);
                        }
                        l0 += s[4 * j] + s[4 * j + 1]; l1 += s[4 * j + 2] + s[4 * j + 3];
                    }
#pragma unroll
                    for (int i = 0; i < 32; i++) p[i] = pack_bf16(s[2 * i], s[2 * i + 1]);
                    if (__any_sync(0xffffffffu, !(l0 <= SAFE_SUM && l1 <= SAFE_SUM && l0 >= lo && l1 >= lo))) goto redo;
                    l[0] = l0; l[1] = l1;
                    if (special) goto tail;
                    release(c, BAR_EMPTY + 8 * ck.slot, 1);
                    release(c, BAR_EMPTY + 8 * cv.slot, 1);
                    ck = nck; cv = ncv;
                    mbar_wait_hot(misc + BAR_FULL + 8 * ck.slot, ck.ph);
                }
            redo:
                {
                    const int rr = r - last;
                    const int grp = (rr == w) ? 3 - rank : rank;
                    recompute_scores(s, g_Q + (size_t)((2 * team + v) * 32 + 4 * (rr ? k : 7 - k) + grp) * 16384, ring + ck.slot * SLOT_BYTES, c);
                    if (was_first) { mask_any(s, was_half ^ 1, c); m[0] = m[1] = -INFINITY; }
                    gen = 1;
                }
            general:
                {
                    float mx[2], alpha[2];
                    row_max<16>(s, mx);
#pragma unroll
                    for (int i = 0; i < 2; i++) {
                        mx[i] = fmaxf(mx[i], m[i]);
                        alpha[i] = was_first ? 1.0f : ex2(m[i] - mx[i]);
                        m[i] = mx[i];
                        l[i] *= alpha[i];
                    }
                    exp_sum<16, true>(s, m, l[0], l[1]);
#pragma unroll
                    for (int i = 0; i < 64; i++) o[i] *= alpha[(i >> 1) & 1];
#pragma unroll
                    for (int i = 0; i < 32; i++) p[i] = pack_bf16(s[2 * i], s[2 * i + 1]);
                }
            tail:
                release(c, BAR_EMPTY + 8 * ck.slot, k_cnt);
                if (pv_cnt) release(c, BAR_EMPTY + 8 * cv.slot, pv_cnt);
                pv_acc = was_first ^ 1; pv_mode = was_half; pv_cnt = k_cnt;
                if (r < 2) { ck = nck; cv = ncv; } else ck = cur;
                mbar_wait_hot(misc + BAR_FULL + 8 * ck.slot, ck.ph);
                if (pending) stage_ctx<0, 2>(o, inv, ce, c);
                if (last) { tq[0] = __shfl_xor_sync(0xffffffffu, l[0], 1); tq[1] = __shfl_xor_sync(0xffffffffu, l[1], 1); }
            }
            if (pending) { stage_ctx<2, 4>(o, inv, ce, c); publish_ctx(EV_CTX + 2 * v, c); }
            token_wait(w);
            PROF_EV(32);
            issue_pv(o, p, ring + cur.slot * SLOT_BYTES, pv_acc, pv_mode);
            if (w == 0 || v == 0) token_pass(w);
            l[0] += tq[0]; l[1] += tq[1];
            inv[0] = rcp_fast(l[0] + __shfl_xor_sync(0xffffffffu, l[0], 2));
            inv[1] = rcp_fast(l[1] + __shfl_xor_sync(0xffffffffu, l[1], 2));
            wg_wait<0>();
            release(c, BAR_EMPTY + 8 * cur.slot, pv_cnt);
            fence_regs(o);
            cur.adv();
            if (v == 0) { stage_ctx<0, 4>(o, inv, cur, c); publish_ctx(EV_CTX + 1, c); cur.adv(); }
        }
        }
        {
            float acc[80];
            undef_regs(acc);
            int st = 0, prev = 0; uint32_t ph3 = 0;
            auto op_stage = [&](int i) {
                mbar_wait(misc + BAR_FULL3 + 8 * st, ph3);
                PROF_EV(44);
                uint32_t base = ring + st * ST3_BYTES;
                uint64_t da = mkdesc(base + w * 8192, 16, 1024, 1);
                uint64_t db = mkdesc(base + 16384, 2048, 512, 2);
                wg_fence();
#pragma unroll
                for (int k = 0; k < 4; k++) wgmma_ss_n160_ta0_tb1(acc, da + 2 * k, db + (k >> 1) * 640 + (k & 1) * 64, k ? 1 : i);
                wg_commit();
                if (i > 0) { wg_wait<1>(); if (i <= 32 - NST3) release(c, BAR_EMPTY3 + 8 * prev, 1); }
                prev = st;
                if (++st == NST3) { st = 0; ph3 ^= 1; }
            };
            PROF_EV(40); PROF_GT(65);
            op_stage(0);
            stage_ctx<0, 4>(o, inv, cur, c);
            publish_ctx(EV_CTX + 3, c);
#pragma unroll 1
            for (int i = 1; i < 12; i++) op_stage(i);
            mbar_wait(misc + BAR_SEL, 0);
            const uint32_t tag = lds32(misc + MISC_EPOCH) & 1;
            const int g = c.lane >> 2, t = c.lane & 3;
            const int row = (2 * u3 + rank) * 128 + 64 * w + perm32(16 * c.warp + 8 * kap + (((g & 3) << 1) | (g >> 2)));
            const int col = 160 * s3 + 8 * t;
            int sel = -1;
#pragma unroll
            for (int i = 0; i < TOPC; i++) if ((int)lds32(misc + MISC_SEL + 4 * i) == row) sel = i;
            const int t256 = tid - 128;
            uint4* sendp = g_part + (size_t)cta * 2560 + t256;
            if (c.lane >= 30) stg128(sendp + 9 * 256, tag ^ 1, tag ^ 1, tag ^ 1, tag ^ 1);
#pragma unroll 1
            for (int i = 12; i < 32; i++) op_stage(i);
            uint4 xv[5], bv[5];
#pragma unroll
            for (int i = 0; i < 5; i++) xv[i] = ldg128(P.x + (size_t)row * DM + col + 32 * i);
            uint2 stat;
            asm volatile("ld.global.cg.v2.b32 {%0,%1}, [%2];" : "=r"(stat.x), "=r"(stat.y) : "l"(g_stats + row) : "memory");
            wg_wait<0>();
            fence_regs(acc);
            PROF_EV(41); PROF_GT(66);
            float keep[40];
#pragma unroll
            for (int j = 0; j < 10; j++) {
                uint32_t v0 = __float_as_uint(kap ? acc[8 * j + 0] : acc[8 * j + 2]), v1 = __float_as_uint(kap ? acc[8 * j + 1] : acc[8 * j + 3]);
                uint32_t v2 = __float_as_uint(kap ? acc[8 * j + 4] : acc[8 * j + 6]), v3 = __float_as_uint(kap ? acc[8 * j + 5] : acc[8 * j + 7]);
                asm volatile("st.relaxed.gpu.global.v4.b32 [%0], {%1,%2,%3,%4};" ::"l"(sendp + j * 256),
                             "r"((v0 & ~1u) | tag), "r"((v1 & ~1u) | tag), "r"((v2 & ~1u) | tag), "r"((v3 & ~1u) | tag) : "memory");
                keep[4 * j + 0] = kap ? acc[8 * j + 2] : acc[8 * j + 0]; keep[4 * j + 1] = kap ? acc[8 * j + 3] : acc[8 * j + 1];
                keep[4 * j + 2] = kap ? acc[8 * j + 6] : acc[8 * j + 4]; keep[4 * j + 3] = kap ? acc[8 * j + 7] : acc[8 * j + 5];
            }
            PROF_GT(67);
#pragma unroll
            for (int i = 0; i < 5; i++) {
                uint32_t xx[4] = {xv[i].x, xv[i].y, xv[i].z, xv[i].w};
#pragma unroll
                for (int e = 0; e < 4; e++) {
                    asm("sub.rn.bf16x2 %0, %0, %1;" : "+r"(xx[e]) : "r"(stat.x));
                    xx[e] = pack_bf16(bf_lo(xx[e]) * __uint_as_float(stat.y), bf_hi(xx[e]) * __uint_as_float(stat.y));
                }
                bv[i] = make_uint4(xx[0], xx[1], xx[2], xx[3]);
            }
            if (sel >= 0) {
#pragma unroll
                for (int i = 0; i < 5; i++) bv[i] = ldg128(g_brow + sel * DM + col + 32 * i);
            }
            const uint4* recvp = g_part + (size_t)partner * 2560 + t256;
            uint4 rv[10];
            int spins = 0;
            while (POLL1) {
                uint32_t v;
                asm volatile("ld.relaxed.gpu.global.b32 %0, [%1];" : "=r"(v) : "l"(recvp + 9 * 256 + (31 - c.lane)) : "memory");
                if (__all_sync(0xffffffffu, (v & 1u) == tag) || ++spins > 2000000) break;
            }
            PROF_GT(68);
            while (true) {
                uint32_t bad = 0u;
#pragma unroll
                for (int j = 0; j < 10; j++) {
                    asm volatile("ld.relaxed.gpu.global.v4.b32 {%0,%1,%2,%3}, [%4];"
                                 : "=r"(rv[j].x), "=r"(rv[j].y), "=r"(rv[j].z), "=r"(rv[j].w) : "l"(recvp + j * 256) : "memory");
                }
#pragma unroll
                for (int j = 0; j < 10; j++) {
                    rv[j].x ^= tag; rv[j].y ^= tag; rv[j].z ^= tag; rv[j].w ^= tag;
                    bad |= rv[j].x | rv[j].y | rv[j].z | rv[j].w;
                }
                if (__all_sync(0xffffffffu, (bad & 1u) == 0) || ++spins > 2000000) break;
            }
            PROF_GT(69);
            uint32_t pk[20];
#pragma unroll
            for (int j = 0; j < 10; j++) {
                pk[2 * j] = pack_bf16(keep[4 * j] + __uint_as_float(rv[j].x), keep[4 * j + 1] + __uint_as_float(rv[j].y));
                pk[2 * j + 1] = pack_bf16(keep[4 * j + 2] + __uint_as_float(rv[j].z), keep[4 * j + 3] + __uint_as_float(rv[j].w));
            }
#pragma unroll
            for (int i = 0; i < 5; i++) {
                uint32_t a0 = pk[4 * i], a1 = pk[4 * i + 1], a2 = pk[4 * i + 2], a3 = pk[4 * i + 3];
                uint32_t x0 = (t & 1) ? a0 : a1, x1 = (t & 1) ? a2 : a3;
                x0 = __shfl_xor_sync(0xffffffffu, x0, 1); x1 = __shfl_xor_sync(0xffffffffu, x1, 1);
                if (t & 1) { a0 = x0; a2 = x1; } else { a1 = x0; a3 = x1; }
                x0 = (t & 2) ? a0 : a2; x1 = (t & 2) ? a1 : a3;
                x0 = __shfl_xor_sync(0xffffffffu, x0, 2); x1 = __shfl_xor_sync(0xffffffffu, x1, 2);
                if (t & 2) { a0 = x0; a1 = x1; } else { a2 = x0; a3 = x1; }
                uint32_t av[4] = {a0, a1, a2, a3};
                uint32_t xx[4] = {xv[i].x, xv[i].y, xv[i].z, xv[i].w}, bb[4] = {bv[i].x, bv[i].y, bv[i].z, bv[i].w};
                uint32_t ov[4];
#pragma unroll
                for (int e = 0; e < 4; e++) {
                    asm("add.rn.bf16x2 %0, %1, %2;" : "=r"(ov[e]) : "r"(xx[e]), "r"(av[e]));
                    asm("add.rn.bf16x2 %0, %0, %1;" : "+r"(ov[e]) : "r"(bb[e]));
                }
                stg128(P.out + (size_t)row * DM + col + 32 * i, ov[0], ov[1], ov[2], ov[3]);
            }
            PROF_EV(42); PROF_GT(43);
        }
    }
}

typedef CUresult (*EncodeFn)(CUtensorMap*, CUtensorMapDataType, cuuint32_t, void*, const cuuint64_t*, const cuuint64_t*, const cuuint32_t*,
                             const cuuint32_t*, CUtensorMapInterleave, CUtensorMapSwizzle, CUtensorMapL2promotion, CUtensorMapFloatOOBfill);

void make_map2d(EncodeFn enc, CUtensorMap* tm, const void* p, uint64_t cols, uint64_t rows) {
    cuuint64_t gd[2] = {cols, rows}, gs[1] = {cols * 2};
    cuuint32_t box[2] = {64, 128}, es[2] = {1, 1};
    enc(tm, CU_TENSOR_MAP_DATA_TYPE_BFLOAT16, 2, const_cast<void*>(p), gd, gs, box, es, CU_TENSOR_MAP_INTERLEAVE_NONE,
        CU_TENSOR_MAP_SWIZZLE_128B, CU_TENSOR_MAP_L2_PROMOTION_L2_128B, CU_TENSOR_MAP_FLOAT_OOB_FILL_NONE);
}

void make_map3d(EncodeFn enc, CUtensorMap* tm, const void* p, uint64_t cols, uint64_t rows, uint32_t bw, uint32_t nb) {
    cuuint64_t gd[3] = {bw, rows, cols / bw}, gs[2] = {cols * 2, bw * 2};
    cuuint32_t box[3] = {bw, 32, nb}, es[3] = {1, 1, 1};
    enc(tm, CU_TENSOR_MAP_DATA_TYPE_BFLOAT16, 3, const_cast<void*>(p), gd, gs, box, es, CU_TENSOR_MAP_INTERLEAVE_NONE,
        bw == 64 ? CU_TENSOR_MAP_SWIZZLE_128B : CU_TENSOR_MAP_SWIZZLE_64B, CU_TENSOR_MAP_L2_PROMOTION_L2_128B, CU_TENSOR_MAP_FLOAT_OOB_FILL_NONE);
}

}

extern "C" void kernel_launch(void* const* d_in, const int* in_sizes, int n_in, void* d_out, int out_size) {
    (void)in_sizes; (void)n_in; (void)out_size;
    static EncodeFn enc = nullptr;
    if (!enc) {
        void* fn = nullptr;
        cudaDriverEntryPointQueryResult qr;
        cudaGetDriverEntryPoint("cuTensorMapEncodeTiled", &fn, cudaEnableDefault, &qr);
        enc = (EncodeFn)fn;
        cudaFuncSetAttribute(fused_kernel, cudaFuncAttributeMaxDynamicSharedMemorySize, SMEM_BYTES);
    }
    CUtensorMap tmC, tmWk, tmWv, tmWq, tmWo, tmG, tmU, tmD;
    make_map2d(enc, &tmC, d_in[1], DC, SEQ);
    make_map2d(enc, &tmWq, d_in[2], 4096, DM);
    make_map2d(enc, &tmWk, d_in[3], 4096, DC);
    make_map2d(enc, &tmWv, d_in[4], 4096, DC);
    make_map3d(enc, &tmWo, d_in[5], DM, 4096, 32, 5);
    make_map3d(enc, &tmG, d_in[8], FF, DM, 64, 7);
    make_map3d(enc, &tmU, d_in[9], FF, DM, 64, 7);
    make_map3d(enc, &tmD, d_in[10], DM, FF, 64, 10);
    Params P;
    P.x = (const __nv_bfloat16*)d_in[0];
    P.c = (const __nv_bfloat16*)d_in[1];
    P.wq = (const __nv_bfloat16*)d_in[2];
    P.wk = (const __nv_bfloat16*)d_in[3];
    P.wv = (const __nv_bfloat16*)d_in[4];
    P.wo = (const __nv_bfloat16*)d_in[5];
    P.wr = (const __nv_bfloat16*)d_in[7];
    P.out = (__nv_bfloat16*)d_out;
    fused_kernel<<<132, 384, SMEM_BYTES>>>(tmC, tmWk, tmWv, tmWq, tmWo, tmG, tmU, tmD, P);
}
```

```cpp
#include <cuda_runtime.h>
#include <cuda_bf16.h>
#include <cuda.h>
#include <stdint.h>

#define HM 960
#define POLL1 1
#define OP_PF 8
#define PF_START 9
#define LATE_AT 18
#define PFV 21
#define CDELAY 2000
#define LNDELAY 0
#define AUXDELAY 1000
#define FV 3
#define MAP 2
namespace {

constexpr int SEQ = 2048, NH = 32, DM = 640, DC = 512, FF = 1728, TOPC = 8;
constexpr int NSLOT = 7, SLOT_BYTES = 32768;
constexpr int NST3 = 6, ST3_BYTES = 36864;
constexpr int RING_BYTES = NSLOT * SLOT_BYTES;
constexpr int SMEM_BYTES = RING_BYTES + 3072;

constexpr int BAR_FULL = 96  , BAR_FULL3 = 152  , BAR_DEP = 200  , BAR_PF = 456, BAR_SEL = 464,
              BAR_LN = 472  , BAR_EV = 504  , BAR_EMPTY = 760  , BAR_EMPTY3 = 816  ,
              BAR_PROG = 864  , MISC_EPOCH = 896, MISC_SEL = 912, MISC_WR = 1024  ;
constexpr int D_LN = 0  , D_KV = 4  , D_Q = 12  , D_WAR = 14  , D_CTX = 16  ;
constexpr int EV_KV = 0  , EV_Q = 8  , EV_CTX = 12  ;

constexpr int FL_MOE_CNT = 0, FL_MOE_DONE = 1, FL_LN = 16  , FL_KV = 32  , FL_Q = 160  , FL_CTX = 416  , FL_WAR = 672  , FL_TOTAL = 704;

__device__ __align__(1024) unsigned char g_K[16 * 32 * 16384];
__device__ __align__(1024) unsigned char g_V[16 * 32 * 16384];
__device__ __align__(1024) unsigned char g_Q[NH * 32 * 16384];
__device__ __align__(1024) unsigned char g_xn[16 * 10 * 16384];
__device__ __align__(1024) uint4 g_part[128 * 10 * 256];
__device__ float g_router[SEQ];
__device__ uint2 g_stats[SEQ];
__device__ __align__(16) float g_moe_part[4 * TOPC * DM];
__device__ __align__(16) __nv_bfloat16 g_brow[TOPC * DM];
__device__ __align__(16) int g_sel[TOPC];
__device__ unsigned g_flags[FL_TOTAL * 8];
__device__ unsigned g_epoch;

struct Params {
    const __nv_bfloat16 *x, *c, *wr, *wq, *wk, *wv, *wo;
    __nv_bfloat16* out;
};

__device__ __forceinline__ uint32_t smem_u32(const void* p) { return (uint32_t)__cvta_generic_to_shared(p); }
__device__ __forceinline__ void mbar_init(uint32_t bar, int cnt) { asm volatile("mbarrier.init.shared::cta.b64 [%0], %1;" ::"r"(bar), "r"(cnt)); }
__device__ __forceinline__ void mbar_expect_tx(uint32_t bar, uint32_t bytes) {
    asm volatile("mbarrier.arrive.expect_tx.shared::cta.b64 _, [%0], %1;" ::"r"(bar), "r"(bytes) : "memory");
}
__device__ __forceinline__ void mbar_arrive(uint32_t bar) { asm volatile("mbarrier.arrive.shared::cta.b64 _, [%0];" ::"r"(bar) : "memory"); }
__device__ __forceinline__ void mbar_arrive_cluster(uint32_t cluster_addr, uint32_t cnt) {
    asm volatile("mbarrier.arrive.shared::cluster.b64 _, [%0], %1;" ::"r"(cluster_addr), "r"(cnt) : "memory");
}
__device__ __forceinline__ uint32_t mapa(uint32_t addr, uint32_t cta) {
    uint32_t r; asm("mapa.shared::cluster.u32 %0, %1, %2;" : "=r"(r) : "r"(addr), "r"(cta)); return r;
}
__device__ __forceinline__ void mbar_wait(uint32_t bar, uint32_t parity) {
    asm volatile(
        "{\n.reg .pred p;\n.reg .u32 n;\n"
        "mbarrier.try_wait.parity.shared::cta.b64 p, [%0], %1;\n"
        "@p bra DONE;\n"
        "mov.u32 n, 0;\n"
        "LAB_WAIT:\n"
        "mbarrier.try_wait.parity.shared::cta.b64 p, [%0], %1, 100000;\n"
        "@p bra DONE;\n"
        "add.u32 n, n, 1;\n"
        "setp.lt.u32 p, n, 200000;\n"
        "@p bra LAB_WAIT;\n"
        "trap;\n"
        "DONE:\n}\n" ::"r"(bar), "r"(parity) : "memory");
}
__device__ __forceinline__ void mbar_wait_hot(uint32_t bar, uint32_t parity) {
    asm volatile("{\n.reg .pred p;\nLAB_WAIT:\nmbarrier.try_wait.parity.shared::cta.b64 p, [%0], %1;\n@!p bra LAB_WAIT;\n}\n" ::"r"(bar), "r"(parity) : "memory");
}
__device__ __forceinline__ void flag_wait(const unsigned* flag, unsigned target) {
    asm volatile(
        "{\n.reg .pred p;\n.reg .u32 n, v;\n.reg .s32 d;\n"
        "mov.u32 n, 0;\n"
        "LAB_WAIT:\n"
        "ld.acquire.gpu.global.u32 v, [%0];\n"
        "sub.s32 d, v, %1;\n"
        "setp.ge.s32 p, d, 0;\n"
        "@p bra DONE;\n"
        "nanosleep.u32 40;\n"
        "add.u32 n, n, 1;\n"
        "setp.lt.u32 p, n, 3000000;\n"
        "@p bra LAB_WAIT;\n"
        "trap;\n"
        "DONE:\n}\n" ::"l"(flag), "r"(target) : "memory");
}
__device__ __forceinline__ void flag_signal(unsigned* flag) {
    asm volatile("red.release.gpu.global.add.u32 [%0], 1;" ::"l"(flag) : "memory");
}
__device__ __forceinline__ void fence_async_global() { asm volatile("fence.proxy.async.global;" ::: "memory"); }
__device__ __forceinline__ unsigned* flag_ptr(int idx) { return g_flags + idx * 8; }

__device__ __forceinline__ uint64_t policy_stream() {
    uint64_t p; asm("createpolicy.fractional.L2::evict_first.b64 %0, 1.0;" : "=l"(p)); return p;
}
__device__ __forceinline__ uint64_t policy_normal() { return 0x1000000000000000ull; }
__device__ __forceinline__ uint64_t policy(bool stream) { return stream ? policy_stream() : policy_normal(); }
__device__ __forceinline__ void bulk_load(uint32_t dst, const void* src, uint32_t bytes, uint32_t bar, uint64_t pol) {
    asm volatile("cp.async.bulk.shared::cluster.global.mbarrier::complete_tx::bytes.L2::cache_hint [%0], [%1], %2, [%3], %4;"
                 ::"r"(dst), "l"(src), "r"(bytes), "r"(bar), "l"(pol) : "memory");
}
__device__ __forceinline__ void bulk_load_mc(uint32_t dst, const void* src, uint32_t bytes, uint32_t bar, uint64_t pol) {
    asm volatile("cp.async.bulk.shared::cluster.global.mbarrier::complete_tx::bytes.multicast::cluster.L2::cache_hint [%0], [%1], %2, [%3], %4, %5;"
                 ::"r"(dst), "l"(src), "r"(bytes), "r"(bar), "h"((uint16_t)3), "l"(pol) : "memory");
}
__device__ __forceinline__ void tma2d(uint32_t dst, const CUtensorMap* tm, int c0, int c1, uint32_t bar, uint64_t pol) {
    asm volatile("cp.async.bulk.tensor.2d.shared::cluster.global.mbarrier::complete_tx::bytes.L2::cache_hint [%0], [%1, {%3, %4}], [%2], %5;"
                 ::"r"(dst), "l"(tm), "r"(bar), "r"(c0), "r"(c1), "l"(pol) : "memory");
}
__device__ __forceinline__ void tma2d_mc(uint32_t dst, const CUtensorMap* tm, int c0, int c1, uint32_t bar, uint64_t pol) {
    asm volatile("cp.async.bulk.tensor.2d.shared::cluster.global.mbarrier::complete_tx::bytes.multicast::cluster.L2::cache_hint [%0], [%1, {%3, %4}], [%2], %5, %6;"
                 ::"r"(dst), "l"(tm), "r"(bar), "r"(c0), "r"(c1), "h"((uint16_t)3), "l"(pol) : "memory");
}
__device__ __forceinline__ void tma3d_mc(uint32_t dst, const CUtensorMap* tm, int c0, int c1, int c2, uint32_t bar, uint64_t pol) {
    asm volatile("cp.async.bulk.tensor.3d.shared::cluster.global.mbarrier::complete_tx::bytes.multicast::cluster.L2::cache_hint [%0], [%1, {%3, %4, %5}], [%2], %6, %7;"
                 ::"r"(dst), "l"(tm), "r"(bar), "r"(c0), "r"(c1), "r"(c2), "h"((uint16_t)3), "l"(pol) : "memory");
}
__device__ __forceinline__ void tma3d(uint32_t dst, const CUtensorMap* tm, int c0, int c1, int c2, uint32_t bar) {
    asm volatile("cp.async.bulk.tensor.3d.shared::cluster.global.mbarrier::complete_tx::bytes.L2::cache_hint [%0], [%1, {%3, %4, %5}], [%2], %6;"
                 ::"r"(dst), "l"(tm), "r"(bar), "r"(c0), "r"(c1), "r"(c2), "l"(policy_stream()) : "memory");
}
__device__ __forceinline__ void tma2d_prefetch(const CUtensorMap* tm, int c0, int c1) {
    asm volatile("cp.async.bulk.prefetch.tensor.2d.L2.global [%0, {%1, %2}];" ::"l"(tm), "r"(c0), "r"(c1) : "memory");
}
__device__ __forceinline__ void tma3d_prefetch(const CUtensorMap* tm, int c0, int c1, int c2) {
    asm volatile("cp.async.bulk.prefetch.tensor.3d.L2.global [%0, {%1, %2, %3}];" ::"l"(tm), "r"(c0), "r"(c1), "r"(c2) : "memory");
}
__device__ __forceinline__ void l2_prefetch(const void* p, uint32_t bytes) {
    asm volatile("cp.async.bulk.prefetch.L2.global [%0], %1;" ::"l"(p), "r"(bytes) : "memory");
}
__device__ __forceinline__ bool elect_one() {
    uint32_t r; asm volatile("{\n.reg .pred p;\nelect.sync _|p, 0xffffffff;\nselp.u32 %0, 1, 0, p;\n}\n" : "=r"(r)); return r != 0;
}
__device__ __forceinline__ void wg_fence() { asm volatile("wgmma.fence.sync.aligned;" ::: "memory"); }
__device__ __forceinline__ void wg_commit() { asm volatile("wgmma.commit_group.sync.aligned;" ::: "memory"); }
template <int N> __device__ __forceinline__ void wg_wait() { asm volatile("wgmma.wait_group.sync.aligned %0;" ::"n"(N) : "memory"); }
__device__ __forceinline__ void bar_sync(int id, int n) { asm volatile("bar.sync %0, %1;" ::"r"(id), "r"(n) : "memory"); }
__device__ __forceinline__ void bar_arrive(int id, int n) { asm volatile("bar.arrive %0, %1;" ::"r"(id), "r"(n) : "memory"); }
__device__ __forceinline__ void token_wait(int w) {
    asm volatile("{\n.reg .pred p;\nsetp.eq.u32 p, %0, 0;\n@p bar.sync 1, 256;\n@!p bar.sync 2, 256;\n}\n" ::"r"(w) : "memory");
}
__device__ __forceinline__ void token_pass(int w) {
    asm volatile("{\n.reg .pred p;\nsetp.eq.u32 p, %0, 0;\n@p bar.arrive 2, 256;\n@!p bar.arrive 1, 256;\n}\n" ::"r"(w) : "memory");
}
template <int N> __device__ __forceinline__ void fence_regs(float (&a)[N]) {
#pragma unroll
    for (int i = 0; i < N; i++) asm volatile("" : "+f"(a[i])::"memory");
}
template <int N> __device__ __forceinline__ void undef_regs(float (&a)[N]) {
#pragma unroll
    for (int i = 0; i < N; i++) asm volatile("" : "=f"(a[i]));
}
__device__ __forceinline__ void ldsm4t(uint32_t& r0, uint32_t& r1, uint32_t& r2, uint32_t& r3, uint32_t addr) {
    asm volatile("ldmatrix.sync.aligned.m8n8.x4.trans.shared.b16 {%0,%1,%2,%3}, [%4];"
                 : "=r"(r0), "=r"(r1), "=r"(r2), "=r"(r3) : "r"(addr) : "memory");
}
__device__ __forceinline__ uint32_t pack_bf16(float lo, float hi) {
    uint32_t r; asm("cvt.rn.bf16x2.f32 %0, %1, %2;" : "=r"(r) : "f"(hi), "f"(lo)); return r;
}
__device__ __forceinline__ float bf_lo(uint32_t v) { return __uint_as_float(v << 16); }
__device__ __forceinline__ float bf_hi(uint32_t v) { return __uint_as_float(v & 0xffff0000u); }
__device__ __forceinline__ float bf_round(float v) { return __bfloat162float(__float2bfloat16_rn(v)); }
__device__ __forceinline__ float ex2(float v) { float r; asm("ex2.approx.ftz.f32 %0, %1;" : "=f"(r) : "f"(v)); return r; }
__device__ __forceinline__ void ex2v(float& v) { asm volatile("ex2.approx.ftz.f32 %0, %0;" : "+f"(v)); }
__device__ __forceinline__ float rcp_fast(float v) { float r; asm("rcp.approx.ftz.f32 %0, %1;" : "=f"(r) : "f"(v)); return r; }
__device__ __forceinline__ float sqrt_fast(float v) { float r; asm("sqrt.approx.ftz.f32 %0, %1;" : "=f"(r) : "f"(v)); return r; }
__device__ __forceinline__ void stg128(void* p, uint32_t a, uint32_t b, uint32_t c, uint32_t d) {
    asm volatile("st.global.v4.b32 [%0], {%1,%2,%3,%4};" ::"l"(p), "r"(a), "r"(b), "r"(c), "r"(d) : "memory");
}
__device__ __forceinline__ void stg128_hint(void* p, uint32_t a, uint32_t b, uint32_t c, uint32_t d, uint64_t pol) {
    asm volatile("st.global.L2::cache_hint.v4.b32 [%0], {%1,%2,%3,%4}, %5;" ::"l"(p), "r"(a), "r"(b), "r"(c), "r"(d), "l"(pol) : "memory");
}
__device__ __forceinline__ uint4 ldg128(const void* p) {
    uint4 v; asm volatile("ld.global.cg.v4.b32 {%0,%1,%2,%3}, [%4];" : "=r"(v.x), "=r"(v.y), "=r"(v.z), "=r"(v.w) : "l"(p) : "memory"); return v;
}
__device__ __forceinline__ uint64_t mkdesc(uint32_t addr, uint32_t lbo, uint32_t sbo, uint32_t swz) {
    uint32_t lo = ((addr & 0x3FFFF) >> 4) | ((lbo >> 4) << 16);
    uint32_t hi = (sbo >> 4) | (swz << 30);
    return ((uint64_t)hi << 32) | lo;
}
__device__ __forceinline__ int perm32(int v) { return (v & ~30) | ((v >> 2) & 6) | ((v << 2) & 24); }

__device__ __forceinline__ void wgmma_rs_n128_ta0_tb0(float (&d)[64], uint32_t a0, uint32_t a1, uint32_t a2, uint32_t a3, uint64_t descB, int scaleD) {
  asm volatile("{\n.reg .pred p;\nsetp.ne.b32 p, %69, 0;\n"
    "wgmma.mma_async.sync.aligned.m64n128k16.f32.bf16.bf16 "
    "{%0, %1, %2, %3, %4, %5, %6, %7, %8, %9, %10, %11, %12, %13, %14, %15, %16, %17, %18, %19, %20, %21, %22, %23, %24, %25, %26, %27, %28, %29, %30, %31, %32, %33, %34, %35, %36, %37, %38, %39, %40, %41, %42, %43, %44, %45, %46, %47, %48, %49, %50, %51, %52, %53, %54, %55, %56, %57, %58, %59, %60, %61, %62, %63}, "
    "{%64, %65, %66, %67}, %68, p, 1, 1, 0;\n}\n"
    : "+f"(d[0]), "+f"(d[1]), "+f"(d[2]), "+f"(d[3]), "+f"(d[4]), "+f"(d[5]), "+f"(d[6]), "+f"(d[7]), "+f"(d[8]), "+f"(d[9]), "+f"(d[10]), "+f"(d[11]), "+f"(d[12]), "+f"(d[13]), "+f"(d[14]), "+f"(d[15]), "+f"(d[16]), "+f"(d[17]), "+f"(d[18]), "+f"(d[19]), "+f"(d[20]), "+f"(d[21]), "+f"(d[22]), "+f"(d[23]), "+f"(d[24]), "+f"(d[25]), "+f"(d[26]), "+f"(d[27]), "+f"(d[28]), "+f"(d[29]), "+f"(d[30]), "+f"(d[31]), "+f"(d[32]), "+f"(d[33]), "+f"(d[34]), "+f"(d[35]), "+f"(d[36]), "+f"(d[37]), "+f"(d[38]), "+f"(d[39]), "+f"(d[40]), "+f"(d[41]), "+f"(d[42]), "+f"(d[43]), "+f"(d[44]), "+f"(d[45]), "+f"(d[46]), "+f"(d[47]), "+f"(d[48]), "+f"(d[49]), "+f"(d[50]), "+f"(d[51]), "+f"(d[52]), "+f"(d[53]), "+f"(d[54]), "+f"(d[55]), "+f"(d[56]), "+f"(d[57]), "+f"(d[58]), "+f"(d[59]), "+f"(d[60]), "+f"(d[61]), "+f"(d[62]), "+f"(d[63])
    : "r"(a0), "r"(a1), "r"(a2), "r"(a3), "l"(descB), "r"(scaleD));
}
__device__ __forceinline__ void wgmma_rs_n128_ta0_tb1(float (&d)[64], uint32_t a0, uint32_t a1, uint32_t a2, uint32_t a3, uint64_t descB, int scaleD) {
  asm volatile("{\n.reg .pred p;\nsetp.ne.b32 p, %69, 0;\n"
    "wgmma.mma_async.sync.aligned.m64n128k16.f32.bf16.bf16 "
    "{%0, %1, %2, %3, %4, %5, %6, %7, %8, %9, %10, %11, %12, %13, %14, %15, %16, %17, %18, %19, %20, %21, %22, %23, %24, %25, %26, %27, %28, %29, %30, %31, %32, %33, %34, %35, %36, %37, %38, %39, %40, %41, %42, %43, %44, %45, %46, %47, %48, %49, %50, %51, %52, %53, %54, %55, %56, %57, %58, %59, %60, %61, %62, %63}, "
    "{%64, %65, %66, %67}, %68, p, 1, 1, 1;\n}\n"
    : "+f"(d[0]), "+f"(d[1]), "+f"(d[2]), "+f"(d[3]), "+f"(d[4]), "+f"(d[5]), "+f"(d[6]), "+f"(d[7]), "+f"(d[8]), "+f"(d[9]), "+f"(d[10]), "+f"(d[11]), "+f"(d[12]), "+f"(d[13]), "+f"(d[14]), "+f"(d[15]), "+f"(d[16]), "+f"(d[17]), "+f"(d[18]), "+f"(d[19]), "+f"(d[20]), "+f"(d[21]), "+f"(d[22]), "+f"(d[23]), "+f"(d[24]), "+f"(d[25]), "+f"(d[26]), "+f"(d[27]), "+f"(d[28]), "+f"(d[29]), "+f"(d[30]), "+f"(d[31]), "+f"(d[32]), "+f"(d[33]), "+f"(d[34]), "+f"(d[35]), "+f"(d[36]), "+f"(d[37]), "+f"(d[38]), "+f"(d[39]), "+f"(d[40]), "+f"(d[41]), "+f"(d[42]), "+f"(d[43]), "+f"(d[44]), "+f"(d[45]), "+f"(d[46]), "+f"(d[47]), "+f"(d[48]), "+f"(d[49]), "+f"(d[50]), "+f"(d[51]), "+f"(d[52]), "+f"(d[53]), "+f"(d[54]), "+f"(d[55]), "+f"(d[56]), "+f"(d[57]), "+f"(d[58]), "+f"(d[59]), "+f"(d[60]), "+f"(d[61]), "+f"(d[62]), "+f"(d[63])
    : "r"(a0), "r"(a1), "r"(a2), "r"(a3), "l"(descB), "r"(scaleD));
}
__device__ __forceinline__ void wgmma_rs_n64_ta0_tb1(float (&d)[32], uint32_t a0, uint32_t a1, uint32_t a2, uint32_t a3, uint64_t descB, int scaleD) {
  asm volatile("{\n.reg .pred p;\nsetp.ne.b32 p, %37, 0;\n"
    "wgmma.mma_async.sync.aligned.m64n64k16.f32.bf16.bf16 "
    "{%0, %1, %2, %3, %4, %5, %6, %7, %8, %9, %10, %11, %12, %13, %14, %15, %16, %17, %18, %19, %20, %21, %22, %23, %24, %25, %26, %27, %28, %29, %30, %31}, "
    "{%32, %33, %34, %35}, %36, p, 1, 1, 1;\n}\n"
    : "+f"(d[0]), "+f"(d[1]), "+f"(d[2]), "+f"(d[3]), "+f"(d[4]), "+f"(d[5]), "+f"(d[6]), "+f"(d[7]), "+f"(d[8]), "+f"(d[9]), "+f"(d[10]), "+f"(d[11]), "+f"(d[12]), "+f"(d[13]), "+f"(d[14]), "+f"(d[15]), "+f"(d[16]), "+f"(d[17]), "+f"(d[18]), "+f"(d[19]), "+f"(d[20]), "+f"(d[21]), "+f"(d[22]), "+f"(d[23]), "+f"(d[24]), "+f"(d[25]), "+f"(d[26]), "+f"(d[27]), "+f"(d[28]), "+f"(d[29]), "+f"(d[30]), "+f"(d[31])
    : "r"(a0), "r"(a1), "r"(a2), "r"(a3), "l"(descB), "r"(scaleD));
}
__device__ __forceinline__ void wgmma_ss_n128_ta1_tb0(float (&d)[64], uint64_t descA, uint64_t descB, int scaleD) {
  asm volatile("{\n.reg .pred p;\nsetp.ne.b32 p, %66, 0;\n"
    "wgmma.mma_async.sync.aligned.m64n128k16.f32.bf16.bf16 "
    "{%0, %1, %2, %3, %4, %5, %6, %7, %8, %9, %10, %11, %12, %13, %14, %15, %16, %17, %18, %19, %20, %21, %22, %23, %24, %25, %26, %27, %28, %29, %30, %31, %32, %33, %34, %35, %36, %37, %38, %39, %40, %41, %42, %43, %44, %45, %46, %47, %48, %49, %50, %51, %52, %53, %54, %55, %56, %57, %58, %59, %60, %61, %62, %63}, "
    "%64, %65, p, 1, 1, 1, 0;\n}\n"
    : "+f"(d[0]), "+f"(d[1]), "+f"(d[2]), "+f"(d[3]), "+f"(d[4]), "+f"(d[5]), "+f"(d[6]), "+f"(d[7]), "+f"(d[8]), "+f"(d[9]), "+f"(d[10]), "+f"(d[11]), "+f"(d[12]), "+f"(d[13]), "+f"(d[14]), "+f"(d[15]), "+f"(d[16]), "+f"(d[17]), "+f"(d[18]), "+f"(d[19]), "+f"(d[20]), "+f"(d[21]), "+f"(d[22]), "+f"(d[23]), "+f"(d[24]), "+f"(d[25]), "+f"(d[26]), "+f"(d[27]), "+f"(d[28]), "+f"(d[29]), "+f"(d[30]), "+f"(d[31]), "+f"(d[32]), "+f"(d[33]), "+f"(d[34]), "+f"(d[35]), "+f"(d[36]), "+f"(d[37]), "+f"(d[38]), "+f"(d[39]), "+f"(d[40]), "+f"(d[41]), "+f"(d[42]), "+f"(d[43]), "+f"(d[44]), "+f"(d[45]), "+f"(d[46]), "+f"(d[47]), "+f"(d[48]), "+f"(d[49]), "+f"(d[50]), "+f"(d[51]), "+f"(d[52]), "+f"(d[53]), "+f"(d[54]), "+f"(d[55]), "+f"(d[56]), "+f"(d[57]), "+f"(d[58]), "+f"(d[59]), "+f"(d[60]), "+f"(d[61]), "+f"(d[62]), "+f"(d[63])
    : "l"(descA), "l"(descB), "r"(scaleD));
}
__device__ __forceinline__ void wgmma_ss_n160_ta0_tb1(float (&d)[80], uint64_t descA, uint64_t descB, int scaleD) {
  asm volatile("{\n.reg .pred p;\nsetp.ne.b32 p, %82, 0;\n"
    "wgmma.mma_async.sync.aligned.m64n160k16.f32.bf16.bf16 "
    "{%0, %1, %2, %3, %4, %5, %6, %7, %8, %9, %10, %11, %12, %13, %14, %15, %16, %17, %18, %19, %20, %21, %22, %23, %24, %25, %26, %27, %28, %29, %30, %31, %32, %33, %34, %35, %36, %37, %38, %39, %40, %41, %42, %43, %44, %45, %46, %47, %48, %49, %50, %51, %52, %53, %54, %55, %56, %57, %58, %59, %60, %61, %62, %63, %64, %65, %66, %67, %68, %69, %70, %71, %72, %73, %74, %75, %76, %77, %78, %79}, "
    "%80, %81, p, 1, 1, 0, 1;\n}\n"
    : "+f"(d[0]), "+f"(d[1]), "+f"(d[2]), "+f"(d[3]), "+f"(d[4]), "+f"(d[5]), "+f"(d[6]), "+f"(d[7]), "+f"(d[8]), "+f"(d[9]), "+f"(d[10]), "+f"(d[11]), "+f"(d[12]), "+f"(d[13]), "+f"(d[14]), "+f"(d[15]), "+f"(d[16]), "+f"(d[17]), "+f"(d[18]), "+f"(d[19]), "+f"(d[20]), "+f"(d[21]), "+f"(d[22]), "+f"(d[23]), "+f"(d[24]), "+f"(d[25]), "+f"(d[26]), "+f"(d[27]), "+f"(d[28]), "+f"(d[29]), "+f"(d[30]), "+f"(d[31]), "+f"(d[32]), "+f"(d[33]), "+f"(d[34]), "+f"(d[35]), "+f"(d[36]), "+f"(d[37]), "+f"(d[38]), "+f"(d[39]), "+f"(d[40]), "+f"(d[41]), "+f"(d[42]), "+f"(d[43]), "+f"(d[44]), "+f"(d[45]), "+f"(d[46]), "+f"(d[47]), "+f"(d[48]), "+f"(d[49]), "+f"(d[50]), "+f"(d[51]), "+f"(d[52]), "+f"(d[53]), "+f"(d[54]), "+f"(d[55]), "+f"(d[56]), "+f"(d[57]), "+f"(d[58]), "+f"(d[59]), "+f"(d[60]), "+f"(d[61]), "+f"(d[62]), "+f"(d[63]), "+f"(d[64]), "+f"(d[65]), "+f"(d[66]), "+f"(d[67]), "+f"(d[68]), "+f"(d[69]), "+f"(d[70]), "+f"(d[71]), "+f"(d[72]), "+f"(d[73]), "+f"(d[74]), "+f"(d[75]), "+f"(d[76]), "+f"(d[77]), "+f"(d[78]), "+f"(d[79])
    : "l"(descA), "l"(descB), "r"(scaleD));
}

#define PROF_DECL(b)
#define PROF_EV(tag)
#define PROF_GT(tag)

template <int N> struct IC { static constexpr int value = N; };
struct Cur {
    uint32_t slot, ph;
    __device__ __forceinline__ void adv() { if (++slot == NSLOT) { slot = 0; ph ^= 1; } }
};
constexpr int E0 = 6, E_ATT0 = 48, E_ATT1 = 108;
__host__ __device__ constexpr uint32_t slot_of(int e) { return (e + E0) % NSLOT; }
__device__ __forceinline__ Cur cur_at(int e) { Cur c; c.slot = (e + E0) % NSLOT; c.ph = ((e + E0) / NSLOT) & 1; return c; }

__device__ __forceinline__ int q_tile(int k, int t) { return (t < 2 ? 14 - 2 * k : 2 * k) + (t & 1); }
__device__ __forceinline__ int op_head(int i, int kap) { return 16 * kap + 2 * (i & 7) + (i >> 3); }

constexpr float SM_SCALE = 0.08838834764831845f * 1.4426950408889634f;

struct Ctx {
    uint32_t ring, misc;
    uint32_t rel;
    int w, warp, lane;
};
__device__ __forceinline__ void release(const Ctx& c, uint32_t off, uint32_t cnt) {
    if (c.lane < 2) mbar_arrive_cluster(c.rel + off, cnt);
}
__device__ __forceinline__ void signal_event(const Ctx& c, int ev) {
    __syncwarp();
    if (c.lane == 0) mbar_arrive(c.misc + BAR_EV + (c.w * 16 + ev) * 8);
}
template <int NK, int OFF, int N>
__device__ __forceinline__ uint32_t load_afrag(uint32_t (&a)[N], uint32_t base, const Ctx& c) {
    int r = c.lane & 7, mat = c.lane >> 3;
    uint32_t addr = base + (8 * (mat >> 1) + r) * 128 + (((2 * c.warp + (mat & 1)) ^ r) << 4);
#pragma unroll
    for (int k = 0; k < NK; k++) ldsm4t(a[OFF + 4 * k], a[OFF + 4 * k + 1], a[OFF + 4 * k + 2], a[OFF + 4 * k + 3], addr + k * 2048);
    uint32_t dep = 0;
#pragma unroll
    for (int k = 0; k < NK; k++) dep |= a[OFF + 4 * k];
    return dep & blockIdx.y;
}
__device__ __forceinline__ void store_proj(const float (&acc)[64], unsigned char* dst  , const Ctx& c, uint64_t pol) {
    int g = c.lane >> 2, t = c.lane & 3;
#pragma unroll
    for (int i = 0; i < 2; i++) {
        int row = perm32(64 * c.w + 16 * c.warp + 8 * i + g);
        unsigned char* p = dst + row * 128;
#pragma unroll
        for (int q = 0; q < 4; q++) {
            int chunk = (4 * (q & 1) + t) ^ (row & 7);
            stg128_hint(p + (q >> 1) * 16384 + chunk * 16,
                   pack_bf16(acc[16 * q + 2 * i], acc[16 * q + 2 * i + 1]), pack_bf16(acc[16 * q + 4 + 2 * i], acc[16 * q + 4 + 2 * i + 1]),
                   pack_bf16(acc[16 * q + 8 + 2 * i], acc[16 * q + 8 + 2 * i + 1]), pack_bf16(acc[16 * q + 12 + 2 * i], acc[16 * q + 12 + 2 * i + 1]), pol);
        }
    }
}

constexpr float SAFE_SUM = 1099511627776.0f;
template <int NJ>
__device__ __forceinline__ void row_max(const float (&s)[4 * NJ], float (&mx)[2]) {
#pragma unroll
    for (int i = 0; i < 2; i++) {
        float a = fmaxf(s[2 * i], s[2 * i + 1]), b = fmaxf(s[4 + 2 * i], s[4 + 2 * i + 1]);
#pragma unroll
        for (int j = 2; j < NJ; j += 2) {
            a = fmaxf(a, fmaxf(s[4 * j + 2 * i], s[4 * j + 2 * i + 1]));
            b = fmaxf(b, fmaxf(s[4 * j + 4 + 2 * i], s[4 * j + 4 + 2 * i + 1]));
        }
        a = fmaxf(a, b);
        a = fmaxf(a, __shfl_xor_sync(0xffffffffu, a, 1));
        mx[i] = fmaxf(a, __shfl_xor_sync(0xffffffffu, a, 2));
    }
}
template <int NJ, bool SHIFT>
__device__ __forceinline__ void exp_sum(float (&s)[4 * NJ], const float (&m)[2], float& l0, float& l1) {
#pragma unroll
    for (int j = 0; j < NJ; j++) {
#pragma unroll
        for (int e = 0; e < 4; e++) s[4 * j + e] = ex2(SHIFT ? s[4 * j + e] - m[e >> 1] : s[4 * j + e]);
        l0 += s[4 * j + 0] + s[4 * j + 1]; l1 += s[4 * j + 2] + s[4 * j + 3];
    }
}
__device__ __forceinline__ void recompute_scores(float (&s)[64], const unsigned char* qh, uint32_t kaddr, const Ctx& c) {
    const int r = c.lane & 7, mat = c.lane >> 3, g = c.lane >> 2, t = c.lane & 3;
    const uint32_t a0 = kaddr + (8 * (mat & 1) + r) * 128 + (((mat >> 1) ^ r) << 4);
    uint32_t q[32];
#pragma unroll
    for (int i = 0; i < 32; i++) {
        const uint32_t v = __ldcg(reinterpret_cast<const uint32_t*>(qh + (8 * (i >> 1) + g) * 128 + (((2 * c.warp + (i & 1)) ^ g) << 4) + 4 * t));
        asm volatile("movmatrix.sync.aligned.m8n8.trans.b16 %0, %1;" : "=r"(q[i]) : "r"(v));
    }
#pragma unroll
    for (int i = 0; i < 64; i++) s[i] = 0.f;
#pragma unroll
    for (int jp = 0; jp < 8; jp++) {
#pragma unroll
        for (int k = 0; k < 8; k++) {
            asm volatile(
                "{\n.reg .b32 b0, b1, b2, b3;\n"
                "ldmatrix.sync.aligned.m8n8.x4.trans.shared.b16 {b0,b1,b2,b3}, [%12];\n"
                "mma.sync.aligned.m16n8k16.row.col.f32.bf16.bf16.f32 {%0,%1,%2,%3}, {%8,%9,%10,%11}, {b0,b1}, {%0,%1,%2,%3};\n"
                "mma.sync.aligned.m16n8k16.row.col.f32.bf16.bf16.f32 {%4,%5,%6,%7}, {%8,%9,%10,%11}, {b2,b3}, {%4,%5,%6,%7};\n}\n"
                : "+f"(s[8 * jp]), "+f"(s[8 * jp + 1]), "+f"(s[8 * jp + 2]), "+f"(s[8 * jp + 3]),
                  "+f"(s[8 * jp + 4]), "+f"(s[8 * jp + 5]), "+f"(s[8 * jp + 6]), "+f"(s[8 * jp + 7])
                : "r"(q[4 * k]), "r"(q[4 * k + 1]), "r"(q[4 * k + 2]), "r"(q[4 * k + 3]),
                  "r"((a0 ^ ((jp & 3) << 5)) + (jp >> 2) * 16384 + k * 2048) : "memory");
        }
    }
}
__device__ __forceinline__ int mask_lim(const Ctx& c) { return perm32(16 * c.warp + (c.lane >> 2)) - 8 * (c.lane & 3); }
template <int J0>
__device__ __forceinline__ void mask_diag(float (&s)[4 * J0 + 32], const Ctx& c) {
    const int lim = mask_lim(c);
    if (c.warp < 2) {
#pragma unroll
        for (int x = 0; x < 16; x++) {
            if (2 * (x >> 2) + (x & 1) - (x & 2) > lim) s[4 * J0 + x] = -INFINITY;
            s[4 * J0 + 16 + x] = -INFINITY;
        }
    } else {
#pragma unroll
        for (int x = 0; x < 16; x++)
            if (32 + 2 * (x >> 2) + (x & 1) - (x & 2) > lim) s[4 * J0 + 16 + x] = -INFINITY;
    }
}
__device__ __forceinline__ void mask_any(float (&s)[64], int hh, const Ctx& c) {
    const int lim = mask_lim(c) + 64 * hh;
#pragma unroll
    for (int x = 0; x < 64; x++)
        if (32 * (x >> 4) + 2 * ((x >> 2) & 3) + (x & 1) - (x & 2) > lim) s[x] = -INFINITY;
}
__device__ __forceinline__ void issue_pv(float (&o)[64], const uint32_t (&p)[32], uint32_t vaddr, int acc, int mode  ) {
    uint64_t d = mkdesc(vaddr, 16, 1024, 1);
    if (mode == 0) {
        wg_fence();
#pragma unroll
        for (int k = 0; k < 8; k++)
            wgmma_rs_n128_ta0_tb0(o, p[4 * k], p[4 * k + 1], p[4 * k + 2], p[4 * k + 3], d + (k >> 2) * 1024 + 2 * (k & 3), k ? 1 : acc);
        wg_commit();
    } else if (mode == 1) {
        wg_fence();
#pragma unroll
        for (int k = 0; k < 4; k++) wgmma_rs_n128_ta0_tb0(o, p[4 * k], p[4 * k + 1], p[4 * k + 2], p[4 * k + 3], d + 2 * k, k != 0);
        wg_commit();
    } else {
        wg_fence();
        wgmma_rs_n128_ta0_tb0(o, p[0], p[1], p[2], p[3], d, 0);
        wg_commit();
    }
}
__device__ __forceinline__ void issue_qk(float (&s)[64], const uint32_t (&q)[32], uint32_t kaddr) {
    uint64_t d = mkdesc(kaddr, 16384, 1024, 1);
    wg_fence();
#pragma unroll
    for (int k = 0; k < 8; k++) wgmma_rs_n128_ta0_tb1(s, q[4 * k], q[4 * k + 1], q[4 * k + 2], q[4 * k + 3], d + 128 * k, k != 0);
    wg_commit();
}
__device__ __forceinline__ void issue_qk_half(float (&s32)[32], const uint32_t (&q)[32], uint32_t kaddr) {
    uint64_t d = mkdesc(kaddr, 16384, 1024, 1);
    wg_fence();
#pragma unroll
    for (int k = 0; k < 8; k++) wgmma_rs_n64_ta0_tb1(s32, q[4 * k], q[4 * k + 1], q[4 * k + 2], q[4 * k + 3], d + 128 * k, k != 0);
    wg_commit();
}
template <int Q0, int Q1>
__device__ __forceinline__ void stage_ctx(float (&o)[64], const float (&inv)[2], Cur ce, const Ctx& c) {
    const int g = c.lane >> 2, t = c.lane & 3, r7 = ((g & 1) << 2) | (g >> 1);
    const uint32_t base = c.ring + ce.slot * SLOT_BYTES + c.w * 16384 + (16 * c.warp + r7) * 128 + ((t ^ r7) << 4);
    if (Q0 == 0) mbar_wait_hot(c.misc + BAR_FULL + 8 * ce.slot, ce.ph);
#pragma unroll
    for (int q = Q0; q < Q1; q++) {
        uint32_t v[8];
#pragma unroll
        for (int i = 0; i < 2; i++)
#pragma unroll
            for (int j = 0; j < 4; j++) v[4 * i + j] = pack_bf16(o[16 * q + 4 * j + 2 * i] * inv[i], o[16 * q + 4 * j + 2 * i + 1] * inv[i]);
#pragma unroll
        for (int i = 0; i < 8; i++) { o[16 * q + i] = __uint_as_float(v[i]); asm volatile("" : "=f"(o[16 * q + 8 + i])); }
#pragma unroll
        for (int i = 0; i < 2; i++)
            asm volatile("st.shared.v4.b32 [%0], {%1,%2,%3,%4};" ::"r"((base ^ ((q & 1) << 6)) + (q >> 1) * 8192 + i * 1024),
                         "r"(v[4 * i]), "r"(v[4 * i + 1]), "r"(v[4 * i + 2]), "r"(v[4 * i + 3]) : "memory");
    }
}
__device__ __forceinline__ void publish_ctx(int ev, const Ctx& c) {
    asm volatile("fence.proxy.async.shared::cta;" ::: "memory");
    signal_event(c, ev);
}

__device__ __forceinline__ const unsigned char* xn_addr(int row, int col) {
    return g_xn + ((row >> 7) * 10 + (col >> 6)) * 16384 + (row & 127) * 128 + ((((col & 63) >> 3) ^ (row & 7)) << 4);
}
__device__ __forceinline__ void mma16816(float (&d)[4], uint32_t a0, uint32_t a1, uint32_t a2, uint32_t a3, uint32_t b0, uint32_t b1) {
    asm volatile("mma.sync.aligned.m16n8k16.row.col.f32.bf16.bf16.f32 {%0,%1,%2,%3}, {%4,%5,%6,%7}, {%8,%9}, {%0,%1,%2,%3};"
                 : "+f"(d[0]), "+f"(d[1]), "+f"(d[2]), "+f"(d[3]) : "r"(a0), "r"(a1), "r"(a2), "r"(a3), "r"(b0), "r"(b1));
}
__device__ __forceinline__ uint32_t lds32(uint32_t addr) { uint32_t v; asm volatile("ld.shared.u32 %0, [%1];" : "=r"(v) : "r"(addr)); return v; }

__device__ __forceinline__ void ln_rows(const Params& P, int row0, int lane, uint32_t wr_s) {
    const int hl = lane & 15, row = row0 + (lane >> 4);
    uint32_t v[20];
#pragma unroll
    for (int i = 0; i < 5; i++) {
        uint4 u;
        asm("ld.global.nc.L2::cache_hint.v4.b32 {%0,%1,%2,%3}, [%4], %5;" : "=r"(u.x), "=r"(u.y), "=r"(u.z), "=r"(u.w)
            : "l"(P.x + (size_t)row * DM + 128 * i + 8 * hl), "l"(policy(HM & 512)));
        v[4 * i] = u.x; v[4 * i + 1] = u.y; v[4 * i + 2] = u.z; v[4 * i + 3] = u.w;
    }
    float mean = 0.f, m2 = 0.f, acc2 = 0.f;
#pragma unroll
    for (int i = 0; i < 20; i++) { mean += bf_lo(v[i]); acc2 += bf_hi(v[i]); }
    mean = (mean + acc2) * (1.0f / 40);
    acc2 = 0.f;
#pragma unroll
    for (int i = 0; i < 20; i++) {
        float d0 = __uint_as_float(__byte_perm(v[i], 0, 0x1044)) - mean, d1 = __uint_as_float(__byte_perm(v[i], 0, 0x3244)) - mean;
        m2 = fmaf(d0, d0, m2); acc2 = fmaf(d1, d1, acc2);
    }
    m2 += acc2;
    acc2 = 0.f;
#pragma unroll
    for (int o = 1; o < 16; o <<= 1) {
        float mo = __shfl_xor_sync(0xffffffffu, mean, o), qo = __shfl_xor_sync(0xffffffffu, m2, o), d = mo - mean;
        m2 = fmaf(d * d, 20.0f * o, m2 + qo);
        mean = 0.5f * (mean + mo);
    }
    const uint32_t mb2 = pack_bf16(mean, mean);
    const float inv = rcp_fast(bf_round(sqrt_fast(bf_round(bf_round(m2 * (1.0f / DM)) + 1e-5f))));
    float dot = 0.f;
    unsigned char* xp = g_xn + ((row >> 7) * 10 + (hl >> 3)) * 16384 + (row & 127) * 128 + (((hl & 7) ^ (row & 7)) << 4);
#pragma unroll
    for (int i = 0; i < 5; i++) {
        uint32_t ww[4];
        asm volatile("ld.shared.v4.b32 {%0,%1,%2,%3}, [%4];" : "=r"(ww[0]), "=r"(ww[1]), "=r"(ww[2]), "=r"(ww[3]) : "r"(wr_s + 256 * i + 16 * hl) : "memory");
#pragma unroll
        for (int e = 0; e < 4; e++) {
            uint32_t d;
            asm("sub.rn.bf16x2 %0, %1, %2;" : "=r"(d) : "r"(v[4 * i + e]), "r"(mb2));
            d = pack_bf16(bf_lo(d) * inv, bf_hi(d) * inv);
            v[4 * i + e] = d;
            dot = fmaf(bf_lo(d), bf_lo(ww[e]), dot);
            acc2 = fmaf(bf_hi(d), bf_hi(ww[e]), acc2);
        }
        stg128(xp + i * 32768, v[4 * i], v[4 * i + 1], v[4 * i + 2], v[4 * i + 3]);
    }
    dot += acc2;
#pragma unroll
    for (int o = 8; o > 0; o >>= 1) dot += __shfl_xor_sync(0xffffffffu, dot, o);
    if (hl == 0) { g_router[row] = bf_round(dot); g_stats[row] = make_uint2(mb2, __float_as_uint(inv)); }
}

__device__ __forceinline__ void aux_cta(const Params& P, const CUtensorMap* tmG, const CUtensorMap* tmU, const CUtensorMap* tmD, unsigned char* sm, int a) {
    constexpr int STG = 57344, XS = 3 * STG, HS = XS + 8 * 1296, KEY = HS + 8 * 912, MI = KEY + 8192;
    const int tid = threadIdx.x, warp = __shfl_sync(0xffffffffu, tid >> 5, 0), lane = tid & 31;
    const uint32_t sb = smem_u32(sm);
    const uint32_t full = sb + MI, empty = sb + MI + 32;
    int* s_sel = reinterpret_cast<int*>(sm + MI + 64);
    float* s_r = reinterpret_cast<float*>(sm + MI + 96);
    volatile unsigned* s_misc = reinterpret_cast<volatile unsigned*>(sm + MI + 128);
    uint32_t* s_key = reinterpret_cast<uint32_t*>(sm + KEY);
    PROF_DECL(128 + a)
    PROF_GT(0);
    if (tid == 0) {
        for (int i = 0; i < 3; i++) { mbar_init(full + 8 * i, 1); mbar_init(empty + 8 * i, 10); }
        asm volatile("fence.mbarrier_init.release.cluster;" ::: "memory");
    }
    __syncthreads();
    if (warp == 11) {
        if (elect_one()) {
            int st = 0; uint32_t ph = 0;
#pragma unroll 1
            for (int s = 0; s < 34; s++) {
                mbar_wait(empty + 8 * st, ph ^ 1);
                const uint32_t dst = sb + st * STG, fb = full + 8 * st;
                if (s < 20) {
                    mbar_expect_tx(fb, 57344);
                    tma3d(dst, tmG, 0, 32 * s, 7 * a, fb);
                    tma3d(dst + 28672, tmU, 0, 32 * s, 7 * a, fb);
                } else {
                    mbar_expect_tx(fb, 40960);
                    tma3d(dst, tmD, 0, 448 * a + 32 * (s - 20), 0, fb);
                }
                if (s >= 3) {
#pragma unroll 1
                    for (int f = (s == 3 ? 4 : s + 6); f <= s + 6 && f < 34; f++) {
                        if (f < 20) { tma3d_prefetch(tmG, 0, 32 * f, 7 * a); tma3d_prefetch(tmU, 0, 32 * f, 7 * a); }
                        else tma3d_prefetch(tmD, 0, 448 * a + 32 * (f - 20), 0);
                    }
                }
                if (++st == 3) { st = 0; ph ^= 1; }
            }
        }
        return;
    }
    if (tid < 80) *reinterpret_cast<uint4*>(sm + KEY + 1024 + tid * 16) = __ldg(reinterpret_cast<const uint4*>(P.wr) + tid);
    __nanosleep(AUXDELAY);
#pragma unroll 1
    for (int i = tid; i < 128 * 40; i += 352) asm volatile("prefetch.global.L2 [%0];" ::"l"(P.x + (size_t)(2 * a) * 128 * DM + i * 16));
    bar_sync(2, 352);
#pragma unroll 1
    for (int i = warp; i < 64; i += 11) ln_rows(P, 2 * a * 128 + 2 * i, lane, sb + KEY + 1024);
    bar_sync(2, 352);
    if (tid == 320) asm volatile("red.release.gpu.global.add.u32 [%0], 32;" ::"l"(flag_ptr(FL_LN + 2 * a)) : "memory");
    PROF_GT(49);
    if (warp == 10) return;
    if (tid < 16) {
        unsigned e = *reinterpret_cast<volatile unsigned*>(&g_epoch);
        if (tid == 0) s_misc[0] = e;
        flag_wait(flag_ptr(FL_LN + tid), (e + 1) * 32u);
    }
    bar_sync(1, 320);
    PROF_GT(50);
    const unsigned ep = s_misc[0];
    auto top8 = [&](uint32_t (&key)[8]) {
        uint32_t mine = 0;
#pragma unroll 1
        for (int r = 0; r < TOPC; r++) {
            uint32_t best = 0;
#pragma unroll
            for (int i = 0; i < 8; i++) best = max(best, key[i]);
            best = __reduce_max_sync(0xffffffffu, best);
#pragma unroll
            for (int i = 0; i < 8; i++) if (key[i] == best) key[i] = 0;
            if (lane == r) mine = best;
        }
        return mine;
    };
#pragma unroll 1
    for (int pass = 0; pass < 2; pass++) {
        if (warp < (pass ? 1 : 8)) {
            uint32_t key[8];
#pragma unroll
            for (int i = 0; i < 8; i++) {
                if (pass == 0) {
                    int idx = warp * 256 + i * 32 + lane;
                    uint32_t b = __float_as_uint(__ldcg(g_router + idx)) >> 16;
                    b = (b & 0x8000u) ? (~b & 0xffffu) : (b | 0x8000u);
                    key[i] = (b << 16) | (uint32_t)(0xffff - idx);
                } else key[i] = i < 2 ? s_key[i * 32 + lane] : 0u;
            }
            uint32_t best = top8(key);
            if (lane < TOPC) {
                if (pass == 0) s_key[warp * 8 + lane] = best;
                else {
                    uint32_t b = best >> 16;
                    b = (b & 0x8000u) ? (b & 0x7fffu) : (~b & 0xffffu);
                    s_sel[lane] = 0xffff - (int)(best & 0xffffu);
                    s_r[lane] = __uint_as_float(b << 16);
                }
            }
        }
        bar_sync(1, 320);
    }
#pragma unroll
    for (int it = 0; it < 2; it++) {
        int i = tid + it * 320, tk = i / 80, ch = i % 80;
        *reinterpret_cast<uint4*>(sm + XS + tk * 1296 + ch * 16) = __ldcg(reinterpret_cast<const uint4*>(xn_addr(s_sel[tk], ch * 8)));
    }
    bar_sync(1, 320);
    PROF_GT(51);
    const int g = lane >> 2, t = lane & 3;
    const uint32_t woff = warp * 4096 + (8 * (lane >> 4) + (lane & 7)) * 128 + ((((lane >> 3) & 1) ^ (lane & 7)) << 4);
    int st = 0; uint32_t ph = 0;
    float ga[4][4], ua[4][4];
#pragma unroll
    for (int i = 0; i < 4; i++)
#pragma unroll
        for (int e = 0; e < 4; e++) { ga[i][e] = 0.f; ua[i][e] = 0.f; }
#pragma unroll 1
    for (int s = 0; s < 34; s++) {
        if (s == 20) {
            if (warp < 7) {
#pragma unroll
                for (int i = 0; i < 4; i++)
#pragma unroll
                    for (int e = 0; e < 4; e++) {
                        float gv = bf_round(ga[i][e]), uv = bf_round(ua[i][e]);
                        float sg = bf_round(__fdividef(gv, 1.0f + __expf(fminf(-gv, 80.f))));
                        int f = warp * 64 + i * 16 + g + 8 * (e >> 1), tk = 2 * t + (e & 1);
                        *reinterpret_cast<__nv_bfloat16*>(sm + HS + tk * 912 + f * 2) = __float2bfloat16_rn(sg * uv);
                        ga[i][e] = 0.f;
                    }
            }
            bar_sync(1, 320);
            PROF_GT(52);
        }
        mbar_wait(full + 8 * st, ph);
        if (s >= 20 || warp < 7) {
#pragma unroll
            for (int kk = 0; kk < 2; kk++) {
                uint32_t xb = sb + (s < 20 ? XS + g * 1296 + s * 64 : HS + g * 912 + (s - 20) * 64) + 32 * kk + 4 * t;
                uint32_t b0 = lds32(xb), b1 = lds32(xb + 16);
                uint32_t wa = sb + st * STG + woff + kk * 2048;
#pragma unroll
                for (int i = 0; i < 4; i++) {
                    uint32_t a0, a1, a2, a3;
                    ldsm4t(a0, a1, a2, a3, wa ^ (i << 5));
                    mma16816(ga[i], a0, a1, a2, a3, b0, b1);
                    if (s < 20) {
                        ldsm4t(a0, a1, a2, a3, (wa ^ (i << 5)) + 28672);
                        mma16816(ua[i], a0, a1, a2, a3, b0, b1);
                    }
                }
            }
        }
        asm volatile("fence.proxy.async.shared::cta;" ::: "memory");
        __syncwarp();
        if (lane == 0) mbar_arrive(empty + 8 * st);
        if (++st == 3) { st = 0; ph ^= 1; }
    }
#pragma unroll
    for (int i = 0; i < 4; i++)
#pragma unroll
        for (int e = 0; e < 4; e += 2)
            *reinterpret_cast<float2*>(g_moe_part + (a * DM + warp * 64 + i * 16 + g + 4 * e) * 8 + 2 * t) = make_float2(ga[i][e], ga[i][e + 1]);
    bar_sync(1, 320);
    if (tid == 0) {
        __threadfence();
        unsigned old = atomicAdd(flag_ptr(FL_MOE_CNT), 1u);
        s_misc[1] = (old == ep * 4u + 3u);
        __threadfence();
    }
    bar_sync(1, 320);
    PROF_GT(53);
    if (s_misc[1]) {
        const float4* pp = reinterpret_cast<const float4*>(g_moe_part);
#pragma unroll 2
        for (int i = tid; i < DM * 2; i += 320) {
            float4 v0 = __ldcg(pp + i), v1 = __ldcg(pp + DM * 2 + i), v2 = __ldcg(pp + DM * 4 + i), v3 = __ldcg(pp + DM * 6 + i);
            float y[4] = {v0.x + v1.x + v2.x + v3.x, v0.y + v1.y + v2.y + v3.y, v0.z + v1.z + v2.z + v3.z, v0.w + v1.w + v2.w + v3.w};
#pragma unroll
            for (int e = 0; e < 4; e++) {
                int col = i >> 1, tk = (i & 1) * 4 + e;
                float sg = bf_round(__fdividef(1.0f, 1.0f + __expf(fminf(-s_r[tk], 80.f))));
                float upd = bf_round(bf_round(y[e]) * sg);
                float xn = __bfloat162float(*reinterpret_cast<const __nv_bfloat16*>(sm + XS + tk * 1296 + col * 2));
                g_brow[tk * DM + col] = __float2bfloat16_rn(xn + upd);
            }
        }
        if (tid < TOPC) g_sel[tid] = s_sel[tid];
        bar_sync(1, 320);
        if (tid == 0) {
            flag_signal(flag_ptr(FL_MOE_DONE));
            *reinterpret_cast<volatile unsigned*>(&g_epoch) = ep + 1;
        }
        PROF_GT(54);
    }
}

__global__ void __cluster_dims__(2, 1, 1) __launch_bounds__(384, 1)
fused_kernel(const __grid_constant__ CUtensorMap tmC, const __grid_constant__ CUtensorMap tmWk, const __grid_constant__ CUtensorMap tmWv,
             const __grid_constant__ CUtensorMap tmWq, const __grid_constant__ CUtensorMap tmWo,
             const __grid_constant__ CUtensorMap tmG, const __grid_constant__ CUtensorMap tmU, const __grid_constant__ CUtensorMap tmD, const Params P) {
    extern __shared__ __align__(1024) unsigned char smem_raw[];
    const uint32_t ring = smem_u32(smem_raw);
    const uint32_t misc = ring + RING_BYTES;
    const int tid = threadIdx.x;
    const int rank = blockIdx.x & 1;
    uint32_t smid; asm("mov.u32 %0, %%smid;" : "=r"(smid));
    const int tpc = smid >> 1;
    const int mc = tpc < 32 ? (tpc & 7) * 8 + (tpc >> 3) : tpc < 60 ? (1 + (tpc - 32) % 7) * 8 + 4 + (tpc - 32) / 7 : tpc < 64 ? tpc - 56 : tpc;
    const int cta = mc * 2 + rank;
    if (mc >= 64) { aux_cta(P, &tmG, &tmU, &tmD, smem_raw, cta - 128); return; }
    PROF_DECL(cta)
    PROF_GT(0); PROF_EV(1);
    const int team = mc >> 2, k = mc & 3;
    const int u3 = (mc >> 4) * 2 + (team & 1), s3 = k, kap = (mc >> 3) & 1;
    const int partner = cta ^ 16;

    if (tid >= 128) {
        const int i = tid - 128;
        if (i < 128) asm volatile("prefetch.global.L2 [%0];" ::"l"(P.c + (size_t)((12 + k) * 128 + (team * 2 + rank) * 4) * DC + i * 16));
    }
    auto prefetch_w = [&](int ch) {
        const int i = tid - 128;
        asm volatile("prefetch.global.L2 [%0];" ::"l"((rank ? P.wv : P.wk) + (size_t)(ch * 128 + k * 32 + (i >> 3)) * 4096 + team * 256 + (i & 7) * 16));
    };
    if (tid >= 128) { if (PFV & 1) prefetch_w(0); if (PFV & 2) prefetch_w(1); }
    if (tid == 0) {
#pragma unroll
        for (int i = 0; i < NSLOT; i++) mbar_init(misc + BAR_FULL + 8 * i, 1);
#pragma unroll
        for (int i = 0; i < E0; i++) mbar_arrive(misc + BAR_FULL + 8 * i);
        asm volatile("fence.mbarrier_init.release.cluster;" ::: "memory");
        const CUtensorMap* tw = rank ? &tmWv : &tmWk;
        mbar_expect_tx(misc + BAR_FULL + 8 * slot_of(0), SLOT_BYTES);
        tma2d(ring + slot_of(0) * SLOT_BYTES, tw, team * 256, 0, misc + BAR_FULL + 8 * slot_of(0), policy(HM & 1));
        tma2d(ring + slot_of(0) * SLOT_BYTES + 16384, tw, team * 256 + 64, 0, misc + BAR_FULL + 8 * slot_of(0), policy(HM & 1));
    }
    if (tid == 32) {
        asm volatile("prefetch.tensormap [%0];" ::"l"(&tmC) : "memory");
#pragma unroll
        for (int i = 0; i < NSLOT; i++) mbar_init(misc + BAR_EMPTY + 8 * i, 16);
#pragma unroll
        for (int i = 0; i < E0; i++) mbar_arrive_cluster(misc + BAR_EMPTY + 8 * i, 16);
        asm volatile("fence.mbarrier_init.release.cluster;" ::: "memory");
    }
    if (tid == 64) {
#pragma unroll
        for (int i = 0; i < NST3; i++) { mbar_init(misc + BAR_FULL3 + 8 * i, 1); mbar_init(misc + BAR_EMPTY3 + 8 * i, 16); }
#pragma unroll
        for (int i = 0; i < 4; i++) mbar_init(misc + BAR_LN + 8 * i, 2);
        mbar_init(misc + BAR_PROG, 1); mbar_init(misc + BAR_PROG + 8, 1); mbar_init(misc + BAR_PROG + 16, 1);
        asm volatile("fence.mbarrier_init.release.cluster;" ::: "memory");
    }
    if (tid == 96) {
#pragma unroll
        for (int i = 0; i < 34; i++) mbar_init(misc + BAR_DEP + 8 * i, 1);
    }
    if (tid == 128) {
#pragma unroll
        for (int i = 0; i < 32; i++) mbar_init(misc + BAR_EV + 8 * i, 4);
    }
    __syncthreads();
    asm volatile("barrier.cluster.arrive.relaxed.aligned;\nbarrier.cluster.wait.aligned;" ::: "memory");
    if (tid >= 128) { if (PFV & 4) prefetch_w(1); if (PFV & 8) prefetch_w(2); }
    if (tid == 256) {
        const CUtensorMap* tw = rank ? &tmWv : &tmWk;
#pragma unroll
        for (int e = 1; e < NSLOT; e++) {
            const uint32_t fb = misc + BAR_FULL + 8 * slot_of(e), dst = ring + slot_of(e) * SLOT_BYTES;
            mbar_expect_tx(fb, SLOT_BYTES);
            if (e & 1) tma2d_mc(dst + rank * 16384, &tmC, (e >> 1) * 128 + rank * 64, (12 + k) * 128, fb, policy(false));
            else { tma2d(dst, tw, team * 256, e * 64, fb, policy(false)); tma2d(dst + 16384, tw, team * 256 + 64, e * 64, fb, policy(false)); }
        }
    }
    PROF_EV(5);
    const int wg = __shfl_sync(0xffffffffu, tid >> 7, 0);

    if (wg == 0) {
        asm volatile("setmaxnreg.dec.sync.aligned.u32 40;");
        const int warp = __shfl_sync(0xffffffffu, tid >> 5, 0), lane = tid & 31;
        if (warp == 0) {
            const bool lead = elect_one();
            Cur c = cur_at(NSLOT);
            uint32_t dst, fb;
            auto acquire = [&]() {
                mbar_wait(misc + BAR_EMPTY + 8 * c.slot, c.ph ^ 1);
                fb = misc + BAR_FULL + 8 * c.slot; dst = ring + c.slot * SLOT_BYTES;
                if (lead) mbar_expect_tx(fb, SLOT_BYTES);
                c.adv();
            };
            auto load_w = [&](const CUtensorMap* tm, int col, int row, bool stream) {
                acquire();
                if (lead) { tma2d(dst, tm, col, row, fb, policy(stream)); tma2d(dst + 16384, tm, col + 64, row, fb, policy(stream)); }
            };
            auto load_half = [&](const unsigned char* src, bool stream) {
                acquire();
                if (lead) bulk_load_mc(dst + rank * 16384, src, 16384, fb, policy(stream));
            };
            auto staging = [&]() {
                mbar_wait(misc + BAR_EMPTY + 8 * c.slot, c.ph ^ 1);
                if (lead) mbar_arrive(misc + BAR_FULL + 8 * c.slot);
                c.adv();
            };
            auto dep_wait = [&](int d) { mbar_wait(misc + BAR_DEP + 8 * d, 0); fence_async_global(); };
            auto op_prefetch = [&](int i) {
                const int head = op_head(i, kap);
                l2_prefetch(reinterpret_cast<const unsigned char*>(P.wo) + head * 163840 + (u3 * 8 + s3 * 2 + rank) * 2560, 2560);
                if (i < 8) l2_prefetch(g_Q + (size_t)(head * 32 + 4 * u3 + 2 * rank) * 16384 + s3 * 8192, 8192);
            };
            const CUtensorMap* tw = rank ? &tmWv : &tmWk;
            const unsigned char* Kh = g_K + (size_t)team * 32 * 16384 + rank * 16384;
            const unsigned char* Vh = g_V + (size_t)team * 32 * 16384 + rank * 16384;
#pragma unroll 1
            for (int v = 0; v < 2; v++) {
                const int h = 2 * team + v;
#pragma unroll 1
                for (int i = v ? 0 : 3; i < 16; i++) {
                    if (i < 4 && v) load_w(tw, h * 128, i * 128, HM & 1);
                    if (v && (i & 7) == 3) dep_wait(D_WAR + (i >> 3));
                    acquire();
                    if (lead) tma2d_mc(dst + rank * 16384, &tmC, (i & 3) * 128 + rank * 64, (12 - (i & 12) + k) * 128, fb, policy(HM & 2));
                    if (v && i == 2 && lead) mbar_arrive(misc + BAR_PROG + 8);
                }
                if (v == 0) {
                    const int cq = (h + rank) * 128;
                    load_w(&tmWq, cq, 0, HM & 1); load_w(&tmWq, cq, 128, HM & 1); load_w(&tmWq, cq, 256, HM & 1);
#pragma unroll 1
                    for (int t = 0; t < 4; t++) {
                        const unsigned char* xt = g_xn + (q_tile(k, t) * 10 + rank) * 16384;
                        dep_wait(D_LN + t);
                        if (t == 3 && lead) l2_prefetch((rank ? Vh - 16384 : Kh) + (13 - 2 * k) * 32768, 3 * 32768);
#pragma unroll 1
                        for (int ch = 0; ch < 5; ch++) {
                            load_half(xt + ch * 32768, HM & 4);
                            if (t == 0 && ch == 0) load_w(&tmWq, cq, 384, HM & 1);
                        }
                        load_w(&tmWq, cq, 512, (HM & 1) && t == 3);
                    }
                }
                int togo = v ? PF_START : 11;
#pragma unroll 1
                for (int r = 0; r < 2; r++) {
                    const int p = r ? k : 7 - k, n = 2 * p + 1;
                    if (v == 0) dep_wait(D_Q + r);
                    acquire();
                    if (lead) {
                        const int g0 = r ? rank : 3 - rank;
                        bulk_load(dst, g_Q + (size_t)(h * 32 + 4 * p + g0) * 16384, 16384, fb, policy(HM & 8));
                        bulk_load(dst + 16384, g_Q + (size_t)(h * 32 + 4 * p + 3 - g0) * 16384, 16384, fb, policy(HM & 8));
                    }
                    if (v && r == 0) dep_wait(D_KV + 4 + (k >> 1));
                    load_half(Kh + n * 32768, HM & 16);
                    if (r) { load_half(Vh, HM & 16); staging(); }
#pragma unroll 1
                    for (int j = n - 1; j >= 0; j--) {
                        if (v && r == 0 && (j & 3) == 3) dep_wait(D_KV + 7 - (j >> 2));
                        load_half(Kh + j * 32768, HM & 16); load_half(Vh + (j + 1) * 32768, HM & 16);
                        if (v == 0 && r == 0 && j == 3 && lead) mbar_arrive(misc + BAR_PROG);
                        --togo;
                        if (v == 0 && togo == 0 && lead) {
                            tma2d_prefetch(tw, h * 128 + 128, k * 128); tma2d_prefetch(tw, h * 128 + 192, k * 128);
                            l2_prefetch(reinterpret_cast<const unsigned char*>(P.c) + (size_t)cta * 16384, 16384);
                        }
                        if (v && togo <= 0 && togo > -OP_PF && lead) op_prefetch(-togo);
                    }
                }
                load_half(Vh, HM & 16);
                staging();
                if (v == 0 && lead) l2_prefetch(g_Q + (size_t)((h + 1) * 32 + 8 * k + 4 * rank) * 16384, 65536);
            }
            mbar_wait(misc + BAR_EMPTY + 8 * c.slot, c.ph ^ 1); c.adv();
            int st = 0; uint32_t ph3 = 0;
#pragma unroll 1
            for (int i = 0; i < 32; i++) {
                const int head = op_head(i >> 1, kap);
                if ((i & 1) == 0) dep_wait(D_CTX + (i >> 1));
                if (i < NST3) { mbar_wait(misc + BAR_EMPTY + 8 * c.slot, c.ph ^ 1); c.adv(); }
                else mbar_wait(misc + BAR_EMPTY3 + 8 * st, ph3 ^ 1);
                fb = misc + BAR_FULL3 + 8 * st; dst = ring + st * ST3_BYTES;
                if (i == LATE_AT && lead) mbar_arrive(misc + BAR_PROG + 16);
                if (lead) {
                    mbar_expect_tx(fb, ST3_BYTES);
                    const unsigned char* src = g_Q + (size_t)(head * 32 + 4 * u3 + 2 * rank) * 16384 + (i & 1) * 8192;
                    bulk_load(dst, src, 8192, fb, policy(HM & 32));
                    bulk_load(dst + 8192, src + 16384, 8192, fb, policy(HM & 32));
                    tma3d_mc(dst + 16384 + rank * 10240, &tmWo, 0, head * 128 + (i & 1) * 64 + rank * 32, 5 * s3, fb, policy(HM & 32));
                    if ((i & 1) && (i >> 1) + OP_PF < 16) op_prefetch((i >> 1) + OP_PF);
                }
                if (++st == NST3) { st = 0; ph3 ^= 1; }
            }
        } else if (warp == 3) {
            const unsigned ep1 = *reinterpret_cast<volatile unsigned*>(&g_epoch) + 1;
            if (lane == 0) {
                asm volatile("st.shared.u32 [%0], %1;" ::"r"(misc + MISC_EPOCH), "r"(ep1) : "memory");
                if (CDELAY) __nanosleep(CDELAY);
                l2_prefetch(reinterpret_cast<const unsigned char*>(P.c) + (size_t)cta * 12288, 12288);
#pragma unroll 1
                for (int t = 0; t < 4; t++) {
                    if (t == 1) {
                        mbar_wait(misc + BAR_PF, 0);
                        l2_prefetch(reinterpret_cast<const unsigned char*>(P.wq) + (size_t)cta * 40960, 40960);
                    }
                    if (t != 2) {
                        mbar_wait(misc + BAR_LN + 8 * t, 0);
                        flag_signal(flag_ptr(FL_LN + q_tile(cta >> 5, t)));
                    }
                    flag_wait(flag_ptr(FL_LN + q_tile(k, t)), ep1 * 32u);
                    mbar_arrive(misc + BAR_DEP + 8 * (D_LN + t));
                }
                mbar_wait(misc + BAR_EV + 8 * (16 + EV_KV + 3), 0);
                flag_wait(flag_ptr(FL_KV + team * 8), ep1 * 16u);
#pragma unroll 1
                for (int i = 0; i < 2; i++) {
                    mbar_wait(misc + BAR_EV + 8 * (16 + EV_Q + 1 + 2 * i), 0);
                    flag_wait(flag_ptr(FL_Q + team * 8 + (i ? k : 7 - k)), ep1 * 4u);
                    mbar_arrive(misc + BAR_DEP + 8 * (D_Q + i));
                }
#pragma unroll 1
                for (int i = 0; i < 2; i++) {
                    mbar_wait(misc + BAR_PROG + 8 * i, 0);
                    flag_signal(flag_ptr(FL_WAR + 2 * team + i));
                    flag_wait(flag_ptr(FL_WAR + 2 * team + i), ep1 * 8u);
                    mbar_arrive(misc + BAR_DEP + 8 * (D_WAR + i));
                }
#pragma unroll 1
                for (int i = 4; i < 8; i++) {
                    mbar_wait(misc + BAR_EV + 8 * (16 + EV_KV + i), 0);
                    flag_wait(flag_ptr(FL_KV + team * 8 + i), ep1 * 16u);
                    mbar_arrive(misc + BAR_DEP + 8 * (D_KV + i));
                }
                flag_wait(flag_ptr(FL_MOE_DONE), ep1);
                int4 s0 = __ldcg(reinterpret_cast<const int4*>(g_sel)), s1 = __ldcg(reinterpret_cast<const int4*>(g_sel) + 1);
                asm volatile("st.shared.v4.u32 [%0], {%1,%2,%3,%4};" ::"r"(misc + MISC_SEL), "r"(s0.x), "r"(s0.y), "r"(s0.z), "r"(s0.w) : "memory");
                asm volatile("st.shared.v4.u32 [%0], {%1,%2,%3,%4};" ::"r"(misc + MISC_SEL + 16), "r"(s1.x), "r"(s1.y), "r"(s1.z), "r"(s1.w) : "memory");
                mbar_arrive(misc + BAR_SEL);
            }
            __syncwarp();
            const unsigned* cf = flag_ptr(FL_CTX + op_head(lane & 15, kap) * 8 + u3);
#pragma unroll 1
            for (int half = 0; half < 2; half++) {
                if (half) mbar_wait(misc + BAR_EV + 8 * (EV_CTX + 3), 0);
                bool done = (lane >> 3) != half;
                for (int spin = 0; spin < 4000000; spin++) {
                    if (!done) {
                        unsigned v;
                        asm volatile("ld.acquire.gpu.global.u32 %0, [%1];" : "=r"(v) : "l"(cf) : "memory");
                        if ((int)(v - ep1 * 4u) >= 0) { mbar_arrive(misc + BAR_DEP + 8 * (D_CTX + lane)); done = true; }
                    }
                    if (__all_sync(0xffffffffu, done)) break;
                    __nanosleep(64);
                }
            }
        } else {
            const int w = warp - 1;
            if (lane < 20) {
#pragma unroll
                for (int i = 0; i < 2; i++) {
                    const int ch = w * 40 + i * 20 + lane;
                    uint4 u = __ldg(reinterpret_cast<const uint4*>(P.wr) + ch);
                    asm volatile("st.shared.v4.b32 [%0], {%1,%2,%3,%4};" ::"r"(misc + MISC_WR + 16 * ch), "r"(u.x), "r"(u.y), "r"(u.z), "r"(u.w) : "memory");
                }
            }
            const int rsub = (cta & 31) * 4 + 2 * w;
            if (LNDELAY) __nanosleep(LNDELAY);
            bar_sync(3, 64);
#pragma unroll 1
            for (int t = 0; t < 4; t += 1 + (t & 1)) {
                if (t < 2) {
#pragma unroll
                    for (int i = 0; i < 3; i++)
                        if (i * 32 + lane < 80) asm volatile("prefetch.global.L2 [%0];" ::"l"(P.x + (size_t)(q_tile(cta >> 5, 2 * t + 1) * 128 + rsub) * DM + (i * 32 + lane) * 16));
                }
                ln_rows(P, q_tile(cta >> 5, t) * 128 + rsub, lane, misc + MISC_WR);
                __syncwarp();
                if (lane == 0) mbar_arrive(misc + BAR_LN + 8 * t);
            }
            if (lane == 0) {
                const uint32_t eb = misc + BAR_EV + w * 128;
#pragma unroll 1
                for (int v = 0; v < 2; v++) {
#pragma unroll 1
                    for (int i = 0; i < (v ? 4 : 3); i++) {
                        mbar_wait(eb + 8 * (v ? EV_KV + 4 + i : i ? EV_Q + 2 * i - 1 : EV_KV + 3), 0);
                        flag_signal(flag_ptr(v ? FL_KV + team * 8 + 4 + i : i ? FL_Q + team * 8 + (i == 1 ? 7 - k : k) : FL_KV + team * 8));
                    }
#pragma unroll 1
                    for (int r = 0; r < 2; r++) {
                        const int p = r ? k : 7 - k;
                        const uint32_t slot = ((v ? E_ATT1 : E_ATT0) + (r ? 39 : 4 * p + 7) + E0) % NSLOT;
                        const int grp = (r == w) ? 3 - rank : rank;
                        mbar_wait(eb + 8 * (EV_CTX + 2 * v + r), 0);
                        asm volatile("cp.async.bulk.global.shared::cta.bulk_group.L2::cache_hint [%0], [%1], 16384, %2;"
                                     ::"l"(g_Q + (size_t)((2 * team + v) * 32 + 4 * p + grp) * 16384), "r"(ring + slot * SLOT_BYTES + w * 16384),
                                       "l"(policy((HM & 256) && v == 0)) : "memory");
                        asm volatile("cp.async.bulk.commit_group;" ::: "memory");
                        asm volatile("cp.async.bulk.wait_group.read 0;" ::: "memory");
                        mbar_arrive_cluster(mapa(misc + BAR_EMPTY + 8 * slot, 0), 4);
                        mbar_arrive_cluster(mapa(misc + BAR_EMPTY + 8 * slot, 1), 4);
                        asm volatile("cp.async.bulk.wait_group 0;" ::: "memory");
                        fence_async_global();
                        flag_signal(flag_ptr(FL_CTX + (2 * team + v) * 8 + p));
                    }
                }
            }
            __syncwarp();
            mbar_wait(misc + BAR_PROG + 16, 0);
            const int row = (2 * u3 + rank) * 128 + 64 * w + perm32(16 * (lane >> 3) + 8 * kap + (lane & 7));
#pragma unroll
            for (int i = 0; i < 10; i++) asm volatile("prefetch.global.L2 [%0];" ::"l"(P.x + (size_t)row * DM + 160 * s3 + 16 * i));
            asm volatile("prefetch.global.L2 [%0];" ::"l"(g_stats + row));
        }
    } else {
        asm volatile("setmaxnreg.inc.sync.aligned.u32 232;");
        Ctx c;
        c.ring = ring; c.misc = misc; c.w = wg - 1; c.warp = __shfl_sync(0xffffffffu, (tid >> 5) & 3, 0); c.lane = tid & 31;
        c.rel = mapa(misc, tid & 1);
        const int w = c.w;
        if (w == 1) bar_arrive(1, 256);
        if (PFV & 16) prefetch_w(2);
        prefetch_w(3);
        Cur cur = cur_at(0);
        float o[64], inv[2];
#pragma unroll 1
        for (int v = 0; v < 2; v++) {
        {
            uint32_t wf[128];
            float acc[64];
#pragma unroll
            for (int i = 32; i < 128; i++) wf[i] = 0u;
            Cur cw = cur;
            int wstep = 2;
            auto load_wchunk = [&](auto CH) {
                constexpr int ch = decltype(CH)::value;
                mbar_wait_hot(misc + BAR_FULL + 8 * cw.slot, cw.ph);
                const uint32_t z = load_afrag<8, 32 * ch>(wf, ring + cw.slot * SLOT_BYTES + w * 16384, c);
                release(c, BAR_EMPTY + 8 * cw.slot + z, 1);
                cw.adv();
                if (wstep == 2 || ch == 2) cw.adv();
            };
            load_wchunk(IC<0>{});
            cur.adv();
            int nload = 1;
            PROF_EV(2); PROF_GT(60);
#pragma unroll 1
            for (int t = 0; t < (v ? 4 : 8); t++) {
                uint32_t last = 0;
                token_wait(w);
                PROF_EV(t < 4 ? 10 : 20);
                undef_regs(acc);
                auto chunk = [&](auto CH) {
                    constexpr int ch = decltype(CH)::value;
                    mbar_wait_hot(misc + BAR_FULL + 8 * cur.slot, cur.ph);
                    if (t == 0 || t == 4) { PROF_EV(12 + ch); }
                    uint64_t d = mkdesc(ring + cur.slot * SLOT_BYTES, 16, 1024, 1);
                    wg_fence();
#pragma unroll
                    for (int ks = 0; ks < 8; ks++)
                        wgmma_rs_n128_ta0_tb0(acc, wf[32 * ch + 4 * ks], wf[32 * ch + 4 * ks + 1], wf[32 * ch + 4 * ks + 2], wf[32 * ch + 4 * ks + 3],
                                              d + (ks >> 2) * 1024 + (ks & 3) * 2, (ch | ks) != 0);
                    wg_commit();
                    const bool swap = (ch < (FV == 2 ? 3 : 2) && t == 0) || (ch == 3 && t < 4);
                    if (swap) token_pass(w);
                    if constexpr (ch < 3) { if (nload == ch + 1) { load_wchunk(IC<ch + 1>{}); nload++; } }
                    if (ch > 0) { wg_wait<1>(); release(c, BAR_EMPTY + 8 * last, 1); }
                    last = cur.slot;
                    cur.adv();
                    if ((ch < 3 && t == 0) || (ch == 0 && t == 4)) cur.adv();
                    if constexpr (FV == 1 && ch == 1) { if (t == 0) { load_wchunk(IC<3>{}); nload++; } }
                    if constexpr (FV == 3 && ch == 1) { if (t == 0 && w) { load_wchunk(IC<3>{}); nload++; } }
                    if (ch < 3 && swap) token_wait(w);
                };
                chunk(IC<0>{}); chunk(IC<1>{}); chunk(IC<2>{}); chunk(IC<3>{});
                if (t < 4) {
                    wg_wait<0>();
                    release(c, BAR_EMPTY + 8 * last, 1);
                } else {
                    Cur cx = cur; cur.adv();
                    mbar_wait_hot(misc + BAR_FULL + 8 * cx.slot, cx.ph);
                    mbar_wait_hot(misc + BAR_FULL + 8 * cur.slot, cur.ph);
                    uint64_t db = mkdesc(ring + cx.slot * SLOT_BYTES, 16, 1024, 1);
                    uint64_t da = mkdesc(ring + cur.slot * SLOT_BYTES + w * 16384, 16384, 1024, 1);
                    wg_fence();
#pragma unroll
                    for (int ks = 0; ks < 8; ks++) wgmma_ss_n128_ta1_tb0(acc, da + 128 * ks, db + (ks >> 2) * 1024 + (ks & 3) * 2, 1);
                    wg_commit();
                    token_pass(w);
                    wg_wait<1>(); release(c, BAR_EMPTY + 8 * last, 1);
                    wg_wait<0>(); release(c, BAR_EMPTY + 8 * cx.slot, 1); release(c, BAR_EMPTY + 8 * cur.slot, 1);
                    cur.adv();
                    fence_regs(acc);
#pragma unroll
                    for (int i = 0; i < 64; i++) acc[i] *= SM_SCALE;
                }
                PROF_EV(t < 4 ? 11 : 21);
                fence_regs(acc);
                if (t == 0 && v == 0 && tid == 128) mbar_arrive(misc + BAR_PF);
                const bool wswitch = t == 3 && v == 0;
                if (wswitch) {
                    cw = cur; wstep = 1; nload = 0;
                    cur.adv(); cur.adv(); cur.adv();
                    if (w) { load_wchunk(IC<0>{}); load_wchunk(IC<1>{}); load_wchunk(IC<2>{}); nload = 3; }
                }
                unsigned char* dst = t < 4 ? (rank ? g_V : g_K) + (size_t)(team * 32 + 24 + 2 * k - 8 * t) * 16384
                                           : g_Q + (size_t)((2 * team + rank) * 32 + q_tile(k, t & 3) * 2) * 16384;
                store_proj(acc, dst, c, policy(((HM & 64) && t >= 4 && rank) || ((HM & 128) && t >= 6)));
                signal_event(c, t < 4 ? EV_KV + 4 * v + t : EV_Q + t - 4);
                if (wswitch) {
                    if (w) { load_wchunk(IC<3>{}); nload = 4; }
                    else { load_wchunk(IC<0>{}); load_wchunk(IC<1>{}); nload = 2; }
                }
                if (t == 3) { PROF_EV(61); PROF_GT(62); }
            }
        }
        PROF_EV(63); PROF_GT(64);
        {
            uint32_t q[32], p[32];
            float m[2], l[2], tq[2];
#pragma unroll
            for (int i = 0; i < 64; i++) o[i] = 0.f;
#pragma unroll
            for (int i = 0; i < 32; i++) p[i] = 0u;
            m[0] = m[1] = inv[0] = inv[1] = 0.f;
            l[0] = l[1] = tq[0] = tq[1] = 1.f;
            int gen = 0;
            Cur ck = cur, cv = cur, cq, ce;
            int r = 0, left;
            int first = 1, half, heavy;
            int pv_acc = 0, pv_mode = 2; uint32_t pv_cnt = 0;
            int pending = 0;
            Cur nck, ncv;
            auto next_task = [&](int rr) {
                heavy = 1 ^ rr ^ w;
                half = 1 ^ heavy ^ rank;
                left = 2 * (rr ? k : 7 - k) + 1 + heavy;
                cq = cur; cur.adv();
                nck = cur; cur.adv();
                if (rr) { ncv = cur; cur.adv(); ce = cur; cur.adv(); }
                if (!heavy) { nck = cur; cur.adv(); cur.adv(); }
                if (!rr) { ncv = nck; ce = nck; }
            };
            auto load_q = [&]() {
                mbar_wait_hot(misc + BAR_FULL + 8 * cq.slot, cq.ph);
                load_afrag<8, 0>(q, ring + cq.slot * SLOT_BYTES + w * 16384, c);
            };
            next_task(0);
            load_q();
            uint32_t k_cnt = 1; int last = 0, was_first = 0, was_half = 0, publish = 0;
            auto window = [&]() {
                mbar_wait_hot(misc + BAR_FULL + 8 * cv.slot, cv.ph);
                publish = pending;
                if (pending) stage_ctx<2, 4>(o, inv, ce, c);
                pending = 0;
                k_cnt = 1;
                was_first = first; was_half = half;
                if (first) {
                    release(c, BAR_EMPTY + 8 * cq.slot, 1);
                    l[0] += tq[0]; l[1] += tq[1];
                    tq[0] = __shfl_xor_sync(0xffffffffu, l[0], 2); tq[1] = __shfl_xor_sync(0xffffffffu, l[1], 2);
                    pending = r;
                    k_cnt = 1 + heavy;
                }
                last = --left == 0 ? 1 : 0;
                first = last;
                if (!last) { nck = cur; cur.adv(); ncv = cur; cur.adv(); half = 0; }
                else if (++r < 2) next_task(1);
            };
            auto new_rows = [&]() {
                inv[0] = rcp_fast(l[0] + tq[0]); inv[1] = rcp_fast(l[1] + tq[1]);
                l[0] = l[1] = m[0] = m[1] = 0.f;
                gen = 0;
            };
            ck = nck; cv = ncv;
            mbar_wait_hot(misc + BAR_FULL + 8 * ck.slot, ck.ph);
            uint32_t qaddr1 = ring + (((v ? E_ATT1 : E_ATT0) + 32 - 4 * k + E0) % NSLOT) * SLOT_BYTES + w * 16384 +
                              (8 * (c.lane >> 4) + (c.lane & 7)) * 128 + (((2 * c.warp + ((c.lane >> 3) & 1)) ^ (c.lane & 7)) << 4);
            qaddr1 = __shfl_sync(0xffffffffu, qaddr1, c.lane);
#pragma unroll 1
            while (r < 2) {
                float s[64];
                if (half) {
                    token_wait(w);
                    PROF_EV(30);
                    float sh[32];
                    undef_regs(sh);
                    issue_qk_half(sh, q, ring + ck.slot * SLOT_BYTES);
                    window();
                    issue_pv(o, p, ring + cv.slot * SLOT_BYTES, pv_acc, pv_mode);
                    token_pass(w);
                    wg_wait<1>();
                    PROF_EV(34);
                    fence_regs(sh);
                    new_rows();
                    mask_diag<0>(sh, c);
                    float l0 = 0.f, l1 = 0.f;
                    if (blockIdx.y == 0) {
#pragma unroll
                        for (int j = 0; j < 8; j++) {
#pragma unroll
                            for (int e = 0; e < 4; e++) ex2v(sh[4 * j + e]);
                            l0 += sh[4 * j] + sh[4 * j + 1]; l1 += sh[4 * j + 2] + sh[4 * j + 3];
                        }
                    }
                    const int lim = mask_lim(c);
                    const bool bad = __any_sync(0xffffffffu, !(l0 <= SAFE_SUM && l1 <= SAFE_SUM && (l0 >= 1.0f / SAFE_SUM || lim < 0) &&
                                                               (l1 >= 1.0f / SAFE_SUM || lim < -2)));
                    if (!bad) { l[0] = l0; l[1] = l1; asm volatile("" ::: "memory"); }
                    wg_wait<0>();
                    fence_regs(o);
                    fence_regs(sh);
                    if (bad) goto redo;
#pragma unroll
                    for (int i = 0; i < 16; i++) p[i] = pack_bf16(sh[2 * i], sh[2 * i + 1]);
                    goto tail;
                }
#pragma unroll 1
                while (true) {
                    token_wait(w);
                    PROF_EV(first ? 30 : 31);
                    undef_regs(s);
                    issue_qk(s, q, ring + ck.slot * SLOT_BYTES);
                    const bool special = first > 0 || pv_acc == 0 || left == 1;
                    if (special) window();
                    else {
                        nck = cur; cur.adv(); ncv = cur; cur.adv();
                        --left;
                        mbar_wait_hot(misc + BAR_FULL + 8 * cv.slot, cv.ph);
                    }
                    issue_pv(o, p, ring + cv.slot * SLOT_BYTES, pv_acc, pv_mode);
                    token_pass(w);
                    wg_wait<1>();
                    PROF_EV(33);
                    fence_regs(s);
                    float lo = 0.f;
                    if (special) {
                        if (last && r < 2) {
                            mbar_wait_hot(misc + BAR_FULL + 8 * cq.slot, cq.ph);
#pragma unroll
                            for (int ks = 0; ks < 8; ks++) ldsm4t(q[4 * ks], q[4 * ks + 1], q[4 * ks + 2], q[4 * ks + 3], qaddr1 + ks * 2048);
                        }
                        if (publish) publish_ctx(EV_CTX + 2 * v, c);
                        if (was_first) {
                            new_rows();
                            lo = 1.0f / SAFE_SUM;
                            mask_diag<8>(s, c);
                        }
                    }
                    constexpr int JB = 11;
                    float l0 = l[0], l1 = l[1];
                    if (!gen) {
#pragma unroll
                        for (int j = 0; j < JB; j++) {
#pragma unroll
                            for (int e = 0; e < 4; e++) ex2v(s[4 * j + e]);
                            if (j < JB - 1) { l0 += s[4 * j] + s[4 * j + 1]; l1 += s[4 * j + 2] + s[4 * j + 3]; }
                        }
                    }
                    wg_wait<0>();
                    fence_regs(o);
                    if (gen) goto general;
#pragma unroll
                    for (int j = JB - 1; j < 16; j++) {
                        if (j >= JB) {
#pragma unroll
                            for (int e = 0; e < 4; e++) ex2v(s[4 * j + e]);
                        }
                        l0 += s[4 * j] + s[4 * j + 1]; l1 += s[4 * j + 2] + s[4 * j + 3];
                    }
#pragma unroll
                    for (int i = 0; i < 32; i++) p[i] = pack_bf16(s[2 * i], s[2 * i + 1]);
                    if (__any_sync(0xffffffffu, !(l0 <= SAFE_SUM && l1 <= SAFE_SUM && l0 >= lo && l1 >= lo))) goto redo;
                    l[0] = l0; l[1] = l1;
                    if (special) goto tail;
                    release(c, BAR_EMPTY + 8 * ck.slot, 1);
                    release(c, BAR_EMPTY + 8 * cv.slot, 1);
                    ck = nck; cv = ncv;
                    mbar_wait_hot(misc + BAR_FULL + 8 * ck.slot, ck.ph);
                }
            redo:
                {
                    const int rr = r - last;
                    const int grp = (rr == w) ? 3 - rank : rank;
                    recompute_scores(s, g_Q + (size_t)((2 * team + v) * 32 + 4 * (rr ? k : 7 - k) + grp) * 16384, ring + ck.slot * SLOT_BYTES, c);
                    if (was_first) { mask_any(s, was_half ^ 1, c); m[0] = m[1] = -INFINITY; }
                    gen = 1;
                }
            general:
                {
                    float mx[2], alpha[2];
                    row_max<16>(s, mx);
#pragma unroll
                    for (int i = 0; i < 2; i++) {
                        mx[i] = fmaxf(mx[i], m[i]);
                        alpha[i] = was_first ? 1.0f : ex2(m[i] - mx[i]);
                        m[i] = mx[i];
                        l[i] *= alpha[i];
                    }
                    exp_sum<16, true>(s, m, l[0], l[1]);
#pragma unroll
                    for (int i = 0; i < 64; i++) o[i] *= alpha[(i >> 1) & 1];
#pragma unroll
                    for (int i = 0; i < 32; i++) p[i] = pack_bf16(s[2 * i], s[2 * i + 1]);
                }
            tail:
                release(c, BAR_EMPTY + 8 * ck.slot, k_cnt);
                if (pv_cnt) release(c, BAR_EMPTY + 8 * cv.slot, pv_cnt);
                pv_acc = was_first ^ 1; pv_mode = was_half; pv_cnt = k_cnt;
                if (r < 2) { ck = nck; cv = ncv; } else ck = cur;
                mbar_wait_hot(misc + BAR_FULL + 8 * ck.slot, ck.ph);
                if (pending) stage_ctx<0, 2>(o, inv, ce, c);
                if (last) { tq[0] = __shfl_xor_sync(0xffffffffu, l[0], 1); tq[1] = __shfl_xor_sync(0xffffffffu, l[1], 1); }
            }
            if (pending) { stage_ctx<2, 4>(o, inv, ce, c); publish_ctx(EV_CTX + 2 * v, c); }
            token_wait(w);
            PROF_EV(32);
            issue_pv(o, p, ring + cur.slot * SLOT_BYTES, pv_acc, pv_mode);
            if (w == 0 || v == 0) token_pass(w);
            l[0] += tq[0]; l[1] += tq[1];
            inv[0] = rcp_fast(l[0] + __shfl_xor_sync(0xffffffffu, l[0], 2));
            inv[1] = rcp_fast(l[1] + __shfl_xor_sync(0xffffffffu, l[1], 2));
            wg_wait<0>();
            release(c, BAR_EMPTY + 8 * cur.slot, pv_cnt);
            fence_regs(o);
            cur.adv();
            if (v == 0) { stage_ctx<0, 4>(o, inv, cur, c); publish_ctx(EV_CTX + 1, c); cur.adv(); }
        }
        }
        {
            float acc[80];
            undef_regs(acc);
            int st = 0, prev = 0; uint32_t ph3 = 0;
            auto op_stage = [&](int i) {
                mbar_wait(misc + BAR_FULL3 + 8 * st, ph3);
                PROF_EV(44);
                uint32_t base = ring + st * ST3_BYTES;
                uint64_t da = mkdesc(base + w * 8192, 16, 1024, 1);
                uint64_t db = mkdesc(base + 16384, 2048, 512, 2);
                wg_fence();
#pragma unroll
                for (int k = 0; k < 4; k++) wgmma_ss_n160_ta0_tb1(acc, da + 2 * k, db + (k >> 1) * 640 + (k & 1) * 64, k ? 1 : i);
                wg_commit();
                if (i > 0) { wg_wait<1>(); if (i <= 32 - NST3) release(c, BAR_EMPTY3 + 8 * prev, 1); }
                prev = st;
                if (++st == NST3) { st = 0; ph3 ^= 1; }
            };
            PROF_EV(40); PROF_GT(65);
            op_stage(0);
            stage_ctx<0, 4>(o, inv, cur, c);
            publish_ctx(EV_CTX + 3, c);
#pragma unroll 1
            for (int i = 1; i < 12; i++) op_stage(i);
            mbar_wait(misc + BAR_SEL, 0);
            const uint32_t tag = lds32(misc + MISC_EPOCH) & 1;
            const int g = c.lane >> 2, t = c.lane & 3;
            const int row = (2 * u3 + rank) * 128 + 64 * w + perm32(16 * c.warp + 8 * kap + (((g & 3) << 1) | (g >> 2)));
            const int col = 160 * s3 + 8 * t;
            int sel = -1;
#pragma unroll
            for (int i = 0; i < TOPC; i++) if ((int)lds32(misc + MISC_SEL + 4 * i) == row) sel = i;
            const int t256 = tid - 128;
            uint4* sendp = g_part + (size_t)cta * 2560 + t256;
            if (c.lane >= 30) stg128(sendp + 9 * 256, tag ^ 1, tag ^ 1, tag ^ 1, tag ^ 1);
#pragma unroll 1
            for (int i = 12; i < 32; i++) op_stage(i);
            uint4 xv[5], bv[5];
#pragma unroll
            for (int i = 0; i < 5; i++) xv[i] = ldg128(P.x + (size_t)row * DM + col + 32 * i);
            uint2 stat;
            asm volatile("ld.global.cg.v2.b32 {%0,%1}, [%2];" : "=r"(stat.x), "=r"(stat.y) : "l"(g_stats + row) : "memory");
            wg_wait<0>();
            fence_regs(acc);
            PROF_EV(41); PROF_GT(66);
            float keep[40];
#pragma unroll
            for (int j = 0; j < 10; j++) {
                uint32_t v0 = __float_as_uint(kap ? acc[8 * j + 0] : acc[8 * j + 2]), v1 = __float_as_uint(kap ? acc[8 * j + 1] : acc[8 * j + 3]);
                uint32_t v2 = __float_as_uint(kap ? acc[8 * j + 4] : acc[8 * j + 6]), v3 = __float_as_uint(kap ? acc[8 * j + 5] : acc[8 * j + 7]);
                asm volatile("st.relaxed.gpu.global.v4.b32 [%0], {%1,%2,%3,%4};" ::"l"(sendp + j * 256),
                             "r"((v0 & ~1u) | tag), "r"((v1 & ~1u) | tag), "r"((v2 & ~1u) | tag), "r"((v3 & ~1u) | tag) : "memory");
                keep[4 * j + 0] = kap ? acc[8 * j + 2] : acc[8 * j + 0]; keep[4 * j + 1] = kap ? acc[8 * j + 3] : acc[8 * j + 1];
                keep[4 * j + 2] = kap ? acc[8 * j + 6] : acc[8 * j + 4]; keep[4 * j + 3] = kap ? acc[8 * j + 7] : acc[8 * j + 5];
            }
            PROF_GT(67);
#pragma unroll
            for (int i = 0; i < 5; i++) {
                uint32_t xx[4] = {xv[i].x, xv[i].y, xv[i].z, xv[i].w};
#pragma unroll
                for (int e = 0; e < 4; e++) {
                    asm("sub.rn.bf16x2 %0, %0, %1;" : "+r"(xx[e]) : "r"(stat.x));
                    xx[e] = pack_bf16(bf_lo(xx[e]) * __uint_as_float(stat.y), bf_hi(xx[e]) * __uint_as_float(stat.y));
                }
                bv[i] = make_uint4(xx[0], xx[1], xx[2], xx[3]);
            }
            if (sel >= 0) {
#pragma unroll
                for (int i = 0; i < 5; i++) bv[i] = ldg128(g_brow + sel * DM + col + 32 * i);
            }
            const uint4* recvp = g_part + (size_t)partner * 2560 + t256;
            uint4 rv[10];
            int spins = 0;
            while (POLL1) {
                uint32_t v;
                asm volatile("ld.relaxed.gpu.global.b32 %0, [%1];" : "=r"(v) : "l"(recvp + 9 * 256 + (31 - c.lane)) : "memory");
                if (__all_sync(0xffffffffu, (v & 1u) == tag) || ++spins > 2000000) break;
            }
            PROF_GT(68);
            while (true) {
                uint32_t bad = 0u;
#pragma unroll
                for (int j = 0; j < 10; j++) {
                    asm volatile("ld.relaxed.gpu.global.v4.b32 {%0,%1,%2,%3}, [%4];"
                                 : "=r"(rv[j].x), "=r"(rv[j].y), "=r"(rv[j].z), "=r"(rv[j].w) : "l"(recvp + j * 256) : "memory");
                }
#pragma unroll
                for (int j = 0; j < 10; j++) {
                    rv[j].x ^= tag; rv[j].y ^= tag; rv[j].z ^= tag; rv[j].w ^= tag;
                    bad |= rv[j].x | rv[j].y | rv[j].z | rv[j].w;
                }
                if (__all_sync(0xffffffffu, (bad & 1u) == 0) || ++spins > 2000000) break;
            }
            PROF_GT(69);
            uint32_t pk[20];
#pragma unroll
            for (int j = 0; j < 10; j++) {
                pk[2 * j] = pack_bf16(keep[4 * j] + __uint_as_float(rv[j].x), keep[4 * j + 1] + __uint_as_float(rv[j].y));
                pk[2 * j + 1] = pack_bf16(keep[4 * j + 2] + __uint_as_float(rv[j].z), keep[4 * j + 3] + __uint_as_float(rv[j].w));
            }
#pragma unroll
            for (int i = 0; i < 5; i++) {
                uint32_t a0 = pk[4 * i], a1 = pk[4 * i + 1], a2 = pk[4 * i + 2], a3 = pk[4 * i + 3];
                uint32_t x0 = (t & 1) ? a0 : a1, x1 = (t & 1) ? a2 : a3;
                x0 = __shfl_xor_sync(0xffffffffu, x0, 1); x1 = __shfl_xor_sync(0xffffffffu, x1, 1);
                if (t & 1) { a0 = x0; a2 = x1; } else { a1 = x0; a3 = x1; }
                x0 = (t & 2) ? a0 : a2; x1 = (t & 2) ? a1 : a3;
                x0 = __shfl_xor_sync(0xffffffffu, x0, 2); x1 = __shfl_xor_sync(0xffffffffu, x1, 2);
                if (t & 2) { a0 = x0; a1 = x1; } else { a2 = x0; a3 = x1; }
                uint32_t av[4] = {a0, a1, a2, a3};
                uint32_t xx[4] = {xv[i].x, xv[i].y, xv[i].z, xv[i].w}, bb[4] = {bv[i].x, bv[i].y, bv[i].z, bv[i].w};
                uint32_t ov[4];
#pragma unroll
                for (int e = 0; e < 4; e++) {
                    asm("add.rn.bf16x2 %0, %1, %2;" : "=r"(ov[e]) : "r"(xx[e]), "r"(av[e]));
                    asm("add.rn.bf16x2 %0, %0, %1;" : "+r"(ov[e]) : "r"(bb[e]));
                }
                stg128(P.out + (size_t)row * DM + col + 32 * i, ov[0], ov[1], ov[2], ov[3]);
            }
            PROF_EV(42); PROF_GT(43);
        }
    }
}

typedef CUresult (*EncodeFn)(CUtensorMap*, CUtensorMapDataType, cuuint32_t, void*, const cuuint64_t*, const cuuint64_t*, const cuuint32_t*,
                             const cuuint32_t*, CUtensorMapInterleave, CUtensorMapSwizzle, CUtensorMapL2promotion, CUtensorMapFloatOOBfill);

void make_map2d(EncodeFn enc, CUtensorMap* tm, const void* p, uint64_t cols, uint64_t rows) {
    cuuint64_t gd[2] = {cols, rows}, gs[1] = {cols * 2};
    cuuint32_t box[2] = {64, 128}, es[2] = {1, 1};
    enc(tm, CU_TENSOR_MAP_DATA_TYPE_BFLOAT16, 2, const_cast<void*>(p), gd, gs, box, es, CU_TENSOR_MAP_INTERLEAVE_NONE,
        CU_TENSOR_MAP_SWIZZLE_128B, CU_TENSOR_MAP_L2_PROMOTION_L2_128B, CU_TENSOR_MAP_FLOAT_OOB_FILL_NONE);
}

void make_map3d(EncodeFn enc, CUtensorMap* tm, const void* p, uint64_t cols, uint64_t rows, uint32_t bw, uint32_t nb) {
    cuuint64_t gd[3] = {bw, rows, cols / bw}, gs[2] = {cols * 2, bw * 2};
    cuuint32_t box[3] = {bw, 32, nb}, es[3] = {1, 1, 1};
    enc(tm, CU_TENSOR_MAP_DATA_TYPE_BFLOAT16, 3, const_cast<void*>(p), gd, gs, box, es, CU_TENSOR_MAP_INTERLEAVE_NONE,
        bw == 64 ? CU_TENSOR_MAP_SWIZZLE_128B : CU_TENSOR_MAP_SWIZZLE_64B, CU_TENSOR_MAP_L2_PROMOTION_L2_128B, CU_TENSOR_MAP_FLOAT_OOB_FILL_NONE);
}

}

extern "C" void kernel_launch(void* const* d_in, const int* in_sizes, int n_in, void* d_out, int out_size) {
    (void)in_sizes; (void)n_in; (void)out_size;
    static EncodeFn enc = nullptr;
    if (!enc) {
        void* fn = nullptr;
        cudaDriverEntryPointQueryResult qr;
        cudaGetDriverEntryPoint("cuTensorMapEncodeTiled", &fn, cudaEnableDefault, &qr);
        enc = (EncodeFn)fn;
        cudaFuncSetAttribute(fused_kernel, cudaFuncAttributeMaxDynamicSharedMemorySize, SMEM_BYTES);
    }
    CUtensorMap tmC, tmWk, tmWv, tmWq, tmWo, tmG, tmU, tmD;
    make_map2d(enc, &tmC, d_in[1], DC, SEQ);
    make_map2d(enc, &tmWq, d_in[2], 4096, DM);
    make_map2d(enc, &tmWk, d_in[3], 4096, DC);
    make_map2d(enc, &tmWv, d_in[4], 4096, DC);
    make_map3d(enc, &tmWo, d_in[5], DM, 4096, 32, 5);
    make_map3d(enc, &tmG, d_in[8], FF, DM, 64, 7);
    make_map3d(enc, &tmU, d_in[9], FF, DM, 64, 7);
    make_map3d(enc, &tmD, d_in[10], DM, FF, 64, 10);
    Params P;
    P.x = (const __nv_bfloat16*)d_in[0];
    P.c = (const __nv_bfloat16*)d_in[1];
    P.wq = (const __nv_bfloat16*)d_in[2];
    P.wk = (const __nv_bfloat16*)d_in[3];
    P.wv = (const __nv_bfloat16*)d_in[4];
    P.wo = (const __nv_bfloat16*)d_in[5];
    P.wr = (const __nv_bfloat16*)d_in[7];
    P.out = (__nv_bfloat16*)d_out;
    fused_kernel<<<132, 384, SMEM_BYTES>>>(tmC, tmWk, tmWv, tmWq, tmWo, tmG, tmU, tmD, P);
}
```

```cpp
#include <cuda_runtime.h>
#include <cuda_bf16.h>
#include <cuda.h>
#include <stdint.h>

#define HM 960
#define POLL1 1
#define OP_PF 8
#define PF_START 9
#define LATE_AT 18
#define CDELAY 2000
#define LNDELAY 0
#define AUXDELAY 1000
#define FV 3
namespace {

constexpr int SEQ = 2048, NH = 32, DM = 640, DC = 512, FF = 1728, TOPC = 8;
constexpr int NSLOT = 7, SLOT_BYTES = 32768;
constexpr int NST3 = 6, ST3_BYTES = 36864;
constexpr int RING_BYTES = NSLOT * SLOT_BYTES;
constexpr int SMEM_BYTES = RING_BYTES + 3072;

constexpr int BAR_FULL = 96  , BAR_FULL3 = 152  , BAR_DEP = 200  , BAR_PF = 456, BAR_SEL = 464,
              BAR_LN = 472  , BAR_EV = 504  , BAR_EMPTY = 760  , BAR_EMPTY3 = 816  ,
              BAR_PROG = 864  , MISC_EPOCH = 896, MISC_SMID = 900  , MISC_SEL = 912, MISC_WR = 1024  ;
constexpr int D_LN = 0  , D_KV = 4  , D_Q = 12  , D_WAR = 14  , D_CTX = 16  ;
constexpr int EV_KV = 0  , EV_Q = 8  , EV_CTX = 12  ;

constexpr int FL_MOE_CNT = 0, FL_MOE_DONE = 1, FL_LN = 16  , FL_KV = 32  , FL_Q = 160  , FL_CTX = 416  , FL_WAR = 672  , FL_TOTAL = 704;

__device__ __align__(1024) unsigned char g_K[16 * 32 * 16384];
__device__ __align__(1024) unsigned char g_V[16 * 32 * 16384];
__device__ __align__(1024) unsigned char g_Q[NH * 32 * 16384];
__device__ __align__(1024) unsigned char g_xn[16 * 10 * 16384];
__device__ __align__(1024) uint4 g_part[128 * 10 * 256];
__device__ float g_router[SEQ];
__device__ uint2 g_stats[SEQ];
__device__ __align__(16) float g_moe_part[4 * TOPC * DM];
__device__ __align__(16) __nv_bfloat16 g_brow[TOPC * DM];
__device__ __align__(16) int g_sel[TOPC];
__device__ unsigned g_flags[FL_TOTAL * 8];
__device__ unsigned g_epoch;
__device__ unsigned g_roleq[130];

struct Params {
    const __nv_bfloat16 *x, *c, *wr, *wq, *wk, *wv, *wo;
    __nv_bfloat16* out;
};

__device__ __forceinline__ uint32_t smem_u32(const void* p) { return (uint32_t)__cvta_generic_to_shared(p); }
__device__ __forceinline__ void mbar_init(uint32_t bar, int cnt) { asm volatile("mbarrier.init.shared::cta.b64 [%0], %1;" ::"r"(bar), "r"(cnt)); }
__device__ __forceinline__ void mbar_expect_tx(uint32_t bar, uint32_t bytes) {
    asm volatile("mbarrier.arrive.expect_tx.shared::cta.b64 _, [%0], %1;" ::"r"(bar), "r"(bytes) : "memory");
}
__device__ __forceinline__ void mbar_arrive(uint32_t bar) { asm volatile("mbarrier.arrive.shared::cta.b64 _, [%0];" ::"r"(bar) : "memory"); }
__device__ __forceinline__ void mbar_arrive_cluster(uint32_t cluster_addr, uint32_t cnt) {
    asm volatile("mbarrier.arrive.shared::cluster.b64 _, [%0], %1;" ::"r"(cluster_addr), "r"(cnt) : "memory");
}
__device__ __forceinline__ uint32_t mapa(uint32_t addr, uint32_t cta) {
    uint32_t r; asm("mapa.shared::cluster.u32 %0, %1, %2;" : "=r"(r) : "r"(addr), "r"(cta)); return r;
}
__device__ __forceinline__ void mbar_wait(uint32_t bar, uint32_t parity) {
    asm volatile(
        "{\n.reg .pred p;\n.reg .u32 n;\n"
        "mbarrier.try_wait.parity.shared::cta.b64 p, [%0], %1;\n"
        "@p bra DONE;\n"
        "mov.u32 n, 0;\n"
        "LAB_WAIT:\n"
        "mbarrier.try_wait.parity.shared::cta.b64 p, [%0], %1, 100000;\n"
        "@p bra DONE;\n"
        "add.u32 n, n, 1;\n"
        "setp.lt.u32 p, n, 200000;\n"
        "@p bra LAB_WAIT;\n"
        "trap;\n"
        "DONE:\n}\n" ::"r"(bar), "r"(parity) : "memory");
}
__device__ __forceinline__ void mbar_wait_hot(uint32_t bar, uint32_t parity) {
    asm volatile("{\n.reg .pred p;\nLAB_WAIT:\nmbarrier.try_wait.parity.shared::cta.b64 p, [%0], %1;\n@!p bra LAB_WAIT;\n}\n" ::"r"(bar), "r"(parity) : "memory");
}
__device__ __forceinline__ void flag_wait(const unsigned* flag, unsigned target) {
    asm volatile(
        "{\n.reg .pred p;\n.reg .u32 n, v;\n.reg .s32 d;\n"
        "mov.u32 n, 0;\n"
        "LAB_WAIT:\n"
        "ld.acquire.gpu.global.u32 v, [%0];\n"
        "sub.s32 d, v, %1;\n"
        "setp.ge.s32 p, d, 0;\n"
        "@p bra DONE;\n"
        "nanosleep.u32 40;\n"
        "add.u32 n, n, 1;\n"
        "setp.lt.u32 p, n, 3000000;\n"
        "@p bra LAB_WAIT;\n"
        "trap;\n"
        "DONE:\n}\n" ::"l"(flag), "r"(target) : "memory");
}
__device__ __forceinline__ void flag_signal(unsigned* flag) {
    asm volatile("red.release.gpu.global.add.u32 [%0], 1;" ::"l"(flag) : "memory");
}
__device__ __forceinline__ void fence_async_global() { asm volatile("fence.proxy.async.global;" ::: "memory"); }
__device__ __forceinline__ unsigned* flag_ptr(int idx) { return g_flags + idx * 8; }

__device__ __forceinline__ uint64_t policy_stream() {
    uint64_t p; asm("createpolicy.fractional.L2::evict_first.b64 %0, 1.0;" : "=l"(p)); return p;
}
__device__ __forceinline__ uint64_t policy_normal() { return 0x1000000000000000ull; }
__device__ __forceinline__ uint64_t policy(bool stream) { return stream ? policy_stream() : policy_normal(); }
__device__ __forceinline__ void bulk_load(uint32_t dst, const void* src, uint32_t bytes, uint32_t bar, uint64_t pol) {
    asm volatile("cp.async.bulk.shared::cluster.global.mbarrier::complete_tx::bytes.L2::cache_hint [%0], [%1], %2, [%3], %4;"
                 ::"r"(dst), "l"(src), "r"(bytes), "r"(bar), "l"(pol) : "memory");
}
__device__ __forceinline__ void bulk_load_mc(uint32_t dst, const void* src, uint32_t bytes, uint32_t bar, uint64_t pol) {
    asm volatile("cp.async.bulk.shared::cluster.global.mbarrier::complete_tx::bytes.multicast::cluster.L2::cache_hint [%0], [%1], %2, [%3], %4, %5;"
                 ::"r"(dst), "l"(src), "r"(bytes), "r"(bar), "h"((uint16_t)3), "l"(pol) : "memory");
}
__device__ __forceinline__ void tma2d(uint32_t dst, const CUtensorMap* tm, int c0, int c1, uint32_t bar, uint64_t pol) {
    asm volatile("cp.async.bulk.tensor.2d.shared::cluster.global.mbarrier::complete_tx::bytes.L2::cache_hint [%0], [%1, {%3, %4}], [%2], %5;"
                 ::"r"(dst), "l"(tm), "r"(bar), "r"(c0), "r"(c1), "l"(pol) : "memory");
}
__device__ __forceinline__ void tma2d_mc(uint32_t dst, const CUtensorMap* tm, int c0, int c1, uint32_t bar, uint64_t pol) {
    asm volatile("cp.async.bulk.tensor.2d.shared::cluster.global.mbarrier::complete_tx::bytes.multicast::cluster.L2::cache_hint [%0], [%1, {%3, %4}], [%2], %5, %6;"
                 ::"r"(dst), "l"(tm), "r"(bar), "r"(c0), "r"(c1), "h"((uint16_t)3), "l"(pol) : "memory");
}
__device__ __forceinline__ void tma3d_mc(uint32_t dst, const CUtensorMap* tm, int c0, int c1, int c2, uint32_t bar, uint64_t pol) {
    asm volatile("cp.async.bulk.tensor.3d.shared::cluster.global.mbarrier::complete_tx::bytes.multicast::cluster.L2::cache_hint [%0], [%1, {%3, %4, %5}], [%2], %6, %7;"
                 ::"r"(dst), "l"(tm), "r"(bar), "r"(c0), "r"(c1), "r"(c2), "h"((uint16_t)3), "l"(pol) : "memory");
}
__device__ __forceinline__ void tma3d(uint32_t dst, const CUtensorMap* tm, int c0, int c1, int c2, uint32_t bar) {
    asm volatile("cp.async.bulk.tensor.3d.shared::cluster.global.mbarrier::complete_tx::bytes.L2::cache_hint [%0], [%1, {%3, %4, %5}], [%2], %6;"
                 ::"r"(dst), "l"(tm), "r"(bar), "r"(c0), "r"(c1), "r"(c2), "l"(policy_stream()) : "memory");
}
__device__ __forceinline__ void tma2d_prefetch(const CUtensorMap* tm, int c0, int c1) {
    asm volatile("cp.async.bulk.prefetch.tensor.2d.L2.global [%0, {%1, %2}];" ::"l"(tm), "r"(c0), "r"(c1) : "memory");
}
__device__ __forceinline__ void tma3d_prefetch(const CUtensorMap* tm, int c0, int c1, int c2) {
    asm volatile("cp.async.bulk.prefetch.tensor.3d.L2.global [%0, {%1, %2, %3}];" ::"l"(tm), "r"(c0), "r"(c1), "r"(c2) : "memory");
}
__device__ __forceinline__ void l2_prefetch(const void* p, uint32_t bytes) {
    asm volatile("cp.async.bulk.prefetch.L2.global [%0], %1;" ::"l"(p), "r"(bytes) : "memory");
}
__device__ __forceinline__ bool elect_one() {
    uint32_t r; asm volatile("{\n.reg .pred p;\nelect.sync _|p, 0xffffffff;\nselp.u32 %0, 1, 0, p;\n}\n" : "=r"(r)); return r != 0;
}
__device__ __forceinline__ void wg_fence() { asm volatile("wgmma.fence.sync.aligned;" ::: "memory"); }
__device__ __forceinline__ void wg_commit() { asm volatile("wgmma.commit_group.sync.aligned;" ::: "memory"); }
template <int N> __device__ __forceinline__ void wg_wait() { asm volatile("wgmma.wait_group.sync.aligned %0;" ::"n"(N) : "memory"); }
__device__ __forceinline__ void bar_sync(int id, int n) { asm volatile("bar.sync %0, %1;" ::"r"(id), "r"(n) : "memory"); }
__device__ __forceinline__ void bar_arrive(int id, int n) { asm volatile("bar.arrive %0, %1;" ::"r"(id), "r"(n) : "memory"); }
__device__ __forceinline__ void token_wait(int w) {
    asm volatile("{\n.reg .pred p;\nsetp.eq.u32 p, %0, 0;\n@p bar.sync 1, 256;\n@!p bar.sync 2, 256;\n}\n" ::"r"(w) : "memory");
}
__device__ __forceinline__ void token_pass(int w) {
    asm volatile("{\n.reg .pred p;\nsetp.eq.u32 p, %0, 0;\n@p bar.arrive 2, 256;\n@!p bar.arrive 1, 256;\n}\n" ::"r"(w) : "memory");
}
template <int N> __device__ __forceinline__ void fence_regs(float (&a)[N]) {
#pragma unroll
    for (int i = 0; i < N; i++) asm volatile("" : "+f"(a[i])::"memory");
}
template <int N> __device__ __forceinline__ void undef_regs(float (&a)[N]) {
#pragma unroll
    for (int i = 0; i < N; i++) asm volatile("" : "=f"(a[i]));
}
__device__ __forceinline__ void ldsm4t(uint32_t& r0, uint32_t& r1, uint32_t& r2, uint32_t& r3, uint32_t addr) {
    asm volatile("ldmatrix.sync.aligned.m8n8.x4.trans.shared.b16 {%0,%1,%2,%3}, [%4];"
                 : "=r"(r0), "=r"(r1), "=r"(r2), "=r"(r3) : "r"(addr) : "memory");
}
__device__ __forceinline__ uint32_t pack_bf16(float lo, float hi) {
    uint32_t r; asm("cvt.rn.bf16x2.f32 %0, %1, %2;" : "=r"(r) : "f"(hi), "f"(lo)); return r;
}
__device__ __forceinline__ float bf_lo(uint32_t v) { return __uint_as_float(v << 16); }
__device__ __forceinline__ float bf_hi(uint32_t v) { return __uint_as_float(v & 0xffff0000u); }
__device__ __forceinline__ float bf_round(float v) { return __bfloat162float(__float2bfloat16_rn(v)); }
__device__ __forceinline__ float ex2(float v) { float r; asm("ex2.approx.ftz.f32 %0, %1;" : "=f"(r) : "f"(v)); return r; }
__device__ __forceinline__ void ex2v(float& v) { asm volatile("ex2.approx.ftz.f32 %0, %0;" : "+f"(v)); }
__device__ __forceinline__ float rcp_fast(float v) { float r; asm("rcp.approx.ftz.f32 %0, %1;" : "=f"(r) : "f"(v)); return r; }
__device__ __forceinline__ float sqrt_fast(float v) { float r; asm("sqrt.approx.ftz.f32 %0, %1;" : "=f"(r) : "f"(v)); return r; }
__device__ __forceinline__ void stg128(void* p, uint32_t a, uint32_t b, uint32_t c, uint32_t d) {
    asm volatile("st.global.v4.b32 [%0], {%1,%2,%3,%4};" ::"l"(p), "r"(a), "r"(b), "r"(c), "r"(d) : "memory");
}
__device__ __forceinline__ void stg128_hint(void* p, uint32_t a, uint32_t b, uint32_t c, uint32_t d, uint64_t pol) {
    asm volatile("st.global.L2::cache_hint.v4.b32 [%0], {%1,%2,%3,%4}, %5;" ::"l"(p), "r"(a), "r"(b), "r"(c), "r"(d), "l"(pol) : "memory");
}
__device__ __forceinline__ uint4 ldg128(const void* p) {
    uint4 v; asm volatile("ld.global.cg.v4.b32 {%0,%1,%2,%3}, [%4];" : "=r"(v.x), "=r"(v.y), "=r"(v.z), "=r"(v.w) : "l"(p) : "memory"); return v;
}
__device__ __forceinline__ uint64_t mkdesc(uint32_t addr, uint32_t lbo, uint32_t sbo, uint32_t swz) {
    uint32_t lo = ((addr & 0x3FFFF) >> 4) | ((lbo >> 4) << 16);
    uint32_t hi = (sbo >> 4) | (swz << 30);
    return ((uint64_t)hi << 32) | lo;
}
__device__ __forceinline__ int perm32(int v) { return (v & ~30) | ((v >> 2) & 6) | ((v << 2) & 24); }

__device__ __forceinline__ void wgmma_rs_n128_ta0_tb0(float (&d)[64], uint32_t a0, uint32_t a1, uint32_t a2, uint32_t a3, uint64_t descB, int scaleD) {
  asm volatile("{\n.reg .pred p;\nsetp.ne.b32 p, %69, 0;\n"
    "wgmma.mma_async.sync.aligned.m64n128k16.f32.bf16.bf16 "
    "{%0, %1, %2, %3, %4, %5, %6, %7, %8, %9, %10, %11, %12, %13, %14, %15, %16, %17, %18, %19, %20, %21, %22, %23, %24, %25, %26, %27, %28, %29, %30, %31, %32, %33, %34, %35, %36, %37, %38, %39, %40, %41, %42, %43, %44, %45, %46, %47, %48, %49, %50, %51, %52, %53, %54, %55, %56, %57, %58, %59, %60, %61, %62, %63}, "
    "{%64, %65, %66, %67}, %68, p, 1, 1, 0;\n}\n"
    : "+f"(d[0]), "+f"(d[1]), "+f"(d[2]), "+f"(d[3]), "+f"(d[4]), "+f"(d[5]), "+f"(d[6]), "+f"(d[7]), "+f"(d[8]), "+f"(d[9]), "+f"(d[10]), "+f"(d[11]), "+f"(d[12]), "+f"(d[13]), "+f"(d[14]), "+f"(d[15]), "+f"(d[16]), "+f"(d[17]), "+f"(d[18]), "+f"(d[19]), "+f"(d[20]), "+f"(d[21]), "+f"(d[22]), "+f"(d[23]), "+f"(d[24]), "+f"(d[25]), "+f"(d[26]), "+f"(d[27]), "+f"(d[28]), "+f"(d[29]), "+f"(d[30]), "+f"(d[31]), "+f"(d[32]), "+f"(d[33]), "+f"(d[34]), "+f"(d[35]), "+f"(d[36]), "+f"(d[37]), "+f"(d[38]), "+f"(d[39]), "+f"(d[40]), "+f"(d[41]), "+f"(d[42]), "+f"(d[43]), "+f"(d[44]), "+f"(d[45]), "+f"(d[46]), "+f"(d[47]), "+f"(d[48]), "+f"(d[49]), "+f"(d[50]), "+f"(d[51]), "+f"(d[52]), "+f"(d[53]), "+f"(d[54]), "+f"(d[55]), "+f"(d[56]), "+f"(d[57]), "+f"(d[58]), "+f"(d[59]), "+f"(d[60]), "+f"(d[61]), "+f"(d[62]), "+f"(d[63])
    : "r"(a0), "r"(a1), "r"(a2), "r"(a3), "l"(descB), "r"(scaleD));
}
__device__ __forceinline__ void wgmma_rs_n128_ta0_tb1(float (&d)[64], uint32_t a0, uint32_t a1, uint32_t a2, uint32_t a3, uint64_t descB, int scaleD) {
  asm volatile("{\n.reg .pred p;\nsetp.ne.b32 p, %69, 0;\n"
    "wgmma.mma_async.sync.aligned.m64n128k16.f32.bf16.bf16 "
    "{%0, %1, %2, %3, %4, %5, %6, %7, %8, %9, %10, %11, %12, %13, %14, %15, %16, %17, %18, %19, %20, %21, %22, %23, %24, %25, %26, %27, %28, %29, %30, %31, %32, %33, %34, %35, %36, %37, %38, %39, %40, %41, %42, %43, %44, %45, %46, %47, %48, %49, %50, %51, %52, %53, %54, %55, %56, %57, %58, %59, %60, %61, %62, %63}, "
    "{%64, %65, %66, %67}, %68, p, 1, 1, 1;\n}\n"
    : "+f"(d[0]), "+f"(d[1]), "+f"(d[2]), "+f"(d[3]), "+f"(d[4]), "+f"(d[5]), "+f"(d[6]), "+f"(d[7]), "+f"(d[8]), "+f"(d[9]), "+f"(d[10]), "+f"(d[11]), "+f"(d[12]), "+f"(d[13]), "+f"(d[14]), "+f"(d[15]), "+f"(d[16]), "+f"(d[17]), "+f"(d[18]), "+f"(d[19]), "+f"(d[20]), "+f"(d[21]), "+f"(d[22]), "+f"(d[23]), "+f"(d[24]), "+f"(d[25]), "+f"(d[26]), "+f"(d[27]), "+f"(d[28]), "+f"(d[29]), "+f"(d[30]), "+f"(d[31]), "+f"(d[32]), "+f"(d[33]), "+f"(d[34]), "+f"(d[35]), "+f"(d[36]), "+f"(d[37]), "+f"(d[38]), "+f"(d[39]), "+f"(d[40]), "+f"(d[41]), "+f"(d[42]), "+f"(d[43]), "+f"(d[44]), "+f"(d[45]), "+f"(d[46]), "+f"(d[47]), "+f"(d[48]), "+f"(d[49]), "+f"(d[50]), "+f"(d[51]), "+f"(d[52]), "+f"(d[53]), "+f"(d[54]), "+f"(d[55]), "+f"(d[56]), "+f"(d[57]), "+f"(d[58]), "+f"(d[59]), "+f"(d[60]), "+f"(d[61]), "+f"(d[62]), "+f"(d[63])
    : "r"(a0), "r"(a1), "r"(a2), "r"(a3), "l"(descB), "r"(scaleD));
}
__device__ __forceinline__ void wgmma_rs_n64_ta0_tb1(float (&d)[32], uint32_t a0, uint32_t a1, uint32_t a2, uint32_t a3, uint64_t descB, int scaleD) {
  asm volatile("{\n.reg .pred p;\nsetp.ne.b32 p, %37, 0;\n"
    "wgmma.mma_async.sync.aligned.m64n64k16.f32.bf16.bf16 "
    "{%0, %1, %2, %3, %4, %5, %6, %7, %8, %9, %10, %11, %12, %13, %14, %15, %16, %17, %18, %19, %20, %21, %22, %23, %24, %25, %26, %27, %28, %29, %30, %31}, "
    "{%32, %33, %34, %35}, %36, p, 1, 1, 1;\n}\n"
    : "+f"(d[0]), "+f"(d[1]), "+f"(d[2]), "+f"(d[3]), "+f"(d[4]), "+f"(d[5]), "+f"(d[6]), "+f"(d[7]), "+f"(d[8]), "+f"(d[9]), "+f"(d[10]), "+f"(d[11]), "+f"(d[12]), "+f"(d[13]), "+f"(d[14]), "+f"(d[15]), "+f"(d[16]), "+f"(d[17]), "+f"(d[18]), "+f"(d[19]), "+f"(d[20]), "+f"(d[21]), "+f"(d[22]), "+f"(d[23]), "+f"(d[24]), "+f"(d[25]), "+f"(d[26]), "+f"(d[27]), "+f"(d[28]), "+f"(d[29]), "+f"(d[30]), "+f"(d[31])
    : "r"(a0), "r"(a1), "r"(a2), "r"(a3), "l"(descB), "r"(scaleD));
}
__device__ __forceinline__ void wgmma_ss_n128_ta1_tb0(float (&d)[64], uint64_t descA, uint64_t descB, int scaleD) {
  asm volatile("{\n.reg .pred p;\nsetp.ne.b32 p, %66, 0;\n"
    "wgmma.mma_async.sync.aligned.m64n128k16.f32.bf16.bf16 "
    "{%0, %1, %2, %3, %4, %5, %6, %7, %8, %9, %10, %11, %12, %13, %14, %15, %16, %17, %18, %19, %20, %21, %22, %23, %24, %25, %26, %27, %28, %29, %30, %31, %32, %33, %34, %35, %36, %37, %38, %39, %40, %41, %42, %43, %44, %45, %46, %47, %48, %49, %50, %51, %52, %53, %54, %55, %56, %57, %58, %59, %60, %61, %62, %63}, "
    "%64, %65, p, 1, 1, 1, 0;\n}\n"
    : "+f"(d[0]), "+f"(d[1]), "+f"(d[2]), "+f"(d[3]), "+f"(d[4]), "+f"(d[5]), "+f"(d[6]), "+f"(d[7]), "+f"(d[8]), "+f"(d[9]), "+f"(d[10]), "+f"(d[11]), "+f"(d[12]), "+f"(d[13]), "+f"(d[14]), "+f"(d[15]), "+f"(d[16]), "+f"(d[17]), "+f"(d[18]), "+f"(d[19]), "+f"(d[20]), "+f"(d[21]), "+f"(d[22]), "+f"(d[23]), "+f"(d[24]), "+f"(d[25]), "+f"(d[26]), "+f"(d[27]), "+f"(d[28]), "+f"(d[29]), "+f"(d[30]), "+f"(d[31]), "+f"(d[32]), "+f"(d[33]), "+f"(d[34]), "+f"(d[35]), "+f"(d[36]), "+f"(d[37]), "+f"(d[38]), "+f"(d[39]), "+f"(d[40]), "+f"(d[41]), "+f"(d[42]), "+f"(d[43]), "+f"(d[44]), "+f"(d[45]), "+f"(d[46]), "+f"(d[47]), "+f"(d[48]), "+f"(d[49]), "+f"(d[50]), "+f"(d[51]), "+f"(d[52]), "+f"(d[53]), "+f"(d[54]), "+f"(d[55]), "+f"(d[56]), "+f"(d[57]), "+f"(d[58]), "+f"(d[59]), "+f"(d[60]), "+f"(d[61]), "+f"(d[62]), "+f"(d[63])
    : "l"(descA), "l"(descB), "r"(scaleD));
}
__device__ __forceinline__ void wgmma_ss_n160_ta0_tb1(float (&d)[80], uint64_t descA, uint64_t descB, int scaleD) {
  asm volatile("{\n.reg .pred p;\nsetp.ne.b32 p, %82, 0;\n"
    "wgmma.mma_async.sync.aligned.m64n160k16.f32.bf16.bf16 "
    "{%0, %1, %2, %3, %4, %5, %6, %7, %8, %9, %10, %11, %12, %13, %14, %15, %16, %17, %18, %19, %20, %21, %22, %23, %24, %25, %26, %27, %28, %29, %30, %31, %32, %33, %34, %35, %36, %37, %38, %39, %40, %41, %42, %43, %44, %45, %46, %47, %48, %49, %50, %51, %52, %53, %54, %55, %56, %57, %58, %59, %60, %61, %62, %63, %64, %65, %66, %67, %68, %69, %70, %71, %72, %73, %74, %75, %76, %77, %78, %79}, "
    "%80, %81, p, 1, 1, 0, 1;\n}\n"
    : "+f"(d[0]), "+f"(d[1]), "+f"(d[2]), "+f"(d[3]), "+f"(d[4]), "+f"(d[5]), "+f"(d[6]), "+f"(d[7]), "+f"(d[8]), "+f"(d[9]), "+f"(d[10]), "+f"(d[11]), "+f"(d[12]), "+f"(d[13]), "+f"(d[14]), "+f"(d[15]), "+f"(d[16]), "+f"(d[17]), "+f"(d[18]), "+f"(d[19]), "+f"(d[20]), "+f"(d[21]), "+f"(d[22]), "+f"(d[23]), "+f"(d[24]), "+f"(d[25]), "+f"(d[26]), "+f"(d[27]), "+f"(d[28]), "+f"(d[29]), "+f"(d[30]), "+f"(d[31]), "+f"(d[32]), "+f"(d[33]), "+f"(d[34]), "+f"(d[35]), "+f"(d[36]), "+f"(d[37]), "+f"(d[38]), "+f"(d[39]), "+f"(d[40]), "+f"(d[41]), "+f"(d[42]), "+f"(d[43]), "+f"(d[44]), "+f"(d[45]), "+f"(d[46]), "+f"(d[47]), "+f"(d[48]), "+f"(d[49]), "+f"(d[50]), "+f"(d[51]), "+f"(d[52]), "+f"(d[53]), "+f"(d[54]), "+f"(d[55]), "+f"(d[56]), "+f"(d[57]), "+f"(d[58]), "+f"(d[59]), "+f"(d[60]), "+f"(d[61]), "+f"(d[62]), "+f"(d[63]), "+f"(d[64]), "+f"(d[65]), "+f"(d[66]), "+f"(d[67]), "+f"(d[68]), "+f"(d[69]), "+f"(d[70]), "+f"(d[71]), "+f"(d[72]), "+f"(d[73]), "+f"(d[74]), "+f"(d[75]), "+f"(d[76]), "+f"(d[77]), "+f"(d[78]), "+f"(d[79])
    : "l"(descA), "l"(descB), "r"(scaleD));
}

#define PROF_DECL(b)
#define PROF_EV(tag)
#define PROF_GT(tag)

template <int N> struct IC { static constexpr int value = N; };
struct Cur {
    uint32_t slot, ph;
    __device__ __forceinline__ void adv() { if (++slot == NSLOT) { slot = 0; ph ^= 1; } }
};
constexpr int E0 = 6, E_ATT0 = 48, E_ATT1 = 108;
__host__ __device__ constexpr uint32_t slot_of(int e) { return (e + E0) % NSLOT; }
__device__ __forceinline__ Cur cur_at(int e) { Cur c; c.slot = (e + E0) % NSLOT; c.ph = ((e + E0) / NSLOT) & 1; return c; }

__device__ __forceinline__ int q_tile(int k, int t) { return (t < 2 ? 14 - 2 * k : 2 * k) + (t & 1); }
__device__ __forceinline__ int op_head(int i, int kap) { return 16 * kap + 2 * (i & 7) + (i >> 3); }

constexpr float SM_SCALE = 0.08838834764831845f * 1.4426950408889634f;

struct Ctx {
    uint32_t ring, misc;
    uint32_t rel;
    int w, warp, lane;
};
__device__ __forceinline__ void release(const Ctx& c, uint32_t off, uint32_t cnt) {
    if (c.lane < 2) mbar_arrive_cluster(c.rel + off, cnt);
}
__device__ __forceinline__ void signal_event(const Ctx& c, int ev) {
    __syncwarp();
    if (c.lane == 0) mbar_arrive(c.misc + BAR_EV + (c.w * 16 + ev) * 8);
}
template <int NK, int OFF, int N>
__device__ __forceinline__ uint32_t load_afrag(uint32_t (&a)[N], uint32_t base, const Ctx& c) {
    int r = c.lane & 7, mat = c.lane >> 3;
    uint32_t addr = base + (8 * (mat >> 1) + r) * 128 + (((2 * c.warp + (mat & 1)) ^ r) << 4);
#pragma unroll
    for (int k = 0; k < NK; k++) ldsm4t(a[OFF + 4 * k], a[OFF + 4 * k + 1], a[OFF + 4 * k + 2], a[OFF + 4 * k + 3], addr + k * 2048);
    uint32_t dep = 0;
#pragma unroll
    for (int k = 0; k < NK; k++) dep |= a[OFF + 4 * k];
    return dep & blockIdx.y;
}
__device__ __forceinline__ void store_proj(const float (&acc)[64], unsigned char* dst  , const Ctx& c, uint64_t pol) {
    int g = c.lane >> 2, t = c.lane & 3;
#pragma unroll
    for (int i = 0; i < 2; i++) {
        int row = perm32(64 * c.w + 16 * c.warp + 8 * i + g);
        unsigned char* p = dst + row * 128;
#pragma unroll
        for (int q = 0; q < 4; q++) {
            int chunk = (4 * (q & 1) + t) ^ (row & 7);
            stg128_hint(p + (q >> 1) * 16384 + chunk * 16,
                   pack_bf16(acc[16 * q + 2 * i], acc[16 * q + 2 * i + 1]), pack_bf16(acc[16 * q + 4 + 2 * i], acc[16 * q + 4 + 2 * i + 1]),
                   pack_bf16(acc[16 * q + 8 + 2 * i], acc[16 * q + 8 + 2 * i + 1]), pack_bf16(acc[16 * q + 12 + 2 * i], acc[16 * q + 12 + 2 * i + 1]), pol);
        }
    }
}

constexpr float SAFE_SUM = 1099511627776.0f;
template <int NJ>
__device__ __forceinline__ void row_max(const float (&s)[4 * NJ], float (&mx)[2]) {
#pragma unroll
    for (int i = 0; i < 2; i++) {
        float a = fmaxf(s[2 * i], s[2 * i + 1]), b = fmaxf(s[4 + 2 * i], s[4 + 2 * i + 1]);
#pragma unroll
        for (int j = 2; j < NJ; j += 2) {
            a = fmaxf(a, fmaxf(s[4 * j + 2 * i], s[4 * j + 2 * i + 1]));
            b = fmaxf(b, fmaxf(s[4 * j + 4 + 2 * i], s[4 * j + 4 + 2 * i + 1]));
        }
        a = fmaxf(a, b);
        a = fmaxf(a, __shfl_xor_sync(0xffffffffu, a, 1));
        mx[i] = fmaxf(a, __shfl_xor_sync(0xffffffffu, a, 2));
    }
}
template <int NJ, bool SHIFT>
__device__ __forceinline__ void exp_sum(float (&s)[4 * NJ], const float (&m)[2], float& l0, float& l1) {
#pragma unroll
    for (int j = 0; j < NJ; j++) {
#pragma unroll
        for (int e = 0; e < 4; e++) s[4 * j + e] = ex2(SHIFT ? s[4 * j + e] - m[e >> 1] : s[4 * j + e]);
        l0 += s[4 * j + 0] + s[4 * j + 1]; l1 += s[4 * j + 2] + s[4 * j + 3];
    }
}
__device__ __forceinline__ void recompute_scores(float (&s)[64], const unsigned char* qh, uint32_t kaddr, const Ctx& c) {
    const int r = c.lane & 7, mat = c.lane >> 3, g = c.lane >> 2, t = c.lane & 3;
    const uint32_t a0 = kaddr + (8 * (mat & 1) + r) * 128 + (((mat >> 1) ^ r) << 4);
    uint32_t q[32];
#pragma unroll
    for (int i = 0; i < 32; i++) {
        const uint32_t v = __ldcg(reinterpret_cast<const uint32_t*>(qh + (8 * (i >> 1) + g) * 128 + (((2 * c.warp + (i & 1)) ^ g) << 4) + 4 * t));
        asm volatile("movmatrix.sync.aligned.m8n8.trans.b16 %0, %1;" : "=r"(q[i]) : "r"(v));
    }
#pragma unroll
    for (int i = 0; i < 64; i++) s[i] = 0.f;
#pragma unroll
    for (int jp = 0; jp < 8; jp++) {
#pragma unroll
        for (int k = 0; k < 8; k++) {
            asm volatile(
                "{\n.reg .b32 b0, b1, b2, b3;\n"
                "ldmatrix.sync.aligned.m8n8.x4.trans.shared.b16 {b0,b1,b2,b3}, [%12];\n"
                "mma.sync.aligned.m16n8k16.row.col.f32.bf16.bf16.f32 {%0,%1,%2,%3}, {%8,%9,%10,%11}, {b0,b1}, {%0,%1,%2,%3};\n"
                "mma.sync.aligned.m16n8k16.row.col.f32.bf16.bf16.f32 {%4,%5,%6,%7}, {%8,%9,%10,%11}, {b2,b3}, {%4,%5,%6,%7};\n}\n"
                : "+f"(s[8 * jp]), "+f"(s[8 * jp + 1]), "+f"(s[8 * jp + 2]), "+f"(s[8 * jp + 3]),
                  "+f"(s[8 * jp + 4]), "+f"(s[8 * jp + 5]), "+f"(s[8 * jp + 6]), "+f"(s[8 * jp + 7])
                : "r"(q[4 * k]), "r"(q[4 * k + 1]), "r"(q[4 * k + 2]), "r"(q[4 * k + 3]),
                  "r"((a0 ^ ((jp & 3) << 5)) + (jp >> 2) * 16384 + k * 2048) : "memory");
        }
    }
}
__device__ __forceinline__ int mask_lim(const Ctx& c) { return perm32(16 * c.warp + (c.lane >> 2)) - 8 * (c.lane & 3); }
template <int J0>
__device__ __forceinline__ void mask_diag(float (&s)[4 * J0 + 32], const Ctx& c) {
    const int lim = mask_lim(c);
    if (c.warp < 2) {
#pragma unroll
        for (int x = 0; x < 16; x++) {
            if (2 * (x >> 2) + (x & 1) - (x & 2) > lim) s[4 * J0 + x] = -INFINITY;
            s[4 * J0 + 16 + x] = -INFINITY;
        }
    } else {
#pragma unroll
        for (int x = 0; x < 16; x++)
            if (32 + 2 * (x >> 2) + (x & 1) - (x & 2) > lim) s[4 * J0 + 16 + x] = -INFINITY;
    }
}
__device__ __forceinline__ void mask_any(float (&s)[64], int hh, const Ctx& c) {
    const int lim = mask_lim(c) + 64 * hh;
#pragma unroll
    for (int x = 0; x < 64; x++)
        if (32 * (x >> 4) + 2 * ((x >> 2) & 3) + (x & 1) - (x & 2) > lim) s[x] = -INFINITY;
}
__device__ __forceinline__ void issue_pv(float (&o)[64], const uint32_t (&p)[32], uint32_t vaddr, int acc, int mode  ) {
    uint64_t d = mkdesc(vaddr, 16, 1024, 1);
    if (mode == 0) {
        wg_fence();
#pragma unroll
        for (int k = 0; k < 8; k++)
            wgmma_rs_n128_ta0_tb0(o, p[4 * k], p[4 * k + 1], p[4 * k + 2], p[4 * k + 3], d + (k >> 2) * 1024 + 2 * (k & 3), k ? 1 : acc);
        wg_commit();
    } else if (mode == 1) {
        wg_fence();
#pragma unroll
        for (int k = 0; k < 4; k++) wgmma_rs_n128_ta0_tb0(o, p[4 * k], p[4 * k + 1], p[4 * k + 2], p[4 * k + 3], d + 2 * k, k != 0);
        wg_commit();
    } else {
        wg_fence();
        wgmma_rs_n128_ta0_tb0(o, p[0], p[1], p[2], p[3], d, 0);
        wg_commit();
    }
}
__device__ __forceinline__ void issue_qk(float (&s)[64], const uint32_t (&q)[32], uint32_t kaddr) {
    uint64_t d = mkdesc(kaddr, 16384, 1024, 1);
    wg_fence();
#pragma unroll
    for (int k = 0; k < 8; k++) wgmma_rs_n128_ta0_tb1(s, q[4 * k], q[4 * k + 1], q[4 * k + 2], q[4 * k + 3], d + 128 * k, k != 0);
    wg_commit();
}
__device__ __forceinline__ void issue_qk_half(float (&s32)[32], const uint32_t (&q)[32], uint32_t kaddr) {
    uint64_t d = mkdesc(kaddr, 16384, 1024, 1);
    wg_fence();
#pragma unroll
    for (int k = 0; k < 8; k++) wgmma_rs_n64_ta0_tb1(s32, q[4 * k], q[4 * k + 1], q[4 * k + 2], q[4 * k + 3], d + 128 * k, k != 0);
    wg_commit();
}
template <int Q0, int Q1>
__device__ __forceinline__ void stage_ctx(float (&o)[64], const float (&inv)[2], Cur ce, const Ctx& c) {
    const int g = c.lane >> 2, t = c.lane & 3, r7 = ((g & 1) << 2) | (g >> 1);
    const uint32_t base = c.ring + ce.slot * SLOT_BYTES + c.w * 16384 + (16 * c.warp + r7) * 128 + ((t ^ r7) << 4);
    if (Q0 == 0) mbar_wait_hot(c.misc + BAR_FULL + 8 * ce.slot, ce.ph);
#pragma unroll
    for (int q = Q0; q < Q1; q++) {
        uint32_t v[8];
#pragma unroll
        for (int i = 0; i < 2; i++)
#pragma unroll
            for (int j = 0; j < 4; j++) v[4 * i + j] = pack_bf16(o[16 * q + 4 * j + 2 * i] * inv[i], o[16 * q + 4 * j + 2 * i + 1] * inv[i]);
#pragma unroll
        for (int i = 0; i < 8; i++) { o[16 * q + i] = __uint_as_float(v[i]); asm volatile("" : "=f"(o[16 * q + 8 + i])); }
#pragma unroll
        for (int i = 0; i < 2; i++)
            asm volatile("st.shared.v4.b32 [%0], {%1,%2,%3,%4};" ::"r"((base ^ ((q & 1) << 6)) + (q >> 1) * 8192 + i * 1024),
                         "r"(v[4 * i]), "r"(v[4 * i + 1]), "r"(v[4 * i + 2]), "r"(v[4 * i + 3]) : "memory");
    }
}
__device__ __forceinline__ void publish_ctx(int ev, const Ctx& c) {
    asm volatile("fence.proxy.async.shared::cta;" ::: "memory");
    signal_event(c, ev);
}

__device__ __forceinline__ const unsigned char* xn_addr(int row, int col) {
    return g_xn + ((row >> 7) * 10 + (col >> 6)) * 16384 + (row & 127) * 128 + ((((col & 63) >> 3) ^ (row & 7)) << 4);
}
__device__ __forceinline__ void mma16816(float (&d)[4], uint32_t a0, uint32_t a1, uint32_t a2, uint32_t a3, uint32_t b0, uint32_t b1) {
    asm volatile("mma.sync.aligned.m16n8k16.row.col.f32.bf16.bf16.f32 {%0,%1,%2,%3}, {%4,%5,%6,%7}, {%8,%9}, {%0,%1,%2,%3};"
                 : "+f"(d[0]), "+f"(d[1]), "+f"(d[2]), "+f"(d[3]) : "r"(a0), "r"(a1), "r"(a2), "r"(a3), "r"(b0), "r"(b1));
}
__device__ __forceinline__ uint32_t lds32(uint32_t addr) { uint32_t v; asm volatile("ld.shared.u32 %0, [%1];" : "=r"(v) : "r"(addr)); return v; }

__device__ __forceinline__ void ln_rows(const Params& P, int row0, int lane, uint32_t wr_s) {
    const int hl = lane & 15, row = row0 + (lane >> 4);
    uint32_t v[20];
#pragma unroll
    for (int i = 0; i < 5; i++) {
        uint4 u;
        asm("ld.global.nc.L2::cache_hint.v4.b32 {%0,%1,%2,%3}, [%4], %5;" : "=r"(u.x), "=r"(u.y), "=r"(u.z), "=r"(u.w)
            : "l"(P.x + (size_t)row * DM + 128 * i + 8 * hl), "l"(policy(HM & 512)));
        v[4 * i] = u.x; v[4 * i + 1] = u.y; v[4 * i + 2] = u.z; v[4 * i + 3] = u.w;
    }
    float mean = 0.f, m2 = 0.f, acc2 = 0.f;
#pragma unroll
    for (int i = 0; i < 20; i++) { mean += bf_lo(v[i]); acc2 += bf_hi(v[i]); }
    mean = (mean + acc2) * (1.0f / 40);
    acc2 = 0.f;
#pragma unroll
    for (int i = 0; i < 20; i++) {
        float d0 = __uint_as_float(__byte_perm(v[i], 0, 0x1044)) - mean, d1 = __uint_as_float(__byte_perm(v[i], 0, 0x3244)) - mean;
        m2 = fmaf(d0, d0, m2); acc2 = fmaf(d1, d1, acc2);
    }
    m2 += acc2;
    acc2 = 0.f;
#pragma unroll
    for (int o = 1; o < 16; o <<= 1) {
        float mo = __shfl_xor_sync(0xffffffffu, mean, o), qo = __shfl_xor_sync(0xffffffffu, m2, o), d = mo - mean;
        m2 = fmaf(d * d, 20.0f * o, m2 + qo);
        mean = 0.5f * (mean + mo);
    }
    const uint32_t mb2 = pack_bf16(mean, mean);
    const float inv = rcp_fast(bf_round(sqrt_fast(bf_round(bf_round(m2 * (1.0f / DM)) + 1e-5f))));
    float dot = 0.f;
    unsigned char* xp = g_xn + ((row >> 7) * 10 + (hl >> 3)) * 16384 + (row & 127) * 128 + (((hl & 7) ^ (row & 7)) << 4);
#pragma unroll
    for (int i = 0; i < 5; i++) {
        uint32_t ww[4];
        asm volatile("ld.shared.v4.b32 {%0,%1,%2,%3}, [%4];" : "=r"(ww[0]), "=r"(ww[1]), "=r"(ww[2]), "=r"(ww[3]) : "r"(wr_s + 256 * i + 16 * hl) : "memory");
#pragma unroll
        for (int e = 0; e < 4; e++) {
            uint32_t d;
            asm("sub.rn.bf16x2 %0, %1, %2;" : "=r"(d) : "r"(v[4 * i + e]), "r"(mb2));
            d = pack_bf16(bf_lo(d) * inv, bf_hi(d) * inv);
            v[4 * i + e] = d;
            dot = fmaf(bf_lo(d), bf_lo(ww[e]), dot);
            acc2 = fmaf(bf_hi(d), bf_hi(ww[e]), acc2);
        }
        stg128(xp + i * 32768, v[4 * i], v[4 * i + 1], v[4 * i + 2], v[4 * i + 3]);
    }
    dot += acc2;
#pragma unroll
    for (int o = 8; o > 0; o >>= 1) dot += __shfl_xor_sync(0xffffffffu, dot, o);
    if (hl == 0) { g_router[row] = bf_round(dot); g_stats[row] = make_uint2(mb2, __float_as_uint(inv)); }
}

__device__ __forceinline__ void aux_cta(const Params& P, const CUtensorMap* tmG, const CUtensorMap* tmU, const CUtensorMap* tmD, unsigned char* sm, int a) {
    constexpr int STG = 57344, XS = 3 * STG, HS = XS + 8 * 1296, KEY = HS + 8 * 912, MI = KEY + 8192;
    const int tid = threadIdx.x, warp = __shfl_sync(0xffffffffu, tid >> 5, 0), lane = tid & 31;
    const uint32_t sb = smem_u32(sm);
    const uint32_t full = sb + MI, empty = sb + MI + 32;
    int* s_sel = reinterpret_cast<int*>(sm + MI + 64);
    float* s_r = reinterpret_cast<float*>(sm + MI + 96);
    volatile unsigned* s_misc = reinterpret_cast<volatile unsigned*>(sm + MI + 128);
    uint32_t* s_key = reinterpret_cast<uint32_t*>(sm + KEY);
    PROF_DECL(128 + a)
    PROF_GT(0);
    if (tid == 0) {
        for (int i = 0; i < 3; i++) { mbar_init(full + 8 * i, 1); mbar_init(empty + 8 * i, 10); }
        asm volatile("fence.mbarrier_init.release.cluster;" ::: "memory");
    }
    __syncthreads();
    if (warp == 11) {
        if (elect_one()) {
            int st = 0; uint32_t ph = 0;
#pragma unroll 1
            for (int s = 0; s < 34; s++) {
                mbar_wait(empty + 8 * st, ph ^ 1);
                const uint32_t dst = sb + st * STG, fb = full + 8 * st;
                if (s < 20) {
                    mbar_expect_tx(fb, 57344);
                    tma3d(dst, tmG, 0, 32 * s, 7 * a, fb);
                    tma3d(dst + 28672, tmU, 0, 32 * s, 7 * a, fb);
                } else {
                    mbar_expect_tx(fb, 40960);
                    tma3d(dst, tmD, 0, 448 * a + 32 * (s - 20), 0, fb);
                }
                if (s >= 3) {
#pragma unroll 1
                    for (int f = (s == 3 ? 4 : s + 6); f <= s + 6 && f < 34; f++) {
                        if (f < 20) { tma3d_prefetch(tmG, 0, 32 * f, 7 * a); tma3d_prefetch(tmU, 0, 32 * f, 7 * a); }
                        else tma3d_prefetch(tmD, 0, 448 * a + 32 * (f - 20), 0);
                    }
                }
                if (++st == 3) { st = 0; ph ^= 1; }
            }
        }
        return;
    }
    if (tid < 80) *reinterpret_cast<uint4*>(sm + KEY + 1024 + tid * 16) = __ldg(reinterpret_cast<const uint4*>(P.wr) + tid);
    __nanosleep(AUXDELAY);
#pragma unroll 1
    for (int i = tid; i < 128 * 40; i += 352) asm volatile("prefetch.global.L2 [%0];" ::"l"(P.x + (size_t)(2 * a) * 128 * DM + i * 16));
    bar_sync(2, 352);
#pragma unroll 1
    for (int i = warp; i < 64; i += 11) ln_rows(P, 2 * a * 128 + 2 * i, lane, sb + KEY + 1024);
    bar_sync(2, 352);
    if (tid == 320) asm volatile("red.release.gpu.global.add.u32 [%0], 32;" ::"l"(flag_ptr(FL_LN + 2 * a)) : "memory");
    PROF_GT(49);
    if (warp == 10) return;
    if (tid < 16) {
        unsigned e = *reinterpret_cast<volatile unsigned*>(&g_epoch);
        if (tid == 0) s_misc[0] = e;
        flag_wait(flag_ptr(FL_LN + tid), (e + 1) * 32u);
    }
    bar_sync(1, 320);
    PROF_GT(50);
    const unsigned ep = s_misc[0];
    auto top8 = [&](uint32_t (&key)[8]) {
        uint32_t mine = 0;
#pragma unroll 1
        for (int r = 0; r < TOPC; r++) {
            uint32_t best = 0;
#pragma unroll
            for (int i = 0; i < 8; i++) best = max(best, key[i]);
            best = __reduce_max_sync(0xffffffffu, best);
#pragma unroll
            for (int i = 0; i < 8; i++) if (key[i] == best) key[i] = 0;
            if (lane == r) mine = best;
        }
        return mine;
    };
#pragma unroll 1
    for (int pass = 0; pass < 2; pass++) {
        if (warp < (pass ? 1 : 8)) {
            uint32_t key[8];
#pragma unroll
            for (int i = 0; i < 8; i++) {
                if (pass == 0) {
                    int idx = warp * 256 + i * 32 + lane;
                    uint32_t b = __float_as_uint(__ldcg(g_router + idx)) >> 16;
                    b = (b & 0x8000u) ? (~b & 0xffffu) : (b | 0x8000u);
                    key[i] = (b << 16) | (uint32_t)(0xffff - idx);
                } else key[i] = i < 2 ? s_key[i * 32 + lane] : 0u;
            }
            uint32_t best = top8(key);
            if (lane < TOPC) {
                if (pass == 0) s_key[warp * 8 + lane] = best;
                else {
                    uint32_t b = best >> 16;
                    b = (b & 0x8000u) ? (b & 0x7fffu) : (~b & 0xffffu);
                    s_sel[lane] = 0xffff - (int)(best & 0xffffu);
                    s_r[lane] = __uint_as_float(b << 16);
                }
            }
        }
        bar_sync(1, 320);
    }
#pragma unroll
    for (int it = 0; it < 2; it++) {
        int i = tid + it * 320, tk = i / 80, ch = i % 80;
        *reinterpret_cast<uint4*>(sm + XS + tk * 1296 + ch * 16) = __ldcg(reinterpret_cast<const uint4*>(xn_addr(s_sel[tk], ch * 8)));
    }
    bar_sync(1, 320);
    PROF_GT(51);
    const int g = lane >> 2, t = lane & 3;
    const uint32_t woff = warp * 4096 + (8 * (lane >> 4) + (lane & 7)) * 128 + ((((lane >> 3) & 1) ^ (lane & 7)) << 4);
    int st = 0; uint32_t ph = 0;
    float ga[4][4], ua[4][4];
#pragma unroll
    for (int i = 0; i < 4; i++)
#pragma unroll
        for (int e = 0; e < 4; e++) { ga[i][e] = 0.f; ua[i][e] = 0.f; }
#pragma unroll 1
    for (int s = 0; s < 34; s++) {
        if (s == 20) {
            if (warp < 7) {
#pragma unroll
                for (int i = 0; i < 4; i++)
#pragma unroll
                    for (int e = 0; e < 4; e++) {
                        float gv = bf_round(ga[i][e]), uv = bf_round(ua[i][e]);
                        float sg = bf_round(__fdividef(gv, 1.0f + __expf(fminf(-gv, 80.f))));
                        int f = warp * 64 + i * 16 + g + 8 * (e >> 1), tk = 2 * t + (e & 1);
                        *reinterpret_cast<__nv_bfloat16*>(sm + HS + tk * 912 + f * 2) = __float2bfloat16_rn(sg * uv);
                        ga[i][e] = 0.f;
                    }
            }
            bar_sync(1, 320);
            PROF_GT(52);
        }
        mbar_wait(full + 8 * st, ph);
        if (s >= 20 || warp < 7) {
#pragma unroll
            for (int kk = 0; kk < 2; kk++) {
                uint32_t xb = sb + (s < 20 ? XS + g * 1296 + s * 64 : HS + g * 912 + (s - 20) * 64) + 32 * kk + 4 * t;
                uint32_t b0 = lds32(xb), b1 = lds32(xb + 16);
                uint32_t wa = sb + st * STG + woff + kk * 2048;
#pragma unroll
                for (int i = 0; i < 4; i++) {
                    uint32_t a0, a1, a2, a3;
                    ldsm4t(a0, a1, a2, a3, wa ^ (i << 5));
                    mma16816(ga[i], a0, a1, a2, a3, b0, b1);
                    if (s < 20) {
                        ldsm4t(a0, a1, a2, a3, (wa ^ (i << 5)) + 28672);
                        mma16816(ua[i], a0, a1, a2, a3, b0, b1);
                    }
                }
            }
        }
        asm volatile("fence.proxy.async.shared::cta;" ::: "memory");
        __syncwarp();
        if (lane == 0) mbar_arrive(empty + 8 * st);
        if (++st == 3) { st = 0; ph ^= 1; }
    }
#pragma unroll
    for (int i = 0; i < 4; i++)
#pragma unroll
        for (int e = 0; e < 4; e += 2)
            *reinterpret_cast<float2*>(g_moe_part + (a * DM + warp * 64 + i * 16 + g + 4 * e) * 8 + 2 * t) = make_float2(ga[i][e], ga[i][e + 1]);
    bar_sync(1, 320);
    if (tid == 0) {
        __threadfence();
        unsigned old = atomicAdd(flag_ptr(FL_MOE_CNT), 1u);
        s_misc[1] = (old == ep * 4u + 3u);
        __threadfence();
    }
    bar_sync(1, 320);
    PROF_GT(53);
    if (s_misc[1]) {
        const float4* pp = reinterpret_cast<const float4*>(g_moe_part);
#pragma unroll 2
        for (int i = tid; i < DM * 2; i += 320) {
            float4 v0 = __ldcg(pp + i), v1 = __ldcg(pp + DM * 2 + i), v2 = __ldcg(pp + DM * 4 + i), v3 = __ldcg(pp + DM * 6 + i);
            float y[4] = {v0.x + v1.x + v2.x + v3.x, v0.y + v1.y + v2.y + v3.y, v0.z + v1.z + v2.z + v3.z, v0.w + v1.w + v2.w + v3.w};
#pragma unroll
            for (int e = 0; e < 4; e++) {
                int col = i >> 1, tk = (i & 1) * 4 + e;
                float sg = bf_round(__fdividef(1.0f, 1.0f + __expf(fminf(-s_r[tk], 80.f))));
                float upd = bf_round(bf_round(y[e]) * sg);
                float xn = __bfloat162float(*reinterpret_cast<const __nv_bfloat16*>(sm + XS + tk * 1296 + col * 2));
                g_brow[tk * DM + col] = __float2bfloat16_rn(xn + upd);
            }
        }
        if (tid < TOPC) g_sel[tid] = s_sel[tid];
        bar_sync(1, 320);
        if (tid == 0) {
            flag_signal(flag_ptr(FL_MOE_DONE));
            *reinterpret_cast<volatile unsigned*>(&g_epoch) = ep + 1;
        }
        PROF_GT(54);
    }
}

__global__ void __cluster_dims__(2, 1, 1) __launch_bounds__(384, 1)
fused_kernel(const __grid_constant__ CUtensorMap tmC, const __grid_constant__ CUtensorMap tmWk, const __grid_constant__ CUtensorMap tmWv,
             const __grid_constant__ CUtensorMap tmWq, const __grid_constant__ CUtensorMap tmWo,
             const __grid_constant__ CUtensorMap tmG, const __grid_constant__ CUtensorMap tmU, const __grid_constant__ CUtensorMap tmD, const Params P) {
    extern __shared__ __align__(1024) unsigned char smem_raw[];
    const uint32_t ring = smem_u32(smem_raw);
    const uint32_t misc = ring + RING_BYTES;
    const int tid = threadIdx.x;
    const int rank = blockIdx.x & 1;
    uint32_t smid, nsm;
    asm("mov.u32 %0, %%smid;" : "=r"(smid));
    asm("mov.u32 %0, %%nsmid;" : "=r"(nsm));
    if (nsm != 132) smid = blockIdx.x;
    auto role_of = [](int tpc) {
        return tpc < 32 ? (tpc & 7) * 8 + (tpc >> 3) : tpc < 60 ? (1 + (tpc - 32) % 7) * 8 + 4 + (tpc - 32) / 7 : tpc < 64 ? tpc - 56 : tpc;
    };
    int mc = role_of(smid >> 1);
    PROF_DECL(mc * 2 + rank)
    PROF_GT(0); PROF_EV(1);

    auto prefetch_w = [&](int ch) {
        const int i = tid - 128;
        asm volatile("prefetch.global.L2 [%0];" ::"l"((rank ? P.wv : P.wk) + (size_t)(ch * 128 + (mc & 3) * 32 + (i >> 3)) * 4096 + (mc >> 2) * 256 + (i & 7) * 16));
    };
    if (tid >= 128 && mc < 64) {
        if (tid < 256) asm volatile("prefetch.global.L2 [%0];" ::"l"(P.c + (size_t)((12 + (mc & 3)) * 128 + ((mc >> 2) * 2 + rank) * 4) * DC + (tid - 128) * 16));
        prefetch_w(0);
    }
    auto load_w0 = [&]() {
        const CUtensorMap* tw = rank ? &tmWv : &tmWk;
        mbar_expect_tx(misc + BAR_FULL + 8 * slot_of(0), SLOT_BYTES);
        tma2d(ring + slot_of(0) * SLOT_BYTES, tw, (mc >> 2) * 256, 0, misc + BAR_FULL + 8 * slot_of(0), policy(HM & 1));
        tma2d(ring + slot_of(0) * SLOT_BYTES + 16384, tw, (mc >> 2) * 256 + 64, 0, misc + BAR_FULL + 8 * slot_of(0), policy(HM & 1));
    };
    if (tid == 0) {
#pragma unroll
        for (int i = 0; i < NSLOT; i++) mbar_init(misc + BAR_FULL + 8 * i, 1);
#pragma unroll
        for (int i = 0; i < E0; i++) mbar_arrive(misc + BAR_FULL + 8 * i);
        asm volatile("fence.mbarrier_init.release.cluster;" ::: "memory");
        if (mc < 64) load_w0();
    }
    if (tid == 160) {
        asm volatile("st.shared.u32 [%0], %1;" ::"r"(misc + MISC_SMID), "r"(smid) : "memory");
        asm volatile("fence.release.sync_restrict::shared::cta.cluster;" ::: "memory");
    }
    if (tid == 32) {
        asm volatile("prefetch.tensormap [%0];" ::"l"(&tmC) : "memory");
#pragma unroll
        for (int i = 0; i < NSLOT; i++) mbar_init(misc + BAR_EMPTY + 8 * i, 16);
#pragma unroll
        for (int i = 0; i < E0; i++) mbar_arrive_cluster(misc + BAR_EMPTY + 8 * i, 16);
        asm volatile("fence.mbarrier_init.release.cluster;" ::: "memory");
    }
    if (tid == 64) {
#pragma unroll
        for (int i = 0; i < NST3; i++) { mbar_init(misc + BAR_FULL3 + 8 * i, 1); mbar_init(misc + BAR_EMPTY3 + 8 * i, 16); }
#pragma unroll
        for (int i = 0; i < 4; i++) mbar_init(misc + BAR_LN + 8 * i, 2);
        mbar_init(misc + BAR_PROG, 1); mbar_init(misc + BAR_PROG + 8, 1); mbar_init(misc + BAR_PROG + 16, 1);
        asm volatile("fence.mbarrier_init.release.cluster;" ::: "memory");
    }
    if (tid == 96) {
#pragma unroll
        for (int i = 0; i < 34; i++) mbar_init(misc + BAR_DEP + 8 * i, 1);
    }
    if (tid == 128) {
#pragma unroll
        for (int i = 0; i < 32; i++) mbar_init(misc + BAR_EV + 8 * i, 4);
    }
    __syncthreads();
    asm volatile("barrier.cluster.arrive.relaxed.aligned;\nbarrier.cluster.wait.aligned;" ::: "memory");
    {
        uint32_t peer;
        asm volatile("ld.shared::cluster.u32 %0, [%1];" : "=r"(peer) : "r"(mapa(misc + MISC_SMID, rank ^ 1)) : "memory");
        if ((__shfl_sync(0xffffffffu, peer, 0) ^ smid) != 1) {
            if (tid == 0) {
                const unsigned ep1 = *reinterpret_cast<volatile unsigned*>(&g_epoch) + 1;
                if ((smid & 1) == 0) atomicExch(g_roleq + 2 + (atomicAdd(g_roleq, 1u) & 127), (ep1 << 8) | (smid >> 1));
                if (rank == 0) {
                    unsigned* slot = g_roleq + 2 + (atomicAdd(g_roleq + 1, 1u) & 127);
                    unsigned v = 0;
                    for (int spin = 0; spin < 4000000 && ((v = atomicAdd(slot, 0u)) >> 8) != (ep1 & 0xffffffu); spin++) {}
                    asm volatile("st.shared::cluster.u32 [%0], %1;" ::"r"(mapa(misc + MISC_SMID + 4, 0)), "r"(v & 255) : "memory");
                    asm volatile("st.shared::cluster.u32 [%0], %1;" ::"r"(mapa(misc + MISC_SMID + 4, 1)), "r"(v & 255) : "memory");
                }
                if (mc < 64) {
                    mbar_wait(misc + BAR_FULL + 8 * slot_of(0), 0);
                    asm volatile("mbarrier.inval.shared::cta.b64 [%0];" ::"r"(misc + BAR_FULL + 8 * slot_of(0)) : "memory");
                    mbar_init(misc + BAR_FULL + 8 * slot_of(0), 1);
                    asm volatile("fence.mbarrier_init.release.cluster;" ::: "memory");
                }
            }
            __syncwarp();
            asm volatile("barrier.cluster.arrive.aligned;\nbarrier.cluster.wait.aligned;" ::: "memory");
            mc = role_of(__shfl_sync(0xffffffffu, lds32(misc + MISC_SMID + 4), 0));
            if (tid == 0 && mc < 64) load_w0();
            __syncwarp();
        }
    }
    const int cta = mc * 2 + rank;
    if (mc >= 64) { aux_cta(P, &tmG, &tmU, &tmD, smem_raw, cta - 128); return; }
    const int team = mc >> 2, k = mc & 3;
    const int u3 = (mc >> 4) * 2 + (team & 1), s3 = k, kap = (mc >> 3) & 1;
    const int partner = cta ^ 16;
    if (tid >= 128) prefetch_w(1);
    if (tid == 256) {
        const CUtensorMap* tw = rank ? &tmWv : &tmWk;
#pragma unroll
        for (int e = 1; e < NSLOT; e++) {
            const uint32_t fb = misc + BAR_FULL + 8 * slot_of(e), dst = ring + slot_of(e) * SLOT_BYTES;
            mbar_expect_tx(fb, SLOT_BYTES);
            if (e & 1) tma2d_mc(dst + rank * 16384, &tmC, (e >> 1) * 128 + rank * 64, (12 + k) * 128, fb, policy(false));
            else { tma2d(dst, tw, team * 256, e * 64, fb, policy(false)); tma2d(dst + 16384, tw, team * 256 + 64, e * 64, fb, policy(false)); }
        }
    }
    PROF_EV(5);
    const int wg = __shfl_sync(0xffffffffu, tid >> 7, 0);

    if (wg == 0) {
        asm volatile("setmaxnreg.dec.sync.aligned.u32 40;");
        const int warp = __shfl_sync(0xffffffffu, tid >> 5, 0), lane = tid & 31;
        if (warp == 0) {
            const bool lead = elect_one();
            Cur c = cur_at(NSLOT);
            uint32_t dst, fb;
            auto acquire = [&]() {
                mbar_wait(misc + BAR_EMPTY + 8 * c.slot, c.ph ^ 1);
                fb = misc + BAR_FULL + 8 * c.slot; dst = ring + c.slot * SLOT_BYTES;
                if (lead) mbar_expect_tx(fb, SLOT_BYTES);
                c.adv();
            };
            auto load_w = [&](const CUtensorMap* tm, int col, int row, bool stream) {
                acquire();
                if (lead) { tma2d(dst, tm, col, row, fb, policy(stream)); tma2d(dst + 16384, tm, col + 64, row, fb, policy(stream)); }
            };
            auto load_half = [&](const unsigned char* src, bool stream) {
                acquire();
                if (lead) bulk_load_mc(dst + rank * 16384, src, 16384, fb, policy(stream));
            };
            auto staging = [&]() {
                mbar_wait(misc + BAR_EMPTY + 8 * c.slot, c.ph ^ 1);
                if (lead) mbar_arrive(misc + BAR_FULL + 8 * c.slot);
                c.adv();
            };
            auto dep_wait = [&](int d) { mbar_wait(misc + BAR_DEP + 8 * d, 0); fence_async_global(); };
            auto op_prefetch = [&](int i) {
                const int head = op_head(i, kap);
                l2_prefetch(reinterpret_cast<const unsigned char*>(P.wo) + head * 163840 + (u3 * 8 + s3 * 2 + rank) * 2560, 2560);
                if (i < 8) l2_prefetch(g_Q + (size_t)(head * 32 + 4 * u3 + 2 * rank) * 16384 + s3 * 8192, 8192);
            };
            const CUtensorMap* tw = rank ? &tmWv : &tmWk;
            const unsigned char* Kh = g_K + (size_t)team * 32 * 16384 + rank * 16384;
            const unsigned char* Vh = g_V + (size_t)team * 32 * 16384 + rank * 16384;
#pragma unroll 1
            for (int v = 0; v < 2; v++) {
                const int h = 2 * team + v;
#pragma unroll 1
                for (int i = v ? 0 : 3; i < 16; i++) {
                    if (i < 4 && v) load_w(tw, h * 128, i * 128, HM & 1);
                    if (v && (i & 7) == 3) dep_wait(D_WAR + (i >> 3));
                    acquire();
                    if (lead) tma2d_mc(dst + rank * 16384, &tmC, (i & 3) * 128 + rank * 64, (12 - (i & 12) + k) * 128, fb, policy(HM & 2));
                    if (v && i == 2 && lead) mbar_arrive(misc + BAR_PROG + 8);
                }
                if (v == 0) {
                    const int cq = (h + rank) * 128;
                    load_w(&tmWq, cq, 0, HM & 1); load_w(&tmWq, cq, 128, HM & 1); load_w(&tmWq, cq, 256, HM & 1);
#pragma unroll 1
                    for (int t = 0; t < 4; t++) {
                        const unsigned char* xt = g_xn + (q_tile(k, t) * 10 + rank) * 16384;
                        dep_wait(D_LN + t);
                        if (t == 3 && lead) l2_prefetch((rank ? Vh - 16384 : Kh) + (13 - 2 * k) * 32768, 3 * 32768);
#pragma unroll 1
                        for (int ch = 0; ch < 5; ch++) {
                            load_half(xt + ch * 32768, HM & 4);
                            if (t == 0 && ch == 0) load_w(&tmWq, cq, 384, HM & 1);
                        }
                        load_w(&tmWq, cq, 512, (HM & 1) && t == 3);
                    }
                }
                int togo = v ? PF_START : 11;
#pragma unroll 1
                for (int r = 0; r < 2; r++) {
                    const int p = r ? k : 7 - k, n = 2 * p + 1;
                    if (v == 0) dep_wait(D_Q + r);
                    acquire();
                    if (lead) {
                        const int g0 = r ? rank : 3 - rank;
                        bulk_load(dst, g_Q + (size_t)(h * 32 + 4 * p + g0) * 16384, 16384, fb, policy(HM & 8));
                        bulk_load(dst + 16384, g_Q + (size_t)(h * 32 + 4 * p + 3 - g0) * 16384, 16384, fb, policy(HM & 8));
                    }
                    if (v && r == 0) dep_wait(D_KV + 4 + (k >> 1));
                    load_half(Kh + n * 32768, HM & 16);
                    if (r) { load_half(Vh, HM & 16); staging(); }
#pragma unroll 1
                    for (int j = n - 1; j >= 0; j--) {
                        if (v && r == 0 && (j & 3) == 3) dep_wait(D_KV + 7 - (j >> 2));
                        load_half(Kh + j * 32768, HM & 16); load_half(Vh + (j + 1) * 32768, HM & 16);
                        if (v == 0 && r == 0 && j == 3 && lead) mbar_arrive(misc + BAR_PROG);
                        --togo;
                        if (v == 0 && togo == 0 && lead) {
                            tma2d_prefetch(tw, h * 128 + 128, k * 128); tma2d_prefetch(tw, h * 128 + 192, k * 128);
                            l2_prefetch(reinterpret_cast<const unsigned char*>(P.c) + (size_t)cta * 16384, 16384);
                        }
                        if (v && togo <= 0 && togo > -OP_PF && lead) op_prefetch(-togo);
                    }
                }
                load_half(Vh, HM & 16);
                staging();
                if (v == 0 && lead) l2_prefetch(g_Q + (size_t)((h + 1) * 32 + 8 * k + 4 * rank) * 16384, 65536);
            }
            mbar_wait(misc + BAR_EMPTY + 8 * c.slot, c.ph ^ 1); c.adv();
            int st = 0; uint32_t ph3 = 0;
#pragma unroll 1
            for (int i = 0; i < 32; i++) {
                const int head = op_head(i >> 1, kap);
                if ((i & 1) == 0) dep_wait(D_CTX + (i >> 1));
                if (i < NST3) { mbar_wait(misc + BAR_EMPTY + 8 * c.slot, c.ph ^ 1); c.adv(); }
                else mbar_wait(misc + BAR_EMPTY3 + 8 * st, ph3 ^ 1);
                fb = misc + BAR_FULL3 + 8 * st; dst = ring + st * ST3_BYTES;
                if (i == LATE_AT && lead) mbar_arrive(misc + BAR_PROG + 16);
                if (lead) {
                    mbar_expect_tx(fb, ST3_BYTES);
                    const unsigned char* src = g_Q + (size_t)(head * 32 + 4 * u3 + 2 * rank) * 16384 + (i & 1) * 8192;
                    bulk_load(dst, src, 8192, fb, policy(HM & 32));
                    bulk_load(dst + 8192, src + 16384, 8192, fb, policy(HM & 32));
                    tma3d_mc(dst + 16384 + rank * 10240, &tmWo, 0, head * 128 + (i & 1) * 64 + rank * 32, 5 * s3, fb, policy(HM & 32));
                    if ((i & 1) && (i >> 1) + OP_PF < 16) op_prefetch((i >> 1) + OP_PF);
                }
                if (++st == NST3) { st = 0; ph3 ^= 1; }
            }
        } else if (warp == 3) {
            const unsigned ep1 = *reinterpret_cast<volatile unsigned*>(&g_epoch) + 1;
            if (lane == 0) {
                asm volatile("st.shared.u32 [%0], %1;" ::"r"(misc + MISC_EPOCH), "r"(ep1) : "memory");
                if (CDELAY) __nanosleep(CDELAY);
                l2_prefetch(reinterpret_cast<const unsigned char*>(P.c) + (size_t)cta * 12288, 12288);
#pragma unroll 1
                for (int t = 0; t < 4; t++) {
                    if (t == 1) {
                        mbar_wait(misc + BAR_PF, 0);
                        l2_prefetch(reinterpret_cast<const unsigned char*>(P.wq) + (size_t)cta * 40960, 40960);
                    }
                    if (t != 2) {
                        mbar_wait(misc + BAR_LN + 8 * t, 0);
                        flag_signal(flag_ptr(FL_LN + q_tile(cta >> 5, t)));
                    }
                    flag_wait(flag_ptr(FL_LN + q_tile(k, t)), ep1 * 32u);
                    mbar_arrive(misc + BAR_DEP + 8 * (D_LN + t));
                }
                mbar_wait(misc + BAR_EV + 8 * (16 + EV_KV + 3), 0);
                flag_wait(flag_ptr(FL_KV + team * 8), ep1 * 16u);
#pragma unroll 1
                for (int i = 0; i < 2; i++) {
                    mbar_wait(misc + BAR_EV + 8 * (16 + EV_Q + 1 + 2 * i), 0);
                    flag_wait(flag_ptr(FL_Q + team * 8 + (i ? k : 7 - k)), ep1 * 4u);
                    mbar_arrive(misc + BAR_DEP + 8 * (D_Q + i));
                }
#pragma unroll 1
                for (int i = 0; i < 2; i++) {
                    mbar_wait(misc + BAR_PROG + 8 * i, 0);
                    flag_signal(flag_ptr(FL_WAR + 2 * team + i));
                    flag_wait(flag_ptr(FL_WAR + 2 * team + i), ep1 * 8u);
                    mbar_arrive(misc + BAR_DEP + 8 * (D_WAR + i));
                }
#pragma unroll 1
                for (int i = 4; i < 8; i++) {
                    mbar_wait(misc + BAR_EV + 8 * (16 + EV_KV + i), 0);
                    flag_wait(flag_ptr(FL_KV + team * 8 + i), ep1 * 16u);
                    mbar_arrive(misc + BAR_DEP + 8 * (D_KV + i));
                }
                flag_wait(flag_ptr(FL_MOE_DONE), ep1);
                int4 s0 = __ldcg(reinterpret_cast<const int4*>(g_sel)), s1 = __ldcg(reinterpret_cast<const int4*>(g_sel) + 1);
                asm volatile("st.shared.v4.u32 [%0], {%1,%2,%3,%4};" ::"r"(misc + MISC_SEL), "r"(s0.x), "r"(s0.y), "r"(s0.z), "r"(s0.w) : "memory");
                asm volatile("st.shared.v4.u32 [%0], {%1,%2,%3,%4};" ::"r"(misc + MISC_SEL + 16), "r"(s1.x), "r"(s1.y), "r"(s1.z), "r"(s1.w) : "memory");
                mbar_arrive(misc + BAR_SEL);
            }
            __syncwarp();
            const unsigned* cf = flag_ptr(FL_CTX + op_head(lane & 15, kap) * 8 + u3);
#pragma unroll 1
            for (int half = 0; half < 2; half++) {
                if (half) mbar_wait(misc + BAR_EV + 8 * (EV_CTX + 3), 0);
                bool done = (lane >> 3) != half;
                for (int spin = 0; spin < 4000000; spin++) {
                    if (!done) {
                        unsigned v;
                        asm volatile("ld.acquire.gpu.global.u32 %0, [%1];" : "=r"(v) : "l"(cf) : "memory");
                        if ((int)(v - ep1 * 4u) >= 0) { mbar_arrive(misc + BAR_DEP + 8 * (D_CTX + lane)); done = true; }
                    }
                    if (__all_sync(0xffffffffu, done)) break;
                    __nanosleep(64);
                }
            }
        } else {
            const int w = warp - 1;
            if (lane < 20) {
#pragma unroll
                for (int i = 0; i < 2; i++) {
                    const int ch = w * 40 + i * 20 + lane;
                    uint4 u = __ldg(reinterpret_cast<const uint4*>(P.wr) + ch);
                    asm volatile("st.shared.v4.b32 [%0], {%1,%2,%3,%4};" ::"r"(misc + MISC_WR + 16 * ch), "r"(u.x), "r"(u.y), "r"(u.z), "r"(u.w) : "memory");
                }
            }
            const int rsub = (cta & 31) * 4 + 2 * w;
            if (LNDELAY) __nanosleep(LNDELAY);
            bar_sync(3, 64);
#pragma unroll 1
            for (int t = 0; t < 4; t += 1 + (t & 1)) {
                if (t < 2) {
#pragma unroll
                    for (int i = 0; i < 3; i++)
                        if (i * 32 + lane < 80) asm volatile("prefetch.global.L2 [%0];" ::"l"(P.x + (size_t)(q_tile(cta >> 5, 2 * t + 1) * 128 + rsub) * DM + (i * 32 + lane) * 16));
                }
                ln_rows(P, q_tile(cta >> 5, t) * 128 + rsub, lane, misc + MISC_WR);
                __syncwarp();
                if (lane == 0) mbar_arrive(misc + BAR_LN + 8 * t);
            }
            if (lane == 0) {
                const uint32_t eb = misc + BAR_EV + w * 128;
#pragma unroll 1
                for (int v = 0; v < 2; v++) {
#pragma unroll 1
                    for (int i = 0; i < (v ? 4 : 3); i++) {
                        mbar_wait(eb + 8 * (v ? EV_KV + 4 + i : i ? EV_Q + 2 * i - 1 : EV_KV + 3), 0);
                        flag_signal(flag_ptr(v ? FL_KV + team * 8 + 4 + i : i ? FL_Q + team * 8 + (i == 1 ? 7 - k : k) : FL_KV + team * 8));
                    }
#pragma unroll 1
                    for (int r = 0; r < 2; r++) {
                        const int p = r ? k : 7 - k;
                        const uint32_t slot = ((v ? E_ATT1 : E_ATT0) + (r ? 39 : 4 * p + 7) + E0) % NSLOT;
                        const int grp = (r == w) ? 3 - rank : rank;
                        mbar_wait(eb + 8 * (EV_CTX + 2 * v + r), 0);
                        asm volatile("cp.async.bulk.global.shared::cta.bulk_group.L2::cache_hint [%0], [%1], 16384, %2;"
                                     ::"l"(g_Q + (size_t)((2 * team + v) * 32 + 4 * p + grp) * 16384), "r"(ring + slot * SLOT_BYTES + w * 16384),
                                       "l"(policy((HM & 256) && v == 0)) : "memory");
                        asm volatile("cp.async.bulk.commit_group;" ::: "memory");
                        asm volatile("cp.async.bulk.wait_group.read 0;" ::: "memory");
                        mbar_arrive_cluster(mapa(misc + BAR_EMPTY + 8 * slot, 0), 4);
                        mbar_arrive_cluster(mapa(misc + BAR_EMPTY + 8 * slot, 1), 4);
                        asm volatile("cp.async.bulk.wait_group 0;" ::: "memory");
                        fence_async_global();
                        flag_signal(flag_ptr(FL_CTX + (2 * team + v) * 8 + p));
                    }
                }
            }
            __syncwarp();
            mbar_wait(misc + BAR_PROG + 16, 0);
            const int row = (2 * u3 + rank) * 128 + 64 * w + perm32(16 * (lane >> 3) + 8 * kap + (lane & 7));
#pragma unroll
            for (int i = 0; i < 10; i++) asm volatile("prefetch.global.L2 [%0];" ::"l"(P.x + (size_t)row * DM + 160 * s3 + 16 * i));
            asm volatile("prefetch.global.L2 [%0];" ::"l"(g_stats + row));
        }
    } else {
        asm volatile("setmaxnreg.inc.sync.aligned.u32 232;");
        Ctx c;
        c.ring = ring; c.misc = misc; c.w = wg - 1; c.warp = __shfl_sync(0xffffffffu, (tid >> 5) & 3, 0); c.lane = tid & 31;
        c.rel = mapa(misc, tid & 1);
        const int w = c.w;
        if (w == 1) bar_arrive(1, 256);
        prefetch_w(2); prefetch_w(3);
        Cur cur = cur_at(0);
        float o[64], inv[2];
#pragma unroll 1
        for (int v = 0; v < 2; v++) {
        {
            uint32_t wf[128];
            float acc[64];
#pragma unroll
            for (int i = 32; i < 128; i++) wf[i] = 0u;
            Cur cw = cur;
            int wstep = 2;
            auto load_wchunk = [&](auto CH) {
                constexpr int ch = decltype(CH)::value;
                mbar_wait_hot(misc + BAR_FULL + 8 * cw.slot, cw.ph);
                const uint32_t z = load_afrag<8, 32 * ch>(wf, ring + cw.slot * SLOT_BYTES + w * 16384, c);
                release(c, BAR_EMPTY + 8 * cw.slot + z, 1);
                cw.adv();
                if (wstep == 2 || ch == 2) cw.adv();
            };
            load_wchunk(IC<0>{});
            cur.adv();
            int nload = 1;
            PROF_EV(2); PROF_GT(60);
#pragma unroll 1
            for (int t = 0; t < (v ? 4 : 8); t++) {
                uint32_t last = 0;
                token_wait(w);
                PROF_EV(t < 4 ? 10 : 20);
                undef_regs(acc);
                auto chunk = [&](auto CH) {
                    constexpr int ch = decltype(CH)::value;
                    mbar_wait_hot(misc + BAR_FULL + 8 * cur.slot, cur.ph);
                    if (t == 0 || t == 4) { PROF_EV(12 + ch); }
                    uint64_t d = mkdesc(ring + cur.slot * SLOT_BYTES, 16, 1024, 1);
                    wg_fence();
#pragma unroll
                    for (int ks = 0; ks < 8; ks++)
                        wgmma_rs_n128_ta0_tb0(acc, wf[32 * ch + 4 * ks], wf[32 * ch + 4 * ks + 1], wf[32 * ch + 4 * ks + 2], wf[32 * ch + 4 * ks + 3],
                                              d + (ks >> 2) * 1024 + (ks & 3) * 2, (ch | ks) != 0);
                    wg_commit();
                    const bool swap = (ch < (FV == 2 ? 3 : 2) && t == 0) || (ch == 3 && t < 4);
                    if (swap) token_pass(w);
                    if constexpr (ch < 3) { if (nload == ch + 1) { load_wchunk(IC<ch + 1>{}); nload++; } }
                    if (ch > 0) { wg_wait<1>(); release(c, BAR_EMPTY + 8 * last, 1); }
                    last = cur.slot;
                    cur.adv();
                    if ((ch < 3 && t == 0) || (ch == 0 && t == 4)) cur.adv();
                    if constexpr (FV == 1 && ch == 1) { if (t == 0) { load_wchunk(IC<3>{}); nload++; } }
                    if constexpr (FV == 3 && ch == 1) { if (t == 0 && w) { load_wchunk(IC<3>{}); nload++; } }
                    if (ch < 3 && swap) token_wait(w);
                };
                chunk(IC<0>{}); chunk(IC<1>{}); chunk(IC<2>{}); chunk(IC<3>{});
                if (t < 4) {
                    wg_wait<0>();
                    release(c, BAR_EMPTY + 8 * last, 1);
                } else {
                    Cur cx = cur; cur.adv();
                    mbar_wait_hot(misc + BAR_FULL + 8 * cx.slot, cx.ph);
                    mbar_wait_hot(misc + BAR_FULL + 8 * cur.slot, cur.ph);
                    uint64_t db = mkdesc(ring + cx.slot * SLOT_BYTES, 16, 1024, 1);
                    uint64_t da = mkdesc(ring + cur.slot * SLOT_BYTES + w * 16384, 16384, 1024, 1);
                    wg_fence();
#pragma unroll
                    for (int ks = 0; ks < 8; ks++) wgmma_ss_n128_ta1_tb0(acc, da + 128 * ks, db + (ks >> 2) * 1024 + (ks & 3) * 2, 1);
                    wg_commit();
                    token_pass(w);
                    wg_wait<1>(); release(c, BAR_EMPTY + 8 * last, 1);
                    wg_wait<0>(); release(c, BAR_EMPTY + 8 * cx.slot, 1); release(c, BAR_EMPTY + 8 * cur.slot, 1);
                    cur.adv();
                    fence_regs(acc);
#pragma unroll
                    for (int i = 0; i < 64; i++) acc[i] *= SM_SCALE;
                }
                PROF_EV(t < 4 ? 11 : 21);
                fence_regs(acc);
                if (t == 0 && v == 0 && tid == 128) mbar_arrive(misc + BAR_PF);
                const bool wswitch = t == 3 && v == 0;
                if (wswitch) {
                    cw = cur; wstep = 1; nload = 0;
                    cur.adv(); cur.adv(); cur.adv();
                    if (w) { load_wchunk(IC<0>{}); load_wchunk(IC<1>{}); load_wchunk(IC<2>{}); nload = 3; }
                }
                unsigned char* dst = t < 4 ? (rank ? g_V : g_K) + (size_t)(team * 32 + 24 + 2 * k - 8 * t) * 16384
                                           : g_Q + (size_t)((2 * team + rank) * 32 + q_tile(k, t & 3) * 2) * 16384;
                store_proj(acc, dst, c, policy(((HM & 64) && t >= 4 && rank) || ((HM & 128) && t >= 6)));
                signal_event(c, t < 4 ? EV_KV + 4 * v + t : EV_Q + t - 4);
                if (wswitch) {
                    if (w) { load_wchunk(IC<3>{}); nload = 4; }
                    else { load_wchunk(IC<0>{}); load_wchunk(IC<1>{}); nload = 2; }
                }
                if (t == 3) { PROF_EV(61); PROF_GT(62); }
            }
        }
        PROF_EV(63); PROF_GT(64);
        {
            uint32_t q[32], p[32];
            float m[2], l[2], tq[2];
#pragma unroll
            for (int i = 0; i < 64; i++) o[i] = 0.f;
#pragma unroll
            for (int i = 0; i < 32; i++) p[i] = 0u;
            m[0] = m[1] = inv[0] = inv[1] = 0.f;
            l[0] = l[1] = tq[0] = tq[1] = 1.f;
            int gen = 0;
            Cur ck = cur, cv = cur, cq, ce;
            int r = 0, left;
            int first = 1, half, heavy;
            int pv_acc = 0, pv_mode = 2; uint32_t pv_cnt = 0;
            int pending = 0;
            Cur nck, ncv;
            auto next_task = [&](int rr) {
                heavy = 1 ^ rr ^ w;
                half = 1 ^ heavy ^ rank;
                left = 2 * (rr ? k : 7 - k) + 1 + heavy;
                cq = cur; cur.adv();
                nck = cur; cur.adv();
                if (rr) { ncv = cur; cur.adv(); ce = cur; cur.adv(); }
                if (!heavy) { nck = cur; cur.adv(); cur.adv(); }
                if (!rr) { ncv = nck; ce = nck; }
            };
            auto load_q = [&]() {
                mbar_wait_hot(misc + BAR_FULL + 8 * cq.slot, cq.ph);
                load_afrag<8, 0>(q, ring + cq.slot * SLOT_BYTES + w * 16384, c);
            };
            next_task(0);
            load_q();
            uint32_t k_cnt = 1; int last = 0, was_first = 0, was_half = 0, publish = 0;
            auto window = [&]() {
                mbar_wait_hot(misc + BAR_FULL + 8 * cv.slot, cv.ph);
                publish = pending;
                if (pending) stage_ctx<2, 4>(o, inv, ce, c);
                pending = 0;
                k_cnt = 1;
                was_first = first; was_half = half;
                if (first) {
                    release(c, BAR_EMPTY + 8 * cq.slot, 1);
                    l[0] += tq[0]; l[1] += tq[1];
                    tq[0] = __shfl_xor_sync(0xffffffffu, l[0], 2); tq[1] = __shfl_xor_sync(0xffffffffu, l[1], 2);
                    pending = r;
                    k_cnt = 1 + heavy;
                }
                last = --left == 0 ? 1 : 0;
                first = last;
                if (!last) { nck = cur; cur.adv(); ncv = cur; cur.adv(); half = 0; }
                else if (++r < 2) next_task(1);
            };
            auto new_rows = [&]() {
                inv[0] = rcp_fast(l[0] + tq[0]); inv[1] = rcp_fast(l[1] + tq[1]);
                l[0] = l[1] = m[0] = m[1] = 0.f;
                gen = 0;
            };
            ck = nck; cv = ncv;
            mbar_wait_hot(misc + BAR_FULL + 8 * ck.slot, ck.ph);
            uint32_t qaddr1 = ring + (((v ? E_ATT1 : E_ATT0) + 32 - 4 * k + E0) % NSLOT) * SLOT_BYTES + w * 16384 +
                              (8 * (c.lane >> 4) + (c.lane & 7)) * 128 + (((2 * c.warp + ((c.lane >> 3) & 1)) ^ (c.lane & 7)) << 4);
            qaddr1 = __shfl_sync(0xffffffffu, qaddr1, c.lane);
#pragma unroll 1
            while (r < 2) {
                float s[64];
                if (half) {
                    token_wait(w);
                    PROF_EV(30);
                    float sh[32];
                    undef_regs(sh);
                    issue_qk_half(sh, q, ring + ck.slot * SLOT_BYTES);
                    window();
                    issue_pv(o, p, ring + cv.slot * SLOT_BYTES, pv_acc, pv_mode);
                    token_pass(w);
                    wg_wait<1>();
                    PROF_EV(34);
                    fence_regs(sh);
                    new_rows();
                    mask_diag<0>(sh, c);
                    float l0 = 0.f, l1 = 0.f;
                    if (blockIdx.y == 0) {
#pragma unroll
                        for (int j = 0; j < 8; j++) {
#pragma unroll
                            for (int e = 0; e < 4; e++) ex2v(sh[4 * j + e]);
                            l0 += sh[4 * j] + sh[4 * j + 1]; l1 += sh[4 * j + 2] + sh[4 * j + 3];
                        }
                    }
                    const int lim = mask_lim(c);
                    const bool bad = __any_sync(0xffffffffu, !(l0 <= SAFE_SUM && l1 <= SAFE_SUM && (l0 >= 1.0f / SAFE_SUM || lim < 0) &&
                                                               (l1 >= 1.0f / SAFE_SUM || lim < -2)));
                    if (!bad) { l[0] = l0; l[1] = l1; asm volatile("" ::: "memory"); }
                    wg_wait<0>();
                    fence_regs(o);
                    fence_regs(sh);
                    if (bad) goto redo;
#pragma unroll
                    for (int i = 0; i < 16; i++) p[i] = pack_bf16(sh[2 * i], sh[2 * i + 1]);
                    goto tail;
                }
#pragma unroll 1
                while (true) {
                    token_wait(w);
                    PROF_EV(first ? 30 : 31);
                    undef_regs(s);
                    issue_qk(s, q, ring + ck.slot * SLOT_BYTES);
                    const bool special = first > 0 || pv_acc == 0 || left == 1;
                    if (special) window();
                    else {
                        nck = cur; cur.adv(); ncv = cur; cur.adv();
                        --left;
                        mbar_wait_hot(misc + BAR_FULL + 8 * cv.slot, cv.ph);
                    }
                    issue_pv(o, p, ring + cv.slot * SLOT_BYTES, pv_acc, pv_mode);
                    token_pass(w);
                    wg_wait<1>();
                    PROF_EV(33);
                    fence_regs(s);
                    float lo = 0.f;
                    if (special) {
                        if (last && r < 2) {
                            mbar_wait_hot(misc + BAR_FULL + 8 * cq.slot, cq.ph);
#pragma unroll
                            for (int ks = 0; ks < 8; ks++) ldsm4t(q[4 * ks], q[4 * ks + 1], q[4 * ks + 2], q[4 * ks + 3], qaddr1 + ks * 2048);
                        }
                        if (publish) publish_ctx(EV_CTX + 2 * v, c);
                        if (was_first) {
                            new_rows();
                            lo = 1.0f / SAFE_SUM;
                            mask_diag<8>(s, c);
                        }
                    }
                    constexpr int JB = 11;
                    float l0 = l[0], l1 = l[1];
                    if (!gen) {
#pragma unroll
                        for (int j = 0; j < JB; j++) {
#pragma unroll
                            for (int e = 0; e < 4; e++) ex2v(s[4 * j + e]);
                            if (j < JB - 1) { l0 += s[4 * j] + s[4 * j + 1]; l1 += s[4 * j + 2] + s[4 * j + 3]; }
                        }
                    }
                    wg_wait<0>();
                    fence_regs(o);
                    if (gen) goto general;
#pragma unroll
                    for (int j = JB - 1; j < 16; j++) {
                        if (j >= JB) {
#pragma unroll
                            for (int e = 0; e < 4; e++) ex2v(s[4 * j + e]);
                        }
                        l0 += s[4 * j] + s[4 * j + 1]; l1 += s[4 * j + 2] + s[4 * j + 3];
                    }
#pragma unroll
                    for (int i = 0; i < 32; i++) p[i] = pack_bf16(s[2 * i], s[2 * i + 1]);
                    if (__any_sync(0xffffffffu, !(l0 <= SAFE_SUM && l1 <= SAFE_SUM && l0 >= lo && l1 >= lo))) goto redo;
                    l[0] = l0; l[1] = l1;
                    if (special) goto tail;
                    release(c, BAR_EMPTY + 8 * ck.slot, 1);
                    release(c, BAR_EMPTY + 8 * cv.slot, 1);
                    ck = nck; cv = ncv;
                    mbar_wait_hot(misc + BAR_FULL + 8 * ck.slot, ck.ph);
                }
            redo:
                {
                    const int rr = r - last;
                    const int grp = (rr == w) ? 3 - rank : rank;
                    recompute_scores(s, g_Q + (size_t)((2 * team + v) * 32 + 4 * (rr ? k : 7 - k) + grp) * 16384, ring + ck.slot * SLOT_BYTES, c);
                    if (was_first) { mask_any(s, was_half ^ 1, c); m[0] = m[1] = -INFINITY; }
                    gen = 1;
                }
            general:
                {
                    float mx[2], alpha[2];
                    row_max<16>(s, mx);
#pragma unroll
                    for (int i = 0; i < 2; i++) {
                        mx[i] = fmaxf(mx[i], m[i]);
                        alpha[i] = was_first ? 1.0f : ex2(m[i] - mx[i]);
                        m[i] = mx[i];
                        l[i] *= alpha[i];
                    }
                    exp_sum<16, true>(s, m, l[0], l[1]);
#pragma unroll
                    for (int i = 0; i < 64; i++) o[i] *= alpha[(i >> 1) & 1];
#pragma unroll
                    for (int i = 0; i < 32; i++) p[i] = pack_bf16(s[2 * i], s[2 * i + 1]);
                }
            tail:
                release(c, BAR_EMPTY + 8 * ck.slot, k_cnt);
                if (pv_cnt) release(c, BAR_EMPTY + 8 * cv.slot, pv_cnt);
                pv_acc = was_first ^ 1; pv_mode = was_half; pv_cnt = k_cnt;
                if (r < 2) { ck = nck; cv = ncv; } else ck = cur;
                mbar_wait_hot(misc + BAR_FULL + 8 * ck.slot, ck.ph);
                if (pending) stage_ctx<0, 2>(o, inv, ce, c);
                if (last) { tq[0] = __shfl_xor_sync(0xffffffffu, l[0], 1); tq[1] = __shfl_xor_sync(0xffffffffu, l[1], 1); }
            }
            if (pending) { stage_ctx<2, 4>(o, inv, ce, c); publish_ctx(EV_CTX + 2 * v, c); }
            token_wait(w);
            PROF_EV(32);
            issue_pv(o, p, ring + cur.slot * SLOT_BYTES, pv_acc, pv_mode);
            if (w == 0 || v == 0) token_pass(w);
            l[0] += tq[0]; l[1] += tq[1];
            inv[0] = rcp_fast(l[0] + __shfl_xor_sync(0xffffffffu, l[0], 2));
            inv[1] = rcp_fast(l[1] + __shfl_xor_sync(0xffffffffu, l[1], 2));
            wg_wait<0>();
            release(c, BAR_EMPTY + 8 * cur.slot, pv_cnt);
            fence_regs(o);
            cur.adv();
            if (v == 0) { stage_ctx<0, 4>(o, inv, cur, c); publish_ctx(EV_CTX + 1, c); cur.adv(); }
        }
        }
        {
            float acc[80];
            undef_regs(acc);
            int st = 0, prev = 0; uint32_t ph3 = 0;
            auto op_stage = [&](int i) {
                mbar_wait(misc + BAR_FULL3 + 8 * st, ph3);
                PROF_EV(44);
                uint32_t base = ring + st * ST3_BYTES;
                uint64_t da = mkdesc(base + w * 8192, 16, 1024, 1);
                uint64_t db = mkdesc(base + 16384, 2048, 512, 2);
                wg_fence();
#pragma unroll
                for (int k = 0; k < 4; k++) wgmma_ss_n160_ta0_tb1(acc, da + 2 * k, db + (k >> 1) * 640 + (k & 1) * 64, k ? 1 : i);
                wg_commit();
                if (i > 0) { wg_wait<1>(); if (i <= 32 - NST3) release(c, BAR_EMPTY3 + 8 * prev, 1); }
                prev = st;
                if (++st == NST3) { st = 0; ph3 ^= 1; }
            };
            PROF_EV(40); PROF_GT(65);
            op_stage(0);
            stage_ctx<0, 4>(o, inv, cur, c);
            publish_ctx(EV_CTX + 3, c);
#pragma unroll 1
            for (int i = 1; i < 12; i++) op_stage(i);
            mbar_wait(misc + BAR_SEL, 0);
            const uint32_t tag = lds32(misc + MISC_EPOCH) & 1;
            const int g = c.lane >> 2, t = c.lane & 3;
            const int row = (2 * u3 + rank) * 128 + 64 * w + perm32(16 * c.warp + 8 * kap + (((g & 3) << 1) | (g >> 2)));
            const int col = 160 * s3 + 8 * t;
            int sel = -1;
#pragma unroll
            for (int i = 0; i < TOPC; i++) if ((int)lds32(misc + MISC_SEL + 4 * i) == row) sel = i;
            const int t256 = tid - 128;
            uint4* sendp = g_part + (size_t)cta * 2560 + t256;
            if (c.lane >= 30) stg128(sendp + 9 * 256, tag ^ 1, tag ^ 1, tag ^ 1, tag ^ 1);
#pragma unroll 1
            for (int i = 12; i < 32; i++) op_stage(i);
            uint4 xv[5], bv[5];
#pragma unroll
            for (int i = 0; i < 5; i++) xv[i] = ldg128(P.x + (size_t)row * DM + col + 32 * i);
            uint2 stat;
            asm volatile("ld.global.cg.v2.b32 {%0,%1}, [%2];" : "=r"(stat.x), "=r"(stat.y) : "l"(g_stats + row) : "memory");
            wg_wait<0>();
            fence_regs(acc);
            PROF_EV(41); PROF_GT(66);
            float keep[40];
#pragma unroll
            for (int j = 0; j < 10; j++) {
                uint32_t v0 = __float_as_uint(kap ? acc[8 * j + 0] : acc[8 * j + 2]), v1 = __float_as_uint(kap ? acc[8 * j + 1] : acc[8 * j + 3]);
                uint32_t v2 = __float_as_uint(kap ? acc[8 * j + 4] : acc[8 * j + 6]), v3 = __float_as_uint(kap ? acc[8 * j + 5] : acc[8 * j + 7]);
                asm volatile("st.relaxed.gpu.global.v4.b32 [%0], {%1,%2,%3,%4};" ::"l"(sendp + j * 256),
                             "r"((v0 & ~1u) | tag), "r"((v1 & ~1u) | tag), "r"((v2 & ~1u) | tag), "r"((v3 & ~1u) | tag) : "memory");
                keep[4 * j + 0] = kap ? acc[8 * j + 2] : acc[8 * j + 0]; keep[4 * j + 1] = kap ? acc[8 * j + 3] : acc[8 * j + 1];
                keep[4 * j + 2] = kap ? acc[8 * j + 6] : acc[8 * j + 4]; keep[4 * j + 3] = kap ? acc[8 * j + 7] : acc[8 * j + 5];
            }
            PROF_GT(67);
#pragma unroll
            for (int i = 0; i < 5; i++) {
                uint32_t xx[4] = {xv[i].x, xv[i].y, xv[i].z, xv[i].w};
#pragma unroll
                for (int e = 0; e < 4; e++) {
                    asm("sub.rn.bf16x2 %0, %0, %1;" : "+r"(xx[e]) : "r"(stat.x));
                    xx[e] = pack_bf16(bf_lo(xx[e]) * __uint_as_float(stat.y), bf_hi(xx[e]) * __uint_as_float(stat.y));
                }
                bv[i] = make_uint4(xx[0], xx[1], xx[2], xx[3]);
            }
            if (sel >= 0) {
#pragma unroll
                for (int i = 0; i < 5; i++) bv[i] = ldg128(g_brow + sel * DM + col + 32 * i);
            }
            const uint4* recvp = g_part + (size_t)partner * 2560 + t256;
            uint4 rv[10];
            int spins = 0;
            while (POLL1) {
                uint32_t v;
                asm volatile("ld.relaxed.gpu.global.b32 %0, [%1];" : "=r"(v) : "l"(recvp + 9 * 256 + (31 - c.lane)) : "memory");
                if (__all_sync(0xffffffffu, (v & 1u) == tag) || ++spins > 2000000) break;
            }
            PROF_GT(68);
            while (true) {
                uint32_t bad = 0u;
#pragma unroll
                for (int j = 0; j < 10; j++) {
                    asm volatile("ld.relaxed.gpu.global.v4.b32 {%0,%1,%2,%3}, [%4];"
                                 : "=r"(rv[j].x), "=r"(rv[j].y), "=r"(rv[j].z), "=r"(rv[j].w) : "l"(recvp + j * 256) : "memory");
                }
#pragma unroll
                for (int j = 0; j < 10; j++) {
                    rv[j].x ^= tag; rv[j].y ^= tag; rv[j].z ^= tag; rv[j].w ^= tag;
                    bad |= rv[j].x | rv[j].y | rv[j].z | rv[j].w;
                }
                if (__all_sync(0xffffffffu, (bad & 1u) == 0) || ++spins > 2000000) break;
            }
            PROF_GT(69);
            uint32_t pk[20];
#pragma unroll
            for (int j = 0; j < 10; j++) {
                pk[2 * j] = pack_bf16(keep[4 * j] + __uint_as_float(rv[j].x), keep[4 * j + 1] + __uint_as_float(rv[j].y));
                pk[2 * j + 1] = pack_bf16(keep[4 * j + 2] + __uint_as_float(rv[j].z), keep[4 * j + 3] + __uint_as_float(rv[j].w));
            }
#pragma unroll
            for (int i = 0; i < 5; i++) {
                uint32_t a0 = pk[4 * i], a1 = pk[4 * i + 1], a2 = pk[4 * i + 2], a3 = pk[4 * i + 3];
                uint32_t x0 = (t & 1) ? a0 : a1, x1 = (t & 1) ? a2 : a3;
                x0 = __shfl_xor_sync(0xffffffffu, x0, 1); x1 = __shfl_xor_sync(0xffffffffu, x1, 1);
                if (t & 1) { a0 = x0; a2 = x1; } else { a1 = x0; a3 = x1; }
                x0 = (t & 2) ? a0 : a2; x1 = (t & 2) ? a1 : a3;
                x0 = __shfl_xor_sync(0xffffffffu, x0, 2); x1 = __shfl_xor_sync(0xffffffffu, x1, 2);
                if (t & 2) { a0 = x0; a1 = x1; } else { a2 = x0; a3 = x1; }
                uint32_t av[4] = {a0, a1, a2, a3};
                uint32_t xx[4] = {xv[i].x, xv[i].y, xv[i].z, xv[i].w}, bb[4] = {bv[i].x, bv[i].y, bv[i].z, bv[i].w};
                uint32_t ov[4];
#pragma unroll
                for (int e = 0; e < 4; e++) {
                    asm("add.rn.bf16x2 %0, %1, %2;" : "=r"(ov[e]) : "r"(xx[e]), "r"(av[e]));
                    asm("add.rn.bf16x2 %0, %0, %1;" : "+r"(ov[e]) : "r"(bb[e]));
                }
                stg128(P.out + (size_t)row * DM + col + 32 * i, ov[0], ov[1], ov[2], ov[3]);
            }
            PROF_EV(42); PROF_GT(43);
        }
    }
}

typedef CUresult (*EncodeFn)(CUtensorMap*, CUtensorMapDataType, cuuint32_t, void*, const cuuint64_t*, const cuuint64_t*, const cuuint32_t*,
                             const cuuint32_t*, CUtensorMapInterleave, CUtensorMapSwizzle, CUtensorMapL2promotion, CUtensorMapFloatOOBfill);

void make_map2d(EncodeFn enc, CUtensorMap* tm, const void* p, uint64_t cols, uint64_t rows) {
    cuuint64_t gd[2] = {cols, rows}, gs[1] = {cols * 2};
    cuuint32_t box[2] = {64, 128}, es[2] = {1, 1};
    enc(tm, CU_TENSOR_MAP_DATA_TYPE_BFLOAT16, 2, const_cast<void*>(p), gd, gs, box, es, CU_TENSOR_MAP_INTERLEAVE_NONE,
        CU_TENSOR_MAP_SWIZZLE_128B, CU_TENSOR_MAP_L2_PROMOTION_L2_128B, CU_TENSOR_MAP_FLOAT_OOB_FILL_NONE);
}

void make_map3d(EncodeFn enc, CUtensorMap* tm, const void* p, uint64_t cols, uint64_t rows, uint32_t bw, uint32_t nb) {
    cuuint64_t gd[3] = {bw, rows, cols / bw}, gs[2] = {cols * 2, bw * 2};
    cuuint32_t box[3] = {bw, 32, nb}, es[3] = {1, 1, 1};
    enc(tm, CU_TENSOR_MAP_DATA_TYPE_BFLOAT16, 3, const_cast<void*>(p), gd, gs, box, es, CU_TENSOR_MAP_INTERLEAVE_NONE,
        bw == 64 ? CU_TENSOR_MAP_SWIZZLE_128B : CU_TENSOR_MAP_SWIZZLE_64B, CU_TENSOR_MAP_L2_PROMOTION_L2_128B, CU_TENSOR_MAP_FLOAT_OOB_FILL_NONE);
}

}

extern "C" void kernel_launch(void* const* d_in, const int* in_sizes, int n_in, void* d_out, int out_size) {
    (void)in_sizes; (void)n_in; (void)out_size;
    static EncodeFn enc = nullptr;
    if (!enc) {
        void* fn = nullptr;
        cudaDriverEntryPointQueryResult qr;
        cudaGetDriverEntryPoint("cuTensorMapEncodeTiled", &fn, cudaEnableDefault, &qr);
        enc = (EncodeFn)fn;
        cudaFuncSetAttribute(fused_kernel, cudaFuncAttributeMaxDynamicSharedMemorySize, SMEM_BYTES);
    }
    CUtensorMap tmC, tmWk, tmWv, tmWq, tmWo, tmG, tmU, tmD;
    make_map2d(enc, &tmC, d_in[1], DC, SEQ);
    make_map2d(enc, &tmWq, d_in[2], 4096, DM);
    make_map2d(enc, &tmWk, d_in[3], 4096, DC);
    make_map2d(enc, &tmWv, d_in[4], 4096, DC);
    make_map3d(enc, &tmWo, d_in[5], DM, 4096, 32, 5);
    make_map3d(enc, &tmG, d_in[8], FF, DM, 64, 7);
    make_map3d(enc, &tmU, d_in[9], FF, DM, 64, 7);
    make_map3d(enc, &tmD, d_in[10], DM, FF, 64, 10);
    Params P;
    P.x = (const __nv_bfloat16*)d_in[0];
    P.c = (const __nv_bfloat16*)d_in[1];
    P.wq = (const __nv_bfloat16*)d_in[2];
    P.wk = (const __nv_bfloat16*)d_in[3];
    P.wv = (const __nv_bfloat16*)d_in[4];
    P.wo = (const __nv_bfloat16*)d_in[5];
    P.wr = (const __nv_bfloat16*)d_in[7];
    P.out = (__nv_bfloat16*)d_out;
    fused_kernel<<<132, 384, SMEM_BYTES>>>(tmC, tmWk, tmWv, tmWq, tmWo, tmG, tmU, tmD, P);
}
```

```cpp
#include <cuda_runtime.h>
#include <cuda_bf16.h>
#include <cuda.h>
#include <stdint.h>

#define HM 960
#define POLL1 1
#define OP_PF 8
#define PF_START 9
#define LATE_AT 18
#define CDELAY 500
#define AUXDELAY 1000
namespace {

constexpr int SEQ = 2048, NH = 32, DM = 640, DC = 512, FF = 1728, TOPC = 8;
constexpr int NSLOT = 7, SLOT_BYTES = 32768;
constexpr int NST3 = 6, ST3_BYTES = 36864;
constexpr int RING_BYTES = NSLOT * SLOT_BYTES;
constexpr int SMEM_BYTES = RING_BYTES + 3072;

constexpr int BAR_FULL = 96  , BAR_FULL3 = 152  , BAR_DEP = 200  , BAR_SEL = 464,
              BAR_LN = 472  , BAR_EV = 504  , BAR_EMPTY = 760  , BAR_EMPTY3 = 816  ,
              BAR_PROG = 864  , MISC_EPOCH = 896, MISC_SMID = 900  , MISC_SEL = 912, MISC_WR = 1024  ;
constexpr int D_LN = 0  , D_KV = 4  , D_WAR = 14  , D_CTX = 16  ;
constexpr int EV_KV = 0  , EV_CTX = 12  ;

constexpr int FL_MOE_CNT = 0, FL_MOE_DONE = 1, FL_LN = 16  , FL_KV = 32  , FL_CTX = 416  , FL_WAR = 672  , FL_TOTAL = 704;

__device__ __align__(1024) unsigned char g_K[16 * 32 * 16384];
__device__ __align__(1024) unsigned char g_V[16 * 32 * 16384];
__device__ __align__(1024) unsigned char g_ctx[NH * 32 * 16384];
__device__ __align__(1024) unsigned char g_xn[16 * 10 * 16384];
__device__ __align__(1024) uint4 g_part[128 * 10 * 256];
__device__ float g_router[SEQ];
__device__ uint2 g_stats[SEQ];
__device__ __align__(16) float g_moe_part[4 * TOPC * DM];
__device__ __align__(16) __nv_bfloat16 g_brow[TOPC * DM];
__device__ __align__(16) int g_sel[TOPC];
__device__ unsigned g_flags[FL_TOTAL * 8];
__device__ unsigned g_epoch;
__device__ unsigned g_roleq[130];

struct Params {
    const __nv_bfloat16 *x, *c, *wr, *wk, *wv, *wo;
    __nv_bfloat16* out;
};

__device__ __forceinline__ uint32_t smem_u32(const void* p) { return (uint32_t)__cvta_generic_to_shared(p); }
__device__ __forceinline__ void mbar_init(uint32_t bar, int cnt) { asm volatile("mbarrier.init.shared::cta.b64 [%0], %1;" ::"r"(bar), "r"(cnt)); }
__device__ __forceinline__ void mbar_expect_tx(uint32_t bar, uint32_t bytes) {
    asm volatile("mbarrier.arrive.expect_tx.shared::cta.b64 _, [%0], %1;" ::"r"(bar), "r"(bytes) : "memory");
}
__device__ __forceinline__ void mbar_arrive(uint32_t bar) { asm volatile("mbarrier.arrive.shared::cta.b64 _, [%0];" ::"r"(bar) : "memory"); }
__device__ __forceinline__ void mbar_arrive_cluster(uint32_t cluster_addr, uint32_t cnt) {
    asm volatile("mbarrier.arrive.shared::cluster.b64 _, [%0], %1;" ::"r"(cluster_addr), "r"(cnt) : "memory");
}
__device__ __forceinline__ uint32_t mapa(uint32_t addr, uint32_t cta) {
    uint32_t r; asm("mapa.shared::cluster.u32 %0, %1, %2;" : "=r"(r) : "r"(addr), "r"(cta)); return r;
}
__device__ __forceinline__ void mbar_wait(uint32_t bar, uint32_t parity) {
    asm volatile(
        "{\n.reg .pred p;\n.reg .u32 n;\n"
        "mbarrier.try_wait.parity.shared::cta.b64 p, [%0], %1;\n"
        "@p bra DONE;\n"
        "mov.u32 n, 0;\n"
        "LAB_WAIT:\n"
        "mbarrier.try_wait.parity.shared::cta.b64 p, [%0], %1, 100000;\n"
        "@p bra DONE;\n"
        "add.u32 n, n, 1;\n"
        "setp.lt.u32 p, n, 200000;\n"
        "@p bra LAB_WAIT;\n"
        "trap;\n"
        "DONE:\n}\n" ::"r"(bar), "r"(parity) : "memory");
}
__device__ __forceinline__ void mbar_wait_hot(uint32_t bar, uint32_t parity) {
    asm volatile("{\n.reg .pred p;\nLAB_WAIT:\nmbarrier.try_wait.parity.shared::cta.b64 p, [%0], %1;\n@!p bra LAB_WAIT;\n}\n" ::"r"(bar), "r"(parity) : "memory");
}
__device__ __forceinline__ void flag_wait(const unsigned* flag, unsigned target) {
    asm volatile(
        "{\n.reg .pred p;\n.reg .u32 n, v;\n.reg .s32 d;\n"
        "mov.u32 n, 0;\n"
        "LAB_WAIT:\n"
        "ld.acquire.gpu.global.u32 v, [%0];\n"
        "sub.s32 d, v, %1;\n"
        "setp.ge.s32 p, d, 0;\n"
        "@p bra DONE;\n"
        "nanosleep.u32 40;\n"
        "add.u32 n, n, 1;\n"
        "setp.lt.u32 p, n, 3000000;\n"
        "@p bra LAB_WAIT;\n"
        "trap;\n"
        "DONE:\n}\n" ::"l"(flag), "r"(target) : "memory");
}
__device__ __forceinline__ void flag_signal(unsigned* flag) {
    asm volatile("red.release.gpu.global.add.u32 [%0], 1;" ::"l"(flag) : "memory");
}
__device__ __forceinline__ void fence_async_global() { asm volatile("fence.proxy.async.global;" ::: "memory"); }
__device__ __forceinline__ unsigned* flag_ptr(int idx) { return g_flags + idx * 8; }

__device__ __forceinline__ uint64_t policy_stream() {
    uint64_t p; asm("createpolicy.fractional.L2::evict_first.b64 %0, 1.0;" : "=l"(p)); return p;
}
__device__ __forceinline__ uint64_t policy_normal() { return 0x1000000000000000ull; }
__device__ __forceinline__ uint64_t policy(bool stream) { return stream ? policy_stream() : policy_normal(); }
__device__ __forceinline__ void bulk_load(uint32_t dst, const void* src, uint32_t bytes, uint32_t bar, uint64_t pol) {
    asm volatile("cp.async.bulk.shared::cluster.global.mbarrier::complete_tx::bytes.L2::cache_hint [%0], [%1], %2, [%3], %4;"
                 ::"r"(dst), "l"(src), "r"(bytes), "r"(bar), "l"(pol) : "memory");
}
__device__ __forceinline__ void bulk_load_mc(uint32_t dst, const void* src, uint32_t bytes, uint32_t bar, uint64_t pol) {
    asm volatile("cp.async.bulk.shared::cluster.global.mbarrier::complete_tx::bytes.multicast::cluster.L2::cache_hint [%0], [%1], %2, [%3], %4, %5;"
                 ::"r"(dst), "l"(src), "r"(bytes), "r"(bar), "h"((uint16_t)3), "l"(pol) : "memory");
}
__device__ __forceinline__ void tma2d(uint32_t dst, const CUtensorMap* tm, int c0, int c1, uint32_t bar, uint64_t pol) {
    asm volatile("cp.async.bulk.tensor.2d.shared::cluster.global.mbarrier::complete_tx::bytes.L2::cache_hint [%0], [%1, {%3, %4}], [%2], %5;"
                 ::"r"(dst), "l"(tm), "r"(bar), "r"(c0), "r"(c1), "l"(pol) : "memory");
}
__device__ __forceinline__ void tma2d_mc(uint32_t dst, const CUtensorMap* tm, int c0, int c1, uint32_t bar, uint64_t pol) {
    asm volatile("cp.async.bulk.tensor.2d.shared::cluster.global.mbarrier::complete_tx::bytes.multicast::cluster.L2::cache_hint [%0], [%1, {%3, %4}], [%2], %5, %6;"
                 ::"r"(dst), "l"(tm), "r"(bar), "r"(c0), "r"(c1), "h"((uint16_t)3), "l"(pol) : "memory");
}
__device__ __forceinline__ void tma3d_mc(uint32_t dst, const CUtensorMap* tm, int c0, int c1, int c2, uint32_t bar, uint64_t pol) {
    asm volatile("cp.async.bulk.tensor.3d.shared::cluster.global.mbarrier::complete_tx::bytes.multicast::cluster.L2::cache_hint [%0], [%1, {%3, %4, %5}], [%2], %6, %7;"
                 ::"r"(dst), "l"(tm), "r"(bar), "r"(c0), "r"(c1), "r"(c2), "h"((uint16_t)3), "l"(pol) : "memory");
}
__device__ __forceinline__ void tma3d(uint32_t dst, const CUtensorMap* tm, int c0, int c1, int c2, uint32_t bar) {
    asm volatile("cp.async.bulk.tensor.3d.shared::cluster.global.mbarrier::complete_tx::bytes.L2::cache_hint [%0], [%1, {%3, %4, %5}], [%2], %6;"
                 ::"r"(dst), "l"(tm), "r"(bar), "r"(c0), "r"(c1), "r"(c2), "l"(policy_stream()) : "memory");
}
__device__ __forceinline__ void tma2d_prefetch(const CUtensorMap* tm, int c0, int c1) {
    asm volatile("cp.async.bulk.prefetch.tensor.2d.L2.global [%0, {%1, %2}];" ::"l"(tm), "r"(c0), "r"(c1) : "memory");
}
__device__ __forceinline__ void tma3d_prefetch(const CUtensorMap* tm, int c0, int c1, int c2) {
    asm volatile("cp.async.bulk.prefetch.tensor.3d.L2.global [%0, {%1, %2, %3}];" ::"l"(tm), "r"(c0), "r"(c1), "r"(c2) : "memory");
}
__device__ __forceinline__ void l2_prefetch(const void* p, uint32_t bytes) {
    asm volatile("cp.async.bulk.prefetch.L2.global [%0], %1;" ::"l"(p), "r"(bytes) : "memory");
}
__device__ __forceinline__ bool elect_one() {
    uint32_t r; asm volatile("{\n.reg .pred p;\nelect.sync _|p, 0xffffffff;\nselp.u32 %0, 1, 0, p;\n}\n" : "=r"(r)); return r != 0;
}
__device__ __forceinline__ void wg_fence() { asm volatile("wgmma.fence.sync.aligned;" ::: "memory"); }
__device__ __forceinline__ void wg_commit() { asm volatile("wgmma.commit_group.sync.aligned;" ::: "memory"); }
template <int N> __device__ __forceinline__ void wg_wait() { asm volatile("wgmma.wait_group.sync.aligned %0;" ::"n"(N) : "memory"); }
__device__ __forceinline__ void bar_sync(int id, int n) { asm volatile("bar.sync %0, %1;" ::"r"(id), "r"(n) : "memory"); }
__device__ __forceinline__ void bar_arrive(int id, int n) { asm volatile("bar.arrive %0, %1;" ::"r"(id), "r"(n) : "memory"); }
__device__ __forceinline__ void token_wait(int w) {
    asm volatile("{\n.reg .pred p;\nsetp.eq.u32 p, %0, 0;\n@p bar.sync 1, 256;\n@!p bar.sync 2, 256;\n}\n" ::"r"(w) : "memory");
}
__device__ __forceinline__ void token_pass(int w) {
    asm volatile("{\n.reg .pred p;\nsetp.eq.u32 p, %0, 0;\n@p bar.arrive 2, 256;\n@!p bar.arrive 1, 256;\n}\n" ::"r"(w) : "memory");
}
template <int N> __device__ __forceinline__ void fence_regs(float (&a)[N]) {
#pragma unroll
    for (int i = 0; i < N; i++) asm volatile("" : "+f"(a[i])::"memory");
}
template <int N> __device__ __forceinline__ void undef_regs(float (&a)[N]) {
#pragma unroll
    for (int i = 0; i < N; i++) asm volatile("" : "=f"(a[i]));
}
__device__ __forceinline__ void ldsm4t(uint32_t& r0, uint32_t& r1, uint32_t& r2, uint32_t& r3, uint32_t addr) {
    asm volatile("ldmatrix.sync.aligned.m8n8.x4.trans.shared.b16 {%0,%1,%2,%3}, [%4];"
                 : "=r"(r0), "=r"(r1), "=r"(r2), "=r"(r3) : "r"(addr) : "memory");
}
__device__ __forceinline__ uint32_t pack_bf16(float lo, float hi) {
    uint32_t r; asm("cvt.rn.bf16x2.f32 %0, %1, %2;" : "=r"(r) : "f"(hi), "f"(lo)); return r;
}
__device__ __forceinline__ float bf_lo(uint32_t v) { return __uint_as_float(v << 16); }
__device__ __forceinline__ float bf_hi(uint32_t v) { return __uint_as_float(v & 0xffff0000u); }
__device__ __forceinline__ float bf_round(float v) { return __bfloat162float(__float2bfloat16_rn(v)); }
__device__ __forceinline__ float ex2(float v) { float r; asm("ex2.approx.ftz.f32 %0, %1;" : "=f"(r) : "f"(v)); return r; }
__device__ __forceinline__ void ex2v(float& v) { asm volatile("ex2.approx.ftz.f32 %0, %0;" : "+f"(v)); }
__device__ __forceinline__ float rcp_fast(float v) { float r; asm("rcp.approx.ftz.f32 %0, %1;" : "=f"(r) : "f"(v)); return r; }
__device__ __forceinline__ float sqrt_fast(float v) { float r; asm("sqrt.approx.ftz.f32 %0, %1;" : "=f"(r) : "f"(v)); return r; }
__device__ __forceinline__ void stg128(void* p, uint32_t a, uint32_t b, uint32_t c, uint32_t d) {
    asm volatile("st.global.v4.b32 [%0], {%1,%2,%3,%4};" ::"l"(p), "r"(a), "r"(b), "r"(c), "r"(d) : "memory");
}
__device__ __forceinline__ void stg128_hint(void* p, uint32_t a, uint32_t b, uint32_t c, uint32_t d, uint64_t pol) {
    asm volatile("st.global.L2::cache_hint.v4.b32 [%0], {%1,%2,%3,%4}, %5;" ::"l"(p), "r"(a), "r"(b), "r"(c), "r"(d), "l"(pol) : "memory");
}
__device__ __forceinline__ uint4 ldg128(const void* p) {
    uint4 v; asm volatile("ld.global.cg.v4.b32 {%0,%1,%2,%3}, [%4];" : "=r"(v.x), "=r"(v.y), "=r"(v.z), "=r"(v.w) : "l"(p) : "memory"); return v;
}
__device__ __forceinline__ uint64_t mkdesc(uint32_t addr, uint32_t lbo, uint32_t sbo, uint32_t swz) {
    uint32_t lo = ((addr & 0x3FFFF) >> 4) | ((lbo >> 4) << 16);
    uint32_t hi = (sbo >> 4) | (swz << 30);
    return ((uint64_t)hi << 32) | lo;
}
__device__ __forceinline__ int perm32(int v) { return (v & ~30) | ((v >> 2) & 6) | ((v << 2) & 24); }

__device__ __forceinline__ void wgmma_rs_n128_ta0_tb0(float (&d)[64], uint32_t a0, uint32_t a1, uint32_t a2, uint32_t a3, uint64_t descB, int scaleD) {
  asm volatile("{\n.reg .pred p;\nsetp.ne.b32 p, %69, 0;\n"
    "wgmma.mma_async.sync.aligned.m64n128k16.f32.bf16.bf16 "
    "{%0, %1, %2, %3, %4, %5, %6, %7, %8, %9, %10, %11, %12, %13, %14, %15, %16, %17, %18, %19, %20, %21, %22, %23, %24, %25, %26, %27, %28, %29, %30, %31, %32, %33, %34, %35, %36, %37, %38, %39, %40, %41, %42, %43, %44, %45, %46, %47, %48, %49, %50, %51, %52, %53, %54, %55, %56, %57, %58, %59, %60, %61, %62, %63}, "
    "{%64, %65, %66, %67}, %68, p, 1, 1, 0;\n}\n"
    : "+f"(d[0]), "+f"(d[1]), "+f"(d[2]), "+f"(d[3]), "+f"(d[4]), "+f"(d[5]), "+f"(d[6]), "+f"(d[7]), "+f"(d[8]), "+f"(d[9]), "+f"(d[10]), "+f"(d[11]), "+f"(d[12]), "+f"(d[13]), "+f"(d[14]), "+f"(d[15]), "+f"(d[16]), "+f"(d[17]), "+f"(d[18]), "+f"(d[19]), "+f"(d[20]), "+f"(d[21]), "+f"(d[22]), "+f"(d[23]), "+f"(d[24]), "+f"(d[25]), "+f"(d[26]), "+f"(d[27]), "+f"(d[28]), "+f"(d[29]), "+f"(d[30]), "+f"(d[31]), "+f"(d[32]), "+f"(d[33]), "+f"(d[34]), "+f"(d[35]), "+f"(d[36]), "+f"(d[37]), "+f"(d[38]), "+f"(d[39]), "+f"(d[40]), "+f"(d[41]), "+f"(d[42]), "+f"(d[43]), "+f"(d[44]), "+f"(d[45]), "+f"(d[46]), "+f"(d[47]), "+f"(d[48]), "+f"(d[49]), "+f"(d[50]), "+f"(d[51]), "+f"(d[52]), "+f"(d[53]), "+f"(d[54]), "+f"(d[55]), "+f"(d[56]), "+f"(d[57]), "+f"(d[58]), "+f"(d[59]), "+f"(d[60]), "+f"(d[61]), "+f"(d[62]), "+f"(d[63])
    : "r"(a0), "r"(a1), "r"(a2), "r"(a3), "l"(descB), "r"(scaleD));
}
__device__ __forceinline__ void wgmma_rs_n128_ta0_tb1(float (&d)[64], uint32_t a0, uint32_t a1, uint32_t a2, uint32_t a3, uint64_t descB, int scaleD) {
  asm volatile("{\n.reg .pred p;\nsetp.ne.b32 p, %69, 0;\n"
    "wgmma.mma_async.sync.aligned.m64n128k16.f32.bf16.bf16 "
    "{%0, %1, %2, %3, %4, %5, %6, %7, %8, %9, %10, %11, %12, %13, %14, %15, %16, %17, %18, %19, %20, %21, %22, %23, %24, %25, %26, %27, %28, %29, %30, %31, %32, %33, %34, %35, %36, %37, %38, %39, %40, %41, %42, %43, %44, %45, %46, %47, %48, %49, %50, %51, %52, %53, %54, %55, %56, %57, %58, %59, %60, %61, %62, %63}, "
    "{%64, %65, %66, %67}, %68, p, 1, 1, 1;\n}\n"
    : "+f"(d[0]), "+f"(d[1]), "+f"(d[2]), "+f"(d[3]), "+f"(d[4]), "+f"(d[5]), "+f"(d[6]), "+f"(d[7]), "+f"(d[8]), "+f"(d[9]), "+f"(d[10]), "+f"(d[11]), "+f"(d[12]), "+f"(d[13]), "+f"(d[14]), "+f"(d[15]), "+f"(d[16]), "+f"(d[17]), "+f"(d[18]), "+f"(d[19]), "+f"(d[20]), "+f"(d[21]), "+f"(d[22]), "+f"(d[23]), "+f"(d[24]), "+f"(d[25]), "+f"(d[26]), "+f"(d[27]), "+f"(d[28]), "+f"(d[29]), "+f"(d[30]), "+f"(d[31]), "+f"(d[32]), "+f"(d[33]), "+f"(d[34]), "+f"(d[35]), "+f"(d[36]), "+f"(d[37]), "+f"(d[38]), "+f"(d[39]), "+f"(d[40]), "+f"(d[41]), "+f"(d[42]), "+f"(d[43]), "+f"(d[44]), "+f"(d[45]), "+f"(d[46]), "+f"(d[47]), "+f"(d[48]), "+f"(d[49]), "+f"(d[50]), "+f"(d[51]), "+f"(d[52]), "+f"(d[53]), "+f"(d[54]), "+f"(d[55]), "+f"(d[56]), "+f"(d[57]), "+f"(d[58]), "+f"(d[59]), "+f"(d[60]), "+f"(d[61]), "+f"(d[62]), "+f"(d[63])
    : "r"(a0), "r"(a1), "r"(a2), "r"(a3), "l"(descB), "r"(scaleD));
}
__device__ __forceinline__ void wgmma_rs_n64_ta0_tb1(float (&d)[32], uint32_t a0, uint32_t a1, uint32_t a2, uint32_t a3, uint64_t descB, int scaleD) {
  asm volatile("{\n.reg .pred p;\nsetp.ne.b32 p, %37, 0;\n"
    "wgmma.mma_async.sync.aligned.m64n64k16.f32.bf16.bf16 "
    "{%0, %1, %2, %3, %4, %5, %6, %7, %8, %9, %10, %11, %12, %13, %14, %15, %16, %17, %18, %19, %20, %21, %22, %23, %24, %25, %26, %27, %28, %29, %30, %31}, "
    "{%32, %33, %34, %35}, %36, p, 1, 1, 1;\n}\n"
    : "+f"(d[0]), "+f"(d[1]), "+f"(d[2]), "+f"(d[3]), "+f"(d[4]), "+f"(d[5]), "+f"(d[6]), "+f"(d[7]), "+f"(d[8]), "+f"(d[9]), "+f"(d[10]), "+f"(d[11]), "+f"(d[12]), "+f"(d[13]), "+f"(d[14]), "+f"(d[15]), "+f"(d[16]), "+f"(d[17]), "+f"(d[18]), "+f"(d[19]), "+f"(d[20]), "+f"(d[21]), "+f"(d[22]), "+f"(d[23]), "+f"(d[24]), "+f"(d[25]), "+f"(d[26]), "+f"(d[27]), "+f"(d[28]), "+f"(d[29]), "+f"(d[30]), "+f"(d[31])
    : "r"(a0), "r"(a1), "r"(a2), "r"(a3), "l"(descB), "r"(scaleD));
}
__device__ __forceinline__ void wgmma_ss_n128_ta0_tb1(float (&d)[64], uint64_t descA, uint64_t descB, int scaleD) {
  asm volatile("{\n.reg .pred p;\nsetp.ne.b32 p, %66, 0;\n"
    "wgmma.mma_async.sync.aligned.m64n128k16.f32.bf16.bf16 "
    "{%0, %1, %2, %3, %4, %5, %6, %7, %8, %9, %10, %11, %12, %13, %14, %15, %16, %17, %18, %19, %20, %21, %22, %23, %24, %25, %26, %27, %28, %29, %30, %31, %32, %33, %34, %35, %36, %37, %38, %39, %40, %41, %42, %43, %44, %45, %46, %47, %48, %49, %50, %51, %52, %53, %54, %55, %56, %57, %58, %59, %60, %61, %62, %63}, "
    "%64, %65, p, 1, 1, 0, 1;\n}\n"
    : "+f"(d[0]), "+f"(d[1]), "+f"(d[2]), "+f"(d[3]), "+f"(d[4]), "+f"(d[5]), "+f"(d[6]), "+f"(d[7]), "+f"(d[8]), "+f"(d[9]), "+f"(d[10]), "+f"(d[11]), "+f"(d[12]), "+f"(d[13]), "+f"(d[14]), "+f"(d[15]), "+f"(d[16]), "+f"(d[17]), "+f"(d[18]), "+f"(d[19]), "+f"(d[20]), "+f"(d[21]), "+f"(d[22]), "+f"(d[23]), "+f"(d[24]), "+f"(d[25]), "+f"(d[26]), "+f"(d[27]), "+f"(d[28]), "+f"(d[29]), "+f"(d[30]), "+f"(d[31]), "+f"(d[32]), "+f"(d[33]), "+f"(d[34]), "+f"(d[35]), "+f"(d[36]), "+f"(d[37]), "+f"(d[38]), "+f"(d[39]), "+f"(d[40]), "+f"(d[41]), "+f"(d[42]), "+f"(d[43]), "+f"(d[44]), "+f"(d[45]), "+f"(d[46]), "+f"(d[47]), "+f"(d[48]), "+f"(d[49]), "+f"(d[50]), "+f"(d[51]), "+f"(d[52]), "+f"(d[53]), "+f"(d[54]), "+f"(d[55]), "+f"(d[56]), "+f"(d[57]), "+f"(d[58]), "+f"(d[59]), "+f"(d[60]), "+f"(d[61]), "+f"(d[62]), "+f"(d[63])
    : "l"(descA), "l"(descB), "r"(scaleD));
}
__device__ __forceinline__ void wgmma_ss_n160_ta0_tb1(float (&d)[80], uint64_t descA, uint64_t descB, int scaleD) {
  asm volatile("{\n.reg .pred p;\nsetp.ne.b32 p, %82, 0;\n"
    "wgmma.mma_async.sync.aligned.m64n160k16.f32.bf16.bf16 "
    "{%0, %1, %2, %3, %4, %5, %6, %7, %8, %9, %10, %11, %12, %13, %14, %15, %16, %17, %18, %19, %20, %21, %22, %23, %24, %25, %26, %27, %28, %29, %30, %31, %32, %33, %34, %35, %36, %37, %38, %39, %40, %41, %42, %43, %44, %45, %46, %47, %48, %49, %50, %51, %52, %53, %54, %55, %56, %57, %58, %59, %60, %61, %62, %63, %64, %65, %66, %67, %68, %69, %70, %71, %72, %73, %74, %75, %76, %77, %78, %79}, "
    "%80, %81, p, 1, 1, 0, 1;\n}\n"
    : "+f"(d[0]), "+f"(d[1]), "+f"(d[2]), "+f"(d[3]), "+f"(d[4]), "+f"(d[5]), "+f"(d[6]), "+f"(d[7]), "+f"(d[8]), "+f"(d[9]), "+f"(d[10]), "+f"(d[11]), "+f"(d[12]), "+f"(d[13]), "+f"(d[14]), "+f"(d[15]), "+f"(d[16]), "+f"(d[17]), "+f"(d[18]), "+f"(d[19]), "+f"(d[20]), "+f"(d[21]), "+f"(d[22]), "+f"(d[23]), "+f"(d[24]), "+f"(d[25]), "+f"(d[26]), "+f"(d[27]), "+f"(d[28]), "+f"(d[29]), "+f"(d[30]), "+f"(d[31]), "+f"(d[32]), "+f"(d[33]), "+f"(d[34]), "+f"(d[35]), "+f"(d[36]), "+f"(d[37]), "+f"(d[38]), "+f"(d[39]), "+f"(d[40]), "+f"(d[41]), "+f"(d[42]), "+f"(d[43]), "+f"(d[44]), "+f"(d[45]), "+f"(d[46]), "+f"(d[47]), "+f"(d[48]), "+f"(d[49]), "+f"(d[50]), "+f"(d[51]), "+f"(d[52]), "+f"(d[53]), "+f"(d[54]), "+f"(d[55]), "+f"(d[56]), "+f"(d[57]), "+f"(d[58]), "+f"(d[59]), "+f"(d[60]), "+f"(d[61]), "+f"(d[62]), "+f"(d[63]), "+f"(d[64]), "+f"(d[65]), "+f"(d[66]), "+f"(d[67]), "+f"(d[68]), "+f"(d[69]), "+f"(d[70]), "+f"(d[71]), "+f"(d[72]), "+f"(d[73]), "+f"(d[74]), "+f"(d[75]), "+f"(d[76]), "+f"(d[77]), "+f"(d[78]), "+f"(d[79])
    : "l"(descA), "l"(descB), "r"(scaleD));
}

#define PROF_DECL(b)
#define PROF_EV(tag)
#define PROF_GT(tag)

template <int N> struct IC { static constexpr int value = N; };
struct Cur {
    uint32_t slot, ph;
    __device__ __forceinline__ void adv() { if (++slot == NSLOT) { slot = 0; ph ^= 1; } }
};
constexpr int E0 = 2;
__host__ __device__ constexpr uint32_t slot_of(int e) { return (e + E0) % NSLOT; }
__device__ __forceinline__ Cur cur_at(int e) { Cur c; c.slot = (e + E0) % NSLOT; c.ph = ((e + E0) / NSLOT) & 1; return c; }

__device__ __forceinline__ int op_head(int i, int kap) { return 16 * kap + 2 * (i & 7) + (i >> 3); }

constexpr float SM_SCALE = 0.08838834764831845f * 1.4426950408889634f;

struct Ctx {
    uint32_t ring, misc;
    uint32_t rel;
    int w, warp, lane;
};
__device__ __forceinline__ void release(const Ctx& c, uint32_t off, uint32_t cnt) {
    if (c.lane < 2) mbar_arrive_cluster(c.rel + off, cnt);
}
__device__ __forceinline__ void signal_event(const Ctx& c, int ev) {
    __syncwarp();
    if (c.lane == 0) mbar_arrive(c.misc + BAR_EV + (c.w * 16 + ev) * 8);
}
template <int NK, int OFF, int N>
__device__ __forceinline__ uint32_t load_afrag(uint32_t (&a)[N], uint32_t base, const Ctx& c) {
    int r = c.lane & 7, mat = c.lane >> 3;
    uint32_t addr = base + (8 * (mat >> 1) + r) * 128 + (((2 * c.warp + (mat & 1)) ^ r) << 4);
#pragma unroll
    for (int k = 0; k < NK; k++) ldsm4t(a[OFF + 4 * k], a[OFF + 4 * k + 1], a[OFF + 4 * k + 2], a[OFF + 4 * k + 3], addr + k * 2048);
    uint32_t dep = 0;
#pragma unroll
    for (int k = 0; k < NK; k++) dep |= a[OFF + 4 * k];
    return dep & blockIdx.y;
}
__device__ __forceinline__ void store_proj(const float (&acc)[64], unsigned char* dst  , int perm, const Ctx& c) {
    int g = c.lane >> 2, t = c.lane & 3;
#pragma unroll
    for (int i = 0; i < 2; i++) {
        int row = 64 * c.w + 16 * c.warp + 8 * i + g;
        if (perm) row = perm32(row);
        unsigned char* p = dst + row * 128;
#pragma unroll
        for (int q = 0; q < 4; q++) {
            int chunk = (4 * (q & 1) + t) ^ (row & 7);
            stg128(p + (q >> 1) * 16384 + chunk * 16,
                   pack_bf16(acc[16 * q + 2 * i], acc[16 * q + 2 * i + 1]), pack_bf16(acc[16 * q + 4 + 2 * i], acc[16 * q + 4 + 2 * i + 1]),
                   pack_bf16(acc[16 * q + 8 + 2 * i], acc[16 * q + 8 + 2 * i + 1]), pack_bf16(acc[16 * q + 12 + 2 * i], acc[16 * q + 12 + 2 * i + 1]));
        }
    }
}

constexpr float SAFE_SUM = 1099511627776.0f;
template <int NJ>
__device__ __forceinline__ void row_max(const float (&s)[4 * NJ], float (&mx)[2]) {
#pragma unroll
    for (int i = 0; i < 2; i++) {
        float a = fmaxf(s[2 * i], s[2 * i + 1]), b = fmaxf(s[4 + 2 * i], s[4 + 2 * i + 1]);
#pragma unroll
        for (int j = 2; j < NJ; j += 2) {
            a = fmaxf(a, fmaxf(s[4 * j + 2 * i], s[4 * j + 2 * i + 1]));
            b = fmaxf(b, fmaxf(s[4 * j + 4 + 2 * i], s[4 * j + 4 + 2 * i + 1]));
        }
        a = fmaxf(a, b);
        a = fmaxf(a, __shfl_xor_sync(0xffffffffu, a, 1));
        mx[i] = fmaxf(a, __shfl_xor_sync(0xffffffffu, a, 2));
    }
}
template <int NJ, bool SHIFT>
__device__ __forceinline__ void exp_sum(float (&s)[4 * NJ], const float (&m)[2], float& l0, float& l1) {
#pragma unroll
    for (int j = 0; j < NJ; j++) {
#pragma unroll
        for (int e = 0; e < 4; e++) s[4 * j + e] = ex2(SHIFT ? s[4 * j + e] - m[e >> 1] : s[4 * j + e]);
        l0 += s[4 * j + 0] + s[4 * j + 1]; l1 += s[4 * j + 2] + s[4 * j + 3];
    }
}
__device__ __forceinline__ void recompute_scores(float (&s)[64], const uint32_t (&q)[32], uint32_t kaddr, const Ctx& c) {
    const int r = c.lane & 7, mat = c.lane >> 3;
    const uint32_t a0 = kaddr + (8 * (mat & 1) + r) * 128 + (((mat >> 1) ^ r) << 4);
#pragma unroll
    for (int i = 0; i < 64; i++) s[i] = 0.f;
#pragma unroll
    for (int jp = 0; jp < 8; jp++) {
#pragma unroll
        for (int k = 0; k < 8; k++) {
            asm volatile(
                "{\n.reg .b32 b0, b1, b2, b3;\n"
                "ldmatrix.sync.aligned.m8n8.x4.trans.shared.b16 {b0,b1,b2,b3}, [%12];\n"
                "mma.sync.aligned.m16n8k16.row.col.f32.bf16.bf16.f32 {%0,%1,%2,%3}, {%8,%9,%10,%11}, {b0,b1}, {%0,%1,%2,%3};\n"
                "mma.sync.aligned.m16n8k16.row.col.f32.bf16.bf16.f32 {%4,%5,%6,%7}, {%8,%9,%10,%11}, {b2,b3}, {%4,%5,%6,%7};\n}\n"
                : "+f"(s[8 * jp]), "+f"(s[8 * jp + 1]), "+f"(s[8 * jp + 2]), "+f"(s[8 * jp + 3]),
                  "+f"(s[8 * jp + 4]), "+f"(s[8 * jp + 5]), "+f"(s[8 * jp + 6]), "+f"(s[8 * jp + 7])
                : "r"(q[4 * k]), "r"(q[4 * k + 1]), "r"(q[4 * k + 2]), "r"(q[4 * k + 3]),
                  "r"((a0 ^ ((jp & 3) << 5)) + (jp >> 2) * 16384 + k * 2048) : "memory");
        }
    }
}
__device__ __forceinline__ int mask_lim(const Ctx& c) { return perm32(16 * c.warp + (c.lane >> 2)) - 8 * (c.lane & 3); }
template <int J0>
__device__ __forceinline__ void mask_diag(float (&s)[4 * J0 + 32], const Ctx& c) {
    const int lim = mask_lim(c);
    if (c.warp < 2) {
#pragma unroll
        for (int x = 0; x < 16; x++) {
            if (2 * (x >> 2) + (x & 1) - (x & 2) > lim) s[4 * J0 + x] = -INFINITY;
            s[4 * J0 + 16 + x] = -INFINITY;
        }
    } else {
#pragma unroll
        for (int x = 0; x < 16; x++)
            if (32 + 2 * (x >> 2) + (x & 1) - (x & 2) > lim) s[4 * J0 + 16 + x] = -INFINITY;
    }
}
__device__ __forceinline__ void mask_any(float (&s)[64], int hh, const Ctx& c) {
    const int lim = mask_lim(c) + 64 * hh;
#pragma unroll
    for (int x = 0; x < 64; x++)
        if (32 * (x >> 4) + 2 * ((x >> 2) & 3) + (x & 1) - (x & 2) > lim) s[x] = -INFINITY;
}
__device__ __forceinline__ void issue_pv(float (&o)[64], const uint32_t (&p)[32], uint32_t vaddr, int acc, int mode  ) {
    uint64_t d = mkdesc(vaddr, 16, 1024, 1);
    if (mode == 0) {
        wg_fence();
#pragma unroll
        for (int k = 0; k < 8; k++)
            wgmma_rs_n128_ta0_tb0(o, p[4 * k], p[4 * k + 1], p[4 * k + 2], p[4 * k + 3], d + (k >> 2) * 1024 + 2 * (k & 3), k ? 1 : acc);
        wg_commit();
    } else if (mode == 1) {
        wg_fence();
#pragma unroll
        for (int k = 0; k < 4; k++) wgmma_rs_n128_ta0_tb0(o, p[4 * k], p[4 * k + 1], p[4 * k + 2], p[4 * k + 3], d + 2 * k, k != 0);
        wg_commit();
    } else {
        wg_fence();
        wgmma_rs_n128_ta0_tb0(o, p[0], p[1], p[2], p[3], d, 0);
        wg_commit();
    }
}
__device__ __forceinline__ void issue_qk(float (&s)[64], const uint32_t (&q)[32], uint32_t kaddr) {
    uint64_t d = mkdesc(kaddr, 16384, 1024, 1);
    wg_fence();
#pragma unroll
    for (int k = 0; k < 8; k++) wgmma_rs_n128_ta0_tb1(s, q[4 * k], q[4 * k + 1], q[4 * k + 2], q[4 * k + 3], d + 128 * k, k != 0);
    wg_commit();
}
__device__ __forceinline__ void issue_qk_half(float (&s32)[32], const uint32_t (&q)[32], uint32_t kaddr) {
    uint64_t d = mkdesc(kaddr, 16384, 1024, 1);
    wg_fence();
#pragma unroll
    for (int k = 0; k < 8; k++) wgmma_rs_n64_ta0_tb1(s32, q[4 * k], q[4 * k + 1], q[4 * k + 2], q[4 * k + 3], d + 128 * k, k != 0);
    wg_commit();
}
__device__ __forceinline__ void row_inv(const float (&l)[2], float (&inv)[2]) {
#pragma unroll
    for (int i = 0; i < 2; i++) {
        float sum = l[i];
        sum += __shfl_xor_sync(0xffffffffu, sum, 1);
        sum += __shfl_xor_sync(0xffffffffu, sum, 2);
        inv[i] = rcp_fast(sum);
    }
}
__device__ __forceinline__ void store_ctx(const float (&o)[64], const float (&inv)[2], unsigned char* dst, uint64_t pol, const Ctx& c) {
    const int g = c.lane >> 2, t = c.lane & 3;
    unsigned char* p0 = dst + (16 * c.warp + g) * 128 + ((t ^ g) << 4);
    unsigned char* p1 = dst + (16 * c.warp + g) * 128 + (((4 + t) ^ g) << 4);
#pragma unroll
    for (int i = 0; i < 2; i++)
#pragma unroll
        for (int q = 0; q < 4; q++)
            stg128_hint(((q & 1) ? p1 : p0) + (q >> 1) * 8192 + i * 1024,
                        pack_bf16(o[16 * q + 2 * i] * inv[i], o[16 * q + 2 * i + 1] * inv[i]),
                        pack_bf16(o[16 * q + 4 + 2 * i] * inv[i], o[16 * q + 4 + 2 * i + 1] * inv[i]),
                        pack_bf16(o[16 * q + 8 + 2 * i] * inv[i], o[16 * q + 8 + 2 * i + 1] * inv[i]),
                        pack_bf16(o[16 * q + 12 + 2 * i] * inv[i], o[16 * q + 12 + 2 * i + 1] * inv[i]), pol);
}

__device__ __forceinline__ const unsigned char* xn_addr(int row, int col) {
    row = perm32(row);
    return g_xn + ((row >> 7) * 10 + (col >> 6)) * 16384 + (row & 127) * 128 + ((((col & 63) >> 3) ^ (row & 7)) << 4);
}
__device__ __forceinline__ void mma16816(float (&d)[4], uint32_t a0, uint32_t a1, uint32_t a2, uint32_t a3, uint32_t b0, uint32_t b1) {
    asm volatile("mma.sync.aligned.m16n8k16.row.col.f32.bf16.bf16.f32 {%0,%1,%2,%3}, {%4,%5,%6,%7}, {%8,%9}, {%0,%1,%2,%3};"
                 : "+f"(d[0]), "+f"(d[1]), "+f"(d[2]), "+f"(d[3]) : "r"(a0), "r"(a1), "r"(a2), "r"(a3), "r"(b0), "r"(b1));
}
__device__ __forceinline__ uint32_t lds32(uint32_t addr) { uint32_t v; asm volatile("ld.shared.u32 %0, [%1];" : "=r"(v) : "r"(addr)); return v; }

__device__ __forceinline__ void ln_rows(const Params& P, int row0, int lane, uint32_t wr_s) {
    const int hl = lane & 15, row = row0 + (lane >> 4);
    uint32_t v[20];
#pragma unroll
    for (int i = 0; i < 5; i++) {
        uint4 u;
        asm("ld.global.nc.L2::cache_hint.v4.b32 {%0,%1,%2,%3}, [%4], %5;" : "=r"(u.x), "=r"(u.y), "=r"(u.z), "=r"(u.w)
            : "l"(P.x + (size_t)row * DM + 128 * i + 8 * hl), "l"(policy(HM & 512)));
        v[4 * i] = u.x; v[4 * i + 1] = u.y; v[4 * i + 2] = u.z; v[4 * i + 3] = u.w;
    }
    float mean = 0.f, m2 = 0.f, acc2 = 0.f;
#pragma unroll
    for (int i = 0; i < 20; i++) { mean += bf_lo(v[i]); acc2 += bf_hi(v[i]); }
    mean = (mean + acc2) * (1.0f / 40);
    acc2 = 0.f;
#pragma unroll
    for (int i = 0; i < 20; i++) {
        float d0 = __uint_as_float(__byte_perm(v[i], 0, 0x1044)) - mean, d1 = __uint_as_float(__byte_perm(v[i], 0, 0x3244)) - mean;
        m2 = fmaf(d0, d0, m2); acc2 = fmaf(d1, d1, acc2);
    }
    m2 += acc2;
    acc2 = 0.f;
#pragma unroll
    for (int o = 1; o < 16; o <<= 1) {
        float mo = __shfl_xor_sync(0xffffffffu, mean, o), qo = __shfl_xor_sync(0xffffffffu, m2, o), d = mo - mean;
        m2 = fmaf(d * d, 20.0f * o, m2 + qo);
        mean = 0.5f * (mean + mo);
    }
    const uint32_t mb2 = pack_bf16(mean, mean);
    const float inv = rcp_fast(bf_round(sqrt_fast(bf_round(bf_round(m2 * (1.0f / DM)) + 1e-5f))));
    float dot = 0.f;
    unsigned char* xp = const_cast<unsigned char*>(xn_addr(row, 8 * hl));
#pragma unroll
    for (int i = 0; i < 5; i++) {
        uint32_t ww[4];
        asm volatile("ld.shared.v4.b32 {%0,%1,%2,%3}, [%4];" : "=r"(ww[0]), "=r"(ww[1]), "=r"(ww[2]), "=r"(ww[3]) : "r"(wr_s + 256 * i + 16 * hl) : "memory");
#pragma unroll
        for (int e = 0; e < 4; e++) {
            uint32_t d;
            asm("sub.rn.bf16x2 %0, %1, %2;" : "=r"(d) : "r"(v[4 * i + e]), "r"(mb2));
            d = pack_bf16(bf_lo(d) * inv, bf_hi(d) * inv);
            v[4 * i + e] = d;
            dot = fmaf(bf_lo(d), bf_lo(ww[e]), dot);
            acc2 = fmaf(bf_hi(d), bf_hi(ww[e]), acc2);
        }
        stg128(xp + i * 32768, v[4 * i], v[4 * i + 1], v[4 * i + 2], v[4 * i + 3]);
    }
    dot += acc2;
#pragma unroll
    for (int o = 8; o > 0; o >>= 1) dot += __shfl_xor_sync(0xffffffffu, dot, o);
    if (hl == 0) { g_router[row] = bf_round(dot); g_stats[row] = make_uint2(mb2, __float_as_uint(inv)); }
}

__device__ __forceinline__ void aux_cta(const Params& P, const CUtensorMap* tmG, const CUtensorMap* tmU, const CUtensorMap* tmD, unsigned char* sm, int a) {
    constexpr int STG = 57344, XS = 3 * STG, HS = XS + 8 * 1296, KEY = HS + 8 * 912, MI = KEY + 8192;
    const int tid = threadIdx.x, warp = __shfl_sync(0xffffffffu, tid >> 5, 0), lane = tid & 31;
    const uint32_t sb = smem_u32(sm);
    const uint32_t full = sb + MI, empty = sb + MI + 32;
    int* s_sel = reinterpret_cast<int*>(sm + MI + 64);
    float* s_r = reinterpret_cast<float*>(sm + MI + 96);
    volatile unsigned* s_misc = reinterpret_cast<volatile unsigned*>(sm + MI + 128);
    uint32_t* s_key = reinterpret_cast<uint32_t*>(sm + KEY);
    PROF_DECL(128 + a)
    PROF_GT(0);
    if (tid == 0) {
        for (int i = 0; i < 3; i++) { mbar_init(full + 8 * i, 1); mbar_init(empty + 8 * i, 10); }
        asm volatile("fence.mbarrier_init.release.cluster;" ::: "memory");
    }
    __syncthreads();
    if (warp == 11) {
        if (elect_one()) {
            int st = 0; uint32_t ph = 0;
#pragma unroll 1
            for (int s = 0; s < 34; s++) {
                mbar_wait(empty + 8 * st, ph ^ 1);
                const uint32_t dst = sb + st * STG, fb = full + 8 * st;
                if (s < 20) {
                    mbar_expect_tx(fb, 57344);
                    tma3d(dst, tmG, 0, 32 * s, 7 * a, fb);
                    tma3d(dst + 28672, tmU, 0, 32 * s, 7 * a, fb);
                } else {
                    mbar_expect_tx(fb, 40960);
                    tma3d(dst, tmD, 0, 448 * a + 32 * (s - 20), 0, fb);
                }
                if (s >= 3) {
#pragma unroll 1
                    for (int f = (s == 3 ? 4 : s + 6); f <= s + 6 && f < 34; f++) {
                        if (f < 20) { tma3d_prefetch(tmG, 0, 32 * f, 7 * a); tma3d_prefetch(tmU, 0, 32 * f, 7 * a); }
                        else tma3d_prefetch(tmD, 0, 448 * a + 32 * (f - 20), 0);
                    }
                }
                if (++st == 3) { st = 0; ph ^= 1; }
            }
        }
        return;
    }
    if (tid < 80) *reinterpret_cast<uint4*>(sm + KEY + 1024 + tid * 16) = __ldg(reinterpret_cast<const uint4*>(P.wr) + tid);
    __nanosleep(AUXDELAY);
#pragma unroll 1
    for (int i = tid; i < 64 * 40; i += 352) asm volatile("prefetch.global.L2 [%0];" ::"l"(P.x + (size_t)((4 + a) * 256 + 192) * DM + i * 16));
    bar_sync(2, 352);
#pragma unroll 1
    for (int i = warp; i < 32; i += 11) ln_rows(P, (4 + a) * 256 + 192 + 2 * i, lane, sb + KEY + 1024);
    bar_sync(2, 352);
    if (tid == 320) flag_signal(flag_ptr(FL_LN + 4 + a));
    PROF_GT(49);
    if (warp == 10) return;
    if (tid < 8) {
        unsigned e = *reinterpret_cast<volatile unsigned*>(&g_epoch);
        if (tid == 0) s_misc[0] = e;
        flag_wait(flag_ptr(FL_LN + tid), (e + 1) * (32u + (tid >> 2)));
    }
    bar_sync(1, 320);
    PROF_GT(50);
    const unsigned ep = s_misc[0];
    auto top8 = [&](uint32_t (&key)[8]) {
        uint32_t mine = 0;
#pragma unroll 1
        for (int r = 0; r < TOPC; r++) {
            uint32_t best = 0;
#pragma unroll
            for (int i = 0; i < 8; i++) best = max(best, key[i]);
            best = __reduce_max_sync(0xffffffffu, best);
#pragma unroll
            for (int i = 0; i < 8; i++) if (key[i] == best) key[i] = 0;
            if (lane == r) mine = best;
        }
        return mine;
    };
#pragma unroll 1
    for (int pass = 0; pass < 2; pass++) {
        if (warp < (pass ? 1 : 8)) {
            uint32_t key[8];
#pragma unroll
            for (int i = 0; i < 8; i++) {
                if (pass == 0) {
                    int idx = warp * 256 + i * 32 + lane;
                    uint32_t b = __float_as_uint(__ldcg(g_router + idx)) >> 16;
                    b = (b & 0x8000u) ? (~b & 0xffffu) : (b | 0x8000u);
                    key[i] = (b << 16) | (uint32_t)(0xffff - idx);
                } else key[i] = i < 2 ? s_key[i * 32 + lane] : 0u;
            }
            uint32_t best = top8(key);
            if (lane < TOPC) {
                if (pass == 0) s_key[warp * 8 + lane] = best;
                else {
                    uint32_t b = best >> 16;
                    b = (b & 0x8000u) ? (b & 0x7fffu) : (~b & 0xffffu);
                    s_sel[lane] = 0xffff - (int)(best & 0xffffu);
                    s_r[lane] = __uint_as_float(b << 16);
                }
            }
        }
        bar_sync(1, 320);
    }
#pragma unroll
    for (int it = 0; it < 2; it++) {
        int i = tid + it * 320, tk = i / 80, ch = i % 80;
        *reinterpret_cast<uint4*>(sm + XS + tk * 1296 + ch * 16) = __ldcg(reinterpret_cast<const uint4*>(xn_addr(s_sel[tk], ch * 8)));
    }
    bar_sync(1, 320);
    PROF_GT(51);
    const int g = lane >> 2, t = lane & 3;
    const uint32_t woff = warp * 4096 + (8 * (lane >> 4) + (lane & 7)) * 128 + ((((lane >> 3) & 1) ^ (lane & 7)) << 4);
    int st = 0; uint32_t ph = 0;
    float ga[4][4], ua[4][4];
#pragma unroll
    for (int i = 0; i < 4; i++)
#pragma unroll
        for (int e = 0; e < 4; e++) { ga[i][e] = 0.f; ua[i][e] = 0.f; }
#pragma unroll 1
    for (int s = 0; s < 34; s++) {
        if (s == 20) {
            if (warp < 7) {
#pragma unroll
                for (int i = 0; i < 4; i++)
#pragma unroll
                    for (int e = 0; e < 4; e++) {
                        float gv = bf_round(ga[i][e]), uv = bf_round(ua[i][e]);
                        float sg = bf_round(__fdividef(gv, 1.0f + __expf(fminf(-gv, 80.f))));
                        int f = warp * 64 + i * 16 + g + 8 * (e >> 1), tk = 2 * t + (e & 1);
                        *reinterpret_cast<__nv_bfloat16*>(sm + HS + tk * 912 + f * 2) = __float2bfloat16_rn(sg * uv);
                        ga[i][e] = 0.f;
                    }
            }
            bar_sync(1, 320);
            PROF_GT(52);
        }
        mbar_wait(full + 8 * st, ph);
        if (s >= 20 || warp < 7) {
#pragma unroll
            for (int kk = 0; kk < 2; kk++) {
                uint32_t xb = sb + (s < 20 ? XS + g * 1296 + s * 64 : HS + g * 912 + (s - 20) * 64) + 32 * kk + 4 * t;
                uint32_t b0 = lds32(xb), b1 = lds32(xb + 16);
                uint32_t wa = sb + st * STG + woff + kk * 2048;
#pragma unroll
                for (int i = 0; i < 4; i++) {
                    uint32_t a0, a1, a2, a3;
                    ldsm4t(a0, a1, a2, a3, wa ^ (i << 5));
                    mma16816(ga[i], a0, a1, a2, a3, b0, b1);
                    if (s < 20) {
                        ldsm4t(a0, a1, a2, a3, (wa ^ (i << 5)) + 28672);
                        mma16816(ua[i], a0, a1, a2, a3, b0, b1);
                    }
                }
            }
        }
        asm volatile("fence.proxy.async.shared::cta;" ::: "memory");
        __syncwarp();
        if (lane == 0) mbar_arrive(empty + 8 * st);
        if (++st == 3) { st = 0; ph ^= 1; }
    }
#pragma unroll
    for (int i = 0; i < 4; i++)
#pragma unroll
        for (int e = 0; e < 4; e += 2)
            *reinterpret_cast<float2*>(g_moe_part + (a * DM + warp * 64 + i * 16 + g + 4 * e) * 8 + 2 * t) = make_float2(ga[i][e], ga[i][e + 1]);
    bar_sync(1, 320);
    if (tid == 0) {
        __threadfence();
        unsigned old = atomicAdd(flag_ptr(FL_MOE_CNT), 1u);
        s_misc[1] = (old == ep * 4u + 3u);
        __threadfence();
    }
    bar_sync(1, 320);
    PROF_GT(53);
    if (s_misc[1]) {
        const float4* pp = reinterpret_cast<const float4*>(g_moe_part);
#pragma unroll 2
        for (int i = tid; i < DM * 2; i += 320) {
            float4 v0 = __ldcg(pp + i), v1 = __ldcg(pp + DM * 2 + i), v2 = __ldcg(pp + DM * 4 + i), v3 = __ldcg(pp + DM * 6 + i);
            float y[4] = {v0.x + v1.x + v2.x + v3.x, v0.y + v1.y + v2.y + v3.y, v0.z + v1.z + v2.z + v3.z, v0.w + v1.w + v2.w + v3.w};
#pragma unroll
            for (int e = 0; e < 4; e++) {
                int col = i >> 1, tk = (i & 1) * 4 + e;
                float sg = bf_round(__fdividef(1.0f, 1.0f + __expf(fminf(-s_r[tk], 80.f))));
                float upd = bf_round(bf_round(y[e]) * sg);
                float xn = __bfloat162float(*reinterpret_cast<const __nv_bfloat16*>(sm + XS + tk * 1296 + col * 2));
                g_brow[tk * DM + col] = __float2bfloat16_rn(xn + upd);
            }
        }
        if (tid < TOPC) g_sel[tid] = s_sel[tid];
        bar_sync(1, 320);
        if (tid == 0) {
            flag_signal(flag_ptr(FL_MOE_DONE));
            *reinterpret_cast<volatile unsigned*>(&g_epoch) = ep + 1;
        }
        PROF_GT(54);
    }
}

__global__ void __cluster_dims__(2, 1, 1) __launch_bounds__(384, 1)
fused_kernel(const __grid_constant__ CUtensorMap tmC, const __grid_constant__ CUtensorMap tmWk, const __grid_constant__ CUtensorMap tmWv,
             const __grid_constant__ CUtensorMap tmWq, const __grid_constant__ CUtensorMap tmWo,
             const __grid_constant__ CUtensorMap tmG, const __grid_constant__ CUtensorMap tmU, const __grid_constant__ CUtensorMap tmD, const Params P) {
    extern __shared__ __align__(1024) unsigned char smem_raw[];
    const uint32_t ring = smem_u32(smem_raw);
    const uint32_t misc = ring + RING_BYTES;
    const int tid = threadIdx.x;
    const int rank = blockIdx.x & 1;
    uint32_t smid, nsm;
    asm("mov.u32 %0, %%smid;" : "=r"(smid));
    asm("mov.u32 %0, %%nsmid;" : "=r"(nsm));
    if (nsm != 132) smid = blockIdx.x;
    auto role_of = [](int tpc) {
        return tpc < 32 ? (tpc & 7) * 8 + (tpc >> 3) : tpc < 60 ? (1 + (tpc - 32) % 7) * 8 + 4 + (tpc - 32) / 7 : tpc < 64 ? tpc - 56 : tpc;
    };
    int mc = role_of(smid >> 1);
    PROF_DECL(mc * 2 + rank)
    PROF_GT(0); PROF_EV(1);

    auto prefetch_w = [&](int ch) {
        const int i = tid - 128;
        asm volatile("prefetch.global.L2 [%0];" ::"l"((rank ? P.wv : P.wk) + (size_t)(ch * 128 + (mc & 3) * 32 + (i >> 3)) * 4096 + (mc >> 2) * 256 + (i & 7) * 16));
    };
    if (tid >= 128 && mc < 64) {
        if (tid < 256) asm volatile("prefetch.global.L2 [%0];" ::"l"(P.c + (size_t)((12 + (mc & 3)) * 128 + ((mc >> 2) * 2 + rank) * 4) * DC + (tid - 128) * 16));
        prefetch_w(0);
    }
    auto load_w0 = [&]() {
        const CUtensorMap* tw = rank ? &tmWv : &tmWk;
        mbar_expect_tx(misc + BAR_FULL + 8 * slot_of(0), SLOT_BYTES);
        tma2d(ring + slot_of(0) * SLOT_BYTES, tw, (mc >> 2) * 256, 0, misc + BAR_FULL + 8 * slot_of(0), policy(HM & 1));
        tma2d(ring + slot_of(0) * SLOT_BYTES + 16384, tw, (mc >> 2) * 256 + 64, 0, misc + BAR_FULL + 8 * slot_of(0), policy(HM & 1));
    };
    if (tid == 0) {
#pragma unroll
        for (int i = 0; i < NSLOT; i++) mbar_init(misc + BAR_FULL + 8 * i, 1);
#pragma unroll
        for (int i = 0; i < E0; i++) mbar_arrive(misc + BAR_FULL + 8 * i);
        asm volatile("fence.mbarrier_init.release.cluster;" ::: "memory");
        if (mc < 64) load_w0();
    }
    if (tid == 160) {
        asm volatile("st.shared.u32 [%0], %1;" ::"r"(misc + MISC_SMID), "r"(smid) : "memory");
        asm volatile("fence.release.sync_restrict::shared::cta.cluster;" ::: "memory");
    }
    if (tid == 32) {
        asm volatile("prefetch.tensormap [%0];" ::"l"(&tmC) : "memory");
#pragma unroll
        for (int i = 0; i < NSLOT; i++) mbar_init(misc + BAR_EMPTY + 8 * i, 16);
#pragma unroll
        for (int i = 0; i < E0; i++) mbar_arrive_cluster(misc + BAR_EMPTY + 8 * i, 16);
        asm volatile("fence.mbarrier_init.release.cluster;" ::: "memory");
    }
    if (tid == 64) {
#pragma unroll
        for (int i = 0; i < NST3; i++) { mbar_init(misc + BAR_FULL3 + 8 * i, 1); mbar_init(misc + BAR_EMPTY3 + 8 * i, 16); }
#pragma unroll
        for (int i = 0; i < 4; i++) mbar_init(misc + BAR_LN + 8 * i, 2);
        mbar_init(misc + BAR_PROG, 1); mbar_init(misc + BAR_PROG + 8, 1); mbar_init(misc + BAR_PROG + 16, 1);
        asm volatile("fence.mbarrier_init.release.cluster;" ::: "memory");
    }
    if (tid == 96) {
#pragma unroll
        for (int i = 0; i < 34; i++) mbar_init(misc + BAR_DEP + 8 * i, 1);
    }
    if (tid == 128) {
#pragma unroll
        for (int i = 0; i < 32; i++) mbar_init(misc + BAR_EV + 8 * i, 4);
    }
    __syncthreads();
    asm volatile("barrier.cluster.arrive.relaxed.aligned;\nbarrier.cluster.wait.aligned;" ::: "memory");
    {
        uint32_t peer;
        asm volatile("ld.shared::cluster.u32 %0, [%1];" : "=r"(peer) : "r"(mapa(misc + MISC_SMID, rank ^ 1)) : "memory");
        if ((__shfl_sync(0xffffffffu, peer, 0) ^ smid) != 1) {
            if (tid == 0) {
                const unsigned ep1 = *reinterpret_cast<volatile unsigned*>(&g_epoch) + 1;
                if ((smid & 1) == 0) atomicExch(g_roleq + 2 + (atomicAdd(g_roleq, 1u) & 127), (ep1 << 8) | (smid >> 1));
                if (rank == 0) {
                    unsigned* slot = g_roleq + 2 + (atomicAdd(g_roleq + 1, 1u) & 127);
                    unsigned v = 0;
                    for (int spin = 0; spin < 4000000 && ((v = atomicAdd(slot, 0u)) >> 8) != (ep1 & 0xffffffu); spin++) {}
                    asm volatile("st.shared::cluster.u32 [%0], %1;" ::"r"(mapa(misc + MISC_SMID + 4, 0)), "r"(v & 255) : "memory");
                    asm volatile("st.shared::cluster.u32 [%0], %1;" ::"r"(mapa(misc + MISC_SMID + 4, 1)), "r"(v & 255) : "memory");
                }
                if (mc < 64) {
                    mbar_wait(misc + BAR_FULL + 8 * slot_of(0), 0);
                    asm volatile("mbarrier.inval.shared::cta.b64 [%0];" ::"r"(misc + BAR_FULL + 8 * slot_of(0)) : "memory");
                    mbar_init(misc + BAR_FULL + 8 * slot_of(0), 1);
                    asm volatile("fence.mbarrier_init.release.cluster;" ::: "memory");
                }
            }
            __syncwarp();
            asm volatile("barrier.cluster.arrive.aligned;\nbarrier.cluster.wait.aligned;" ::: "memory");
            mc = role_of(__shfl_sync(0xffffffffu, lds32(misc + MISC_SMID + 4), 0));
            if (tid == 0 && mc < 64) load_w0();
            __syncwarp();
        }
    }
    const int cta = mc * 2 + rank;
    if (mc >= 64) { aux_cta(P, &tmG, &tmU, &tmD, smem_raw, cta - 128); return; }
    const int team = mc >> 2, k = mc & 3;
    const int u3 = (mc >> 4) * 2 + (team & 1), s3 = k, kap = (mc >> 3) & 1;
    const int partner = cta ^ 16;
    if (tid >= 128) prefetch_w(1);
    if (tid == 256) {
        const CUtensorMap* tw = rank ? &tmWv : &tmWk;
#pragma unroll
        for (int e = 1; e < NSLOT; e++) {
            const uint32_t fb = misc + BAR_FULL + 8 * slot_of(e), dst = ring + slot_of(e) * SLOT_BYTES;
            mbar_expect_tx(fb, SLOT_BYTES);
            if (e & 1) tma2d_mc(dst + rank * 16384, &tmC, (e >> 1) * 128 + rank * 64, (12 + k) * 128, fb, policy(false));
            else { tma2d(dst, tw, team * 256, e * 64, fb, policy(false)); tma2d(dst + 16384, tw, team * 256 + 64, e * 64, fb, policy(false)); }
        }
    }
    PROF_EV(5);
    const int wg = __shfl_sync(0xffffffffu, tid >> 7, 0);

    if (wg == 0) {
        asm volatile("setmaxnreg.dec.sync.aligned.u32 40;");
        const int warp = __shfl_sync(0xffffffffu, tid >> 5, 0), lane = tid & 31;
        if (warp == 0) {
            const bool lead = elect_one();
            Cur c = cur_at(NSLOT);
            uint32_t dst, fb;
            auto acquire = [&]() {
                mbar_wait(misc + BAR_EMPTY + 8 * c.slot, c.ph ^ 1);
                fb = misc + BAR_FULL + 8 * c.slot; dst = ring + c.slot * SLOT_BYTES;
                if (lead) mbar_expect_tx(fb, SLOT_BYTES);
                c.adv();
            };
            auto load_w = [&](const CUtensorMap* tm, int col, int row, bool stream) {
                acquire();
                if (lead) { tma2d(dst, tm, col, row, fb, policy(stream)); tma2d(dst + 16384, tm, col + 64, row, fb, policy(stream)); }
            };
            auto load_half = [&](const unsigned char* src, bool stream) {
                acquire();
                if (lead) bulk_load_mc(dst + rank * 16384, src, 16384, fb, policy(stream));
            };
            auto dep_wait = [&](int d) { mbar_wait(misc + BAR_DEP + 8 * d, 0); fence_async_global(); };
            auto op_prefetch = [&](int i) {
                const int head = op_head(i, kap);
                l2_prefetch(reinterpret_cast<const unsigned char*>(P.wo) + head * 163840 + (u3 * 8 + s3 * 2 + rank) * 2560, 2560);
                if (i < 8) l2_prefetch(g_ctx + (size_t)(head * 32 + 4 * u3 + 2 * rank) * 16384 + s3 * 8192, 8192);
            };
            __nanosleep(CDELAY);
            if (lead) l2_prefetch(reinterpret_cast<const unsigned char*>(P.c) + (size_t)cta * 12288, 12288);
            const CUtensorMap* tw = rank ? &tmWv : &tmWk;
            const unsigned char* Kh = g_K + (size_t)team * 32 * 16384 + rank * 16384;
            const unsigned char* Vh = g_V + (size_t)team * 32 * 16384 + rank * 16384;
#pragma unroll 1
            for (int v = 0; v < 2; v++) {
                const int h = 2 * team + v;
#pragma unroll 1
                for (int i = v ? 0 : 3; i < 16; i++) {
                    if (i < 4 && v) load_w(tw, h * 128, i * 128, HM & 1);
                    if (v && (i & 7) == 3) dep_wait(D_WAR + (i >> 3));
                    acquire();
                    if (lead) tma2d_mc(dst + rank * 16384, &tmC, (i & 3) * 128 + rank * 64, (12 - (i & 12) + k) * 128, fb, policy(HM & 2));
                    if (v && i == 3 && lead) mbar_arrive(misc + BAR_PROG + 8);
                    if (i == 8 && lead) {
                        tma2d_prefetch(&tmWq, h * 128 + rank * 64, k * 64); tma2d_prefetch(&tmWq, h * 128 + rank * 64, k * 64 + 256);
                        if (k < 2) tma2d_prefetch(&tmWq, h * 128 + rank * 64, k * 64 + 512);
                        if (v) l2_prefetch(g_xn + 8 * 163840 + cta * 10240, 10240);
                    }
                }
                int togo = v ? PF_START : 11;
#pragma unroll 1
                for (int r = 0; r < 2; r++) {
                    const int p = r ? k : 7 - k, n = 2 * p + 1;
                    if (v == 0) dep_wait(D_LN + r);
                    const int g0 = r ? rank : 3 - rank, g1 = 3 - g0;
                    const unsigned char* x0 = g_xn + (2 * p + (g0 >> 1)) * 163840 + (g0 & 1) * 8192;
                    const unsigned char* x1 = g_xn + (2 * p + (g1 >> 1)) * 163840 + (g1 & 1) * 8192;
#pragma unroll 1
                    for (int kc = 0; kc < 10; kc++) {
                        acquire();
                        if (lead) {
                            tma2d_mc(dst + 16384 + rank * 8192, &tmWq, h * 128 + rank * 64, kc * 64, fb, policy(false));
                            bulk_load(dst, x0 + kc * 16384, 8192, fb, policy(false));
                            bulk_load(dst + 8192, x1 + kc * 16384, 8192, fb, policy(false));
                        }
                    }
                    if (r == 0) dep_wait(D_KV + 4 * v + (k >> 1));
                    load_half(Kh + n * 32768, HM & 16);
#pragma unroll 1
                    for (int j = n - 1; j >= 0; j--) {
                        if (r == 0 && (j & 3) == 3) dep_wait(D_KV + 4 * v + 3 - (j >> 2));
                        load_half(Kh + j * 32768, HM & 16); load_half(Vh + (j + 1) * 32768, HM & 16);
                        if (v == 0 && r == 0 && j == 3 && lead) mbar_arrive(misc + BAR_PROG);
                        --togo;
                        if (v == 0 && togo == 0 && lead) {
                            tma2d_prefetch(tw, h * 128 + 128, k * 128); tma2d_prefetch(tw, h * 128 + 192, k * 128);
                            l2_prefetch(reinterpret_cast<const unsigned char*>(P.c) + (size_t)cta * 16384, 16384);
                        }
                        if (v && togo <= 0 && togo > -OP_PF && lead) op_prefetch(-togo);
                    }
                    load_half(Vh, HM & 16);
                }
            }
            mbar_wait(misc + BAR_EMPTY + 8 * c.slot, c.ph ^ 1); c.adv();
            int st = 0; uint32_t ph3 = 0;
#pragma unroll 1
            for (int i = 0; i < 32; i++) {
                const int head = op_head(i >> 1, kap);
                if ((i & 1) == 0) dep_wait(D_CTX + (i >> 1));
                if (i < NST3) { mbar_wait(misc + BAR_EMPTY + 8 * c.slot, c.ph ^ 1); c.adv(); }
                else mbar_wait(misc + BAR_EMPTY3 + 8 * st, ph3 ^ 1);
                fb = misc + BAR_FULL3 + 8 * st; dst = ring + st * ST3_BYTES;
                if (i == LATE_AT && lead) mbar_arrive(misc + BAR_PROG + 16);
                if (lead) {
                    mbar_expect_tx(fb, ST3_BYTES);
                    const unsigned char* src = g_ctx + (size_t)(head * 32 + 4 * u3 + 2 * rank) * 16384 + (i & 1) * 8192;
                    bulk_load(dst, src, 8192, fb, policy(HM & 32));
                    bulk_load(dst + 8192, src + 16384, 8192, fb, policy(HM & 32));
                    tma3d_mc(dst + 16384 + rank * 10240, &tmWo, 0, head * 128 + (i & 1) * 64 + rank * 32, 5 * s3, fb, policy(HM & 32));
                    if ((i & 1) && (i >> 1) + OP_PF < 16) op_prefetch((i >> 1) + OP_PF);
                }
                if (++st == NST3) { st = 0; ph3 ^= 1; }
            }
        } else {
        if (lane < 27 && (warp - 1) * 27 + lane < 80) {
            const int ch = (warp - 1) * 27 + lane;
            uint4 u = __ldg(reinterpret_cast<const uint4*>(P.wr) + ch);
            asm volatile("st.shared.v4.b32 [%0], {%1,%2,%3,%4};" ::"r"(misc + MISC_WR + 16 * ch), "r"(u.x), "r"(u.y), "r"(u.z), "r"(u.w) : "memory");
        }
        bar_sync(3, 96);
#pragma unroll 1
        for (int t = 0; t < (warp == 3 ? 1 : 3); t++) {
            const int row2 = (cta >> 5) * 256 + (cta & 31) * 8 + (warp - 1) * 4;
            if (t < 2 && warp < 3) {
#pragma unroll
                for (int i = 0; i < 3; i++)
                    if (i * 32 + lane < 80) asm volatile("prefetch.global.L2 [%0];" ::"l"(P.x + (size_t)(row2 + 2 * t) * DM + (i * 32 + lane) * 16));
            }
            ln_rows(P, t ? row2 + 2 * t - 2 : (4 + (cta >> 5)) * 256 + (cta & 31) * 6 + (warp - 1) * 2, lane, misc + MISC_WR);
            __syncwarp();
            if (lane == 0 && warp < 3 && t != 1) mbar_arrive(misc + BAR_LN + 4 * t);
        }
        if (warp == 3) {
            const unsigned ep1 = *reinterpret_cast<volatile unsigned*>(&g_epoch) + 1;
            if (lane == 0) {
                asm volatile("st.shared.u32 [%0], %1;" ::"r"(misc + MISC_EPOCH), "r"(ep1) : "memory");
                mbar_wait(misc + BAR_LN, 0);
                flag_signal(flag_ptr(FL_LN + 4 + (cta >> 5)));
                flag_wait(flag_ptr(FL_LN + 7 - k), ep1 * 33u);
                mbar_arrive(misc + BAR_DEP + 8 * D_LN);
#pragma unroll 1
                for (int v = 0; v < 2; v++) {
#pragma unroll 1
                    for (int i = 4 * v; i < 4 * v + 4; i++) {
                        mbar_wait(misc + BAR_EV + 8 * (16 + EV_KV + i), 0);
                        if (v == 0) {
                            mbar_wait(misc + BAR_EV + 8 * (EV_KV + i), 0);
                            asm volatile("red.release.gpu.global.add.u32 [%0], 2;" ::"l"(flag_ptr(FL_KV + team * 8 + i)) : "memory");
                        }
                        flag_wait(flag_ptr(FL_KV + team * 8 + i), ep1 * 16u);
                        mbar_arrive(misc + BAR_DEP + 8 * (D_KV + i));
                    }
                    if (v) break;
                    mbar_wait(misc + BAR_LN + 8, 0);
                    flag_signal(flag_ptr(FL_LN + (cta >> 5)));
                    flag_wait(flag_ptr(FL_LN + k), ep1 * 32u);
                    mbar_arrive(misc + BAR_DEP + 8 * (D_LN + 1));
#pragma unroll 1
                    for (int i = 0; i < 2; i++) {
                        mbar_wait(misc + BAR_PROG + 8 * i, 0);
                        flag_signal(flag_ptr(FL_WAR + 2 * team + i));
                        flag_wait(flag_ptr(FL_WAR + 2 * team + i), ep1 * 8u);
                        mbar_arrive(misc + BAR_DEP + 8 * (D_WAR + i));
                    }
                }
                flag_wait(flag_ptr(FL_MOE_DONE), ep1);
                int4 s0 = __ldcg(reinterpret_cast<const int4*>(g_sel)), s1 = __ldcg(reinterpret_cast<const int4*>(g_sel) + 1);
                asm volatile("st.shared.v4.u32 [%0], {%1,%2,%3,%4};" ::"r"(misc + MISC_SEL), "r"(s0.x), "r"(s0.y), "r"(s0.z), "r"(s0.w) : "memory");
                asm volatile("st.shared.v4.u32 [%0], {%1,%2,%3,%4};" ::"r"(misc + MISC_SEL + 16), "r"(s1.x), "r"(s1.y), "r"(s1.z), "r"(s1.w) : "memory");
                mbar_arrive(misc + BAR_SEL);
            }
            __syncwarp();
            const unsigned* cf = flag_ptr(FL_CTX + op_head(lane & 15, kap) * 8 + u3);
#pragma unroll 1
            for (int half = 0; half < 2; half++) {
                if (half) mbar_wait(misc + BAR_EV + 8 * (EV_CTX + 3), 0);
                bool done = (lane >> 3) != half;
                for (int spin = 0; spin < 4000000; spin++) {
                    if (!done) {
                        unsigned v;
                        asm volatile("ld.acquire.gpu.global.u32 %0, [%1];" : "=r"(v) : "l"(cf) : "memory");
                        if ((int)(v - ep1 * 4u) >= 0) { mbar_arrive(misc + BAR_DEP + 8 * (D_CTX + lane)); done = true; }
                    }
                    if (__all_sync(0xffffffffu, done)) break;
                    __nanosleep(64);
                }
            }
        } else {
            const int w = warp - 1;
            if (lane == 0) {
                const uint32_t eb = misc + BAR_EV + w * 128;
#pragma unroll 1
                for (int i = 0; i < 8; i++) {
                    const bool kv = i >= 2 && i < 6;
                    mbar_wait(eb + 8 * (kv ? EV_KV + 2 + i : EV_CTX + (i & 3)), 0);
                    flag_signal(flag_ptr(kv ? FL_KV + team * 8 + 2 + i : FL_CTX + (2 * team + (i >> 2)) * 8 + ((i & 1) ? k : 7 - k)));
                }
            }
            __syncwarp();
            mbar_wait(misc + BAR_PROG + 16, 0);
            const int row = (2 * u3 + rank) * 128 + 64 * w + perm32(16 * (lane >> 3) + 8 * kap + (lane & 7));
#pragma unroll
            for (int i = 0; i < 10; i++) asm volatile("prefetch.global.L2 [%0];" ::"l"(P.x + (size_t)row * DM + 160 * s3 + 16 * i));
            asm volatile("prefetch.global.L2 [%0];" ::"l"(g_stats + row));
        }
        }
    } else {
        asm volatile("setmaxnreg.inc.sync.aligned.u32 232;");
        Ctx c;
        c.ring = ring; c.misc = misc; c.w = wg - 1; c.warp = __shfl_sync(0xffffffffu, (tid >> 5) & 3, 0); c.lane = tid & 31;
        c.rel = mapa(misc, tid & 1);
        const int w = c.w;
        if (w == 1) bar_arrive(1, 256);
        prefetch_w(2); prefetch_w(3);
        Cur cur = cur_at(0);
        float o[64], inv[2];
#pragma unroll 1
        for (int v = 0; v < 2; v++) {
        {
            uint32_t wf[128];
            float acc[64];
#pragma unroll
            for (int i = 32; i < 128; i++) wf[i] = 0u;
            Cur cw = cur;
            auto load_wchunk = [&](auto CH) {
                constexpr int ch = decltype(CH)::value;
                mbar_wait_hot(misc + BAR_FULL + 8 * cw.slot, cw.ph);
                const uint32_t z = load_afrag<8, 32 * ch>(wf, ring + cw.slot * SLOT_BYTES + w * 16384, c);
                release(c, BAR_EMPTY + 8 * cw.slot + z, 1);
                cw.adv(); cw.adv();
            };
            load_wchunk(IC<0>{});
            cur.adv();
            PROF_EV(2); PROF_GT(60);
#pragma unroll 1
            for (int t = 0; t < 4; t++) {
                uint32_t last = 0;
                token_wait(w);
                PROF_EV(10);
                undef_regs(acc);
                auto chunk = [&](auto CH) {
                    constexpr int ch = decltype(CH)::value;
                    mbar_wait_hot(misc + BAR_FULL + 8 * cur.slot, cur.ph);
                    if (t == 0) { PROF_EV(12 + ch); }
                    uint64_t d = mkdesc(ring + cur.slot * SLOT_BYTES, 16, 1024, 1);
                    wg_fence();
#pragma unroll
                    for (int ks = 0; ks < 8; ks++)
                        wgmma_rs_n128_ta0_tb0(acc, wf[32 * ch + 4 * ks], wf[32 * ch + 4 * ks + 1], wf[32 * ch + 4 * ks + 2], wf[32 * ch + 4 * ks + 3],
                                              d + (ks >> 2) * 1024 + (ks & 3) * 2, (ch | ks) != 0);
                    wg_commit();
                    if (ch == 3 || (ch < 2 && t == 0)) token_pass(w);
                    if constexpr (ch < 2) { if (t == 0) load_wchunk(IC<ch + 1>{}); }
                    if constexpr (ch == 2) { if (t == 0 && !w) load_wchunk(IC<3>{}); }
                    if (ch > 0) { wg_wait<1>(); release(c, BAR_EMPTY + 8 * last, 1); }
                    last = cur.slot;
                    cur.adv();
                    if (ch < 3 && t == 0) cur.adv();
                    if constexpr (ch == 1) { if (t == 0 && w) load_wchunk(IC<3>{}); }
                    if (ch < 2 && t == 0) token_wait(w);
                };
                chunk(IC<0>{}); chunk(IC<1>{}); chunk(IC<2>{}); chunk(IC<3>{});
                wg_wait<0>();
                release(c, BAR_EMPTY + 8 * last, 1);
                PROF_EV(11);
                fence_regs(acc);
                store_proj(acc, (rank ? g_V : g_K) + (size_t)(team * 32 + 24 + 2 * k - 8 * t) * 16384, rank, c);
                signal_event(c, EV_KV + 4 * v + t);
            }
            PROF_EV(61); PROF_GT(62);
        }
        PROF_EV(63); PROF_GT(64);
        {
            uint32_t q[32], p[32];
            float m[2], l[2];
#pragma unroll
            for (int i = 0; i < 64; i++) o[i] = 0.f;
#pragma unroll
            for (int i = 0; i < 32; i++) p[i] = 0u;
            l[0] = l[1] = 1.f;
            int pv_acc = 0, pv_mode = 2;
#pragma unroll 1
            for (int r = 0; r < 2; r++) {
                {
                    float s[64];
                    Cur cv = cur;
                    if (r) cur.adv();
                    mbar_wait_hot(misc + BAR_FULL + 8 * cv.slot, cv.ph);
                    token_wait(w);
                    PROF_EV(20);
                    issue_pv(o, p, ring + cv.slot * SLOT_BYTES, pv_acc, pv_mode);
                    undef_regs(s);
                    uint32_t prev = 0;
                    auto qchunk = [&](int acc) {
                        mbar_wait_hot(misc + BAR_FULL + 8 * cur.slot, cur.ph);
                        const uint64_t da = mkdesc(ring + cur.slot * SLOT_BYTES + w * 8192, 16, 1024, 1);
                        const uint64_t db = mkdesc(ring + cur.slot * SLOT_BYTES + 16384, 8192, 1024, 1);
                        wg_fence();
#pragma unroll
                        for (int ks = 0; ks < 4; ks++) wgmma_ss_n128_ta0_tb1(s, da + 2 * ks, db + 128 * ks, ks ? 1 : acc);
                        wg_commit();
                    };
                    qchunk(0);
                    const uint32_t slot0 = cur.slot; cur.adv();
                    qchunk(1);
                    prev = cur.slot; cur.adv();
                    token_pass(w);
                    row_inv(l, inv);
                    wg_wait<2>();
                    fence_regs(o);
                    if (r) {
                        release(c, BAR_EMPTY + 8 * cv.slot, 1);
                        store_ctx(o, inv, g_ctx + (size_t)((2 * team + v) * 32 + 4 * (7 - k) + (w ? rank : 3 - rank)) * 16384, policy((HM & 256) && v == 0), c);
                        signal_event(c, EV_CTX + 2 * v);
                    }
                    wg_wait<1>();
                    release(c, BAR_EMPTY + 8 * slot0, 1);
#pragma unroll 1
                    for (int kc = 2; kc < 10; kc++) {
                        qchunk(1);
                        wg_wait<1>();
                        release(c, BAR_EMPTY + 8 * prev, 1);
                        prev = cur.slot; cur.adv();
                    }
                    wg_wait<0>();
                    release(c, BAR_EMPTY + 8 * prev, 1);
                    PROF_EV(21);
                    fence_regs(s);
#pragma unroll
                    for (int i = 0; i < 32; i++) q[i] = pack_bf16(s[2 * i] * SM_SCALE, s[2 * i + 1] * SM_SCALE);
                }
                const int heavy = 1 ^ r ^ w;
                const int half = 1 ^ heavy ^ rank;
                int left = 2 * (r ? k : 7 - k) + 1 + heavy;
                if (!heavy) cur.adv();
                Cur ck = cur, cv = cur;
                cur.adv();
                if (!heavy) cur.adv();
                int first = 1, gen = 0;
                uint32_t pv_cnt = 0;
                pv_acc = 0; pv_mode = 2;
                l[0] = l[1] = m[0] = m[1] = 0.f;
                mbar_wait_hot(misc + BAR_FULL + 8 * ck.slot, ck.ph);
#pragma unroll 1
                while (true) {
                    float s[64];
                    if (half & first) {
                        token_wait(w);
                        PROF_EV(30);
                        float sh[32];
                        undef_regs(sh);
                        issue_qk_half(sh, q, ring + ck.slot * SLOT_BYTES);
                        token_pass(w);
                        --left;
                        wg_wait<0>();
                        PROF_EV(34);
                        fence_regs(sh);
                        mask_diag<0>(sh, c);
                        float l0 = 0.f, l1 = 0.f;
#pragma unroll
                        for (int j = 0; j < 8; j++) {
#pragma unroll
                            for (int e = 0; e < 4; e++) ex2v(sh[4 * j + e]);
                            l0 += sh[4 * j] + sh[4 * j + 1]; l1 += sh[4 * j + 2] + sh[4 * j + 3];
                        }
#pragma unroll
                        for (int i = 0; i < 16; i++) p[i] = pack_bf16(sh[2 * i], sh[2 * i + 1]);
                        const int lim = mask_lim(c);
                        if (__any_sync(0xffffffffu, !(l0 <= SAFE_SUM && l1 <= SAFE_SUM && (l0 >= 1.0f / SAFE_SUM || lim < 0) &&
                                                      (l1 >= 1.0f / SAFE_SUM || lim < -2)))) goto redo;
                        l[0] = l0; l[1] = l1;
                        goto tail;
                    }
#pragma unroll 1
                    while (true) {
                        token_wait(w);
                        PROF_EV(first ? 30 : 31);
                        undef_regs(s);
                        issue_qk(s, q, ring + ck.slot * SLOT_BYTES);
                        Cur nck = cur, ncv = cur, ncur;
                        ncv.adv(); ncur = ncv; ncur.adv();
                        --left;
                        mbar_wait_hot(misc + BAR_FULL + 8 * cv.slot, cv.ph);
                        issue_pv(o, p, ring + cv.slot * SLOT_BYTES, pv_acc, pv_mode);
                        token_pass(w);
                        wg_wait<1>();
                        PROF_EV(33);
                        fence_regs(s);
                        float lo = 0.f;
                        if (first) {
                            lo = 1.0f / SAFE_SUM;
                            mask_diag<8>(s, c);
                        }
                        constexpr int JB = 11;
                        float l0 = l[0], l1 = l[1];
                        if (!gen) {
#pragma unroll
                            for (int j = 0; j < JB; j++) {
#pragma unroll
                                for (int e = 0; e < 4; e++) ex2v(s[4 * j + e]);
                                if (j < JB - 1) { l0 += s[4 * j] + s[4 * j + 1]; l1 += s[4 * j + 2] + s[4 * j + 3]; }
                            }
                        }
                        wg_wait<0>();
                        fence_regs(o);
                        if (gen) goto general;
#pragma unroll
                        for (int j = JB - 1; j < 16; j++) {
                            if (j >= JB) {
#pragma unroll
                                for (int e = 0; e < 4; e++) ex2v(s[4 * j + e]);
                            }
                            l0 += s[4 * j] + s[4 * j + 1]; l1 += s[4 * j + 2] + s[4 * j + 3];
                        }
#pragma unroll
                        for (int i = 0; i < 32; i++) p[i] = pack_bf16(s[2 * i], s[2 * i + 1]);
                        if (__any_sync(0xffffffffu, !(l0 <= SAFE_SUM && l1 <= SAFE_SUM && l0 >= lo && l1 >= lo))) goto redo;
                        l[0] = l0; l[1] = l1;
                        if (left == 0) goto tail;
                        release(c, BAR_EMPTY + 8 * ck.slot, 1 + (first & heavy));
                        if (pv_cnt) release(c, BAR_EMPTY + 8 * cv.slot, pv_cnt);
                        pv_acc = first ^ 1; pv_mode = 0; pv_cnt = 1 + (first & heavy); first = 0;
                        ck = nck; cv = ncv; cur = ncur;
                        mbar_wait_hot(misc + BAR_FULL + 8 * ck.slot, ck.ph);
                    }
                redo:
                    recompute_scores(s, q, ring + ck.slot * SLOT_BYTES, c);
                    if (first) { mask_any(s, half ^ 1, c); m[0] = m[1] = -INFINITY; }
                    gen = 1;
                general:
                    {
                        float mx[2], alpha[2];
                        row_max<16>(s, mx);
#pragma unroll
                        for (int i = 0; i < 2; i++) {
                            mx[i] = fmaxf(mx[i], m[i]);
                            alpha[i] = ex2(m[i] - mx[i]);
                            m[i] = mx[i];
                            l[i] *= alpha[i];
                        }
                        exp_sum<16, true>(s, m, l[0], l[1]);
#pragma unroll
                        for (int i = 0; i < 64; i++) o[i] *= alpha[(i >> 1) & 1];
#pragma unroll
                        for (int i = 0; i < 32; i++) p[i] = pack_bf16(s[2 * i], s[2 * i + 1]);
                    }
                tail:
                    release(c, BAR_EMPTY + 8 * ck.slot, 1 + (first & heavy));
                    if (pv_cnt) release(c, BAR_EMPTY + 8 * cv.slot, pv_cnt);
                    pv_acc = first ^ 1; pv_mode = first & half; pv_cnt = 1 + (first & heavy); first = 0;
                    if (left == 0) break;
                    ck = cur; cur.adv(); cv = cur; cur.adv();
                    mbar_wait_hot(misc + BAR_FULL + 8 * ck.slot, ck.ph);
                }
            }
            mbar_wait_hot(misc + BAR_FULL + 8 * cur.slot, cur.ph);
            token_wait(w);
            PROF_EV(32);
            issue_pv(o, p, ring + cur.slot * SLOT_BYTES, pv_acc, pv_mode);
            if (w == 0 || v == 0) token_pass(w);
            row_inv(l, inv);
            wg_wait<0>();
            release(c, BAR_EMPTY + 8 * cur.slot, 1);
            fence_regs(o);
            cur.adv();
            if (v == 0) {
                store_ctx(o, inv, g_ctx + (size_t)(2 * team * 32 + 4 * k + (w ? 3 - rank : rank)) * 16384, policy(HM & 256), c);
                signal_event(c, EV_CTX + 1);
            }
        }
        }
        {
            float acc[80];
            undef_regs(acc);
            int st = 0, prev = 0; uint32_t ph3 = 0;
            auto op_stage = [&](int i) {
                mbar_wait(misc + BAR_FULL3 + 8 * st, ph3);
                PROF_EV(44);
                uint32_t base = ring + st * ST3_BYTES;
                uint64_t da = mkdesc(base + w * 8192, 16, 1024, 1);
                uint64_t db = mkdesc(base + 16384, 2048, 512, 2);
                wg_fence();
#pragma unroll
                for (int k = 0; k < 4; k++) wgmma_ss_n160_ta0_tb1(acc, da + 2 * k, db + (k >> 1) * 640 + (k & 1) * 64, k ? 1 : i);
                wg_commit();
                if (i > 0) { wg_wait<1>(); if (i <= 32 - NST3) release(c, BAR_EMPTY3 + 8 * prev, 1); }
                prev = st;
                if (++st == NST3) { st = 0; ph3 ^= 1; }
            };
            PROF_EV(40); PROF_GT(65);
            op_stage(0);
            store_ctx(o, inv, g_ctx + (size_t)((2 * team + 1) * 32 + 4 * k + (w ? 3 - rank : rank)) * 16384, policy(false), c);
            signal_event(c, EV_CTX + 3);
#pragma unroll 1
            for (int i = 1; i < 12; i++) op_stage(i);
            mbar_wait(misc + BAR_SEL, 0);
            const uint32_t tag = lds32(misc + MISC_EPOCH) & 1;
            const int g = c.lane >> 2, t = c.lane & 3;
            const int row = (2 * u3 + rank) * 128 + 64 * w + perm32(16 * c.warp + 8 * kap + g);
            const int col = 160 * s3 + 8 * t;
            int sel = -1;
#pragma unroll
            for (int i = 0; i < TOPC; i++) if ((int)lds32(misc + MISC_SEL + 4 * i) == row) sel = i;
            const int t256 = tid - 128;
            uint4* sendp = g_part + (size_t)cta * 2560 + t256;
            if (c.lane >= 30) stg128(sendp + 9 * 256, tag ^ 1, tag ^ 1, tag ^ 1, tag ^ 1);
#pragma unroll 1
            for (int i = 12; i < 32; i++) op_stage(i);
            uint4 xv[5], bv[5];
#pragma unroll
            for (int i = 0; i < 5; i++) xv[i] = ldg128(P.x + (size_t)row * DM + col + 32 * i);
            uint2 stat;
            asm volatile("ld.global.cg.v2.b32 {%0,%1}, [%2];" : "=r"(stat.x), "=r"(stat.y) : "l"(g_stats + row) : "memory");
            wg_wait<0>();
            fence_regs(acc);
            PROF_EV(41); PROF_GT(66);
            float keep[40];
#pragma unroll
            for (int j = 0; j < 10; j++) {
                uint32_t v0 = __float_as_uint(kap ? acc[8 * j + 0] : acc[8 * j + 2]), v1 = __float_as_uint(kap ? acc[8 * j + 1] : acc[8 * j + 3]);
                uint32_t v2 = __float_as_uint(kap ? acc[8 * j + 4] : acc[8 * j + 6]), v3 = __float_as_uint(kap ? acc[8 * j + 5] : acc[8 * j + 7]);
                asm volatile("st.relaxed.gpu.global.v4.b32 [%0], {%1,%2,%3,%4};" ::"l"(sendp + j * 256),
                             "r"((v0 & ~1u) | tag), "r"((v1 & ~1u) | tag), "r"((v2 & ~1u) | tag), "r"((v3 & ~1u) | tag) : "memory");
                keep[4 * j + 0] = kap ? acc[8 * j + 2] : acc[8 * j + 0]; keep[4 * j + 1] = kap ? acc[8 * j + 3] : acc[8 * j + 1];
                keep[4 * j + 2] = kap ? acc[8 * j + 6] : acc[8 * j + 4]; keep[4 * j + 3] = kap ? acc[8 * j + 7] : acc[8 * j + 5];
            }
            PROF_GT(67);
#pragma unroll
            for (int i = 0; i < 5; i++) {
                uint32_t xx[4] = {xv[i].x, xv[i].y, xv[i].z, xv[i].w};
#pragma unroll
                for (int e = 0; e < 4; e++) {
                    asm("sub.rn.bf16x2 %0, %0, %1;" : "+r"(xx[e]) : "r"(stat.x));
                    xx[e] = pack_bf16(bf_lo(xx[e]) * __uint_as_float(stat.y), bf_hi(xx[e]) * __uint_as_float(stat.y));
                }
                bv[i] = make_uint4(xx[0], xx[1], xx[2], xx[3]);
            }
            if (sel >= 0) {
#pragma unroll
                for (int i = 0; i < 5; i++) bv[i] = ldg128(g_brow + sel * DM + col + 32 * i);
            }
            const uint4* recvp = g_part + (size_t)partner * 2560 + t256;
            uint4 rv[10];
            int spins = 0;
            while (POLL1) {
                uint32_t v;
                asm volatile("ld.relaxed.gpu.global.b32 %0, [%1];" : "=r"(v) : "l"(recvp + 9 * 256 + (31 - c.lane)) : "memory");
                if (__all_sync(0xffffffffu, (v & 1u) == tag) || ++spins > 2000000) break;
            }
            PROF_GT(68);
            while (true) {
                uint32_t bad = 0u;
#pragma unroll
                for (int j = 0; j < 10; j++) {
                    asm volatile("ld.relaxed.gpu.global.v4.b32 {%0,%1,%2,%3}, [%4];"
                                 : "=r"(rv[j].x), "=r"(rv[j].y), "=r"(rv[j].z), "=r"(rv[j].w) : "l"(recvp + j * 256) : "memory");
                }
#pragma unroll
                for (int j = 0; j < 10; j++) {
                    rv[j].x ^= tag; rv[j].y ^= tag; rv[j].z ^= tag; rv[j].w ^= tag;
                    bad |= rv[j].x | rv[j].y | rv[j].z | rv[j].w;
                }
                if (__all_sync(0xffffffffu, (bad & 1u) == 0) || ++spins > 2000000) break;
            }
            PROF_GT(69);
            uint32_t pk[20];
#pragma unroll
            for (int j = 0; j < 10; j++) {
                pk[2 * j] = pack_bf16(keep[4 * j] + __uint_as_float(rv[j].x), keep[4 * j + 1] + __uint_as_float(rv[j].y));
                pk[2 * j + 1] = pack_bf16(keep[4 * j + 2] + __uint_as_float(rv[j].z), keep[4 * j + 3] + __uint_as_float(rv[j].w));
            }
#pragma unroll
            for (int i = 0; i < 5; i++) {
                uint32_t a0 = pk[4 * i], a1 = pk[4 * i + 1], a2 = pk[4 * i + 2], a3 = pk[4 * i + 3];
                uint32_t x0 = (t & 1) ? a0 : a1, x1 = (t & 1) ? a2 : a3;
                x0 = __shfl_xor_sync(0xffffffffu, x0, 1); x1 = __shfl_xor_sync(0xffffffffu, x1, 1);
                if (t & 1) { a0 = x0; a2 = x1; } else { a1 = x0; a3 = x1; }
                x0 = (t & 2) ? a0 : a2; x1 = (t & 2) ? a1 : a3;
                x0 = __shfl_xor_sync(0xffffffffu, x0, 2); x1 = __shfl_xor_sync(0xffffffffu, x1, 2);
                if (t & 2) { a0 = x0; a1 = x1; } else { a2 = x0; a3 = x1; }
                uint32_t av[4] = {a0, a1, a2, a3};
                uint32_t xx[4] = {xv[i].x, xv[i].y, xv[i].z, xv[i].w}, bb[4] = {bv[i].x, bv[i].y, bv[i].z, bv[i].w};
                uint32_t ov[4];
#pragma unroll
                for (int e = 0; e < 4; e++) {
                    asm("add.rn.bf16x2 %0, %1, %2;" : "=r"(ov[e]) : "r"(xx[e]), "r"(av[e]));
                    asm("add.rn.bf16x2 %0, %0, %1;" : "+r"(ov[e]) : "r"(bb[e]));
                }
                stg128(P.out + (size_t)row * DM + col + 32 * i, ov[0], ov[1], ov[2], ov[3]);
            }
            PROF_EV(42); PROF_GT(43);
        }
    }
}

typedef CUresult (*EncodeFn)(CUtensorMap*, CUtensorMapDataType, cuuint32_t, void*, const cuuint64_t*, const cuuint64_t*, const cuuint32_t*,
                             const cuuint32_t*, CUtensorMapInterleave, CUtensorMapSwizzle, CUtensorMapL2promotion, CUtensorMapFloatOOBfill);

void make_map2d(EncodeFn enc, CUtensorMap* tm, const void* p, uint64_t cols, uint64_t rows, uint32_t box_rows = 128) {
    cuuint64_t gd[2] = {cols, rows}, gs[1] = {cols * 2};
    cuuint32_t box[2] = {64, box_rows}, es[2] = {1, 1};
    enc(tm, CU_TENSOR_MAP_DATA_TYPE_BFLOAT16, 2, const_cast<void*>(p), gd, gs, box, es, CU_TENSOR_MAP_INTERLEAVE_NONE,
        CU_TENSOR_MAP_SWIZZLE_128B, CU_TENSOR_MAP_L2_PROMOTION_L2_128B, CU_TENSOR_MAP_FLOAT_OOB_FILL_NONE);
}

void make_map3d(EncodeFn enc, CUtensorMap* tm, const void* p, uint64_t cols, uint64_t rows, uint32_t bw, uint32_t nb) {
    cuuint64_t gd[3] = {bw, rows, cols / bw}, gs[2] = {cols * 2, bw * 2};
    cuuint32_t box[3] = {bw, 32, nb}, es[3] = {1, 1, 1};
    enc(tm, CU_TENSOR_MAP_DATA_TYPE_BFLOAT16, 3, const_cast<void*>(p), gd, gs, box, es, CU_TENSOR_MAP_INTERLEAVE_NONE,
        bw == 64 ? CU_TENSOR_MAP_SWIZZLE_128B : CU_TENSOR_MAP_SWIZZLE_64B, CU_TENSOR_MAP_L2_PROMOTION_L2_128B, CU_TENSOR_MAP_FLOAT_OOB_FILL_NONE);
}

}

extern "C" void kernel_launch(void* const* d_in, const int* in_sizes, int n_in, void* d_out, int out_size) {
    (void)in_sizes; (void)n_in; (void)out_size;
    static EncodeFn enc = nullptr;
    if (!enc) {
        void* fn = nullptr;
        cudaDriverEntryPointQueryResult qr;
        cudaGetDriverEntryPoint("cuTensorMapEncodeTiled", &fn, cudaEnableDefault, &qr);
        enc = (EncodeFn)fn;
        cudaFuncSetAttribute(fused_kernel, cudaFuncAttributeMaxDynamicSharedMemorySize, SMEM_BYTES);
    }
    CUtensorMap tmC, tmWk, tmWv, tmWq, tmWo, tmG, tmU, tmD;
    make_map2d(enc, &tmC, d_in[1], DC, SEQ);
    make_map2d(enc, &tmWq, d_in[2], 4096, DM, 64);
    make_map2d(enc, &tmWk, d_in[3], 4096, DC);
    make_map2d(enc, &tmWv, d_in[4], 4096, DC);
    make_map3d(enc, &tmWo, d_in[5], DM, 4096, 32, 5);
    make_map3d(enc, &tmG, d_in[8], FF, DM, 64, 7);
    make_map3d(enc, &tmU, d_in[9], FF, DM, 64, 7);
    make_map3d(enc, &tmD, d_in[10], DM, FF, 64, 10);
    Params P;
    P.x = (const __nv_bfloat16*)d_in[0];
    P.c = (const __nv_bfloat16*)d_in[1];
    P.wk = (const __nv_bfloat16*)d_in[3];
    P.wv = (const __nv_bfloat16*)d_in[4];
    P.wo = (const __nv_bfloat16*)d_in[5];
    P.wr = (const __nv_bfloat16*)d_in[7];
    P.out = (__nv_bfloat16*)d_out;
    fused_kernel<<<132, 384, SMEM_BYTES>>>(tmC, tmWk, tmWv, tmWq, tmWo, tmG, tmU, tmD, P);
}
```

```cpp
#include <cuda_runtime.h>
#include <cuda_bf16.h>
#include <cuda.h>
#include <stdint.h>

#define SWAPT 1
#define HM 512
#define POLL1 1
#define OP_PF 8
#define PF_START 9
#define LATE_AT 18
#define CDELAY 500
#define AUXDELAY 1000
namespace {

constexpr int SEQ = 2048, NH = 32, DM = 640, DC = 512, FF = 1728, TOPC = 8;
constexpr int NSLOT = 7, SLOT_BYTES = 32768;
constexpr int NST3 = 6, ST3_BYTES = 36864;
constexpr int RING_BYTES = NSLOT * SLOT_BYTES;
constexpr int SMEM_BYTES = RING_BYTES + 3072;

constexpr int BAR_FULL = 96  , BAR_FULL3 = 152  , BAR_DEP = 200  , BAR_SEL = 464,
              BAR_LN = 472  , BAR_EV = 504  , BAR_EMPTY = 760  , BAR_EMPTY3 = 816  ,
              BAR_PROG = 864  , MISC_EPOCH = 896, MISC_SMID = 900  , MISC_SEL = 912, MISC_WR = 1024  ;
constexpr int D_LN = 0  , D_KV = 4  , D_WAR = 14  , D_CTX = 16  ;
constexpr int EV_KV = 0  , EV_CTX = 12  ;

constexpr int FL_MOE_CNT = 0, FL_MOE_DONE = 1, FL_LN = 16  , FL_KV = 32  , FL_CTX = 416  , FL_WAR = 672  , FL_TOTAL = 704;

__device__ __align__(1024) unsigned char g_K[16 * 32 * 16384];
__device__ __align__(1024) unsigned char g_V[16 * 32 * 16384];
__device__ __align__(1024) unsigned char g_ctx[NH * 32 * 16384];
__device__ __align__(1024) unsigned char g_xn[16 * 10 * 16384];
__device__ __align__(1024) uint4 g_part[128 * 10 * 256];
__device__ float g_router[SEQ];
__device__ uint2 g_stats[SEQ];
__device__ __align__(16) float g_moe_part[4 * TOPC * DM];
__device__ __align__(16) __nv_bfloat16 g_brow[TOPC * DM];
__device__ __align__(16) int g_sel[TOPC];
__device__ unsigned g_flags[FL_TOTAL * 8];
__device__ unsigned g_epoch;
__device__ unsigned g_roleq[130];

struct Params {
    const __nv_bfloat16 *x, *c, *wr, *wk, *wv, *wo;
    __nv_bfloat16* out;
};

__device__ __forceinline__ uint32_t smem_u32(const void* p) { return (uint32_t)__cvta_generic_to_shared(p); }
__device__ __forceinline__ void mbar_init(uint32_t bar, int cnt) { asm volatile("mbarrier.init.shared::cta.b64 [%0], %1;" ::"r"(bar), "r"(cnt)); }
__device__ __forceinline__ void mbar_expect_tx(uint32_t bar, uint32_t bytes) {
    asm volatile("mbarrier.arrive.expect_tx.shared::cta.b64 _, [%0], %1;" ::"r"(bar), "r"(bytes) : "memory");
}
__device__ __forceinline__ void mbar_arrive(uint32_t bar) { asm volatile("mbarrier.arrive.shared::cta.b64 _, [%0];" ::"r"(bar) : "memory"); }
__device__ __forceinline__ void mbar_arrive_cluster(uint32_t cluster_addr, uint32_t cnt) {
    asm volatile("mbarrier.arrive.shared::cluster.b64 _, [%0], %1;" ::"r"(cluster_addr), "r"(cnt) : "memory");
}
__device__ __forceinline__ uint32_t mapa(uint32_t addr, uint32_t cta) {
    uint32_t r; asm("mapa.shared::cluster.u32 %0, %1, %2;" : "=r"(r) : "r"(addr), "r"(cta)); return r;
}
__device__ __forceinline__ void mbar_wait(uint32_t bar, uint32_t parity) {
    asm volatile(
        "{\n.reg .pred p;\n.reg .u32 n;\n"
        "mbarrier.try_wait.parity.shared::cta.b64 p, [%0], %1;\n"
        "@p bra DONE;\n"
        "mov.u32 n, 0;\n"
        "LAB_WAIT:\n"
        "mbarrier.try_wait.parity.shared::cta.b64 p, [%0], %1, 100000;\n"
        "@p bra DONE;\n"
        "add.u32 n, n, 1;\n"
        "setp.lt.u32 p, n, 200000;\n"
        "@p bra LAB_WAIT;\n"
        "trap;\n"
        "DONE:\n}\n" ::"r"(bar), "r"(parity) : "memory");
}
__device__ __forceinline__ void mbar_wait_hot(uint32_t bar, uint32_t parity) {
    asm volatile("{\n.reg .pred p;\nLAB_WAIT:\nmbarrier.try_wait.parity.shared::cta.b64 p, [%0], %1;\n@!p bra LAB_WAIT;\n}\n" ::"r"(bar), "r"(parity) : "memory");
}
__device__ __forceinline__ void flag_wait(const unsigned* flag, unsigned target) {
    asm volatile(
        "{\n.reg .pred p;\n.reg .u32 n, v;\n.reg .s32 d;\n"
        "mov.u32 n, 0;\n"
        "LAB_WAIT:\n"
        "ld.acquire.gpu.global.u32 v, [%0];\n"
        "sub.s32 d, v, %1;\n"
        "setp.ge.s32 p, d, 0;\n"
        "@p bra DONE;\n"
        "nanosleep.u32 40;\n"
        "add.u32 n, n, 1;\n"
        "setp.lt.u32 p, n, 3000000;\n"
        "@p bra LAB_WAIT;\n"
        "trap;\n"
        "DONE:\n}\n" ::"l"(flag), "r"(target) : "memory");
}
__device__ __forceinline__ void flag_signal(unsigned* flag) {
    asm volatile("red.release.gpu.global.add.u32 [%0], 1;" ::"l"(flag) : "memory");
}
__device__ __forceinline__ void fence_async_global() { asm volatile("fence.proxy.async.global;" ::: "memory"); }
__device__ __forceinline__ unsigned* flag_ptr(int idx) { return g_flags + idx * 8; }

__device__ __forceinline__ uint64_t policy_stream() {
    uint64_t p; asm("createpolicy.fractional.L2::evict_first.b64 %0, 1.0;" : "=l"(p)); return p;
}
__device__ __forceinline__ uint64_t policy_normal() { return 0x1000000000000000ull; }
__device__ __forceinline__ uint64_t policy(bool stream) { return stream ? policy_stream() : policy_normal(); }
__device__ __forceinline__ void bulk_load(uint32_t dst, const void* src, uint32_t bytes, uint32_t bar, uint64_t pol) {
    asm volatile("cp.async.bulk.shared::cluster.global.mbarrier::complete_tx::bytes.L2::cache_hint [%0], [%1], %2, [%3], %4;"
                 ::"r"(dst), "l"(src), "r"(bytes), "r"(bar), "l"(pol) : "memory");
}
__device__ __forceinline__ void bulk_load_mc(uint32_t dst, const void* src, uint32_t bytes, uint32_t bar, uint64_t pol) {
    asm volatile("cp.async.bulk.shared::cluster.global.mbarrier::complete_tx::bytes.multicast::cluster.L2::cache_hint [%0], [%1], %2, [%3], %4, %5;"
                 ::"r"(dst), "l"(src), "r"(bytes), "r"(bar), "h"((uint16_t)3), "l"(pol) : "memory");
}
__device__ __forceinline__ void tma2d(uint32_t dst, const CUtensorMap* tm, int c0, int c1, uint32_t bar, uint64_t pol) {
    asm volatile("cp.async.bulk.tensor.2d.shared::cluster.global.mbarrier::complete_tx::bytes.L2::cache_hint [%0], [%1, {%3, %4}], [%2], %5;"
                 ::"r"(dst), "l"(tm), "r"(bar), "r"(c0), "r"(c1), "l"(pol) : "memory");
}
__device__ __forceinline__ void tma2d_mc(uint32_t dst, const CUtensorMap* tm, int c0, int c1, uint32_t bar, uint64_t pol) {
    asm volatile("cp.async.bulk.tensor.2d.shared::cluster.global.mbarrier::complete_tx::bytes.multicast::cluster.L2::cache_hint [%0], [%1, {%3, %4}], [%2], %5, %6;"
                 ::"r"(dst), "l"(tm), "r"(bar), "r"(c0), "r"(c1), "h"((uint16_t)3), "l"(pol) : "memory");
}
__device__ __forceinline__ void tma3d_mc(uint32_t dst, const CUtensorMap* tm, int c0, int c1, int c2, uint32_t bar, uint64_t pol) {
    asm volatile("cp.async.bulk.tensor.3d.shared::cluster.global.mbarrier::complete_tx::bytes.multicast::cluster.L2::cache_hint [%0], [%1, {%3, %4, %5}], [%2], %6, %7;"
                 ::"r"(dst), "l"(tm), "r"(bar), "r"(c0), "r"(c1), "r"(c2), "h"((uint16_t)3), "l"(pol) : "memory");
}
__device__ __forceinline__ void tma3d(uint32_t dst, const CUtensorMap* tm, int c0, int c1, int c2, uint32_t bar) {
    asm volatile("cp.async.bulk.tensor.3d.shared::cluster.global.mbarrier::complete_tx::bytes.L2::cache_hint [%0], [%1, {%3, %4, %5}], [%2], %6;"
                 ::"r"(dst), "l"(tm), "r"(bar), "r"(c0), "r"(c1), "r"(c2), "l"(policy_stream()) : "memory");
}
__device__ __forceinline__ void tma2d_prefetch(const CUtensorMap* tm, int c0, int c1) {
    asm volatile("cp.async.bulk.prefetch.tensor.2d.L2.global [%0, {%1, %2}];" ::"l"(tm), "r"(c0), "r"(c1) : "memory");
}
__device__ __forceinline__ void tma3d_prefetch(const CUtensorMap* tm, int c0, int c1, int c2) {
    asm volatile("cp.async.bulk.prefetch.tensor.3d.L2.global [%0, {%1, %2, %3}];" ::"l"(tm), "r"(c0), "r"(c1), "r"(c2) : "memory");
}
__device__ __forceinline__ void l2_prefetch(const void* p, uint32_t bytes) {
    asm volatile("cp.async.bulk.prefetch.L2.global [%0], %1;" ::"l"(p), "r"(bytes) : "memory");
}
__device__ __forceinline__ bool elect_one() {
    uint32_t r; asm volatile("{\n.reg .pred p;\nelect.sync _|p, 0xffffffff;\nselp.u32 %0, 1, 0, p;\n}\n" : "=r"(r)); return r != 0;
}
__device__ __forceinline__ void wg_fence() { asm volatile("wgmma.fence.sync.aligned;" ::: "memory"); }
__device__ __forceinline__ void wg_commit() { asm volatile("wgmma.commit_group.sync.aligned;" ::: "memory"); }
template <int N> __device__ __forceinline__ void wg_wait() { asm volatile("wgmma.wait_group.sync.aligned %0;" ::"n"(N) : "memory"); }
__device__ __forceinline__ void bar_sync(int id, int n) { asm volatile("bar.sync %0, %1;" ::"r"(id), "r"(n) : "memory"); }
__device__ __forceinline__ void bar_arrive(int id, int n) { asm volatile("bar.arrive %0, %1;" ::"r"(id), "r"(n) : "memory"); }
__device__ __forceinline__ void token_wait(int w) {
    asm volatile("{\n.reg .pred p;\nsetp.eq.u32 p, %0, 0;\n@p bar.sync 1, 256;\n@!p bar.sync 2, 256;\n}\n" ::"r"(w) : "memory");
}
__device__ __forceinline__ void token_pass(int w) {
    asm volatile("{\n.reg .pred p;\nsetp.eq.u32 p, %0, 0;\n@p bar.arrive 2, 256;\n@!p bar.arrive 1, 256;\n}\n" ::"r"(w) : "memory");
}
template <int N> __device__ __forceinline__ void fence_regs(float (&a)[N]) {
#pragma unroll
    for (int i = 0; i < N; i++) asm volatile("" : "+f"(a[i])::"memory");
}
template <int N> __device__ __forceinline__ void undef_regs(float (&a)[N]) {
#pragma unroll
    for (int i = 0; i < N; i++) asm volatile("" : "=f"(a[i]));
}
__device__ __forceinline__ void ldsm4t(uint32_t& r0, uint32_t& r1, uint32_t& r2, uint32_t& r3, uint32_t addr) {
    asm volatile("ldmatrix.sync.aligned.m8n8.x4.trans.shared.b16 {%0,%1,%2,%3}, [%4];"
                 : "=r"(r0), "=r"(r1), "=r"(r2), "=r"(r3) : "r"(addr) : "memory");
}
__device__ __forceinline__ uint32_t pack_bf16(float lo, float hi) {
    uint32_t r; asm("cvt.rn.bf16x2.f32 %0, %1, %2;" : "=r"(r) : "f"(hi), "f"(lo)); return r;
}
__device__ __forceinline__ float bf_lo(uint32_t v) { return __uint_as_float(v << 16); }
__device__ __forceinline__ float bf_hi(uint32_t v) { return __uint_as_float(v & 0xffff0000u); }
__device__ __forceinline__ float bf_round(float v) { return __bfloat162float(__float2bfloat16_rn(v)); }
__device__ __forceinline__ float ex2(float v) { float r; asm("ex2.approx.ftz.f32 %0, %1;" : "=f"(r) : "f"(v)); return r; }
__device__ __forceinline__ void ex2v(float& v) { asm volatile("ex2.approx.ftz.f32 %0, %0;" : "+f"(v)); }
__device__ __forceinline__ float rcp_fast(float v) { float r; asm("rcp.approx.ftz.f32 %0, %1;" : "=f"(r) : "f"(v)); return r; }
__device__ __forceinline__ float sqrt_fast(float v) { float r; asm("sqrt.approx.ftz.f32 %0, %1;" : "=f"(r) : "f"(v)); return r; }
__device__ __forceinline__ void stg128(void* p, uint32_t a, uint32_t b, uint32_t c, uint32_t d) {
    asm volatile("st.global.v4.b32 [%0], {%1,%2,%3,%4};" ::"l"(p), "r"(a), "r"(b), "r"(c), "r"(d) : "memory");
}
__device__ __forceinline__ void stg128_hint(void* p, uint32_t a, uint32_t b, uint32_t c, uint32_t d, uint64_t pol) {
    asm volatile("st.global.L2::cache_hint.v4.b32 [%0], {%1,%2,%3,%4}, %5;" ::"l"(p), "r"(a), "r"(b), "r"(c), "r"(d), "l"(pol) : "memory");
}
__device__ __forceinline__ uint4 ldg128(const void* p) {
    uint4 v; asm volatile("ld.global.cg.v4.b32 {%0,%1,%2,%3}, [%4];" : "=r"(v.x), "=r"(v.y), "=r"(v.z), "=r"(v.w) : "l"(p) : "memory"); return v;
}
__device__ __forceinline__ uint64_t mkdesc(uint32_t addr, uint32_t lbo, uint32_t sbo, uint32_t swz) {
    uint32_t lo = ((addr & 0x3FFFF) >> 4) | ((lbo >> 4) << 16);
    uint32_t hi = (sbo >> 4) | (swz << 30);
    return ((uint64_t)hi << 32) | lo;
}
__device__ __forceinline__ int perm32(int v) { return (v & ~30) | ((v >> 2) & 6) | ((v << 2) & 24); }

__device__ __forceinline__ void wgmma_rs_n128_ta0_tb0(float (&d)[64], uint32_t a0, uint32_t a1, uint32_t a2, uint32_t a3, uint64_t descB, int scaleD) {
  asm volatile("{\n.reg .pred p;\nsetp.ne.b32 p, %69, 0;\n"
    "wgmma.mma_async.sync.aligned.m64n128k16.f32.bf16.bf16 "
    "{%0, %1, %2, %3, %4, %5, %6, %7, %8, %9, %10, %11, %12, %13, %14, %15, %16, %17, %18, %19, %20, %21, %22, %23, %24, %25, %26, %27, %28, %29, %30, %31, %32, %33, %34, %35, %36, %37, %38, %39, %40, %41, %42, %43, %44, %45, %46, %47, %48, %49, %50, %51, %52, %53, %54, %55, %56, %57, %58, %59, %60, %61, %62, %63}, "
    "{%64, %65, %66, %67}, %68, p, 1, 1, 0;\n}\n"
    : "+f"(d[0]), "+f"(d[1]), "+f"(d[2]), "+f"(d[3]), "+f"(d[4]), "+f"(d[5]), "+f"(d[6]), "+f"(d[7]), "+f"(d[8]), "+f"(d[9]), "+f"(d[10]), "+f"(d[11]), "+f"(d[12]), "+f"(d[13]), "+f"(d[14]), "+f"(d[15]), "+f"(d[16]), "+f"(d[17]), "+f"(d[18]), "+f"(d[19]), "+f"(d[20]), "+f"(d[21]), "+f"(d[22]), "+f"(d[23]), "+f"(d[24]), "+f"(d[25]), "+f"(d[26]), "+f"(d[27]), "+f"(d[28]), "+f"(d[29]), "+f"(d[30]), "+f"(d[31]), "+f"(d[32]), "+f"(d[33]), "+f"(d[34]), "+f"(d[35]), "+f"(d[36]), "+f"(d[37]), "+f"(d[38]), "+f"(d[39]), "+f"(d[40]), "+f"(d[41]), "+f"(d[42]), "+f"(d[43]), "+f"(d[44]), "+f"(d[45]), "+f"(d[46]), "+f"(d[47]), "+f"(d[48]), "+f"(d[49]), "+f"(d[50]), "+f"(d[51]), "+f"(d[52]), "+f"(d[53]), "+f"(d[54]), "+f"(d[55]), "+f"(d[56]), "+f"(d[57]), "+f"(d[58]), "+f"(d[59]), "+f"(d[60]), "+f"(d[61]), "+f"(d[62]), "+f"(d[63])
    : "r"(a0), "r"(a1), "r"(a2), "r"(a3), "l"(descB), "r"(scaleD));
}
__device__ __forceinline__ void wgmma_rs_n128_ta0_tb1(float (&d)[64], uint32_t a0, uint32_t a1, uint32_t a2, uint32_t a3, uint64_t descB, int scaleD) {
  asm volatile("{\n.reg .pred p;\nsetp.ne.b32 p, %69, 0;\n"
    "wgmma.mma_async.sync.aligned.m64n128k16.f32.bf16.bf16 "
    "{%0, %1, %2, %3, %4, %5, %6, %7, %8, %9, %10, %11, %12, %13, %14, %15, %16, %17, %18, %19, %20, %21, %22, %23, %24, %25, %26, %27, %28, %29, %30, %31, %32, %33, %34, %35, %36, %37, %38, %39, %40, %41, %42, %43, %44, %45, %46, %47, %48, %49, %50, %51, %52, %53, %54, %55, %56, %57, %58, %59, %60, %61, %62, %63}, "
    "{%64, %65, %66, %67}, %68, p, 1, 1, 1;\n}\n"
    : "+f"(d[0]), "+f"(d[1]), "+f"(d[2]), "+f"(d[3]), "+f"(d[4]), "+f"(d[5]), "+f"(d[6]), "+f"(d[7]), "+f"(d[8]), "+f"(d[9]), "+f"(d[10]), "+f"(d[11]), "+f"(d[12]), "+f"(d[13]), "+f"(d[14]), "+f"(d[15]), "+f"(d[16]), "+f"(d[17]), "+f"(d[18]), "+f"(d[19]), "+f"(d[20]), "+f"(d[21]), "+f"(d[22]), "+f"(d[23]), "+f"(d[24]), "+f"(d[25]), "+f"(d[26]), "+f"(d[27]), "+f"(d[28]), "+f"(d[29]), "+f"(d[30]), "+f"(d[31]), "+f"(d[32]), "+f"(d[33]), "+f"(d[34]), "+f"(d[35]), "+f"(d[36]), "+f"(d[37]), "+f"(d[38]), "+f"(d[39]), "+f"(d[40]), "+f"(d[41]), "+f"(d[42]), "+f"(d[43]), "+f"(d[44]), "+f"(d[45]), "+f"(d[46]), "+f"(d[47]), "+f"(d[48]), "+f"(d[49]), "+f"(d[50]), "+f"(d[51]), "+f"(d[52]), "+f"(d[53]), "+f"(d[54]), "+f"(d[55]), "+f"(d[56]), "+f"(d[57]), "+f"(d[58]), "+f"(d[59]), "+f"(d[60]), "+f"(d[61]), "+f"(d[62]), "+f"(d[63])
    : "r"(a0), "r"(a1), "r"(a2), "r"(a3), "l"(descB), "r"(scaleD));
}
__device__ __forceinline__ void wgmma_rs_n64_ta0_tb1(float (&d)[32], uint32_t a0, uint32_t a1, uint32_t a2, uint32_t a3, uint64_t descB, int scaleD) {
  asm volatile("{\n.reg .pred p;\nsetp.ne.b32 p, %37, 0;\n"
    "wgmma.mma_async.sync.aligned.m64n64k16.f32.bf16.bf16 "
    "{%0, %1, %2, %3, %4, %5, %6, %7, %8, %9, %10, %11, %12, %13, %14, %15, %16, %17, %18, %19, %20, %21, %22, %23, %24, %25, %26, %27, %28, %29, %30, %31}, "
    "{%32, %33, %34, %35}, %36, p, 1, 1, 1;\n}\n"
    : "+f"(d[0]), "+f"(d[1]), "+f"(d[2]), "+f"(d[3]), "+f"(d[4]), "+f"(d[5]), "+f"(d[6]), "+f"(d[7]), "+f"(d[8]), "+f"(d[9]), "+f"(d[10]), "+f"(d[11]), "+f"(d[12]), "+f"(d[13]), "+f"(d[14]), "+f"(d[15]), "+f"(d[16]), "+f"(d[17]), "+f"(d[18]), "+f"(d[19]), "+f"(d[20]), "+f"(d[21]), "+f"(d[22]), "+f"(d[23]), "+f"(d[24]), "+f"(d[25]), "+f"(d[26]), "+f"(d[27]), "+f"(d[28]), "+f"(d[29]), "+f"(d[30]), "+f"(d[31])
    : "r"(a0), "r"(a1), "r"(a2), "r"(a3), "l"(descB), "r"(scaleD));
}
__device__ __forceinline__ void wgmma_ss_n128_ta0_tb1(float (&d)[64], uint64_t descA, uint64_t descB, int scaleD) {
  asm volatile("{\n.reg .pred p;\nsetp.ne.b32 p, %66, 0;\n"
    "wgmma.mma_async.sync.aligned.m64n128k16.f32.bf16.bf16 "
    "{%0, %1, %2, %3, %4, %5, %6, %7, %8, %9, %10, %11, %12, %13, %14, %15, %16, %17, %18, %19, %20, %21, %22, %23, %24, %25, %26, %27, %28, %29, %30, %31, %32, %33, %34, %35, %36, %37, %38, %39, %40, %41, %42, %43, %44, %45, %46, %47, %48, %49, %50, %51, %52, %53, %54, %55, %56, %57, %58, %59, %60, %61, %62, %63}, "
    "%64, %65, p, 1, 1, 0, 1;\n}\n"
    : "+f"(d[0]), "+f"(d[1]), "+f"(d[2]), "+f"(d[3]), "+f"(d[4]), "+f"(d[5]), "+f"(d[6]), "+f"(d[7]), "+f"(d[8]), "+f"(d[9]), "+f"(d[10]), "+f"(d[11]), "+f"(d[12]), "+f"(d[13]), "+f"(d[14]), "+f"(d[15]), "+f"(d[16]), "+f"(d[17]), "+f"(d[18]), "+f"(d[19]), "+f"(d[20]), "+f"(d[21]), "+f"(d[22]), "+f"(d[23]), "+f"(d[24]), "+f"(d[25]), "+f"(d[26]), "+f"(d[27]), "+f"(d[28]), "+f"(d[29]), "+f"(d[30]), "+f"(d[31]), "+f"(d[32]), "+f"(d[33]), "+f"(d[34]), "+f"(d[35]), "+f"(d[36]), "+f"(d[37]), "+f"(d[38]), "+f"(d[39]), "+f"(d[40]), "+f"(d[41]), "+f"(d[42]), "+f"(d[43]), "+f"(d[44]), "+f"(d[45]), "+f"(d[46]), "+f"(d[47]), "+f"(d[48]), "+f"(d[49]), "+f"(d[50]), "+f"(d[51]), "+f"(d[52]), "+f"(d[53]), "+f"(d[54]), "+f"(d[55]), "+f"(d[56]), "+f"(d[57]), "+f"(d[58]), "+f"(d[59]), "+f"(d[60]), "+f"(d[61]), "+f"(d[62]), "+f"(d[63])
    : "l"(descA), "l"(descB), "r"(scaleD));
}
__device__ __forceinline__ void wgmma_ss_n160_ta0_tb1(float (&d)[80], uint64_t descA, uint64_t descB, int scaleD) {
  asm volatile("{\n.reg .pred p;\nsetp.ne.b32 p, %82, 0;\n"
    "wgmma.mma_async.sync.aligned.m64n160k16.f32.bf16.bf16 "
    "{%0, %1, %2, %3, %4, %5, %6, %7, %8, %9, %10, %11, %12, %13, %14, %15, %16, %17, %18, %19, %20, %21, %22, %23, %24, %25, %26, %27, %28, %29, %30, %31, %32, %33, %34, %35, %36, %37, %38, %39, %40, %41, %42, %43, %44, %45, %46, %47, %48, %49, %50, %51, %52, %53, %54, %55, %56, %57, %58, %59, %60, %61, %62, %63, %64, %65, %66, %67, %68, %69, %70, %71, %72, %73, %74, %75, %76, %77, %78, %79}, "
    "%80, %81, p, 1, 1, 0, 1;\n}\n"
    : "+f"(d[0]), "+f"(d[1]), "+f"(d[2]), "+f"(d[3]), "+f"(d[4]), "+f"(d[5]), "+f"(d[6]), "+f"(d[7]), "+f"(d[8]), "+f"(d[9]), "+f"(d[10]), "+f"(d[11]), "+f"(d[12]), "+f"(d[13]), "+f"(d[14]), "+f"(d[15]), "+f"(d[16]), "+f"(d[17]), "+f"(d[18]), "+f"(d[19]), "+f"(d[20]), "+f"(d[21]), "+f"(d[22]), "+f"(d[23]), "+f"(d[24]), "+f"(d[25]), "+f"(d[26]), "+f"(d[27]), "+f"(d[28]), "+f"(d[29]), "+f"(d[30]), "+f"(d[31]), "+f"(d[32]), "+f"(d[33]), "+f"(d[34]), "+f"(d[35]), "+f"(d[36]), "+f"(d[37]), "+f"(d[38]), "+f"(d[39]), "+f"(d[40]), "+f"(d[41]), "+f"(d[42]), "+f"(d[43]), "+f"(d[44]), "+f"(d[45]), "+f"(d[46]), "+f"(d[47]), "+f"(d[48]), "+f"(d[49]), "+f"(d[50]), "+f"(d[51]), "+f"(d[52]), "+f"(d[53]), "+f"(d[54]), "+f"(d[55]), "+f"(d[56]), "+f"(d[57]), "+f"(d[58]), "+f"(d[59]), "+f"(d[60]), "+f"(d[61]), "+f"(d[62]), "+f"(d[63]), "+f"(d[64]), "+f"(d[65]), "+f"(d[66]), "+f"(d[67]), "+f"(d[68]), "+f"(d[69]), "+f"(d[70]), "+f"(d[71]), "+f"(d[72]), "+f"(d[73]), "+f"(d[74]), "+f"(d[75]), "+f"(d[76]), "+f"(d[77]), "+f"(d[78]), "+f"(d[79])
    : "l"(descA), "l"(descB), "r"(scaleD));
}

#define PROF_DECL(b)
#define PROF_EV(tag)
#define PROF_GT(tag)

template <int N> struct IC { static constexpr int value = N; };
struct Cur {
    uint32_t slot, ph;
    __device__ __forceinline__ void adv() { if (++slot == NSLOT) { slot = 0; ph ^= 1; } }
};
constexpr int E0 = 2;
__host__ __device__ constexpr uint32_t slot_of(int e) { return (e + E0) % NSLOT; }
__device__ __forceinline__ Cur cur_at(int e) { Cur c; c.slot = (e + E0) % NSLOT; c.ph = ((e + E0) / NSLOT) & 1; return c; }

__device__ __forceinline__ int op_head(int i, int kap) { return 16 * kap + 2 * (i & 7) + (i >> 3); }

constexpr float SM_SCALE = 0.08838834764831845f * 1.4426950408889634f;

struct Ctx {
    uint32_t ring, misc;
    uint32_t rel;
    int w, warp, lane;
};
__device__ __forceinline__ void release(const Ctx& c, uint32_t off, uint32_t cnt) {
    if (c.lane < 2) mbar_arrive_cluster(c.rel + off, cnt);
}
__device__ __forceinline__ void signal_event(const Ctx& c, int ev) {
    __syncwarp();
    if (c.lane == 0) mbar_arrive(c.misc + BAR_EV + (c.w * 16 + ev) * 8);
}
template <int NK, int OFF, int N>
__device__ __forceinline__ uint32_t load_afrag(uint32_t (&a)[N], uint32_t base, const Ctx& c) {
    int r = c.lane & 7, mat = c.lane >> 3;
    uint32_t addr = base + (8 * (mat >> 1) + r) * 128 + (((2 * c.warp + (mat & 1)) ^ r) << 4);
#pragma unroll
    for (int k = 0; k < NK; k++) ldsm4t(a[OFF + 4 * k], a[OFF + 4 * k + 1], a[OFF + 4 * k + 2], a[OFF + 4 * k + 3], addr + k * 2048);
    uint32_t dep = 0;
#pragma unroll
    for (int k = 0; k < NK; k++) dep |= a[OFF + 4 * k];
    return dep & blockIdx.y;
}
__device__ __forceinline__ void store_proj(const float (&acc)[64], unsigned char* dst  , int perm, const Ctx& c) {
    int g = c.lane >> 2, t = c.lane & 3;
#pragma unroll
    for (int i = 0; i < 2; i++) {
        int row = 64 * c.w + 16 * c.warp + 8 * i + g;
        if (perm) row = perm32(row);
        unsigned char* p = dst + row * 128;
#pragma unroll
        for (int q = 0; q < 4; q++) {
            int chunk = (4 * (q & 1) + t) ^ (row & 7);
            stg128(p + (q >> 1) * 16384 + chunk * 16,
                   pack_bf16(acc[16 * q + 2 * i], acc[16 * q + 2 * i + 1]), pack_bf16(acc[16 * q + 4 + 2 * i], acc[16 * q + 4 + 2 * i + 1]),
                   pack_bf16(acc[16 * q + 8 + 2 * i], acc[16 * q + 8 + 2 * i + 1]), pack_bf16(acc[16 * q + 12 + 2 * i], acc[16 * q + 12 + 2 * i + 1]));
        }
    }
}

constexpr float SAFE_SUM = 1099511627776.0f;
template <int NJ>
__device__ __forceinline__ void row_max(const float (&s)[4 * NJ], float (&mx)[2]) {
#pragma unroll
    for (int i = 0; i < 2; i++) {
        float a = fmaxf(s[2 * i], s[2 * i + 1]), b = fmaxf(s[4 + 2 * i], s[4 + 2 * i + 1]);
#pragma unroll
        for (int j = 2; j < NJ; j += 2) {
            a = fmaxf(a, fmaxf(s[4 * j + 2 * i], s[4 * j + 2 * i + 1]));
            b = fmaxf(b, fmaxf(s[4 * j + 4 + 2 * i], s[4 * j + 4 + 2 * i + 1]));
        }
        a = fmaxf(a, b);
        a = fmaxf(a, __shfl_xor_sync(0xffffffffu, a, 1));
        mx[i] = fmaxf(a, __shfl_xor_sync(0xffffffffu, a, 2));
    }
}
template <int NJ, bool SHIFT>
__device__ __forceinline__ void exp_sum(float (&s)[4 * NJ], const float (&m)[2], float& l0, float& l1) {
#pragma unroll
    for (int j = 0; j < NJ; j++) {
#pragma unroll
        for (int e = 0; e < 4; e++) s[4 * j + e] = ex2(SHIFT ? s[4 * j + e] - m[e >> 1] : s[4 * j + e]);
        l0 += s[4 * j + 0] + s[4 * j + 1]; l1 += s[4 * j + 2] + s[4 * j + 3];
    }
}
__device__ __forceinline__ void recompute_scores(float (&s)[64], const uint32_t (&q)[32], uint32_t kaddr, const Ctx& c) {
    const int r = c.lane & 7, mat = c.lane >> 3;
    const uint32_t a0 = kaddr + (8 * (mat & 1) + r) * 128 + (((mat >> 1) ^ r) << 4);
#pragma unroll
    for (int i = 0; i < 64; i++) s[i] = 0.f;
#pragma unroll
    for (int jp = 0; jp < 8; jp++) {
#pragma unroll
        for (int k = 0; k < 8; k++) {
            asm volatile(
                "{\n.reg .b32 b0, b1, b2, b3;\n"
                "ldmatrix.sync.aligned.m8n8.x4.trans.shared.b16 {b0,b1,b2,b3}, [%12];\n"
                "mma.sync.aligned.m16n8k16.row.col.f32.bf16.bf16.f32 {%0,%1,%2,%3}, {%8,%9,%10,%11}, {b0,b1}, {%0,%1,%2,%3};\n"
                "mma.sync.aligned.m16n8k16.row.col.f32.bf16.bf16.f32 {%4,%5,%6,%7}, {%8,%9,%10,%11}, {b2,b3}, {%4,%5,%6,%7};\n}\n"
                : "+f"(s[8 * jp]), "+f"(s[8 * jp + 1]), "+f"(s[8 * jp + 2]), "+f"(s[8 * jp + 3]),
                  "+f"(s[8 * jp + 4]), "+f"(s[8 * jp + 5]), "+f"(s[8 * jp + 6]), "+f"(s[8 * jp + 7])
                : "r"(q[4 * k]), "r"(q[4 * k + 1]), "r"(q[4 * k + 2]), "r"(q[4 * k + 3]),
                  "r"((a0 ^ ((jp & 3) << 5)) + (jp >> 2) * 16384 + k * 2048) : "memory");
        }
    }
}
__device__ __forceinline__ int mask_lim(const Ctx& c) { return perm32(16 * c.warp + (c.lane >> 2)) - 8 * (c.lane & 3); }
template <int J0>
__device__ __forceinline__ void mask_diag(float (&s)[4 * J0 + 32], const Ctx& c) {
    const int lim = mask_lim(c);
    if (c.warp < 2) {
#pragma unroll
        for (int x = 0; x < 16; x++) {
            if (2 * (x >> 2) + (x & 1) - (x & 2) > lim) s[4 * J0 + x] = -INFINITY;
            s[4 * J0 + 16 + x] = -INFINITY;
        }
    } else {
#pragma unroll
        for (int x = 0; x < 16; x++)
            if (32 + 2 * (x >> 2) + (x & 1) - (x & 2) > lim) s[4 * J0 + 16 + x] = -INFINITY;
    }
}
__device__ __forceinline__ void mask_any(float (&s)[64], int hh, const Ctx& c) {
    const int lim = mask_lim(c) + 64 * hh;
#pragma unroll
    for (int x = 0; x < 64; x++)
        if (32 * (x >> 4) + 2 * ((x >> 2) & 3) + (x & 1) - (x & 2) > lim) s[x] = -INFINITY;
}
__device__ __forceinline__ void issue_pv(float (&o)[64], const uint32_t (&p)[32], uint32_t vaddr, int acc, int mode  ) {
    uint64_t d = mkdesc(vaddr, 16, 1024, 1);
    if (mode == 0) {
        wg_fence();
#pragma unroll
        for (int k = 0; k < 8; k++)
            wgmma_rs_n128_ta0_tb0(o, p[4 * k], p[4 * k + 1], p[4 * k + 2], p[4 * k + 3], d + (k >> 2) * 1024 + 2 * (k & 3), k ? 1 : acc);
        wg_commit();
    } else if (mode == 1) {
        wg_fence();
#pragma unroll
        for (int k = 0; k < 4; k++) wgmma_rs_n128_ta0_tb0(o, p[4 * k], p[4 * k + 1], p[4 * k + 2], p[4 * k + 3], d + 2 * k, k != 0);
        wg_commit();
    } else {
        wg_fence();
        wgmma_rs_n128_ta0_tb0(o, p[0], p[1], p[2], p[3], d, 0);
        wg_commit();
    }
}
__device__ __forceinline__ void issue_qk(float (&s)[64], const uint32_t (&q)[32], uint32_t kaddr) {
    uint64_t d = mkdesc(kaddr, 16384, 1024, 1);
    wg_fence();
#pragma unroll
    for (int k = 0; k < 8; k++) wgmma_rs_n128_ta0_tb1(s, q[4 * k], q[4 * k + 1], q[4 * k + 2], q[4 * k + 3], d + 128 * k, k != 0);
    wg_commit();
}
__device__ __forceinline__ void issue_qk_half(float (&s32)[32], const uint32_t (&q)[32], uint32_t kaddr) {
    uint64_t d = mkdesc(kaddr, 16384, 1024, 1);
    wg_fence();
#pragma unroll
    for (int k = 0; k < 8; k++) wgmma_rs_n64_ta0_tb1(s32, q[4 * k], q[4 * k + 1], q[4 * k + 2], q[4 * k + 3], d + 128 * k, k != 0);
    wg_commit();
}
__device__ __forceinline__ void row_inv(const float (&l)[2], float (&inv)[2]) {
#pragma unroll
    for (int i = 0; i < 2; i++) {
        float sum = l[i];
        sum += __shfl_xor_sync(0xffffffffu, sum, 1);
        sum += __shfl_xor_sync(0xffffffffu, sum, 2);
        inv[i] = rcp_fast(sum);
    }
}
__device__ __forceinline__ void store_ctx(const float (&o)[64], const float (&inv)[2], unsigned char* dst, uint64_t pol, const Ctx& c) {
    const int g = c.lane >> 2, t = c.lane & 3;
    unsigned char* p0 = dst + (16 * c.warp + g) * 128 + ((t ^ g) << 4);
    unsigned char* p1 = dst + (16 * c.warp + g) * 128 + (((4 + t) ^ g) << 4);
#pragma unroll
    for (int i = 0; i < 2; i++)
#pragma unroll
        for (int q = 0; q < 4; q++)
            stg128_hint(((q & 1) ? p1 : p0) + (q >> 1) * 8192 + i * 1024,
                        pack_bf16(o[16 * q + 2 * i] * inv[i], o[16 * q + 2 * i + 1] * inv[i]),
                        pack_bf16(o[16 * q + 4 + 2 * i] * inv[i], o[16 * q + 4 + 2 * i + 1] * inv[i]),
                        pack_bf16(o[16 * q + 8 + 2 * i] * inv[i], o[16 * q + 8 + 2 * i + 1] * inv[i]),
                        pack_bf16(o[16 * q + 12 + 2 * i] * inv[i], o[16 * q + 12 + 2 * i + 1] * inv[i]), pol);
}

__device__ __forceinline__ const unsigned char* xn_addr(int row, int col) {
    row = perm32(row);
    return g_xn + ((row >> 7) * 10 + (col >> 6)) * 16384 + (row & 127) * 128 + ((((col & 63) >> 3) ^ (row & 7)) << 4);
}
__device__ __forceinline__ void mma16816(float (&d)[4], uint32_t a0, uint32_t a1, uint32_t a2, uint32_t a3, uint32_t b0, uint32_t b1) {
    asm volatile("mma.sync.aligned.m16n8k16.row.col.f32.bf16.bf16.f32 {%0,%1,%2,%3}, {%4,%5,%6,%7}, {%8,%9}, {%0,%1,%2,%3};"
                 : "+f"(d[0]), "+f"(d[1]), "+f"(d[2]), "+f"(d[3]) : "r"(a0), "r"(a1), "r"(a2), "r"(a3), "r"(b0), "r"(b1));
}
__device__ __forceinline__ uint32_t lds32(uint32_t addr) { uint32_t v; asm volatile("ld.shared.u32 %0, [%1];" : "=r"(v) : "r"(addr)); return v; }

__device__ __forceinline__ void ln_rows(const Params& P, int row0, int lane, uint32_t wr_s) {
    const int hl = lane & 15, row = row0 + (lane >> 4);
    uint32_t v[20];
#pragma unroll
    for (int i = 0; i < 5; i++) {
        uint4 u;
        asm("ld.global.nc.L2::cache_hint.v4.b32 {%0,%1,%2,%3}, [%4], %5;" : "=r"(u.x), "=r"(u.y), "=r"(u.z), "=r"(u.w)
            : "l"(P.x + (size_t)row * DM + 128 * i + 8 * hl), "l"(policy(HM & 512)));
        v[4 * i] = u.x; v[4 * i + 1] = u.y; v[4 * i + 2] = u.z; v[4 * i + 3] = u.w;
    }
    float mean = 0.f, m2 = 0.f, acc2 = 0.f;
#pragma unroll
    for (int i = 0; i < 20; i++) { mean += bf_lo(v[i]); acc2 += bf_hi(v[i]); }
    mean = (mean + acc2) * (1.0f / 40);
    acc2 = 0.f;
#pragma unroll
    for (int i = 0; i < 20; i++) {
        float d0 = __uint_as_float(__byte_perm(v[i], 0, 0x1044)) - mean, d1 = __uint_as_float(__byte_perm(v[i], 0, 0x3244)) - mean;
        m2 = fmaf(d0, d0, m2); acc2 = fmaf(d1, d1, acc2);
    }
    m2 += acc2;
    acc2 = 0.f;
#pragma unroll
    for (int o = 1; o < 16; o <<= 1) {
        float mo = __shfl_xor_sync(0xffffffffu, mean, o), qo = __shfl_xor_sync(0xffffffffu, m2, o), d = mo - mean;
        m2 = fmaf(d * d, 20.0f * o, m2 + qo);
        mean = 0.5f * (mean + mo);
    }
    const uint32_t mb2 = pack_bf16(mean, mean);
    const float inv = rcp_fast(bf_round(sqrt_fast(bf_round(bf_round(m2 * (1.0f / DM)) + 1e-5f))));
    float dot = 0.f;
    unsigned char* xp = const_cast<unsigned char*>(xn_addr(row, 8 * hl));
#pragma unroll
    for (int i = 0; i < 5; i++) {
        uint32_t ww[4];
        asm volatile("ld.shared.v4.b32 {%0,%1,%2,%3}, [%4];" : "=r"(ww[0]), "=r"(ww[1]), "=r"(ww[2]), "=r"(ww[3]) : "r"(wr_s + 256 * i + 16 * hl) : "memory");
#pragma unroll
        for (int e = 0; e < 4; e++) {
            uint32_t d;
            asm("sub.rn.bf16x2 %0, %1, %2;" : "=r"(d) : "r"(v[4 * i + e]), "r"(mb2));
            d = pack_bf16(bf_lo(d) * inv, bf_hi(d) * inv);
            v[4 * i + e] = d;
            dot = fmaf(bf_lo(d), bf_lo(ww[e]), dot);
            acc2 = fmaf(bf_hi(d), bf_hi(ww[e]), acc2);
        }
        stg128(xp + i * 32768, v[4 * i], v[4 * i + 1], v[4 * i + 2], v[4 * i + 3]);
    }
    dot += acc2;
#pragma unroll
    for (int o = 8; o > 0; o >>= 1) dot += __shfl_xor_sync(0xffffffffu, dot, o);
    if (hl == 0) { g_router[row] = bf_round(dot); g_stats[row] = make_uint2(mb2, __float_as_uint(inv)); }
}

__device__ __forceinline__ void aux_cta(const Params& P, const CUtensorMap* tmG, const CUtensorMap* tmU, const CUtensorMap* tmD, unsigned char* sm, int a) {
    constexpr int STG = 57344, XS = 3 * STG, HS = XS + 8 * 1296, KEY = HS + 8 * 912, MI = KEY + 8192;
    const int tid = threadIdx.x, warp = __shfl_sync(0xffffffffu, tid >> 5, 0), lane = tid & 31;
    const uint32_t sb = smem_u32(sm);
    const uint32_t full = sb + MI, empty = sb + MI + 32;
    int* s_sel = reinterpret_cast<int*>(sm + MI + 64);
    float* s_r = reinterpret_cast<float*>(sm + MI + 96);
    volatile unsigned* s_misc = reinterpret_cast<volatile unsigned*>(sm + MI + 128);
    uint32_t* s_key = reinterpret_cast<uint32_t*>(sm + KEY);
    PROF_DECL(128 + a)
    PROF_GT(0);
    if (tid == 0) {
        for (int i = 0; i < 3; i++) { mbar_init(full + 8 * i, 1); mbar_init(empty + 8 * i, 10); }
        asm volatile("fence.mbarrier_init.release.cluster;" ::: "memory");
    }
    __syncthreads();
    if (warp == 11) {
        if (elect_one()) {
            int st = 0; uint32_t ph = 0;
#pragma unroll 1
            for (int s = 0; s < 34; s++) {
                mbar_wait(empty + 8 * st, ph ^ 1);
                const uint32_t dst = sb + st * STG, fb = full + 8 * st;
                if (s < 20) {
                    mbar_expect_tx(fb, 57344);
                    tma3d(dst, tmG, 0, 32 * s, 7 * a, fb);
                    tma3d(dst + 28672, tmU, 0, 32 * s, 7 * a, fb);
                } else {
                    mbar_expect_tx(fb, 40960);
                    tma3d(dst, tmD, 0, 448 * a + 32 * (s - 20), 0, fb);
                }
                if (s >= 3) {
#pragma unroll 1
                    for (int f = (s == 3 ? 4 : s + 6); f <= s + 6 && f < 34; f++) {
                        if (f < 20) { tma3d_prefetch(tmG, 0, 32 * f, 7 * a); tma3d_prefetch(tmU, 0, 32 * f, 7 * a); }
                        else tma3d_prefetch(tmD, 0, 448 * a + 32 * (f - 20), 0);
                    }
                }
                if (++st == 3) { st = 0; ph ^= 1; }
            }
        }
        return;
    }
    if (tid < 80) *reinterpret_cast<uint4*>(sm + KEY + 1024 + tid * 16) = __ldg(reinterpret_cast<const uint4*>(P.wr) + tid);
    __nanosleep(AUXDELAY);
#pragma unroll 1
    for (int i = tid; i < 64 * 40; i += 352) asm volatile("prefetch.global.L2 [%0];" ::"l"(P.x + (size_t)((4 + a) * 256 + 192) * DM + i * 16));
    bar_sync(2, 352);
#pragma unroll 1
    for (int i = warp; i < 32; i += 11) ln_rows(P, (4 + a) * 256 + 192 + 2 * i, lane, sb + KEY + 1024);
    bar_sync(2, 352);
    if (tid == 320) flag_signal(flag_ptr(FL_LN + 4 + a));
    PROF_GT(49);
    if (warp == 10) return;
    if (tid < 8) {
        unsigned e = *reinterpret_cast<volatile unsigned*>(&g_epoch);
        if (tid == 0) s_misc[0] = e;
        flag_wait(flag_ptr(FL_LN + tid), (e + 1) * (32u + (tid >> 2)));
    }
    bar_sync(1, 320);
    PROF_GT(50);
    const unsigned ep = s_misc[0];
    auto top8 = [&](uint32_t (&key)[8]) {
        uint32_t mine = 0;
#pragma unroll 1
        for (int r = 0; r < TOPC; r++) {
            uint32_t best = 0;
#pragma unroll
            for (int i = 0; i < 8; i++) best = max(best, key[i]);
            best = __reduce_max_sync(0xffffffffu, best);
#pragma unroll
            for (int i = 0; i < 8; i++) if (key[i] == best) key[i] = 0;
            if (lane == r) mine = best;
        }
        return mine;
    };
#pragma unroll 1
    for (int pass = 0; pass < 2; pass++) {
        if (warp < (pass ? 1 : 8)) {
            uint32_t key[8];
#pragma unroll
            for (int i = 0; i < 8; i++) {
                if (pass == 0) {
                    int idx = warp * 256 + i * 32 + lane;
                    uint32_t b = __float_as_uint(__ldcg(g_router + idx)) >> 16;
                    b = (b & 0x8000u) ? (~b & 0xffffu) : (b | 0x8000u);
                    key[i] = (b << 16) | (uint32_t)(0xffff - idx);
                } else key[i] = i < 2 ? s_key[i * 32 + lane] : 0u;
            }
            uint32_t best = top8(key);
            if (lane < TOPC) {
                if (pass == 0) s_key[warp * 8 + lane] = best;
                else {
                    uint32_t b = best >> 16;
                    b = (b & 0x8000u) ? (b & 0x7fffu) : (~b & 0xffffu);
                    s_sel[lane] = 0xffff - (int)(best & 0xffffu);
                    s_r[lane] = __uint_as_float(b << 16);
                }
            }
        }
        bar_sync(1, 320);
    }
#pragma unroll
    for (int it = 0; it < 2; it++) {
        int i = tid + it * 320, tk = i / 80, ch = i % 80;
        *reinterpret_cast<uint4*>(sm + XS + tk * 1296 + ch * 16) = __ldcg(reinterpret_cast<const uint4*>(xn_addr(s_sel[tk], ch * 8)));
    }
    bar_sync(1, 320);
    PROF_GT(51);
    const int g = lane >> 2, t = lane & 3;
    const uint32_t woff = warp * 4096 + (8 * (lane >> 4) + (lane & 7)) * 128 + ((((lane >> 3) & 1) ^ (lane & 7)) << 4);
    int st = 0; uint32_t ph = 0;
    float ga[4][4], ua[4][4];
#pragma unroll
    for (int i = 0; i < 4; i++)
#pragma unroll
        for (int e = 0; e < 4; e++) { ga[i][e] = 0.f; ua[i][e] = 0.f; }
#pragma unroll 1
    for (int s = 0; s < 34; s++) {
        if (s == 20) {
            if (warp < 7) {
#pragma unroll
                for (int i = 0; i < 4; i++)
#pragma unroll
                    for (int e = 0; e < 4; e++) {
                        float gv = bf_round(ga[i][e]), uv = bf_round(ua[i][e]);
                        float sg = bf_round(__fdividef(gv, 1.0f + __expf(fminf(-gv, 80.f))));
                        int f = warp * 64 + i * 16 + g + 8 * (e >> 1), tk = 2 * t + (e & 1);
                        *reinterpret_cast<__nv_bfloat16*>(sm + HS + tk * 912 + f * 2) = __float2bfloat16_rn(sg * uv);
                        ga[i][e] = 0.f;
                    }
            }
            bar_sync(1, 320);
            PROF_GT(52);
        }
        mbar_wait(full + 8 * st, ph);
        if (s >= 20 || warp < 7) {
#pragma unroll
            for (int kk = 0; kk < 2; kk++) {
                uint32_t xb = sb + (s < 20 ? XS + g * 1296 + s * 64 : HS + g * 912 + (s - 20) * 64) + 32 * kk + 4 * t;
                uint32_t b0 = lds32(xb), b1 = lds32(xb + 16);
                uint32_t wa = sb + st * STG + woff + kk * 2048;
#pragma unroll
                for (int i = 0; i < 4; i++) {
                    uint32_t a0, a1, a2, a3;
                    ldsm4t(a0, a1, a2, a3, wa ^ (i << 5));
                    mma16816(ga[i], a0, a1, a2, a3, b0, b1);
                    if (s < 20) {
                        ldsm4t(a0, a1, a2, a3, (wa ^ (i << 5)) + 28672);
                        mma16816(ua[i], a0, a1, a2, a3, b0, b1);
                    }
                }
            }
        }
        asm volatile("fence.proxy.async.shared::cta;" ::: "memory");
        __syncwarp();
        if (lane == 0) mbar_arrive(empty + 8 * st);
        if (++st == 3) { st = 0; ph ^= 1; }
    }
#pragma unroll
    for (int i = 0; i < 4; i++)
#pragma unroll
        for (int e = 0; e < 4; e += 2)
            *reinterpret_cast<float2*>(g_moe_part + (a * DM + warp * 64 + i * 16 + g + 4 * e) * 8 + 2 * t) = make_float2(ga[i][e], ga[i][e + 1]);
    bar_sync(1, 320);
    if (tid == 0) {
        __threadfence();
        unsigned old = atomicAdd(flag_ptr(FL_MOE_CNT), 1u);
        s_misc[1] = (old == ep * 4u + 3u);
        __threadfence();
    }
    bar_sync(1, 320);
    PROF_GT(53);
    if (s_misc[1]) {
        const float4* pp = reinterpret_cast<const float4*>(g_moe_part);
#pragma unroll 2
        for (int i = tid; i < DM * 2; i += 320) {
            float4 v0 = __ldcg(pp + i), v1 = __ldcg(pp + DM * 2 + i), v2 = __ldcg(pp + DM * 4 + i), v3 = __ldcg(pp + DM * 6 + i);
            float y[4] = {v0.x + v1.x + v2.x + v3.x, v0.y + v1.y + v2.y + v3.y, v0.z + v1.z + v2.z + v3.z, v0.w + v1.w + v2.w + v3.w};
#pragma unroll
            for (int e = 0; e < 4; e++) {
                int col = i >> 1, tk = (i & 1) * 4 + e;
                float sg = bf_round(__fdividef(1.0f, 1.0f + __expf(fminf(-s_r[tk], 80.f))));
                float upd = bf_round(bf_round(y[e]) * sg);
                float xn = __bfloat162float(*reinterpret_cast<const __nv_bfloat16*>(sm + XS + tk * 1296 + col * 2));
                g_brow[tk * DM + col] = __float2bfloat16_rn(xn + upd);
            }
        }
        if (tid < TOPC) g_sel[tid] = s_sel[tid];
        bar_sync(1, 320);
        if (tid == 0) {
            flag_signal(flag_ptr(FL_MOE_DONE));
            *reinterpret_cast<volatile unsigned*>(&g_epoch) = ep + 1;
        }
        PROF_GT(54);
    }
}

__global__ void __cluster_dims__(2, 1, 1) __launch_bounds__(384, 1)
fused_kernel(const __grid_constant__ CUtensorMap tmC, const __grid_constant__ CUtensorMap tmWk, const __grid_constant__ CUtensorMap tmWv,
             const __grid_constant__ CUtensorMap tmWq, const __grid_constant__ CUtensorMap tmWo,
             const __grid_constant__ CUtensorMap tmG, const __grid_constant__ CUtensorMap tmU, const __grid_constant__ CUtensorMap tmD, const Params P) {
    extern __shared__ __align__(1024) unsigned char smem_raw[];
    const uint32_t ring = smem_u32(smem_raw);
    const uint32_t misc = ring + RING_BYTES;
    const int tid = threadIdx.x;
    const int rank = blockIdx.x & 1;
    uint32_t smid, nsm;
    asm("mov.u32 %0, %%smid;" : "=r"(smid));
    asm("mov.u32 %0, %%nsmid;" : "=r"(nsm));
    if (nsm != 132) smid = blockIdx.x;
    auto role_of = [](int tpc) {
        return tpc < 32 ? (tpc & 7) * 8 + (tpc >> 3) : tpc < 60 ? (1 + (tpc - 32) % 7) * 8 + 4 + (tpc - 32) / 7 : tpc < 64 ? tpc - 56 : tpc;
    };
    int mc = role_of(smid >> 1);
    PROF_DECL(mc * 2 + rank)
    PROF_GT(0); PROF_EV(1);

    auto prefetch_w = [&](int ch) {
        const int i = tid - 128;
        asm volatile("prefetch.global.L2 [%0];" ::"l"((rank ? P.wv : P.wk) + (size_t)(ch * 128 + (mc & 3) * 32 + (i >> 3)) * 4096 + (mc >> 2) * 256 + (i & 7) * 16));
    };
    if (tid >= 128 && mc < 64) {
        if (tid < 256) asm volatile("prefetch.global.L2 [%0];" ::"l"(P.c + (size_t)((12 + (mc & 3)) * 128 + ((mc >> 2) * 2 + rank) * 4) * DC + (tid - 128) * 16));
        prefetch_w(0);
    }
    auto load_w0 = [&]() {
        const CUtensorMap* tw = rank ? &tmWv : &tmWk;
        mbar_expect_tx(misc + BAR_FULL + 8 * slot_of(0), SLOT_BYTES);
        tma2d(ring + slot_of(0) * SLOT_BYTES, tw, (mc >> 2) * 256, 0, misc + BAR_FULL + 8 * slot_of(0), policy(HM & 1));
        tma2d(ring + slot_of(0) * SLOT_BYTES + 16384, tw, (mc >> 2) * 256 + 64, 0, misc + BAR_FULL + 8 * slot_of(0), policy(HM & 1));
    };
    if (tid == 0) {
#pragma unroll
        for (int i = 0; i < NSLOT; i++) mbar_init(misc + BAR_FULL + 8 * i, 1);
#pragma unroll
        for (int i = 0; i < E0; i++) mbar_arrive(misc + BAR_FULL + 8 * i);
        asm volatile("fence.mbarrier_init.release.cluster;" ::: "memory");
        if (mc < 64) load_w0();
    }
    if (tid == 160) {
        asm volatile("st.shared.u32 [%0], %1;" ::"r"(misc + MISC_SMID), "r"(smid) : "memory");
        asm volatile("fence.release.sync_restrict::shared::cta.cluster;" ::: "memory");
    }
    if (tid == 32) {
        asm volatile("prefetch.tensormap [%0];" ::"l"(&tmC) : "memory");
#pragma unroll
        for (int i = 0; i < NSLOT; i++) mbar_init(misc + BAR_EMPTY + 8 * i, 16);
#pragma unroll
        for (int i = 0; i < E0; i++) mbar_arrive_cluster(misc + BAR_EMPTY + 8 * i, 16);
        asm volatile("fence.mbarrier_init.release.cluster;" ::: "memory");
    }
    if (tid == 64) {
#pragma unroll
        for (int i = 0; i < NST3; i++) { mbar_init(misc + BAR_FULL3 + 8 * i, 1); mbar_init(misc + BAR_EMPTY3 + 8 * i, 16); }
#pragma unroll
        for (int i = 0; i < 4; i++) mbar_init(misc + BAR_LN + 8 * i, 2);
        mbar_init(misc + BAR_PROG, 1); mbar_init(misc + BAR_PROG + 8, 1); mbar_init(misc + BAR_PROG + 16, 1);
        asm volatile("fence.mbarrier_init.release.cluster;" ::: "memory");
    }
    if (tid == 96) {
#pragma unroll
        for (int i = 0; i < 34; i++) mbar_init(misc + BAR_DEP + 8 * i, 1);
    }
    if (tid == 128) {
#pragma unroll
        for (int i = 0; i < 32; i++) mbar_init(misc + BAR_EV + 8 * i, 4);
    }
    __syncthreads();
    asm volatile("barrier.cluster.arrive.relaxed.aligned;\nbarrier.cluster.wait.aligned;" ::: "memory");
    {
        uint32_t peer;
        asm volatile("ld.shared::cluster.u32 %0, [%1];" : "=r"(peer) : "r"(mapa(misc + MISC_SMID, rank ^ 1)) : "memory");
        if ((__shfl_sync(0xffffffffu, peer, 0) ^ smid) != 1) {
            if (tid == 0) {
                const unsigned ep1 = *reinterpret_cast<volatile unsigned*>(&g_epoch) + 1;
                if ((smid & 1) == 0) atomicExch(g_roleq + 2 + (atomicAdd(g_roleq, 1u) & 127), (ep1 << 8) | (smid >> 1));
                if (rank == 0) {
                    unsigned* slot = g_roleq + 2 + (atomicAdd(g_roleq + 1, 1u) & 127);
                    unsigned v = 0;
                    for (int spin = 0; spin < 4000000 && ((v = atomicAdd(slot, 0u)) >> 8) != (ep1 & 0xffffffu); spin++) {}
                    asm volatile("st.shared::cluster.u32 [%0], %1;" ::"r"(mapa(misc + MISC_SMID + 4, 0)), "r"(v & 255) : "memory");
                    asm volatile("st.shared::cluster.u32 [%0], %1;" ::"r"(mapa(misc + MISC_SMID + 4, 1)), "r"(v & 255) : "memory");
                }
                if (mc < 64) {
                    mbar_wait(misc + BAR_FULL + 8 * slot_of(0), 0);
                    asm volatile("mbarrier.inval.shared::cta.b64 [%0];" ::"r"(misc + BAR_FULL + 8 * slot_of(0)) : "memory");
                    mbar_init(misc + BAR_FULL + 8 * slot_of(0), 1);
                    asm volatile("fence.mbarrier_init.release.cluster;" ::: "memory");
                }
            }
            __syncwarp();
            asm volatile("barrier.cluster.arrive.aligned;\nbarrier.cluster.wait.aligned;" ::: "memory");
            mc = role_of(__shfl_sync(0xffffffffu, lds32(misc + MISC_SMID + 4), 0));
            if (tid == 0 && mc < 64) load_w0();
            __syncwarp();
        }
    }
    const int cta = mc * 2 + rank;
    if (mc >= 64) { aux_cta(P, &tmG, &tmU, &tmD, smem_raw, cta - 128); return; }
    const int team = mc >> 2, k = mc & 3;
    const int u3 = (mc >> 4) * 2 + (team & 1), s3 = k, kap = (mc >> 3) & 1;
    const int partner = cta ^ 16;
    if (tid >= 128) prefetch_w(1);
    if (tid == 256) {
        const CUtensorMap* tw = rank ? &tmWv : &tmWk;
#pragma unroll
        for (int e = 1; e < NSLOT; e++) {
            const uint32_t fb = misc + BAR_FULL + 8 * slot_of(e), dst = ring + slot_of(e) * SLOT_BYTES;
            mbar_expect_tx(fb, SLOT_BYTES);
            if (e & 1) tma2d_mc(dst + rank * 16384, &tmC, (e >> 1) * 128 + rank * 64, (12 + k) * 128, fb, policy(false));
            else { tma2d(dst, tw, team * 256, e * 64, fb, policy(false)); tma2d(dst + 16384, tw, team * 256 + 64, e * 64, fb, policy(false)); }
        }
    }
    PROF_EV(5);
    const int wg = __shfl_sync(0xffffffffu, tid >> 7, 0);

    if (wg == 0) {
        asm volatile("setmaxnreg.dec.sync.aligned.u32 40;");
        const int warp = __shfl_sync(0xffffffffu, tid >> 5, 0), lane = tid & 31;
        if (warp == 0) {
            const bool lead = elect_one();
            Cur c = cur_at(NSLOT);
            uint32_t dst, fb;
            auto acquire = [&]() {
                mbar_wait(misc + BAR_EMPTY + 8 * c.slot, c.ph ^ 1);
                fb = misc + BAR_FULL + 8 * c.slot; dst = ring + c.slot * SLOT_BYTES;
                if (lead) mbar_expect_tx(fb, SLOT_BYTES);
                c.adv();
            };
            auto load_w = [&](const CUtensorMap* tm, int col, int row, bool stream) {
                acquire();
                if (lead) { tma2d(dst, tm, col, row, fb, policy(stream)); tma2d(dst + 16384, tm, col + 64, row, fb, policy(stream)); }
            };
            auto load_half = [&](const unsigned char* src, bool stream) {
                acquire();
                if (lead) bulk_load_mc(dst + rank * 16384, src, 16384, fb, policy(stream));
            };
            auto dep_wait = [&](int d) { mbar_wait(misc + BAR_DEP + 8 * d, 0); fence_async_global(); };
            auto op_prefetch = [&](int i) {
                const int head = op_head(i, kap);
                l2_prefetch(reinterpret_cast<const unsigned char*>(P.wo) + head * 163840 + (u3 * 8 + s3 * 2 + rank) * 2560, 2560);
                if (i < 8) l2_prefetch(g_ctx + (size_t)(head * 32 + 4 * u3 + 2 * rank) * 16384 + s3 * 8192, 8192);
            };
            __nanosleep(CDELAY);
            if (lead) l2_prefetch(reinterpret_cast<const unsigned char*>(P.c) + (size_t)cta * 12288, 12288);
            const CUtensorMap* tw = rank ? &tmWv : &tmWk;
            const unsigned char* Kh = g_K + (size_t)team * 32 * 16384 + rank * 16384;
            const unsigned char* Vh = g_V + (size_t)team * 32 * 16384 + rank * 16384;
#pragma unroll 1
            for (int v = 0; v < 2; v++) {
                const int h = 2 * team + v;
#pragma unroll 1
                for (int i = v ? 0 : 3; i < 16; i++) {
                    if (i < 4 && v) load_w(tw, h * 128, i * 128, HM & 1);
                    if (v && (i & 7) == 3) dep_wait(D_WAR + (i >> 3));
                    acquire();
                    if (lead) tma2d_mc(dst + rank * 16384, &tmC, (i & 3) * 128 + rank * 64, (12 - (i & 12) + k) * 128, fb, policy(HM & 2));
                    if (v && i == 3 && lead) mbar_arrive(misc + BAR_PROG + 8);
                    if (i == 8 && lead) {
                        tma2d_prefetch(&tmWq, h * 128 + rank * 64, k * 64); tma2d_prefetch(&tmWq, h * 128 + rank * 64, k * 64 + 256);
                        if (k < 2) tma2d_prefetch(&tmWq, h * 128 + rank * 64, k * 64 + 512);
                        if (v) l2_prefetch(g_xn + 8 * 163840 + cta * 10240, 10240);
                    }
                }
                int togo = v ? PF_START : 11;
#pragma unroll 1
                for (int r = 0; r < 2; r++) {
                    const int p = r ? k : 7 - k, n = 2 * p + 1;
                    if (v == 0) dep_wait(D_LN + r);
                    const int g0 = r ? rank ^ SWAPT : 3 - rank, g1 = 3 - g0;
                    const unsigned char* x0 = g_xn + (2 * p + (g0 >> 1)) * 163840 + (g0 & 1) * 8192;
                    const unsigned char* x1 = g_xn + (2 * p + (g1 >> 1)) * 163840 + (g1 & 1) * 8192;
#pragma unroll 1
                    for (int kc = 0; kc < 10; kc++) {
                        acquire();
                        if (lead) {
                            tma2d_mc(dst + 16384 + rank * 8192, &tmWq, h * 128 + rank * 64, kc * 64, fb, policy(false));
                            bulk_load(dst, x0 + kc * 16384, 8192, fb, policy(false));
                            bulk_load(dst + 8192, x1 + kc * 16384, 8192, fb, policy(false));
                        }
                    }
                    if (r == 0) dep_wait(D_KV + 2 * v);
                    load_half(Kh + n * 32768, HM & 16);
#pragma unroll 1
                    for (int j = n - 1; j >= 0; j--) {
                        if (r == 0 && j == 7) dep_wait(D_KV + 2 * v + 1);
                        load_half(Kh + j * 32768, HM & 16); load_half(Vh + (j + 1) * 32768, HM & 16);
                        if (v == 0 && r == 0 && j == 3 && lead) mbar_arrive(misc + BAR_PROG);
                        --togo;
                        if (v == 0 && togo == 0 && lead) {
                            tma2d_prefetch(tw, h * 128 + 128, k * 128); tma2d_prefetch(tw, h * 128 + 192, k * 128);
                            l2_prefetch(reinterpret_cast<const unsigned char*>(P.c) + (size_t)cta * 16384, 16384);
                        }
                        if (v && togo <= 0 && togo > -OP_PF && lead) op_prefetch(-togo);
                    }
                    load_half(Vh, HM & 16);
                }
            }
            mbar_wait(misc + BAR_EMPTY + 8 * c.slot, c.ph ^ 1); c.adv();
            int st = 0; uint32_t ph3 = 0;
#pragma unroll 1
            for (int i = 0; i < 32; i++) {
                const int head = op_head(i >> 1, kap);
                if ((i & 1) == 0) dep_wait(D_CTX + (i >> 1));
                if (i < NST3) { mbar_wait(misc + BAR_EMPTY + 8 * c.slot, c.ph ^ 1); c.adv(); }
                else mbar_wait(misc + BAR_EMPTY3 + 8 * st, ph3 ^ 1);
                fb = misc + BAR_FULL3 + 8 * st; dst = ring + st * ST3_BYTES;
                if (i == LATE_AT && lead) mbar_arrive(misc + BAR_PROG + 16);
                if (lead) {
                    mbar_expect_tx(fb, ST3_BYTES);
                    const unsigned char* src = g_ctx + (size_t)(head * 32 + 4 * u3 + 2 * rank) * 16384 + (i & 1) * 8192;
                    bulk_load(dst, src, 8192, fb, policy(HM & 32));
                    bulk_load(dst + 8192, src + 16384, 8192, fb, policy(HM & 32));
                    tma3d_mc(dst + 16384 + rank * 10240, &tmWo, 0, head * 128 + (i & 1) * 64 + rank * 32, 5 * s3, fb, policy(HM & 32));
                    if ((i & 1) && (i >> 1) + OP_PF < 16) op_prefetch((i >> 1) + OP_PF);
                }
                if (++st == NST3) { st = 0; ph3 ^= 1; }
            }
        } else {
        if (lane < 27 && (warp - 1) * 27 + lane < 80) {
            const int ch = (warp - 1) * 27 + lane;
            uint4 u = __ldg(reinterpret_cast<const uint4*>(P.wr) + ch);
            asm volatile("st.shared.v4.b32 [%0], {%1,%2,%3,%4};" ::"r"(misc + MISC_WR + 16 * ch), "r"(u.x), "r"(u.y), "r"(u.z), "r"(u.w) : "memory");
        }
        bar_sync(3, 96);
#pragma unroll 1
        for (int t = 0; t < (warp == 3 ? 1 : 3); t++) {
            const int row2 = (cta >> 5) * 256 + (cta & 31) * 8 + (warp - 1) * 4;
            if (t < 2 && warp < 3) {
#pragma unroll
                for (int i = 0; i < 3; i++)
                    if (i * 32 + lane < 80) asm volatile("prefetch.global.L2 [%0];" ::"l"(P.x + (size_t)(row2 + 2 * t) * DM + (i * 32 + lane) * 16));
            }
            ln_rows(P, t ? row2 + 2 * t - 2 : (4 + (cta >> 5)) * 256 + (cta & 31) * 6 + (warp - 1) * 2, lane, misc + MISC_WR);
            __syncwarp();
            if (lane == 0 && warp < 3 && t != 1) mbar_arrive(misc + BAR_LN + 4 * t);
        }
        if (warp == 3) {
            const unsigned ep1 = *reinterpret_cast<volatile unsigned*>(&g_epoch) + 1;
            if (lane == 0) {
                asm volatile("st.shared.u32 [%0], %1;" ::"r"(misc + MISC_EPOCH), "r"(ep1) : "memory");
                mbar_wait(misc + BAR_LN, 0);
                flag_signal(flag_ptr(FL_LN + 4 + (cta >> 5)));
                flag_wait(flag_ptr(FL_LN + 7 - k), ep1 * 33u);
                mbar_arrive(misc + BAR_DEP + 8 * D_LN);
#pragma unroll 1
                for (int v = 0; v < 2; v++) {
#pragma unroll 1
                    for (int i = 2 * v; i < 2 * v + 2; i++) {
                        mbar_wait(misc + BAR_EV + 8 * (16 + EV_KV + i), 0);
                        if (v == 0) {
                            mbar_wait(misc + BAR_EV + 8 * (EV_KV + i), 0);
                            asm volatile("red.release.gpu.global.add.u32 [%0], 2;" ::"l"(flag_ptr(FL_KV + team * 8 + i)) : "memory");
                        }
                        flag_wait(flag_ptr(FL_KV + team * 8 + i), ep1 * 16u);
                        mbar_arrive(misc + BAR_DEP + 8 * (D_KV + i));
                    }
                    if (v) break;
                    mbar_wait(misc + BAR_LN + 8, 0);
                    flag_signal(flag_ptr(FL_LN + (cta >> 5)));
                    flag_wait(flag_ptr(FL_LN + k), ep1 * 32u);
                    mbar_arrive(misc + BAR_DEP + 8 * (D_LN + 1));
#pragma unroll 1
                    for (int i = 0; i < 2; i++) {
                        mbar_wait(misc + BAR_PROG + 8 * i, 0);
                        flag_signal(flag_ptr(FL_WAR + 2 * team + i));
                        flag_wait(flag_ptr(FL_WAR + 2 * team + i), ep1 * 8u);
                        mbar_arrive(misc + BAR_DEP + 8 * (D_WAR + i));
                    }
                }
                flag_wait(flag_ptr(FL_MOE_DONE), ep1);
                int4 s0 = __ldcg(reinterpret_cast<const int4*>(g_sel)), s1 = __ldcg(reinterpret_cast<const int4*>(g_sel) + 1);
                asm volatile("st.shared.v4.u32 [%0], {%1,%2,%3,%4};" ::"r"(misc + MISC_SEL), "r"(s0.x), "r"(s0.y), "r"(s0.z), "r"(s0.w) : "memory");
                asm volatile("st.shared.v4.u32 [%0], {%1,%2,%3,%4};" ::"r"(misc + MISC_SEL + 16), "r"(s1.x), "r"(s1.y), "r"(s1.z), "r"(s1.w) : "memory");
                mbar_arrive(misc + BAR_SEL);
            }
            __syncwarp();
            const unsigned* cf = flag_ptr(FL_CTX + op_head(lane & 15, kap) * 8 + u3);
#pragma unroll 1
            for (int half = 0; half < 2; half++) {
                if (half) mbar_wait(misc + BAR_EV + 8 * (EV_CTX + 3), 0);
                bool done = (lane >> 3) != half;
                for (int spin = 0; spin < 4000000; spin++) {
                    if (!done) {
                        unsigned v;
                        asm volatile("ld.acquire.gpu.global.u32 %0, [%1];" : "=r"(v) : "l"(cf) : "memory");
                        if ((int)(v - ep1 * 4u) >= 0) { mbar_arrive(misc + BAR_DEP + 8 * (D_CTX + lane)); done = true; }
                    }
                    if (__all_sync(0xffffffffu, done)) break;
                    __nanosleep(64);
                }
            }
        } else {
            const int w = warp - 1;
            if (lane == 0) {
                const uint32_t eb = misc + BAR_EV + w * 128;
#pragma unroll 1
                for (int i = 0; i < 6; i++) {
                    const bool kv = (i >> 1) == 1;
                    mbar_wait(eb + 8 * (kv ? EV_KV + i : EV_CTX + (i >> 1) + (i & 1)), 0);
                    flag_signal(flag_ptr(kv ? FL_KV + team * 8 + i : FL_CTX + (2 * team + (i >> 2)) * 8 + ((i & 1) ? k : 7 - k)));
                }
            }
            __syncwarp();
            mbar_wait(misc + BAR_PROG + 16, 0);
            const int row = (2 * u3 + rank) * 128 + 64 * w + perm32(16 * (lane >> 3) + 8 * kap + (lane & 7));
#pragma unroll
            for (int i = 0; i < 10; i++) asm volatile("prefetch.global.L2 [%0];" ::"l"(P.x + (size_t)row * DM + 160 * s3 + 16 * i));
            asm volatile("prefetch.global.L2 [%0];" ::"l"(g_stats + row));
        }
        }
    } else {
        asm volatile("setmaxnreg.inc.sync.aligned.u32 232;");
        Ctx c;
        c.ring = ring; c.misc = misc; c.w = wg - 1; c.warp = __shfl_sync(0xffffffffu, (tid >> 5) & 3, 0); c.lane = tid & 31;
        c.rel = mapa(misc, tid & 1);
        const int w = c.w;
        if (w == 1) bar_arrive(1, 256);
        prefetch_w(2); prefetch_w(3);
        Cur cur = cur_at(0);
        float o[64], inv[2];
#pragma unroll 1
        for (int v = 0; v < 2; v++) {
        {
            uint32_t wf[128];
            float acc[64];
#pragma unroll
            for (int i = 32; i < 128; i++) wf[i] = 0u;
            Cur cw = cur;
            auto load_wchunk = [&](auto CH) {
                constexpr int ch = decltype(CH)::value;
                mbar_wait_hot(misc + BAR_FULL + 8 * cw.slot, cw.ph);
                const uint32_t z = load_afrag<8, 32 * ch>(wf, ring + cw.slot * SLOT_BYTES + w * 16384, c);
                release(c, BAR_EMPTY + 8 * cw.slot + z, 1);
                cw.adv(); cw.adv();
            };
            load_wchunk(IC<0>{});
            cur.adv();
            PROF_EV(2); PROF_GT(60);
#pragma unroll 1
            for (int t = 0; t < 4; t++) {
                uint32_t last = 0;
                token_wait(w);
                PROF_EV(10);
                undef_regs(acc);
                auto chunk = [&](auto CH) {
                    constexpr int ch = decltype(CH)::value;
                    mbar_wait_hot(misc + BAR_FULL + 8 * cur.slot, cur.ph);
                    if (t == 0) { PROF_EV(12 + ch); }
                    uint64_t d = mkdesc(ring + cur.slot * SLOT_BYTES, 16, 1024, 1);
                    wg_fence();
#pragma unroll
                    for (int ks = 0; ks < 8; ks++)
                        wgmma_rs_n128_ta0_tb0(acc, wf[32 * ch + 4 * ks], wf[32 * ch + 4 * ks + 1], wf[32 * ch + 4 * ks + 2], wf[32 * ch + 4 * ks + 3],
                                              d + (ks >> 2) * 1024 + (ks & 3) * 2, (ch | ks) != 0);
                    wg_commit();
                    if (ch == 3 || (ch < 2 && t == 0)) token_pass(w);
                    if constexpr (ch < 2) { if (t == 0) load_wchunk(IC<ch + 1>{}); }
                    if constexpr (ch == 2) { if (t == 0 && !w) load_wchunk(IC<3>{}); }
                    if (ch > 0) { wg_wait<1>(); release(c, BAR_EMPTY + 8 * last, 1); }
                    last = cur.slot;
                    cur.adv();
                    if (ch < 3 && t == 0) cur.adv();
                    if constexpr (ch == 1) { if (t == 0 && w) load_wchunk(IC<3>{}); }
                    if (ch < 2 && t == 0) token_wait(w);
                };
                chunk(IC<0>{}); chunk(IC<1>{}); chunk(IC<2>{}); chunk(IC<3>{});
                wg_wait<0>();
                release(c, BAR_EMPTY + 8 * last, 1);
                PROF_EV(11);
                fence_regs(acc);
                if (rank == 0) {
#pragma unroll
                    for (int i = 0; i < 64; i++) acc[i] *= SM_SCALE;
                }
                store_proj(acc, (rank ? g_V : g_K) + (size_t)(team * 32 + 24 + 2 * k - 8 * t) * 16384, rank, c);
                if (t & 1) signal_event(c, EV_KV + 2 * v + (t >> 1));
            }
            PROF_EV(61); PROF_GT(62);
        }
        PROF_EV(63); PROF_GT(64);
        {
            uint32_t q[32], p[32];
            float m[2], l[2];
#pragma unroll
            for (int i = 0; i < 64; i++) o[i] = 0.f;
#pragma unroll
            for (int i = 0; i < 32; i++) p[i] = 0u;
            l[0] = l[1] = 1.f;
            int pv_acc = 0, pv_mode = 2;
#pragma unroll 1
            for (int r = 0; r < 2; r++) {
                const int heavy = 1 ^ r ^ w;
                const int half = 1 ^ heavy ^ rank ^ (r & SWAPT);
                int left = 2 * (r ? k : 7 - k) + 1 + heavy;
                Cur ck, cv = cur;
                {
                    float s[64];
                    if (r) cur.adv();
                    mbar_wait_hot(misc + BAR_FULL + 8 * cv.slot, cv.ph);
                    token_wait(w);
                    PROF_EV(20);
                    issue_pv(o, p, ring + cv.slot * SLOT_BYTES, pv_acc, pv_mode);
                    undef_regs(s);
                    uint32_t prev = 0;
                    auto qchunk = [&](int acc) {
                        mbar_wait_hot(misc + BAR_FULL + 8 * cur.slot, cur.ph);
                        const uint64_t da = mkdesc(ring + cur.slot * SLOT_BYTES + w * 8192, 16, 1024, 1);
                        const uint64_t db = mkdesc(ring + cur.slot * SLOT_BYTES + 16384, 8192, 1024, 1);
                        wg_fence();
#pragma unroll
                        for (int ks = 0; ks < 4; ks++) wgmma_ss_n128_ta0_tb1(s, da + 2 * ks, db + 128 * ks, ks ? 1 : acc);
                        wg_commit();
                    };
                    qchunk(0);
                    const uint32_t slot0 = cur.slot; cur.adv();
                    qchunk(1);
                    prev = cur.slot; cur.adv();
                    token_pass(w);
                    row_inv(l, inv);
                    wg_wait<2>();
                    fence_regs(o);
                    if (r) {
                        release(c, BAR_EMPTY + 8 * cv.slot, 1);
                        store_ctx(o, inv, g_ctx + (size_t)((2 * team + v) * 32 + 4 * (7 - k) + (w ? rank : 3 - rank)) * 16384, policy((HM & 256) && v == 0), c);
                        signal_event(c, EV_CTX + 2 * v);
                    }
                    wg_wait<1>();
                    release(c, BAR_EMPTY + 8 * slot0, 1);
#pragma unroll 1
                    for (int kc = 2; kc < 10; kc++) {
                        qchunk(1);
                        wg_wait<1>();
                        release(c, BAR_EMPTY + 8 * prev, 1);
                        prev = cur.slot; cur.adv();
                    }
                    if (!heavy) cur.adv();
                    ck = cur;
                    cur.adv();
                    if (!heavy) cur.adv();
                    wg_wait<0>();
                    release(c, BAR_EMPTY + 8 * prev, 1);
                    PROF_EV(21);
                    fence_regs(s);
#pragma unroll
                    for (int i = 0; i < 32; i++) q[i] = pack_bf16(s[2 * i], s[2 * i + 1]);
                }
                cv = ck;
                int first = 1, gen = 0;
                uint32_t pv_cnt = 0;
                pv_acc = 0; pv_mode = 2;
                l[0] = l[1] = m[0] = m[1] = 0.f;
                mbar_wait_hot(misc + BAR_FULL + 8 * ck.slot, ck.ph);
#pragma unroll 1
                while (true) {
                    float s[64];
                    if (half & first) {
                        token_wait(w);
                        PROF_EV(30);
                        float sh[32];
                        undef_regs(sh);
                        issue_qk_half(sh, q, ring + ck.slot * SLOT_BYTES);
                        token_pass(w);
                        --left;
                        wg_wait<0>();
                        PROF_EV(34);
                        fence_regs(sh);
                        mask_diag<0>(sh, c);
                        float l0 = 0.f, l1 = 0.f;
#pragma unroll
                        for (int j = 0; j < 8; j++) {
#pragma unroll
                            for (int e = 0; e < 4; e++) ex2v(sh[4 * j + e]);
                            l0 += sh[4 * j] + sh[4 * j + 1]; l1 += sh[4 * j + 2] + sh[4 * j + 3];
                        }
#pragma unroll
                        for (int i = 0; i < 16; i++) p[i] = pack_bf16(sh[2 * i], sh[2 * i + 1]);
                        const int lim = mask_lim(c);
                        if (__any_sync(0xffffffffu, !(l0 <= SAFE_SUM && l1 <= SAFE_SUM && (l0 >= 1.0f / SAFE_SUM || lim < 0) &&
                                                      (l1 >= 1.0f / SAFE_SUM || lim < -2)))) goto redo;
                        l[0] = l0; l[1] = l1;
                        goto tail;
                    }
#pragma unroll 1
                    while (true) {
                        token_wait(w);
                        PROF_EV(first ? 30 : 31);
                        undef_regs(s);
                        issue_qk(s, q, ring + ck.slot * SLOT_BYTES);
                        Cur nck = cur, ncv = cur, ncur;
                        ncv.adv(); ncur = ncv; ncur.adv();
                        --left;
                        mbar_wait_hot(misc + BAR_FULL + 8 * cv.slot, cv.ph);
                        issue_pv(o, p, ring + cv.slot * SLOT_BYTES, pv_acc, pv_mode);
                        token_pass(w);
                        wg_wait<1>();
                        PROF_EV(33);
                        fence_regs(s);
                        float lo = 0.f;
                        if (first) {
                            lo = 1.0f / SAFE_SUM;
                            mask_diag<8>(s, c);
                        }
                        constexpr int JB = 11;
                        float l0 = l[0], l1 = l[1];
                        if (!gen) {
#pragma unroll
                            for (int j = 0; j < JB; j++) {
#pragma unroll
                                for (int e = 0; e < 4; e++) ex2v(s[4 * j + e]);
                                if (j < JB - 1) { l0 += s[4 * j] + s[4 * j + 1]; l1 += s[4 * j + 2] + s[4 * j + 3]; }
                            }
                        }
                        wg_wait<0>();
                        fence_regs(o);
                        if (gen) goto general;
#pragma unroll
                        for (int j = JB - 1; j < 16; j++) {
                            if (j >= JB) {
#pragma unroll
                                for (int e = 0; e < 4; e++) ex2v(s[4 * j + e]);
                            }
                            l0 += s[4 * j] + s[4 * j + 1]; l1 += s[4 * j + 2] + s[4 * j + 3];
                        }
#pragma unroll
                        for (int i = 0; i < 32; i++) p[i] = pack_bf16(s[2 * i], s[2 * i + 1]);
                        if (__any_sync(0xffffffffu, !(l0 <= SAFE_SUM && l1 <= SAFE_SUM && l0 >= lo && l1 >= lo))) goto redo;
                        l[0] = l0; l[1] = l1;
                        if (left == 0) goto tail;
                        release(c, BAR_EMPTY + 8 * ck.slot, 1 + (first & heavy));
                        if (pv_cnt) release(c, BAR_EMPTY + 8 * cv.slot, pv_cnt);
                        pv_acc = first ^ 1; pv_mode = 0; pv_cnt = 1 + (first & heavy); first = 0;
                        ck = nck; cv = ncv; cur = ncur;
                        mbar_wait_hot(misc + BAR_FULL + 8 * ck.slot, ck.ph);
                    }
                redo:
                    recompute_scores(s, q, ring + ck.slot * SLOT_BYTES, c);
                    if (first) { mask_any(s, half ^ 1, c); m[0] = m[1] = -INFINITY; }
                    gen = 1;
                general:
                    {
                        float mx[2], alpha[2];
                        row_max<16>(s, mx);
#pragma unroll
                        for (int i = 0; i < 2; i++) {
                            mx[i] = fmaxf(mx[i], m[i]);
                            alpha[i] = ex2(m[i] - mx[i]);
                            m[i] = mx[i];
                            l[i] *= alpha[i];
                        }
                        exp_sum<16, true>(s, m, l[0], l[1]);
#pragma unroll
                        for (int i = 0; i < 64; i++) o[i] *= alpha[(i >> 1) & 1];
#pragma unroll
                        for (int i = 0; i < 32; i++) p[i] = pack_bf16(s[2 * i], s[2 * i + 1]);
                    }
                tail:
                    release(c, BAR_EMPTY + 8 * ck.slot, 1 + (first & heavy));
                    if (pv_cnt) release(c, BAR_EMPTY + 8 * cv.slot, pv_cnt);
                    pv_acc = first ^ 1; pv_mode = first & half; pv_cnt = 1 + (first & heavy); first = 0;
                    if (left == 0) break;
                    ck = cur; cur.adv(); cv = cur; cur.adv();
                    mbar_wait_hot(misc + BAR_FULL + 8 * ck.slot, ck.ph);
                }
            }
            mbar_wait_hot(misc + BAR_FULL + 8 * cur.slot, cur.ph);
            token_wait(w);
            PROF_EV(32);
            issue_pv(o, p, ring + cur.slot * SLOT_BYTES, pv_acc, pv_mode);
            if (w == 0 || v == 0) token_pass(w);
            row_inv(l, inv);
            wg_wait<0>();
            release(c, BAR_EMPTY + 8 * cur.slot, 1);
            fence_regs(o);
            cur.adv();
            if (v == 0) {
                store_ctx(o, inv, g_ctx + (size_t)(2 * team * 32 + 4 * k + (w ? 3 - (rank ^ SWAPT) : rank ^ SWAPT)) * 16384, policy(HM & 256), c);
                signal_event(c, EV_CTX + 1);
            }
        }
        }
        {
            float acc[80];
            undef_regs(acc);
            int st = 0, prev = 0; uint32_t ph3 = 0;
            auto op_stage = [&](int i) {
                mbar_wait(misc + BAR_FULL3 + 8 * st, ph3);
                PROF_EV(44);
                uint32_t base = ring + st * ST3_BYTES;
                uint64_t da = mkdesc(base + w * 8192, 16, 1024, 1);
                uint64_t db = mkdesc(base + 16384, 2048, 512, 2);
                wg_fence();
#pragma unroll
                for (int k = 0; k < 4; k++) wgmma_ss_n160_ta0_tb1(acc, da + 2 * k, db + (k >> 1) * 640 + (k & 1) * 64, k ? 1 : i);
                wg_commit();
                if (i > 0) { wg_wait<1>(); if (i <= 32 - NST3) release(c, BAR_EMPTY3 + 8 * prev, 1); }
                prev = st;
                if (++st == NST3) { st = 0; ph3 ^= 1; }
            };
            PROF_EV(40); PROF_GT(65);
            op_stage(0);
            store_ctx(o, inv, g_ctx + (size_t)((2 * team + 1) * 32 + 4 * k + (w ? 3 - (rank ^ SWAPT) : rank ^ SWAPT)) * 16384, policy(false), c);
            signal_event(c, EV_CTX + 3);
#pragma unroll 1
            for (int i = 1; i < 12; i++) op_stage(i);
            mbar_wait(misc + BAR_SEL, 0);
            const uint32_t tag = lds32(misc + MISC_EPOCH) & 1;
            const int g = c.lane >> 2, t = c.lane & 3;
            const int row = (2 * u3 + rank) * 128 + 64 * w + perm32(16 * c.warp + 8 * kap + g);
            const int col = 160 * s3 + 8 * t;
            int sel = -1;
#pragma unroll
            for (int i = 0; i < TOPC; i++) if ((int)lds32(misc + MISC_SEL + 4 * i) == row) sel = i;
            const int t256 = tid - 128;
            uint4* sendp = g_part + (size_t)cta * 2560 + t256;
            if (c.lane >= 30) stg128(sendp + 9 * 256, tag ^ 1, tag ^ 1, tag ^ 1, tag ^ 1);
#pragma unroll 1
            for (int i = 12; i < 32; i++) op_stage(i);
            uint4 xv[5], bv[5];
#pragma unroll
            for (int i = 0; i < 5; i++) xv[i] = ldg128(P.x + (size_t)row * DM + col + 32 * i);
            uint2 stat;
            asm volatile("ld.global.cg.v2.b32 {%0,%1}, [%2];" : "=r"(stat.x), "=r"(stat.y) : "l"(g_stats + row) : "memory");
            wg_wait<0>();
            fence_regs(acc);
            PROF_EV(41); PROF_GT(66);
            float keep[40];
#pragma unroll
            for (int j = 0; j < 10; j++) {
                uint32_t v0 = __float_as_uint(kap ? acc[8 * j + 0] : acc[8 * j + 2]), v1 = __float_as_uint(kap ? acc[8 * j + 1] : acc[8 * j + 3]);
                uint32_t v2 = __float_as_uint(kap ? acc[8 * j + 4] : acc[8 * j + 6]), v3 = __float_as_uint(kap ? acc[8 * j + 5] : acc[8 * j + 7]);
                asm volatile("st.relaxed.gpu.global.v4.b32 [%0], {%1,%2,%3,%4};" ::"l"(sendp + j * 256),
                             "r"((v0 & ~1u) | tag), "r"((v1 & ~1u) | tag), "r"((v2 & ~1u) | tag), "r"((v3 & ~1u) | tag) : "memory");
                keep[4 * j + 0] = kap ? acc[8 * j + 2] : acc[8 * j + 0]; keep[4 * j + 1] = kap ? acc[8 * j + 3] : acc[8 * j + 1];
                keep[4 * j + 2] = kap ? acc[8 * j + 6] : acc[8 * j + 4]; keep[4 * j + 3] = kap ? acc[8 * j + 7] : acc[8 * j + 5];
            }
            PROF_GT(67);
#pragma unroll
            for (int i = 0; i < 5; i++) {
                uint32_t xx[4] = {xv[i].x, xv[i].y, xv[i].z, xv[i].w};
#pragma unroll
                for (int e = 0; e < 4; e++) {
                    asm("sub.rn.bf16x2 %0, %0, %1;" : "+r"(xx[e]) : "r"(stat.x));
                    xx[e] = pack_bf16(bf_lo(xx[e]) * __uint_as_float(stat.y), bf_hi(xx[e]) * __uint_as_float(stat.y));
                }
                bv[i] = make_uint4(xx[0], xx[1], xx[2], xx[3]);
            }
            if (sel >= 0) {
#pragma unroll
                for (int i = 0; i < 5; i++) bv[i] = ldg128(g_brow + sel * DM + col + 32 * i);
            }
            const uint4* recvp = g_part + (size_t)partner * 2560 + t256;
            uint4 rv[10];
            int spins = 0;
            while (POLL1) {
                uint32_t v;
                asm volatile("ld.relaxed.gpu.global.b32 %0, [%1];" : "=r"(v) : "l"(recvp + 9 * 256 + (31 - c.lane)) : "memory");
                if (__all_sync(0xffffffffu, (v & 1u) == tag) || ++spins > 2000000) break;
            }
            PROF_GT(68);
            while (true) {
                uint32_t bad = 0u;
#pragma unroll
                for (int j = 0; j < 10; j++) {
                    asm volatile("ld.relaxed.gpu.global.v4.b32 {%0,%1,%2,%3}, [%4];"
                                 : "=r"(rv[j].x), "=r"(rv[j].y), "=r"(rv[j].z), "=r"(rv[j].w) : "l"(recvp + j * 256) : "memory");
                }
#pragma unroll
                for (int j = 0; j < 10; j++) {
                    rv[j].x ^= tag; rv[j].y ^= tag; rv[j].z ^= tag; rv[j].w ^= tag;
                    bad |= rv[j].x | rv[j].y | rv[j].z | rv[j].w;
                }
                if (__all_sync(0xffffffffu, (bad & 1u) == 0) || ++spins > 2000000) break;
            }
            PROF_GT(69);
            uint32_t pk[20];
#pragma unroll
            for (int j = 0; j < 10; j++) {
                pk[2 * j] = pack_bf16(keep[4 * j] + __uint_as_float(rv[j].x), keep[4 * j + 1] + __uint_as_float(rv[j].y));
                pk[2 * j + 1] = pack_bf16(keep[4 * j + 2] + __uint_as_float(rv[j].z), keep[4 * j + 3] + __uint_as_float(rv[j].w));
            }
#pragma unroll
            for (int i = 0; i < 5; i++) {
                uint32_t a0 = pk[4 * i], a1 = pk[4 * i + 1], a2 = pk[4 * i + 2], a3 = pk[4 * i + 3];
                uint32_t x0 = (t & 1) ? a0 : a1, x1 = (t & 1) ? a2 : a3;
                x0 = __shfl_xor_sync(0xffffffffu, x0, 1); x1 = __shfl_xor_sync(0xffffffffu, x1, 1);
                if (t & 1) { a0 = x0; a2 = x1; } else { a1 = x0; a3 = x1; }
                x0 = (t & 2) ? a0 : a2; x1 = (t & 2) ? a1 : a3;
                x0 = __shfl_xor_sync(0xffffffffu, x0, 2); x1 = __shfl_xor_sync(0xffffffffu, x1, 2);
                if (t & 2) { a0 = x0; a1 = x1; } else { a2 = x0; a3 = x1; }
                uint32_t av[4] = {a0, a1, a2, a3};
                uint32_t xx[4] = {xv[i].x, xv[i].y, xv[i].z, xv[i].w}, bb[4] = {bv[i].x, bv[i].y, bv[i].z, bv[i].w};
                uint32_t ov[4];
#pragma unroll
                for (int e = 0; e < 4; e++) {
                    asm("add.rn.bf16x2 %0, %1, %2;" : "=r"(ov[e]) : "r"(xx[e]), "r"(av[e]));
                    asm("add.rn.bf16x2 %0, %0, %1;" : "+r"(ov[e]) : "r"(bb[e]));
                }
                stg128(P.out + (size_t)row * DM + col + 32 * i, ov[0], ov[1], ov[2], ov[3]);
            }
            PROF_EV(42); PROF_GT(43);
        }
    }
}

typedef CUresult (*EncodeFn)(CUtensorMap*, CUtensorMapDataType, cuuint32_t, void*, const cuuint64_t*, const cuuint64_t*, const cuuint32_t*,
                             const cuuint32_t*, CUtensorMapInterleave, CUtensorMapSwizzle, CUtensorMapL2promotion, CUtensorMapFloatOOBfill);

void make_map2d(EncodeFn enc, CUtensorMap* tm, const void* p, uint64_t cols, uint64_t rows, uint32_t box_rows = 128) {
    cuuint64_t gd[2] = {cols, rows}, gs[1] = {cols * 2};
    cuuint32_t box[2] = {64, box_rows}, es[2] = {1, 1};
    enc(tm, CU_TENSOR_MAP_DATA_TYPE_BFLOAT16, 2, const_cast<void*>(p), gd, gs, box, es, CU_TENSOR_MAP_INTERLEAVE_NONE,
        CU_TENSOR_MAP_SWIZZLE_128B, CU_TENSOR_MAP_L2_PROMOTION_L2_128B, CU_TENSOR_MAP_FLOAT_OOB_FILL_NONE);
}

void make_map3d(EncodeFn enc, CUtensorMap* tm, const void* p, uint64_t cols, uint64_t rows, uint32_t bw, uint32_t nb) {
    cuuint64_t gd[3] = {bw, rows, cols / bw}, gs[2] = {cols * 2, bw * 2};
    cuuint32_t box[3] = {bw, 32, nb}, es[3] = {1, 1, 1};
    enc(tm, CU_TENSOR_MAP_DATA_TYPE_BFLOAT16, 3, const_cast<void*>(p), gd, gs, box, es, CU_TENSOR_MAP_INTERLEAVE_NONE,
        bw == 64 ? CU_TENSOR_MAP_SWIZZLE_128B : CU_TENSOR_MAP_SWIZZLE_64B, CU_TENSOR_MAP_L2_PROMOTION_L2_128B, CU_TENSOR_MAP_FLOAT_OOB_FILL_NONE);
}

}

extern "C" void kernel_launch(void* const* d_in, const int* in_sizes, int n_in, void* d_out, int out_size) {
    (void)in_sizes; (void)n_in; (void)out_size;
    static EncodeFn enc = nullptr;
    if (!enc) {
        void* fn = nullptr;
        cudaDriverEntryPointQueryResult qr;
        cudaGetDriverEntryPoint("cuTensorMapEncodeTiled", &fn, cudaEnableDefault, &qr);
        enc = (EncodeFn)fn;
        cudaFuncSetAttribute(fused_kernel, cudaFuncAttributeMaxDynamicSharedMemorySize, SMEM_BYTES);
    }
    CUtensorMap tmC, tmWk, tmWv, tmWq, tmWo, tmG, tmU, tmD;
    make_map2d(enc, &tmC, d_in[1], DC, SEQ);
    make_map2d(enc, &tmWq, d_in[2], 4096, DM, 64);
    make_map2d(enc, &tmWk, d_in[3], 4096, DC);
    make_map2d(enc, &tmWv, d_in[4], 4096, DC);
    make_map3d(enc, &tmWo, d_in[5], DM, 4096, 32, 5);
    make_map3d(enc, &tmG, d_in[8], FF, DM, 64, 7);
    make_map3d(enc, &tmU, d_in[9], FF, DM, 64, 7);
    make_map3d(enc, &tmD, d_in[10], DM, FF, 64, 10);
    Params P;
    P.x = (const __nv_bfloat16*)d_in[0];
    P.c = (const __nv_bfloat16*)d_in[1];
    P.wk = (const __nv_bfloat16*)d_in[3];
    P.wv = (const __nv_bfloat16*)d_in[4];
    P.wo = (const __nv_bfloat16*)d_in[5];
    P.wr = (const __nv_bfloat16*)d_in[7];
    P.out = (__nv_bfloat16*)d_out;
    fused_kernel<<<132, 384, SMEM_BYTES>>>(tmC, tmWk, tmWv, tmWq, tmWo, tmG, tmU, tmD, P);
}
```

```cpp
#include <cuda_runtime.h>
#include <cuda_bf16.h>
#include <cuda.h>
#include <stdint.h>

#define SWAPT 1
#define DEFER 1
#define HOLD0 6
#define HM 512
#define POLL1 1
#define OP_PF 8
#define PF_START 9
#define LATE_AT 18
#define CDELAY 500
#define AUXDELAY 1000
namespace {

constexpr int SEQ = 2048, NH = 32, DM = 640, DC = 512, FF = 1728, TOPC = 8;
constexpr int NSLOT = 7, SLOT_BYTES = 32768;
constexpr int NST3 = 6, ST3_BYTES = 36864;
constexpr int RING_BYTES = NSLOT * SLOT_BYTES;
constexpr int SMEM_BYTES = RING_BYTES + 3072;

constexpr int BAR_FULL = 96  , BAR_FULL3 = 152  , BAR_DEP = 200  , BAR_SEL = 464,
              BAR_LN = 472  , BAR_EV = 504  , BAR_EMPTY = 760  , BAR_EMPTY3 = 816  ,
              BAR_PROG = 864  , MISC_EPOCH = 896, MISC_SMID = 900  , MISC_SEL = 912, MISC_WR = 1024  ;
constexpr int D_LN = 0  , D_KV = 4  , D_WAR = 14  , D_CTX = 16  ;
constexpr int EV_KV = 0  , EV_CTX = 12  ;

constexpr int FL_MOE_CNT = 0, FL_MOE_DONE = 1, FL_LN = 16  , FL_KV = 32  , FL_CTX = 416  , FL_WAR = 672  , FL_TOTAL = 704;

__device__ __align__(1024) unsigned char g_K[16 * 32 * 16384];
__device__ __align__(1024) unsigned char g_V[16 * 32 * 16384];
__device__ __align__(1024) unsigned char g_ctx[NH * 32 * 16384];
__device__ __align__(1024) unsigned char g_xn[16 * 10 * 16384];
__device__ __align__(1024) uint4 g_part[128 * 10 * 256];
__device__ float g_router[SEQ];
__device__ uint2 g_stats[SEQ];
__device__ __align__(16) float g_moe_part[4 * TOPC * DM];
__device__ __align__(16) __nv_bfloat16 g_brow[TOPC * DM];
__device__ __align__(16) int g_sel[TOPC];
__device__ unsigned g_flags[FL_TOTAL * 8];
__device__ unsigned g_epoch;
__device__ unsigned g_roleq[130];

struct Params {
    const __nv_bfloat16 *x, *c, *wr, *wk, *wv, *wo;
    __nv_bfloat16* out;
};

__device__ __forceinline__ uint32_t smem_u32(const void* p) { return (uint32_t)__cvta_generic_to_shared(p); }
__device__ __forceinline__ void mbar_init(uint32_t bar, int cnt) { asm volatile("mbarrier.init.shared::cta.b64 [%0], %1;" ::"r"(bar), "r"(cnt)); }
__device__ __forceinline__ void mbar_expect_tx(uint32_t bar, uint32_t bytes) {
    asm volatile("mbarrier.arrive.expect_tx.shared::cta.b64 _, [%0], %1;" ::"r"(bar), "r"(bytes) : "memory");
}
__device__ __forceinline__ void mbar_arrive(uint32_t bar) { asm volatile("mbarrier.arrive.shared::cta.b64 _, [%0];" ::"r"(bar) : "memory"); }
__device__ __forceinline__ void mbar_arrive_cluster(uint32_t cluster_addr, uint32_t cnt) {
    asm volatile("mbarrier.arrive.shared::cluster.b64 _, [%0], %1;" ::"r"(cluster_addr), "r"(cnt) : "memory");
}
__device__ __forceinline__ uint32_t mapa(uint32_t addr, uint32_t cta) {
    uint32_t r; asm("mapa.shared::cluster.u32 %0, %1, %2;" : "=r"(r) : "r"(addr), "r"(cta)); return r;
}
__device__ __forceinline__ void mbar_wait(uint32_t bar, uint32_t parity) {
    asm volatile(
        "{\n.reg .pred p;\n.reg .u32 n;\n"
        "mbarrier.try_wait.parity.shared::cta.b64 p, [%0], %1;\n"
        "@p bra DONE;\n"
        "mov.u32 n, 0;\n"
        "LAB_WAIT:\n"
        "mbarrier.try_wait.parity.shared::cta.b64 p, [%0], %1, 100000;\n"
        "@p bra DONE;\n"
        "add.u32 n, n, 1;\n"
        "setp.lt.u32 p, n, 200000;\n"
        "@p bra LAB_WAIT;\n"
        "trap;\n"
        "DONE:\n}\n" ::"r"(bar), "r"(parity) : "memory");
}
__device__ __forceinline__ void mbar_wait_hot(uint32_t bar, uint32_t parity) {
    asm volatile("{\n.reg .pred p;\nLAB_WAIT:\nmbarrier.try_wait.parity.shared::cta.b64 p, [%0], %1;\n@!p bra LAB_WAIT;\n}\n" ::"r"(bar), "r"(parity) : "memory");
}
__device__ __forceinline__ void flag_wait(const unsigned* flag, unsigned target) {
    asm volatile(
        "{\n.reg .pred p;\n.reg .u32 n, v;\n.reg .s32 d;\n"
        "mov.u32 n, 0;\n"
        "LAB_WAIT:\n"
        "ld.acquire.gpu.global.u32 v, [%0];\n"
        "sub.s32 d, v, %1;\n"
        "setp.ge.s32 p, d, 0;\n"
        "@p bra DONE;\n"
        "nanosleep.u32 40;\n"
        "add.u32 n, n, 1;\n"
        "setp.lt.u32 p, n, 3000000;\n"
        "@p bra LAB_WAIT;\n"
        "trap;\n"
        "DONE:\n}\n" ::"l"(flag), "r"(target) : "memory");
}
__device__ __forceinline__ void flag_signal(unsigned* flag) {
    asm volatile("red.release.gpu.global.add.u32 [%0], 1;" ::"l"(flag) : "memory");
}
__device__ __forceinline__ void fence_async_global() { asm volatile("fence.proxy.async.global;" ::: "memory"); }
__device__ __forceinline__ unsigned* flag_ptr(int idx) { return g_flags + idx * 8; }

__device__ __forceinline__ uint64_t policy_stream() {
    uint64_t p; asm("createpolicy.fractional.L2::evict_first.b64 %0, 1.0;" : "=l"(p)); return p;
}
__device__ __forceinline__ uint64_t policy_normal() { return 0x1000000000000000ull; }
__device__ __forceinline__ uint64_t policy(bool stream) { return stream ? policy_stream() : policy_normal(); }
__device__ __forceinline__ void bulk_load(uint32_t dst, const void* src, uint32_t bytes, uint32_t bar, uint64_t pol) {
    asm volatile("cp.async.bulk.shared::cluster.global.mbarrier::complete_tx::bytes.L2::cache_hint [%0], [%1], %2, [%3], %4;"
                 ::"r"(dst), "l"(src), "r"(bytes), "r"(bar), "l"(pol) : "memory");
}
__device__ __forceinline__ void bulk_load_mc(uint32_t dst, const void* src, uint32_t bytes, uint32_t bar, uint64_t pol) {
    asm volatile("cp.async.bulk.shared::cluster.global.mbarrier::complete_tx::bytes.multicast::cluster.L2::cache_hint [%0], [%1], %2, [%3], %4, %5;"
                 ::"r"(dst), "l"(src), "r"(bytes), "r"(bar), "h"((uint16_t)3), "l"(pol) : "memory");
}
__device__ __forceinline__ void tma2d(uint32_t dst, const CUtensorMap* tm, int c0, int c1, uint32_t bar, uint64_t pol) {
    asm volatile("cp.async.bulk.tensor.2d.shared::cluster.global.mbarrier::complete_tx::bytes.L2::cache_hint [%0], [%1, {%3, %4}], [%2], %5;"
                 ::"r"(dst), "l"(tm), "r"(bar), "r"(c0), "r"(c1), "l"(pol) : "memory");
}
__device__ __forceinline__ void tma2d_mc(uint32_t dst, const CUtensorMap* tm, int c0, int c1, uint32_t bar, uint64_t pol) {
    asm volatile("cp.async.bulk.tensor.2d.shared::cluster.global.mbarrier::complete_tx::bytes.multicast::cluster.L2::cache_hint [%0], [%1, {%3, %4}], [%2], %5, %6;"
                 ::"r"(dst), "l"(tm), "r"(bar), "r"(c0), "r"(c1), "h"((uint16_t)3), "l"(pol) : "memory");
}
__device__ __forceinline__ void tma3d_mc(uint32_t dst, const CUtensorMap* tm, int c0, int c1, int c2, uint32_t bar, uint64_t pol) {
    asm volatile("cp.async.bulk.tensor.3d.shared::cluster.global.mbarrier::complete_tx::bytes.multicast::cluster.L2::cache_hint [%0], [%1, {%3, %4, %5}], [%2], %6, %7;"
                 ::"r"(dst), "l"(tm), "r"(bar), "r"(c0), "r"(c1), "r"(c2), "h"((uint16_t)3), "l"(pol) : "memory");
}
__device__ __forceinline__ void tma3d(uint32_t dst, const CUtensorMap* tm, int c0, int c1, int c2, uint32_t bar) {
    asm volatile("cp.async.bulk.tensor.3d.shared::cluster.global.mbarrier::complete_tx::bytes.L2::cache_hint [%0], [%1, {%3, %4, %5}], [%2], %6;"
                 ::"r"(dst), "l"(tm), "r"(bar), "r"(c0), "r"(c1), "r"(c2), "l"(policy_stream()) : "memory");
}
__device__ __forceinline__ void tma2d_prefetch(const CUtensorMap* tm, int c0, int c1) {
    asm volatile("cp.async.bulk.prefetch.tensor.2d.L2.global [%0, {%1, %2}];" ::"l"(tm), "r"(c0), "r"(c1) : "memory");
}
__device__ __forceinline__ void tma3d_prefetch(const CUtensorMap* tm, int c0, int c1, int c2) {
    asm volatile("cp.async.bulk.prefetch.tensor.3d.L2.global [%0, {%1, %2, %3}];" ::"l"(tm), "r"(c0), "r"(c1), "r"(c2) : "memory");
}
__device__ __forceinline__ void l2_prefetch(const void* p, uint32_t bytes) {
    asm volatile("cp.async.bulk.prefetch.L2.global [%0], %1;" ::"l"(p), "r"(bytes) : "memory");
}
__device__ __forceinline__ bool elect_one() {
    uint32_t r; asm volatile("{\n.reg .pred p;\nelect.sync _|p, 0xffffffff;\nselp.u32 %0, 1, 0, p;\n}\n" : "=r"(r)); return r != 0;
}
__device__ __forceinline__ void wg_fence() { asm volatile("wgmma.fence.sync.aligned;" ::: "memory"); }
__device__ __forceinline__ void wg_commit() { asm volatile("wgmma.commit_group.sync.aligned;" ::: "memory"); }
template <int N> __device__ __forceinline__ void wg_wait() { asm volatile("wgmma.wait_group.sync.aligned %0;" ::"n"(N) : "memory"); }
__device__ __forceinline__ void bar_sync(int id, int n) { asm volatile("bar.sync %0, %1;" ::"r"(id), "r"(n) : "memory"); }
__device__ __forceinline__ void bar_arrive(int id, int n) { asm volatile("bar.arrive %0, %1;" ::"r"(id), "r"(n) : "memory"); }
__device__ __forceinline__ void token_wait(int w) {
    asm volatile("{\n.reg .pred p;\nsetp.eq.u32 p, %0, 0;\n@p bar.sync 1, 256;\n@!p bar.sync 2, 256;\n}\n" ::"r"(w) : "memory");
}
__device__ __forceinline__ void token_pass(int w) {
    asm volatile("{\n.reg .pred p;\nsetp.eq.u32 p, %0, 0;\n@p bar.arrive 2, 256;\n@!p bar.arrive 1, 256;\n}\n" ::"r"(w) : "memory");
}
template <int N> __device__ __forceinline__ void fence_regs(float (&a)[N]) {
#pragma unroll
    for (int i = 0; i < N; i++) asm volatile("" : "+f"(a[i])::"memory");
}
template <int N> __device__ __forceinline__ void undef_regs(float (&a)[N]) {
#pragma unroll
    for (int i = 0; i < N; i++) asm volatile("" : "=f"(a[i]));
}
__device__ __forceinline__ void ldsm4t(uint32_t& r0, uint32_t& r1, uint32_t& r2, uint32_t& r3, uint32_t addr) {
    asm volatile("ldmatrix.sync.aligned.m8n8.x4.trans.shared.b16 {%0,%1,%2,%3}, [%4];"
                 : "=r"(r0), "=r"(r1), "=r"(r2), "=r"(r3) : "r"(addr) : "memory");
}
__device__ __forceinline__ uint32_t pack_bf16(float lo, float hi) {
    uint32_t r; asm("cvt.rn.bf16x2.f32 %0, %1, %2;" : "=r"(r) : "f"(hi), "f"(lo)); return r;
}
__device__ __forceinline__ float bf_lo(uint32_t v) { return __uint_as_float(v << 16); }
__device__ __forceinline__ float bf_hi(uint32_t v) { return __uint_as_float(v & 0xffff0000u); }
__device__ __forceinline__ float bf_round(float v) { return __bfloat162float(__float2bfloat16_rn(v)); }
__device__ __forceinline__ float ex2(float v) { float r; asm("ex2.approx.ftz.f32 %0, %1;" : "=f"(r) : "f"(v)); return r; }
__device__ __forceinline__ void ex2v(float& v) { asm volatile("ex2.approx.ftz.f32 %0, %0;" : "+f"(v)); }
__device__ __forceinline__ float rcp_fast(float v) { float r; asm("rcp.approx.ftz.f32 %0, %1;" : "=f"(r) : "f"(v)); return r; }
__device__ __forceinline__ float sqrt_fast(float v) { float r; asm("sqrt.approx.ftz.f32 %0, %1;" : "=f"(r) : "f"(v)); return r; }
__device__ __forceinline__ void stg128(void* p, uint32_t a, uint32_t b, uint32_t c, uint32_t d) {
    asm volatile("st.global.v4.b32 [%0], {%1,%2,%3,%4};" ::"l"(p), "r"(a), "r"(b), "r"(c), "r"(d) : "memory");
}
__device__ __forceinline__ uint4 ldg128(const void* p) {
    uint4 v; asm volatile("ld.global.cg.v4.b32 {%0,%1,%2,%3}, [%4];" : "=r"(v.x), "=r"(v.y), "=r"(v.z), "=r"(v.w) : "l"(p) : "memory"); return v;
}
__device__ __forceinline__ uint64_t mkdesc(uint32_t addr, uint32_t lbo, uint32_t sbo, uint32_t swz) {
    uint32_t lo = ((addr & 0x3FFFF) >> 4) | ((lbo >> 4) << 16);
    uint32_t hi = (sbo >> 4) | (swz << 30);
    return ((uint64_t)hi << 32) | lo;
}
__device__ __forceinline__ int perm32(int v) { return (v & ~30) | ((v >> 2) & 6) | ((v << 2) & 24); }

__device__ __forceinline__ void wgmma_rs_n128_ta0_tb0(float (&d)[64], uint32_t a0, uint32_t a1, uint32_t a2, uint32_t a3, uint64_t descB, int scaleD) {
  asm volatile("{\n.reg .pred p;\nsetp.ne.b32 p, %69, 0;\n"
    "wgmma.mma_async.sync.aligned.m64n128k16.f32.bf16.bf16 "
    "{%0, %1, %2, %3, %4, %5, %6, %7, %8, %9, %10, %11, %12, %13, %14, %15, %16, %17, %18, %19, %20, %21, %22, %23, %24, %25, %26, %27, %28, %29, %30, %31, %32, %33, %34, %35, %36, %37, %38, %39, %40, %41, %42, %43, %44, %45, %46, %47, %48, %49, %50, %51, %52, %53, %54, %55, %56, %57, %58, %59, %60, %61, %62, %63}, "
    "{%64, %65, %66, %67}, %68, p, 1, 1, 0;\n}\n"
    : "+f"(d[0]), "+f"(d[1]), "+f"(d[2]), "+f"(d[3]), "+f"(d[4]), "+f"(d[5]), "+f"(d[6]), "+f"(d[7]), "+f"(d[8]), "+f"(d[9]), "+f"(d[10]), "+f"(d[11]), "+f"(d[12]), "+f"(d[13]), "+f"(d[14]), "+f"(d[15]), "+f"(d[16]), "+f"(d[17]), "+f"(d[18]), "+f"(d[19]), "+f"(d[20]), "+f"(d[21]), "+f"(d[22]), "+f"(d[23]), "+f"(d[24]), "+f"(d[25]), "+f"(d[26]), "+f"(d[27]), "+f"(d[28]), "+f"(d[29]), "+f"(d[30]), "+f"(d[31]), "+f"(d[32]), "+f"(d[33]), "+f"(d[34]), "+f"(d[35]), "+f"(d[36]), "+f"(d[37]), "+f"(d[38]), "+f"(d[39]), "+f"(d[40]), "+f"(d[41]), "+f"(d[42]), "+f"(d[43]), "+f"(d[44]), "+f"(d[45]), "+f"(d[46]), "+f"(d[47]), "+f"(d[48]), "+f"(d[49]), "+f"(d[50]), "+f"(d[51]), "+f"(d[52]), "+f"(d[53]), "+f"(d[54]), "+f"(d[55]), "+f"(d[56]), "+f"(d[57]), "+f"(d[58]), "+f"(d[59]), "+f"(d[60]), "+f"(d[61]), "+f"(d[62]), "+f"(d[63])
    : "r"(a0), "r"(a1), "r"(a2), "r"(a3), "l"(descB), "r"(scaleD));
}
__device__ __forceinline__ void wgmma_rs_n128_ta0_tb1(float (&d)[64], uint32_t a0, uint32_t a1, uint32_t a2, uint32_t a3, uint64_t descB, int scaleD) {
  asm volatile("{\n.reg .pred p;\nsetp.ne.b32 p, %69, 0;\n"
    "wgmma.mma_async.sync.aligned.m64n128k16.f32.bf16.bf16 "
    "{%0, %1, %2, %3, %4, %5, %6, %7, %8, %9, %10, %11, %12, %13, %14, %15, %16, %17, %18, %19, %20, %21, %22, %23, %24, %25, %26, %27, %28, %29, %30, %31, %32, %33, %34, %35, %36, %37, %38, %39, %40, %41, %42, %43, %44, %45, %46, %47, %48, %49, %50, %51, %52, %53, %54, %55, %56, %57, %58, %59, %60, %61, %62, %63}, "
    "{%64, %65, %66, %67}, %68, p, 1, 1, 1;\n}\n"
    : "+f"(d[0]), "+f"(d[1]), "+f"(d[2]), "+f"(d[3]), "+f"(d[4]), "+f"(d[5]), "+f"(d[6]), "+f"(d[7]), "+f"(d[8]), "+f"(d[9]), "+f"(d[10]), "+f"(d[11]), "+f"(d[12]), "+f"(d[13]), "+f"(d[14]), "+f"(d[15]), "+f"(d[16]), "+f"(d[17]), "+f"(d[18]), "+f"(d[19]), "+f"(d[20]), "+f"(d[21]), "+f"(d[22]), "+f"(d[23]), "+f"(d[24]), "+f"(d[25]), "+f"(d[26]), "+f"(d[27]), "+f"(d[28]), "+f"(d[29]), "+f"(d[30]), "+f"(d[31]), "+f"(d[32]), "+f"(d[33]), "+f"(d[34]), "+f"(d[35]), "+f"(d[36]), "+f"(d[37]), "+f"(d[38]), "+f"(d[39]), "+f"(d[40]), "+f"(d[41]), "+f"(d[42]), "+f"(d[43]), "+f"(d[44]), "+f"(d[45]), "+f"(d[46]), "+f"(d[47]), "+f"(d[48]), "+f"(d[49]), "+f"(d[50]), "+f"(d[51]), "+f"(d[52]), "+f"(d[53]), "+f"(d[54]), "+f"(d[55]), "+f"(d[56]), "+f"(d[57]), "+f"(d[58]), "+f"(d[59]), "+f"(d[60]), "+f"(d[61]), "+f"(d[62]), "+f"(d[63])
    : "r"(a0), "r"(a1), "r"(a2), "r"(a3), "l"(descB), "r"(scaleD));
}
__device__ __forceinline__ void wgmma_rs_n64_ta0_tb1(float (&d)[32], uint32_t a0, uint32_t a1, uint32_t a2, uint32_t a3, uint64_t descB, int scaleD) {
  asm volatile("{\n.reg .pred p;\nsetp.ne.b32 p, %37, 0;\n"
    "wgmma.mma_async.sync.aligned.m64n64k16.f32.bf16.bf16 "
    "{%0, %1, %2, %3, %4, %5, %6, %7, %8, %9, %10, %11, %12, %13, %14, %15, %16, %17, %18, %19, %20, %21, %22, %23, %24, %25, %26, %27, %28, %29, %30, %31}, "
    "{%32, %33, %34, %35}, %36, p, 1, 1, 1;\n}\n"
    : "+f"(d[0]), "+f"(d[1]), "+f"(d[2]), "+f"(d[3]), "+f"(d[4]), "+f"(d[5]), "+f"(d[6]), "+f"(d[7]), "+f"(d[8]), "+f"(d[9]), "+f"(d[10]), "+f"(d[11]), "+f"(d[12]), "+f"(d[13]), "+f"(d[14]), "+f"(d[15]), "+f"(d[16]), "+f"(d[17]), "+f"(d[18]), "+f"(d[19]), "+f"(d[20]), "+f"(d[21]), "+f"(d[22]), "+f"(d[23]), "+f"(d[24]), "+f"(d[25]), "+f"(d[26]), "+f"(d[27]), "+f"(d[28]), "+f"(d[29]), "+f"(d[30]), "+f"(d[31])
    : "r"(a0), "r"(a1), "r"(a2), "r"(a3), "l"(descB), "r"(scaleD));
}
__device__ __forceinline__ void wgmma_ss_n128_ta0_tb1(float (&d)[64], uint64_t descA, uint64_t descB, int scaleD) {
  asm volatile("{\n.reg .pred p;\nsetp.ne.b32 p, %66, 0;\n"
    "wgmma.mma_async.sync.aligned.m64n128k16.f32.bf16.bf16 "
    "{%0, %1, %2, %3, %4, %5, %6, %7, %8, %9, %10, %11, %12, %13, %14, %15, %16, %17, %18, %19, %20, %21, %22, %23, %24, %25, %26, %27, %28, %29, %30, %31, %32, %33, %34, %35, %36, %37, %38, %39, %40, %41, %42, %43, %44, %45, %46, %47, %48, %49, %50, %51, %52, %53, %54, %55, %56, %57, %58, %59, %60, %61, %62, %63}, "
    "%64, %65, p, 1, 1, 0, 1;\n}\n"
    : "+f"(d[0]), "+f"(d[1]), "+f"(d[2]), "+f"(d[3]), "+f"(d[4]), "+f"(d[5]), "+f"(d[6]), "+f"(d[7]), "+f"(d[8]), "+f"(d[9]), "+f"(d[10]), "+f"(d[11]), "+f"(d[12]), "+f"(d[13]), "+f"(d[14]), "+f"(d[15]), "+f"(d[16]), "+f"(d[17]), "+f"(d[18]), "+f"(d[19]), "+f"(d[20]), "+f"(d[21]), "+f"(d[22]), "+f"(d[23]), "+f"(d[24]), "+f"(d[25]), "+f"(d[26]), "+f"(d[27]), "+f"(d[28]), "+f"(d[29]), "+f"(d[30]), "+f"(d[31]), "+f"(d[32]), "+f"(d[33]), "+f"(d[34]), "+f"(d[35]), "+f"(d[36]), "+f"(d[37]), "+f"(d[38]), "+f"(d[39]), "+f"(d[40]), "+f"(d[41]), "+f"(d[42]), "+f"(d[43]), "+f"(d[44]), "+f"(d[45]), "+f"(d[46]), "+f"(d[47]), "+f"(d[48]), "+f"(d[49]), "+f"(d[50]), "+f"(d[51]), "+f"(d[52]), "+f"(d[53]), "+f"(d[54]), "+f"(d[55]), "+f"(d[56]), "+f"(d[57]), "+f"(d[58]), "+f"(d[59]), "+f"(d[60]), "+f"(d[61]), "+f"(d[62]), "+f"(d[63])
    : "l"(descA), "l"(descB), "r"(scaleD));
}
__device__ __forceinline__ void wgmma_ss_n160_ta0_tb1(float (&d)[80], uint64_t descA, uint64_t descB, int scaleD) {
  asm volatile("{\n.reg .pred p;\nsetp.ne.b32 p, %82, 0;\n"
    "wgmma.mma_async.sync.aligned.m64n160k16.f32.bf16.bf16 "
    "{%0, %1, %2, %3, %4, %5, %6, %7, %8, %9, %10, %11, %12, %13, %14, %15, %16, %17, %18, %19, %20, %21, %22, %23, %24, %25, %26, %27, %28, %29, %30, %31, %32, %33, %34, %35, %36, %37, %38, %39, %40, %41, %42, %43, %44, %45, %46, %47, %48, %49, %50, %51, %52, %53, %54, %55, %56, %57, %58, %59, %60, %61, %62, %63, %64, %65, %66, %67, %68, %69, %70, %71, %72, %73, %74, %75, %76, %77, %78, %79}, "
    "%80, %81, p, 1, 1, 0, 1;\n}\n"
    : "+f"(d[0]), "+f"(d[1]), "+f"(d[2]), "+f"(d[3]), "+f"(d[4]), "+f"(d[5]), "+f"(d[6]), "+f"(d[7]), "+f"(d[8]), "+f"(d[9]), "+f"(d[10]), "+f"(d[11]), "+f"(d[12]), "+f"(d[13]), "+f"(d[14]), "+f"(d[15]), "+f"(d[16]), "+f"(d[17]), "+f"(d[18]), "+f"(d[19]), "+f"(d[20]), "+f"(d[21]), "+f"(d[22]), "+f"(d[23]), "+f"(d[24]), "+f"(d[25]), "+f"(d[26]), "+f"(d[27]), "+f"(d[28]), "+f"(d[29]), "+f"(d[30]), "+f"(d[31]), "+f"(d[32]), "+f"(d[33]), "+f"(d[34]), "+f"(d[35]), "+f"(d[36]), "+f"(d[37]), "+f"(d[38]), "+f"(d[39]), "+f"(d[40]), "+f"(d[41]), "+f"(d[42]), "+f"(d[43]), "+f"(d[44]), "+f"(d[45]), "+f"(d[46]), "+f"(d[47]), "+f"(d[48]), "+f"(d[49]), "+f"(d[50]), "+f"(d[51]), "+f"(d[52]), "+f"(d[53]), "+f"(d[54]), "+f"(d[55]), "+f"(d[56]), "+f"(d[57]), "+f"(d[58]), "+f"(d[59]), "+f"(d[60]), "+f"(d[61]), "+f"(d[62]), "+f"(d[63]), "+f"(d[64]), "+f"(d[65]), "+f"(d[66]), "+f"(d[67]), "+f"(d[68]), "+f"(d[69]), "+f"(d[70]), "+f"(d[71]), "+f"(d[72]), "+f"(d[73]), "+f"(d[74]), "+f"(d[75]), "+f"(d[76]), "+f"(d[77]), "+f"(d[78]), "+f"(d[79])
    : "l"(descA), "l"(descB), "r"(scaleD));
}

#define PROF_DECL(b)
#define PROF_EV(tag)
#define PROF_GT(tag)

template <int N> struct IC { static constexpr int value = N; };
struct Cur {
    uint32_t slot, ph;
    __device__ __forceinline__ void adv() { if (++slot == NSLOT) { slot = 0; ph ^= 1; } }
};
constexpr int E0 = 2;
__host__ __device__ constexpr uint32_t slot_of(int e) { return (e + E0) % NSLOT; }
__device__ __forceinline__ Cur cur_at(int e) { Cur c; c.slot = (e + E0) % NSLOT; c.ph = ((e + E0) / NSLOT) & 1; return c; }

__device__ __forceinline__ int op_head(int i, int kap) { return 16 * kap + 2 * (i & 7) + (i >> 3); }

constexpr float SM_SCALE = 0.08838834764831845f * 1.4426950408889634f;

struct Ctx {
    uint32_t ring, misc;
    uint32_t rel;
    int w, warp, lane;
};
__device__ __forceinline__ void release(const Ctx& c, uint32_t off, uint32_t cnt) {
    if (c.lane < 2) mbar_arrive_cluster(c.rel + off, cnt);
}
__device__ __forceinline__ void signal_event(const Ctx& c, int ev) {
    __syncwarp();
    if (c.lane == 0) mbar_arrive(c.misc + BAR_EV + (c.w * 16 + ev) * 8);
}
template <int NK, int OFF, int N>
__device__ __forceinline__ uint32_t load_afrag(uint32_t (&a)[N], uint32_t base, const Ctx& c) {
    int r = c.lane & 7, mat = c.lane >> 3;
    uint32_t addr = base + (8 * (mat >> 1) + r) * 128 + (((2 * c.warp + (mat & 1)) ^ r) << 4);
#pragma unroll
    for (int k = 0; k < NK; k++) ldsm4t(a[OFF + 4 * k], a[OFF + 4 * k + 1], a[OFF + 4 * k + 2], a[OFF + 4 * k + 3], addr + k * 2048);
    uint32_t dep = 0;
#pragma unroll
    for (int k = 0; k < NK; k++) dep |= a[OFF + 4 * k];
    return dep & blockIdx.y;
}
__device__ __forceinline__ void tile_out(unsigned char* (&out)[2], unsigned char* dst, int row0, int perm, const Ctx& c) {
#pragma unroll
    for (int i = 0; i < 2; i++) {
        int row = row0 + 16 * c.warp + 8 * i + (c.lane >> 2);
        if (perm) row = perm32(row);
        out[i] = dst + row * 128 + (((c.lane & 3) ^ (row & 7)) << 4);
    }
}
__device__ __forceinline__ void store_pair(const float (&a)[64], int n, unsigned char* const (&out)[2], int half_stride, const float (&f)[2]) {
    const int i = n & 1;
#pragma unroll
    for (int q = 2 * (n >> 1); q < 2 * (n >> 1) + 2; q++)
        stg128(reinterpret_cast<unsigned char*>(reinterpret_cast<uint64_t>(out[i]) ^ ((q & 1) << 6)) + (q >> 1) * half_stride,
               pack_bf16(a[16 * q + 2 * i] * f[i], a[16 * q + 2 * i + 1] * f[i]), pack_bf16(a[16 * q + 4 + 2 * i] * f[i], a[16 * q + 4 + 2 * i + 1] * f[i]),
               pack_bf16(a[16 * q + 8 + 2 * i] * f[i], a[16 * q + 8 + 2 * i + 1] * f[i]), pack_bf16(a[16 * q + 12 + 2 * i] * f[i], a[16 * q + 12 + 2 * i + 1] * f[i]));
}

constexpr float SAFE_SUM = 1099511627776.0f;
template <int NJ>
__device__ __forceinline__ void row_max(const float (&s)[4 * NJ], float (&mx)[2]) {
#pragma unroll
    for (int i = 0; i < 2; i++) {
        float a = fmaxf(s[2 * i], s[2 * i + 1]), b = fmaxf(s[4 + 2 * i], s[4 + 2 * i + 1]);
#pragma unroll
        for (int j = 2; j < NJ; j += 2) {
            a = fmaxf(a, fmaxf(s[4 * j + 2 * i], s[4 * j + 2 * i + 1]));
            b = fmaxf(b, fmaxf(s[4 * j + 4 + 2 * i], s[4 * j + 4 + 2 * i + 1]));
        }
        a = fmaxf(a, b);
        a = fmaxf(a, __shfl_xor_sync(0xffffffffu, a, 1));
        mx[i] = fmaxf(a, __shfl_xor_sync(0xffffffffu, a, 2));
    }
}
template <int NJ, bool SHIFT>
__device__ __forceinline__ void exp_sum(float (&s)[4 * NJ], const float (&m)[2], float& l0, float& l1) {
#pragma unroll
    for (int j = 0; j < NJ; j++) {
#pragma unroll
        for (int e = 0; e < 4; e++) s[4 * j + e] = ex2(SHIFT ? s[4 * j + e] - m[e >> 1] : s[4 * j + e]);
        l0 += s[4 * j + 0] + s[4 * j + 1]; l1 += s[4 * j + 2] + s[4 * j + 3];
    }
}
__device__ __forceinline__ void recompute_scores(float (&s)[64], const uint32_t (&q)[32], uint32_t kaddr, const Ctx& c) {
    const int r = c.lane & 7, mat = c.lane >> 3;
    const uint32_t a0 = kaddr + (8 * (mat & 1) + r) * 128 + (((mat >> 1) ^ r) << 4);
#pragma unroll
    for (int i = 0; i < 64; i++) s[i] = 0.f;
#pragma unroll
    for (int jp = 0; jp < 8; jp++) {
#pragma unroll
        for (int k = 0; k < 8; k++) {
            asm volatile(
                "{\n.reg .b32 b0, b1, b2, b3;\n"
                "ldmatrix.sync.aligned.m8n8.x4.trans.shared.b16 {b0,b1,b2,b3}, [%12];\n"
                "mma.sync.aligned.m16n8k16.row.col.f32.bf16.bf16.f32 {%0,%1,%2,%3}, {%8,%9,%10,%11}, {b0,b1}, {%0,%1,%2,%3};\n"
                "mma.sync.aligned.m16n8k16.row.col.f32.bf16.bf16.f32 {%4,%5,%6,%7}, {%8,%9,%10,%11}, {b2,b3}, {%4,%5,%6,%7};\n}\n"
                : "+f"(s[8 * jp]), "+f"(s[8 * jp + 1]), "+f"(s[8 * jp + 2]), "+f"(s[8 * jp + 3]),
                  "+f"(s[8 * jp + 4]), "+f"(s[8 * jp + 5]), "+f"(s[8 * jp + 6]), "+f"(s[8 * jp + 7])
                : "r"(q[4 * k]), "r"(q[4 * k + 1]), "r"(q[4 * k + 2]), "r"(q[4 * k + 3]),
                  "r"((a0 ^ ((jp & 3) << 5)) + (jp >> 2) * 16384 + k * 2048) : "memory");
        }
    }
}
__device__ __forceinline__ int mask_lim(const Ctx& c) { return perm32(16 * c.warp + (c.lane >> 2)) - 8 * (c.lane & 3); }
template <int J0>
__device__ __forceinline__ void mask_diag(float (&s)[4 * J0 + 32], const Ctx& c) {
    const int lim = mask_lim(c);
    if (c.warp < 2) {
#pragma unroll
        for (int x = 0; x < 16; x++) {
            if (2 * (x >> 2) + (x & 1) - (x & 2) > lim) s[4 * J0 + x] = -INFINITY;
            s[4 * J0 + 16 + x] = -INFINITY;
        }
    } else {
#pragma unroll
        for (int x = 0; x < 16; x++)
            if (32 + 2 * (x >> 2) + (x & 1) - (x & 2) > lim) s[4 * J0 + 16 + x] = -INFINITY;
    }
}
__device__ __forceinline__ void mask_any(float (&s)[64], int hh, const Ctx& c) {
    const int lim = mask_lim(c) + 64 * hh;
#pragma unroll
    for (int x = 0; x < 64; x++)
        if (32 * (x >> 4) + 2 * ((x >> 2) & 3) + (x & 1) - (x & 2) > lim) s[x] = -INFINITY;
}
__device__ __forceinline__ void issue_pv(float (&o)[64], const uint32_t (&p)[32], uint32_t vaddr, int acc, int mode  ) {
    uint64_t d = mkdesc(vaddr, 16, 1024, 1);
    if (mode == 0) {
        wg_fence();
#pragma unroll
        for (int k = 0; k < 8; k++)
            wgmma_rs_n128_ta0_tb0(o, p[4 * k], p[4 * k + 1], p[4 * k + 2], p[4 * k + 3], d + (k >> 2) * 1024 + 2 * (k & 3), k ? 1 : acc);
        wg_commit();
    } else if (mode == 1) {
        wg_fence();
#pragma unroll
        for (int k = 0; k < 4; k++) wgmma_rs_n128_ta0_tb0(o, p[4 * k], p[4 * k + 1], p[4 * k + 2], p[4 * k + 3], d + 2 * k, k != 0);
        wg_commit();
    } else {
        wg_fence();
        wgmma_rs_n128_ta0_tb0(o, p[0], p[1], p[2], p[3], d, acc);
        wg_commit();
    }
}
__device__ __forceinline__ void issue_qk(float (&s)[64], const uint32_t (&q)[32], uint32_t kaddr) {
    uint64_t d = mkdesc(kaddr, 16384, 1024, 1);
    wg_fence();
#pragma unroll
    for (int k = 0; k < 8; k++) wgmma_rs_n128_ta0_tb1(s, q[4 * k], q[4 * k + 1], q[4 * k + 2], q[4 * k + 3], d + 128 * k, k != 0);
    wg_commit();
}
__device__ __forceinline__ void issue_qk_half(float (&s32)[32], const uint32_t (&q)[32], uint32_t kaddr) {
    uint64_t d = mkdesc(kaddr, 16384, 1024, 1);
    wg_fence();
#pragma unroll
    for (int k = 0; k < 8; k++) wgmma_rs_n64_ta0_tb1(s32, q[4 * k], q[4 * k + 1], q[4 * k + 2], q[4 * k + 3], d + 128 * k, k != 0);
    wg_commit();
}
__device__ __forceinline__ void row_inv(const float (&l)[2], float (&inv)[2]) {
#pragma unroll
    for (int i = 0; i < 2; i++) {
        float sum = l[i];
        sum += __shfl_xor_sync(0xffffffffu, sum, 1);
        sum += __shfl_xor_sync(0xffffffffu, sum, 2);
        inv[i] = rcp_fast(sum);
    }
}

__device__ __forceinline__ const unsigned char* xn_addr(int row, int col) {
    row = perm32(row);
    return g_xn + ((row >> 7) * 10 + (col >> 6)) * 16384 + (row & 127) * 128 + ((((col & 63) >> 3) ^ (row & 7)) << 4);
}
__device__ __forceinline__ void mma16816(float (&d)[4], uint32_t a0, uint32_t a1, uint32_t a2, uint32_t a3, uint32_t b0, uint32_t b1) {
    asm volatile("mma.sync.aligned.m16n8k16.row.col.f32.bf16.bf16.f32 {%0,%1,%2,%3}, {%4,%5,%6,%7}, {%8,%9}, {%0,%1,%2,%3};"
                 : "+f"(d[0]), "+f"(d[1]), "+f"(d[2]), "+f"(d[3]) : "r"(a0), "r"(a1), "r"(a2), "r"(a3), "r"(b0), "r"(b1));
}
__device__ __forceinline__ uint32_t lds32(uint32_t addr) { uint32_t v; asm volatile("ld.shared.u32 %0, [%1];" : "=r"(v) : "r"(addr)); return v; }

__device__ __forceinline__ void ln_rows(const Params& P, int row0, int lane, uint32_t wr_s) {
    const int hl = lane & 15, row = row0 + (lane >> 4);
    uint32_t v[20];
#pragma unroll
    for (int i = 0; i < 5; i++) {
        uint4 u;
        asm("ld.global.nc.L2::cache_hint.v4.b32 {%0,%1,%2,%3}, [%4], %5;" : "=r"(u.x), "=r"(u.y), "=r"(u.z), "=r"(u.w)
            : "l"(P.x + (size_t)row * DM + 128 * i + 8 * hl), "l"(policy(HM & 512)));
        v[4 * i] = u.x; v[4 * i + 1] = u.y; v[4 * i + 2] = u.z; v[4 * i + 3] = u.w;
    }
    float mean = 0.f, m2 = 0.f, acc2 = 0.f;
#pragma unroll
    for (int i = 0; i < 20; i++) { mean += bf_lo(v[i]); acc2 += bf_hi(v[i]); }
    mean = (mean + acc2) * (1.0f / 40);
    acc2 = 0.f;
#pragma unroll
    for (int i = 0; i < 20; i++) {
        float d0 = __uint_as_float(__byte_perm(v[i], 0, 0x1044)) - mean, d1 = __uint_as_float(__byte_perm(v[i], 0, 0x3244)) - mean;
        m2 = fmaf(d0, d0, m2); acc2 = fmaf(d1, d1, acc2);
    }
    m2 += acc2;
    acc2 = 0.f;
#pragma unroll
    for (int o = 1; o < 16; o <<= 1) {
        float mo = __shfl_xor_sync(0xffffffffu, mean, o), qo = __shfl_xor_sync(0xffffffffu, m2, o), d = mo - mean;
        m2 = fmaf(d * d, 20.0f * o, m2 + qo);
        mean = 0.5f * (mean + mo);
    }
    const uint32_t mb2 = pack_bf16(mean, mean);
    const float inv = rcp_fast(bf_round(sqrt_fast(bf_round(bf_round(m2 * (1.0f / DM)) + 1e-5f))));
    float dot = 0.f;
    unsigned char* xp = const_cast<unsigned char*>(xn_addr(row, 8 * hl));
#pragma unroll
    for (int i = 0; i < 5; i++) {
        uint32_t ww[4];
        asm volatile("ld.shared.v4.b32 {%0,%1,%2,%3}, [%4];" : "=r"(ww[0]), "=r"(ww[1]), "=r"(ww[2]), "=r"(ww[3]) : "r"(wr_s + 256 * i + 16 * hl) : "memory");
#pragma unroll
        for (int e = 0; e < 4; e++) {
            uint32_t d;
            asm("sub.rn.bf16x2 %0, %1, %2;" : "=r"(d) : "r"(v[4 * i + e]), "r"(mb2));
            d = pack_bf16(bf_lo(d) * inv, bf_hi(d) * inv);
            v[4 * i + e] = d;
            dot = fmaf(bf_lo(d), bf_lo(ww[e]), dot);
            acc2 = fmaf(bf_hi(d), bf_hi(ww[e]), acc2);
        }
        stg128(xp + i * 32768, v[4 * i], v[4 * i + 1], v[4 * i + 2], v[4 * i + 3]);
    }
    dot += acc2;
#pragma unroll
    for (int o = 8; o > 0; o >>= 1) dot += __shfl_xor_sync(0xffffffffu, dot, o);
    if (hl == 0) { g_router[row] = bf_round(dot); g_stats[row] = make_uint2(mb2, __float_as_uint(inv)); }
}

__device__ __forceinline__ void aux_cta(const Params& P, const CUtensorMap* tmG, const CUtensorMap* tmU, const CUtensorMap* tmD, unsigned char* sm, int a) {
    constexpr int STG = 57344, XS = 3 * STG, HS = XS + 8 * 1296, KEY = HS + 8 * 912, MI = KEY + 8192;
    const int tid = threadIdx.x, warp = __shfl_sync(0xffffffffu, tid >> 5, 0), lane = tid & 31;
    const uint32_t sb = smem_u32(sm);
    const uint32_t full = sb + MI, empty = sb + MI + 32;
    int* s_sel = reinterpret_cast<int*>(sm + MI + 64);
    float* s_r = reinterpret_cast<float*>(sm + MI + 96);
    volatile unsigned* s_misc = reinterpret_cast<volatile unsigned*>(sm + MI + 128);
    uint32_t* s_key = reinterpret_cast<uint32_t*>(sm + KEY);
    PROF_DECL(128 + a)
    PROF_GT(0);
    if (tid == 0) {
        for (int i = 0; i < 3; i++) { mbar_init(full + 8 * i, 1); mbar_init(empty + 8 * i, 10); }
        asm volatile("fence.mbarrier_init.release.cluster;" ::: "memory");
    }
    __syncthreads();
    if (warp == 11) {
        if (elect_one()) {
            int st = 0; uint32_t ph = 0;
#pragma unroll 1
            for (int s = 0; s < 34; s++) {
                mbar_wait(empty + 8 * st, ph ^ 1);
                const uint32_t dst = sb + st * STG, fb = full + 8 * st;
                if (s < 20) {
                    mbar_expect_tx(fb, 57344);
                    tma3d(dst, tmG, 0, 32 * s, 7 * a, fb);
                    tma3d(dst + 28672, tmU, 0, 32 * s, 7 * a, fb);
                } else {
                    mbar_expect_tx(fb, 40960);
                    tma3d(dst, tmD, 0, 448 * a + 32 * (s - 20), 0, fb);
                }
                if (s >= 3) {
#pragma unroll 1
                    for (int f = (s == 3 ? 4 : s + 6); f <= s + 6 && f < 34; f++) {
                        if (f < 20) { tma3d_prefetch(tmG, 0, 32 * f, 7 * a); tma3d_prefetch(tmU, 0, 32 * f, 7 * a); }
                        else tma3d_prefetch(tmD, 0, 448 * a + 32 * (f - 20), 0);
                    }
                }
                if (++st == 3) { st = 0; ph ^= 1; }
            }
        }
        return;
    }
    if (tid < 80) *reinterpret_cast<uint4*>(sm + KEY + 1024 + tid * 16) = __ldg(reinterpret_cast<const uint4*>(P.wr) + tid);
    __nanosleep(AUXDELAY);
#pragma unroll 1
    for (int i = tid; i < 64 * 40; i += 352) asm volatile("prefetch.global.L2 [%0];" ::"l"(P.x + (size_t)((4 + a) * 256 + 192) * DM + i * 16));
    bar_sync(2, 352);
#pragma unroll 1
    for (int i = warp; i < 32; i += 11) ln_rows(P, (4 + a) * 256 + 192 + 2 * i, lane, sb + KEY + 1024);
    bar_sync(2, 352);
    if (tid == 320) flag_signal(flag_ptr(FL_LN + 4 + a));
    PROF_GT(49);
    if (warp == 10) return;
    if (tid < 8) {
        unsigned e = *reinterpret_cast<volatile unsigned*>(&g_epoch);
        if (tid == 0) s_misc[0] = e;
        flag_wait(flag_ptr(FL_LN + tid), (e + 1) * (32u + (tid >> 2)));
    }
    bar_sync(1, 320);
    PROF_GT(50);
    const unsigned ep = s_misc[0];
    auto top8 = [&](uint32_t (&key)[8]) {
        uint32_t mine = 0;
#pragma unroll 1
        for (int r = 0; r < TOPC; r++) {
            uint32_t best = 0;
#pragma unroll
            for (int i = 0; i < 8; i++) best = max(best, key[i]);
            best = __reduce_max_sync(0xffffffffu, best);
#pragma unroll
            for (int i = 0; i < 8; i++) if (key[i] == best) key[i] = 0;
            if (lane == r) mine = best;
        }
        return mine;
    };
#pragma unroll 1
    for (int pass = 0; pass < 2; pass++) {
        if (warp < (pass ? 1 : 8)) {
            uint32_t key[8];
#pragma unroll
            for (int i = 0; i < 8; i++) {
                if (pass == 0) {
                    int idx = warp * 256 + i * 32 + lane;
                    uint32_t b = __float_as_uint(__ldcg(g_router + idx)) >> 16;
                    b = (b & 0x8000u) ? (~b & 0xffffu) : (b | 0x8000u);
                    key[i] = (b << 16) | (uint32_t)(0xffff - idx);
                } else key[i] = i < 2 ? s_key[i * 32 + lane] : 0u;
            }
            uint32_t best = top8(key);
            if (lane < TOPC) {
                if (pass == 0) s_key[warp * 8 + lane] = best;
                else {
                    uint32_t b = best >> 16;
                    b = (b & 0x8000u) ? (b & 0x7fffu) : (~b & 0xffffu);
                    s_sel[lane] = 0xffff - (int)(best & 0xffffu);
                    s_r[lane] = __uint_as_float(b << 16);
                }
            }
        }
        bar_sync(1, 320);
    }
#pragma unroll
    for (int it = 0; it < 2; it++) {
        int i = tid + it * 320, tk = i / 80, ch = i % 80;
        *reinterpret_cast<uint4*>(sm + XS + tk * 1296 + ch * 16) = __ldcg(reinterpret_cast<const uint4*>(xn_addr(s_sel[tk], ch * 8)));
    }
    bar_sync(1, 320);
    PROF_GT(51);
    const int g = lane >> 2, t = lane & 3;
    const uint32_t woff = warp * 4096 + (8 * (lane >> 4) + (lane & 7)) * 128 + ((((lane >> 3) & 1) ^ (lane & 7)) << 4);
    int st = 0; uint32_t ph = 0;
    float ga[4][4], ua[4][4];
#pragma unroll
    for (int i = 0; i < 4; i++)
#pragma unroll
        for (int e = 0; e < 4; e++) { ga[i][e] = 0.f; ua[i][e] = 0.f; }
#pragma unroll 1
    for (int s = 0; s < 34; s++) {
        if (s == 20) {
            if (warp < 7) {
#pragma unroll
                for (int i = 0; i < 4; i++)
#pragma unroll
                    for (int e = 0; e < 4; e++) {
                        float gv = bf_round(ga[i][e]), uv = bf_round(ua[i][e]);
                        float sg = bf_round(__fdividef(gv, 1.0f + __expf(fminf(-gv, 80.f))));
                        int f = warp * 64 + i * 16 + g + 8 * (e >> 1), tk = 2 * t + (e & 1);
                        *reinterpret_cast<__nv_bfloat16*>(sm + HS + tk * 912 + f * 2) = __float2bfloat16_rn(sg * uv);
                        ga[i][e] = 0.f;
                    }
            }
            bar_sync(1, 320);
            PROF_GT(52);
        }
        mbar_wait(full + 8 * st, ph);
        if (s >= 20 || warp < 7) {
#pragma unroll
            for (int kk = 0; kk < 2; kk++) {
                uint32_t xb = sb + (s < 20 ? XS + g * 1296 + s * 64 : HS + g * 912 + (s - 20) * 64) + 32 * kk + 4 * t;
                uint32_t b0 = lds32(xb), b1 = lds32(xb + 16);
                uint32_t wa = sb + st * STG + woff + kk * 2048;
#pragma unroll
                for (int i = 0; i < 4; i++) {
                    uint32_t a0, a1, a2, a3;
                    ldsm4t(a0, a1, a2, a3, wa ^ (i << 5));
                    mma16816(ga[i], a0, a1, a2, a3, b0, b1);
                    if (s < 20) {
                        ldsm4t(a0, a1, a2, a3, (wa ^ (i << 5)) + 28672);
                        mma16816(ua[i], a0, a1, a2, a3, b0, b1);
                    }
                }
            }
        }
        asm volatile("fence.proxy.async.shared::cta;" ::: "memory");
        __syncwarp();
        if (lane == 0) mbar_arrive(empty + 8 * st);
        if (++st == 3) { st = 0; ph ^= 1; }
    }
#pragma unroll
    for (int i = 0; i < 4; i++)
#pragma unroll
        for (int e = 0; e < 4; e += 2)
            *reinterpret_cast<float2*>(g_moe_part + (a * DM + warp * 64 + i * 16 + g + 4 * e) * 8 + 2 * t) = make_float2(ga[i][e], ga[i][e + 1]);
    bar_sync(1, 320);
    if (tid == 0) {
        __threadfence();
        unsigned old = atomicAdd(flag_ptr(FL_MOE_CNT), 1u);
        s_misc[1] = (old == ep * 4u + 3u);
        __threadfence();
    }
    bar_sync(1, 320);
    PROF_GT(53);
    if (s_misc[1]) {
        const float4* pp = reinterpret_cast<const float4*>(g_moe_part);
#pragma unroll 2
        for (int i = tid; i < DM * 2; i += 320) {
            float4 v0 = __ldcg(pp + i), v1 = __ldcg(pp + DM * 2 + i), v2 = __ldcg(pp + DM * 4 + i), v3 = __ldcg(pp + DM * 6 + i);
            float y[4] = {v0.x + v1.x + v2.x + v3.x, v0.y + v1.y + v2.y + v3.y, v0.z + v1.z + v2.z + v3.z, v0.w + v1.w + v2.w + v3.w};
#pragma unroll
            for (int e = 0; e < 4; e++) {
                int col = i >> 1, tk = (i & 1) * 4 + e;
                float sg = bf_round(__fdividef(1.0f, 1.0f + __expf(fminf(-s_r[tk], 80.f))));
                float upd = bf_round(bf_round(y[e]) * sg);
                float xn = __bfloat162float(*reinterpret_cast<const __nv_bfloat16*>(sm + XS + tk * 1296 + col * 2));
                g_brow[tk * DM + col] = __float2bfloat16_rn(xn + upd);
            }
        }
        if (tid < TOPC) g_sel[tid] = s_sel[tid];
        bar_sync(1, 320);
        if (tid == 0) {
            flag_signal(flag_ptr(FL_MOE_DONE));
            *reinterpret_cast<volatile unsigned*>(&g_epoch) = ep + 1;
        }
        PROF_GT(54);
    }
}

__global__ void __cluster_dims__(2, 1, 1) __launch_bounds__(384, 1)
fused_kernel(const __grid_constant__ CUtensorMap tmC, const __grid_constant__ CUtensorMap tmWk, const __grid_constant__ CUtensorMap tmWv,
             const __grid_constant__ CUtensorMap tmWq, const __grid_constant__ CUtensorMap tmWo,
             const __grid_constant__ CUtensorMap tmG, const __grid_constant__ CUtensorMap tmU, const __grid_constant__ CUtensorMap tmD, const Params P) {
    extern __shared__ __align__(1024) unsigned char smem_raw[];
    const uint32_t ring = smem_u32(smem_raw);
    const uint32_t misc = ring + RING_BYTES;
    const int tid = threadIdx.x;
    const int rank = blockIdx.x & 1;
    uint32_t smid, nsm;
    asm("mov.u32 %0, %%smid;" : "=r"(smid));
    asm("mov.u32 %0, %%nsmid;" : "=r"(nsm));
    if (nsm != 132) smid = blockIdx.x;
    auto role_of = [](int tpc) {
        return tpc < 32 ? (tpc & 7) * 8 + (tpc >> 3) : tpc < 60 ? (1 + (tpc - 32) % 7) * 8 + 4 + (tpc - 32) / 7 : tpc < 64 ? tpc - 56 : tpc;
    };
    int mc = role_of(smid >> 1);
    PROF_DECL(mc * 2 + rank)
    PROF_GT(0); PROF_EV(1);

    auto prefetch_w = [&](int ch) {
        const int i = tid - 128;
        asm volatile("prefetch.global.L2 [%0];" ::"l"((rank ? P.wv : P.wk) + (size_t)(ch * 128 + (mc & 3) * 32 + (i >> 3)) * 4096 + (mc >> 2) * 256 + (i & 7) * 16));
    };
    if (tid >= 128 && mc < 64) {
        if (tid < 256) asm volatile("prefetch.global.L2 [%0];" ::"l"(P.c + (size_t)((12 + (mc & 3)) * 128 + ((mc >> 2) * 2 + rank) * 4) * DC + (tid - 128) * 16));
        prefetch_w(0);
    }
    auto load_w0 = [&]() {
        const CUtensorMap* tw = rank ? &tmWv : &tmWk;
        mbar_expect_tx(misc + BAR_FULL + 8 * slot_of(0), SLOT_BYTES);
        tma2d(ring + slot_of(0) * SLOT_BYTES, tw, (mc >> 2) * 256, 0, misc + BAR_FULL + 8 * slot_of(0), policy(HM & 1));
        tma2d(ring + slot_of(0) * SLOT_BYTES + 16384, tw, (mc >> 2) * 256 + 64, 0, misc + BAR_FULL + 8 * slot_of(0), policy(HM & 1));
    };
    if (tid == 0) {
#pragma unroll
        for (int i = 0; i < NSLOT; i++) mbar_init(misc + BAR_FULL + 8 * i, 1);
#pragma unroll
        for (int i = 0; i < E0; i++) mbar_arrive(misc + BAR_FULL + 8 * i);
        asm volatile("fence.mbarrier_init.release.cluster;" ::: "memory");
        if (mc < 64) load_w0();
    }
    if (tid == 160) {
        asm volatile("st.shared.u32 [%0], %1;" ::"r"(misc + MISC_SMID), "r"(smid) : "memory");
        asm volatile("fence.release.sync_restrict::shared::cta.cluster;" ::: "memory");
    }
    if (tid == 32) {
        asm volatile("prefetch.tensormap [%0];" ::"l"(&tmC) : "memory");
#pragma unroll
        for (int i = 0; i < NSLOT; i++) mbar_init(misc + BAR_EMPTY + 8 * i, 16);
#pragma unroll
        for (int i = 0; i < E0; i++) mbar_arrive_cluster(misc + BAR_EMPTY + 8 * i, 16);
        asm volatile("fence.mbarrier_init.release.cluster;" ::: "memory");
    }
    if (tid == 64) {
#pragma unroll
        for (int i = 0; i < NST3; i++) { mbar_init(misc + BAR_FULL3 + 8 * i, 1); mbar_init(misc + BAR_EMPTY3 + 8 * i, 16); }
#pragma unroll
        for (int i = 0; i < 4; i++) mbar_init(misc + BAR_LN + 8 * i, 2);
        mbar_init(misc + BAR_PROG, 1); mbar_init(misc + BAR_PROG + 8, 1); mbar_init(misc + BAR_PROG + 16, 1);
        asm volatile("fence.mbarrier_init.release.cluster;" ::: "memory");
    }
    if (tid == 96) {
#pragma unroll
        for (int i = 0; i < 34; i++) mbar_init(misc + BAR_DEP + 8 * i, 1);
    }
    if (tid == 128) {
#pragma unroll
        for (int i = 0; i < 32; i++) mbar_init(misc + BAR_EV + 8 * i, 4);
    }
    __syncthreads();
    asm volatile("barrier.cluster.arrive.relaxed.aligned;\nbarrier.cluster.wait.aligned;" ::: "memory");
    {
        uint32_t peer;
        asm volatile("ld.shared::cluster.u32 %0, [%1];" : "=r"(peer) : "r"(mapa(misc + MISC_SMID, rank ^ 1)) : "memory");
        if ((__shfl_sync(0xffffffffu, peer, 0) ^ smid) != 1) {
            if (tid == 0) {
                const unsigned ep1 = *reinterpret_cast<volatile unsigned*>(&g_epoch) + 1;
                if ((smid & 1) == 0) atomicExch(g_roleq + 2 + (atomicAdd(g_roleq, 1u) & 127), (ep1 << 8) | (smid >> 1));
                if (rank == 0) {
                    unsigned* slot = g_roleq + 2 + (atomicAdd(g_roleq + 1, 1u) & 127);
                    unsigned v = 0;
                    for (int spin = 0; spin < 4000000 && ((v = atomicAdd(slot, 0u)) >> 8) != (ep1 & 0xffffffu); spin++) {}
                    asm volatile("st.shared::cluster.u32 [%0], %1;" ::"r"(mapa(misc + MISC_SMID + 4, 0)), "r"(v & 255) : "memory");
                    asm volatile("st.shared::cluster.u32 [%0], %1;" ::"r"(mapa(misc + MISC_SMID + 4, 1)), "r"(v & 255) : "memory");
                }
                if (mc < 64) {
                    mbar_wait(misc + BAR_FULL + 8 * slot_of(0), 0);
                    asm volatile("mbarrier.inval.shared::cta.b64 [%0];" ::"r"(misc + BAR_FULL + 8 * slot_of(0)) : "memory");
                    mbar_init(misc + BAR_FULL + 8 * slot_of(0), 1);
                    asm volatile("fence.mbarrier_init.release.cluster;" ::: "memory");
                }
            }
            __syncwarp();
            asm volatile("barrier.cluster.arrive.aligned;\nbarrier.cluster.wait.aligned;" ::: "memory");
            mc = role_of(__shfl_sync(0xffffffffu, lds32(misc + MISC_SMID + 4), 0));
            if (tid == 0 && mc < 64) load_w0();
            __syncwarp();
        }
    }
    const int cta = mc * 2 + rank;
    if (mc >= 64) { aux_cta(P, &tmG, &tmU, &tmD, smem_raw, cta - 128); return; }
    const int team = mc >> 2, k = mc & 3;
    const int u3 = (mc >> 4) * 2 + (team & 1), s3 = k, kap = (mc >> 3) & 1;
    const int partner = cta ^ 16;
    if (tid >= 128) prefetch_w(1);
    if (tid == 256) {
        const CUtensorMap* tw = rank ? &tmWv : &tmWk;
#pragma unroll
        for (int e = 1; e < NSLOT; e++) {
            const uint32_t fb = misc + BAR_FULL + 8 * slot_of(e), dst = ring + slot_of(e) * SLOT_BYTES;
            mbar_expect_tx(fb, SLOT_BYTES);
            if (e & 1) tma2d_mc(dst + rank * 16384, &tmC, (e >> 1) * 128 + rank * 64, (12 + k) * 128, fb, policy(false));
            else { tma2d(dst, tw, team * 256, e * 64, fb, policy(false)); tma2d(dst + 16384, tw, team * 256 + 64, e * 64, fb, policy(false)); }
        }
    }
    PROF_EV(5);
    const int wg = __shfl_sync(0xffffffffu, tid >> 7, 0);

    if (wg == 0) {
        asm volatile("setmaxnreg.dec.sync.aligned.u32 40;");
        const int warp = __shfl_sync(0xffffffffu, tid >> 5, 0), lane = tid & 31;
        if (warp == 0) {
            const bool lead = elect_one();
            Cur c = cur_at(NSLOT);
            uint32_t dst, fb;
            auto acquire = [&]() {
                mbar_wait(misc + BAR_EMPTY + 8 * c.slot, c.ph ^ 1);
                fb = misc + BAR_FULL + 8 * c.slot; dst = ring + c.slot * SLOT_BYTES;
                if (lead) mbar_expect_tx(fb, SLOT_BYTES);
                c.adv();
            };
            auto load_w = [&](const CUtensorMap* tm, int col, int row, bool stream) {
                acquire();
                if (lead) { tma2d(dst, tm, col, row, fb, policy(stream)); tma2d(dst + 16384, tm, col + 64, row, fb, policy(stream)); }
            };
            auto load_half = [&](const unsigned char* src, bool stream) {
                acquire();
                if (lead) bulk_load_mc(dst + rank * 16384, src, 16384, fb, policy(stream));
            };
            auto dep_wait = [&](int d) { mbar_wait(misc + BAR_DEP + 8 * d, 0); fence_async_global(); };
            auto op_prefetch = [&](int i) {
                const int head = op_head(i, kap);
                l2_prefetch(reinterpret_cast<const unsigned char*>(P.wo) + head * 163840 + (u3 * 8 + s3 * 2 + rank) * 2560, 2560);
                if (i < 8) l2_prefetch(g_ctx + (size_t)(head * 32 + 4 * u3 + 2 * rank) * 16384 + s3 * 8192, 8192);
            };
            __nanosleep(CDELAY);
            if (lead) l2_prefetch(reinterpret_cast<const unsigned char*>(P.c) + (size_t)cta * 12288, 12288);
            const CUtensorMap* tw = rank ? &tmWv : &tmWk;
            const unsigned char* Kh = g_K + (size_t)team * 32 * 16384 + rank * 16384;
            const unsigned char* Vh = g_V + (size_t)team * 32 * 16384 + rank * 16384;
#pragma unroll 1
            for (int v = 0; v < 2; v++) {
                const int h = 2 * team + v;
#pragma unroll 1
                for (int i = v ? 0 : 3; i < 16; i++) {
                    if (i < 4 && v) load_w(tw, h * 128, i * 128, HM & 1);
                    if (v && (i & 7) == 3) dep_wait(D_WAR + (i >> 3));
                    acquire();
                    if (lead) tma2d_mc(dst + rank * 16384, &tmC, (i & 3) * 128 + rank * 64, (12 - (i & 12) + k) * 128, fb, policy(HM & 2));
                    if (v && i == 3 && lead) mbar_arrive(misc + BAR_PROG + 8);
                    if (i == 8 && lead) {
                        tma2d_prefetch(&tmWq, h * 128 + rank * 64, k * 64); tma2d_prefetch(&tmWq, h * 128 + rank * 64, k * 64 + 256);
                        if (k < 2) tma2d_prefetch(&tmWq, h * 128 + rank * 64, k * 64 + 512);
                        if (v) l2_prefetch(g_xn + 8 * 163840 + cta * 10240, 10240);
                    }
                }
                int togo = v ? PF_START : 11;
#pragma unroll 1
                for (int r = 0; r < 2; r++) {
                    const int p = r ? k : 7 - k, n = 2 * p + 1;
                    if (v == 0) dep_wait(D_LN + r);
                    const int g0 = r ? rank ^ SWAPT : 3 - rank, g1 = 3 - g0;
                    const unsigned char* x0 = g_xn + (2 * p + (g0 >> 1)) * 163840 + (g0 & 1) * 8192;
                    const unsigned char* x1 = g_xn + (2 * p + (g1 >> 1)) * 163840 + (g1 & 1) * 8192;
#pragma unroll 1
                    for (int kc = 0; kc < 10; kc++) {
                        acquire();
                        if (lead) {
                            tma2d_mc(dst + 16384 + rank * 8192, &tmWq, h * 128 + rank * 64, kc * 64, fb, policy(false));
                            bulk_load(dst, x0 + kc * 16384, 8192, fb, policy(false));
                            bulk_load(dst + 8192, x1 + kc * 16384, 8192, fb, policy(false));
                        }
                    }
                    if (r == 0) dep_wait(D_KV + 3 * v);
                    load_half(Kh + n * 32768, HM & 16);
#pragma unroll 1
                    for (int j = n - 1; j >= 0; j--) {
                        if (r == 0 && (j == 7 || j == 3)) dep_wait(D_KV + 3 * v + 2 - (j >> 2));
                        load_half(Kh + j * 32768, HM & 16); load_half(Vh + (j + 1) * 32768, HM & 16);
                        if (v == 0 && r == 0 && j == 3 && lead) mbar_arrive(misc + BAR_PROG);
                        --togo;
                        if (v == 0 && togo == 0 && lead) {
                            tma2d_prefetch(tw, h * 128 + 128, k * 128); tma2d_prefetch(tw, h * 128 + 192, k * 128);
                            l2_prefetch(reinterpret_cast<const unsigned char*>(P.c) + (size_t)cta * 16384, 16384);
                        }
                        if (v && togo <= 0 && togo > -OP_PF && lead) op_prefetch(-togo);
                    }
                    load_half(Vh, HM & 16);
                }
            }
            mbar_wait(misc + BAR_EMPTY + 8 * c.slot, c.ph ^ 1); c.adv();
            int st = 0; uint32_t ph3 = 0;
#pragma unroll 1
            for (int i = 0; i < 32; i++) {
                const int head = op_head(i >> 1, kap);
                if ((i & 1) == 0) dep_wait(D_CTX + (i >> 1));
                if (i < NST3) { mbar_wait(misc + BAR_EMPTY + 8 * c.slot, c.ph ^ 1); c.adv(); }
                else mbar_wait(misc + BAR_EMPTY3 + 8 * st, ph3 ^ 1);
                fb = misc + BAR_FULL3 + 8 * st; dst = ring + st * ST3_BYTES;
                if (i == LATE_AT && lead) mbar_arrive(misc + BAR_PROG + 16);
                if (lead) {
                    mbar_expect_tx(fb, ST3_BYTES);
                    const unsigned char* src = g_ctx + (size_t)(head * 32 + 4 * u3 + 2 * rank) * 16384 + (i & 1) * 8192;
                    bulk_load(dst, src, 8192, fb, policy(HM & 32));
                    bulk_load(dst + 8192, src + 16384, 8192, fb, policy(HM & 32));
                    tma3d_mc(dst + 16384 + rank * 10240, &tmWo, 0, head * 128 + (i & 1) * 64 + rank * 32, 5 * s3, fb, policy(HM & 32));
                    if ((i & 1) && (i >> 1) + OP_PF < 16) op_prefetch((i >> 1) + OP_PF);
                }
                if (++st == NST3) { st = 0; ph3 ^= 1; }
            }
        } else {
        if (lane < 27 && (warp - 1) * 27 + lane < 80) {
            const int ch = (warp - 1) * 27 + lane;
            uint4 u = __ldg(reinterpret_cast<const uint4*>(P.wr) + ch);
            asm volatile("st.shared.v4.b32 [%0], {%1,%2,%3,%4};" ::"r"(misc + MISC_WR + 16 * ch), "r"(u.x), "r"(u.y), "r"(u.z), "r"(u.w) : "memory");
        }
        bar_sync(3, 96);
#pragma unroll 1
        for (int t = 0; t < (warp == 3 ? 1 : 3); t++) {
            const int row2 = (cta >> 5) * 256 + (cta & 31) * 8 + (warp - 1) * 4;
            if (t < 2 && warp < 3) {
#pragma unroll
                for (int i = 0; i < 3; i++)
                    if (i * 32 + lane < 80) asm volatile("prefetch.global.L2 [%0];" ::"l"(P.x + (size_t)(row2 + 2 * t) * DM + (i * 32 + lane) * 16));
            }
            ln_rows(P, t ? row2 + 2 * t - 2 : (4 + (cta >> 5)) * 256 + (cta & 31) * 6 + (warp - 1) * 2, lane, misc + MISC_WR);
            __syncwarp();
            if (lane == 0 && warp < 3 && t != 1) mbar_arrive(misc + BAR_LN + 4 * t);
        }
        if (warp == 3) {
            const unsigned ep1 = *reinterpret_cast<volatile unsigned*>(&g_epoch) + 1;
            if (lane == 0) {
                asm volatile("st.shared.u32 [%0], %1;" ::"r"(misc + MISC_EPOCH), "r"(ep1) : "memory");
                mbar_wait(misc + BAR_LN, 0);
                flag_signal(flag_ptr(FL_LN + 4 + (cta >> 5)));
                flag_wait(flag_ptr(FL_LN + 7 - k), ep1 * 33u);
                mbar_arrive(misc + BAR_DEP + 8 * D_LN);
#pragma unroll 1
                for (int v = 0; v < 2; v++) {
#pragma unroll 1
                    for (int i = 3 * v; i < 3 * v + 3; i++) {
                        mbar_wait(misc + BAR_EV + 8 * (16 + EV_KV + i), 0);
                        if (v == 0) {
                            mbar_wait(misc + BAR_EV + 8 * (EV_KV + i), 0);
                            asm volatile("red.release.gpu.global.add.u32 [%0], 2;" ::"l"(flag_ptr(FL_KV + team * 8 + i)) : "memory");
                        }
                        flag_wait(flag_ptr(FL_KV + team * 8 + i), ep1 * 16u);
                        mbar_arrive(misc + BAR_DEP + 8 * (D_KV + i));
                    }
                    if (v) break;
                    mbar_wait(misc + BAR_LN + 8, 0);
                    flag_signal(flag_ptr(FL_LN + (cta >> 5)));
                    flag_wait(flag_ptr(FL_LN + k), ep1 * 32u);
                    mbar_arrive(misc + BAR_DEP + 8 * (D_LN + 1));
#pragma unroll 1
                    for (int i = 0; i < 2; i++) {
                        mbar_wait(misc + BAR_PROG + 8 * i, 0);
                        flag_signal(flag_ptr(FL_WAR + 2 * team + i));
                        flag_wait(flag_ptr(FL_WAR + 2 * team + i), ep1 * 8u);
                        mbar_arrive(misc + BAR_DEP + 8 * (D_WAR + i));
                    }
                }
                flag_wait(flag_ptr(FL_MOE_DONE), ep1);
                int4 s0 = __ldcg(reinterpret_cast<const int4*>(g_sel)), s1 = __ldcg(reinterpret_cast<const int4*>(g_sel) + 1);
                asm volatile("st.shared.v4.u32 [%0], {%1,%2,%3,%4};" ::"r"(misc + MISC_SEL), "r"(s0.x), "r"(s0.y), "r"(s0.z), "r"(s0.w) : "memory");
                asm volatile("st.shared.v4.u32 [%0], {%1,%2,%3,%4};" ::"r"(misc + MISC_SEL + 16), "r"(s1.x), "r"(s1.y), "r"(s1.z), "r"(s1.w) : "memory");
                mbar_arrive(misc + BAR_SEL);
            }
            __syncwarp();
            const unsigned* cf = flag_ptr(FL_CTX + op_head(lane & 15, kap) * 8 + u3);
#pragma unroll 1
            for (int half = 0; half < 2; half++) {
                if (half) mbar_wait(misc + BAR_EV + 8 * (EV_CTX + 3), 0);
                bool done = (lane >> 3) != half;
                for (int spin = 0; spin < 4000000; spin++) {
                    if (!done) {
                        unsigned v;
                        asm volatile("ld.acquire.gpu.global.u32 %0, [%1];" : "=r"(v) : "l"(cf) : "memory");
                        if ((int)(v - ep1 * 4u) >= 0) { mbar_arrive(misc + BAR_DEP + 8 * (D_CTX + lane)); done = true; }
                    }
                    if (__all_sync(0xffffffffu, done)) break;
                    __nanosleep(64);
                }
            }
        } else {
            const int w = warp - 1;
            if (lane == 0) {
                const uint32_t eb = misc + BAR_EV + w * 128;
#pragma unroll 1
                for (int i = 0; i < 7; i++) {
                    const bool kv = i >= 2 && i < 5;
                    const int ci = i < 2 ? i : i - 3;
                    mbar_wait(eb + 8 * (kv ? EV_KV + i + 1 : EV_CTX + ci), 0);
                    flag_signal(flag_ptr(kv ? FL_KV + team * 8 + i + 1 : FL_CTX + (2 * team + (ci >> 1)) * 8 + ((ci & 1) ? k : 7 - k)));
                }
            }
            __syncwarp();
            mbar_wait(misc + BAR_PROG + 16, 0);
            const int row = (2 * u3 + rank) * 128 + 64 * w + perm32(16 * (lane >> 3) + 8 * kap + (lane & 7));
#pragma unroll
            for (int i = 0; i < 10; i++) asm volatile("prefetch.global.L2 [%0];" ::"l"(P.x + (size_t)row * DM + 160 * s3 + 16 * i));
            asm volatile("prefetch.global.L2 [%0];" ::"l"(g_stats + row));
        }
        }
    } else {
        asm volatile("setmaxnreg.inc.sync.aligned.u32 232;");
        Ctx c;
        c.ring = ring; c.misc = misc; c.w = wg - 1; c.warp = __shfl_sync(0xffffffffu, (tid >> 5) & 3, 0); c.lane = tid & 31;
        c.rel = mapa(misc, tid & 1);
        const int w = c.w;
        if (w == 1) bar_arrive(1, 256);
        prefetch_w(2); prefetch_w(3);
        Cur cur = cur_at(0);
        float o[64], inv[2];
        unsigned char* out[2];
#pragma unroll 1
        for (int v = 0; v < 2; v++) {
        {
            uint32_t wf[128];
            float (&acc)[64] = o;
#pragma unroll
            for (int i = 32; i < 128; i++) wf[i] = 0u;
            Cur cw = cur;
            auto load_wchunk = [&](auto CH) {
                constexpr int ch = decltype(CH)::value;
                mbar_wait_hot(misc + BAR_FULL + 8 * cw.slot, cw.ph);
                const uint32_t z = load_afrag<8, 32 * ch>(wf, ring + cw.slot * SLOT_BYTES + w * 16384, c);
                release(c, BAR_EMPTY + 8 * cw.slot + z, 1);
                cw.adv(); cw.adv();
            };
            load_wchunk(IC<0>{});
            cur.adv();
            inv[0] = inv[1] = rank ? 1.0f : SM_SCALE;
            PROF_EV(2); PROF_GT(60);
#pragma unroll 1
            for (int t = 0; t < 4; t++) {
                uint32_t last = 0;
                token_wait(w);
                PROF_EV(10);
                undef_regs(acc);
                auto chunk = [&](auto CH) {
                    constexpr int ch = decltype(CH)::value;
                    mbar_wait_hot(misc + BAR_FULL + 8 * cur.slot, cur.ph);
                    if (t == 0) { PROF_EV(12 + ch); }
                    uint64_t d = mkdesc(ring + cur.slot * SLOT_BYTES, 16, 1024, 1);
                    wg_fence();
#pragma unroll
                    for (int ks = 0; ks < 8; ks++)
                        wgmma_rs_n128_ta0_tb0(acc, wf[32 * ch + 4 * ks], wf[32 * ch + 4 * ks + 1], wf[32 * ch + 4 * ks + 2], wf[32 * ch + 4 * ks + 3],
                                              d + (ks >> 2) * 1024 + (ks & 3) * 2, (ch | ks) != 0);
                    wg_commit();
                    if (ch == 3 || (ch < 2 && t == 0)) token_pass(w);
                    if constexpr (ch < 2) { if (t == 0) load_wchunk(IC<ch + 1>{}); }
                    if constexpr (ch == 2) { if (t == 0 && !w) load_wchunk(IC<3>{}); }
                    if (ch > 0) { wg_wait<1>(); release(c, BAR_EMPTY + 8 * last, 1); }
                    last = cur.slot;
                    cur.adv();
                    if (ch < 3 && t == 0) cur.adv();
                    if constexpr (ch == 1) { if (t == 0 && w) load_wchunk(IC<3>{}); }
                    if (ch < 2 && t == 0) token_wait(w);
                };
                chunk(IC<0>{}); chunk(IC<1>{}); chunk(IC<2>{}); chunk(IC<3>{});
                wg_wait<0>();
                release(c, BAR_EMPTY + 8 * last, 1);
                PROF_EV(11);
                fence_regs(acc);
                tile_out(out, (rank ? g_V : g_K) + (size_t)(team * 32 + 24 + 2 * k - 8 * t) * 16384, 64 * w, rank, c);
                if (DEFER && t == 3 && w) break;
#pragma unroll
                for (int i = 0; i < 4; i++) store_pair(acc, i, out, 16384, inv);
                if (t) signal_event(c, EV_KV + 3 * v + t - 1);
            }
            PROF_EV(61); PROF_GT(62);
        }
        PROF_EV(63); PROF_GT(64);
        {
            uint32_t q[32], p[32];
            float m[2], l[2];
#pragma unroll
            for (int i = 0; i < 32; i++) p[i] = 0u;
            l[0] = l[1] = 1.f;
            int pv_acc = 0, pv_mode = 2;
#pragma unroll 1
            for (int r = 0; r < 2; r++) {
                const int heavy = 1 ^ r ^ w;
                const int half = 1 ^ heavy ^ rank ^ (r & SWAPT);
                int left = 2 * (r ? k : 7 - k) + 1 + heavy;
                Cur ck, cv = cur;
                {
                    float s[64];
                    if (r) cur.adv();
                    mbar_wait_hot(misc + BAR_FULL + 8 * cv.slot, cv.ph);
                    token_wait(w);
                    PROF_EV(20);
                    issue_pv(o, p, ring + cv.slot * SLOT_BYTES, 1, r ? 0 : 2);
                    undef_regs(s);
                    uint32_t prev;
                    auto qchunk = [&](int acc) {
                        mbar_wait_hot(misc + BAR_FULL + 8 * cur.slot, cur.ph);
                        const uint64_t da = mkdesc(ring + cur.slot * SLOT_BYTES + w * 8192, 16, 1024, 1);
                        const uint64_t db = mkdesc(ring + cur.slot * SLOT_BYTES + 16384, 8192, 1024, 1);
                        wg_fence();
#pragma unroll
                        for (int ks = 0; ks < 4; ks++) wgmma_ss_n128_ta0_tb1(s, da + 2 * ks, db + 128 * ks, ks ? 1 : acc);
                        wg_commit();
                    };
                    qchunk(0);
                    prev = cur.slot; cur.adv();
                    token_pass(w);
                    if (r) {
                        row_inv(l, inv);
                        tile_out(out, g_ctx + (size_t)((2 * team + v) * 32 + 4 * (7 - k) + (w ? rank : 3 - rank)) * 16384, 0, 0, c);
                    }
                    const int epi = r | (w & DEFER), hs = r ? 8192 : 16384;
                    const int hold = heavy ? -10 : half ? HOLD0 : 8;
#pragma unroll
                    for (int kc = 1; kc < 10; kc++) {
                        if (HOLD0 && kc >= HOLD0 && (kc == hold || kc == hold + 2)) token_wait(w);
                        qchunk(1);
                        if (HOLD0 && kc > HOLD0 && kc == hold + 1) token_pass(w);
                        if (HOLD0 && kc == 9 && heavy) { token_wait(w); token_pass(w); }
                        wg_wait<1>();
                        release(c, BAR_EMPTY + 8 * prev, 1);
                        prev = cur.slot; cur.adv();
                        if (kc == 1) { fence_regs(o); if (r) release(c, BAR_EMPTY + 8 * cv.slot, 1); }
                        if (kc <= 4 && epi) {
                            store_pair(o, kc - 1, out, hs, inv);
                            if (kc == 4) signal_event(c, r ? EV_CTX + 2 * v : EV_KV + 3 * v + 2);
                        }
                    }
                    if (!heavy) cur.adv();
                    ck = cur;
                    cur.adv();
                    if (!heavy) cur.adv();
                    wg_wait<0>();
                    release(c, BAR_EMPTY + 8 * prev, 1);
                    PROF_EV(21);
                    fence_regs(s);
#pragma unroll
                    for (int i = 0; i < 32; i++) q[i] = pack_bf16(s[2 * i], s[2 * i + 1]);
                }
                cv = ck;
                int first = 1, gen = 0;
                uint32_t pv_cnt = 0;
                pv_acc = 0; pv_mode = 2;
                l[0] = l[1] = m[0] = m[1] = 0.f;
                mbar_wait_hot(misc + BAR_FULL + 8 * ck.slot, ck.ph);
#pragma unroll 1
                while (true) {
                    float s[64];
                    if (half & first) {
                        if (heavy || HOLD0 == 0 || HOLD0 == 8) token_wait(w);
                        PROF_EV(30);
                        float sh[32];
                        undef_regs(sh);
                        issue_qk_half(sh, q, ring + ck.slot * SLOT_BYTES);
                        token_pass(w);
                        --left;
                        wg_wait<0>();
                        PROF_EV(34);
                        fence_regs(sh);
                        mask_diag<0>(sh, c);
                        float l0 = 0.f, l1 = 0.f;
#pragma unroll
                        for (int j = 0; j < 8; j++) {
#pragma unroll
                            for (int e = 0; e < 4; e++) ex2v(sh[4 * j + e]);
                            l0 += sh[4 * j] + sh[4 * j + 1]; l1 += sh[4 * j + 2] + sh[4 * j + 3];
                        }
#pragma unroll
                        for (int i = 0; i < 16; i++) p[i] = pack_bf16(sh[2 * i], sh[2 * i + 1]);
                        const int lim = mask_lim(c);
                        if (__any_sync(0xffffffffu, !(l0 <= SAFE_SUM && l1 <= SAFE_SUM && (l0 >= 1.0f / SAFE_SUM || lim < 0) &&
                                                      (l1 >= 1.0f / SAFE_SUM || lim < -2)))) goto redo;
                        l[0] = l0; l[1] = l1;
                        goto tail;
                    }
#pragma unroll 1
                    while (true) {
                        token_wait(w);
                        PROF_EV(first ? 30 : 31);
                        undef_regs(s);
                        issue_qk(s, q, ring + ck.slot * SLOT_BYTES);
                        Cur nck = cur, ncv = cur, ncur;
                        ncv.adv(); ncur = ncv; ncur.adv();
                        --left;
                        mbar_wait_hot(misc + BAR_FULL + 8 * cv.slot, cv.ph);
                        issue_pv(o, p, ring + cv.slot * SLOT_BYTES, pv_acc, pv_mode);
                        token_pass(w);
                        wg_wait<1>();
                        PROF_EV(33);
                        fence_regs(s);
                        float lo = 0.f;
                        if (first) {
                            lo = 1.0f / SAFE_SUM;
                            mask_diag<8>(s, c);
                        }
                        constexpr int JB = 11;
                        float l0 = l[0], l1 = l[1];
                        if (!gen) {
#pragma unroll
                            for (int j = 0; j < JB; j++) {
#pragma unroll
                                for (int e = 0; e < 4; e++) ex2v(s[4 * j + e]);
                                if (j < JB - 1) { l0 += s[4 * j] + s[4 * j + 1]; l1 += s[4 * j + 2] + s[4 * j + 3]; }
                            }
                        }
                        wg_wait<0>();
                        fence_regs(o);
                        if (gen) goto general;
#pragma unroll
                        for (int j = JB - 1; j < 16; j++) {
                            if (j >= JB) {
#pragma unroll
                                for (int e = 0; e < 4; e++) ex2v(s[4 * j + e]);
                            }
                            l0 += s[4 * j] + s[4 * j + 1]; l1 += s[4 * j + 2] + s[4 * j + 3];
                        }
#pragma unroll
                        for (int i = 0; i < 32; i++) p[i] = pack_bf16(s[2 * i], s[2 * i + 1]);
                        if (__any_sync(0xffffffffu, !(l0 <= SAFE_SUM && l1 <= SAFE_SUM && l0 >= lo && l1 >= lo))) goto redo;
                        l[0] = l0; l[1] = l1;
                        if (left == 0) goto tail;
                        release(c, BAR_EMPTY + 8 * ck.slot, 1 + (first & heavy));
                        if (pv_cnt) release(c, BAR_EMPTY + 8 * cv.slot, pv_cnt);
                        pv_acc = first ^ 1; pv_mode = 0; pv_cnt = 1 + (first & heavy); first = 0;
                        ck = nck; cv = ncv; cur = ncur;
                        mbar_wait_hot(misc + BAR_FULL + 8 * ck.slot, ck.ph);
                    }
                redo:
                    recompute_scores(s, q, ring + ck.slot * SLOT_BYTES, c);
                    if (first) { mask_any(s, half ^ 1, c); m[0] = m[1] = -INFINITY; }
                    gen = 1;
                general:
                    {
                        float mx[2], alpha[2];
                        row_max<16>(s, mx);
#pragma unroll
                        for (int i = 0; i < 2; i++) {
                            mx[i] = fmaxf(mx[i], m[i]);
                            alpha[i] = ex2(m[i] - mx[i]);
                            m[i] = mx[i];
                            l[i] *= alpha[i];
                        }
                        exp_sum<16, true>(s, m, l[0], l[1]);
#pragma unroll
                        for (int i = 0; i < 64; i++) o[i] *= alpha[(i >> 1) & 1];
#pragma unroll
                        for (int i = 0; i < 32; i++) p[i] = pack_bf16(s[2 * i], s[2 * i + 1]);
                    }
                tail:
                    release(c, BAR_EMPTY + 8 * ck.slot, 1 + (first & heavy));
                    if (pv_cnt) release(c, BAR_EMPTY + 8 * cv.slot, pv_cnt);
                    pv_acc = first ^ 1; pv_mode = first & half; pv_cnt = 1 + (first & heavy); first = 0;
                    if (left == 0) break;
                    ck = cur; cur.adv(); cv = cur; cur.adv();
                    mbar_wait_hot(misc + BAR_FULL + 8 * ck.slot, ck.ph);
                }
            }
            mbar_wait_hot(misc + BAR_FULL + 8 * cur.slot, cur.ph);
            token_wait(w);
            PROF_EV(32);
            issue_pv(o, p, ring + cur.slot * SLOT_BYTES, pv_acc, pv_mode);
            if (w == 0 || v == 0) token_pass(w);
            row_inv(l, inv);
            wg_wait<0>();
            release(c, BAR_EMPTY + 8 * cur.slot, 1);
            fence_regs(o);
            cur.adv();
            tile_out(out, g_ctx + (size_t)((2 * team + v) * 32 + 4 * k + (w ? 3 - (rank ^ SWAPT) : rank ^ SWAPT)) * 16384, 0, 0, c);
            if (v == 0) {
#pragma unroll
                for (int i = 0; i < 4; i++) store_pair(o, i, out, 8192, inv);
                signal_event(c, EV_CTX + 1);
            }
        }
        }
        {
            float acc[80];
            undef_regs(acc);
            int st = 0, prev = 0; uint32_t ph3 = 0;
            auto op_stage = [&](int i) {
                mbar_wait(misc + BAR_FULL3 + 8 * st, ph3);
                PROF_EV(44);
                uint32_t base = ring + st * ST3_BYTES;
                uint64_t da = mkdesc(base + w * 8192, 16, 1024, 1);
                uint64_t db = mkdesc(base + 16384, 2048, 512, 2);
                wg_fence();
#pragma unroll
                for (int k = 0; k < 4; k++) wgmma_ss_n160_ta0_tb1(acc, da + 2 * k, db + (k >> 1) * 640 + (k & 1) * 64, k ? 1 : i);
                wg_commit();
                if (i > 0) { wg_wait<1>(); if (i <= 32 - NST3) release(c, BAR_EMPTY3 + 8 * prev, 1); }
                prev = st;
                if (++st == NST3) { st = 0; ph3 ^= 1; }
            };
            PROF_EV(40); PROF_GT(65);
#pragma unroll
            for (int i = 0; i < 4; i++) { op_stage(i); store_pair(o, i, out, 8192, inv); }
            signal_event(c, EV_CTX + 3);
#pragma unroll 1
            for (int i = 4; i < 12; i++) op_stage(i);
            mbar_wait(misc + BAR_SEL, 0);
            const uint32_t tag = lds32(misc + MISC_EPOCH) & 1;
            const int g = c.lane >> 2, t = c.lane & 3;
            const int row = (2 * u3 + rank) * 128 + 64 * w + perm32(16 * c.warp + 8 * kap + g);
            const int col = 160 * s3 + 8 * t;
            int sel = -1;
#pragma unroll
            for (int i = 0; i < TOPC; i++) if ((int)lds32(misc + MISC_SEL + 4 * i) == row) sel = i;
            const int t256 = tid - 128;
            uint4* sendp = g_part + (size_t)cta * 2560 + t256;
            if (c.lane >= 30) stg128(sendp + 9 * 256, tag ^ 1, tag ^ 1, tag ^ 1, tag ^ 1);
#pragma unroll 1
            for (int i = 12; i < 32; i++) op_stage(i);
            uint4 xv[5], bv[5];
#pragma unroll
            for (int i = 0; i < 5; i++) xv[i] = ldg128(P.x + (size_t)row * DM + col + 32 * i);
            uint2 stat;
            asm volatile("ld.global.cg.v2.b32 {%0,%1}, [%2];" : "=r"(stat.x), "=r"(stat.y) : "l"(g_stats + row) : "memory");
            wg_wait<0>();
            fence_regs(acc);
            PROF_EV(41); PROF_GT(66);
            float keep[40];
#pragma unroll
            for (int j = 0; j < 10; j++) {
                uint32_t v0 = __float_as_uint(kap ? acc[8 * j + 0] : acc[8 * j + 2]), v1 = __float_as_uint(kap ? acc[8 * j + 1] : acc[8 * j + 3]);
                uint32_t v2 = __float_as_uint(kap ? acc[8 * j + 4] : acc[8 * j + 6]), v3 = __float_as_uint(kap ? acc[8 * j + 5] : acc[8 * j + 7]);
                asm volatile("st.relaxed.gpu.global.v4.b32 [%0], {%1,%2,%3,%4};" ::"l"(sendp + j * 256),
                             "r"((v0 & ~1u) | tag), "r"((v1 & ~1u) | tag), "r"((v2 & ~1u) | tag), "r"((v3 & ~1u) | tag) : "memory");
                keep[4 * j + 0] = kap ? acc[8 * j + 2] : acc[8 * j + 0]; keep[4 * j + 1] = kap ? acc[8 * j + 3] : acc[8 * j + 1];
                keep[4 * j + 2] = kap ? acc[8 * j + 6] : acc[8 * j + 4]; keep[4 * j + 3] = kap ? acc[8 * j + 7] : acc[8 * j + 5];
            }
            PROF_GT(67);
#pragma unroll
            for (int i = 0; i < 5; i++) {
                uint32_t xx[4] = {xv[i].x, xv[i].y, xv[i].z, xv[i].w};
#pragma unroll
                for (int e = 0; e < 4; e++) {
                    asm("sub.rn.bf16x2 %0, %0, %1;" : "+r"(xx[e]) : "r"(stat.x));
                    xx[e] = pack_bf16(bf_lo(xx[e]) * __uint_as_float(stat.y), bf_hi(xx[e]) * __uint_as_float(stat.y));
                }
                bv[i] = make_uint4(xx[0], xx[1], xx[2], xx[3]);
            }
            if (sel >= 0) {
#pragma unroll
                for (int i = 0; i < 5; i++) bv[i] = ldg128(g_brow + sel * DM + col + 32 * i);
            }
            const uint4* recvp = g_part + (size_t)partner * 2560 + t256;
            uint4 rv[10];
            int spins = 0;
            while (POLL1) {
                uint32_t v;
                asm volatile("ld.relaxed.gpu.global.b32 %0, [%1];" : "=r"(v) : "l"(recvp + 9 * 256 + (31 - c.lane)) : "memory");
                if (__all_sync(0xffffffffu, (v & 1u) == tag) || ++spins > 2000000) break;
            }
            PROF_GT(68);
            while (true) {
                uint32_t bad = 0u;
#pragma unroll
                for (int j = 0; j < 10; j++) {
                    asm volatile("ld.relaxed.gpu.global.v4.b32 {%0,%1,%2,%3}, [%4];"
                                 : "=r"(rv[j].x), "=r"(rv[j].y), "=r"(rv[j].z), "=r"(rv[j].w) : "l"(recvp + j * 256) : "memory");
                }
#pragma unroll
                for (int j = 0; j < 10; j++) {
                    rv[j].x ^= tag; rv[j].y ^= tag; rv[j].z ^= tag; rv[j].w ^= tag;
                    bad |= rv[j].x | rv[j].y | rv[j].z | rv[j].w;
                }
                if (__all_sync(0xffffffffu, (bad & 1u) == 0) || ++spins > 2000000) break;
            }
            PROF_GT(69);
            uint32_t pk[20];
#pragma unroll
            for (int j = 0; j < 10; j++) {
                pk[2 * j] = pack_bf16(keep[4 * j] + __uint_as_float(rv[j].x), keep[4 * j + 1] + __uint_as_float(rv[j].y));
                pk[2 * j + 1] = pack_bf16(keep[4 * j + 2] + __uint_as_float(rv[j].z), keep[4 * j + 3] + __uint_as_float(rv[j].w));
            }
#pragma unroll
            for (int i = 0; i < 5; i++) {
                uint32_t a0 = pk[4 * i], a1 = pk[4 * i + 1], a2 = pk[4 * i + 2], a3 = pk[4 * i + 3];
                uint32_t x0 = (t & 1) ? a0 : a1, x1 = (t & 1) ? a2 : a3;
                x0 = __shfl_xor_sync(0xffffffffu, x0, 1); x1 = __shfl_xor_sync(0xffffffffu, x1, 1);
                if (t & 1) { a0 = x0; a2 = x1; } else { a1 = x0; a3 = x1; }
                x0 = (t & 2) ? a0 : a2; x1 = (t & 2) ? a1 : a3;
                x0 = __shfl_xor_sync(0xffffffffu, x0, 2); x1 = __shfl_xor_sync(0xffffffffu, x1, 2);
                if (t & 2) { a0 = x0; a1 = x1; } else { a2 = x0; a3 = x1; }
                uint32_t av[4] = {a0, a1, a2, a3};
                uint32_t xx[4] = {xv[i].x, xv[i].y, xv[i].z, xv[i].w}, bb[4] = {bv[i].x, bv[i].y, bv[i].z, bv[i].w};
                uint32_t ov[4];
#pragma unroll
                for (int e = 0; e < 4; e++) {
                    asm("add.rn.bf16x2 %0, %1, %2;" : "=r"(ov[e]) : "r"(xx[e]), "r"(av[e]));
                    asm("add.rn.bf16x2 %0, %0, %1;" : "+r"(ov[e]) : "r"(bb[e]));
                }
                stg128(P.out + (size_t)row * DM + col + 32 * i, ov[0], ov[1], ov[2], ov[3]);
            }
            PROF_EV(42); PROF_GT(43);
        }
    }
}

typedef CUresult (*EncodeFn)(CUtensorMap*, CUtensorMapDataType, cuuint32_t, void*, const cuuint64_t*, const cuuint64_t*, const cuuint32_t*,
                             const cuuint32_t*, CUtensorMapInterleave, CUtensorMapSwizzle, CUtensorMapL2promotion, CUtensorMapFloatOOBfill);

void make_map2d(EncodeFn enc, CUtensorMap* tm, const void* p, uint64_t cols, uint64_t rows, uint32_t box_rows = 128) {
    cuuint64_t gd[2] = {cols, rows}, gs[1] = {cols * 2};
    cuuint32_t box[2] = {64, box_rows}, es[2] = {1, 1};
    enc(tm, CU_TENSOR_MAP_DATA_TYPE_BFLOAT16, 2, const_cast<void*>(p), gd, gs, box, es, CU_TENSOR_MAP_INTERLEAVE_NONE,
        CU_TENSOR_MAP_SWIZZLE_128B, CU_TENSOR_MAP_L2_PROMOTION_L2_128B, CU_TENSOR_MAP_FLOAT_OOB_FILL_NONE);
}

void make_map3d(EncodeFn enc, CUtensorMap* tm, const void* p, uint64_t cols, uint64_t rows, uint32_t bw, uint32_t nb) {
    cuuint64_t gd[3] = {bw, rows, cols / bw}, gs[2] = {cols * 2, bw * 2};
    cuuint32_t box[3] = {bw, 32, nb}, es[3] = {1, 1, 1};
    enc(tm, CU_TENSOR_MAP_DATA_TYPE_BFLOAT16, 3, const_cast<void*>(p), gd, gs, box, es, CU_TENSOR_MAP_INTERLEAVE_NONE,
        bw == 64 ? CU_TENSOR_MAP_SWIZZLE_128B : CU_TENSOR_MAP_SWIZZLE_64B, CU_TENSOR_MAP_L2_PROMOTION_L2_128B, CU_TENSOR_MAP_FLOAT_OOB_FILL_NONE);
}

}

extern "C" void kernel_launch(void* const* d_in, const int* in_sizes, int n_in, void* d_out, int out_size) {
    (void)in_sizes; (void)n_in; (void)out_size;
    static EncodeFn enc = nullptr;
    if (!enc) {
        void* fn = nullptr;
        cudaDriverEntryPointQueryResult qr;
        cudaGetDriverEntryPoint("cuTensorMapEncodeTiled", &fn, cudaEnableDefault, &qr);
        enc = (EncodeFn)fn;
        cudaFuncSetAttribute(fused_kernel, cudaFuncAttributeMaxDynamicSharedMemorySize, SMEM_BYTES);
    }
    CUtensorMap tmC, tmWk, tmWv, tmWq, tmWo, tmG, tmU, tmD;
    make_map2d(enc, &tmC, d_in[1], DC, SEQ);
    make_map2d(enc, &tmWq, d_in[2], 4096, DM, 64);
    make_map2d(enc, &tmWk, d_in[3], 4096, DC);
    make_map2d(enc, &tmWv, d_in[4], 4096, DC);
    make_map3d(enc, &tmWo, d_in[5], DM, 4096, 32, 5);
    make_map3d(enc, &tmG, d_in[8], FF, DM, 64, 7);
    make_map3d(enc, &tmU, d_in[9], FF, DM, 64, 7);
    make_map3d(enc, &tmD, d_in[10], DM, FF, 64, 10);
    Params P;
    P.x = (const __nv_bfloat16*)d_in[0];
    P.c = (const __nv_bfloat16*)d_in[1];
    P.wk = (const __nv_bfloat16*)d_in[3];
    P.wv = (const __nv_bfloat16*)d_in[4];
    P.wo = (const __nv_bfloat16*)d_in[5];
    P.wr = (const __nv_bfloat16*)d_in[7];
    P.out = (__nv_bfloat16*)d_out;
    fused_kernel<<<132, 384, SMEM_BYTES>>>(tmC, tmWk, tmWv, tmWq, tmWo, tmG, tmU, tmD, P);
}
```

```cpp
#include <cuda_runtime.h>
#include <cuda_bf16.h>
#include <cuda.h>
#include <stdint.h>

#define SWAPT 1
#define DEFER 1
#define HOLD0 6
#define HM 512
#define POLL1 1
#define OP_PF 8
#define PF_START 9
#define LATE_AT 18
#define CDELAY 500
#define AUXDELAY 1000
namespace {

constexpr int SEQ = 2048, NH = 32, DM = 640, DC = 512, FF = 1728, TOPC = 8;
constexpr int NSLOT = 7, SLOT_BYTES = 32768;
constexpr int NST3 = 6, ST3_BYTES = 36864;
constexpr int RING_BYTES = NSLOT * SLOT_BYTES;
constexpr int SMEM_BYTES = RING_BYTES + 3072;

constexpr int BAR_FULL = 96  , BAR_FULL3 = 152  , BAR_DEP = 200  , BAR_SEL = 464,
              BAR_LN = 472  , BAR_EV = 504  , BAR_EMPTY = 760  , BAR_EMPTY3 = 816  ,
              BAR_PROG = 864  , MISC_EPOCH = 896, MISC_SMID = 900  , MISC_SEL = 912, MISC_WR = 1024  ;
constexpr int D_LN = 0  , D_KV = 4  , D_WAR = 14  , D_CTX = 16  ;
constexpr int EV_KV = 0  , EV_CTX = 12  ;

constexpr int FL_MOE_CNT = 0, FL_MOE_DONE = 1, FL_LN = 16  , FL_KV = 32  , FL_CTX = 416  , FL_WAR = 672  , FL_TOTAL = 704;

__device__ __align__(1024) unsigned char g_K[16 * 32 * 16384];
__device__ __align__(1024) unsigned char g_V[16 * 32 * 16384];
__device__ __align__(1024) unsigned char g_ctx[NH * 32 * 16384];
__device__ __align__(1024) unsigned char g_xn[16 * 10 * 16384];
__device__ __align__(1024) uint4 g_part[128 * 10 * 256];
__device__ float g_router[SEQ];
__device__ uint2 g_stats[SEQ];
__device__ __align__(16) float g_moe_part[4 * TOPC * DM];
__device__ __align__(16) __nv_bfloat16 g_brow[TOPC * DM];
__device__ __align__(16) int g_sel[TOPC];
__device__ unsigned g_flags[FL_TOTAL * 8];
__device__ unsigned g_epoch;
__device__ unsigned g_roleq[130];

struct Params {
    const __nv_bfloat16 *x, *c, *wr, *wk, *wv, *wo;
    __nv_bfloat16* out;
};

__device__ __forceinline__ uint32_t smem_u32(const void* p) { return (uint32_t)__cvta_generic_to_shared(p); }
__device__ __forceinline__ void mbar_init(uint32_t bar, int cnt) { asm volatile("mbarrier.init.shared::cta.b64 [%0], %1;" ::"r"(bar), "r"(cnt)); }
__device__ __forceinline__ void mbar_expect_tx(uint32_t bar, uint32_t bytes) {
    asm volatile("mbarrier.arrive.expect_tx.shared::cta.b64 _, [%0], %1;" ::"r"(bar), "r"(bytes) : "memory");
}
__device__ __forceinline__ void mbar_arrive(uint32_t bar) { asm volatile("mbarrier.arrive.shared::cta.b64 _, [%0];" ::"r"(bar) : "memory"); }
__device__ __forceinline__ void mbar_arrive_cluster(uint32_t cluster_addr, uint32_t cnt) {
    asm volatile("mbarrier.arrive.shared::cluster.b64 _, [%0], %1;" ::"r"(cluster_addr), "r"(cnt) : "memory");
}
__device__ __forceinline__ uint32_t mapa(uint32_t addr, uint32_t cta) {
    uint32_t r; asm("mapa.shared::cluster.u32 %0, %1, %2;" : "=r"(r) : "r"(addr), "r"(cta)); return r;
}
__device__ __forceinline__ void mbar_wait(uint32_t bar, uint32_t parity) {
    asm volatile(
        "{\n.reg .pred p;\n.reg .u32 n;\n"
        "mbarrier.try_wait.parity.shared::cta.b64 p, [%0], %1;\n"
        "@p bra DONE;\n"
        "mov.u32 n, 0;\n"
        "LAB_WAIT:\n"
        "mbarrier.try_wait.parity.shared::cta.b64 p, [%0], %1, 100000;\n"
        "@p bra DONE;\n"
        "add.u32 n, n, 1;\n"
        "setp.lt.u32 p, n, 200000;\n"
        "@p bra LAB_WAIT;\n"
        "trap;\n"
        "DONE:\n}\n" ::"r"(bar), "r"(parity) : "memory");
}
__device__ __forceinline__ void mbar_wait_hot(uint32_t bar, uint32_t parity) {
    asm volatile("{\n.reg .pred p;\nLAB_WAIT:\nmbarrier.try_wait.parity.shared::cta.b64 p, [%0], %1;\n@!p bra LAB_WAIT;\n}\n" ::"r"(bar), "r"(parity) : "memory");
}
__device__ __forceinline__ void flag_wait(const unsigned* flag, unsigned target) {
    asm volatile(
        "{\n.reg .pred p;\n.reg .u32 n, v;\n.reg .s32 d;\n"
        "mov.u32 n, 0;\n"
        "LAB_WAIT:\n"
        "ld.acquire.gpu.global.u32 v, [%0];\n"
        "sub.s32 d, v, %1;\n"
        "setp.ge.s32 p, d, 0;\n"
        "@p bra DONE;\n"
        "nanosleep.u32 40;\n"
        "add.u32 n, n, 1;\n"
        "setp.lt.u32 p, n, 3000000;\n"
        "@p bra LAB_WAIT;\n"
        "trap;\n"
        "DONE:\n}\n" ::"l"(flag), "r"(target) : "memory");
}
__device__ __forceinline__ void flag_signal(unsigned* flag) {
    asm volatile("red.release.gpu.global.add.u32 [%0], 1;" ::"l"(flag) : "memory");
}
__device__ __forceinline__ void fence_async_global() { asm volatile("fence.proxy.async.global;" ::: "memory"); }
__device__ __forceinline__ unsigned* flag_ptr(int idx) { return g_flags + idx * 8; }

__device__ __forceinline__ uint64_t policy_stream() {
    uint64_t p; asm("createpolicy.fractional.L2::evict_first.b64 %0, 1.0;" : "=l"(p)); return p;
}
__device__ __forceinline__ uint64_t policy_normal() { return 0x1000000000000000ull; }
__device__ __forceinline__ uint64_t policy(bool stream) { return stream ? policy_stream() : policy_normal(); }
__device__ __forceinline__ void bulk_load(uint32_t dst, const void* src, uint32_t bytes, uint32_t bar, uint64_t pol) {
    asm volatile("cp.async.bulk.shared::cluster.global.mbarrier::complete_tx::bytes.L2::cache_hint [%0], [%1], %2, [%3], %4;"
                 ::"r"(dst), "l"(src), "r"(bytes), "r"(bar), "l"(pol) : "memory");
}
__device__ __forceinline__ void bulk_load_mc(uint32_t dst, const void* src, uint32_t bytes, uint32_t bar, uint64_t pol) {
    asm volatile("cp.async.bulk.shared::cluster.global.mbarrier::complete_tx::bytes.multicast::cluster.L2::cache_hint [%0], [%1], %2, [%3], %4, %5;"
                 ::"r"(dst), "l"(src), "r"(bytes), "r"(bar), "h"((uint16_t)3), "l"(pol) : "memory");
}
__device__ __forceinline__ void tma2d(uint32_t dst, const CUtensorMap* tm, int c0, int c1, uint32_t bar, uint64_t pol) {
    asm volatile("cp.async.bulk.tensor.2d.shared::cluster.global.mbarrier::complete_tx::bytes.L2::cache_hint [%0], [%1, {%3, %4}], [%2], %5;"
                 ::"r"(dst), "l"(tm), "r"(bar), "r"(c0), "r"(c1), "l"(pol) : "memory");
}
__device__ __forceinline__ void tma2d_mc(uint32_t dst, const CUtensorMap* tm, int c0, int c1, uint32_t bar, uint64_t pol) {
    asm volatile("cp.async.bulk.tensor.2d.shared::cluster.global.mbarrier::complete_tx::bytes.multicast::cluster.L2::cache_hint [%0], [%1, {%3, %4}], [%2], %5, %6;"
                 ::"r"(dst), "l"(tm), "r"(bar), "r"(c0), "r"(c1), "h"((uint16_t)3), "l"(pol) : "memory");
}
__device__ __forceinline__ void tma3d_mc(uint32_t dst, const CUtensorMap* tm, int c0, int c1, int c2, uint32_t bar, uint64_t pol) {
    asm volatile("cp.async.bulk.tensor.3d.shared::cluster.global.mbarrier::complete_tx::bytes.multicast::cluster.L2::cache_hint [%0], [%1, {%3, %4, %5}], [%2], %6, %7;"
                 ::"r"(dst), "l"(tm), "r"(bar), "r"(c0), "r"(c1), "r"(c2), "h"((uint16_t)3), "l"(pol) : "memory");
}
__device__ __forceinline__ void tma3d(uint32_t dst, const CUtensorMap* tm, int c0, int c1, int c2, uint32_t bar) {
    asm volatile("cp.async.bulk.tensor.3d.shared::cluster.global.mbarrier::complete_tx::bytes.L2::cache_hint [%0], [%1, {%3, %4, %5}], [%2], %6;"
                 ::"r"(dst), "l"(tm), "r"(bar), "r"(c0), "r"(c1), "r"(c2), "l"(policy_stream()) : "memory");
}
__device__ __forceinline__ void tma2d_prefetch(const CUtensorMap* tm, int c0, int c1) {
    asm volatile("cp.async.bulk.prefetch.tensor.2d.L2.global [%0, {%1, %2}];" ::"l"(tm), "r"(c0), "r"(c1) : "memory");
}
__device__ __forceinline__ void tma3d_prefetch(const CUtensorMap* tm, int c0, int c1, int c2) {
    asm volatile("cp.async.bulk.prefetch.tensor.3d.L2.global [%0, {%1, %2, %3}];" ::"l"(tm), "r"(c0), "r"(c1), "r"(c2) : "memory");
}
__device__ __forceinline__ void l2_prefetch(const void* p, uint32_t bytes) {
    asm volatile("cp.async.bulk.prefetch.L2.global [%0], %1;" ::"l"(p), "r"(bytes) : "memory");
}
__device__ __forceinline__ bool elect_one() {
    uint32_t r; asm volatile("{\n.reg .pred p;\nelect.sync _|p, 0xffffffff;\nselp.u32 %0, 1, 0, p;\n}\n" : "=r"(r)); return r != 0;
}
__device__ __forceinline__ void wg_fence() { asm volatile("wgmma.fence.sync.aligned;" ::: "memory"); }
__device__ __forceinline__ void wg_commit() { asm volatile("wgmma.commit_group.sync.aligned;" ::: "memory"); }
template <int N> __device__ __forceinline__ void wg_wait() { asm volatile("wgmma.wait_group.sync.aligned %0;" ::"n"(N) : "memory"); }
__device__ __forceinline__ void bar_sync(int id, int n) { asm volatile("bar.sync %0, %1;" ::"r"(id), "r"(n) : "memory"); }
__device__ __forceinline__ void bar_arrive(int id, int n) { asm volatile("bar.arrive %0, %1;" ::"r"(id), "r"(n) : "memory"); }
__device__ __forceinline__ void token_wait(int w) {
    asm volatile("{\n.reg .pred p;\nsetp.eq.u32 p, %0, 0;\n@p bar.sync 1, 256;\n@!p bar.sync 2, 256;\n}\n" ::"r"(w) : "memory");
}
__device__ __forceinline__ void token_pass(int w) {
    asm volatile("{\n.reg .pred p;\nsetp.eq.u32 p, %0, 0;\n@p bar.arrive 2, 256;\n@!p bar.arrive 1, 256;\n}\n" ::"r"(w) : "memory");
}
template <int N> __device__ __forceinline__ void fence_regs(float (&a)[N]) {
#pragma unroll
    for (int i = 0; i < N; i++) asm volatile("" : "+f"(a[i])::"memory");
}
template <int N> __device__ __forceinline__ void undef_regs(float (&a)[N]) {
#pragma unroll
    for (int i = 0; i < N; i++) asm volatile("" : "=f"(a[i]));
}
__device__ __forceinline__ void ldsm4t(uint32_t& r0, uint32_t& r1, uint32_t& r2, uint32_t& r3, uint32_t addr) {
    asm volatile("ldmatrix.sync.aligned.m8n8.x4.trans.shared.b16 {%0,%1,%2,%3}, [%4];"
                 : "=r"(r0), "=r"(r1), "=r"(r2), "=r"(r3) : "r"(addr) : "memory");
}
__device__ __forceinline__ uint32_t pack_bf16(float lo, float hi) {
    uint32_t r; asm("cvt.rn.bf16x2.f32 %0, %1, %2;" : "=r"(r) : "f"(hi), "f"(lo)); return r;
}
__device__ __forceinline__ float bf_lo(uint32_t v) { return __uint_as_float(v << 16); }
__device__ __forceinline__ float bf_hi(uint32_t v) { return __uint_as_float(v & 0xffff0000u); }
__device__ __forceinline__ float bf_round(float v) { return __bfloat162float(__float2bfloat16_rn(v)); }
__device__ __forceinline__ float ex2(float v) { float r; asm("ex2.approx.ftz.f32 %0, %1;" : "=f"(r) : "f"(v)); return r; }
__device__ __forceinline__ void ex2v(float& v) { asm volatile("ex2.approx.ftz.f32 %0, %0;" : "+f"(v)); }
__device__ __forceinline__ float rcp_fast(float v) { float r; asm("rcp.approx.ftz.f32 %0, %1;" : "=f"(r) : "f"(v)); return r; }
__device__ __forceinline__ float sqrt_fast(float v) { float r; asm("sqrt.approx.ftz.f32 %0, %1;" : "=f"(r) : "f"(v)); return r; }
__device__ __forceinline__ void stg128(void* p, uint32_t a, uint32_t b, uint32_t c, uint32_t d) {
    asm volatile("st.global.v4.b32 [%0], {%1,%2,%3,%4};" ::"l"(p), "r"(a), "r"(b), "r"(c), "r"(d) : "memory");
}
__device__ __forceinline__ uint4 ldg128(const void* p) {
    uint4 v; asm volatile("ld.global.cg.v4.b32 {%0,%1,%2,%3}, [%4];" : "=r"(v.x), "=r"(v.y), "=r"(v.z), "=r"(v.w) : "l"(p) : "memory"); return v;
}
__device__ __forceinline__ uint64_t mkdesc(uint32_t addr, uint32_t lbo, uint32_t sbo, uint32_t swz) {
    uint32_t lo = ((addr & 0x3FFFF) >> 4) | ((lbo >> 4) << 16);
    uint32_t hi = (sbo >> 4) | (swz << 30);
    return ((uint64_t)hi << 32) | lo;
}
__device__ __forceinline__ int perm32(int v) { return (v & ~30) | ((v >> 2) & 6) | ((v << 2) & 24); }

__device__ __forceinline__ void wgmma_rs_n128_ta0_tb0(float (&d)[64], uint32_t a0, uint32_t a1, uint32_t a2, uint32_t a3, uint64_t descB, int scaleD) {
  asm volatile("{\n.reg .pred p;\nsetp.ne.b32 p, %69, 0;\n"
    "wgmma.mma_async.sync.aligned.m64n128k16.f32.bf16.bf16 "
    "{%0, %1, %2, %3, %4, %5, %6, %7, %8, %9, %10, %11, %12, %13, %14, %15, %16, %17, %18, %19, %20, %21, %22, %23, %24, %25, %26, %27, %28, %29, %30, %31, %32, %33, %34, %35, %36, %37, %38, %39, %40, %41, %42, %43, %44, %45, %46, %47, %48, %49, %50, %51, %52, %53, %54, %55, %56, %57, %58, %59, %60, %61, %62, %63}, "
    "{%64, %65, %66, %67}, %68, p, 1, 1, 0;\n}\n"
    : "+f"(d[0]), "+f"(d[1]), "+f"(d[2]), "+f"(d[3]), "+f"(d[4]), "+f"(d[5]), "+f"(d[6]), "+f"(d[7]), "+f"(d[8]), "+f"(d[9]), "+f"(d[10]), "+f"(d[11]), "+f"(d[12]), "+f"(d[13]), "+f"(d[14]), "+f"(d[15]), "+f"(d[16]), "+f"(d[17]), "+f"(d[18]), "+f"(d[19]), "+f"(d[20]), "+f"(d[21]), "+f"(d[22]), "+f"(d[23]), "+f"(d[24]), "+f"(d[25]), "+f"(d[26]), "+f"(d[27]), "+f"(d[28]), "+f"(d[29]), "+f"(d[30]), "+f"(d[31]), "+f"(d[32]), "+f"(d[33]), "+f"(d[34]), "+f"(d[35]), "+f"(d[36]), "+f"(d[37]), "+f"(d[38]), "+f"(d[39]), "+f"(d[40]), "+f"(d[41]), "+f"(d[42]), "+f"(d[43]), "+f"(d[44]), "+f"(d[45]), "+f"(d[46]), "+f"(d[47]), "+f"(d[48]), "+f"(d[49]), "+f"(d[50]), "+f"(d[51]), "+f"(d[52]), "+f"(d[53]), "+f"(d[54]), "+f"(d[55]), "+f"(d[56]), "+f"(d[57]), "+f"(d[58]), "+f"(d[59]), "+f"(d[60]), "+f"(d[61]), "+f"(d[62]), "+f"(d[63])
    : "r"(a0), "r"(a1), "r"(a2), "r"(a3), "l"(descB), "r"(scaleD));
}
__device__ __forceinline__ void wgmma_rs_n128_ta0_tb1(float (&d)[64], uint32_t a0, uint32_t a1, uint32_t a2, uint32_t a3, uint64_t descB, int scaleD) {
  asm volatile("{\n.reg .pred p;\nsetp.ne.b32 p, %69, 0;\n"
    "wgmma.mma_async.sync.aligned.m64n128k16.f32.bf16.bf16 "
    "{%0, %1, %2, %3, %4, %5, %6, %7, %8, %9, %10, %11, %12, %13, %14, %15, %16, %17, %18, %19, %20, %21, %22, %23, %24, %25, %26, %27, %28, %29, %30, %31, %32, %33, %34, %35, %36, %37, %38, %39, %40, %41, %42, %43, %44, %45, %46, %47, %48, %49, %50, %51, %52, %53, %54, %55, %56, %57, %58, %59, %60, %61, %62, %63}, "
    "{%64, %65, %66, %67}, %68, p, 1, 1, 1;\n}\n"
    : "+f"(d[0]), "+f"(d[1]), "+f"(d[2]), "+f"(d[3]), "+f"(d[4]), "+f"(d[5]), "+f"(d[6]), "+f"(d[7]), "+f"(d[8]), "+f"(d[9]), "+f"(d[10]), "+f"(d[11]), "+f"(d[12]), "+f"(d[13]), "+f"(d[14]), "+f"(d[15]), "+f"(d[16]), "+f"(d[17]), "+f"(d[18]), "+f"(d[19]), "+f"(d[20]), "+f"(d[21]), "+f"(d[22]), "+f"(d[23]), "+f"(d[24]), "+f"(d[25]), "+f"(d[26]), "+f"(d[27]), "+f"(d[28]), "+f"(d[29]), "+f"(d[30]), "+f"(d[31]), "+f"(d[32]), "+f"(d[33]), "+f"(d[34]), "+f"(d[35]), "+f"(d[36]), "+f"(d[37]), "+f"(d[38]), "+f"(d[39]), "+f"(d[40]), "+f"(d[41]), "+f"(d[42]), "+f"(d[43]), "+f"(d[44]), "+f"(d[45]), "+f"(d[46]), "+f"(d[47]), "+f"(d[48]), "+f"(d[49]), "+f"(d[50]), "+f"(d[51]), "+f"(d[52]), "+f"(d[53]), "+f"(d[54]), "+f"(d[55]), "+f"(d[56]), "+f"(d[57]), "+f"(d[58]), "+f"(d[59]), "+f"(d[60]), "+f"(d[61]), "+f"(d[62]), "+f"(d[63])
    : "r"(a0), "r"(a1), "r"(a2), "r"(a3), "l"(descB), "r"(scaleD));
}
__device__ __forceinline__ void wgmma_rs_n64_ta0_tb1(float (&d)[32], uint32_t a0, uint32_t a1, uint32_t a2, uint32_t a3, uint64_t descB, int scaleD) {
  asm volatile("{\n.reg .pred p;\nsetp.ne.b32 p, %37, 0;\n"
    "wgmma.mma_async.sync.aligned.m64n64k16.f32.bf16.bf16 "
    "{%0, %1, %2, %3, %4, %5, %6, %7, %8, %9, %10, %11, %12, %13, %14, %15, %16, %17, %18, %19, %20, %21, %22, %23, %24, %25, %26, %27, %28, %29, %30, %31}, "
    "{%32, %33, %34, %35}, %36, p, 1, 1, 1;\n}\n"
    : "+f"(d[0]), "+f"(d[1]), "+f"(d[2]), "+f"(d[3]), "+f"(d[4]), "+f"(d[5]), "+f"(d[6]), "+f"(d[7]), "+f"(d[8]), "+f"(d[9]), "+f"(d[10]), "+f"(d[11]), "+f"(d[12]), "+f"(d[13]), "+f"(d[14]), "+f"(d[15]), "+f"(d[16]), "+f"(d[17]), "+f"(d[18]), "+f"(d[19]), "+f"(d[20]), "+f"(d[21]), "+f"(d[22]), "+f"(d[23]), "+f"(d[24]), "+f"(d[25]), "+f"(d[26]), "+f"(d[27]), "+f"(d[28]), "+f"(d[29]), "+f"(d[30]), "+f"(d[31])
    : "r"(a0), "r"(a1), "r"(a2), "r"(a3), "l"(descB), "r"(scaleD));
}
__device__ __forceinline__ void wgmma_ss_n128_ta0_tb1(float (&d)[64], uint64_t descA, uint64_t descB, int scaleD) {
  asm volatile("{\n.reg .pred p;\nsetp.ne.b32 p, %66, 0;\n"
    "wgmma.mma_async.sync.aligned.m64n128k16.f32.bf16.bf16 "
    "{%0, %1, %2, %3, %4, %5, %6, %7, %8, %9, %10, %11, %12, %13, %14, %15, %16, %17, %18, %19, %20, %21, %22, %23, %24, %25, %26, %27, %28, %29, %30, %31, %32, %33, %34, %35, %36, %37, %38, %39, %40, %41, %42, %43, %44, %45, %46, %47, %48, %49, %50, %51, %52, %53, %54, %55, %56, %57, %58, %59, %60, %61, %62, %63}, "
    "%64, %65, p, 1, 1, 0, 1;\n}\n"
    : "+f"(d[0]), "+f"(d[1]), "+f"(d[2]), "+f"(d[3]), "+f"(d[4]), "+f"(d[5]), "+f"(d[6]), "+f"(d[7]), "+f"(d[8]), "+f"(d[9]), "+f"(d[10]), "+f"(d[11]), "+f"(d[12]), "+f"(d[13]), "+f"(d[14]), "+f"(d[15]), "+f"(d[16]), "+f"(d[17]), "+f"(d[18]), "+f"(d[19]), "+f"(d[20]), "+f"(d[21]), "+f"(d[22]), "+f"(d[23]), "+f"(d[24]), "+f"(d[25]), "+f"(d[26]), "+f"(d[27]), "+f"(d[28]), "+f"(d[29]), "+f"(d[30]), "+f"(d[31]), "+f"(d[32]), "+f"(d[33]), "+f"(d[34]), "+f"(d[35]), "+f"(d[36]), "+f"(d[37]), "+f"(d[38]), "+f"(d[39]), "+f"(d[40]), "+f"(d[41]), "+f"(d[42]), "+f"(d[43]), "+f"(d[44]), "+f"(d[45]), "+f"(d[46]), "+f"(d[47]), "+f"(d[48]), "+f"(d[49]), "+f"(d[50]), "+f"(d[51]), "+f"(d[52]), "+f"(d[53]), "+f"(d[54]), "+f"(d[55]), "+f"(d[56]), "+f"(d[57]), "+f"(d[58]), "+f"(d[59]), "+f"(d[60]), "+f"(d[61]), "+f"(d[62]), "+f"(d[63])
    : "l"(descA), "l"(descB), "r"(scaleD));
}
__device__ __forceinline__ void wgmma_ss_n160_ta0_tb1(float (&d)[80], uint64_t descA, uint64_t descB, int scaleD) {
  asm volatile("{\n.reg .pred p;\nsetp.ne.b32 p, %82, 0;\n"
    "wgmma.mma_async.sync.aligned.m64n160k16.f32.bf16.bf16 "
    "{%0, %1, %2, %3, %4, %5, %6, %7, %8, %9, %10, %11, %12, %13, %14, %15, %16, %17, %18, %19, %20, %21, %22, %23, %24, %25, %26, %27, %28, %29, %30, %31, %32, %33, %34, %35, %36, %37, %38, %39, %40, %41, %42, %43, %44, %45, %46, %47, %48, %49, %50, %51, %52, %53, %54, %55, %56, %57, %58, %59, %60, %61, %62, %63, %64, %65, %66, %67, %68, %69, %70, %71, %72, %73, %74, %75, %76, %77, %78, %79}, "
    "%80, %81, p, 1, 1, 0, 1;\n}\n"
    : "+f"(d[0]), "+f"(d[1]), "+f"(d[2]), "+f"(d[3]), "+f"(d[4]), "+f"(d[5]), "+f"(d[6]), "+f"(d[7]), "+f"(d[8]), "+f"(d[9]), "+f"(d[10]), "+f"(d[11]), "+f"(d[12]), "+f"(d[13]), "+f"(d[14]), "+f"(d[15]), "+f"(d[16]), "+f"(d[17]), "+f"(d[18]), "+f"(d[19]), "+f"(d[20]), "+f"(d[21]), "+f"(d[22]), "+f"(d[23]), "+f"(d[24]), "+f"(d[25]), "+f"(d[26]), "+f"(d[27]), "+f"(d[28]), "+f"(d[29]), "+f"(d[30]), "+f"(d[31]), "+f"(d[32]), "+f"(d[33]), "+f"(d[34]), "+f"(d[35]), "+f"(d[36]), "+f"(d[37]), "+f"(d[38]), "+f"(d[39]), "+f"(d[40]), "+f"(d[41]), "+f"(d[42]), "+f"(d[43]), "+f"(d[44]), "+f"(d[45]), "+f"(d[46]), "+f"(d[47]), "+f"(d[48]), "+f"(d[49]), "+f"(d[50]), "+f"(d[51]), "+f"(d[52]), "+f"(d[53]), "+f"(d[54]), "+f"(d[55]), "+f"(d[56]), "+f"(d[57]), "+f"(d[58]), "+f"(d[59]), "+f"(d[60]), "+f"(d[61]), "+f"(d[62]), "+f"(d[63]), "+f"(d[64]), "+f"(d[65]), "+f"(d[66]), "+f"(d[67]), "+f"(d[68]), "+f"(d[69]), "+f"(d[70]), "+f"(d[71]), "+f"(d[72]), "+f"(d[73]), "+f"(d[74]), "+f"(d[75]), "+f"(d[76]), "+f"(d[77]), "+f"(d[78]), "+f"(d[79])
    : "l"(descA), "l"(descB), "r"(scaleD));
}

#define PROF_DECL(b)
#define PROF_EV(tag)
#define PROF_GT(tag)

template <int N> struct IC { static constexpr int value = N; };
struct Cur {
    uint32_t slot, ph;
    __device__ __forceinline__ void adv() { if (++slot == NSLOT) { slot = 0; ph ^= 1; } }
};
constexpr int E0 = 2;
__host__ __device__ constexpr uint32_t slot_of(int e) { return (e + E0) % NSLOT; }
__device__ __forceinline__ Cur cur_at(int e) { Cur c; c.slot = (e + E0) % NSLOT; c.ph = ((e + E0) / NSLOT) & 1; return c; }

__device__ __forceinline__ int op_head(int i, int kap) { return 16 * kap + 2 * (i & 7) + (i >> 3); }

constexpr float SM_SCALE = 0.08838834764831845f * 1.4426950408889634f;

struct Ctx {
    uint32_t ring, misc;
    uint32_t rel;
    int w, warp, lane;
};
__device__ __forceinline__ void release(const Ctx& c, uint32_t off, uint32_t cnt) {
    if (c.lane < 2) mbar_arrive_cluster(c.rel + off, cnt);
}
__device__ __forceinline__ void signal_event(const Ctx& c, int ev) {
    __syncwarp();
    if (c.lane == 0) mbar_arrive(c.misc + BAR_EV + (c.w * 16 + ev) * 8);
}
template <int NK, int OFF, int N>
__device__ __forceinline__ uint32_t load_afrag(uint32_t (&a)[N], uint32_t base, const Ctx& c) {
    int r = c.lane & 7, mat = c.lane >> 3;
    uint32_t addr = base + (8 * (mat >> 1) + r) * 128 + (((2 * c.warp + (mat & 1)) ^ r) << 4);
#pragma unroll
    for (int k = 0; k < NK; k++) ldsm4t(a[OFF + 4 * k], a[OFF + 4 * k + 1], a[OFF + 4 * k + 2], a[OFF + 4 * k + 3], addr + k * 2048);
    uint32_t dep = 0;
#pragma unroll
    for (int k = 0; k < NK; k++) dep |= a[OFF + 4 * k];
    return dep & blockIdx.y;
}
__device__ __forceinline__ void tile_out(unsigned char* (&out)[2], unsigned char* dst, int row0, int perm, const Ctx& c) {
#pragma unroll
    for (int i = 0; i < 2; i++) {
        int g = c.lane >> 2;
        if (perm == 2) g = ((g & 1) << 2) | (g >> 1);
        int row = row0 + 16 * c.warp + 8 * i + g;
        if (perm == 1) row = perm32(row);
        out[i] = dst + row * 128 + (((c.lane & 3) ^ (row & 7)) << 4);
    }
}
__device__ __forceinline__ void store_pair(const float (&a)[64], int n, unsigned char* const (&out)[2], int half_stride, const float (&f)[2]) {
    const int i = n & 1;
#pragma unroll
    for (int q = 2 * (n >> 1); q < 2 * (n >> 1) + 2; q++)
        stg128(reinterpret_cast<unsigned char*>(reinterpret_cast<uint64_t>(out[i]) ^ ((q & 1) << 6)) + (q >> 1) * half_stride,
               pack_bf16(a[16 * q + 2 * i] * f[i], a[16 * q + 2 * i + 1] * f[i]), pack_bf16(a[16 * q + 4 + 2 * i] * f[i], a[16 * q + 4 + 2 * i + 1] * f[i]),
               pack_bf16(a[16 * q + 8 + 2 * i] * f[i], a[16 * q + 8 + 2 * i + 1] * f[i]), pack_bf16(a[16 * q + 12 + 2 * i] * f[i], a[16 * q + 12 + 2 * i + 1] * f[i]));
}

constexpr float SAFE_SUM = 1099511627776.0f;
template <int NJ>
__device__ __forceinline__ void row_max(const float (&s)[4 * NJ], float (&mx)[2]) {
#pragma unroll
    for (int i = 0; i < 2; i++) {
        float a = fmaxf(s[2 * i], s[2 * i + 1]), b = fmaxf(s[4 + 2 * i], s[4 + 2 * i + 1]);
#pragma unroll
        for (int j = 2; j < NJ; j += 2) {
            a = fmaxf(a, fmaxf(s[4 * j + 2 * i], s[4 * j + 2 * i + 1]));
            b = fmaxf(b, fmaxf(s[4 * j + 4 + 2 * i], s[4 * j + 4 + 2 * i + 1]));
        }
        a = fmaxf(a, b);
        a = fmaxf(a, __shfl_xor_sync(0xffffffffu, a, 1));
        mx[i] = fmaxf(a, __shfl_xor_sync(0xffffffffu, a, 2));
    }
}
template <int NJ, bool SHIFT>
__device__ __forceinline__ void exp_sum(float (&s)[4 * NJ], const float (&m)[2], float& l0, float& l1) {
#pragma unroll
    for (int j = 0; j < NJ; j++) {
#pragma unroll
        for (int e = 0; e < 4; e++) s[4 * j + e] = ex2(SHIFT ? s[4 * j + e] - m[e >> 1] : s[4 * j + e]);
        l0 += s[4 * j + 0] + s[4 * j + 1]; l1 += s[4 * j + 2] + s[4 * j + 3];
    }
}
__device__ __forceinline__ void recompute_scores(float (&s)[64], const uint32_t (&q)[32], uint32_t kaddr, const Ctx& c) {
    const int r = c.lane & 7, mat = c.lane >> 3;
    const uint32_t a0 = kaddr + (8 * (mat & 1) + r) * 128 + (((mat >> 1) ^ r) << 4);
#pragma unroll
    for (int i = 0; i < 64; i++) s[i] = 0.f;
#pragma unroll
    for (int jp = 0; jp < 8; jp++) {
#pragma unroll
        for (int k = 0; k < 8; k++) {
            asm volatile(
                "{\n.reg .b32 b0, b1, b2, b3;\n"
                "ldmatrix.sync.aligned.m8n8.x4.trans.shared.b16 {b0,b1,b2,b3}, [%12];\n"
                "mma.sync.aligned.m16n8k16.row.col.f32.bf16.bf16.f32 {%0,%1,%2,%3}, {%8,%9,%10,%11}, {b0,b1}, {%0,%1,%2,%3};\n"
                "mma.sync.aligned.m16n8k16.row.col.f32.bf16.bf16.f32 {%4,%5,%6,%7}, {%8,%9,%10,%11}, {b2,b3}, {%4,%5,%6,%7};\n}\n"
                : "+f"(s[8 * jp]), "+f"(s[8 * jp + 1]), "+f"(s[8 * jp + 2]), "+f"(s[8 * jp + 3]),
                  "+f"(s[8 * jp + 4]), "+f"(s[8 * jp + 5]), "+f"(s[8 * jp + 6]), "+f"(s[8 * jp + 7])
                : "r"(q[4 * k]), "r"(q[4 * k + 1]), "r"(q[4 * k + 2]), "r"(q[4 * k + 3]),
                  "r"((a0 ^ ((jp & 3) << 5)) + (jp >> 2) * 16384 + k * 2048) : "memory");
        }
    }
}
__device__ __forceinline__ int mask_lim(const Ctx& c) { return perm32(16 * c.warp + (c.lane >> 2)) - 8 * (c.lane & 3); }
template <int J0>
__device__ __forceinline__ void mask_diag(float (&s)[4 * J0 + 32], const Ctx& c) {
    const int lim = mask_lim(c);
    if (c.warp < 2) {
#pragma unroll
        for (int x = 0; x < 16; x++) {
            if (2 * (x >> 2) + (x & 1) - (x & 2) > lim) s[4 * J0 + x] = -INFINITY;
            s[4 * J0 + 16 + x] = -INFINITY;
        }
    } else {
#pragma unroll
        for (int x = 0; x < 16; x++)
            if (32 + 2 * (x >> 2) + (x & 1) - (x & 2) > lim) s[4 * J0 + 16 + x] = -INFINITY;
    }
}
__device__ __forceinline__ void mask_any(float (&s)[64], int hh, const Ctx& c) {
    const int lim = mask_lim(c) + 64 * hh;
#pragma unroll
    for (int x = 0; x < 64; x++)
        if (32 * (x >> 4) + 2 * ((x >> 2) & 3) + (x & 1) - (x & 2) > lim) s[x] = -INFINITY;
}
__device__ __forceinline__ void issue_pv(float (&o)[64], const uint32_t (&p)[32], uint32_t vaddr, int acc, int mode  ) {
    uint64_t d = mkdesc(vaddr, 16, 1024, 1);
    if (mode == 0) {
        wg_fence();
#pragma unroll
        for (int k = 0; k < 8; k++)
            wgmma_rs_n128_ta0_tb0(o, p[4 * k], p[4 * k + 1], p[4 * k + 2], p[4 * k + 3], d + (k >> 2) * 1024 + 2 * (k & 3), k ? 1 : acc);
        wg_commit();
    } else if (mode == 1) {
        wg_fence();
#pragma unroll
        for (int k = 0; k < 4; k++) wgmma_rs_n128_ta0_tb0(o, p[4 * k], p[4 * k + 1], p[4 * k + 2], p[4 * k + 3], d + 2 * k, k != 0);
        wg_commit();
    } else {
        wg_fence();
        wgmma_rs_n128_ta0_tb0(o, p[0], p[1], p[2], p[3], d, acc);
        wg_commit();
    }
}
__device__ __forceinline__ void issue_qk(float (&s)[64], const uint32_t (&q)[32], uint32_t kaddr) {
    uint64_t d = mkdesc(kaddr, 16384, 1024, 1);
    wg_fence();
#pragma unroll
    for (int k = 0; k < 8; k++) wgmma_rs_n128_ta0_tb1(s, q[4 * k], q[4 * k + 1], q[4 * k + 2], q[4 * k + 3], d + 128 * k, k != 0);
    wg_commit();
}
__device__ __forceinline__ void issue_qk_half(float (&s32)[32], const uint32_t (&q)[32], uint32_t kaddr) {
    uint64_t d = mkdesc(kaddr, 16384, 1024, 1);
    wg_fence();
#pragma unroll
    for (int k = 0; k < 8; k++) wgmma_rs_n64_ta0_tb1(s32, q[4 * k], q[4 * k + 1], q[4 * k + 2], q[4 * k + 3], d + 128 * k, k != 0);
    wg_commit();
}
__device__ __forceinline__ void row_inv(const float (&l)[2], float (&inv)[2]) {
#pragma unroll
    for (int i = 0; i < 2; i++) {
        float sum = l[i];
        sum += __shfl_xor_sync(0xffffffffu, sum, 1);
        sum += __shfl_xor_sync(0xffffffffu, sum, 2);
        inv[i] = rcp_fast(sum);
    }
}

__device__ __forceinline__ const unsigned char* xn_addr(int row, int col) {
    row = perm32(row);
    return g_xn + ((row >> 7) * 10 + (col >> 6)) * 16384 + (row & 127) * 128 + ((((col & 63) >> 3) ^ (row & 7)) << 4);
}
__device__ __forceinline__ void mma16816(float (&d)[4], uint32_t a0, uint32_t a1, uint32_t a2, uint32_t a3, uint32_t b0, uint32_t b1) {
    asm volatile("mma.sync.aligned.m16n8k16.row.col.f32.bf16.bf16.f32 {%0,%1,%2,%3}, {%4,%5,%6,%7}, {%8,%9}, {%0,%1,%2,%3};"
                 : "+f"(d[0]), "+f"(d[1]), "+f"(d[2]), "+f"(d[3]) : "r"(a0), "r"(a1), "r"(a2), "r"(a3), "r"(b0), "r"(b1));
}
__device__ __forceinline__ uint32_t lds32(uint32_t addr) { uint32_t v; asm volatile("ld.shared.u32 %0, [%1];" : "=r"(v) : "r"(addr)); return v; }

__device__ __forceinline__ void ln_rows(const Params& P, int row0, int lane, uint32_t wr_s) {
    const int hl = lane & 15, row = row0 + (lane >> 4);
    uint32_t v[20];
#pragma unroll
    for (int i = 0; i < 5; i++) {
        uint4 u;
        asm("ld.global.nc.L2::cache_hint.v4.b32 {%0,%1,%2,%3}, [%4], %5;" : "=r"(u.x), "=r"(u.y), "=r"(u.z), "=r"(u.w)
            : "l"(P.x + (size_t)row * DM + 128 * i + 8 * hl), "l"(policy(HM & 512)));
        v[4 * i] = u.x; v[4 * i + 1] = u.y; v[4 * i + 2] = u.z; v[4 * i + 3] = u.w;
    }
    float mean = 0.f, m2 = 0.f, acc2 = 0.f;
#pragma unroll
    for (int i = 0; i < 20; i++) { mean += bf_lo(v[i]); acc2 += bf_hi(v[i]); }
    mean = (mean + acc2) * (1.0f / 40);
    acc2 = 0.f;
#pragma unroll
    for (int i = 0; i < 20; i++) {
        float d0 = __uint_as_float(__byte_perm(v[i], 0, 0x1044)) - mean, d1 = __uint_as_float(__byte_perm(v[i], 0, 0x3244)) - mean;
        m2 = fmaf(d0, d0, m2); acc2 = fmaf(d1, d1, acc2);
    }
    m2 += acc2;
    acc2 = 0.f;
#pragma unroll
    for (int o = 1; o < 16; o <<= 1) {
        float mo = __shfl_xor_sync(0xffffffffu, mean, o), qo = __shfl_xor_sync(0xffffffffu, m2, o), d = mo - mean;
        m2 = fmaf(d * d, 20.0f * o, m2 + qo);
        mean = 0.5f * (mean + mo);
    }
    const uint32_t mb2 = pack_bf16(mean, mean);
    const float inv = rcp_fast(bf_round(sqrt_fast(bf_round(bf_round(m2 * (1.0f / DM)) + 1e-5f))));
    float dot = 0.f;
    unsigned char* xp = const_cast<unsigned char*>(xn_addr(row, 8 * hl));
#pragma unroll
    for (int i = 0; i < 5; i++) {
        uint32_t ww[4];
        asm volatile("ld.shared.v4.b32 {%0,%1,%2,%3}, [%4];" : "=r"(ww[0]), "=r"(ww[1]), "=r"(ww[2]), "=r"(ww[3]) : "r"(wr_s + 256 * i + 16 * hl) : "memory");
#pragma unroll
        for (int e = 0; e < 4; e++) {
            uint32_t d;
            asm("sub.rn.bf16x2 %0, %1, %2;" : "=r"(d) : "r"(v[4 * i + e]), "r"(mb2));
            d = pack_bf16(bf_lo(d) * inv, bf_hi(d) * inv);
            v[4 * i + e] = d;
            dot = fmaf(bf_lo(d), bf_lo(ww[e]), dot);
            acc2 = fmaf(bf_hi(d), bf_hi(ww[e]), acc2);
        }
        stg128(xp + i * 32768, v[4 * i], v[4 * i + 1], v[4 * i + 2], v[4 * i + 3]);
    }
    dot += acc2;
#pragma unroll
    for (int o = 8; o > 0; o >>= 1) dot += __shfl_xor_sync(0xffffffffu, dot, o);
    if (hl == 0) { g_router[row] = bf_round(dot); g_stats[row] = make_uint2(mb2, __float_as_uint(inv)); }
}

__device__ __forceinline__ void aux_cta(const Params& P, const CUtensorMap* tmG, const CUtensorMap* tmU, const CUtensorMap* tmD, unsigned char* sm, int a) {
    constexpr int STG = 57344, XS = 3 * STG, HS = XS + 8 * 1296, KEY = HS + 8 * 912, MI = KEY + 8192;
    const int tid = threadIdx.x, warp = __shfl_sync(0xffffffffu, tid >> 5, 0), lane = tid & 31;
    const uint32_t sb = smem_u32(sm);
    const uint32_t full = sb + MI, empty = sb + MI + 32;
    int* s_sel = reinterpret_cast<int*>(sm + MI + 64);
    float* s_r = reinterpret_cast<float*>(sm + MI + 96);
    volatile unsigned* s_misc = reinterpret_cast<volatile unsigned*>(sm + MI + 128);
    uint32_t* s_key = reinterpret_cast<uint32_t*>(sm + KEY);
    PROF_DECL(128 + a)
    PROF_GT(0);
    if (tid == 0) {
        for (int i = 0; i < 3; i++) { mbar_init(full + 8 * i, 1); mbar_init(empty + 8 * i, 10); }
        asm volatile("fence.mbarrier_init.release.cluster;" ::: "memory");
    }
    __syncthreads();
    if (warp == 11) {
        if (elect_one()) {
            int st = 0; uint32_t ph = 0;
#pragma unroll 1
            for (int s = 0; s < 34; s++) {
                mbar_wait(empty + 8 * st, ph ^ 1);
                const uint32_t dst = sb + st * STG, fb = full + 8 * st;
                if (s < 20) {
                    mbar_expect_tx(fb, 57344);
                    tma3d(dst, tmG, 0, 32 * s, 7 * a, fb);
                    tma3d(dst + 28672, tmU, 0, 32 * s, 7 * a, fb);
                } else {
                    mbar_expect_tx(fb, 40960);
                    tma3d(dst, tmD, 0, 448 * a + 32 * (s - 20), 0, fb);
                }
                if (s >= 3) {
#pragma unroll 1
                    for (int f = (s == 3 ? 4 : s + 6); f <= s + 6 && f < 34; f++) {
                        if (f < 20) { tma3d_prefetch(tmG, 0, 32 * f, 7 * a); tma3d_prefetch(tmU, 0, 32 * f, 7 * a); }
                        else tma3d_prefetch(tmD, 0, 448 * a + 32 * (f - 20), 0);
                    }
                }
                if (++st == 3) { st = 0; ph ^= 1; }
            }
        }
        return;
    }
    if (tid < 80) *reinterpret_cast<uint4*>(sm + KEY + 1024 + tid * 16) = __ldg(reinterpret_cast<const uint4*>(P.wr) + tid);
    __nanosleep(AUXDELAY);
#pragma unroll 1
    for (int i = tid; i < 64 * 40; i += 352) asm volatile("prefetch.global.L2 [%0];" ::"l"(P.x + (size_t)((4 + a) * 256 + 192) * DM + i * 16));
    bar_sync(2, 352);
#pragma unroll 1
    for (int i = warp; i < 32; i += 11) ln_rows(P, (4 + a) * 256 + 192 + 2 * i, lane, sb + KEY + 1024);
    bar_sync(2, 352);
    if (tid == 320) flag_signal(flag_ptr(FL_LN + 4 + a));
    PROF_GT(49);
    if (warp == 10) return;
    if (tid < 8) {
        unsigned e = *reinterpret_cast<volatile unsigned*>(&g_epoch);
        if (tid == 0) s_misc[0] = e;
        flag_wait(flag_ptr(FL_LN + tid), (e + 1) * (32u + (tid >> 2)));
    }
    bar_sync(1, 320);
    PROF_GT(50);
    const unsigned ep = s_misc[0];
    auto top8 = [&](uint32_t (&key)[8]) {
        uint32_t mine = 0;
#pragma unroll 1
        for (int r = 0; r < TOPC; r++) {
            uint32_t best = 0;
#pragma unroll
            for (int i = 0; i < 8; i++) best = max(best, key[i]);
            best = __reduce_max_sync(0xffffffffu, best);
#pragma unroll
            for (int i = 0; i < 8; i++) if (key[i] == best) key[i] = 0;
            if (lane == r) mine = best;
        }
        return mine;
    };
#pragma unroll 1
    for (int pass = 0; pass < 2; pass++) {
        if (warp < (pass ? 1 : 8)) {
            uint32_t key[8];
#pragma unroll
            for (int i = 0; i < 8; i++) {
                if (pass == 0) {
                    int idx = warp * 256 + i * 32 + lane;
                    uint32_t b = __float_as_uint(__ldcg(g_router + idx)) >> 16;
                    b = (b & 0x8000u) ? (~b & 0xffffu) : (b | 0x8000u);
                    key[i] = (b << 16) | (uint32_t)(0xffff - idx);
                } else key[i] = i < 2 ? s_key[i * 32 + lane] : 0u;
            }
            uint32_t best = top8(key);
            if (lane < TOPC) {
                if (pass == 0) s_key[warp * 8 + lane] = best;
                else {
                    uint32_t b = best >> 16;
                    b = (b & 0x8000u) ? (b & 0x7fffu) : (~b & 0xffffu);
                    s_sel[lane] = 0xffff - (int)(best & 0xffffu);
                    s_r[lane] = __uint_as_float(b << 16);
                }
            }
        }
        bar_sync(1, 320);
    }
#pragma unroll
    for (int it = 0; it < 2; it++) {
        int i = tid + it * 320, tk = i / 80, ch = i % 80;
        *reinterpret_cast<uint4*>(sm + XS + tk * 1296 + ch * 16) = __ldcg(reinterpret_cast<const uint4*>(xn_addr(s_sel[tk], ch * 8)));
    }
    bar_sync(1, 320);
    PROF_GT(51);
    const int g = lane >> 2, t = lane & 3;
    const uint32_t woff = warp * 4096 + (8 * (lane >> 4) + (lane & 7)) * 128 + ((((lane >> 3) & 1) ^ (lane & 7)) << 4);
    int st = 0; uint32_t ph = 0;
    float ga[4][4], ua[4][4];
#pragma unroll
    for (int i = 0; i < 4; i++)
#pragma unroll
        for (int e = 0; e < 4; e++) { ga[i][e] = 0.f; ua[i][e] = 0.f; }
#pragma unroll 1
    for (int s = 0; s < 34; s++) {
        if (s == 20) {
            if (warp < 7) {
#pragma unroll
                for (int i = 0; i < 4; i++)
#pragma unroll
                    for (int e = 0; e < 4; e++) {
                        float gv = bf_round(ga[i][e]), uv = bf_round(ua[i][e]);
                        float sg = bf_round(__fdividef(gv, 1.0f + __expf(fminf(-gv, 80.f))));
                        int f = warp * 64 + i * 16 + g + 8 * (e >> 1), tk = 2 * t + (e & 1);
                        *reinterpret_cast<__nv_bfloat16*>(sm + HS + tk * 912 + f * 2) = __float2bfloat16_rn(sg * uv);
                        ga[i][e] = 0.f;
                    }
            }
            bar_sync(1, 320);
            PROF_GT(52);
        }
        mbar_wait(full + 8 * st, ph);
        if (s >= 20 || warp < 7) {
#pragma unroll
            for (int kk = 0; kk < 2; kk++) {
                uint32_t xb = sb + (s < 20 ? XS + g * 1296 + s * 64 : HS + g * 912 + (s - 20) * 64) + 32 * kk + 4 * t;
                uint32_t b0 = lds32(xb), b1 = lds32(xb + 16);
                uint32_t wa = sb + st * STG + woff + kk * 2048;
#pragma unroll
                for (int i = 0; i < 4; i++) {
                    uint32_t a0, a1, a2, a3;
                    ldsm4t(a0, a1, a2, a3, wa ^ (i << 5));
                    mma16816(ga[i], a0, a1, a2, a3, b0, b1);
                    if (s < 20) {
                        ldsm4t(a0, a1, a2, a3, (wa ^ (i << 5)) + 28672);
                        mma16816(ua[i], a0, a1, a2, a3, b0, b1);
                    }
                }
            }
        }
        asm volatile("fence.proxy.async.shared::cta;" ::: "memory");
        __syncwarp();
        if (lane == 0) mbar_arrive(empty + 8 * st);
        if (++st == 3) { st = 0; ph ^= 1; }
    }
#pragma unroll
    for (int i = 0; i < 4; i++)
#pragma unroll
        for (int e = 0; e < 4; e += 2)
            *reinterpret_cast<float2*>(g_moe_part + (a * DM + warp * 64 + i * 16 + g + 4 * e) * 8 + 2 * t) = make_float2(ga[i][e], ga[i][e + 1]);
    bar_sync(1, 320);
    if (tid == 0) {
        __threadfence();
        unsigned old = atomicAdd(flag_ptr(FL_MOE_CNT), 1u);
        s_misc[1] = (old == ep * 4u + 3u);
        __threadfence();
    }
    bar_sync(1, 320);
    PROF_GT(53);
    if (s_misc[1]) {
        const float4* pp = reinterpret_cast<const float4*>(g_moe_part);
#pragma unroll 2
        for (int i = tid; i < DM * 2; i += 320) {
            float4 v0 = __ldcg(pp + i), v1 = __ldcg(pp + DM * 2 + i), v2 = __ldcg(pp + DM * 4 + i), v3 = __ldcg(pp + DM * 6 + i);
            float y[4] = {v0.x + v1.x + v2.x + v3.x, v0.y + v1.y + v2.y + v3.y, v0.z + v1.z + v2.z + v3.z, v0.w + v1.w + v2.w + v3.w};
#pragma unroll
            for (int e = 0; e < 4; e++) {
                int col = i >> 1, tk = (i & 1) * 4 + e;
                float sg = bf_round(__fdividef(1.0f, 1.0f + __expf(fminf(-s_r[tk], 80.f))));
                float upd = bf_round(bf_round(y[e]) * sg);
                float xn = __bfloat162float(*reinterpret_cast<const __nv_bfloat16*>(sm + XS + tk * 1296 + col * 2));
                g_brow[tk * DM + col] = __float2bfloat16_rn(xn + upd);
            }
        }
        if (tid < TOPC) g_sel[tid] = s_sel[tid];
        bar_sync(1, 320);
        if (tid == 0) {
            flag_signal(flag_ptr(FL_MOE_DONE));
            *reinterpret_cast<volatile unsigned*>(&g_epoch) = ep + 1;
        }
        PROF_GT(54);
    }
}

__global__ void __cluster_dims__(2, 1, 1) __launch_bounds__(384, 1)
fused_kernel(const __grid_constant__ CUtensorMap tmC, const __grid_constant__ CUtensorMap tmWk, const __grid_constant__ CUtensorMap tmWv,
             const __grid_constant__ CUtensorMap tmWq, const __grid_constant__ CUtensorMap tmWo,
             const __grid_constant__ CUtensorMap tmG, const __grid_constant__ CUtensorMap tmU, const __grid_constant__ CUtensorMap tmD, const Params P) {
    extern __shared__ __align__(1024) unsigned char smem_raw[];
    const uint32_t ring = smem_u32(smem_raw);
    const uint32_t misc = ring + RING_BYTES;
    const int tid = threadIdx.x;
    const int rank = blockIdx.x & 1;
    uint32_t smid, nsm;
    asm("mov.u32 %0, %%smid;" : "=r"(smid));
    asm("mov.u32 %0, %%nsmid;" : "=r"(nsm));
    if (nsm != 132) smid = blockIdx.x;
    auto role_of = [](int tpc) {
        return tpc < 32 ? (tpc & 7) * 8 + (tpc >> 3) : tpc < 60 ? (1 + (tpc - 32) % 7) * 8 + 4 + (tpc - 32) / 7 : tpc < 64 ? tpc - 56 : tpc;
    };
    int mc = role_of(smid >> 1);
    PROF_DECL(mc * 2 + rank)
    PROF_GT(0); PROF_EV(1);

    auto prefetch_w = [&](int ch) {
        const int i = tid - 128;
        asm volatile("prefetch.global.L2 [%0];" ::"l"((rank ? P.wv : P.wk) + (size_t)(ch * 128 + (mc & 3) * 32 + (i >> 3)) * 4096 + (mc >> 2) * 256 + (i & 7) * 16));
    };
    if (tid >= 128 && mc < 64) {
        if (tid < 256) asm volatile("prefetch.global.L2 [%0];" ::"l"(P.c + (size_t)((12 + (mc & 3)) * 128 + ((mc >> 2) * 2 + rank) * 4) * DC + (tid - 128) * 16));
        prefetch_w(0);
    }
    auto load_w0 = [&]() {
        const CUtensorMap* tw = rank ? &tmWv : &tmWk;
        mbar_expect_tx(misc + BAR_FULL + 8 * slot_of(0), SLOT_BYTES);
        tma2d(ring + slot_of(0) * SLOT_BYTES, tw, (mc >> 2) * 256, 0, misc + BAR_FULL + 8 * slot_of(0), policy(HM & 1));
        tma2d(ring + slot_of(0) * SLOT_BYTES + 16384, tw, (mc >> 2) * 256 + 64, 0, misc + BAR_FULL + 8 * slot_of(0), policy(HM & 1));
    };
    if (tid == 0) {
#pragma unroll
        for (int i = 0; i < NSLOT; i++) mbar_init(misc + BAR_FULL + 8 * i, 1);
#pragma unroll
        for (int i = 0; i < E0; i++) mbar_arrive(misc + BAR_FULL + 8 * i);
        asm volatile("fence.mbarrier_init.release.cluster;" ::: "memory");
        if (mc < 64) load_w0();
    }
    if (tid == 160) {
        asm volatile("st.shared.u32 [%0], %1;" ::"r"(misc + MISC_SMID), "r"(smid) : "memory");
        asm volatile("fence.release.sync_restrict::shared::cta.cluster;" ::: "memory");
    }
    if (tid == 32) {
        asm volatile("prefetch.tensormap [%0];" ::"l"(&tmC) : "memory");
#pragma unroll
        for (int i = 0; i < NSLOT; i++) mbar_init(misc + BAR_EMPTY + 8 * i, 16);
#pragma unroll
        for (int i = 0; i < E0; i++) mbar_arrive_cluster(misc + BAR_EMPTY + 8 * i, 16);
        asm volatile("fence.mbarrier_init.release.cluster;" ::: "memory");
    }
    if (tid == 64) {
#pragma unroll
        for (int i = 0; i < NST3; i++) { mbar_init(misc + BAR_FULL3 + 8 * i, 1); mbar_init(misc + BAR_EMPTY3 + 8 * i, 16); }
#pragma unroll
        for (int i = 0; i < 4; i++) mbar_init(misc + BAR_LN + 8 * i, 2);
        mbar_init(misc + BAR_PROG, 1); mbar_init(misc + BAR_PROG + 8, 1); mbar_init(misc + BAR_PROG + 16, 1);
        asm volatile("fence.mbarrier_init.release.cluster;" ::: "memory");
    }
    if (tid == 96) {
#pragma unroll
        for (int i = 0; i < 34; i++) mbar_init(misc + BAR_DEP + 8 * i, 1);
    }
    if (tid == 128) {
#pragma unroll
        for (int i = 0; i < 32; i++) mbar_init(misc + BAR_EV + 8 * i, 4);
    }
    __syncthreads();
    asm volatile("barrier.cluster.arrive.relaxed.aligned;\nbarrier.cluster.wait.aligned;" ::: "memory");
    {
        uint32_t peer;
        asm volatile("ld.shared::cluster.u32 %0, [%1];" : "=r"(peer) : "r"(mapa(misc + MISC_SMID, rank ^ 1)) : "memory");
        if ((__shfl_sync(0xffffffffu, peer, 0) ^ smid) != 1) {
            if (tid == 0) {
                const unsigned ep1 = *reinterpret_cast<volatile unsigned*>(&g_epoch) + 1;
                if ((smid & 1) == 0) atomicExch(g_roleq + 2 + (atomicAdd(g_roleq, 1u) & 127), (ep1 << 8) | (smid >> 1));
                if (rank == 0) {
                    unsigned* slot = g_roleq + 2 + (atomicAdd(g_roleq + 1, 1u) & 127);
                    unsigned v = 0;
                    for (int spin = 0; spin < 4000000 && ((v = atomicAdd(slot, 0u)) >> 8) != (ep1 & 0xffffffu); spin++) {}
                    asm volatile("st.shared::cluster.u32 [%0], %1;" ::"r"(mapa(misc + MISC_SMID + 4, 0)), "r"(v & 255) : "memory");
                    asm volatile("st.shared::cluster.u32 [%0], %1;" ::"r"(mapa(misc + MISC_SMID + 4, 1)), "r"(v & 255) : "memory");
                }
                if (mc < 64) {
                    mbar_wait(misc + BAR_FULL + 8 * slot_of(0), 0);
                    asm volatile("mbarrier.inval.shared::cta.b64 [%0];" ::"r"(misc + BAR_FULL + 8 * slot_of(0)) : "memory");
                    mbar_init(misc + BAR_FULL + 8 * slot_of(0), 1);
                    asm volatile("fence.mbarrier_init.release.cluster;" ::: "memory");
                }
            }
            __syncwarp();
            asm volatile("barrier.cluster.arrive.aligned;\nbarrier.cluster.wait.aligned;" ::: "memory");
            mc = role_of(__shfl_sync(0xffffffffu, lds32(misc + MISC_SMID + 4), 0));
            if (tid == 0 && mc < 64) load_w0();
            __syncwarp();
        }
    }
    const int cta = mc * 2 + rank;
    if (mc >= 64) { aux_cta(P, &tmG, &tmU, &tmD, smem_raw, cta - 128); return; }
    const int team = mc >> 2, k = mc & 3;
    const int u3 = (mc >> 4) * 2 + (team & 1), s3 = k, kap = (mc >> 3) & 1;
    const int partner = cta ^ 16;
    if (tid >= 128) prefetch_w(1);
    if (tid == 256) {
        const CUtensorMap* tw = rank ? &tmWv : &tmWk;
#pragma unroll
        for (int e = 1; e < NSLOT; e++) {
            const uint32_t fb = misc + BAR_FULL + 8 * slot_of(e), dst = ring + slot_of(e) * SLOT_BYTES;
            mbar_expect_tx(fb, SLOT_BYTES);
            if (e & 1) tma2d_mc(dst + rank * 16384, &tmC, (e >> 1) * 128 + rank * 64, (12 + k) * 128, fb, policy(false));
            else { tma2d(dst, tw, team * 256, e * 64, fb, policy(false)); tma2d(dst + 16384, tw, team * 256 + 64, e * 64, fb, policy(false)); }
        }
    }
    PROF_EV(5);
    const int wg = __shfl_sync(0xffffffffu, tid >> 7, 0);

    if (wg == 0) {
        asm volatile("setmaxnreg.dec.sync.aligned.u32 40;");
        const int warp = __shfl_sync(0xffffffffu, tid >> 5, 0), lane = tid & 31;
        if (warp == 0) {
            const bool lead = elect_one();
            Cur c = cur_at(NSLOT);
            uint32_t dst, fb;
            auto acquire = [&]() {
                mbar_wait(misc + BAR_EMPTY + 8 * c.slot, c.ph ^ 1);
                fb = misc + BAR_FULL + 8 * c.slot; dst = ring + c.slot * SLOT_BYTES;
                if (lead) mbar_expect_tx(fb, SLOT_BYTES);
                c.adv();
            };
            auto load_w = [&](const CUtensorMap* tm, int col, int row, bool stream) {
                acquire();
                if (lead) { tma2d(dst, tm, col, row, fb, policy(stream)); tma2d(dst + 16384, tm, col + 64, row, fb, policy(stream)); }
            };
            auto load_half = [&](const unsigned char* src, bool stream) {
                acquire();
                if (lead) bulk_load_mc(dst + rank * 16384, src, 16384, fb, policy(stream));
            };
            auto dep_wait = [&](int d) { mbar_wait(misc + BAR_DEP + 8 * d, 0); fence_async_global(); };
            auto op_prefetch = [&](int i) {
                const int head = op_head(i, kap);
                l2_prefetch(reinterpret_cast<const unsigned char*>(P.wo) + head * 163840 + (u3 * 8 + s3 * 2 + rank) * 2560, 2560);
                if (i < 8) l2_prefetch(g_ctx + (size_t)(head * 32 + 4 * u3 + 2 * rank) * 16384 + s3 * 8192, 8192);
            };
            __nanosleep(CDELAY);
            if (lead) l2_prefetch(reinterpret_cast<const unsigned char*>(P.c) + (size_t)cta * 12288, 12288);
            const CUtensorMap* tw = rank ? &tmWv : &tmWk;
            const unsigned char* Kh = g_K + (size_t)team * 32 * 16384 + rank * 16384;
            const unsigned char* Vh = g_V + (size_t)team * 32 * 16384 + rank * 16384;
#pragma unroll 1
            for (int v = 0; v < 2; v++) {
                const int h = 2 * team + v;
#pragma unroll 1
                for (int i = v ? 0 : 3; i < 16; i++) {
                    if (i < 4 && v) load_w(tw, h * 128, i * 128, HM & 1);
                    if (v && i == 3 && lead) mbar_arrive(misc + BAR_PROG + 8);
                    if (v && (i & 7) == 3) dep_wait(D_WAR + (i >> 3));
                    acquire();
                    if (lead) tma2d_mc(dst + rank * 16384, &tmC, (i & 3) * 128 + rank * 64, (12 - (i & 12) + k) * 128, fb, policy(HM & 2));
                    if (i == 8 && lead) {
                        tma2d_prefetch(&tmWq, h * 128 + rank * 64, k * 64); tma2d_prefetch(&tmWq, h * 128 + rank * 64, k * 64 + 256);
                        if (k < 2) tma2d_prefetch(&tmWq, h * 128 + rank * 64, k * 64 + 512);
                        if (v) l2_prefetch(g_xn + 8 * 163840 + cta * 10240, 10240);
                    }
                }
                int togo = v ? PF_START : 11;
#pragma unroll 1
                for (int r = 0; r < 2; r++) {
                    const int p = r ? k : 7 - k, n = 2 * p + 1;
                    if (v == 0) dep_wait(D_LN + r);
                    const int g0 = r ? rank ^ SWAPT : 3 - rank, g1 = 3 - g0;
                    const unsigned char* x0 = g_xn + (2 * p + (g0 >> 1)) * 163840 + (g0 & 1) * 8192;
                    const unsigned char* x1 = g_xn + (2 * p + (g1 >> 1)) * 163840 + (g1 & 1) * 8192;
#pragma unroll 1
                    for (int kc = 0; kc < 10; kc++) {
                        acquire();
                        if (lead) {
                            tma2d_mc(dst + 16384 + rank * 8192, &tmWq, h * 128 + rank * 64, kc * 64, fb, policy(false));
                            bulk_load(dst, x0 + kc * 16384, 8192, fb, policy(false));
                            bulk_load(dst + 8192, x1 + kc * 16384, 8192, fb, policy(false));
                        }
                    }
                    if (r == 0) dep_wait(D_KV + 3 * v);
                    load_half(Kh + n * 32768, HM & 16);
#pragma unroll 1
                    for (int j = n - 1; j >= 0; j--) {
                        if (r == 0 && (j == 7 || j == 3)) dep_wait(D_KV + 3 * v + 2 - (j >> 2));
                        load_half(Kh + j * 32768, HM & 16); load_half(Vh + (j + 1) * 32768, HM & 16);
                        if (v == 0 && r == 0 && j == 3 && lead) mbar_arrive(misc + BAR_PROG);
                        --togo;
                        if (v == 0 && togo == 0 && lead) {
                            tma2d_prefetch(tw, h * 128 + 128, k * 128); tma2d_prefetch(tw, h * 128 + 192, k * 128);
                            l2_prefetch(reinterpret_cast<const unsigned char*>(P.c) + (size_t)cta * 16384, 16384);
                        }
                        if (v && togo <= 0 && togo > -OP_PF && lead) op_prefetch(-togo);
                    }
                    load_half(Vh, HM & 16);
                }
            }
            mbar_wait(misc + BAR_EMPTY + 8 * c.slot, c.ph ^ 1); c.adv();
            int st = 0; uint32_t ph3 = 0;
#pragma unroll 1
            for (int i = 0; i < 32; i++) {
                const int head = op_head(i >> 1, kap);
                if ((i & 1) == 0) dep_wait(D_CTX + (i >> 1));
                if (i < NST3) { mbar_wait(misc + BAR_EMPTY + 8 * c.slot, c.ph ^ 1); c.adv(); }
                else mbar_wait(misc + BAR_EMPTY3 + 8 * st, ph3 ^ 1);
                fb = misc + BAR_FULL3 + 8 * st; dst = ring + st * ST3_BYTES;
                if (i == LATE_AT && lead) mbar_arrive(misc + BAR_PROG + 16);
                if (lead) {
                    mbar_expect_tx(fb, ST3_BYTES);
                    const unsigned char* src = g_ctx + (size_t)(head * 32 + 4 * u3 + 2 * rank) * 16384 + (i & 1) * 8192;
                    bulk_load(dst, src, 8192, fb, policy(HM & 32));
                    bulk_load(dst + 8192, src + 16384, 8192, fb, policy(HM & 32));
                    tma3d_mc(dst + 16384 + rank * 10240, &tmWo, 0, head * 128 + (i & 1) * 64 + rank * 32, 5 * s3, fb, policy(HM & 32));
                    if ((i & 1) && (i >> 1) + OP_PF < 16) op_prefetch((i >> 1) + OP_PF);
                }
                if (++st == NST3) { st = 0; ph3 ^= 1; }
            }
        } else {
        if (lane < 27 && (warp - 1) * 27 + lane < 80) {
            const int ch = (warp - 1) * 27 + lane;
            uint4 u = __ldg(reinterpret_cast<const uint4*>(P.wr) + ch);
            asm volatile("st.shared.v4.b32 [%0], {%1,%2,%3,%4};" ::"r"(misc + MISC_WR + 16 * ch), "r"(u.x), "r"(u.y), "r"(u.z), "r"(u.w) : "memory");
        }
        bar_sync(3, 96);
#pragma unroll 1
        for (int t = 0; t < (warp == 3 ? 1 : 3); t++) {
            const int row2 = (cta >> 5) * 256 + (cta & 31) * 8 + (warp - 1) * 4;
            if (t < 2 && warp < 3) {
#pragma unroll
                for (int i = 0; i < 3; i++)
                    if (i * 32 + lane < 80) asm volatile("prefetch.global.L2 [%0];" ::"l"(P.x + (size_t)(row2 + 2 * t) * DM + (i * 32 + lane) * 16));
            }
            ln_rows(P, t ? row2 + 2 * t - 2 : (4 + (cta >> 5)) * 256 + (cta & 31) * 6 + (warp - 1) * 2, lane, misc + MISC_WR);
            __syncwarp();
            if (lane == 0 && warp < 3 && t != 1) mbar_arrive(misc + BAR_LN + 4 * t);
        }
        if (warp == 3) {
            const unsigned ep1 = *reinterpret_cast<volatile unsigned*>(&g_epoch) + 1;
            if (lane == 0) {
                asm volatile("st.shared.u32 [%0], %1;" ::"r"(misc + MISC_EPOCH), "r"(ep1) : "memory");
                mbar_wait(misc + BAR_LN, 0);
                flag_signal(flag_ptr(FL_LN + 4 + (cta >> 5)));
                flag_wait(flag_ptr(FL_LN + 7 - k), ep1 * 33u);
                mbar_arrive(misc + BAR_DEP + 8 * D_LN);
#pragma unroll 1
                for (int v = 0; v < 2; v++) {
#pragma unroll 1
                    for (int i = 3 * v; i < 3 * v + 3; i++) {
                        mbar_wait(misc + BAR_EV + 8 * (16 + EV_KV + i), 0);
                        if (v == 0) {
                            mbar_wait(misc + BAR_EV + 8 * (EV_KV + i), 0);
                            asm volatile("red.release.gpu.global.add.u32 [%0], 2;" ::"l"(flag_ptr(FL_KV + team * 8 + i)) : "memory");
                        }
                        flag_wait(flag_ptr(FL_KV + team * 8 + i), ep1 * 16u);
                        mbar_arrive(misc + BAR_DEP + 8 * (D_KV + i));
                    }
                    if (v) break;
                    mbar_wait(misc + BAR_LN + 8, 0);
                    flag_signal(flag_ptr(FL_LN + (cta >> 5)));
                    flag_wait(flag_ptr(FL_LN + k), ep1 * 32u);
                    mbar_arrive(misc + BAR_DEP + 8 * (D_LN + 1));
#pragma unroll 1
                    for (int i = 0; i < 2; i++) {
                        mbar_wait(misc + BAR_PROG + 8 * i, 0);
                        flag_signal(flag_ptr(FL_WAR + 2 * team + i));
                        flag_wait(flag_ptr(FL_WAR + 2 * team + i), ep1 * 8u);
                        mbar_arrive(misc + BAR_DEP + 8 * (D_WAR + i));
                    }
                }
                flag_wait(flag_ptr(FL_MOE_DONE), ep1);
                int4 s0 = __ldcg(reinterpret_cast<const int4*>(g_sel)), s1 = __ldcg(reinterpret_cast<const int4*>(g_sel) + 1);
                asm volatile("st.shared.v4.u32 [%0], {%1,%2,%3,%4};" ::"r"(misc + MISC_SEL), "r"(s0.x), "r"(s0.y), "r"(s0.z), "r"(s0.w) : "memory");
                asm volatile("st.shared.v4.u32 [%0], {%1,%2,%3,%4};" ::"r"(misc + MISC_SEL + 16), "r"(s1.x), "r"(s1.y), "r"(s1.z), "r"(s1.w) : "memory");
                mbar_arrive(misc + BAR_SEL);
            }
            __syncwarp();
            const unsigned* cf = flag_ptr(FL_CTX + op_head(lane & 15, kap) * 8 + u3);
#pragma unroll 1
            for (int half = 0; half < 2; half++) {
                if (half) mbar_wait(misc + BAR_EV + 8 * (EV_CTX + 3), 0);
                bool done = (lane >> 3) != half;
                for (int spin = 0; spin < 4000000; spin++) {
                    if (!done) {
                        unsigned v;
                        asm volatile("ld.acquire.gpu.global.u32 %0, [%1];" : "=r"(v) : "l"(cf) : "memory");
                        if ((int)(v - ep1 * 4u) >= 0) { mbar_arrive(misc + BAR_DEP + 8 * (D_CTX + lane)); done = true; }
                    }
                    if (__all_sync(0xffffffffu, done)) break;
                    __nanosleep(64);
                }
            }
        } else {
            const int w = warp - 1;
            if (lane == 0) {
                const uint32_t eb = misc + BAR_EV + w * 128;
#pragma unroll 1
                for (int i = 0; i < 7; i++) {
                    const bool kv = i >= 2 && i < 5;
                    const int ci = i < 2 ? i : i - 3;
                    mbar_wait(eb + 8 * (kv ? EV_KV + i + 1 : EV_CTX + ci), 0);
                    if (i == 1) {
                        asm volatile("cp.async.bulk.global.shared::cta.bulk_group [%0], [%1], 16384;"
                                     ::"l"(g_ctx + (size_t)(2 * team * 32 + 4 * k + (w ? 3 - (rank ^ SWAPT) : rank ^ SWAPT)) * 16384),
                                       "r"(ring + slot_of(78) * SLOT_BYTES + w * 16384) : "memory");
                        asm volatile("cp.async.bulk.commit_group;" ::: "memory");
                        asm volatile("cp.async.bulk.wait_group.read 0;" ::: "memory");
                        mbar_arrive_cluster(mapa(misc + BAR_EMPTY + 8 * slot_of(78), 0), 4);
                        mbar_arrive_cluster(mapa(misc + BAR_EMPTY + 8 * slot_of(78), 1), 4);
                        asm volatile("cp.async.bulk.wait_group 0;" ::: "memory");
                        fence_async_global();
                    }
                    flag_signal(flag_ptr(kv ? FL_KV + team * 8 + i + 1 : FL_CTX + (2 * team + (ci >> 1)) * 8 + ((ci & 1) ? k : 7 - k)));
                }
            }
            __syncwarp();
            mbar_wait(misc + BAR_PROG + 16, 0);
            const int row = (2 * u3 + rank) * 128 + 64 * w + perm32(16 * (lane >> 3) + 8 * kap + (lane & 7));
#pragma unroll
            for (int i = 0; i < 10; i++) asm volatile("prefetch.global.L2 [%0];" ::"l"(P.x + (size_t)row * DM + 160 * s3 + 16 * i));
            asm volatile("prefetch.global.L2 [%0];" ::"l"(g_stats + row));
        }
        }
    } else {
        asm volatile("setmaxnreg.inc.sync.aligned.u32 232;");
        Ctx c;
        c.ring = ring; c.misc = misc; c.w = wg - 1; c.warp = __shfl_sync(0xffffffffu, (tid >> 5) & 3, 0); c.lane = tid & 31;
        c.rel = mapa(misc, tid & 1);
        const int w = c.w;
        if (w == 1) bar_arrive(1, 256);
        prefetch_w(2); prefetch_w(3);
        Cur cur = cur_at(0);
        float o[64], inv[2];
        unsigned char* out[2];
        uint32_t wf[128];
        Cur cw = cur;
        auto load_wchunk = [&](auto CH) {
            constexpr int ch = decltype(CH)::value;
            mbar_wait_hot(misc + BAR_FULL + 8 * cw.slot, cw.ph);
            const uint32_t z = load_afrag<8, 32 * ch>(wf, ring + cw.slot * SLOT_BYTES + w * 16384, c);
            release(c, BAR_EMPTY + 8 * cw.slot + z, 1);
            cw.adv(); cw.adv();
        };
#pragma unroll
        for (int i = 32; i < 64; i++) wf[i] = 0u;
        load_wchunk(IC<0>{});
#pragma unroll 1
        for (int v = 0; v < 2; v++) {
        {
            float (&acc)[64] = o;
#pragma unroll
            for (int i = 64; i < 128; i++) wf[i] = 0u;
            cur.adv();
            inv[0] = inv[1] = rank ? 1.0f : SM_SCALE;
            PROF_EV(2); PROF_GT(60);
#pragma unroll 1
            for (int t = 0; t < 4; t++) {
                uint32_t last = 0;
                token_wait(w);
                PROF_EV(10);
                undef_regs(acc);
                auto chunk = [&](auto CH) {
                    constexpr int ch = decltype(CH)::value;
                    mbar_wait_hot(misc + BAR_FULL + 8 * cur.slot, cur.ph);
                    if (t == 0) { PROF_EV(12 + ch); }
                    uint64_t d = mkdesc(ring + cur.slot * SLOT_BYTES, 16, 1024, 1);
                    wg_fence();
#pragma unroll
                    for (int ks = 0; ks < 8; ks++)
                        wgmma_rs_n128_ta0_tb0(acc, wf[32 * ch + 4 * ks], wf[32 * ch + 4 * ks + 1], wf[32 * ch + 4 * ks + 2], wf[32 * ch + 4 * ks + 3],
                                              d + (ks >> 2) * 1024 + (ks & 3) * 2, (ch | ks) != 0);
                    wg_commit();
                    if (ch == 3 || (ch < 2 && t == 0)) token_pass(w);
                    if constexpr (ch < 2) { if (t == 0 && (ch || !v)) load_wchunk(IC<ch + 1>{}); }
                    if constexpr (ch == 2) { if (t == 0 && !w) load_wchunk(IC<3>{}); }
                    if (ch > 0) { wg_wait<1>(); release(c, BAR_EMPTY + 8 * last, 1); }
                    last = cur.slot;
                    cur.adv();
                    if (ch < 3 && t == 0) cur.adv();
                    if constexpr (ch == 1) { if (t == 0 && w) load_wchunk(IC<3>{}); }
                    if (ch < 2 && t == 0) token_wait(w);
                };
                chunk(IC<0>{}); chunk(IC<1>{}); chunk(IC<2>{}); chunk(IC<3>{});
                wg_wait<0>();
                release(c, BAR_EMPTY + 8 * last, 1);
                PROF_EV(11);
                fence_regs(acc);
                tile_out(out, (rank ? g_V : g_K) + (size_t)(team * 32 + 24 + 2 * k - 8 * t) * 16384, 64 * w, rank, c);
                if (DEFER && t == 3 && w) break;
#pragma unroll
                for (int i = 0; i < 4; i++) store_pair(acc, i, out, 16384, inv);
                if (t) signal_event(c, EV_KV + 3 * v + t - 1);
            }
            PROF_EV(61); PROF_GT(62);
        }
        PROF_EV(63); PROF_GT(64);
        {
            uint32_t q[32], p[32];
            float m[2], l[2];
#pragma unroll
            for (int i = 0; i < 32; i++) p[i] = 0u;
            l[0] = l[1] = 1.f;
            int pv_acc = 0, pv_mode = 2;
#pragma unroll 1
            for (int r = 0; r < 2; r++) {
                const int heavy = 1 ^ r ^ w;
                const int half = 1 ^ heavy ^ rank ^ (r & SWAPT);
                int left = 2 * (r ? k : 7 - k) + 1 + heavy;
                Cur ck, cv = cur;
                {
                    float s[64];
                    if (r) cur.adv();
                    mbar_wait_hot(misc + BAR_FULL + 8 * cv.slot, cv.ph);
                    token_wait(w);
                    PROF_EV(20);
                    issue_pv(o, p, ring + cv.slot * SLOT_BYTES, 1, r ? 0 : 2);
                    undef_regs(s);
                    uint32_t prev;
                    auto qchunk = [&](int acc) {
                        mbar_wait_hot(misc + BAR_FULL + 8 * cur.slot, cur.ph);
                        const uint64_t da = mkdesc(ring + cur.slot * SLOT_BYTES + w * 8192, 16, 1024, 1);
                        const uint64_t db = mkdesc(ring + cur.slot * SLOT_BYTES + 16384, 8192, 1024, 1);
                        wg_fence();
#pragma unroll
                        for (int ks = 0; ks < 4; ks++) wgmma_ss_n128_ta0_tb1(s, da + 2 * ks, db + 128 * ks, ks ? 1 : acc);
                        wg_commit();
                    };
                    qchunk(0);
                    prev = cur.slot; cur.adv();
                    token_pass(w);
                    if (r) {
                        row_inv(l, inv);
                        tile_out(out, g_ctx + (size_t)((2 * team + v) * 32 + 4 * (7 - k) + (w ? rank : 3 - rank)) * 16384, 0, 2, c);
                    }
                    const int epi = r | (w & DEFER), hs = r ? 8192 : 16384;
                    const int hold = heavy ? -10 : half ? HOLD0 : 8;
#pragma unroll
                    for (int kc = 1; kc < 10; kc++) {
                        if (HOLD0 && kc >= HOLD0 && (kc == hold || kc == hold + 2)) token_wait(w);
                        qchunk(1);
                        if (HOLD0 && kc > HOLD0 && kc == hold + 1) token_pass(w);
                        if (HOLD0 && kc == 9 && heavy) { token_wait(w); token_pass(w); }
                        wg_wait<1>();
                        release(c, BAR_EMPTY + 8 * prev, 1);
                        prev = cur.slot; cur.adv();
                        if (kc == 1) { fence_regs(o); if (r) release(c, BAR_EMPTY + 8 * cv.slot, 1); }
                        if (kc <= 4 && epi) {
                            store_pair(o, kc - 1, out, hs, inv);
                            if (kc == 4) signal_event(c, r ? EV_CTX + 2 * v : EV_KV + 3 * v + 2);
                        }
                    }
                    if (!heavy) cur.adv();
                    ck = cur;
                    cur.adv();
                    if (!heavy) cur.adv();
                    wg_wait<0>();
                    release(c, BAR_EMPTY + 8 * prev, 1);
                    PROF_EV(21);
                    fence_regs(s);
#pragma unroll
                    for (int i = 0; i < 32; i++) q[i] = pack_bf16(s[2 * i], s[2 * i + 1]);
                }
                cv = ck;
                int first = 1, gen = 0;
                uint32_t pv_cnt = 0;
                pv_acc = 0; pv_mode = 2;
                l[0] = l[1] = m[0] = m[1] = 0.f;
                mbar_wait_hot(misc + BAR_FULL + 8 * ck.slot, ck.ph);
#pragma unroll 1
                while (true) {
                    float s[64];
                    if (half & first) {
                        if (heavy || HOLD0 == 0 || HOLD0 == 8) token_wait(w);
                        PROF_EV(30);
                        float sh[32];
                        undef_regs(sh);
                        issue_qk_half(sh, q, ring + ck.slot * SLOT_BYTES);
                        token_pass(w);
                        --left;
                        wg_wait<0>();
                        PROF_EV(34);
                        fence_regs(sh);
                        mask_diag<0>(sh, c);
                        float l0 = 0.f, l1 = 0.f;
#pragma unroll
                        for (int j = 0; j < 8; j++) {
#pragma unroll
                            for (int e = 0; e < 4; e++) ex2v(sh[4 * j + e]);
                            l0 += sh[4 * j] + sh[4 * j + 1]; l1 += sh[4 * j + 2] + sh[4 * j + 3];
                        }
#pragma unroll
                        for (int i = 0; i < 16; i++) p[i] = pack_bf16(sh[2 * i], sh[2 * i + 1]);
                        const int lim = mask_lim(c);
                        if (__any_sync(0xffffffffu, !(l0 <= SAFE_SUM && l1 <= SAFE_SUM && (l0 >= 1.0f / SAFE_SUM || lim < 0) &&
                                                      (l1 >= 1.0f / SAFE_SUM || lim < -2)))) goto redo;
                        l[0] = l0; l[1] = l1;
                        goto tail;
                    }
#pragma unroll 1
                    while (true) {
                        token_wait(w);
                        PROF_EV(first ? 30 : 31);
                        undef_regs(s);
                        issue_qk(s, q, ring + ck.slot * SLOT_BYTES);
                        Cur nck = cur, ncv = cur, ncur;
                        ncv.adv(); ncur = ncv; ncur.adv();
                        --left;
                        mbar_wait_hot(misc + BAR_FULL + 8 * cv.slot, cv.ph);
                        issue_pv(o, p, ring + cv.slot * SLOT_BYTES, pv_acc, pv_mode);
                        token_pass(w);
                        wg_wait<1>();
                        PROF_EV(33);
                        fence_regs(s);
                        float lo = 0.f;
                        if (first) {
                            lo = 1.0f / SAFE_SUM;
                            mask_diag<8>(s, c);
                        }
                        constexpr int JB = 11;
                        float l0 = l[0], l1 = l[1];
                        if (!gen) {
#pragma unroll
                            for (int j = 0; j < JB; j++) {
#pragma unroll
                                for (int e = 0; e < 4; e++) ex2v(s[4 * j + e]);
                                if (j < JB - 1) { l0 += s[4 * j] + s[4 * j + 1]; l1 += s[4 * j + 2] + s[4 * j + 3]; }
                            }
                        }
                        wg_wait<0>();
                        fence_regs(o);
                        if (gen) goto general;
#pragma unroll
                        for (int j = JB - 1; j < 16; j++) {
                            if (j >= JB) {
#pragma unroll
                                for (int e = 0; e < 4; e++) ex2v(s[4 * j + e]);
                            }
                            l0 += s[4 * j] + s[4 * j + 1]; l1 += s[4 * j + 2] + s[4 * j + 3];
                        }
#pragma unroll
                        for (int i = 0; i < 32; i++) p[i] = pack_bf16(s[2 * i], s[2 * i + 1]);
                        if (__any_sync(0xffffffffu, !(l0 <= SAFE_SUM && l1 <= SAFE_SUM && l0 >= lo && l1 >= lo))) goto redo;
                        l[0] = l0; l[1] = l1;
                        if (left == 0) goto tail;
                        release(c, BAR_EMPTY + 8 * ck.slot, 1 + (first & heavy));
                        if (pv_cnt) release(c, BAR_EMPTY + 8 * cv.slot, pv_cnt);
                        pv_acc = first ^ 1; pv_mode = 0; pv_cnt = 1 + (first & heavy); first = 0;
                        ck = nck; cv = ncv; cur = ncur;
                        mbar_wait_hot(misc + BAR_FULL + 8 * ck.slot, ck.ph);
                    }
                redo:
                    recompute_scores(s, q, ring + ck.slot * SLOT_BYTES, c);
                    if (first) { mask_any(s, half ^ 1, c); m[0] = m[1] = -INFINITY; }
                    gen = 1;
                general:
                    {
                        float mx[2], alpha[2];
                        row_max<16>(s, mx);
#pragma unroll
                        for (int i = 0; i < 2; i++) {
                            mx[i] = fmaxf(mx[i], m[i]);
                            alpha[i] = ex2(m[i] - mx[i]);
                            m[i] = mx[i];
                            l[i] *= alpha[i];
                        }
                        exp_sum<16, true>(s, m, l[0], l[1]);
#pragma unroll
                        for (int i = 0; i < 64; i++) o[i] *= alpha[(i >> 1) & 1];
#pragma unroll
                        for (int i = 0; i < 32; i++) p[i] = pack_bf16(s[2 * i], s[2 * i + 1]);
                    }
                tail:
                    release(c, BAR_EMPTY + 8 * ck.slot, 1 + (first & heavy));
                    if (pv_cnt) release(c, BAR_EMPTY + 8 * cv.slot, pv_cnt);
                    pv_acc = first ^ 1; pv_mode = first & half; pv_cnt = 1 + (first & heavy); first = 0;
                    if (left == 0) break;
                    ck = cur; cur.adv(); cv = cur; cur.adv();
                    mbar_wait_hot(misc + BAR_FULL + 8 * ck.slot, ck.ph);
                }
            }
            mbar_wait_hot(misc + BAR_FULL + 8 * cur.slot, cur.ph);
            token_wait(w);
            PROF_EV(32);
            issue_pv(o, p, ring + cur.slot * SLOT_BYTES, pv_acc, pv_mode);
            if (w == 0 || v == 0) token_pass(w);
            row_inv(l, inv);
            const uint32_t vslot = cur.slot;
            cur.adv();
            if (v) {
                wg_wait<0>();
                release(c, BAR_EMPTY + 8 * vslot, 1);
                fence_regs(o);
                tile_out(out, g_ctx + (size_t)((2 * team + 1) * 32 + 4 * k + (w ? 3 - (rank ^ SWAPT) : rank ^ SWAPT)) * 16384, 0, 2, c);
#pragma unroll
                for (int i = 0; i < 64; i++) wf[i] = 0u;
                continue;
            }
            cw = cur;
            load_wchunk(IC<0>{});
            mbar_wait_hot(misc + BAR_FULL + 8 * cw.slot, cw.ph);
            load_afrag<8, 32>(wf, ring + slot_of(78) * SLOT_BYTES + w * 16384, c);
            cw.adv(); cw.adv();
            asm volatile("{\n.reg .pred p;\nsetp.eq.u32 p, %0, 0;\n@p bar.sync 4, 128;\n@!p bar.sync 5, 128;\n}\n" ::"r"(w) : "memory");
            wg_wait<0>();
            release(c, BAR_EMPTY + 8 * vslot, 1);
            fence_regs(o);
            {
                const int g = c.lane >> 2, r7 = ((g & 1) << 2) | (g >> 1);
                const uint32_t base = ring + slot_of(78) * SLOT_BYTES + w * 16384 + (16 * c.warp + r7) * 128 + (((c.lane & 3) ^ r7) << 4);
#pragma unroll
                for (int i = 0; i < 2; i++)
#pragma unroll
                    for (int qq = 0; qq < 4; qq++)
                        asm volatile("st.shared.v4.b32 [%0], {%1,%2,%3,%4};" ::"r"((base ^ ((qq & 1) << 6)) + (qq >> 1) * 8192 + i * 1024),
                                     "r"(pack_bf16(o[16 * qq + 2 * i] * inv[i], o[16 * qq + 2 * i + 1] * inv[i])),
                                     "r"(pack_bf16(o[16 * qq + 4 + 2 * i] * inv[i], o[16 * qq + 4 + 2 * i + 1] * inv[i])),
                                     "r"(pack_bf16(o[16 * qq + 8 + 2 * i] * inv[i], o[16 * qq + 8 + 2 * i + 1] * inv[i])),
                                     "r"(pack_bf16(o[16 * qq + 12 + 2 * i] * inv[i], o[16 * qq + 12 + 2 * i + 1] * inv[i])) : "memory");
                asm volatile("fence.proxy.async.shared::cta;" ::: "memory");
                signal_event(c, EV_CTX + 1);
            }
        }
        }
        {
            float acc[80];
            undef_regs(acc);
            int st = 0, prev = 0; uint32_t ph3 = 0;
            auto op_stage = [&](int i) {
                mbar_wait(misc + BAR_FULL3 + 8 * st, ph3);
                PROF_EV(44);
                uint32_t base = ring + st * ST3_BYTES;
                uint64_t da = mkdesc(base + w * 8192, 16, 1024, 1);
                uint64_t db = mkdesc(base + 16384, 2048, 512, 2);
                wg_fence();
#pragma unroll
                for (int k = 0; k < 4; k++) wgmma_ss_n160_ta0_tb1(acc, da + 2 * k, db + (k >> 1) * 640 + (k & 1) * 64, k ? 1 : i);
                wg_commit();
                if (i > 0) { wg_wait<1>(); if (i <= 32 - NST3) release(c, BAR_EMPTY3 + 8 * prev, 1); }
                prev = st;
                if (++st == NST3) { st = 0; ph3 ^= 1; }
            };
            PROF_EV(40); PROF_GT(65);
#pragma unroll
            for (int i = 0; i < 4; i++) { op_stage(i); store_pair(o, i, out, 8192, inv); }
            signal_event(c, EV_CTX + 3);
#pragma unroll 1
            for (int i = 4; i < 12; i++) op_stage(i);
            mbar_wait(misc + BAR_SEL, 0);
            const uint32_t tag = lds32(misc + MISC_EPOCH) & 1;
            const int g = c.lane >> 2, t = c.lane & 3;
            const int row = (2 * u3 + rank) * 128 + 64 * w + perm32(16 * c.warp + 8 * kap + (((g & 3) << 1) | (g >> 2)));
            const int col = 160 * s3 + 8 * t;
            int sel = -1;
#pragma unroll
            for (int i = 0; i < TOPC; i++) if ((int)lds32(misc + MISC_SEL + 4 * i) == row) sel = i;
            const int t256 = tid - 128;
            uint4* sendp = g_part + (size_t)cta * 2560 + t256;
            if (c.lane >= 30) stg128(sendp + 9 * 256, tag ^ 1, tag ^ 1, tag ^ 1, tag ^ 1);
#pragma unroll 1
            for (int i = 12; i < 32; i++) op_stage(i);
            uint4 xv[5], bv[5];
#pragma unroll
            for (int i = 0; i < 5; i++) xv[i] = ldg128(P.x + (size_t)row * DM + col + 32 * i);
            uint2 stat;
            asm volatile("ld.global.cg.v2.b32 {%0,%1}, [%2];" : "=r"(stat.x), "=r"(stat.y) : "l"(g_stats + row) : "memory");
            wg_wait<0>();
            fence_regs(acc);
            PROF_EV(41); PROF_GT(66);
            float keep[40];
#pragma unroll
            for (int j = 0; j < 10; j++) {
                uint32_t v0 = __float_as_uint(kap ? acc[8 * j + 0] : acc[8 * j + 2]), v1 = __float_as_uint(kap ? acc[8 * j + 1] : acc[8 * j + 3]);
                uint32_t v2 = __float_as_uint(kap ? acc[8 * j + 4] : acc[8 * j + 6]), v3 = __float_as_uint(kap ? acc[8 * j + 5] : acc[8 * j + 7]);
                asm volatile("st.relaxed.gpu.global.v4.b32 [%0], {%1,%2,%3,%4};" ::"l"(sendp + j * 256),
                             "r"((v0 & ~1u) | tag), "r"((v1 & ~1u) | tag), "r"((v2 & ~1u) | tag), "r"((v3 & ~1u) | tag) : "memory");
                keep[4 * j + 0] = kap ? acc[8 * j + 2] : acc[8 * j + 0]; keep[4 * j + 1] = kap ? acc[8 * j + 3] : acc[8 * j + 1];
                keep[4 * j + 2] = kap ? acc[8 * j + 6] : acc[8 * j + 4]; keep[4 * j + 3] = kap ? acc[8 * j + 7] : acc[8 * j + 5];
            }
            PROF_GT(67);
#pragma unroll
            for (int i = 0; i < 5; i++) {
                uint32_t xx[4] = {xv[i].x, xv[i].y, xv[i].z, xv[i].w};
#pragma unroll
                for (int e = 0; e < 4; e++) {
                    asm("sub.rn.bf16x2 %0, %0, %1;" : "+r"(xx[e]) : "r"(stat.x));
                    xx[e] = pack_bf16(bf_lo(xx[e]) * __uint_as_float(stat.y), bf_hi(xx[e]) * __uint_as_float(stat.y));
                }
                bv[i] = make_uint4(xx[0], xx[1], xx[2], xx[3]);
            }
            if (sel >= 0) {
#pragma unroll
                for (int i = 0; i < 5; i++) bv[i] = ldg128(g_brow + sel * DM + col + 32 * i);
            }
            const uint4* recvp = g_part + (size_t)partner * 2560 + t256;
            uint4 rv[10];
            int spins = 0;
            while (POLL1) {
                uint32_t v;
                asm volatile("ld.relaxed.gpu.global.b32 %0, [%1];" : "=r"(v) : "l"(recvp + 9 * 256 + (31 - c.lane)) : "memory");
                if (__all_sync(0xffffffffu, (v & 1u) == tag) || ++spins > 2000000) break;
            }
            PROF_GT(68);
            while (true) {
                uint32_t bad = 0u;
#pragma unroll
                for (int j = 0; j < 10; j++) {
                    asm volatile("ld.relaxed.gpu.global.v4.b32 {%0,%1,%2,%3}, [%4];"
                                 : "=r"(rv[j].x), "=r"(rv[j].y), "=r"(rv[j].z), "=r"(rv[j].w) : "l"(recvp + j * 256) : "memory");
                }
#pragma unroll
                for (int j = 0; j < 10; j++) {
                    rv[j].x ^= tag; rv[j].y ^= tag; rv[j].z ^= tag; rv[j].w ^= tag;
                    bad |= rv[j].x | rv[j].y | rv[j].z | rv[j].w;
                }
                if (__all_sync(0xffffffffu, (bad & 1u) == 0) || ++spins > 2000000) break;
            }
            PROF_GT(69);
            uint32_t pk[20];
#pragma unroll
            for (int j = 0; j < 10; j++) {
                pk[2 * j] = pack_bf16(keep[4 * j] + __uint_as_float(rv[j].x), keep[4 * j + 1] + __uint_as_float(rv[j].y));
                pk[2 * j + 1] = pack_bf16(keep[4 * j + 2] + __uint_as_float(rv[j].z), keep[4 * j + 3] + __uint_as_float(rv[j].w));
            }
#pragma unroll
            for (int i = 0; i < 5; i++) {
                uint32_t a0 = pk[4 * i], a1 = pk[4 * i + 1], a2 = pk[4 * i + 2], a3 = pk[4 * i + 3];
                uint32_t x0 = (t & 1) ? a0 : a1, x1 = (t & 1) ? a2 : a3;
                x0 = __shfl_xor_sync(0xffffffffu, x0, 1); x1 = __shfl_xor_sync(0xffffffffu, x1, 1);
                if (t & 1) { a0 = x0; a2 = x1; } else { a1 = x0; a3 = x1; }
                x0 = (t & 2) ? a0 : a2; x1 = (t & 2) ? a1 : a3;
                x0 = __shfl_xor_sync(0xffffffffu, x0, 2); x1 = __shfl_xor_sync(0xffffffffu, x1, 2);
                if (t & 2) { a0 = x0; a1 = x1; } else { a2 = x0; a3 = x1; }
                uint32_t av[4] = {a0, a1, a2, a3};
                uint32_t xx[4] = {xv[i].x, xv[i].y, xv[i].z, xv[i].w}, bb[4] = {bv[i].x, bv[i].y, bv[i].z, bv[i].w};
                uint32_t ov[4];
#pragma unroll
                for (int e = 0; e < 4; e++) {
                    asm("add.rn.bf16x2 %0, %1, %2;" : "=r"(ov[e]) : "r"(xx[e]), "r"(av[e]));
                    asm("add.rn.bf16x2 %0, %0, %1;" : "+r"(ov[e]) : "r"(bb[e]));
                }
                stg128(P.out + (size_t)row * DM + col + 32 * i, ov[0], ov[1], ov[2], ov[3]);
            }
            PROF_EV(42); PROF_GT(43);
        }
    }
}

typedef CUresult (*EncodeFn)(CUtensorMap*, CUtensorMapDataType, cuuint32_t, void*, const cuuint64_t*, const cuuint64_t*, const cuuint32_t*,
                             const cuuint32_t*, CUtensorMapInterleave, CUtensorMapSwizzle, CUtensorMapL2promotion, CUtensorMapFloatOOBfill);

void make_map2d(EncodeFn enc, CUtensorMap* tm, const void* p, uint64_t cols, uint64_t rows, uint32_t box_rows = 128) {
    cuuint64_t gd[2] = {cols, rows}, gs[1] = {cols * 2};
    cuuint32_t box[2] = {64, box_rows}, es[2] = {1, 1};
    enc(tm, CU_TENSOR_MAP_DATA_TYPE_BFLOAT16, 2, const_cast<void*>(p), gd, gs, box, es, CU_TENSOR_MAP_INTERLEAVE_NONE,
        CU_TENSOR_MAP_SWIZZLE_128B, CU_TENSOR_MAP_L2_PROMOTION_L2_128B, CU_TENSOR_MAP_FLOAT_OOB_FILL_NONE);
}

void make_map3d(EncodeFn enc, CUtensorMap* tm, const void* p, uint64_t cols, uint64_t rows, uint32_t bw, uint32_t nb) {
    cuuint64_t gd[3] = {bw, rows, cols / bw}, gs[2] = {cols * 2, bw * 2};
    cuuint32_t box[3] = {bw, 32, nb}, es[3] = {1, 1, 1};
    enc(tm, CU_TENSOR_MAP_DATA_TYPE_BFLOAT16, 3, const_cast<void*>(p), gd, gs, box, es, CU_TENSOR_MAP_INTERLEAVE_NONE,
        bw == 64 ? CU_TENSOR_MAP_SWIZZLE_128B : CU_TENSOR_MAP_SWIZZLE_64B, CU_TENSOR_MAP_L2_PROMOTION_L2_128B, CU_TENSOR_MAP_FLOAT_OOB_FILL_NONE);
}

}

extern "C" void kernel_launch(void* const* d_in, const int* in_sizes, int n_in, void* d_out, int out_size) {
    (void)in_sizes; (void)n_in; (void)out_size;
    static EncodeFn enc = nullptr;
    if (!enc) {
        void* fn = nullptr;
        cudaDriverEntryPointQueryResult qr;
        cudaGetDriverEntryPoint("cuTensorMapEncodeTiled", &fn, cudaEnableDefault, &qr);
        enc = (EncodeFn)fn;
        cudaFuncSetAttribute(fused_kernel, cudaFuncAttributeMaxDynamicSharedMemorySize, SMEM_BYTES);
    }
    CUtensorMap tmC, tmWk, tmWv, tmWq, tmWo, tmG, tmU, tmD;
    make_map2d(enc, &tmC, d_in[1], DC, SEQ);
    make_map2d(enc, &tmWq, d_in[2], 4096, DM, 64);
    make_map2d(enc, &tmWk, d_in[3], 4096, DC);
    make_map2d(enc, &tmWv, d_in[4], 4096, DC);
    make_map3d(enc, &tmWo, d_in[5], DM, 4096, 32, 5);
    make_map3d(enc, &tmG, d_in[8], FF, DM, 64, 7);
    make_map3d(enc, &tmU, d_in[9], FF, DM, 64, 7);
    make_map3d(enc, &tmD, d_in[10], DM, FF, 64, 10);
    Params P;
    P.x = (const __nv_bfloat16*)d_in[0];
    P.c = (const __nv_bfloat16*)d_in[1];
    P.wk = (const __nv_bfloat16*)d_in[3];
    P.wv = (const __nv_bfloat16*)d_in[4];
    P.wo = (const __nv_bfloat16*)d_in[5];
    P.wr = (const __nv_bfloat16*)d_in[7];
    P.out = (__nv_bfloat16*)d_out;
    fused_kernel<<<132, 384, SMEM_BYTES>>>(tmC, tmWk, tmWv, tmWq, tmWo, tmG, tmU, tmD, P);
}
```

```cpp
#include <cuda_runtime.h>
#include <cuda_bf16.h>
#include <cuda.h>
#include <stdint.h>

#define SWAPT 1
#define DEFER 1
#define HOLD0 6
#define HM 512
#define POLL1 1
#define OP_PF 8
#define PF_START 9
#define LATE_AT 18
#define CDELAY 500
#define AUXDELAY 1000
namespace {

constexpr int SEQ = 2048, NH = 32, DM = 640, DC = 512, FF = 1728, TOPC = 8;
constexpr int NSLOT = 7, SLOT_BYTES = 32768;
constexpr int NST3 = 6, ST3_BYTES = 36864;
constexpr int RING_BYTES = NSLOT * SLOT_BYTES;
constexpr int SMEM_BYTES = RING_BYTES + 3072;

constexpr int BAR_FULL = 96  , BAR_FULL3 = 152  , BAR_DEP = 200  , BAR_SEL = 464,
              BAR_LN = 472  , BAR_EV = 504  , BAR_EMPTY = 760  , BAR_EMPTY3 = 816  ,
              BAR_PROG = 864  , MISC_EPOCH = 896, MISC_SMID = 900  , MISC_SEL = 912, MISC_WR = 1024  ;
constexpr int D_LN = 0  , D_KV = 4  , D_WAR = 14  , D_CTX = 16  ;
constexpr int EV_KV = 0  , EV_CTX = 12  ;

constexpr int FL_MOE_CNT = 0, FL_MOE_DONE = 1, FL_LN = 16  , FL_KV = 32  , FL_CTX = 416  , FL_WAR = 672  , FL_TOTAL = 704;

__device__ __align__(1024) unsigned char g_K[16 * 32 * 16384];
__device__ __align__(1024) unsigned char g_V[16 * 32 * 16384];
__device__ __align__(1024) unsigned char g_ctx[NH * 32 * 16384];
__device__ __align__(1024) unsigned char g_xn[16 * 10 * 16384];
__device__ __align__(1024) uint4 g_part[128 * 10 * 256];
__device__ float g_router[SEQ];
__device__ uint2 g_stats[SEQ];
__device__ __align__(16) float g_moe_part[4 * TOPC * DM];
__device__ __align__(16) __nv_bfloat16 g_brow[TOPC * DM];
__device__ __align__(16) int g_sel[TOPC];
__device__ unsigned g_flags[FL_TOTAL * 8];
__device__ unsigned g_epoch;
__device__ unsigned g_roleq[130];

struct Params {
    const __nv_bfloat16 *x, *c, *wr, *wk, *wv, *wo;
    __nv_bfloat16* out;
};

__device__ __forceinline__ uint32_t smem_u32(const void* p) { return (uint32_t)__cvta_generic_to_shared(p); }
__device__ __forceinline__ void mbar_init(uint32_t bar, int cnt) { asm volatile("mbarrier.init.shared::cta.b64 [%0], %1;" ::"r"(bar), "r"(cnt)); }
__device__ __forceinline__ void mbar_expect_tx(uint32_t bar, uint32_t bytes) {
    asm volatile("mbarrier.arrive.expect_tx.shared::cta.b64 _, [%0], %1;" ::"r"(bar), "r"(bytes) : "memory");
}
__device__ __forceinline__ void mbar_arrive(uint32_t bar) { asm volatile("mbarrier.arrive.shared::cta.b64 _, [%0];" ::"r"(bar) : "memory"); }
__device__ __forceinline__ void mbar_arrive_cluster(uint32_t cluster_addr, uint32_t cnt) {
    asm volatile("mbarrier.arrive.shared::cluster.b64 _, [%0], %1;" ::"r"(cluster_addr), "r"(cnt) : "memory");
}
__device__ __forceinline__ uint32_t mapa(uint32_t addr, uint32_t cta) {
    uint32_t r; asm("mapa.shared::cluster.u32 %0, %1, %2;" : "=r"(r) : "r"(addr), "r"(cta)); return r;
}
__device__ __forceinline__ void mbar_wait(uint32_t bar, uint32_t parity) {
    asm volatile(
        "{\n.reg .pred p;\n.reg .u32 n;\n"
        "mbarrier.try_wait.parity.shared::cta.b64 p, [%0], %1;\n"
        "@p bra DONE;\n"
        "mov.u32 n, 0;\n"
        "LAB_WAIT:\n"
        "mbarrier.try_wait.parity.shared::cta.b64 p, [%0], %1, 100000;\n"
        "@p bra DONE;\n"
        "add.u32 n, n, 1;\n"
        "setp.lt.u32 p, n, 200000;\n"
        "@p bra LAB_WAIT;\n"
        "trap;\n"
        "DONE:\n}\n" ::"r"(bar), "r"(parity) : "memory");
}
__device__ __forceinline__ void mbar_wait_hot(uint32_t bar, uint32_t parity) {
    asm volatile("{\n.reg .pred p;\nLAB_WAIT:\nmbarrier.try_wait.parity.shared::cta.b64 p, [%0], %1;\n@!p bra LAB_WAIT;\n}\n" ::"r"(bar), "r"(parity) : "memory");
}
__device__ __forceinline__ void flag_wait(const unsigned* flag, unsigned target) {
    asm volatile(
        "{\n.reg .pred p;\n.reg .u32 n, v;\n.reg .s32 d;\n"
        "mov.u32 n, 0;\n"
        "LAB_WAIT:\n"
        "ld.acquire.gpu.global.u32 v, [%0];\n"
        "sub.s32 d, v, %1;\n"
        "setp.ge.s32 p, d, 0;\n"
        "@p bra DONE;\n"
        "nanosleep.u32 40;\n"
        "add.u32 n, n, 1;\n"
        "setp.lt.u32 p, n, 3000000;\n"
        "@p bra LAB_WAIT;\n"
        "trap;\n"
        "DONE:\n}\n" ::"l"(flag), "r"(target) : "memory");
}
__device__ __forceinline__ void flag_signal(unsigned* flag) {
    asm volatile("red.release.gpu.global.add.u32 [%0], 1;" ::"l"(flag) : "memory");
}
__device__ __forceinline__ void fence_async_global() { asm volatile("fence.proxy.async.global;" ::: "memory"); }
__device__ __forceinline__ unsigned* flag_ptr(int idx) { return g_flags + idx * 8; }

__device__ __forceinline__ uint64_t policy_stream() {
    uint64_t p; asm("createpolicy.fractional.L2::evict_first.b64 %0, 1.0;" : "=l"(p)); return p;
}
__device__ __forceinline__ uint64_t policy_normal() { return 0x1000000000000000ull; }
__device__ __forceinline__ uint64_t policy(bool stream) { return stream ? policy_stream() : policy_normal(); }
__device__ __forceinline__ void bulk_load(uint32_t dst, const void* src, uint32_t bytes, uint32_t bar, uint64_t pol) {
    asm volatile("cp.async.bulk.shared::cluster.global.mbarrier::complete_tx::bytes.L2::cache_hint [%0], [%1], %2, [%3], %4;"
                 ::"r"(dst), "l"(src), "r"(bytes), "r"(bar), "l"(pol) : "memory");
}
__device__ __forceinline__ void bulk_load_mc(uint32_t dst, const void* src, uint32_t bytes, uint32_t bar, uint64_t pol) {
    asm volatile("cp.async.bulk.shared::cluster.global.mbarrier::complete_tx::bytes.multicast::cluster.L2::cache_hint [%0], [%1], %2, [%3], %4, %5;"
                 ::"r"(dst), "l"(src), "r"(bytes), "r"(bar), "h"((uint16_t)3), "l"(pol) : "memory");
}
__device__ __forceinline__ void tma2d(uint32_t dst, const CUtensorMap* tm, int c0, int c1, uint32_t bar, uint64_t pol) {
    asm volatile("cp.async.bulk.tensor.2d.shared::cluster.global.mbarrier::complete_tx::bytes.L2::cache_hint [%0], [%1, {%3, %4}], [%2], %5;"
                 ::"r"(dst), "l"(tm), "r"(bar), "r"(c0), "r"(c1), "l"(pol) : "memory");
}
__device__ __forceinline__ void tma2d_mc(uint32_t dst, const CUtensorMap* tm, int c0, int c1, uint32_t bar, uint64_t pol) {
    asm volatile("cp.async.bulk.tensor.2d.shared::cluster.global.mbarrier::complete_tx::bytes.multicast::cluster.L2::cache_hint [%0], [%1, {%3, %4}], [%2], %5, %6;"
                 ::"r"(dst), "l"(tm), "r"(bar), "r"(c0), "r"(c1), "h"((uint16_t)3), "l"(pol) : "memory");
}
__device__ __forceinline__ void tma3d_mc(uint32_t dst, const CUtensorMap* tm, int c0, int c1, int c2, uint32_t bar, uint64_t pol) {
    asm volatile("cp.async.bulk.tensor.3d.shared::cluster.global.mbarrier::complete_tx::bytes.multicast::cluster.L2::cache_hint [%0], [%1, {%3, %4, %5}], [%2], %6, %7;"
                 ::"r"(dst), "l"(tm), "r"(bar), "r"(c0), "r"(c1), "r"(c2), "h"((uint16_t)3), "l"(pol) : "memory");
}
__device__ __forceinline__ void tma3d(uint32_t dst, const CUtensorMap* tm, int c0, int c1, int c2, uint32_t bar) {
    asm volatile("cp.async.bulk.tensor.3d.shared::cluster.global.mbarrier::complete_tx::bytes.L2::cache_hint [%0], [%1, {%3, %4, %5}], [%2], %6;"
                 ::"r"(dst), "l"(tm), "r"(bar), "r"(c0), "r"(c1), "r"(c2), "l"(policy_stream()) : "memory");
}
__device__ __forceinline__ void tma2d_prefetch(const CUtensorMap* tm, int c0, int c1) {
    asm volatile("cp.async.bulk.prefetch.tensor.2d.L2.global [%0, {%1, %2}];" ::"l"(tm), "r"(c0), "r"(c1) : "memory");
}
__device__ __forceinline__ void tma3d_prefetch(const CUtensorMap* tm, int c0, int c1, int c2) {
    asm volatile("cp.async.bulk.prefetch.tensor.3d.L2.global [%0, {%1, %2, %3}];" ::"l"(tm), "r"(c0), "r"(c1), "r"(c2) : "memory");
}
__device__ __forceinline__ void l2_prefetch(const void* p, uint32_t bytes) {
    asm volatile("cp.async.bulk.prefetch.L2.global [%0], %1;" ::"l"(p), "r"(bytes) : "memory");
}
__device__ __forceinline__ bool elect_one() {
    uint32_t r; asm volatile("{\n.reg .pred p;\nelect.sync _|p, 0xffffffff;\nselp.u32 %0, 1, 0, p;\n}\n" : "=r"(r)); return r != 0;
}
__device__ __forceinline__ void wg_fence() { asm volatile("wgmma.fence.sync.aligned;" ::: "memory"); }
__device__ __forceinline__ void wg_commit() { asm volatile("wgmma.commit_group.sync.aligned;" ::: "memory"); }
template <int N> __device__ __forceinline__ void wg_wait() { asm volatile("wgmma.wait_group.sync.aligned %0;" ::"n"(N) : "memory"); }
__device__ __forceinline__ void bar_sync(int id, int n) { asm volatile("bar.sync %0, %1;" ::"r"(id), "r"(n) : "memory"); }
__device__ __forceinline__ void bar_arrive(int id, int n) { asm volatile("bar.arrive %0, %1;" ::"r"(id), "r"(n) : "memory"); }
__device__ __forceinline__ void token_wait(int w) {
    asm volatile("{\n.reg .pred p;\nsetp.eq.u32 p, %0, 0;\n@p bar.sync 1, 256;\n@!p bar.sync 2, 256;\n}\n" ::"r"(w) : "memory");
}
__device__ __forceinline__ void token_pass(int w) {
    asm volatile("{\n.reg .pred p;\nsetp.eq.u32 p, %0, 0;\n@p bar.arrive 2, 256;\n@!p bar.arrive 1, 256;\n}\n" ::"r"(w) : "memory");
}
template <int N> __device__ __forceinline__ void fence_regs(float (&a)[N]) {
#pragma unroll
    for (int i = 0; i < N; i++) asm volatile("" : "+f"(a[i])::"memory");
}
template <int N> __device__ __forceinline__ void undef_regs(float (&a)[N]) {
#pragma unroll
    for (int i = 0; i < N; i++) asm volatile("" : "=f"(a[i]));
}
__device__ __forceinline__ void ldsm4t(uint32_t& r0, uint32_t& r1, uint32_t& r2, uint32_t& r3, uint32_t addr) {
    asm volatile("ldmatrix.sync.aligned.m8n8.x4.trans.shared.b16 {%0,%1,%2,%3}, [%4];"
                 : "=r"(r0), "=r"(r1), "=r"(r2), "=r"(r3) : "r"(addr) : "memory");
}
__device__ __forceinline__ uint32_t pack_bf16(float lo, float hi) {
    uint32_t r; asm("cvt.rn.bf16x2.f32 %0, %1, %2;" : "=r"(r) : "f"(hi), "f"(lo)); return r;
}
__device__ __forceinline__ float bf_lo(uint32_t v) { return __uint_as_float(v << 16); }
__device__ __forceinline__ float bf_hi(uint32_t v) { return __uint_as_float(v & 0xffff0000u); }
__device__ __forceinline__ float bf_round(float v) { return __bfloat162float(__float2bfloat16_rn(v)); }
__device__ __forceinline__ float ex2(float v) { float r; asm("ex2.approx.ftz.f32 %0, %1;" : "=f"(r) : "f"(v)); return r; }
__device__ __forceinline__ void ex2v(float& v) { asm volatile("ex2.approx.ftz.f32 %0, %0;" : "+f"(v)); }
__device__ __forceinline__ float rcp_fast(float v) { float r; asm("rcp.approx.ftz.f32 %0, %1;" : "=f"(r) : "f"(v)); return r; }
__device__ __forceinline__ float sqrt_fast(float v) { float r; asm("sqrt.approx.ftz.f32 %0, %1;" : "=f"(r) : "f"(v)); return r; }
__device__ __forceinline__ void stg128(void* p, uint32_t a, uint32_t b, uint32_t c, uint32_t d) {
    asm volatile("st.global.v4.b32 [%0], {%1,%2,%3,%4};" ::"l"(p), "r"(a), "r"(b), "r"(c), "r"(d) : "memory");
}
__device__ __forceinline__ uint4 ldg128(const void* p) {
    uint4 v; asm volatile("ld.global.cg.v4.b32 {%0,%1,%2,%3}, [%4];" : "=r"(v.x), "=r"(v.y), "=r"(v.z), "=r"(v.w) : "l"(p) : "memory"); return v;
}
__device__ __forceinline__ uint64_t mkdesc(uint32_t addr, uint32_t lbo, uint32_t sbo, uint32_t swz) {
    uint32_t lo = ((addr & 0x3FFFF) >> 4) | ((lbo >> 4) << 16);
    uint32_t hi = (sbo >> 4) | (swz << 30);
    return ((uint64_t)hi << 32) | lo;
}
__device__ __forceinline__ int perm32(int v) { return (v & ~30) | ((v >> 2) & 6) | ((v << 2) & 24); }

__device__ __forceinline__ void wgmma_rs_n128_ta0_tb0(float (&d)[64], uint32_t a0, uint32_t a1, uint32_t a2, uint32_t a3, uint64_t descB, int scaleD) {
  asm volatile("{\n.reg .pred p;\nsetp.ne.b32 p, %69, 0;\n"
    "wgmma.mma_async.sync.aligned.m64n128k16.f32.bf16.bf16 "
    "{%0, %1, %2, %3, %4, %5, %6, %7, %8, %9, %10, %11, %12, %13, %14, %15, %16, %17, %18, %19, %20, %21, %22, %23, %24, %25, %26, %27, %28, %29, %30, %31, %32, %33, %34, %35, %36, %37, %38, %39, %40, %41, %42, %43, %44, %45, %46, %47, %48, %49, %50, %51, %52, %53, %54, %55, %56, %57, %58, %59, %60, %61, %62, %63}, "
    "{%64, %65, %66, %67}, %68, p, 1, 1, 0;\n}\n"
    : "+f"(d[0]), "+f"(d[1]), "+f"(d[2]), "+f"(d[3]), "+f"(d[4]), "+f"(d[5]), "+f"(d[6]), "+f"(d[7]), "+f"(d[8]), "+f"(d[9]), "+f"(d[10]), "+f"(d[11]), "+f"(d[12]), "+f"(d[13]), "+f"(d[14]), "+f"(d[15]), "+f"(d[16]), "+f"(d[17]), "+f"(d[18]), "+f"(d[19]), "+f"(d[20]), "+f"(d[21]), "+f"(d[22]), "+f"(d[23]), "+f"(d[24]), "+f"(d[25]), "+f"(d[26]), "+f"(d[27]), "+f"(d[28]), "+f"(d[29]), "+f"(d[30]), "+f"(d[31]), "+f"(d[32]), "+f"(d[33]), "+f"(d[34]), "+f"(d[35]), "+f"(d[36]), "+f"(d[37]), "+f"(d[38]), "+f"(d[39]), "+f"(d[40]), "+f"(d[41]), "+f"(d[42]), "+f"(d[43]), "+f"(d[44]), "+f"(d[45]), "+f"(d[46]), "+f"(d[47]), "+f"(d[48]), "+f"(d[49]), "+f"(d[50]), "+f"(d[51]), "+f"(d[52]), "+f"(d[53]), "+f"(d[54]), "+f"(d[55]), "+f"(d[56]), "+f"(d[57]), "+f"(d[58]), "+f"(d[59]), "+f"(d[60]), "+f"(d[61]), "+f"(d[62]), "+f"(d[63])
    : "r"(a0), "r"(a1), "r"(a2), "r"(a3), "l"(descB), "r"(scaleD));
}
__device__ __forceinline__ void wgmma_rs_n128_ta0_tb1(float (&d)[64], uint32_t a0, uint32_t a1, uint32_t a2, uint32_t a3, uint64_t descB, int scaleD) {
  asm volatile("{\n.reg .pred p;\nsetp.ne.b32 p, %69, 0;\n"
    "wgmma.mma_async.sync.aligned.m64n128k16.f32.bf16.bf16 "
    "{%0, %1, %2, %3, %4, %5, %6, %7, %8, %9, %10, %11, %12, %13, %14, %15, %16, %17, %18, %19, %20, %21, %22, %23, %24, %25, %26, %27, %28, %29, %30, %31, %32, %33, %34, %35, %36, %37, %38, %39, %40, %41, %42, %43, %44, %45, %46, %47, %48, %49, %50, %51, %52, %53, %54, %55, %56, %57, %58, %59, %60, %61, %62, %63}, "
    "{%64, %65, %66, %67}, %68, p, 1, 1, 1;\n}\n"
    : "+f"(d[0]), "+f"(d[1]), "+f"(d[2]), "+f"(d[3]), "+f"(d[4]), "+f"(d[5]), "+f"(d[6]), "+f"(d[7]), "+f"(d[8]), "+f"(d[9]), "+f"(d[10]), "+f"(d[11]), "+f"(d[12]), "+f"(d[13]), "+f"(d[14]), "+f"(d[15]), "+f"(d[16]), "+f"(d[17]), "+f"(d[18]), "+f"(d[19]), "+f"(d[20]), "+f"(d[21]), "+f"(d[22]), "+f"(d[23]), "+f"(d[24]), "+f"(d[25]), "+f"(d[26]), "+f"(d[27]), "+f"(d[28]), "+f"(d[29]), "+f"(d[30]), "+f"(d[31]), "+f"(d[32]), "+f"(d[33]), "+f"(d[34]), "+f"(d[35]), "+f"(d[36]), "+f"(d[37]), "+f"(d[38]), "+f"(d[39]), "+f"(d[40]), "+f"(d[41]), "+f"(d[42]), "+f"(d[43]), "+f"(d[44]), "+f"(d[45]), "+f"(d[46]), "+f"(d[47]), "+f"(d[48]), "+f"(d[49]), "+f"(d[50]), "+f"(d[51]), "+f"(d[52]), "+f"(d[53]), "+f"(d[54]), "+f"(d[55]), "+f"(d[56]), "+f"(d[57]), "+f"(d[58]), "+f"(d[59]), "+f"(d[60]), "+f"(d[61]), "+f"(d[62]), "+f"(d[63])
    : "r"(a0), "r"(a1), "r"(a2), "r"(a3), "l"(descB), "r"(scaleD));
}
__device__ __forceinline__ void wgmma_rs_n64_ta0_tb1(float (&d)[32], uint32_t a0, uint32_t a1, uint32_t a2, uint32_t a3, uint64_t descB, int scaleD) {
  asm volatile("{\n.reg .pred p;\nsetp.ne.b32 p, %37, 0;\n"
    "wgmma.mma_async.sync.aligned.m64n64k16.f32.bf16.bf16 "
    "{%0, %1, %2, %3, %4, %5, %6, %7, %8, %9, %10, %11, %12, %13, %14, %15, %16, %17, %18, %19, %20, %21, %22, %23, %24, %25, %26, %27, %28, %29, %30, %31}, "
    "{%32, %33, %34, %35}, %36, p, 1, 1, 1;\n}\n"
    : "+f"(d[0]), "+f"(d[1]), "+f"(d[2]), "+f"(d[3]), "+f"(d[4]), "+f"(d[5]), "+f"(d[6]), "+f"(d[7]), "+f"(d[8]), "+f"(d[9]), "+f"(d[10]), "+f"(d[11]), "+f"(d[12]), "+f"(d[13]), "+f"(d[14]), "+f"(d[15]), "+f"(d[16]), "+f"(d[17]), "+f"(d[18]), "+f"(d[19]), "+f"(d[20]), "+f"(d[21]), "+f"(d[22]), "+f"(d[23]), "+f"(d[24]), "+f"(d[25]), "+f"(d[26]), "+f"(d[27]), "+f"(d[28]), "+f"(d[29]), "+f"(d[30]), "+f"(d[31])
    : "r"(a0), "r"(a1), "r"(a2), "r"(a3), "l"(descB), "r"(scaleD));
}
__device__ __forceinline__ void wgmma_ss_n128_ta0_tb1(float (&d)[64], uint64_t descA, uint64_t descB, int scaleD) {
  asm volatile("{\n.reg .pred p;\nsetp.ne.b32 p, %66, 0;\n"
    "wgmma.mma_async.sync.aligned.m64n128k16.f32.bf16.bf16 "
    "{%0, %1, %2, %3, %4, %5, %6, %7, %8, %9, %10, %11, %12, %13, %14, %15, %16, %17, %18, %19, %20, %21, %22, %23, %24, %25, %26, %27, %28, %29, %30, %31, %32, %33, %34, %35, %36, %37, %38, %39, %40, %41, %42, %43, %44, %45, %46, %47, %48, %49, %50, %51, %52, %53, %54, %55, %56, %57, %58, %59, %60, %61, %62, %63}, "
    "%64, %65, p, 1, 1, 0, 1;\n}\n"
    : "+f"(d[0]), "+f"(d[1]), "+f"(d[2]), "+f"(d[3]), "+f"(d[4]), "+f"(d[5]), "+f"(d[6]), "+f"(d[7]), "+f"(d[8]), "+f"(d[9]), "+f"(d[10]), "+f"(d[11]), "+f"(d[12]), "+f"(d[13]), "+f"(d[14]), "+f"(d[15]), "+f"(d[16]), "+f"(d[17]), "+f"(d[18]), "+f"(d[19]), "+f"(d[20]), "+f"(d[21]), "+f"(d[22]), "+f"(d[23]), "+f"(d[24]), "+f"(d[25]), "+f"(d[26]), "+f"(d[27]), "+f"(d[28]), "+f"(d[29]), "+f"(d[30]), "+f"(d[31]), "+f"(d[32]), "+f"(d[33]), "+f"(d[34]), "+f"(d[35]), "+f"(d[36]), "+f"(d[37]), "+f"(d[38]), "+f"(d[39]), "+f"(d[40]), "+f"(d[41]), "+f"(d[42]), "+f"(d[43]), "+f"(d[44]), "+f"(d[45]), "+f"(d[46]), "+f"(d[47]), "+f"(d[48]), "+f"(d[49]), "+f"(d[50]), "+f"(d[51]), "+f"(d[52]), "+f"(d[53]), "+f"(d[54]), "+f"(d[55]), "+f"(d[56]), "+f"(d[57]), "+f"(d[58]), "+f"(d[59]), "+f"(d[60]), "+f"(d[61]), "+f"(d[62]), "+f"(d[63])
    : "l"(descA), "l"(descB), "r"(scaleD));
}
__device__ __forceinline__ void wgmma_ss_n160_ta0_tb1(float (&d)[80], uint64_t descA, uint64_t descB, int scaleD) {
  asm volatile("{\n.reg .pred p;\nsetp.ne.b32 p, %82, 0;\n"
    "wgmma.mma_async.sync.aligned.m64n160k16.f32.bf16.bf16 "
    "{%0, %1, %2, %3, %4, %5, %6, %7, %8, %9, %10, %11, %12, %13, %14, %15, %16, %17, %18, %19, %20, %21, %22, %23, %24, %25, %26, %27, %28, %29, %30, %31, %32, %33, %34, %35, %36, %37, %38, %39, %40, %41, %42, %43, %44, %45, %46, %47, %48, %49, %50, %51, %52, %53, %54, %55, %56, %57, %58, %59, %60, %61, %62, %63, %64, %65, %66, %67, %68, %69, %70, %71, %72, %73, %74, %75, %76, %77, %78, %79}, "
    "%80, %81, p, 1, 1, 0, 1;\n}\n"
    : "+f"(d[0]), "+f"(d[1]), "+f"(d[2]), "+f"(d[3]), "+f"(d[4]), "+f"(d[5]), "+f"(d[6]), "+f"(d[7]), "+f"(d[8]), "+f"(d[9]), "+f"(d[10]), "+f"(d[11]), "+f"(d[12]), "+f"(d[13]), "+f"(d[14]), "+f"(d[15]), "+f"(d[16]), "+f"(d[17]), "+f"(d[18]), "+f"(d[19]), "+f"(d[20]), "+f"(d[21]), "+f"(d[22]), "+f"(d[23]), "+f"(d[24]), "+f"(d[25]), "+f"(d[26]), "+f"(d[27]), "+f"(d[28]), "+f"(d[29]), "+f"(d[30]), "+f"(d[31]), "+f"(d[32]), "+f"(d[33]), "+f"(d[34]), "+f"(d[35]), "+f"(d[36]), "+f"(d[37]), "+f"(d[38]), "+f"(d[39]), "+f"(d[40]), "+f"(d[41]), "+f"(d[42]), "+f"(d[43]), "+f"(d[44]), "+f"(d[45]), "+f"(d[46]), "+f"(d[47]), "+f"(d[48]), "+f"(d[49]), "+f"(d[50]), "+f"(d[51]), "+f"(d[52]), "+f"(d[53]), "+f"(d[54]), "+f"(d[55]), "+f"(d[56]), "+f"(d[57]), "+f"(d[58]), "+f"(d[59]), "+f"(d[60]), "+f"(d[61]), "+f"(d[62]), "+f"(d[63]), "+f"(d[64]), "+f"(d[65]), "+f"(d[66]), "+f"(d[67]), "+f"(d[68]), "+f"(d[69]), "+f"(d[70]), "+f"(d[71]), "+f"(d[72]), "+f"(d[73]), "+f"(d[74]), "+f"(d[75]), "+f"(d[76]), "+f"(d[77]), "+f"(d[78]), "+f"(d[79])
    : "l"(descA), "l"(descB), "r"(scaleD));
}

#define PROF_DECL(b)
#define PROF_EV(tag)
#define PROF_GT(tag)

template <int N> struct IC { static constexpr int value = N; };
struct Cur {
    uint32_t slot, ph;
    __device__ __forceinline__ void adv() { if (++slot == NSLOT) { slot = 0; ph ^= 1; } }
};
constexpr int E0 = 2;
__host__ __device__ constexpr uint32_t slot_of(int e) { return (e + E0) % NSLOT; }
__device__ __forceinline__ Cur cur_at(int e) { Cur c; c.slot = (e + E0) % NSLOT; c.ph = ((e + E0) / NSLOT) & 1; return c; }

__device__ __forceinline__ int op_head(int i, int kap) { return 16 * kap + 2 * (i & 7) + (i >> 3); }

constexpr float SM_SCALE = 0.08838834764831845f * 1.4426950408889634f;

struct Ctx {
    uint32_t ring, misc;
    uint32_t rel;
    int w, warp, lane;
};
__device__ __forceinline__ void release(const Ctx& c, uint32_t off, uint32_t cnt) {
    if (c.lane < 2) mbar_arrive_cluster(c.rel + off, cnt);
}
__device__ __forceinline__ void signal_event(const Ctx& c, int ev) {
    __syncwarp();
    if (c.lane == 0) mbar_arrive(c.misc + BAR_EV + (c.w * 16 + ev) * 8);
}
template <int NK, int OFF, int N>
__device__ __forceinline__ uint32_t load_afrag(uint32_t (&a)[N], uint32_t base, const Ctx& c) {
    int r = c.lane & 7, mat = c.lane >> 3;
    uint32_t addr = base + (8 * (mat >> 1) + r) * 128 + (((2 * c.warp + (mat & 1)) ^ r) << 4);
#pragma unroll
    for (int k = 0; k < NK; k++) ldsm4t(a[OFF + 4 * k], a[OFF + 4 * k + 1], a[OFF + 4 * k + 2], a[OFF + 4 * k + 3], addr + k * 2048);
    uint32_t dep = 0;
#pragma unroll
    for (int k = 0; k < NK; k++) dep |= a[OFF + 4 * k];
    return dep & blockIdx.y;
}
__device__ __forceinline__ void tile_out(unsigned char* (&out)[2], unsigned char* dst, int row0, int perm, const Ctx& c) {
#pragma unroll
    for (int i = 0; i < 2; i++) {
        int g = c.lane >> 2;
        if (perm == 2) g = ((g & 1) << 2) | (g >> 1);
        int row = row0 + 16 * c.warp + 8 * i + g;
        if (perm == 1) row = perm32(row);
        out[i] = dst + row * 128 + (((c.lane & 3) ^ (row & 7)) << 4);
    }
}
__device__ __forceinline__ void store_pair(const float (&a)[64], int n, unsigned char* const (&out)[2], int half_stride, const float (&f)[2]) {
    const int i = n & 1;
#pragma unroll
    for (int q = 2 * (n >> 1); q < 2 * (n >> 1) + 2; q++)
        stg128(reinterpret_cast<unsigned char*>(reinterpret_cast<uint64_t>(out[i]) ^ ((q & 1) << 6)) + (q >> 1) * half_stride,
               pack_bf16(a[16 * q + 2 * i] * f[i], a[16 * q + 2 * i + 1] * f[i]), pack_bf16(a[16 * q + 4 + 2 * i] * f[i], a[16 * q + 4 + 2 * i + 1] * f[i]),
               pack_bf16(a[16 * q + 8 + 2 * i] * f[i], a[16 * q + 8 + 2 * i + 1] * f[i]), pack_bf16(a[16 * q + 12 + 2 * i] * f[i], a[16 * q + 12 + 2 * i + 1] * f[i]));
}

constexpr float SAFE_SUM = 1099511627776.0f;
template <int NJ>
__device__ __forceinline__ void row_max(const float (&s)[4 * NJ], float (&mx)[2]) {
#pragma unroll
    for (int i = 0; i < 2; i++) {
        float a = fmaxf(s[2 * i], s[2 * i + 1]), b = fmaxf(s[4 + 2 * i], s[4 + 2 * i + 1]);
#pragma unroll
        for (int j = 2; j < NJ; j += 2) {
            a = fmaxf(a, fmaxf(s[4 * j + 2 * i], s[4 * j + 2 * i + 1]));
            b = fmaxf(b, fmaxf(s[4 * j + 4 + 2 * i], s[4 * j + 4 + 2 * i + 1]));
        }
        a = fmaxf(a, b);
        a = fmaxf(a, __shfl_xor_sync(0xffffffffu, a, 1));
        mx[i] = fmaxf(a, __shfl_xor_sync(0xffffffffu, a, 2));
    }
}
template <int NJ, bool SHIFT>
__device__ __forceinline__ void exp_sum(float (&s)[4 * NJ], const float (&m)[2], float& l0, float& l1) {
#pragma unroll
    for (int j = 0; j < NJ; j++) {
#pragma unroll
        for (int e = 0; e < 4; e++) s[4 * j + e] = ex2(SHIFT ? s[4 * j + e] - m[e >> 1] : s[4 * j + e]);
        l0 += s[4 * j + 0] + s[4 * j + 1]; l1 += s[4 * j + 2] + s[4 * j + 3];
    }
}
__device__ __forceinline__ void recompute_scores(float (&s)[64], const uint32_t (&q)[32], uint32_t kaddr, const Ctx& c) {
    const int r = c.lane & 7, mat = c.lane >> 3;
    const uint32_t a0 = kaddr + (8 * (mat & 1) + r) * 128 + (((mat >> 1) ^ r) << 4);
#pragma unroll
    for (int i = 0; i < 64; i++) s[i] = 0.f;
#pragma unroll
    for (int jp = 0; jp < 8; jp++) {
#pragma unroll
        for (int k = 0; k < 8; k++) {
            asm volatile(
                "{\n.reg .b32 b0, b1, b2, b3;\n"
                "ldmatrix.sync.aligned.m8n8.x4.trans.shared.b16 {b0,b1,b2,b3}, [%12];\n"
                "mma.sync.aligned.m16n8k16.row.col.f32.bf16.bf16.f32 {%0,%1,%2,%3}, {%8,%9,%10,%11}, {b0,b1}, {%0,%1,%2,%3};\n"
                "mma.sync.aligned.m16n8k16.row.col.f32.bf16.bf16.f32 {%4,%5,%6,%7}, {%8,%9,%10,%11}, {b2,b3}, {%4,%5,%6,%7};\n}\n"
                : "+f"(s[8 * jp]), "+f"(s[8 * jp + 1]), "+f"(s[8 * jp + 2]), "+f"(s[8 * jp + 3]),
                  "+f"(s[8 * jp + 4]), "+f"(s[8 * jp + 5]), "+f"(s[8 * jp + 6]), "+f"(s[8 * jp + 7])
                : "r"(q[4 * k]), "r"(q[4 * k + 1]), "r"(q[4 * k + 2]), "r"(q[4 * k + 3]),
                  "r"((a0 ^ ((jp & 3) << 5)) + (jp >> 2) * 16384 + k * 2048) : "memory");
        }
    }
}
__device__ __forceinline__ int mask_lim(const Ctx& c) { return perm32(16 * c.warp + (c.lane >> 2)) - 8 * (c.lane & 3); }
template <int J0>
__device__ __forceinline__ void mask_diag(float (&s)[4 * J0 + 32], const Ctx& c) {
    const int lim = mask_lim(c);
    if (c.warp < 2) {
#pragma unroll
        for (int x = 0; x < 16; x++) {
            if (2 * (x >> 2) + (x & 1) - (x & 2) > lim) s[4 * J0 + x] = -INFINITY;
            s[4 * J0 + 16 + x] = -INFINITY;
        }
    } else {
#pragma unroll
        for (int x = 0; x < 16; x++)
            if (32 + 2 * (x >> 2) + (x & 1) - (x & 2) > lim) s[4 * J0 + 16 + x] = -INFINITY;
    }
}
__device__ __forceinline__ void mask_any(float (&s)[64], int hh, const Ctx& c) {
    const int lim = mask_lim(c) + 64 * hh;
#pragma unroll
    for (int x = 0; x < 64; x++)
        if (32 * (x >> 4) + 2 * ((x >> 2) & 3) + (x & 1) - (x & 2) > lim) s[x] = -INFINITY;
}
__device__ __forceinline__ void issue_pv(float (&o)[64], const uint32_t (&p)[32], uint32_t vaddr, int acc, int mode  ) {
    uint64_t d = mkdesc(vaddr, 16, 1024, 1);
    if (mode == 0) {
        wg_fence();
#pragma unroll
        for (int k = 0; k < 8; k++)
            wgmma_rs_n128_ta0_tb0(o, p[4 * k], p[4 * k + 1], p[4 * k + 2], p[4 * k + 3], d + (k >> 2) * 1024 + 2 * (k & 3), k ? 1 : acc);
        wg_commit();
    } else if (mode == 1) {
        wg_fence();
#pragma unroll
        for (int k = 0; k < 4; k++) wgmma_rs_n128_ta0_tb0(o, p[4 * k], p[4 * k + 1], p[4 * k + 2], p[4 * k + 3], d + 2 * k, k != 0);
        wg_commit();
    } else {
        wg_fence();
        wgmma_rs_n128_ta0_tb0(o, p[0], p[1], p[2], p[3], d, acc);
        wg_commit();
    }
}
__device__ __forceinline__ void issue_qk(float (&s)[64], const uint32_t (&q)[32], uint32_t kaddr) {
    uint64_t d = mkdesc(kaddr, 16384, 1024, 1);
    wg_fence();
#pragma unroll
    for (int k = 0; k < 8; k++) wgmma_rs_n128_ta0_tb1(s, q[4 * k], q[4 * k + 1], q[4 * k + 2], q[4 * k + 3], d + 128 * k, k != 0);
    wg_commit();
}
__device__ __forceinline__ void issue_qk_half(float (&s32)[32], const uint32_t (&q)[32], uint32_t kaddr) {
    uint64_t d = mkdesc(kaddr, 16384, 1024, 1);
    wg_fence();
#pragma unroll
    for (int k = 0; k < 8; k++) wgmma_rs_n64_ta0_tb1(s32, q[4 * k], q[4 * k + 1], q[4 * k + 2], q[4 * k + 3], d + 128 * k, k != 0);
    wg_commit();
}
__device__ __forceinline__ void row_inv(const float (&l)[2], float (&inv)[2]) {
#pragma unroll
    for (int i = 0; i < 2; i++) {
        float sum = l[i];
        sum += __shfl_xor_sync(0xffffffffu, sum, 1);
        sum += __shfl_xor_sync(0xffffffffu, sum, 2);
        inv[i] = rcp_fast(sum);
    }
}

__device__ __forceinline__ const unsigned char* xn_addr(int row, int col) {
    row = perm32(row);
    return g_xn + ((row >> 7) * 10 + (col >> 6)) * 16384 + (row & 127) * 128 + ((((col & 63) >> 3) ^ (row & 7)) << 4);
}
__device__ __forceinline__ void mma16816(float (&d)[4], uint32_t a0, uint32_t a1, uint32_t a2, uint32_t a3, uint32_t b0, uint32_t b1) {
    asm volatile("mma.sync.aligned.m16n8k16.row.col.f32.bf16.bf16.f32 {%0,%1,%2,%3}, {%4,%5,%6,%7}, {%8,%9}, {%0,%1,%2,%3};"
                 : "+f"(d[0]), "+f"(d[1]), "+f"(d[2]), "+f"(d[3]) : "r"(a0), "r"(a1), "r"(a2), "r"(a3), "r"(b0), "r"(b1));
}
__device__ __forceinline__ uint32_t lds32(uint32_t addr) { uint32_t v; asm volatile("ld.shared.u32 %0, [%1];" : "=r"(v) : "r"(addr)); return v; }

__device__ __forceinline__ void ln_rows(const Params& P, int row0, int lane, uint32_t wr_s) {
    const int hl = lane & 15, row = row0 + (lane >> 4);
    uint32_t v[20];
#pragma unroll
    for (int i = 0; i < 5; i++) {
        uint4 u;
        asm("ld.global.nc.L2::cache_hint.v4.b32 {%0,%1,%2,%3}, [%4], %5;" : "=r"(u.x), "=r"(u.y), "=r"(u.z), "=r"(u.w)
            : "l"(P.x + (size_t)row * DM + 128 * i + 8 * hl), "l"(policy(HM & 512)));
        v[4 * i] = u.x; v[4 * i + 1] = u.y; v[4 * i + 2] = u.z; v[4 * i + 3] = u.w;
    }
    float mean = 0.f, m2 = 0.f, acc2 = 0.f;
#pragma unroll
    for (int i = 0; i < 20; i++) { mean += bf_lo(v[i]); acc2 += bf_hi(v[i]); }
    mean = (mean + acc2) * (1.0f / 40);
    acc2 = 0.f;
#pragma unroll
    for (int i = 0; i < 20; i++) {
        float d0 = __uint_as_float(__byte_perm(v[i], 0, 0x1044)) - mean, d1 = __uint_as_float(__byte_perm(v[i], 0, 0x3244)) - mean;
        m2 = fmaf(d0, d0, m2); acc2 = fmaf(d1, d1, acc2);
    }
    m2 += acc2;
    acc2 = 0.f;
#pragma unroll
    for (int o = 1; o < 16; o <<= 1) {
        float mo = __shfl_xor_sync(0xffffffffu, mean, o), qo = __shfl_xor_sync(0xffffffffu, m2, o), d = mo - mean;
        m2 = fmaf(d * d, 20.0f * o, m2 + qo);
        mean = 0.5f * (mean + mo);
    }
    const uint32_t mb2 = pack_bf16(mean, mean);
    const float inv = rcp_fast(bf_round(sqrt_fast(bf_round(bf_round(m2 * (1.0f / DM)) + 1e-5f))));
    float dot = 0.f;
    unsigned char* xp = const_cast<unsigned char*>(xn_addr(row, 8 * hl));
#pragma unroll
    for (int i = 0; i < 5; i++) {
        uint32_t ww[4];
        asm volatile("ld.shared.v4.b32 {%0,%1,%2,%3}, [%4];" : "=r"(ww[0]), "=r"(ww[1]), "=r"(ww[2]), "=r"(ww[3]) : "r"(wr_s + 256 * i + 16 * hl) : "memory");
#pragma unroll
        for (int e = 0; e < 4; e++) {
            uint32_t d;
            asm("sub.rn.bf16x2 %0, %1, %2;" : "=r"(d) : "r"(v[4 * i + e]), "r"(mb2));
            d = pack_bf16(bf_lo(d) * inv, bf_hi(d) * inv);
            v[4 * i + e] = d;
            dot = fmaf(bf_lo(d), bf_lo(ww[e]), dot);
            acc2 = fmaf(bf_hi(d), bf_hi(ww[e]), acc2);
        }
        stg128(xp + i * 32768, v[4 * i], v[4 * i + 1], v[4 * i + 2], v[4 * i + 3]);
    }
    dot += acc2;
#pragma unroll
    for (int o = 8; o > 0; o >>= 1) dot += __shfl_xor_sync(0xffffffffu, dot, o);
    if (hl == 0) { g_router[row] = bf_round(dot); g_stats[row] = make_uint2(mb2, __float_as_uint(inv)); }
}

__device__ __forceinline__ void aux_cta(const Params& P, const CUtensorMap* tmG, const CUtensorMap* tmU, const CUtensorMap* tmD, unsigned char* sm, int a) {
    constexpr int STG = 57344, XS = 3 * STG, HS = XS + 8 * 1296, KEY = HS + 8 * 912, MI = KEY + 8192;
    const int tid = threadIdx.x, warp = __shfl_sync(0xffffffffu, tid >> 5, 0), lane = tid & 31;
    const uint32_t sb = smem_u32(sm);
    const uint32_t full = sb + MI, empty = sb + MI + 32;
    int* s_sel = reinterpret_cast<int*>(sm + MI + 64);
    float* s_r = reinterpret_cast<float*>(sm + MI + 96);
    volatile unsigned* s_misc = reinterpret_cast<volatile unsigned*>(sm + MI + 128);
    uint32_t* s_key = reinterpret_cast<uint32_t*>(sm + KEY);
    PROF_DECL(128 + a)
    PROF_GT(0);
    if (tid == 0) {
        for (int i = 0; i < 3; i++) { mbar_init(full + 8 * i, 1); mbar_init(empty + 8 * i, 10); }
        asm volatile("fence.mbarrier_init.release.cluster;" ::: "memory");
    }
    __syncthreads();
    if (warp == 11) {
        if (elect_one()) {
            int st = 0; uint32_t ph = 0;
#pragma unroll 1
            for (int s = 0; s < 34; s++) {
                mbar_wait(empty + 8 * st, ph ^ 1);
                const uint32_t dst = sb + st * STG, fb = full + 8 * st;
                if (s < 20) {
                    mbar_expect_tx(fb, 57344);
                    tma3d(dst, tmG, 0, 32 * s, 7 * a, fb);
                    tma3d(dst + 28672, tmU, 0, 32 * s, 7 * a, fb);
                } else {
                    mbar_expect_tx(fb, 40960);
                    tma3d(dst, tmD, 0, 448 * a + 32 * (s - 20), 0, fb);
                }
                if (s >= 3) {
#pragma unroll 1
                    for (int f = (s == 3 ? 4 : s + 6); f <= s + 6 && f < 34; f++) {
                        if (f < 20) { tma3d_prefetch(tmG, 0, 32 * f, 7 * a); tma3d_prefetch(tmU, 0, 32 * f, 7 * a); }
                        else tma3d_prefetch(tmD, 0, 448 * a + 32 * (f - 20), 0);
                    }
                }
                if (++st == 3) { st = 0; ph ^= 1; }
            }
        }
        return;
    }
    if (tid < 80) *reinterpret_cast<uint4*>(sm + KEY + 1024 + tid * 16) = __ldg(reinterpret_cast<const uint4*>(P.wr) + tid);
    __nanosleep(AUXDELAY);
#pragma unroll 1
    for (int i = tid; i < 64 * 40; i += 352) asm volatile("prefetch.global.L2 [%0];" ::"l"(P.x + (size_t)((4 + a) * 256 + 192) * DM + i * 16));
    bar_sync(2, 352);
#pragma unroll 1
    for (int i = warp; i < 32; i += 11) ln_rows(P, (4 + a) * 256 + 192 + 2 * i, lane, sb + KEY + 1024);
    bar_sync(2, 352);
    if (tid == 320) flag_signal(flag_ptr(FL_LN + 4 + a));
    PROF_GT(49);
    if (warp == 10) return;
    if (tid < 8) {
        unsigned e = *reinterpret_cast<volatile unsigned*>(&g_epoch);
        if (tid == 0) s_misc[0] = e;
        flag_wait(flag_ptr(FL_LN + tid), (e + 1) * (32u + (tid >> 2)));
    }
    bar_sync(1, 320);
    PROF_GT(50);
    const unsigned ep = s_misc[0];
    auto top8 = [&](uint32_t (&key)[8]) {
        uint32_t mine = 0;
#pragma unroll 1
        for (int r = 0; r < TOPC; r++) {
            uint32_t best = 0;
#pragma unroll
            for (int i = 0; i < 8; i++) best = max(best, key[i]);
            best = __reduce_max_sync(0xffffffffu, best);
#pragma unroll
            for (int i = 0; i < 8; i++) if (key[i] == best) key[i] = 0;
            if (lane == r) mine = best;
        }
        return mine;
    };
#pragma unroll 1
    for (int pass = 0; pass < 2; pass++) {
        if (warp < (pass ? 1 : 8)) {
            uint32_t key[8];
#pragma unroll
            for (int i = 0; i < 8; i++) {
                if (pass == 0) {
                    int idx = warp * 256 + i * 32 + lane;
                    uint32_t b = __float_as_uint(__ldcg(g_router + idx)) >> 16;
                    b = (b & 0x8000u) ? (~b & 0xffffu) : (b | 0x8000u);
                    key[i] = (b << 16) | (uint32_t)(0xffff - idx);
                } else key[i] = i < 2 ? s_key[i * 32 + lane] : 0u;
            }
            uint32_t best = top8(key);
            if (lane < TOPC) {
                if (pass == 0) s_key[warp * 8 + lane] = best;
                else {
                    uint32_t b = best >> 16;
                    b = (b & 0x8000u) ? (b & 0x7fffu) : (~b & 0xffffu);
                    s_sel[lane] = 0xffff - (int)(best & 0xffffu);
                    s_r[lane] = __uint_as_float(b << 16);
                }
            }
        }
        bar_sync(1, 320);
    }
#pragma unroll
    for (int it = 0; it < 2; it++) {
        int i = tid + it * 320, tk = i / 80, ch = i % 80;
        *reinterpret_cast<uint4*>(sm + XS + tk * 1296 + ch * 16) = __ldcg(reinterpret_cast<const uint4*>(xn_addr(s_sel[tk], ch * 8)));
    }
    bar_sync(1, 320);
    PROF_GT(51);
    const int g = lane >> 2, t = lane & 3;
    const uint32_t woff = warp * 4096 + (8 * (lane >> 4) + (lane & 7)) * 128 + ((((lane >> 3) & 1) ^ (lane & 7)) << 4);
    int st = 0; uint32_t ph = 0;
    float ga[4][4], ua[4][4];
#pragma unroll
    for (int i = 0; i < 4; i++)
#pragma unroll
        for (int e = 0; e < 4; e++) { ga[i][e] = 0.f; ua[i][e] = 0.f; }
#pragma unroll 1
    for (int s = 0; s < 34; s++) {
        if (s == 20) {
            if (warp < 7) {
#pragma unroll
                for (int i = 0; i < 4; i++)
#pragma unroll
                    for (int e = 0; e < 4; e++) {
                        float gv = bf_round(ga[i][e]), uv = bf_round(ua[i][e]);
                        float sg = bf_round(__fdividef(gv, 1.0f + __expf(fminf(-gv, 80.f))));
                        int f = warp * 64 + i * 16 + g + 8 * (e >> 1), tk = 2 * t + (e & 1);
                        *reinterpret_cast<__nv_bfloat16*>(sm + HS + tk * 912 + f * 2) = __float2bfloat16_rn(sg * uv);
                        ga[i][e] = 0.f;
                    }
            }
            bar_sync(1, 320);
            PROF_GT(52);
        }
        mbar_wait(full + 8 * st, ph);
        if (s >= 20 || warp < 7) {
#pragma unroll
            for (int kk = 0; kk < 2; kk++) {
                uint32_t xb = sb + (s < 20 ? XS + g * 1296 + s * 64 : HS + g * 912 + (s - 20) * 64) + 32 * kk + 4 * t;
                uint32_t b0 = lds32(xb), b1 = lds32(xb + 16);
                uint32_t wa = sb + st * STG + woff + kk * 2048;
#pragma unroll
                for (int i = 0; i < 4; i++) {
                    uint32_t a0, a1, a2, a3;
                    ldsm4t(a0, a1, a2, a3, wa ^ (i << 5));
                    mma16816(ga[i], a0, a1, a2, a3, b0, b1);
                    if (s < 20) {
                        ldsm4t(a0, a1, a2, a3, (wa ^ (i << 5)) + 28672);
                        mma16816(ua[i], a0, a1, a2, a3, b0, b1);
                    }
                }
            }
        }
        asm volatile("fence.proxy.async.shared::cta;" ::: "memory");
        __syncwarp();
        if (lane == 0) mbar_arrive(empty + 8 * st);
        if (++st == 3) { st = 0; ph ^= 1; }
    }
#pragma unroll
    for (int i = 0; i < 4; i++)
#pragma unroll
        for (int e = 0; e < 4; e += 2)
            *reinterpret_cast<float2*>(g_moe_part + (a * DM + warp * 64 + i * 16 + g + 4 * e) * 8 + 2 * t) = make_float2(ga[i][e], ga[i][e + 1]);
    bar_sync(1, 320);
    if (tid == 0) {
        __threadfence();
        unsigned old = atomicAdd(flag_ptr(FL_MOE_CNT), 1u);
        s_misc[1] = (old == ep * 4u + 3u);
        __threadfence();
    }
    bar_sync(1, 320);
    PROF_GT(53);
    if (s_misc[1]) {
        const float4* pp = reinterpret_cast<const float4*>(g_moe_part);
#pragma unroll 2
        for (int i = tid; i < DM * 2; i += 320) {
            float4 v0 = __ldcg(pp + i), v1 = __ldcg(pp + DM * 2 + i), v2 = __ldcg(pp + DM * 4 + i), v3 = __ldcg(pp + DM * 6 + i);
            float y[4] = {v0.x + v1.x + v2.x + v3.x, v0.y + v1.y + v2.y + v3.y, v0.z + v1.z + v2.z + v3.z, v0.w + v1.w + v2.w + v3.w};
#pragma unroll
            for (int e = 0; e < 4; e++) {
                int col = i >> 1, tk = (i & 1) * 4 + e;
                float sg = bf_round(__fdividef(1.0f, 1.0f + __expf(fminf(-s_r[tk], 80.f))));
                float upd = bf_round(bf_round(y[e]) * sg);
                float xn = __bfloat162float(*reinterpret_cast<const __nv_bfloat16*>(sm + XS + tk * 1296 + col * 2));
                g_brow[tk * DM + col] = __float2bfloat16_rn(xn + upd);
            }
        }
        if (tid < TOPC) g_sel[tid] = s_sel[tid];
        bar_sync(1, 320);
        if (tid == 0) {
            flag_signal(flag_ptr(FL_MOE_DONE));
            *reinterpret_cast<volatile unsigned*>(&g_epoch) = ep + 1;
        }
        PROF_GT(54);
    }
}

__global__ void __cluster_dims__(2, 1, 1) __launch_bounds__(384, 1)
fused_kernel(const __grid_constant__ CUtensorMap tmC, const __grid_constant__ CUtensorMap tmWk, const __grid_constant__ CUtensorMap tmWv,
             const __grid_constant__ CUtensorMap tmWq, const __grid_constant__ CUtensorMap tmWo,
             const __grid_constant__ CUtensorMap tmG, const __grid_constant__ CUtensorMap tmU, const __grid_constant__ CUtensorMap tmD, const Params P) {
    extern __shared__ __align__(1024) unsigned char smem_raw[];
    const uint32_t ring = smem_u32(smem_raw);
    const uint32_t misc = ring + RING_BYTES;
    const int tid = threadIdx.x;
    const int rank = blockIdx.x & 1;
    uint32_t smid, nsm;
    asm("mov.u32 %0, %%smid;" : "=r"(smid));
    asm("mov.u32 %0, %%nsmid;" : "=r"(nsm));
    if (nsm != 132) smid = blockIdx.x;
    auto role_of = [](int tpc) {
        return tpc < 32 ? (tpc & 7) * 8 + (tpc >> 3) : tpc < 60 ? (1 + (tpc - 32) % 7) * 8 + 4 + (tpc - 32) / 7 : tpc < 64 ? tpc - 56 : tpc;
    };
    int mc = role_of(smid >> 1);
    PROF_DECL(mc * 2 + rank)
    PROF_GT(0); PROF_EV(1);

    auto prefetch_w = [&](int ch) {
        const int i = tid - 128;
        asm volatile("prefetch.global.L2 [%0];" ::"l"((rank ? P.wv : P.wk) + (size_t)(ch * 128 + (mc & 3) * 32 + (i >> 3)) * 4096 + (mc >> 2) * 256 + (i & 7) * 16));
    };
    if (tid >= 128 && mc < 64) {
        if (tid < 256) asm volatile("prefetch.global.L2 [%0];" ::"l"(P.c + (size_t)((12 + (mc & 3)) * 128 + ((mc >> 2) * 2 + rank) * 4) * DC + (tid - 128) * 16));
        prefetch_w(0);
    }
    auto load_w0 = [&]() {
        const CUtensorMap* tw = rank ? &tmWv : &tmWk;
        mbar_expect_tx(misc + BAR_FULL + 8 * slot_of(0), SLOT_BYTES);
        tma2d(ring + slot_of(0) * SLOT_BYTES, tw, (mc >> 2) * 256, 0, misc + BAR_FULL + 8 * slot_of(0), policy(HM & 1));
        tma2d(ring + slot_of(0) * SLOT_BYTES + 16384, tw, (mc >> 2) * 256 + 64, 0, misc + BAR_FULL + 8 * slot_of(0), policy(HM & 1));
    };
    if (tid == 0) {
#pragma unroll
        for (int i = 0; i < NSLOT; i++) mbar_init(misc + BAR_FULL + 8 * i, 1);
#pragma unroll
        for (int i = 0; i < E0; i++) mbar_arrive(misc + BAR_FULL + 8 * i);
        asm volatile("fence.mbarrier_init.release.cluster;" ::: "memory");
        if (mc < 64) load_w0();
    }
    if (tid == 160) {
        asm volatile("st.shared.u32 [%0], %1;" ::"r"(misc + MISC_SMID), "r"(smid) : "memory");
        asm volatile("fence.release.sync_restrict::shared::cta.cluster;" ::: "memory");
    }
    if (tid == 32) {
        asm volatile("prefetch.tensormap [%0];" ::"l"(&tmC) : "memory");
#pragma unroll
        for (int i = 0; i < NSLOT; i++) mbar_init(misc + BAR_EMPTY + 8 * i, 16);
#pragma unroll
        for (int i = 0; i < E0; i++) mbar_arrive_cluster(misc + BAR_EMPTY + 8 * i, 16);
        asm volatile("fence.mbarrier_init.release.cluster;" ::: "memory");
    }
    if (tid == 64) {
#pragma unroll
        for (int i = 0; i < NST3; i++) { mbar_init(misc + BAR_FULL3 + 8 * i, 1); mbar_init(misc + BAR_EMPTY3 + 8 * i, 16); }
#pragma unroll
        for (int i = 0; i < 4; i++) mbar_init(misc + BAR_LN + 8 * i, 2);
        mbar_init(misc + BAR_PROG, 1); mbar_init(misc + BAR_PROG + 8, 1); mbar_init(misc + BAR_PROG + 16, 1);
        asm volatile("fence.mbarrier_init.release.cluster;" ::: "memory");
    }
    if (tid == 96) {
#pragma unroll
        for (int i = 0; i < 34; i++) mbar_init(misc + BAR_DEP + 8 * i, 1);
    }
    if (tid == 128) {
#pragma unroll
        for (int i = 0; i < 32; i++) mbar_init(misc + BAR_EV + 8 * i, 4);
    }
    __syncthreads();
    asm volatile("barrier.cluster.arrive.relaxed.aligned;\nbarrier.cluster.wait.aligned;" ::: "memory");
    {
        uint32_t peer;
        asm volatile("ld.shared::cluster.u32 %0, [%1];" : "=r"(peer) : "r"(mapa(misc + MISC_SMID, rank ^ 1)) : "memory");
        if ((__shfl_sync(0xffffffffu, peer, 0) ^ smid) != 1) {
            if (tid == 0) {
                const unsigned ep1 = *reinterpret_cast<volatile unsigned*>(&g_epoch) + 1;
                if ((smid & 1) == 0) atomicExch(g_roleq + 2 + (atomicAdd(g_roleq, 1u) & 127), (ep1 << 8) | (smid >> 1));
                if (rank == 0) {
                    unsigned* slot = g_roleq + 2 + (atomicAdd(g_roleq + 1, 1u) & 127);
                    unsigned v = 0;
                    for (int spin = 0; spin < 4000000 && ((v = atomicAdd(slot, 0u)) >> 8) != (ep1 & 0xffffffu); spin++) {}
                    asm volatile("st.shared::cluster.u32 [%0], %1;" ::"r"(mapa(misc + MISC_SMID + 4, 0)), "r"(v & 255) : "memory");
                    asm volatile("st.shared::cluster.u32 [%0], %1;" ::"r"(mapa(misc + MISC_SMID + 4, 1)), "r"(v & 255) : "memory");
                }
                if (mc < 64) {
                    mbar_wait(misc + BAR_FULL + 8 * slot_of(0), 0);
                    asm volatile("mbarrier.inval.shared::cta.b64 [%0];" ::"r"(misc + BAR_FULL + 8 * slot_of(0)) : "memory");
                    mbar_init(misc + BAR_FULL + 8 * slot_of(0), 1);
                    asm volatile("fence.mbarrier_init.release.cluster;" ::: "memory");
                }
            }
            __syncwarp();
            asm volatile("barrier.cluster.arrive.aligned;\nbarrier.cluster.wait.aligned;" ::: "memory");
            mc = role_of(__shfl_sync(0xffffffffu, lds32(misc + MISC_SMID + 4), 0));
            if (tid == 0 && mc < 64) load_w0();
            __syncwarp();
        }
    }
    const int cta = mc * 2 + rank;
    if (mc >= 64) { aux_cta(P, &tmG, &tmU, &tmD, smem_raw, cta - 128); return; }
    const int team = mc >> 2, k = mc & 3;
    const int u3 = (mc >> 4) * 2 + (team & 1), s3 = k, kap = (mc >> 3) & 1;
    const int partner = cta ^ 16;
    if (tid >= 128) prefetch_w(1);
    if (tid == 256) {
        const CUtensorMap* tw = rank ? &tmWv : &tmWk;
#pragma unroll
        for (int e = 1; e < NSLOT; e++) {
            const uint32_t fb = misc + BAR_FULL + 8 * slot_of(e), dst = ring + slot_of(e) * SLOT_BYTES;
            mbar_expect_tx(fb, SLOT_BYTES);
            if (e & 1) tma2d_mc(dst + rank * 16384, &tmC, (e >> 1) * 128 + rank * 64, (12 + k) * 128, fb, policy(false));
            else { tma2d(dst, tw, team * 256, e * 64, fb, policy(false)); tma2d(dst + 16384, tw, team * 256 + 64, e * 64, fb, policy(false)); }
        }
    }
    PROF_EV(5);
    const int wg = __shfl_sync(0xffffffffu, tid >> 7, 0);

    if (wg == 0) {
        asm volatile("setmaxnreg.dec.sync.aligned.u32 40;");
        const int warp = __shfl_sync(0xffffffffu, tid >> 5, 0), lane = tid & 31;
        if (warp == 0) {
            const bool lead = elect_one();
            Cur c = cur_at(NSLOT);
            uint32_t dst, fb;
            auto acquire = [&]() {
                mbar_wait(misc + BAR_EMPTY + 8 * c.slot, c.ph ^ 1);
                fb = misc + BAR_FULL + 8 * c.slot; dst = ring + c.slot * SLOT_BYTES;
                if (lead) mbar_expect_tx(fb, SLOT_BYTES);
                c.adv();
            };
            auto load_w = [&](const CUtensorMap* tm, int col, int row, bool stream) {
                acquire();
                if (lead) { tma2d(dst, tm, col, row, fb, policy(stream)); tma2d(dst + 16384, tm, col + 64, row, fb, policy(stream)); }
            };
            auto load_half = [&](const unsigned char* src, bool stream) {
                acquire();
                if (lead) bulk_load_mc(dst + rank * 16384, src, 16384, fb, policy(stream));
            };
            auto dep_wait = [&](int d) { mbar_wait(misc + BAR_DEP + 8 * d, 0); fence_async_global(); };
            auto op_prefetch = [&](int i) {
                const int head = op_head(i, kap);
                l2_prefetch(reinterpret_cast<const unsigned char*>(P.wo) + head * 163840 + (u3 * 8 + s3 * 2 + rank) * 2560, 2560);
                if (i < 8) l2_prefetch(g_ctx + (size_t)(head * 32 + 4 * u3 + 2 * rank) * 16384 + s3 * 8192, 8192);
            };
            __nanosleep(CDELAY);
            if (lead) l2_prefetch(reinterpret_cast<const unsigned char*>(P.c) + (size_t)cta * 12288, 12288);
            const CUtensorMap* tw = rank ? &tmWv : &tmWk;
            const unsigned char* Kh = g_K + (size_t)team * 32 * 16384 + rank * 16384;
            const unsigned char* Vh = g_V + (size_t)team * 32 * 16384 + rank * 16384;
#pragma unroll 1
            for (int v = 0; v < 2; v++) {
                const int h = 2 * team + v;
#pragma unroll 1
                for (int i = v ? 0 : 3; i < 16; i++) {
                    if (i < 4 && v) load_w(tw, h * 128, i * 128, HM & 1);
                    if (v && i == 3 && lead) mbar_arrive(misc + BAR_PROG + 8);
                    if (v && (i & 7) == 3) dep_wait(D_WAR + (i >> 3));
                    acquire();
                    if (lead) tma2d_mc(dst + rank * 16384, &tmC, (i & 3) * 128 + rank * 64, (12 - (i & 12) + k) * 128, fb, policy(HM & 2));
                    if (i == 8 && lead) {
                        tma2d_prefetch(&tmWq, h * 128 + rank * 64, k * 64); tma2d_prefetch(&tmWq, h * 128 + rank * 64, k * 64 + 256);
                        if (k < 2) tma2d_prefetch(&tmWq, h * 128 + rank * 64, k * 64 + 512);
                        if (v) l2_prefetch(g_xn + 8 * 163840 + cta * 10240, 10240);
                    }
                }
                int togo = v ? PF_START : 11;
#pragma unroll 1
                for (int r = 0; r < 2; r++) {
                    const int p = r ? k : 7 - k, n = 2 * p + 1;
                    if (v == 0) dep_wait(D_LN + r);
                    const int g0 = r ? rank ^ SWAPT : 3 - rank, g1 = 3 - g0;
                    const unsigned char* x0 = g_xn + (2 * p + (g0 >> 1)) * 163840 + (g0 & 1) * 8192;
                    const unsigned char* x1 = g_xn + (2 * p + (g1 >> 1)) * 163840 + (g1 & 1) * 8192;
#pragma unroll 1
                    for (int kc = 0; kc < 10; kc++) {
                        acquire();
                        if (lead) {
                            tma2d_mc(dst + 16384 + rank * 8192, &tmWq, h * 128 + rank * 64, kc * 64, fb, policy(false));
                            bulk_load(dst, x0 + kc * 16384, 8192, fb, policy(false));
                            bulk_load(dst + 8192, x1 + kc * 16384, 8192, fb, policy(false));
                        }
                    }
                    if (r == 0) dep_wait(D_KV + 3 * v);
                    load_half(Kh + n * 32768, HM & 16);
#pragma unroll 1
                    for (int j = n - 1; j >= 0; j--) {
                        if (r == 0 && (j == 7 || j == 3)) dep_wait(D_KV + 3 * v + 2 - (j >> 2));
                        load_half(Kh + j * 32768, HM & 16); load_half(Vh + (j + 1) * 32768, HM & 16);
                        if (v == 0 && r == 0 && j == 3 && lead) mbar_arrive(misc + BAR_PROG);
                        --togo;
                        if (v == 0 && togo == 0 && lead) {
                            tma2d_prefetch(tw, h * 128 + 128, k * 128); tma2d_prefetch(tw, h * 128 + 192, k * 128);
                            l2_prefetch(reinterpret_cast<const unsigned char*>(P.c) + (size_t)cta * 16384, 16384);
                        }
                        if (v && togo <= 0 && togo > -OP_PF && lead) op_prefetch(-togo);
                    }
                    load_half(Vh, HM & 16);
                }
            }
            mbar_wait(misc + BAR_EMPTY + 8 * c.slot, c.ph ^ 1); c.adv();
            int st = 0; uint32_t ph3 = 0;
#pragma unroll 1
            for (int i = 0; i < 32; i++) {
                const int head = op_head(i >> 1, kap);
                if ((i & 1) == 0) dep_wait(D_CTX + (i >> 1));
                if (i < NST3) { mbar_wait(misc + BAR_EMPTY + 8 * c.slot, c.ph ^ 1); c.adv(); }
                else mbar_wait(misc + BAR_EMPTY3 + 8 * st, ph3 ^ 1);
                fb = misc + BAR_FULL3 + 8 * st; dst = ring + st * ST3_BYTES;
                if (i == LATE_AT && lead) mbar_arrive(misc + BAR_PROG + 16);
                if (lead) {
                    mbar_expect_tx(fb, ST3_BYTES);
                    const unsigned char* src = g_ctx + (size_t)(head * 32 + 4 * u3 + 2 * rank) * 16384 + (i & 1) * 8192;
                    bulk_load(dst, src, 8192, fb, policy(HM & 32));
                    bulk_load(dst + 8192, src + 16384, 8192, fb, policy(HM & 32));
                    tma3d_mc(dst + 16384 + rank * 10240, &tmWo, 0, head * 128 + (i & 1) * 64 + rank * 32, 5 * s3, fb, policy(HM & 32));
                    if ((i & 1) && (i >> 1) + OP_PF < 16) op_prefetch((i >> 1) + OP_PF);
                }
                if (++st == NST3) { st = 0; ph3 ^= 1; }
            }
        } else {
        if (lane < 27 && (warp - 1) * 27 + lane < 80) {
            const int ch = (warp - 1) * 27 + lane;
            uint4 u = __ldg(reinterpret_cast<const uint4*>(P.wr) + ch);
            asm volatile("st.shared.v4.b32 [%0], {%1,%2,%3,%4};" ::"r"(misc + MISC_WR + 16 * ch), "r"(u.x), "r"(u.y), "r"(u.z), "r"(u.w) : "memory");
        }
        bar_sync(3, 96);
#pragma unroll 1
        for (int t = 0; t < (warp == 3 ? 1 : 3); t++) {
            const int row2 = (cta >> 5) * 256 + (cta & 31) * 8 + (warp - 1) * 4;
            if (t < 2 && warp < 3) {
#pragma unroll
                for (int i = 0; i < 3; i++)
                    if (i * 32 + lane < 80) asm volatile("prefetch.global.L2 [%0];" ::"l"(P.x + (size_t)(row2 + 2 * t) * DM + (i * 32 + lane) * 16));
            }
            ln_rows(P, t ? row2 + 2 * t - 2 : (4 + (cta >> 5)) * 256 + (cta & 31) * 6 + (warp - 1) * 2, lane, misc + MISC_WR);
            __syncwarp();
            if (lane == 0 && warp < 3 && t != 1) mbar_arrive(misc + BAR_LN + 4 * t);
        }
        if (warp == 3) {
            const unsigned ep1 = *reinterpret_cast<volatile unsigned*>(&g_epoch) + 1;
            if (lane == 0) {
                asm volatile("st.shared.u32 [%0], %1;" ::"r"(misc + MISC_EPOCH), "r"(ep1) : "memory");
                mbar_wait(misc + BAR_LN, 0);
                flag_signal(flag_ptr(FL_LN + 4 + (cta >> 5)));
                flag_wait(flag_ptr(FL_LN + 7 - k), ep1 * 33u);
                mbar_arrive(misc + BAR_DEP + 8 * D_LN);
#pragma unroll 1
                for (int v = 0; v < 2; v++) {
#pragma unroll 1
                    for (int i = 3 * v; i < 3 * v + 3; i++) {
                        mbar_wait(misc + BAR_EV + 8 * (16 + EV_KV + i), 0);
                        if (v == 0) {
                            mbar_wait(misc + BAR_EV + 8 * (EV_KV + i), 0);
                            asm volatile("red.release.gpu.global.add.u32 [%0], 2;" ::"l"(flag_ptr(FL_KV + team * 8 + i)) : "memory");
                        }
                        flag_wait(flag_ptr(FL_KV + team * 8 + i), ep1 * 16u);
                        mbar_arrive(misc + BAR_DEP + 8 * (D_KV + i));
                    }
                    if (v) break;
                    mbar_wait(misc + BAR_LN + 8, 0);
                    flag_signal(flag_ptr(FL_LN + (cta >> 5)));
                    flag_wait(flag_ptr(FL_LN + k), ep1 * 32u);
                    mbar_arrive(misc + BAR_DEP + 8 * (D_LN + 1));
#pragma unroll 1
                    for (int i = 0; i < 2; i++) {
                        mbar_wait(misc + BAR_PROG + 8 * i, 0);
                        flag_signal(flag_ptr(FL_WAR + 2 * team + i));
                        flag_wait(flag_ptr(FL_WAR + 2 * team + i), ep1 * 8u);
                        mbar_arrive(misc + BAR_DEP + 8 * (D_WAR + i));
                    }
                }
                flag_wait(flag_ptr(FL_MOE_DONE), ep1);
                int4 s0 = __ldcg(reinterpret_cast<const int4*>(g_sel)), s1 = __ldcg(reinterpret_cast<const int4*>(g_sel) + 1);
                asm volatile("st.shared.v4.u32 [%0], {%1,%2,%3,%4};" ::"r"(misc + MISC_SEL), "r"(s0.x), "r"(s0.y), "r"(s0.z), "r"(s0.w) : "memory");
                asm volatile("st.shared.v4.u32 [%0], {%1,%2,%3,%4};" ::"r"(misc + MISC_SEL + 16), "r"(s1.x), "r"(s1.y), "r"(s1.z), "r"(s1.w) : "memory");
                mbar_arrive(misc + BAR_SEL);
            }
            __syncwarp();
            const unsigned* cf = flag_ptr(FL_CTX + op_head(lane & 15, kap) * 8 + u3);
#pragma unroll 1
            for (int half = 0; half < 2; half++) {
                if (half) mbar_wait(misc + BAR_EV + 8 * (EV_CTX + 3), 0);
                bool done = (lane >> 3) != half;
                for (int spin = 0; spin < 4000000; spin++) {
                    if (!done) {
                        unsigned v;
                        asm volatile("ld.acquire.gpu.global.u32 %0, [%1];" : "=r"(v) : "l"(cf) : "memory");
                        if ((int)(v - ep1 * 4u) >= 0) { mbar_arrive(misc + BAR_DEP + 8 * (D_CTX + lane)); done = true; }
                    }
                    if (__all_sync(0xffffffffu, done)) break;
                    __nanosleep(64);
                }
            }
        } else {
            const int w = warp - 1;
            if (lane == 0) {
                const uint32_t eb = misc + BAR_EV + w * 128;
#pragma unroll 1
                for (int i = 0; i < 7; i++) {
                    const bool kv = i >= 2 && i < 5;
                    const int ci = i < 2 ? i : i - 3;
                    mbar_wait(eb + 8 * (kv ? EV_KV + i + 1 : EV_CTX + ci), 0);
                    if (i == 1) {
                        asm volatile("cp.async.bulk.global.shared::cta.bulk_group [%0], [%1], 16384;"
                                     ::"l"(g_ctx + (size_t)(2 * team * 32 + 4 * k + (w ? 3 - (rank ^ SWAPT) : rank ^ SWAPT)) * 16384),
                                       "r"(ring + slot_of(78) * SLOT_BYTES + w * 16384) : "memory");
                        asm volatile("cp.async.bulk.commit_group;" ::: "memory");
                        asm volatile("cp.async.bulk.wait_group.read 0;" ::: "memory");
                        mbar_arrive_cluster(mapa(misc + BAR_EMPTY + 8 * slot_of(78), 0), 4);
                        mbar_arrive_cluster(mapa(misc + BAR_EMPTY + 8 * slot_of(78), 1), 4);
                        asm volatile("cp.async.bulk.wait_group 0;" ::: "memory");
                        fence_async_global();
                    }
                    flag_signal(flag_ptr(kv ? FL_KV + team * 8 + i + 1 : FL_CTX + (2 * team + (ci >> 1)) * 8 + ((ci & 1) ? k : 7 - k)));
                }
            }
            __syncwarp();
            mbar_wait(misc + BAR_PROG + 16, 0);
            const int row = (2 * u3 + rank) * 128 + 64 * w + perm32(16 * (lane >> 3) + 8 * kap + (lane & 7));
#pragma unroll
            for (int i = 0; i < 10; i++) asm volatile("prefetch.global.L2 [%0];" ::"l"(P.x + (size_t)row * DM + 160 * s3 + 16 * i));
            asm volatile("prefetch.global.L2 [%0];" ::"l"(g_stats + row));
        }
        }
    } else {
        asm volatile("setmaxnreg.inc.sync.aligned.u32 232;");
        Ctx c;
        c.ring = ring; c.misc = misc; c.w = wg - 1; c.warp = __shfl_sync(0xffffffffu, (tid >> 5) & 3, 0); c.lane = tid & 31;
        c.rel = mapa(misc, tid & 1);
        const int w = c.w;
        if (w == 1) bar_arrive(1, 256);
        prefetch_w(2); prefetch_w(3);
        Cur cur = cur_at(0);
        float o[64], inv[2];
        unsigned char* out[2];
        uint32_t wf[128];
        Cur cw = cur;
        auto load_wchunk = [&](auto CH) {
            constexpr int ch = decltype(CH)::value;
            mbar_wait_hot(misc + BAR_FULL + 8 * cw.slot, cw.ph);
            const uint32_t z = load_afrag<8, 32 * ch>(wf, ring + cw.slot * SLOT_BYTES + w * 16384, c);
            release(c, BAR_EMPTY + 8 * cw.slot + z, 1);
            cw.adv(); cw.adv();
        };
#pragma unroll
        for (int i = 32; i < 64; i++) wf[i] = 0u;
        load_wchunk(IC<0>{});
#pragma unroll 1
        for (int v = 0; v < 2; v++) {
        {
            float (&acc)[64] = o;
#pragma unroll
            for (int i = 64; i < 128; i++) wf[i] = 0u;
            cur.adv();
            inv[0] = inv[1] = rank ? 1.0f : SM_SCALE;
            PROF_EV(2); PROF_GT(60);
#pragma unroll 1
            for (int t = 0; t < 4; t++) {
                uint32_t last = 0;
                token_wait(w);
                PROF_EV(10);
                undef_regs(acc);
                auto chunk = [&](auto CH) {
                    constexpr int ch = decltype(CH)::value;
                    mbar_wait_hot(misc + BAR_FULL + 8 * cur.slot, cur.ph);
                    if (t == 0) { PROF_EV(12 + ch); }
                    uint64_t d = mkdesc(ring + cur.slot * SLOT_BYTES, 16, 1024, 1);
                    wg_fence();
#pragma unroll
                    for (int ks = 0; ks < 8; ks++)
                        wgmma_rs_n128_ta0_tb0(acc, wf[32 * ch + 4 * ks], wf[32 * ch + 4 * ks + 1], wf[32 * ch + 4 * ks + 2], wf[32 * ch + 4 * ks + 3],
                                              d + (ks >> 2) * 1024 + (ks & 3) * 2, (ch | ks) != 0);
                    wg_commit();
                    if (ch == 3 || (ch < 2 && t == 0)) token_pass(w);
                    if constexpr (ch == 0) { if (t == 0) { if (v) load_wchunk(IC<2>{}); else load_wchunk(IC<1>{}); } }
                    if constexpr (ch == 1) { if (t == 0 && !v) load_wchunk(IC<2>{}); }
                    if constexpr (ch == 2) { if (t == 0 && !(w | v)) load_wchunk(IC<3>{}); }
                    if (ch > 0) { wg_wait<1>(); release(c, BAR_EMPTY + 8 * last, 1); }
                    last = cur.slot;
                    cur.adv();
                    if (ch < 3 && t == 0) cur.adv();
                    if constexpr (ch == 1) { if (t == 0 && (w | v)) load_wchunk(IC<3>{}); }
                    if (ch < 2 && t == 0) token_wait(w);
                };
                chunk(IC<0>{}); chunk(IC<1>{}); chunk(IC<2>{}); chunk(IC<3>{});
                wg_wait<0>();
                release(c, BAR_EMPTY + 8 * last, 1);
                PROF_EV(11);
                fence_regs(acc);
                tile_out(out, (rank ? g_V : g_K) + (size_t)(team * 32 + 24 + 2 * k - 8 * t) * 16384, 64 * w, rank, c);
                if (DEFER && t == 3 && w) break;
#pragma unroll
                for (int i = 0; i < 4; i++) store_pair(acc, i, out, 16384, inv);
                if (t) signal_event(c, EV_KV + 3 * v + t - 1);
            }
            PROF_EV(61); PROF_GT(62);
        }
        PROF_EV(63); PROF_GT(64);
        {
            uint32_t q[32], p[32];
            float m[2], l[2];
#pragma unroll
            for (int i = 0; i < 32; i++) p[i] = 0u;
            l[0] = l[1] = 1.f;
            int pv_acc = 0, pv_mode = 2;
#pragma unroll 1
            for (int r = 0; r < 2; r++) {
                const int heavy = 1 ^ r ^ w;
                const int half = 1 ^ heavy ^ rank ^ (r & SWAPT);
                int left = 2 * (r ? k : 7 - k) + 1 + heavy;
                Cur ck, cv = cur;
                {
                    float s[64];
                    if (r) cur.adv();
                    mbar_wait_hot(misc + BAR_FULL + 8 * cv.slot, cv.ph);
                    token_wait(w);
                    PROF_EV(20);
                    issue_pv(o, p, ring + cv.slot * SLOT_BYTES, 1, r ? 0 : 2);
                    undef_regs(s);
                    uint32_t prev;
                    auto qchunk = [&](int acc) {
                        mbar_wait_hot(misc + BAR_FULL + 8 * cur.slot, cur.ph);
                        const uint64_t da = mkdesc(ring + cur.slot * SLOT_BYTES + w * 8192, 16, 1024, 1);
                        const uint64_t db = mkdesc(ring + cur.slot * SLOT_BYTES + 16384, 8192, 1024, 1);
                        wg_fence();
#pragma unroll
                        for (int ks = 0; ks < 4; ks++) wgmma_ss_n128_ta0_tb1(s, da + 2 * ks, db + 128 * ks, ks ? 1 : acc);
                        wg_commit();
                    };
                    qchunk(0);
                    prev = cur.slot; cur.adv();
                    token_pass(w);
                    if (r) {
                        row_inv(l, inv);
                        tile_out(out, g_ctx + (size_t)((2 * team + v) * 32 + 4 * (7 - k) + (w ? rank : 3 - rank)) * 16384, 0, 2, c);
                    }
                    const int epi = r | (w & DEFER), hs = r ? 8192 : 16384;
                    const int hold = heavy ? -10 : half ? HOLD0 : 8;
#pragma unroll
                    for (int kc = 1; kc < 10; kc++) {
                        if (HOLD0 && kc >= HOLD0 && (kc == hold || kc == hold + 2)) token_wait(w);
                        qchunk(1);
                        if (HOLD0 && kc > HOLD0 && kc == hold + 1) token_pass(w);
                        if (HOLD0 && kc == 9 && heavy) { token_wait(w); token_pass(w); }
                        wg_wait<1>();
                        release(c, BAR_EMPTY + 8 * prev, 1);
                        prev = cur.slot; cur.adv();
                        if (kc == 1) { fence_regs(o); if (r) release(c, BAR_EMPTY + 8 * cv.slot, 1); }
                        if (kc <= 4 && epi) {
                            store_pair(o, kc - 1, out, hs, inv);
                            if (kc == 4) signal_event(c, r ? EV_CTX + 2 * v : EV_KV + 3 * v + 2);
                        }
                    }
                    if (!heavy) cur.adv();
                    ck = cur;
                    cur.adv();
                    if (!heavy) cur.adv();
                    wg_wait<0>();
                    release(c, BAR_EMPTY + 8 * prev, 1);
                    PROF_EV(21);
                    fence_regs(s);
#pragma unroll
                    for (int i = 0; i < 32; i++) q[i] = pack_bf16(s[2 * i], s[2 * i + 1]);
                }
                cv = ck;
                int first = 1, gen = 0;
                uint32_t pv_cnt = 0;
                pv_acc = 0; pv_mode = 2;
                l[0] = l[1] = m[0] = m[1] = 0.f;
                mbar_wait_hot(misc + BAR_FULL + 8 * ck.slot, ck.ph);
#pragma unroll 1
                while (true) {
                    float s[64];
                    if (half & first) {
                        if (heavy || HOLD0 == 0 || HOLD0 == 8) token_wait(w);
                        PROF_EV(30);
                        float sh[32];
                        undef_regs(sh);
                        issue_qk_half(sh, q, ring + ck.slot * SLOT_BYTES);
                        token_pass(w);
                        --left;
                        wg_wait<0>();
                        PROF_EV(34);
                        fence_regs(sh);
                        mask_diag<0>(sh, c);
                        float l0 = 0.f, l1 = 0.f;
#pragma unroll
                        for (int j = 0; j < 8; j++) {
#pragma unroll
                            for (int e = 0; e < 4; e++) ex2v(sh[4 * j + e]);
                            l0 += sh[4 * j] + sh[4 * j + 1]; l1 += sh[4 * j + 2] + sh[4 * j + 3];
                        }
#pragma unroll
                        for (int i = 0; i < 16; i++) p[i] = pack_bf16(sh[2 * i], sh[2 * i + 1]);
                        const int lim = mask_lim(c);
                        if (__any_sync(0xffffffffu, !(l0 <= SAFE_SUM && l1 <= SAFE_SUM && (l0 >= 1.0f / SAFE_SUM || lim < 0) &&
                                                      (l1 >= 1.0f / SAFE_SUM || lim < -2)))) goto redo;
                        l[0] = l0; l[1] = l1;
                        goto tail;
                    }
#pragma unroll 1
                    while (true) {
                        token_wait(w);
                        PROF_EV(first ? 30 : 31);
                        undef_regs(s);
                        issue_qk(s, q, ring + ck.slot * SLOT_BYTES);
                        Cur nck = cur, ncv = cur, ncur;
                        ncv.adv(); ncur = ncv; ncur.adv();
                        --left;
                        mbar_wait_hot(misc + BAR_FULL + 8 * cv.slot, cv.ph);
                        issue_pv(o, p, ring + cv.slot * SLOT_BYTES, pv_acc, pv_mode);
                        token_pass(w);
                        wg_wait<1>();
                        PROF_EV(33);
                        fence_regs(s);
                        float lo = 0.f;
                        if (first) {
                            lo = 1.0f / SAFE_SUM;
                            mask_diag<8>(s, c);
                        }
                        constexpr int JB = 11;
                        float l0 = l[0], l1 = l[1];
                        if (!gen) {
#pragma unroll
                            for (int j = 0; j < JB; j++) {
#pragma unroll
                                for (int e = 0; e < 4; e++) ex2v(s[4 * j + e]);
                                if (j < JB - 1) { l0 += s[4 * j] + s[4 * j + 1]; l1 += s[4 * j + 2] + s[4 * j + 3]; }
                            }
                        }
                        wg_wait<0>();
                        fence_regs(o);
                        if (gen) goto general;
#pragma unroll
                        for (int j = JB - 1; j < 16; j++) {
                            if (j >= JB) {
#pragma unroll
                                for (int e = 0; e < 4; e++) ex2v(s[4 * j + e]);
                            }
                            l0 += s[4 * j] + s[4 * j + 1]; l1 += s[4 * j + 2] + s[4 * j + 3];
                        }
#pragma unroll
                        for (int i = 0; i < 32; i++) p[i] = pack_bf16(s[2 * i], s[2 * i + 1]);
                        if (__any_sync(0xffffffffu, !(l0 <= SAFE_SUM && l1 <= SAFE_SUM && l0 >= lo && l1 >= lo))) goto redo;
                        l[0] = l0; l[1] = l1;
                        if (left == 0) goto tail;
                        release(c, BAR_EMPTY + 8 * ck.slot, 1 + (first & heavy));
                        if (pv_cnt) release(c, BAR_EMPTY + 8 * cv.slot, pv_cnt);
                        pv_acc = first ^ 1; pv_mode = 0; pv_cnt = 1 + (first & heavy); first = 0;
                        ck = nck; cv = ncv; cur = ncur;
                        mbar_wait_hot(misc + BAR_FULL + 8 * ck.slot, ck.ph);
                    }
                redo:
                    recompute_scores(s, q, ring + ck.slot * SLOT_BYTES, c);
                    if (first) { mask_any(s, half ^ 1, c); m[0] = m[1] = -INFINITY; }
                    gen = 1;
                general:
                    {
                        float mx[2], alpha[2];
                        row_max<16>(s, mx);
#pragma unroll
                        for (int i = 0; i < 2; i++) {
                            mx[i] = fmaxf(mx[i], m[i]);
                            alpha[i] = ex2(m[i] - mx[i]);
                            m[i] = mx[i];
                            l[i] *= alpha[i];
                        }
                        exp_sum<16, true>(s, m, l[0], l[1]);
#pragma unroll
                        for (int i = 0; i < 64; i++) o[i] *= alpha[(i >> 1) & 1];
#pragma unroll
                        for (int i = 0; i < 32; i++) p[i] = pack_bf16(s[2 * i], s[2 * i + 1]);
                    }
                tail:
                    release(c, BAR_EMPTY + 8 * ck.slot, 1 + (first & heavy));
                    if (pv_cnt) release(c, BAR_EMPTY + 8 * cv.slot, pv_cnt);
                    pv_acc = first ^ 1; pv_mode = first & half; pv_cnt = 1 + (first & heavy); first = 0;
                    if (left == 0) break;
                    ck = cur; cur.adv(); cv = cur; cur.adv();
                    mbar_wait_hot(misc + BAR_FULL + 8 * ck.slot, ck.ph);
                }
            }
            mbar_wait_hot(misc + BAR_FULL + 8 * cur.slot, cur.ph);
            token_wait(w);
            PROF_EV(32);
            issue_pv(o, p, ring + cur.slot * SLOT_BYTES, pv_acc, pv_mode);
            if (w == 0 || v == 0) token_pass(w);
            const uint32_t vslot = cur.slot;
            cur.adv();
            if (v) {
                row_inv(l, inv);
                wg_wait<0>();
                release(c, BAR_EMPTY + 8 * vslot, 1);
                fence_regs(o);
                tile_out(out, g_ctx + (size_t)((2 * team + 1) * 32 + 4 * k + (w ? 3 - (rank ^ SWAPT) : rank ^ SWAPT)) * 16384, 0, 2, c);
#pragma unroll
                for (int i = 0; i < 64; i++) wf[i] = 0u;
                continue;
            }
            cw = cur_at(80);
            mbar_wait_hot(misc + BAR_FULL + 8 * slot_of(76), cur_at(76).ph);
            mbar_wait_hot(misc + BAR_FULL + 8 * slot_of(78), cur_at(78).ph);
            load_afrag<8, 32>(wf, ring + slot_of(78) * SLOT_BYTES + w * 16384, c);
            const uint32_t z = load_afrag<8, 0>(wf, ring + slot_of(76) * SLOT_BYTES + w * 16384, c);
            row_inv(l, inv);
            release(c, BAR_EMPTY + 8 * slot_of(76) + z, 1);
            asm volatile("{\n.reg .pred p;\nsetp.eq.u32 p, %0, 0;\n@p bar.sync 4, 128;\n@!p bar.sync 5, 128;\n}\n" ::"r"(w) : "memory");
            wg_wait<0>();
            release(c, BAR_EMPTY + 8 * vslot, 1);
            fence_regs(o);
            {
                const int g = c.lane >> 2, r7 = ((g & 1) << 2) | (g >> 1);
                const uint32_t base = ring + slot_of(78) * SLOT_BYTES + w * 16384 + (16 * c.warp + r7) * 128 + (((c.lane & 3) ^ r7) << 4);
#pragma unroll
                for (int i = 0; i < 2; i++)
#pragma unroll
                    for (int qq = 0; qq < 4; qq++)
                        asm volatile("st.shared.v4.b32 [%0], {%1,%2,%3,%4};" ::"r"((base ^ ((qq & 1) << 6)) + (qq >> 1) * 8192 + i * 1024),
                                     "r"(pack_bf16(o[16 * qq + 2 * i] * inv[i], o[16 * qq + 2 * i + 1] * inv[i])),
                                     "r"(pack_bf16(o[16 * qq + 4 + 2 * i] * inv[i], o[16 * qq + 4 + 2 * i + 1] * inv[i])),
                                     "r"(pack_bf16(o[16 * qq + 8 + 2 * i] * inv[i], o[16 * qq + 8 + 2 * i + 1] * inv[i])),
                                     "r"(pack_bf16(o[16 * qq + 12 + 2 * i] * inv[i], o[16 * qq + 12 + 2 * i + 1] * inv[i])) : "memory");
                asm volatile("fence.proxy.async.shared::cta;" ::: "memory");
                signal_event(c, EV_CTX + 1);
            }
        }
        }
        {
            float acc[80];
            undef_regs(acc);
            int st = 0, prev = 0; uint32_t ph3 = 0;
            auto op_stage = [&](int i) {
                mbar_wait(misc + BAR_FULL3 + 8 * st, ph3);
                PROF_EV(44);
                uint32_t base = ring + st * ST3_BYTES;
                uint64_t da = mkdesc(base + w * 8192, 16, 1024, 1);
                uint64_t db = mkdesc(base + 16384, 2048, 512, 2);
                wg_fence();
#pragma unroll
                for (int k = 0; k < 4; k++) wgmma_ss_n160_ta0_tb1(acc, da + 2 * k, db + (k >> 1) * 640 + (k & 1) * 64, k ? 1 : i);
                wg_commit();
                if (i > 0) { wg_wait<1>(); if (i <= 32 - NST3) release(c, BAR_EMPTY3 + 8 * prev, 1); }
                prev = st;
                if (++st == NST3) { st = 0; ph3 ^= 1; }
            };
            PROF_EV(40); PROF_GT(65);
#pragma unroll
            for (int i = 0; i < 4; i++) { op_stage(i); store_pair(o, i, out, 8192, inv); }
            signal_event(c, EV_CTX + 3);
#pragma unroll 1
            for (int i = 4; i < 12; i++) op_stage(i);
            mbar_wait(misc + BAR_SEL, 0);
            const uint32_t tag = lds32(misc + MISC_EPOCH) & 1;
            const int g = c.lane >> 2, t = c.lane & 3;
            const int row = (2 * u3 + rank) * 128 + 64 * w + perm32(16 * c.warp + 8 * kap + (((g & 3) << 1) | (g >> 2)));
            const int col = 160 * s3 + 8 * t;
            int sel = -1;
#pragma unroll
            for (int i = 0; i < TOPC; i++) if ((int)lds32(misc + MISC_SEL + 4 * i) == row) sel = i;
            const int t256 = tid - 128;
            uint4* sendp = g_part + (size_t)cta * 2560 + t256;
            if (c.lane >= 30) stg128(sendp + 9 * 256, tag ^ 1, tag ^ 1, tag ^ 1, tag ^ 1);
#pragma unroll 1
            for (int i = 12; i < 32; i++) op_stage(i);
            uint4 xv[5], bv[5];
#pragma unroll
            for (int i = 0; i < 5; i++) xv[i] = ldg128(P.x + (size_t)row * DM + col + 32 * i);
            uint2 stat;
            asm volatile("ld.global.cg.v2.b32 {%0,%1}, [%2];" : "=r"(stat.x), "=r"(stat.y) : "l"(g_stats + row) : "memory");
            wg_wait<0>();
            fence_regs(acc);
            PROF_EV(41); PROF_GT(66);
            float keep[40];
#pragma unroll
            for (int j = 0; j < 10; j++) {
                uint32_t v0 = __float_as_uint(kap ? acc[8 * j + 0] : acc[8 * j + 2]), v1 = __float_as_uint(kap ? acc[8 * j + 1] : acc[8 * j + 3]);
                uint32_t v2 = __float_as_uint(kap ? acc[8 * j + 4] : acc[8 * j + 6]), v3 = __float_as_uint(kap ? acc[8 * j + 5] : acc[8 * j + 7]);
                asm volatile("st.relaxed.gpu.global.v4.b32 [%0], {%1,%2,%3,%4};" ::"l"(sendp + j * 256),
                             "r"((v0 & ~1u) | tag), "r"((v1 & ~1u) | tag), "r"((v2 & ~1u) | tag), "r"((v3 & ~1u) | tag) : "memory");
                keep[4 * j + 0] = kap ? acc[8 * j + 2] : acc[8 * j + 0]; keep[4 * j + 1] = kap ? acc[8 * j + 3] : acc[8 * j + 1];
                keep[4 * j + 2] = kap ? acc[8 * j + 6] : acc[8 * j + 4]; keep[4 * j + 3] = kap ? acc[8 * j + 7] : acc[8 * j + 5];
            }
            PROF_GT(67);
#pragma unroll
            for (int i = 0; i < 5; i++) {
                uint32_t xx[4] = {xv[i].x, xv[i].y, xv[i].z, xv[i].w};
#pragma unroll
                for (int e = 0; e < 4; e++) {
                    asm("sub.rn.bf16x2 %0, %0, %1;" : "+r"(xx[e]) : "r"(stat.x));
                    xx[e] = pack_bf16(bf_lo(xx[e]) * __uint_as_float(stat.y), bf_hi(xx[e]) * __uint_as_float(stat.y));
                }
                bv[i] = make_uint4(xx[0], xx[1], xx[2], xx[3]);
            }
            if (sel >= 0) {
#pragma unroll
                for (int i = 0; i < 5; i++) bv[i] = ldg128(g_brow + sel * DM + col + 32 * i);
            }
            const uint4* recvp = g_part + (size_t)partner * 2560 + t256;
            uint4 rv[10];
            int spins = 0;
            while (POLL1) {
                uint32_t v;
                asm volatile("ld.relaxed.gpu.global.b32 %0, [%1];" : "=r"(v) : "l"(recvp + 9 * 256 + (31 - c.lane)) : "memory");
                if (__all_sync(0xffffffffu, (v & 1u) == tag) || ++spins > 2000000) break;
            }
            PROF_GT(68);
            while (true) {
                uint32_t bad = 0u;
#pragma unroll
                for (int j = 0; j < 10; j++) {
                    asm volatile("ld.relaxed.gpu.global.v4.b32 {%0,%1,%2,%3}, [%4];"
                                 : "=r"(rv[j].x), "=r"(rv[j].y), "=r"(rv[j].z), "=r"(rv[j].w) : "l"(recvp + j * 256) : "memory");
                }
#pragma unroll
                for (int j = 0; j < 10; j++) {
                    rv[j].x ^= tag; rv[j].y ^= tag; rv[j].z ^= tag; rv[j].w ^= tag;
                    bad |= rv[j].x | rv[j].y | rv[j].z | rv[j].w;
                }
                if (__all_sync(0xffffffffu, (bad & 1u) == 0) || ++spins > 2000000) break;
            }
            PROF_GT(69);
            uint32_t pk[20];
#pragma unroll
            for (int j = 0; j < 10; j++) {
                pk[2 * j] = pack_bf16(keep[4 * j] + __uint_as_float(rv[j].x), keep[4 * j + 1] + __uint_as_float(rv[j].y));
                pk[2 * j + 1] = pack_bf16(keep[4 * j + 2] + __uint_as_float(rv[j].z), keep[4 * j + 3] + __uint_as_float(rv[j].w));
            }
#pragma unroll
            for (int i = 0; i < 5; i++) {
                uint32_t a0 = pk[4 * i], a1 = pk[4 * i + 1], a2 = pk[4 * i + 2], a3 = pk[4 * i + 3];
                uint32_t x0 = (t & 1) ? a0 : a1, x1 = (t & 1) ? a2 : a3;
                x0 = __shfl_xor_sync(0xffffffffu, x0, 1); x1 = __shfl_xor_sync(0xffffffffu, x1, 1);
                if (t & 1) { a0 = x0; a2 = x1; } else { a1 = x0; a3 = x1; }
                x0 = (t & 2) ? a0 : a2; x1 = (t & 2) ? a1 : a3;
                x0 = __shfl_xor_sync(0xffffffffu, x0, 2); x1 = __shfl_xor_sync(0xffffffffu, x1, 2);
                if (t & 2) { a0 = x0; a1 = x1; } else { a2 = x0; a3 = x1; }
                uint32_t av[4] = {a0, a1, a2, a3};
                uint32_t xx[4] = {xv[i].x, xv[i].y, xv[i].z, xv[i].w}, bb[4] = {bv[i].x, bv[i].y, bv[i].z, bv[i].w};
                uint32_t ov[4];
#pragma unroll
                for (int e = 0; e < 4; e++) {
                    asm("add.rn.bf16x2 %0, %1, %2;" : "=r"(ov[e]) : "r"(xx[e]), "r"(av[e]));
                    asm("add.rn.bf16x2 %0, %0, %1;" : "+r"(ov[e]) : "r"(bb[e]));
                }
                stg128(P.out + (size_t)row * DM + col + 32 * i, ov[0], ov[1], ov[2], ov[3]);
            }
            PROF_EV(42); PROF_GT(43);
        }
    }
}

typedef CUresult (*EncodeFn)(CUtensorMap*, CUtensorMapDataType, cuuint32_t, void*, const cuuint64_t*, const cuuint64_t*, const cuuint32_t*,
                             const cuuint32_t*, CUtensorMapInterleave, CUtensorMapSwizzle, CUtensorMapL2promotion, CUtensorMapFloatOOBfill);

void make_map2d(EncodeFn enc, CUtensorMap* tm, const void* p, uint64_t cols, uint64_t rows, uint32_t box_rows = 128) {
    cuuint64_t gd[2] = {cols, rows}, gs[1] = {cols * 2};
    cuuint32_t box[2] = {64, box_rows}, es[2] = {1, 1};
    enc(tm, CU_TENSOR_MAP_DATA_TYPE_BFLOAT16, 2, const_cast<void*>(p), gd, gs, box, es, CU_TENSOR_MAP_INTERLEAVE_NONE,
        CU_TENSOR_MAP_SWIZZLE_128B, CU_TENSOR_MAP_L2_PROMOTION_L2_128B, CU_TENSOR_MAP_FLOAT_OOB_FILL_NONE);
}

void make_map3d(EncodeFn enc, CUtensorMap* tm, const void* p, uint64_t cols, uint64_t rows, uint32_t bw, uint32_t nb) {
    cuuint64_t gd[3] = {bw, rows, cols / bw}, gs[2] = {cols * 2, bw * 2};
    cuuint32_t box[3] = {bw, 32, nb}, es[3] = {1, 1, 1};
    enc(tm, CU_TENSOR_MAP_DATA_TYPE_BFLOAT16, 3, const_cast<void*>(p), gd, gs, box, es, CU_TENSOR_MAP_INTERLEAVE_NONE,
        bw == 64 ? CU_TENSOR_MAP_SWIZZLE_128B : CU_TENSOR_MAP_SWIZZLE_64B, CU_TENSOR_MAP_L2_PROMOTION_L2_128B, CU_TENSOR_MAP_FLOAT_OOB_FILL_NONE);
}

}

extern "C" void kernel_launch(void* const* d_in, const int* in_sizes, int n_in, void* d_out, int out_size) {
    (void)in_sizes; (void)n_in; (void)out_size;
    static EncodeFn enc = nullptr;
    if (!enc) {
        void* fn = nullptr;
        cudaDriverEntryPointQueryResult qr;
        cudaGetDriverEntryPoint("cuTensorMapEncodeTiled", &fn, cudaEnableDefault, &qr);
        enc = (EncodeFn)fn;
        cudaFuncSetAttribute(fused_kernel, cudaFuncAttributeMaxDynamicSharedMemorySize, SMEM_BYTES);
    }
    CUtensorMap tmC, tmWk, tmWv, tmWq, tmWo, tmG, tmU, tmD;
    make_map2d(enc, &tmC, d_in[1], DC, SEQ);
    make_map2d(enc, &tmWq, d_in[2], 4096, DM, 64);
    make_map2d(enc, &tmWk, d_in[3], 4096, DC);
    make_map2d(enc, &tmWv, d_in[4], 4096, DC);
    make_map3d(enc, &tmWo, d_in[5], DM, 4096, 32, 5);
    make_map3d(enc, &tmG, d_in[8], FF, DM, 64, 7);
    make_map3d(enc, &tmU, d_in[9], FF, DM, 64, 7);
    make_map3d(enc, &tmD, d_in[10], DM, FF, 64, 10);
    Params P;
    P.x = (const __nv_bfloat16*)d_in[0];
    P.c = (const __nv_bfloat16*)d_in[1];
    P.wk = (const __nv_bfloat16*)d_in[3];
    P.wv = (const __nv_bfloat16*)d_in[4];
    P.wo = (const __nv_bfloat16*)d_in[5];
    P.wr = (const __nv_bfloat16*)d_in[7];
    P.out = (__nv_bfloat16*)d_out;
    fused_kernel<<<132, 384, SMEM_BYTES>>>(tmC, tmWk, tmWv, tmWq, tmWo, tmG, tmU, tmD, P);
}
```

```cpp
#include <cuda_runtime.h>
#include <cuda_bf16.h>
#include <cuda.h>
#include <stdint.h>

#define SWAPT 1
#define DEFER 1
#define HOLD0 6
#define KW 0
#define QS 0
#define PREW 0
#define HM 513
#define POLL1 1
#define OP_PF 8
#define PF_START 9
#define LATE_AT 18
#define CDELAY 500
#define AUXDELAY 1000
namespace {

constexpr int SEQ = 2048, NH = 32, DM = 640, DC = 512, FF = 1728, TOPC = 8;
constexpr int NSLOT = 7, SLOT_BYTES = 32768;
constexpr int NST3 = 6, ST3_BYTES = 36864;
constexpr int RING_BYTES = NSLOT * SLOT_BYTES;
constexpr int SMEM_BYTES = RING_BYTES + 3072;

constexpr int BAR_FULL = 96  , BAR_FULL3 = 152  , BAR_DEP = 200  , BAR_SEL = 464,
              BAR_LN = 472  , BAR_EV = 504  , BAR_EMPTY = 760  , BAR_EMPTY3 = 816  ,
              BAR_PROG = 864  , MISC_EPOCH = 896, MISC_SMID = 900  , MISC_SEL = 912, MISC_WR = 1024  ;
constexpr int D_LN = 0  , D_KV = 4  , D_WAR = 14  , D_CTX = 16  ;
constexpr int EV_KV = 0  , EV_CTX = 12  ;

constexpr int FL_MOE_CNT = 0, FL_MOE_DONE = 1, FL_LN = 16  , FL_KV = 32  , FL_CTX = 416  , FL_WAR = 672  , FL_TOTAL = 704;

__device__ __align__(1024) unsigned char g_K[16 * 32 * 16384];
__device__ __align__(1024) unsigned char g_V[16 * 32 * 16384];
__device__ __align__(1024) unsigned char g_ctx[NH * 32 * 16384];
__device__ __align__(1024) unsigned char g_xn[16 * 10 * 16384];
__device__ __align__(1024) uint4 g_part[128 * 10 * 256];
__device__ float g_router[SEQ];
__device__ uint2 g_stats[SEQ];
__device__ __align__(16) float g_moe_part[4 * TOPC * DM];
__device__ __align__(16) __nv_bfloat16 g_brow[TOPC * DM];
__device__ __align__(16) int g_sel[TOPC];
__device__ unsigned g_flags[FL_TOTAL * 8];
__device__ unsigned g_epoch;
__device__ unsigned g_roleq[130];

struct Params {
    const __nv_bfloat16 *x, *c, *wr, *wk, *wv, *wo;
    __nv_bfloat16* out;
};

__device__ __forceinline__ uint32_t smem_u32(const void* p) { return (uint32_t)__cvta_generic_to_shared(p); }
__device__ __forceinline__ void mbar_init(uint32_t bar, int cnt) { asm volatile("mbarrier.init.shared::cta.b64 [%0], %1;" ::"r"(bar), "r"(cnt)); }
__device__ __forceinline__ void mbar_expect_tx(uint32_t bar, uint32_t bytes) {
    asm volatile("mbarrier.arrive.expect_tx.shared::cta.b64 _, [%0], %1;" ::"r"(bar), "r"(bytes) : "memory");
}
__device__ __forceinline__ void mbar_arrive(uint32_t bar) { asm volatile("mbarrier.arrive.shared::cta.b64 _, [%0];" ::"r"(bar) : "memory"); }
__device__ __forceinline__ void mbar_arrive_cluster(uint32_t cluster_addr, uint32_t cnt) {
    asm volatile("mbarrier.arrive.shared::cluster.b64 _, [%0], %1;" ::"r"(cluster_addr), "r"(cnt) : "memory");
}
__device__ __forceinline__ uint32_t mapa(uint32_t addr, uint32_t cta) {
    uint32_t r; asm("mapa.shared::cluster.u32 %0, %1, %2;" : "=r"(r) : "r"(addr), "r"(cta)); return r;
}
__device__ __forceinline__ void mbar_wait(uint32_t bar, uint32_t parity) {
    asm volatile(
        "{\n.reg .pred p;\n.reg .u32 n;\n"
        "mbarrier.try_wait.parity.shared::cta.b64 p, [%0], %1;\n"
        "@p bra DONE;\n"
        "mov.u32 n, 0;\n"
        "LAB_WAIT:\n"
        "mbarrier.try_wait.parity.shared::cta.b64 p, [%0], %1, 100000;\n"
        "@p bra DONE;\n"
        "add.u32 n, n, 1;\n"
        "setp.lt.u32 p, n, 200000;\n"
        "@p bra LAB_WAIT;\n"
        "trap;\n"
        "DONE:\n}\n" ::"r"(bar), "r"(parity) : "memory");
}
__device__ __forceinline__ void mbar_wait_hot(uint32_t bar, uint32_t parity) {
    asm volatile("{\n.reg .pred p;\nLAB_WAIT:\nmbarrier.try_wait.parity.shared::cta.b64 p, [%0], %1;\n@!p bra LAB_WAIT;\n}\n" ::"r"(bar), "r"(parity) : "memory");
}
__device__ __forceinline__ void flag_wait(const unsigned* flag, unsigned target) {
    asm volatile(
        "{\n.reg .pred p;\n.reg .u32 n, v;\n.reg .s32 d;\n"
        "mov.u32 n, 0;\n"
        "LAB_WAIT:\n"
        "ld.acquire.gpu.global.u32 v, [%0];\n"
        "sub.s32 d, v, %1;\n"
        "setp.ge.s32 p, d, 0;\n"
        "@p bra DONE;\n"
        "nanosleep.u32 40;\n"
        "add.u32 n, n, 1;\n"
        "setp.lt.u32 p, n, 3000000;\n"
        "@p bra LAB_WAIT;\n"
        "trap;\n"
        "DONE:\n}\n" ::"l"(flag), "r"(target) : "memory");
}
__device__ __forceinline__ void flag_signal(unsigned* flag) {
    asm volatile("red.release.gpu.global.add.u32 [%0], 1;" ::"l"(flag) : "memory");
}
__device__ __forceinline__ void fence_async_global() { asm volatile("fence.proxy.async.global;" ::: "memory"); }
__device__ __forceinline__ unsigned* flag_ptr(int idx) { return g_flags + idx * 8; }

__device__ __forceinline__ uint64_t policy_stream() {
    uint64_t p; asm("createpolicy.fractional.L2::evict_first.b64 %0, 1.0;" : "=l"(p)); return p;
}
__device__ __forceinline__ uint64_t policy_normal() { return 0x1000000000000000ull; }
__device__ __forceinline__ uint64_t policy(bool stream) { return stream ? policy_stream() : policy_normal(); }
__device__ __forceinline__ void bulk_load(uint32_t dst, const void* src, uint32_t bytes, uint32_t bar, uint64_t pol) {
    asm volatile("cp.async.bulk.shared::cluster.global.mbarrier::complete_tx::bytes.L2::cache_hint [%0], [%1], %2, [%3], %4;"
                 ::"r"(dst), "l"(src), "r"(bytes), "r"(bar), "l"(pol) : "memory");
}
__device__ __forceinline__ void bulk_load_mc(uint32_t dst, const void* src, uint32_t bytes, uint32_t bar, uint64_t pol) {
    asm volatile("cp.async.bulk.shared::cluster.global.mbarrier::complete_tx::bytes.multicast::cluster.L2::cache_hint [%0], [%1], %2, [%3], %4, %5;"
                 ::"r"(dst), "l"(src), "r"(bytes), "r"(bar), "h"((uint16_t)3), "l"(pol) : "memory");
}
__device__ __forceinline__ void tma2d(uint32_t dst, const CUtensorMap* tm, int c0, int c1, uint32_t bar, uint64_t pol) {
    asm volatile("cp.async.bulk.tensor.2d.shared::cluster.global.mbarrier::complete_tx::bytes.L2::cache_hint [%0], [%1, {%3, %4}], [%2], %5;"
                 ::"r"(dst), "l"(tm), "r"(bar), "r"(c0), "r"(c1), "l"(pol) : "memory");
}
__device__ __forceinline__ void tma2d_mc(uint32_t dst, const CUtensorMap* tm, int c0, int c1, uint32_t bar, uint64_t pol) {
    asm volatile("cp.async.bulk.tensor.2d.shared::cluster.global.mbarrier::complete_tx::bytes.multicast::cluster.L2::cache_hint [%0], [%1, {%3, %4}], [%2], %5, %6;"
                 ::"r"(dst), "l"(tm), "r"(bar), "r"(c0), "r"(c1), "h"((uint16_t)3), "l"(pol) : "memory");
}
__device__ __forceinline__ void tma3d_mc(uint32_t dst, const CUtensorMap* tm, int c0, int c1, int c2, uint32_t bar, uint64_t pol) {
    asm volatile("cp.async.bulk.tensor.3d.shared::cluster.global.mbarrier::complete_tx::bytes.multicast::cluster.L2::cache_hint [%0], [%1, {%3, %4, %5}], [%2], %6, %7;"
                 ::"r"(dst), "l"(tm), "r"(bar), "r"(c0), "r"(c1), "r"(c2), "h"((uint16_t)3), "l"(pol) : "memory");
}
__device__ __forceinline__ void tma3d(uint32_t dst, const CUtensorMap* tm, int c0, int c1, int c2, uint32_t bar) {
    asm volatile("cp.async.bulk.tensor.3d.shared::cluster.global.mbarrier::complete_tx::bytes.L2::cache_hint [%0], [%1, {%3, %4, %5}], [%2], %6;"
                 ::"r"(dst), "l"(tm), "r"(bar), "r"(c0), "r"(c1), "r"(c2), "l"(policy_stream()) : "memory");
}
__device__ __forceinline__ void tma2d_prefetch(const CUtensorMap* tm, int c0, int c1) {
    asm volatile("cp.async.bulk.prefetch.tensor.2d.L2.global [%0, {%1, %2}];" ::"l"(tm), "r"(c0), "r"(c1) : "memory");
}
__device__ __forceinline__ void tma3d_prefetch(const CUtensorMap* tm, int c0, int c1, int c2) {
    asm volatile("cp.async.bulk.prefetch.tensor.3d.L2.global [%0, {%1, %2, %3}];" ::"l"(tm), "r"(c0), "r"(c1), "r"(c2) : "memory");
}
__device__ __forceinline__ void l2_prefetch(const void* p, uint32_t bytes) {
    asm volatile("cp.async.bulk.prefetch.L2.global [%0], %1;" ::"l"(p), "r"(bytes) : "memory");
}
__device__ __forceinline__ bool elect_one() {
    uint32_t r; asm volatile("{\n.reg .pred p;\nelect.sync _|p, 0xffffffff;\nselp.u32 %0, 1, 0, p;\n}\n" : "=r"(r)); return r != 0;
}
__device__ __forceinline__ void wg_fence() { asm volatile("wgmma.fence.sync.aligned;" ::: "memory"); }
__device__ __forceinline__ void wg_commit() { asm volatile("wgmma.commit_group.sync.aligned;" ::: "memory"); }
template <int N> __device__ __forceinline__ void wg_wait() { asm volatile("wgmma.wait_group.sync.aligned %0;" ::"n"(N) : "memory"); }
__device__ __forceinline__ void bar_sync(int id, int n) { asm volatile("bar.sync %0, %1;" ::"r"(id), "r"(n) : "memory"); }
__device__ __forceinline__ void bar_arrive(int id, int n) { asm volatile("bar.arrive %0, %1;" ::"r"(id), "r"(n) : "memory"); }
__device__ __forceinline__ void token_wait(int w) {
    asm volatile("{\n.reg .pred p;\nsetp.eq.u32 p, %0, 0;\n@p bar.sync 1, 256;\n@!p bar.sync 2, 256;\n}\n" ::"r"(w) : "memory");
}
__device__ __forceinline__ void token_pass(int w) {
    asm volatile("{\n.reg .pred p;\nsetp.eq.u32 p, %0, 0;\n@p bar.arrive 2, 256;\n@!p bar.arrive 1, 256;\n}\n" ::"r"(w) : "memory");
}
template <int N> __device__ __forceinline__ void fence_regs(float (&a)[N]) {
#pragma unroll
    for (int i = 0; i < N; i++) asm volatile("" : "+f"(a[i])::"memory");
}
template <int N> __device__ __forceinline__ void undef_regs(float (&a)[N]) {
#pragma unroll
    for (int i = 0; i < N; i++) asm volatile("" : "=f"(a[i]));
}
__device__ __forceinline__ void ldsm4t(uint32_t& r0, uint32_t& r1, uint32_t& r2, uint32_t& r3, uint32_t addr) {
    asm volatile("ldmatrix.sync.aligned.m8n8.x4.trans.shared.b16 {%0,%1,%2,%3}, [%4];"
                 : "=r"(r0), "=r"(r1), "=r"(r2), "=r"(r3) : "r"(addr) : "memory");
}
__device__ __forceinline__ uint32_t pack_bf16(float lo, float hi) {
    uint32_t r; asm("cvt.rn.bf16x2.f32 %0, %1, %2;" : "=r"(r) : "f"(hi), "f"(lo)); return r;
}
__device__ __forceinline__ float bf_lo(uint32_t v) { return __uint_as_float(v << 16); }
__device__ __forceinline__ float bf_hi(uint32_t v) { return __uint_as_float(v & 0xffff0000u); }
__device__ __forceinline__ float bf_round(float v) { return __bfloat162float(__float2bfloat16_rn(v)); }
__device__ __forceinline__ float ex2(float v) { float r; asm("ex2.approx.ftz.f32 %0, %1;" : "=f"(r) : "f"(v)); return r; }
__device__ __forceinline__ void ex2v(float& v) { asm volatile("ex2.approx.ftz.f32 %0, %0;" : "+f"(v)); }
__device__ __forceinline__ float rcp_fast(float v) { float r; asm("rcp.approx.ftz.f32 %0, %1;" : "=f"(r) : "f"(v)); return r; }
__device__ __forceinline__ float sqrt_fast(float v) { float r; asm("sqrt.approx.ftz.f32 %0, %1;" : "=f"(r) : "f"(v)); return r; }
__device__ __forceinline__ void stg128(void* p, uint32_t a, uint32_t b, uint32_t c, uint32_t d) {
    asm volatile("st.global.v4.b32 [%0], {%1,%2,%3,%4};" ::"l"(p), "r"(a), "r"(b), "r"(c), "r"(d) : "memory");
}
__device__ __forceinline__ uint4 ldg128(const void* p) {
    uint4 v; asm volatile("ld.global.cg.v4.b32 {%0,%1,%2,%3}, [%4];" : "=r"(v.x), "=r"(v.y), "=r"(v.z), "=r"(v.w) : "l"(p) : "memory"); return v;
}
__device__ __forceinline__ uint64_t mkdesc(uint32_t addr, uint32_t lbo, uint32_t sbo, uint32_t swz) {
    uint32_t lo = ((addr & 0x3FFFF) >> 4) | ((lbo >> 4) << 16);
    uint32_t hi = (sbo >> 4) | (swz << 30);
    return ((uint64_t)hi << 32) | lo;
}
__device__ __forceinline__ int perm32(int v) { return (v & ~30) | ((v >> 2) & 6) | ((v << 2) & 24); }

__device__ __forceinline__ void wgmma_rs_n128_ta0_tb0(float (&d)[64], uint32_t a0, uint32_t a1, uint32_t a2, uint32_t a3, uint64_t descB, int scaleD) {
  asm volatile("{\n.reg .pred p;\nsetp.ne.b32 p, %69, 0;\n"
    "wgmma.mma_async.sync.aligned.m64n128k16.f32.bf16.bf16 "
    "{%0, %1, %2, %3, %4, %5, %6, %7, %8, %9, %10, %11, %12, %13, %14, %15, %16, %17, %18, %19, %20, %21, %22, %23, %24, %25, %26, %27, %28, %29, %30, %31, %32, %33, %34, %35, %36, %37, %38, %39, %40, %41, %42, %43, %44, %45, %46, %47, %48, %49, %50, %51, %52, %53, %54, %55, %56, %57, %58, %59, %60, %61, %62, %63}, "
    "{%64, %65, %66, %67}, %68, p, 1, 1, 0;\n}\n"
    : "+f"(d[0]), "+f"(d[1]), "+f"(d[2]), "+f"(d[3]), "+f"(d[4]), "+f"(d[5]), "+f"(d[6]), "+f"(d[7]), "+f"(d[8]), "+f"(d[9]), "+f"(d[10]), "+f"(d[11]), "+f"(d[12]), "+f"(d[13]), "+f"(d[14]), "+f"(d[15]), "+f"(d[16]), "+f"(d[17]), "+f"(d[18]), "+f"(d[19]), "+f"(d[20]), "+f"(d[21]), "+f"(d[22]), "+f"(d[23]), "+f"(d[24]), "+f"(d[25]), "+f"(d[26]), "+f"(d[27]), "+f"(d[28]), "+f"(d[29]), "+f"(d[30]), "+f"(d[31]), "+f"(d[32]), "+f"(d[33]), "+f"(d[34]), "+f"(d[35]), "+f"(d[36]), "+f"(d[37]), "+f"(d[38]), "+f"(d[39]), "+f"(d[40]), "+f"(d[41]), "+f"(d[42]), "+f"(d[43]), "+f"(d[44]), "+f"(d[45]), "+f"(d[46]), "+f"(d[47]), "+f"(d[48]), "+f"(d[49]), "+f"(d[50]), "+f"(d[51]), "+f"(d[52]), "+f"(d[53]), "+f"(d[54]), "+f"(d[55]), "+f"(d[56]), "+f"(d[57]), "+f"(d[58]), "+f"(d[59]), "+f"(d[60]), "+f"(d[61]), "+f"(d[62]), "+f"(d[63])
    : "r"(a0), "r"(a1), "r"(a2), "r"(a3), "l"(descB), "r"(scaleD));
}
__device__ __forceinline__ void wgmma_rs_n128_ta0_tb1(float (&d)[64], uint32_t a0, uint32_t a1, uint32_t a2, uint32_t a3, uint64_t descB, int scaleD) {
  asm volatile("{\n.reg .pred p;\nsetp.ne.b32 p, %69, 0;\n"
    "wgmma.mma_async.sync.aligned.m64n128k16.f32.bf16.bf16 "
    "{%0, %1, %2, %3, %4, %5, %6, %7, %8, %9, %10, %11, %12, %13, %14, %15, %16, %17, %18, %19, %20, %21, %22, %23, %24, %25, %26, %27, %28, %29, %30, %31, %32, %33, %34, %35, %36, %37, %38, %39, %40, %41, %42, %43, %44, %45, %46, %47, %48, %49, %50, %51, %52, %53, %54, %55, %56, %57, %58, %59, %60, %61, %62, %63}, "
    "{%64, %65, %66, %67}, %68, p, 1, 1, 1;\n}\n"
    : "+f"(d[0]), "+f"(d[1]), "+f"(d[2]), "+f"(d[3]), "+f"(d[4]), "+f"(d[5]), "+f"(d[6]), "+f"(d[7]), "+f"(d[8]), "+f"(d[9]), "+f"(d[10]), "+f"(d[11]), "+f"(d[12]), "+f"(d[13]), "+f"(d[14]), "+f"(d[15]), "+f"(d[16]), "+f"(d[17]), "+f"(d[18]), "+f"(d[19]), "+f"(d[20]), "+f"(d[21]), "+f"(d[22]), "+f"(d[23]), "+f"(d[24]), "+f"(d[25]), "+f"(d[26]), "+f"(d[27]), "+f"(d[28]), "+f"(d[29]), "+f"(d[30]), "+f"(d[31]), "+f"(d[32]), "+f"(d[33]), "+f"(d[34]), "+f"(d[35]), "+f"(d[36]), "+f"(d[37]), "+f"(d[38]), "+f"(d[39]), "+f"(d[40]), "+f"(d[41]), "+f"(d[42]), "+f"(d[43]), "+f"(d[44]), "+f"(d[45]), "+f"(d[46]), "+f"(d[47]), "+f"(d[48]), "+f"(d[49]), "+f"(d[50]), "+f"(d[51]), "+f"(d[52]), "+f"(d[53]), "+f"(d[54]), "+f"(d[55]), "+f"(d[56]), "+f"(d[57]), "+f"(d[58]), "+f"(d[59]), "+f"(d[60]), "+f"(d[61]), "+f"(d[62]), "+f"(d[63])
    : "r"(a0), "r"(a1), "r"(a2), "r"(a3), "l"(descB), "r"(scaleD));
}
__device__ __forceinline__ void wgmma_rs_n64_ta0_tb1(float (&d)[32], uint32_t a0, uint32_t a1, uint32_t a2, uint32_t a3, uint64_t descB, int scaleD) {
  asm volatile("{\n.reg .pred p;\nsetp.ne.b32 p, %37, 0;\n"
    "wgmma.mma_async.sync.aligned.m64n64k16.f32.bf16.bf16 "
    "{%0, %1, %2, %3, %4, %5, %6, %7, %8, %9, %10, %11, %12, %13, %14, %15, %16, %17, %18, %19, %20, %21, %22, %23, %24, %25, %26, %27, %28, %29, %30, %31}, "
    "{%32, %33, %34, %35}, %36, p, 1, 1, 1;\n}\n"
    : "+f"(d[0]), "+f"(d[1]), "+f"(d[2]), "+f"(d[3]), "+f"(d[4]), "+f"(d[5]), "+f"(d[6]), "+f"(d[7]), "+f"(d[8]), "+f"(d[9]), "+f"(d[10]), "+f"(d[11]), "+f"(d[12]), "+f"(d[13]), "+f"(d[14]), "+f"(d[15]), "+f"(d[16]), "+f"(d[17]), "+f"(d[18]), "+f"(d[19]), "+f"(d[20]), "+f"(d[21]), "+f"(d[22]), "+f"(d[23]), "+f"(d[24]), "+f"(d[25]), "+f"(d[26]), "+f"(d[27]), "+f"(d[28]), "+f"(d[29]), "+f"(d[30]), "+f"(d[31])
    : "r"(a0), "r"(a1), "r"(a2), "r"(a3), "l"(descB), "r"(scaleD));
}
__device__ __forceinline__ void wgmma_ss_n128_ta0_tb1(float (&d)[64], uint64_t descA, uint64_t descB, int scaleD) {
  asm volatile("{\n.reg .pred p;\nsetp.ne.b32 p, %66, 0;\n"
    "wgmma.mma_async.sync.aligned.m64n128k16.f32.bf16.bf16 "
    "{%0, %1, %2, %3, %4, %5, %6, %7, %8, %9, %10, %11, %12, %13, %14, %15, %16, %17, %18, %19, %20, %21, %22, %23, %24, %25, %26, %27, %28, %29, %30, %31, %32, %33, %34, %35, %36, %37, %38, %39, %40, %41, %42, %43, %44, %45, %46, %47, %48, %49, %50, %51, %52, %53, %54, %55, %56, %57, %58, %59, %60, %61, %62, %63}, "
    "%64, %65, p, 1, 1, 0, 1;\n}\n"
    : "+f"(d[0]), "+f"(d[1]), "+f"(d[2]), "+f"(d[3]), "+f"(d[4]), "+f"(d[5]), "+f"(d[6]), "+f"(d[7]), "+f"(d[8]), "+f"(d[9]), "+f"(d[10]), "+f"(d[11]), "+f"(d[12]), "+f"(d[13]), "+f"(d[14]), "+f"(d[15]), "+f"(d[16]), "+f"(d[17]), "+f"(d[18]), "+f"(d[19]), "+f"(d[20]), "+f"(d[21]), "+f"(d[22]), "+f"(d[23]), "+f"(d[24]), "+f"(d[25]), "+f"(d[26]), "+f"(d[27]), "+f"(d[28]), "+f"(d[29]), "+f"(d[30]), "+f"(d[31]), "+f"(d[32]), "+f"(d[33]), "+f"(d[34]), "+f"(d[35]), "+f"(d[36]), "+f"(d[37]), "+f"(d[38]), "+f"(d[39]), "+f"(d[40]), "+f"(d[41]), "+f"(d[42]), "+f"(d[43]), "+f"(d[44]), "+f"(d[45]), "+f"(d[46]), "+f"(d[47]), "+f"(d[48]), "+f"(d[49]), "+f"(d[50]), "+f"(d[51]), "+f"(d[52]), "+f"(d[53]), "+f"(d[54]), "+f"(d[55]), "+f"(d[56]), "+f"(d[57]), "+f"(d[58]), "+f"(d[59]), "+f"(d[60]), "+f"(d[61]), "+f"(d[62]), "+f"(d[63])
    : "l"(descA), "l"(descB), "r"(scaleD));
}
__device__ __forceinline__ void wgmma_ss_n160_ta0_tb1(float (&d)[80], uint64_t descA, uint64_t descB, int scaleD) {
  asm volatile("{\n.reg .pred p;\nsetp.ne.b32 p, %82, 0;\n"
    "wgmma.mma_async.sync.aligned.m64n160k16.f32.bf16.bf16 "
    "{%0, %1, %2, %3, %4, %5, %6, %7, %8, %9, %10, %11, %12, %13, %14, %15, %16, %17, %18, %19, %20, %21, %22, %23, %24, %25, %26, %27, %28, %29, %30, %31, %32, %33, %34, %35, %36, %37, %38, %39, %40, %41, %42, %43, %44, %45, %46, %47, %48, %49, %50, %51, %52, %53, %54, %55, %56, %57, %58, %59, %60, %61, %62, %63, %64, %65, %66, %67, %68, %69, %70, %71, %72, %73, %74, %75, %76, %77, %78, %79}, "
    "%80, %81, p, 1, 1, 0, 1;\n}\n"
    : "+f"(d[0]), "+f"(d[1]), "+f"(d[2]), "+f"(d[3]), "+f"(d[4]), "+f"(d[5]), "+f"(d[6]), "+f"(d[7]), "+f"(d[8]), "+f"(d[9]), "+f"(d[10]), "+f"(d[11]), "+f"(d[12]), "+f"(d[13]), "+f"(d[14]), "+f"(d[15]), "+f"(d[16]), "+f"(d[17]), "+f"(d[18]), "+f"(d[19]), "+f"(d[20]), "+f"(d[21]), "+f"(d[22]), "+f"(d[23]), "+f"(d[24]), "+f"(d[25]), "+f"(d[26]), "+f"(d[27]), "+f"(d[28]), "+f"(d[29]), "+f"(d[30]), "+f"(d[31]), "+f"(d[32]), "+f"(d[33]), "+f"(d[34]), "+f"(d[35]), "+f"(d[36]), "+f"(d[37]), "+f"(d[38]), "+f"(d[39]), "+f"(d[40]), "+f"(d[41]), "+f"(d[42]), "+f"(d[43]), "+f"(d[44]), "+f"(d[45]), "+f"(d[46]), "+f"(d[47]), "+f"(d[48]), "+f"(d[49]), "+f"(d[50]), "+f"(d[51]), "+f"(d[52]), "+f"(d[53]), "+f"(d[54]), "+f"(d[55]), "+f"(d[56]), "+f"(d[57]), "+f"(d[58]), "+f"(d[59]), "+f"(d[60]), "+f"(d[61]), "+f"(d[62]), "+f"(d[63]), "+f"(d[64]), "+f"(d[65]), "+f"(d[66]), "+f"(d[67]), "+f"(d[68]), "+f"(d[69]), "+f"(d[70]), "+f"(d[71]), "+f"(d[72]), "+f"(d[73]), "+f"(d[74]), "+f"(d[75]), "+f"(d[76]), "+f"(d[77]), "+f"(d[78]), "+f"(d[79])
    : "l"(descA), "l"(descB), "r"(scaleD));
}

#define PROF_DECL(b)
#define PROF_EV(tag)
#define PROF_GT(tag)

template <int N> struct IC { static constexpr int value = N; };
struct Cur {
    uint32_t slot, ph;
    __device__ __forceinline__ void adv() { if (++slot == NSLOT) { slot = 0; ph ^= 1; } }
};
constexpr int E0 = 2;
__host__ __device__ constexpr uint32_t slot_of(int e) { return (e + E0) % NSLOT; }
__device__ __forceinline__ Cur cur_at(int e) { Cur c; c.slot = (e + E0) % NSLOT; c.ph = ((e + E0) / NSLOT) & 1; return c; }

__device__ __forceinline__ int op_head(int i, int kap) { return 16 * kap + 2 * (i & 7) + (i >> 3); }

constexpr float SM_SCALE = 0.08838834764831845f * 1.4426950408889634f;

struct Ctx {
    uint32_t ring, misc;
    uint32_t rel;
    int w, warp, lane;
};
__device__ __forceinline__ void release(const Ctx& c, uint32_t off, uint32_t cnt) {
    if (c.lane < 2) mbar_arrive_cluster(c.rel + off, cnt);
}
__device__ __forceinline__ void signal_event(const Ctx& c, int ev) {
    __syncwarp();
    if (c.lane == 0) mbar_arrive(c.misc + BAR_EV + (c.w * 16 + ev) * 8);
}
template <int NK, int OFF, int N>
__device__ __forceinline__ uint32_t load_afrag(uint32_t (&a)[N], uint32_t base, const Ctx& c) {
    int r = c.lane & 7, mat = c.lane >> 3;
    uint32_t addr = base + (8 * (mat >> 1) + r) * 128 + (((2 * c.warp + (mat & 1)) ^ r) << 4);
#pragma unroll
    for (int k = 0; k < NK; k++) ldsm4t(a[OFF + 4 * k], a[OFF + 4 * k + 1], a[OFF + 4 * k + 2], a[OFF + 4 * k + 3], addr + k * 2048);
    uint32_t dep = 0;
#pragma unroll
    for (int k = 0; k < NK; k++) dep |= a[OFF + 4 * k];
    return dep & blockIdx.y;
}
__device__ __forceinline__ void tile_out(unsigned char* (&out)[2], unsigned char* dst, int row0, int perm, const Ctx& c) {
#pragma unroll
    for (int i = 0; i < 2; i++) {
        int g = c.lane >> 2;
        if (perm == 2) g = ((g & 1) << 2) | (g >> 1);
        int row = row0 + 16 * c.warp + 8 * i + g;
        if (perm == 1) row = perm32(row);
        out[i] = dst + row * 128 + (((c.lane & 3) ^ (row & 7)) << 4);
    }
}
__device__ __forceinline__ void store_pair(const float (&a)[64], int n, unsigned char* const (&out)[2], int half_stride, const float (&f)[2]) {
    const int i = n & 1;
#pragma unroll
    for (int q = 2 * (n >> 1); q < 2 * (n >> 1) + 2; q++)
        stg128(reinterpret_cast<unsigned char*>(reinterpret_cast<uint64_t>(out[i]) ^ ((q & 1) << 6)) + (q >> 1) * half_stride,
               pack_bf16(a[16 * q + 2 * i] * f[i], a[16 * q + 2 * i + 1] * f[i]), pack_bf16(a[16 * q + 4 + 2 * i] * f[i], a[16 * q + 4 + 2 * i + 1] * f[i]),
               pack_bf16(a[16 * q + 8 + 2 * i] * f[i], a[16 * q + 8 + 2 * i + 1] * f[i]), pack_bf16(a[16 * q + 12 + 2 * i] * f[i], a[16 * q + 12 + 2 * i + 1] * f[i]));
}

constexpr float SAFE_SUM = 1099511627776.0f;
template <int NJ>
__device__ __forceinline__ void row_max(const float (&s)[4 * NJ], float (&mx)[2]) {
#pragma unroll
    for (int i = 0; i < 2; i++) {
        float a = fmaxf(s[2 * i], s[2 * i + 1]), b = fmaxf(s[4 + 2 * i], s[4 + 2 * i + 1]);
#pragma unroll
        for (int j = 2; j < NJ; j += 2) {
            a = fmaxf(a, fmaxf(s[4 * j + 2 * i], s[4 * j + 2 * i + 1]));
            b = fmaxf(b, fmaxf(s[4 * j + 4 + 2 * i], s[4 * j + 4 + 2 * i + 1]));
        }
        a = fmaxf(a, b);
        a = fmaxf(a, __shfl_xor_sync(0xffffffffu, a, 1));
        mx[i] = fmaxf(a, __shfl_xor_sync(0xffffffffu, a, 2));
    }
}
template <int NJ, bool SHIFT>
__device__ __forceinline__ void exp_sum(float (&s)[4 * NJ], const float (&m)[2], float& l0, float& l1) {
#pragma unroll
    for (int j = 0; j < NJ; j++) {
#pragma unroll
        for (int e = 0; e < 4; e++) s[4 * j + e] = ex2(SHIFT ? s[4 * j + e] - m[e >> 1] : s[4 * j + e]);
        l0 += s[4 * j + 0] + s[4 * j + 1]; l1 += s[4 * j + 2] + s[4 * j + 3];
    }
}
__device__ __forceinline__ void recompute_scores(float (&s)[64], const uint32_t (&q)[32], uint32_t kaddr, const Ctx& c) {
    const int r = c.lane & 7, mat = c.lane >> 3;
    const uint32_t a0 = kaddr + (8 * (mat & 1) + r) * 128 + (((mat >> 1) ^ r) << 4);
#pragma unroll
    for (int i = 0; i < 64; i++) s[i] = 0.f;
#pragma unroll
    for (int jp = 0; jp < 8; jp++) {
#pragma unroll
        for (int k = 0; k < 8; k++) {
            asm volatile(
                "{\n.reg .b32 b0, b1, b2, b3;\n"
                "ldmatrix.sync.aligned.m8n8.x4.trans.shared.b16 {b0,b1,b2,b3}, [%12];\n"
                "mma.sync.aligned.m16n8k16.row.col.f32.bf16.bf16.f32 {%0,%1,%2,%3}, {%8,%9,%10,%11}, {b0,b1}, {%0,%1,%2,%3};\n"
                "mma.sync.aligned.m16n8k16.row.col.f32.bf16.bf16.f32 {%4,%5,%6,%7}, {%8,%9,%10,%11}, {b2,b3}, {%4,%5,%6,%7};\n}\n"
                : "+f"(s[8 * jp]), "+f"(s[8 * jp + 1]), "+f"(s[8 * jp + 2]), "+f"(s[8 * jp + 3]),
                  "+f"(s[8 * jp + 4]), "+f"(s[8 * jp + 5]), "+f"(s[8 * jp + 6]), "+f"(s[8 * jp + 7])
                : "r"(q[4 * k]), "r"(q[4 * k + 1]), "r"(q[4 * k + 2]), "r"(q[4 * k + 3]),
                  "r"((a0 ^ ((jp & 3) << 5)) + (jp >> 2) * 16384 + k * 2048) : "memory");
        }
    }
}
__device__ __forceinline__ int mask_lim(const Ctx& c) { return perm32(16 * c.warp + (c.lane >> 2)) - 8 * (c.lane & 3); }
template <int J0>
__device__ __forceinline__ void mask_diag(float (&s)[4 * J0 + 32], const Ctx& c) {
    const int lim = mask_lim(c);
    if (c.warp < 2) {
#pragma unroll
        for (int x = 0; x < 16; x++) {
            if (2 * (x >> 2) + (x & 1) - (x & 2) > lim) s[4 * J0 + x] = -INFINITY;
            s[4 * J0 + 16 + x] = -INFINITY;
        }
    } else {
#pragma unroll
        for (int x = 0; x < 16; x++)
            if (32 + 2 * (x >> 2) + (x & 1) - (x & 2) > lim) s[4 * J0 + 16 + x] = -INFINITY;
    }
}
__device__ __forceinline__ void mask_any(float (&s)[64], int hh, const Ctx& c) {
    const int lim = mask_lim(c) + 64 * hh;
#pragma unroll
    for (int x = 0; x < 64; x++)
        if (32 * (x >> 4) + 2 * ((x >> 2) & 3) + (x & 1) - (x & 2) > lim) s[x] = -INFINITY;
}
__device__ __forceinline__ void issue_pv(float (&o)[64], const uint32_t (&p)[32], uint32_t vaddr, int acc, int mode  ) {
    uint64_t d = mkdesc(vaddr, 16, 1024, 1);
    if (mode == 0) {
        wg_fence();
#pragma unroll
        for (int k = 0; k < 8; k++)
            wgmma_rs_n128_ta0_tb0(o, p[4 * k], p[4 * k + 1], p[4 * k + 2], p[4 * k + 3], d + (k >> 2) * 1024 + 2 * (k & 3), k ? 1 : acc);
        wg_commit();
    } else if (mode == 1) {
        wg_fence();
#pragma unroll
        for (int k = 0; k < 4; k++) wgmma_rs_n128_ta0_tb0(o, p[4 * k], p[4 * k + 1], p[4 * k + 2], p[4 * k + 3], d + 2 * k, k != 0);
        wg_commit();
    } else {
        wg_fence();
        wgmma_rs_n128_ta0_tb0(o, p[0], p[1], p[2], p[3], d, acc);
        wg_commit();
    }
}
__device__ __forceinline__ void issue_qk(float (&s)[64], const uint32_t (&q)[32], uint32_t kaddr) {
    uint64_t d = mkdesc(kaddr, 16384, 1024, 1);
    wg_fence();
#pragma unroll
    for (int k = 0; k < 8; k++) wgmma_rs_n128_ta0_tb1(s, q[4 * k], q[4 * k + 1], q[4 * k + 2], q[4 * k + 3], d + 128 * k, k != 0);
    wg_commit();
}
__device__ __forceinline__ void issue_qk_half(float (&s32)[32], const uint32_t (&q)[32], uint32_t kaddr) {
    uint64_t d = mkdesc(kaddr, 16384, 1024, 1);
    wg_fence();
#pragma unroll
    for (int k = 0; k < 8; k++) wgmma_rs_n64_ta0_tb1(s32, q[4 * k], q[4 * k + 1], q[4 * k + 2], q[4 * k + 3], d + 128 * k, k != 0);
    wg_commit();
}
__device__ __forceinline__ void row_inv(const float (&l)[2], float (&inv)[2]) {
#pragma unroll
    for (int i = 0; i < 2; i++) {
        float sum = l[i];
        sum += __shfl_xor_sync(0xffffffffu, sum, 1);
        sum += __shfl_xor_sync(0xffffffffu, sum, 2);
        inv[i] = rcp_fast(sum);
    }
}

__device__ __forceinline__ const unsigned char* xn_addr(int row, int col) {
    row = perm32(row);
    return g_xn + ((row >> 7) * 10 + (col >> 6)) * 16384 + (row & 127) * 128 + ((((col & 63) >> 3) ^ (row & 7)) << 4);
}
__device__ __forceinline__ void mma16816(float (&d)[4], uint32_t a0, uint32_t a1, uint32_t a2, uint32_t a3, uint32_t b0, uint32_t b1) {
    asm volatile("mma.sync.aligned.m16n8k16.row.col.f32.bf16.bf16.f32 {%0,%1,%2,%3}, {%4,%5,%6,%7}, {%8,%9}, {%0,%1,%2,%3};"
                 : "+f"(d[0]), "+f"(d[1]), "+f"(d[2]), "+f"(d[3]) : "r"(a0), "r"(a1), "r"(a2), "r"(a3), "r"(b0), "r"(b1));
}
__device__ __forceinline__ uint32_t lds32(uint32_t addr) { uint32_t v; asm volatile("ld.shared.u32 %0, [%1];" : "=r"(v) : "r"(addr)); return v; }

__device__ __forceinline__ void ln_rows(const Params& P, int row0, int lane, uint32_t wr_s) {
    const int hl = lane & 15, row = row0 + (lane >> 4);
    uint32_t v[20];
#pragma unroll
    for (int i = 0; i < 5; i++) {
        uint4 u;
        asm("ld.global.nc.L2::cache_hint.v4.b32 {%0,%1,%2,%3}, [%4], %5;" : "=r"(u.x), "=r"(u.y), "=r"(u.z), "=r"(u.w)
            : "l"(P.x + (size_t)row * DM + 128 * i + 8 * hl), "l"(policy(HM & 512)));
        v[4 * i] = u.x; v[4 * i + 1] = u.y; v[4 * i + 2] = u.z; v[4 * i + 3] = u.w;
    }
    float mean = 0.f, m2 = 0.f, acc2 = 0.f;
#pragma unroll
    for (int i = 0; i < 20; i++) { mean += bf_lo(v[i]); acc2 += bf_hi(v[i]); }
    mean = (mean + acc2) * (1.0f / 40);
    acc2 = 0.f;
#pragma unroll
    for (int i = 0; i < 20; i++) {
        float d0 = __uint_as_float(__byte_perm(v[i], 0, 0x1044)) - mean, d1 = __uint_as_float(__byte_perm(v[i], 0, 0x3244)) - mean;
        m2 = fmaf(d0, d0, m2); acc2 = fmaf(d1, d1, acc2);
    }
    m2 += acc2;
    acc2 = 0.f;
#pragma unroll
    for (int o = 1; o < 16; o <<= 1) {
        float mo = __shfl_xor_sync(0xffffffffu, mean, o), qo = __shfl_xor_sync(0xffffffffu, m2, o), d = mo - mean;
        m2 = fmaf(d * d, 20.0f * o, m2 + qo);
        mean = 0.5f * (mean + mo);
    }
    const uint32_t mb2 = pack_bf16(mean, mean);
    const float inv = rcp_fast(bf_round(sqrt_fast(bf_round(bf_round(m2 * (1.0f / DM)) + 1e-5f))));
    float dot = 0.f;
    unsigned char* xp = const_cast<unsigned char*>(xn_addr(row, 8 * hl));
#pragma unroll
    for (int i = 0; i < 5; i++) {
        uint32_t ww[4];
        asm volatile("ld.shared.v4.b32 {%0,%1,%2,%3}, [%4];" : "=r"(ww[0]), "=r"(ww[1]), "=r"(ww[2]), "=r"(ww[3]) : "r"(wr_s + 256 * i + 16 * hl) : "memory");
#pragma unroll
        for (int e = 0; e < 4; e++) {
            uint32_t d;
            asm("sub.rn.bf16x2 %0, %1, %2;" : "=r"(d) : "r"(v[4 * i + e]), "r"(mb2));
            d = pack_bf16(bf_lo(d) * inv, bf_hi(d) * inv);
            v[4 * i + e] = d;
            dot = fmaf(bf_lo(d), bf_lo(ww[e]), dot);
            acc2 = fmaf(bf_hi(d), bf_hi(ww[e]), acc2);
        }
        stg128(xp + i * 32768, v[4 * i], v[4 * i + 1], v[4 * i + 2], v[4 * i + 3]);
    }
    dot += acc2;
#pragma unroll
    for (int o = 8; o > 0; o >>= 1) dot += __shfl_xor_sync(0xffffffffu, dot, o);
    if (hl == 0) { g_router[row] = bf_round(dot); g_stats[row] = make_uint2(mb2, __float_as_uint(inv)); }
}

__device__ __forceinline__ void aux_cta(const Params& P, const CUtensorMap* tmG, const CUtensorMap* tmU, const CUtensorMap* tmD, unsigned char* sm, int a) {
    constexpr int STG = 57344, XS = 3 * STG, HS = XS + 8 * 1296, KEY = HS + 8 * 912, MI = KEY + 8192;
    const int tid = threadIdx.x, warp = __shfl_sync(0xffffffffu, tid >> 5, 0), lane = tid & 31;
    const uint32_t sb = smem_u32(sm);
    const uint32_t full = sb + MI, empty = sb + MI + 32;
    int* s_sel = reinterpret_cast<int*>(sm + MI + 64);
    float* s_r = reinterpret_cast<float*>(sm + MI + 96);
    volatile unsigned* s_misc = reinterpret_cast<volatile unsigned*>(sm + MI + 128);
    uint32_t* s_key = reinterpret_cast<uint32_t*>(sm + KEY);
    PROF_DECL(128 + a)
    PROF_GT(0);
    if (tid == 0) {
        for (int i = 0; i < 3; i++) { mbar_init(full + 8 * i, 1); mbar_init(empty + 8 * i, 10); }
        asm volatile("fence.mbarrier_init.release.cluster;" ::: "memory");
    }
    __syncthreads();
    if (warp == 11) {
        if (elect_one()) {
            int st = 0; uint32_t ph = 0;
#pragma unroll 1
            for (int s = 0; s < 34; s++) {
                mbar_wait(empty + 8 * st, ph ^ 1);
                const uint32_t dst = sb + st * STG, fb = full + 8 * st;
                if (s < 20) {
                    mbar_expect_tx(fb, 57344);
                    tma3d(dst, tmG, 0, 32 * s, 7 * a, fb);
                    tma3d(dst + 28672, tmU, 0, 32 * s, 7 * a, fb);
                } else {
                    mbar_expect_tx(fb, 40960);
                    tma3d(dst, tmD, 0, 448 * a + 32 * (s - 20), 0, fb);
                }
                if (s >= 3) {
#pragma unroll 1
                    for (int f = (s == 3 ? 4 : s + 6); f <= s + 6 && f < 34; f++) {
                        if (f < 20) { tma3d_prefetch(tmG, 0, 32 * f, 7 * a); tma3d_prefetch(tmU, 0, 32 * f, 7 * a); }
                        else tma3d_prefetch(tmD, 0, 448 * a + 32 * (f - 20), 0);
                    }
                }
                if (++st == 3) { st = 0; ph ^= 1; }
            }
        }
        return;
    }
    if (tid < 80) *reinterpret_cast<uint4*>(sm + KEY + 1024 + tid * 16) = __ldg(reinterpret_cast<const uint4*>(P.wr) + tid);
    __nanosleep(AUXDELAY);
#pragma unroll 1
    for (int i = tid; i < 64 * 40; i += 352) asm volatile("prefetch.global.L2 [%0];" ::"l"(P.x + (size_t)((4 + a) * 256 + 192) * DM + i * 16));
    bar_sync(2, 352);
#pragma unroll 1
    for (int i = warp; i < 32; i += 11) ln_rows(P, (4 + a) * 256 + 192 + 2 * i, lane, sb + KEY + 1024);
    bar_sync(2, 352);
    if (tid == 320) flag_signal(flag_ptr(FL_LN + 4 + a));
    PROF_GT(49);
    if (warp == 10) return;
    if (tid < 8) {
        unsigned e = *reinterpret_cast<volatile unsigned*>(&g_epoch);
        if (tid == 0) s_misc[0] = e;
        flag_wait(flag_ptr(FL_LN + tid), (e + 1) * (32u + (tid >> 2)));
    }
    bar_sync(1, 320);
    PROF_GT(50);
    const unsigned ep = s_misc[0];
    auto top8 = [&](uint32_t (&key)[8]) {
        uint32_t mine = 0;
#pragma unroll 1
        for (int r = 0; r < TOPC; r++) {
            uint32_t best = 0;
#pragma unroll
            for (int i = 0; i < 8; i++) best = max(best, key[i]);
            best = __reduce_max_sync(0xffffffffu, best);
#pragma unroll
            for (int i = 0; i < 8; i++) if (key[i] == best) key[i] = 0;
            if (lane == r) mine = best;
        }
        return mine;
    };
#pragma unroll 1
    for (int pass = 0; pass < 2; pass++) {
        if (warp < (pass ? 1 : 8)) {
            uint32_t key[8];
#pragma unroll
            for (int i = 0; i < 8; i++) {
                if (pass == 0) {
                    int idx = warp * 256 + i * 32 + lane;
                    uint32_t b = __float_as_uint(__ldcg(g_router + idx)) >> 16;
                    b = (b & 0x8000u) ? (~b & 0xffffu) : (b | 0x8000u);
                    key[i] = (b << 16) | (uint32_t)(0xffff - idx);
                } else key[i] = i < 2 ? s_key[i * 32 + lane] : 0u;
            }
            uint32_t best = top8(key);
            if (lane < TOPC) {
                if (pass == 0) s_key[warp * 8 + lane] = best;
                else {
                    uint32_t b = best >> 16;
                    b = (b & 0x8000u) ? (b & 0x7fffu) : (~b & 0xffffu);
                    s_sel[lane] = 0xffff - (int)(best & 0xffffu);
                    s_r[lane] = __uint_as_float(b << 16);
                }
            }
        }
        bar_sync(1, 320);
    }
#pragma unroll
    for (int it = 0; it < 2; it++) {
        int i = tid + it * 320, tk = i / 80, ch = i % 80;
        *reinterpret_cast<uint4*>(sm + XS + tk * 1296 + ch * 16) = __ldcg(reinterpret_cast<const uint4*>(xn_addr(s_sel[tk], ch * 8)));
    }
    bar_sync(1, 320);
    PROF_GT(51);
    const int g = lane >> 2, t = lane & 3;
    const uint32_t woff = warp * 4096 + (8 * (lane >> 4) + (lane & 7)) * 128 + ((((lane >> 3) & 1) ^ (lane & 7)) << 4);
    int st = 0; uint32_t ph = 0;
    float ga[4][4], ua[4][4];
#pragma unroll
    for (int i = 0; i < 4; i++)
#pragma unroll
        for (int e = 0; e < 4; e++) { ga[i][e] = 0.f; ua[i][e] = 0.f; }
#pragma unroll 1
    for (int s = 0; s < 34; s++) {
        if (s == 20) {
            if (warp < 7) {
#pragma unroll
                for (int i = 0; i < 4; i++)
#pragma unroll
                    for (int e = 0; e < 4; e++) {
                        float gv = bf_round(ga[i][e]), uv = bf_round(ua[i][e]);
                        float sg = bf_round(__fdividef(gv, 1.0f + __expf(fminf(-gv, 80.f))));
                        int f = warp * 64 + i * 16 + g + 8 * (e >> 1), tk = 2 * t + (e & 1);
                        *reinterpret_cast<__nv_bfloat16*>(sm + HS + tk * 912 + f * 2) = __float2bfloat16_rn(sg * uv);
                        ga[i][e] = 0.f;
                    }
            }
            bar_sync(1, 320);
            PROF_GT(52);
        }
        mbar_wait(full + 8 * st, ph);
        if (s >= 20 || warp < 7) {
#pragma unroll
            for (int kk = 0; kk < 2; kk++) {
                uint32_t xb = sb + (s < 20 ? XS + g * 1296 + s * 64 : HS + g * 912 + (s - 20) * 64) + 32 * kk + 4 * t;
                uint32_t b0 = lds32(xb), b1 = lds32(xb + 16);
                uint32_t wa = sb + st * STG + woff + kk * 2048;
#pragma unroll
                for (int i = 0; i < 4; i++) {
                    uint32_t a0, a1, a2, a3;
                    ldsm4t(a0, a1, a2, a3, wa ^ (i << 5));
                    mma16816(ga[i], a0, a1, a2, a3, b0, b1);
                    if (s < 20) {
                        ldsm4t(a0, a1, a2, a3, (wa ^ (i << 5)) + 28672);
                        mma16816(ua[i], a0, a1, a2, a3, b0, b1);
                    }
                }
            }
        }
        asm volatile("fence.proxy.async.shared::cta;" ::: "memory");
        __syncwarp();
        if (lane == 0) mbar_arrive(empty + 8 * st);
        if (++st == 3) { st = 0; ph ^= 1; }
    }
#pragma unroll
    for (int i = 0; i < 4; i++)
#pragma unroll
        for (int e = 0; e < 4; e += 2)
            *reinterpret_cast<float2*>(g_moe_part + (a * DM + warp * 64 + i * 16 + g + 4 * e) * 8 + 2 * t) = make_float2(ga[i][e], ga[i][e + 1]);
    bar_sync(1, 320);
    if (tid == 0) {
        __threadfence();
        unsigned old = atomicAdd(flag_ptr(FL_MOE_CNT), 1u);
        s_misc[1] = (old == ep * 4u + 3u);
        __threadfence();
    }
    bar_sync(1, 320);
    PROF_GT(53);
    if (s_misc[1]) {
        const float4* pp = reinterpret_cast<const float4*>(g_moe_part);
#pragma unroll 2
        for (int i = tid; i < DM * 2; i += 320) {
            float4 v0 = __ldcg(pp + i), v1 = __ldcg(pp + DM * 2 + i), v2 = __ldcg(pp + DM * 4 + i), v3 = __ldcg(pp + DM * 6 + i);
            float y[4] = {v0.x + v1.x + v2.x + v3.x, v0.y + v1.y + v2.y + v3.y, v0.z + v1.z + v2.z + v3.z, v0.w + v1.w + v2.w + v3.w};
#pragma unroll
            for (int e = 0; e < 4; e++) {
                int col = i >> 1, tk = (i & 1) * 4 + e;
                float sg = bf_round(__fdividef(1.0f, 1.0f + __expf(fminf(-s_r[tk], 80.f))));
                float upd = bf_round(bf_round(y[e]) * sg);
                float xn = __bfloat162float(*reinterpret_cast<const __nv_bfloat16*>(sm + XS + tk * 1296 + col * 2));
                g_brow[tk * DM + col] = __float2bfloat16_rn(xn + upd);
            }
        }
        if (tid < TOPC) g_sel[tid] = s_sel[tid];
        bar_sync(1, 320);
        if (tid == 0) {
            flag_signal(flag_ptr(FL_MOE_DONE));
            *reinterpret_cast<volatile unsigned*>(&g_epoch) = ep + 1;
        }
        PROF_GT(54);
    }
}

__global__ void __cluster_dims__(2, 1, 1) __launch_bounds__(384, 1)
fused_kernel(const __grid_constant__ CUtensorMap tmC, const __grid_constant__ CUtensorMap tmWk, const __grid_constant__ CUtensorMap tmWv,
             const __grid_constant__ CUtensorMap tmWq, const __grid_constant__ CUtensorMap tmWo,
             const __grid_constant__ CUtensorMap tmG, const __grid_constant__ CUtensorMap tmU, const __grid_constant__ CUtensorMap tmD, const Params P) {
    extern __shared__ __align__(1024) unsigned char smem_raw[];
    const uint32_t ring = smem_u32(smem_raw);
    const uint32_t misc = ring + RING_BYTES;
    const int tid = threadIdx.x;
    const int rank = blockIdx.x & 1;
    uint32_t smid, nsm;
    asm("mov.u32 %0, %%smid;" : "=r"(smid));
    asm("mov.u32 %0, %%nsmid;" : "=r"(nsm));
    if (nsm != 132) smid = blockIdx.x;
    auto role_of = [](int tpc) {
        return tpc < 32 ? (tpc & 7) * 8 + (tpc >> 3) : tpc < 60 ? (1 + (tpc - 32) % 7) * 8 + 4 + (tpc - 32) / 7 : tpc < 64 ? tpc - 56 : tpc;
    };
    int mc = role_of(smid >> 1);
    PROF_DECL(mc * 2 + rank)
    PROF_GT(0); PROF_EV(1);

    auto prefetch_w = [&](int ch) {
        const int i = tid - 128;
        asm volatile("prefetch.global.L2 [%0];" ::"l"((rank ? P.wv : P.wk) + (size_t)(ch * 128 + (mc & 3) * 32 + (i >> 3)) * 4096 + (mc >> 2) * 256 + (i & 7) * 16));
    };
    if (tid >= 128 && mc < 64) {
        if (tid < 256) asm volatile("prefetch.global.L2 [%0];" ::"l"(P.c + (size_t)((12 + (mc & 3)) * 128 + ((mc >> 2) * 2 + rank) * 4) * DC + (tid - 128) * 16));
        prefetch_w(0);
    }
    auto load_w0 = [&]() {
        const CUtensorMap* tw = rank ? &tmWv : &tmWk;
        mbar_expect_tx(misc + BAR_FULL + 8 * slot_of(0), SLOT_BYTES);
        tma2d(ring + slot_of(0) * SLOT_BYTES, tw, (mc >> 2) * 256, 0, misc + BAR_FULL + 8 * slot_of(0), policy(HM & 1));
        tma2d(ring + slot_of(0) * SLOT_BYTES + 16384, tw, (mc >> 2) * 256 + 64, 0, misc + BAR_FULL + 8 * slot_of(0), policy(HM & 1));
    };
    if (tid == 0) {
#pragma unroll
        for (int i = 0; i < NSLOT; i++) mbar_init(misc + BAR_FULL + 8 * i, 1);
#pragma unroll
        for (int i = 0; i < E0; i++) mbar_arrive(misc + BAR_FULL + 8 * i);
        asm volatile("fence.mbarrier_init.release.cluster;" ::: "memory");
        if (mc < 64) load_w0();
    }
    if (tid == 160) {
        asm volatile("st.shared.u32 [%0], %1;" ::"r"(misc + MISC_SMID), "r"(smid) : "memory");
        asm volatile("fence.release.sync_restrict::shared::cta.cluster;" ::: "memory");
    }
    if (tid == 32) {
        asm volatile("prefetch.tensormap [%0];" ::"l"(&tmC) : "memory");
#pragma unroll
        for (int i = 0; i < NSLOT; i++) mbar_init(misc + BAR_EMPTY + 8 * i, 16);
#pragma unroll
        for (int i = 0; i < E0; i++) mbar_arrive_cluster(misc + BAR_EMPTY + 8 * i, 16);
        asm volatile("fence.mbarrier_init.release.cluster;" ::: "memory");
    }
    if (tid == 64) {
#pragma unroll
        for (int i = 0; i < NST3; i++) { mbar_init(misc + BAR_FULL3 + 8 * i, 1); mbar_init(misc + BAR_EMPTY3 + 8 * i, 16); }
#pragma unroll
        for (int i = 0; i < 4; i++) mbar_init(misc + BAR_LN + 8 * i, 2);
        mbar_init(misc + BAR_PROG, 1); mbar_init(misc + BAR_PROG + 8, 1); mbar_init(misc + BAR_PROG + 16, 1);
        asm volatile("fence.mbarrier_init.release.cluster;" ::: "memory");
    }
    if (tid == 96) {
#pragma unroll
        for (int i = 0; i < 34; i++) mbar_init(misc + BAR_DEP + 8 * i, 1);
    }
    if (tid == 128) {
#pragma unroll
        for (int i = 0; i < 32; i++) mbar_init(misc + BAR_EV + 8 * i, 4);
    }
    __syncthreads();
    asm volatile("barrier.cluster.arrive.relaxed.aligned;\nbarrier.cluster.wait.aligned;" ::: "memory");
    {
        uint32_t peer;
        asm volatile("ld.shared::cluster.u32 %0, [%1];" : "=r"(peer) : "r"(mapa(misc + MISC_SMID, rank ^ 1)) : "memory");
        if ((__shfl_sync(0xffffffffu, peer, 0) ^ smid) != 1) {
            if (tid == 0) {
                const unsigned ep1 = *reinterpret_cast<volatile unsigned*>(&g_epoch) + 1;
                if ((smid & 1) == 0) atomicExch(g_roleq + 2 + (atomicAdd(g_roleq, 1u) & 127), (ep1 << 8) | (smid >> 1));
                if (rank == 0) {
                    unsigned* slot = g_roleq + 2 + (atomicAdd(g_roleq + 1, 1u) & 127);
                    unsigned v = 0;
                    for (int spin = 0; spin < 4000000 && ((v = atomicAdd(slot, 0u)) >> 8) != (ep1 & 0xffffffu); spin++) {}
                    asm volatile("st.shared::cluster.u32 [%0], %1;" ::"r"(mapa(misc + MISC_SMID + 4, 0)), "r"(v & 255) : "memory");
                    asm volatile("st.shared::cluster.u32 [%0], %1;" ::"r"(mapa(misc + MISC_SMID + 4, 1)), "r"(v & 255) : "memory");
                }
                if (mc < 64) {
                    mbar_wait(misc + BAR_FULL + 8 * slot_of(0), 0);
                    asm volatile("mbarrier.inval.shared::cta.b64 [%0];" ::"r"(misc + BAR_FULL + 8 * slot_of(0)) : "memory");
                    mbar_init(misc + BAR_FULL + 8 * slot_of(0), 1);
                    asm volatile("fence.mbarrier_init.release.cluster;" ::: "memory");
                }
            }
            __syncwarp();
            asm volatile("barrier.cluster.arrive.aligned;\nbarrier.cluster.wait.aligned;" ::: "memory");
            mc = role_of(__shfl_sync(0xffffffffu, lds32(misc + MISC_SMID + 4), 0));
            if (tid == 0 && mc < 64) load_w0();
            __syncwarp();
        }
    }
    const int cta = mc * 2 + rank;
    if (mc >= 64) { aux_cta(P, &tmG, &tmU, &tmD, smem_raw, cta - 128); return; }
    const int team = mc >> 2, k = mc & 3;
    const int u3 = (mc >> 4) * 2 + (team & 1), s3 = k, kap = (mc >> 3) & 1;
    const int partner = cta ^ 16;
    if (tid >= 128) prefetch_w(1);
    if (tid == 256) {
        const CUtensorMap* tw = rank ? &tmWv : &tmWk;
#pragma unroll
        for (int e = 1; e < NSLOT; e++) {
            const uint32_t fb = misc + BAR_FULL + 8 * slot_of(e), dst = ring + slot_of(e) * SLOT_BYTES;
            mbar_expect_tx(fb, SLOT_BYTES);
            if (e & 1) tma2d_mc(dst + rank * 16384, &tmC, (e >> 1) * 128 + rank * 64, (12 + k) * 128, fb, policy(false));
            else { tma2d(dst, tw, team * 256, e * 64, fb, policy(false)); tma2d(dst + 16384, tw, team * 256 + 64, e * 64, fb, policy(false)); }
        }
    }
    PROF_EV(5);
    const int wg = __shfl_sync(0xffffffffu, tid >> 7, 0);

    if (wg == 0) {
        asm volatile("setmaxnreg.dec.sync.aligned.u32 40;");
        const int warp = __shfl_sync(0xffffffffu, tid >> 5, 0), lane = tid & 31;
        if (warp == 0) {
            const bool lead = elect_one();
            Cur c = cur_at(NSLOT);
            uint32_t dst, fb;
            auto acquire = [&]() {
                mbar_wait(misc + BAR_EMPTY + 8 * c.slot, c.ph ^ 1);
                fb = misc + BAR_FULL + 8 * c.slot; dst = ring + c.slot * SLOT_BYTES;
                if (lead) mbar_expect_tx(fb, SLOT_BYTES);
                c.adv();
            };
            auto load_w = [&](const CUtensorMap* tm, int col, int row, bool stream) {
                acquire();
                if (lead) { tma2d(dst, tm, col, row, fb, policy(stream)); tma2d(dst + 16384, tm, col + 64, row, fb, policy(stream)); }
            };
            auto load_half = [&](const unsigned char* src, bool stream) {
                acquire();
                if (lead) bulk_load_mc(dst + rank * 16384, src, 16384, fb, policy(stream));
            };
            auto dep_wait = [&](int d) { mbar_wait(misc + BAR_DEP + 8 * d, 0); fence_async_global(); };
            auto op_prefetch = [&](int i) {
                const int head = op_head(i, kap);
                l2_prefetch(reinterpret_cast<const unsigned char*>(P.wo) + head * 163840 + (u3 * 8 + s3 * 2 + rank) * 2560, 2560);
                if (i < 8) l2_prefetch(g_ctx + (size_t)(head * 32 + 4 * u3 + 2 * rank) * 16384 + s3 * 8192, 8192);
            };
            __nanosleep(CDELAY);
            if (lead) l2_prefetch(reinterpret_cast<const unsigned char*>(P.c) + (size_t)cta * 12288, 12288);
            const CUtensorMap* tw = rank ? &tmWv : &tmWk;
            const unsigned char* Kh = g_K + (size_t)team * 32 * 16384 + rank * 16384;
            const unsigned char* Vh = g_V + (size_t)team * 32 * 16384 + rank * 16384;
#pragma unroll 1
            for (int v = 0; v < 2; v++) {
                const int h = 2 * team + v;
#pragma unroll 1
                for (int i = v ? 0 : 3; i < 16; i++) {
                    if (i < 4 && v) load_w(tw, h * 128, i * 128, HM & 1);
                    if (v && i == 3 && lead) mbar_arrive(misc + BAR_PROG + 8);
                    if (v && (i & 7) == 3) dep_wait(D_WAR + (i >> 3));
                    acquire();
                    if (lead) tma2d_mc(dst + rank * 16384, &tmC, (i & 3) * 128 + rank * 64, (12 - (i & 12) + k) * 128, fb, policy(HM & 2));
                    if (i == 8 && lead) {
                        tma2d_prefetch(&tmWq, h * 128 + rank * 64, k * 64); tma2d_prefetch(&tmWq, h * 128 + rank * 64, k * 64 + 256);
                        if (k < 2) tma2d_prefetch(&tmWq, h * 128 + rank * 64, k * 64 + 512);
                        if (v) l2_prefetch(g_xn + 8 * 163840 + cta * 10240, 10240);
                    }
                }
                int togo = v ? PF_START : 11;
#pragma unroll 1
                for (int r = 0; r < 2; r++) {
                    const int p = r ? k : 7 - k, n = 2 * p + 1;
                    if (v == 0) dep_wait(D_LN + r);
                    const int g0 = r ? rank ^ SWAPT : 3 - rank, g1 = 3 - g0;
                    const unsigned char* x0 = g_xn + (2 * p + (g0 >> 1)) * 163840 + (g0 & 1) * 8192;
                    const unsigned char* x1 = g_xn + (2 * p + (g1 >> 1)) * 163840 + (g1 & 1) * 8192;
#pragma unroll 1
                    for (int kc = 0; kc < 10; kc++) {
                        acquire();
                        if (lead) {
                            tma2d_mc(dst + 16384 + rank * 8192, &tmWq, h * 128 + rank * 64, kc * 64, fb, policy(false));
                            bulk_load(dst, x0 + kc * 16384, 8192, fb, policy(false));
                            bulk_load(dst + 8192, x1 + kc * 16384, 8192, fb, policy(false));
                        }
                    }
                    if (r == 0) dep_wait(D_KV + 3 * v);
                    load_half(Kh + n * 32768, HM & 16);
#pragma unroll 1
                    for (int j = n - 1; j >= 0; j--) {
                        if (r == 0 && (j == 7 || j == 3)) dep_wait(D_KV + 3 * v + 2 - (j >> 2));
                        load_half(Kh + j * 32768, HM & 16); load_half(Vh + (j + 1) * 32768, HM & 16);
                        if (v == 0 && r == 0 && j == 3 && lead) mbar_arrive(misc + BAR_PROG);
                        --togo;
                        if (v == 0 && togo == 0 && lead) {
                            tma2d_prefetch(tw, h * 128 + 128, k * 128); tma2d_prefetch(tw, h * 128 + 192, k * 128);
                            l2_prefetch(reinterpret_cast<const unsigned char*>(P.c) + (size_t)cta * 16384, 16384);
                        }
                        if (v && togo <= 0 && togo > -OP_PF && lead) op_prefetch(-togo);
                    }
                    load_half(Vh, HM & 16);
                }
            }
            mbar_wait(misc + BAR_EMPTY + 8 * c.slot, c.ph ^ 1); c.adv();
            int st = 0; uint32_t ph3 = 0;
#pragma unroll 1
            for (int i = 0; i < 32; i++) {
                const int head = op_head(i >> 1, kap);
                if ((i & 1) == 0) dep_wait(D_CTX + (i >> 1));
                if (i < NST3) { mbar_wait(misc + BAR_EMPTY + 8 * c.slot, c.ph ^ 1); c.adv(); }
                else mbar_wait(misc + BAR_EMPTY3 + 8 * st, ph3 ^ 1);
                fb = misc + BAR_FULL3 + 8 * st; dst = ring + st * ST3_BYTES;
                if (i == LATE_AT && lead) mbar_arrive(misc + BAR_PROG + 16);
                if (lead) {
                    mbar_expect_tx(fb, ST3_BYTES);
                    const unsigned char* src = g_ctx + (size_t)(head * 32 + 4 * u3 + 2 * rank) * 16384 + (i & 1) * 8192;
                    bulk_load(dst, src, 8192, fb, policy(HM & 32));
                    bulk_load(dst + 8192, src + 16384, 8192, fb, policy(HM & 32));
                    tma3d_mc(dst + 16384 + rank * 10240, &tmWo, 0, head * 128 + (i & 1) * 64 + rank * 32, 5 * s3, fb, policy(HM & 32));
                    if ((i & 1) && (i >> 1) + OP_PF < 16) op_prefetch((i >> 1) + OP_PF);
                }
                if (++st == NST3) { st = 0; ph3 ^= 1; }
            }
        } else {
        if (lane < 27 && (warp - 1) * 27 + lane < 80) {
            const int ch = (warp - 1) * 27 + lane;
            uint4 u = __ldg(reinterpret_cast<const uint4*>(P.wr) + ch);
            asm volatile("st.shared.v4.b32 [%0], {%1,%2,%3,%4};" ::"r"(misc + MISC_WR + 16 * ch), "r"(u.x), "r"(u.y), "r"(u.z), "r"(u.w) : "memory");
        }
        bar_sync(3, 96);
#pragma unroll 1
        for (int t = 0; t < (warp == 3 ? 1 : 3); t++) {
            const int row2 = (cta >> 5) * 256 + (cta & 31) * 8 + (warp - 1) * 4;
            if (t < 2 && warp < 3) {
#pragma unroll
                for (int i = 0; i < 3; i++)
                    if (i * 32 + lane < 80) asm volatile("prefetch.global.L2 [%0];" ::"l"(P.x + (size_t)(row2 + 2 * t) * DM + (i * 32 + lane) * 16));
            }
            ln_rows(P, t ? row2 + 2 * t - 2 : (4 + (cta >> 5)) * 256 + (cta & 31) * 6 + (warp - 1) * 2, lane, misc + MISC_WR);
            __syncwarp();
            if (lane == 0 && warp < 3 && t != 1) mbar_arrive(misc + BAR_LN + 4 * t);
        }
        if (warp == 3) {
            const unsigned ep1 = *reinterpret_cast<volatile unsigned*>(&g_epoch) + 1;
            if (lane == 0) {
                asm volatile("st.shared.u32 [%0], %1;" ::"r"(misc + MISC_EPOCH), "r"(ep1) : "memory");
                mbar_wait(misc + BAR_LN, 0);
                flag_signal(flag_ptr(FL_LN + 4 + (cta >> 5)));
                flag_wait(flag_ptr(FL_LN + 7 - k), ep1 * 33u);
                mbar_arrive(misc + BAR_DEP + 8 * D_LN);
#pragma unroll 1
                for (int v = 0; v < 2; v++) {
#pragma unroll 1
                    for (int i = 3 * v; i < 3 * v + 3; i++) {
                        mbar_wait(misc + BAR_EV + 8 * (16 + EV_KV + i), 0);
                        if (v == 0) {
                            mbar_wait(misc + BAR_EV + 8 * (EV_KV + i), 0);
                            asm volatile("red.release.gpu.global.add.u32 [%0], 2;" ::"l"(flag_ptr(FL_KV + team * 8 + i)) : "memory");
                        }
                        flag_wait(flag_ptr(FL_KV + team * 8 + i), ep1 * 16u);
                        mbar_arrive(misc + BAR_DEP + 8 * (D_KV + i));
                    }
                    if (v) break;
                    mbar_wait(misc + BAR_LN + 8, 0);
                    flag_signal(flag_ptr(FL_LN + (cta >> 5)));
                    flag_wait(flag_ptr(FL_LN + k), ep1 * 32u);
                    mbar_arrive(misc + BAR_DEP + 8 * (D_LN + 1));
#pragma unroll 1
                    for (int i = 0; i < 2; i++) {
                        mbar_wait(misc + BAR_PROG + 8 * i, 0);
                        flag_signal(flag_ptr(FL_WAR + 2 * team + i));
                        flag_wait(flag_ptr(FL_WAR + 2 * team + i), ep1 * 8u);
                        mbar_arrive(misc + BAR_DEP + 8 * (D_WAR + i));
                    }
                }
                flag_wait(flag_ptr(FL_MOE_DONE), ep1);
                int4 s0 = __ldcg(reinterpret_cast<const int4*>(g_sel)), s1 = __ldcg(reinterpret_cast<const int4*>(g_sel) + 1);
                asm volatile("st.shared.v4.u32 [%0], {%1,%2,%3,%4};" ::"r"(misc + MISC_SEL), "r"(s0.x), "r"(s0.y), "r"(s0.z), "r"(s0.w) : "memory");
                asm volatile("st.shared.v4.u32 [%0], {%1,%2,%3,%4};" ::"r"(misc + MISC_SEL + 16), "r"(s1.x), "r"(s1.y), "r"(s1.z), "r"(s1.w) : "memory");
                mbar_arrive(misc + BAR_SEL);
            }
            __syncwarp();
            const unsigned* cf = flag_ptr(FL_CTX + op_head(lane & 15, kap) * 8 + u3);
#pragma unroll 1
            for (int half = 0; half < 2; half++) {
                if (half) mbar_wait(misc + BAR_EV + 8 * (EV_CTX + 3), 0);
                bool done = (lane >> 3) != half;
                for (int spin = 0; spin < 4000000; spin++) {
                    if (!done) {
                        unsigned v;
                        asm volatile("ld.acquire.gpu.global.u32 %0, [%1];" : "=r"(v) : "l"(cf) : "memory");
                        if ((int)(v - ep1 * 4u) >= 0) { mbar_arrive(misc + BAR_DEP + 8 * (D_CTX + lane)); done = true; }
                    }
                    if (__all_sync(0xffffffffu, done)) break;
                    __nanosleep(64);
                }
            }
        } else {
            const int w = warp - 1;
            if (lane == 0) {
                const uint32_t eb = misc + BAR_EV + w * 128;
#pragma unroll 1
                for (int i = 0; i < 7; i++) {
                    const bool kv = i >= 2 && i < 5;
                    const int ci = i < 2 ? i : i - 3;
                    mbar_wait(eb + 8 * (kv ? EV_KV + i + 1 : EV_CTX + ci), 0);
                    if (i == 1) {
                        asm volatile("cp.async.bulk.global.shared::cta.bulk_group [%0], [%1], 16384;"
                                     ::"l"(g_ctx + (size_t)(2 * team * 32 + 4 * k + (w ? 3 - (rank ^ SWAPT) : rank ^ SWAPT)) * 16384),
                                       "r"(ring + slot_of(78) * SLOT_BYTES + w * 16384) : "memory");
                        asm volatile("cp.async.bulk.commit_group;" ::: "memory");
                        asm volatile("cp.async.bulk.wait_group.read 0;" ::: "memory");
                        mbar_arrive_cluster(mapa(misc + BAR_EMPTY + 8 * slot_of(78), 0), 4);
                        mbar_arrive_cluster(mapa(misc + BAR_EMPTY + 8 * slot_of(78), 1), 4);
                        asm volatile("cp.async.bulk.wait_group 0;" ::: "memory");
                        fence_async_global();
                    }
                    flag_signal(flag_ptr(kv ? FL_KV + team * 8 + i + 1 : FL_CTX + (2 * team + (ci >> 1)) * 8 + ((ci & 1) ? k : 7 - k)));
                }
            }
            __syncwarp();
            mbar_wait(misc + BAR_PROG + 16, 0);
            const int row = (2 * u3 + rank) * 128 + 64 * w + perm32(16 * (lane >> 3) + 8 * kap + (lane & 7));
#pragma unroll
            for (int i = 0; i < 10; i++) asm volatile("prefetch.global.L2 [%0];" ::"l"(P.x + (size_t)row * DM + 160 * s3 + 16 * i));
            asm volatile("prefetch.global.L2 [%0];" ::"l"(g_stats + row));
        }
        }
    } else {
        asm volatile("setmaxnreg.inc.sync.aligned.u32 232;");
        Ctx c;
        c.ring = ring; c.misc = misc; c.w = wg - 1; c.warp = __shfl_sync(0xffffffffu, (tid >> 5) & 3, 0); c.lane = tid & 31;
        c.rel = mapa(misc, tid & 1);
        const int w = c.w;
        if (w == 1) bar_arrive(1, 256);
        prefetch_w(2); prefetch_w(3);
        Cur cur = cur_at(0);
        float o[64], inv[2];
        unsigned char* out[2];
        uint32_t wf[128];
        Cur cw = cur;
        auto load_wchunk = [&](auto CH) {
            constexpr int ch = decltype(CH)::value;
            mbar_wait_hot(misc + BAR_FULL + 8 * cw.slot, cw.ph);
            const uint32_t z = load_afrag<8, 32 * ch>(wf, ring + cw.slot * SLOT_BYTES + w * 16384, c);
            release(c, BAR_EMPTY + 8 * cw.slot + z, 1);
            cw.adv(); cw.adv();
        };
#pragma unroll
        for (int i = 32; i < 64; i++) wf[i] = 0u;
        load_wchunk(IC<0>{});
#pragma unroll 1
        for (int v = 0; v < 2; v++) {
        {
            float (&acc)[64] = o;
#pragma unroll
            for (int i = 64; i < 128; i++) wf[i] = 0u;
            cur.adv();
            inv[0] = inv[1] = (rank || QS) ? 1.0f : SM_SCALE;
            PROF_EV(2); PROF_GT(60);
#pragma unroll 1
            for (int t = 0; t < 4; t++) {
                uint32_t last = 0;
                token_wait(w);
                PROF_EV(10);
                undef_regs(acc);
                auto chunk = [&](auto CH) {
                    constexpr int ch = decltype(CH)::value;
                    mbar_wait_hot(misc + BAR_FULL + 8 * cur.slot, cur.ph);
                    if (t == 0) { PROF_EV(12 + ch); }
                    uint64_t d = mkdesc(ring + cur.slot * SLOT_BYTES, 16, 1024, 1);
                    wg_fence();
#pragma unroll
                    for (int ks = 0; ks < 8; ks++)
                        wgmma_rs_n128_ta0_tb0(acc, wf[32 * ch + 4 * ks], wf[32 * ch + 4 * ks + 1], wf[32 * ch + 4 * ks + 2], wf[32 * ch + 4 * ks + 3],
                                              d + (ks >> 2) * 1024 + (ks & 3) * 2, (ch | ks) != 0);
                    wg_commit();
                    if (ch == 3 || (ch < 2 && t == 0)) token_pass(w);
                    if constexpr (ch == 0) { if (t == 0) { if (v) load_wchunk(IC<2>{}); else load_wchunk(IC<1>{}); } }
                    if constexpr (ch == 1) { if (t == 0 && !v) load_wchunk(IC<2>{}); }
                    if constexpr (ch == 2) { if (t == 0 && !(w | v)) load_wchunk(IC<3>{}); }
                    if (ch > 0) { wg_wait<1>(); release(c, BAR_EMPTY + 8 * last, 1); }
                    last = cur.slot;
                    cur.adv();
                    if (ch < 3 && t == 0) cur.adv();
                    if constexpr (ch == 1) { if (t == 0 && (w | v)) load_wchunk(IC<3>{}); }
                    if (ch < 2 && t == 0) token_wait(w);
                };
                chunk(IC<0>{}); chunk(IC<1>{}); chunk(IC<2>{}); chunk(IC<3>{});
                wg_wait<0>();
                release(c, BAR_EMPTY + 8 * last, 1);
                PROF_EV(11);
                fence_regs(acc);
                tile_out(out, (rank ? g_V : g_K) + (size_t)(team * 32 + 24 + 2 * k - 8 * t) * 16384, 64 * w, rank, c);
                if (DEFER && t == 3 && w) break;
#pragma unroll
                for (int i = 0; i < 4; i++) { if (QS) { const float one[2] = {1.0f, 1.0f}; store_pair(acc, i, out, 16384, one); } else store_pair(acc, i, out, 16384, inv); }
                if (t) signal_event(c, EV_KV + 3 * v + t - 1);
            }
            PROF_EV(61); PROF_GT(62);
        }
        PROF_EV(63); PROF_GT(64);
        {
            uint32_t q[32], p[32];
            float m[2], l[2];
#pragma unroll
            for (int i = 0; i < 32; i++) p[i] = 0u;
            l[0] = l[1] = 1.f;
            int pv_acc = 0, pv_mode = 2;
#pragma unroll 1
            for (int r = 0; r < 2; r++) {
                const int heavy = 1 ^ r ^ w;
                const int half = 1 ^ heavy ^ rank ^ (r & SWAPT);
                int left = 2 * (r ? k : 7 - k) + 1 + heavy;
                Cur ck, cv = cur;
                {
                    float s[64];
                    if (r) cur.adv();
                    mbar_wait_hot(misc + BAR_FULL + 8 * cv.slot, cv.ph);
                    token_wait(w);
                    PROF_EV(20);
                    issue_pv(o, p, ring + cv.slot * SLOT_BYTES, 1, r ? 0 : 2);
                    undef_regs(s);
                    uint32_t prev;
                    auto qchunk = [&](int acc) {
                        mbar_wait_hot(misc + BAR_FULL + 8 * cur.slot, cur.ph);
                        const uint64_t da = mkdesc(ring + cur.slot * SLOT_BYTES + w * 8192, 16, 1024, 1);
                        const uint64_t db = mkdesc(ring + cur.slot * SLOT_BYTES + 16384, 8192, 1024, 1);
                        wg_fence();
#pragma unroll
                        for (int ks = 0; ks < 4; ks++) wgmma_ss_n128_ta0_tb1(s, da + 2 * ks, db + 128 * ks, ks ? 1 : acc);
                        wg_commit();
                    };
                    qchunk(0);
                    prev = cur.slot; cur.adv();
                    token_pass(w);
                    if (r) {
                        row_inv(l, inv);
                        tile_out(out, g_ctx + (size_t)((2 * team + v) * 32 + 4 * (7 - k) + (w ? rank : 3 - rank)) * 16384, 0, 2, c);
                    }
                    const int epi = r | (w & DEFER), hs = r ? 8192 : 16384;
                    const int hold = heavy ? -10 : half ? HOLD0 : 8;
#pragma unroll
                    for (int kc = 1; kc < 10; kc++) {
                        if (HOLD0 && kc >= HOLD0 && (kc == hold || kc == hold + 2)) token_wait(w);
                        qchunk(1);
                        if (HOLD0 && kc > HOLD0 && kc == hold + 1) token_pass(w);
                        if (HOLD0 && kc == 9 && heavy) { token_wait(w); token_pass(w); }
                        wg_wait<1>();
                        release(c, BAR_EMPTY + 8 * prev, 1);
                        prev = cur.slot; cur.adv();
                        if (kc == 1) { fence_regs(o); if (r) release(c, BAR_EMPTY + 8 * cv.slot, 1); }
                        if (kc <= 4 && epi) {
                            store_pair(o, kc - 1, out, hs, inv);
                            if (kc == 4) signal_event(c, r ? EV_CTX + 2 * v : EV_KV + 3 * v + 2);
                        }
                    }
                    if (!heavy) cur.adv();
                    ck = cur;
                    cur.adv();
                    if (!heavy) cur.adv();
                    if (KW) mbar_wait_hot(misc + BAR_FULL + 8 * ck.slot, ck.ph);
                    wg_wait<0>();
                    release(c, BAR_EMPTY + 8 * prev, 1);
                    PROF_EV(21);
                    fence_regs(s);
#pragma unroll
                    for (int i = 0; i < 32; i++) q[i] = QS ? pack_bf16(s[2 * i] * SM_SCALE, s[2 * i + 1] * SM_SCALE) : pack_bf16(s[2 * i], s[2 * i + 1]);
                }
                cv = ck;
                int first = 1, gen = 0;
                uint32_t pv_cnt = 0;
                pv_acc = 0; pv_mode = 2;
                l[0] = l[1] = m[0] = m[1] = 0.f;
                if (!KW) mbar_wait_hot(misc + BAR_FULL + 8 * ck.slot, ck.ph);
#pragma unroll 1
                while (true) {
                    float s[64];
                    if (half & first) {
                        if (heavy || HOLD0 == 0 || HOLD0 == 8) token_wait(w);
                        PROF_EV(30);
                        float sh[32];
                        undef_regs(sh);
                        issue_qk_half(sh, q, ring + ck.slot * SLOT_BYTES);
                        token_pass(w);
                        --left;
                        wg_wait<0>();
                        PROF_EV(34);
                        fence_regs(sh);
                        mask_diag<0>(sh, c);
                        float l0 = 0.f, l1 = 0.f;
#pragma unroll
                        for (int j = 0; j < 8; j++) {
#pragma unroll
                            for (int e = 0; e < 4; e++) ex2v(sh[4 * j + e]);
                            l0 += sh[4 * j] + sh[4 * j + 1]; l1 += sh[4 * j + 2] + sh[4 * j + 3];
                        }
#pragma unroll
                        for (int i = 0; i < 16; i++) p[i] = pack_bf16(sh[2 * i], sh[2 * i + 1]);
                        const int lim = mask_lim(c);
                        if (__any_sync(0xffffffffu, !(l0 <= SAFE_SUM && l1 <= SAFE_SUM && (l0 >= 1.0f / SAFE_SUM || lim < 0) &&
                                                      (l1 >= 1.0f / SAFE_SUM || lim < -2)))) goto redo;
                        l[0] = l0; l[1] = l1;
                        goto tail;
                    }
#pragma unroll 1
                    while (true) {
                        token_wait(w);
                        PROF_EV(first ? 30 : 31);
                        undef_regs(s);
                        issue_qk(s, q, ring + ck.slot * SLOT_BYTES);
                        Cur nck = cur, ncv = cur, ncur;
                        ncv.adv(); ncur = ncv; ncur.adv();
                        --left;
                        mbar_wait_hot(misc + BAR_FULL + 8 * cv.slot, cv.ph);
                        issue_pv(o, p, ring + cv.slot * SLOT_BYTES, pv_acc, pv_mode);
                        token_pass(w);
                        wg_wait<1>();
                        PROF_EV(33);
                        fence_regs(s);
                        float lo = 0.f;
                        if (first) {
                            lo = 1.0f / SAFE_SUM;
                            mask_diag<8>(s, c);
                        }
                        constexpr int JB = 11;
                        float l0 = l[0], l1 = l[1];
                        if (!gen) {
#pragma unroll
                            for (int j = 0; j < JB; j++) {
#pragma unroll
                                for (int e = 0; e < 4; e++) ex2v(s[4 * j + e]);
                                if (j < JB - 1) { l0 += s[4 * j] + s[4 * j + 1]; l1 += s[4 * j + 2] + s[4 * j + 3]; }
                            }
                        }
                        wg_wait<0>();
                        fence_regs(o);
                        if (gen) goto general;
#pragma unroll
                        for (int j = JB - 1; j < 16; j++) {
                            if (j >= JB) {
#pragma unroll
                                for (int e = 0; e < 4; e++) ex2v(s[4 * j + e]);
                            }
                            l0 += s[4 * j] + s[4 * j + 1]; l1 += s[4 * j + 2] + s[4 * j + 3];
                        }
#pragma unroll
                        for (int i = 0; i < 32; i++) p[i] = pack_bf16(s[2 * i], s[2 * i + 1]);
                        if (__any_sync(0xffffffffu, !(l0 <= SAFE_SUM && l1 <= SAFE_SUM && l0 >= lo && l1 >= lo))) goto redo;
                        l[0] = l0; l[1] = l1;
                        if (left == 0) goto tail;
                        release(c, BAR_EMPTY + 8 * ck.slot, 1 + (first & heavy));
                        if (pv_cnt) release(c, BAR_EMPTY + 8 * cv.slot, pv_cnt);
                        pv_acc = first ^ 1; pv_mode = 0; pv_cnt = 1 + (first & heavy); first = 0;
                        ck = nck; cv = ncv; cur = ncur;
                        mbar_wait_hot(misc + BAR_FULL + 8 * ck.slot, ck.ph);
                    }
                redo:
                    recompute_scores(s, q, ring + ck.slot * SLOT_BYTES, c);
                    if (first) { mask_any(s, half ^ 1, c); m[0] = m[1] = -INFINITY; }
                    gen = 1;
                general:
                    {
                        float mx[2], alpha[2];
                        row_max<16>(s, mx);
#pragma unroll
                        for (int i = 0; i < 2; i++) {
                            mx[i] = fmaxf(mx[i], m[i]);
                            alpha[i] = ex2(m[i] - mx[i]);
                            m[i] = mx[i];
                            l[i] *= alpha[i];
                        }
                        exp_sum<16, true>(s, m, l[0], l[1]);
#pragma unroll
                        for (int i = 0; i < 64; i++) o[i] *= alpha[(i >> 1) & 1];
#pragma unroll
                        for (int i = 0; i < 32; i++) p[i] = pack_bf16(s[2 * i], s[2 * i + 1]);
                    }
                tail:
                    release(c, BAR_EMPTY + 8 * ck.slot, 1 + (first & heavy));
                    if (pv_cnt) release(c, BAR_EMPTY + 8 * cv.slot, pv_cnt);
                    pv_acc = first ^ 1; pv_mode = first & half; pv_cnt = 1 + (first & heavy); first = 0;
                    if (left == 0) break;
                    ck = cur; cur.adv(); cv = cur; cur.adv();
                    mbar_wait_hot(misc + BAR_FULL + 8 * ck.slot, ck.ph);
                }
            }
            mbar_wait_hot(misc + BAR_FULL + 8 * cur.slot, cur.ph);
            token_wait(w);
            PROF_EV(32);
            issue_pv(o, p, ring + cur.slot * SLOT_BYTES, pv_acc, pv_mode);
            if (w == 0 || v == 0) token_pass(w);
            const uint32_t vslot = cur.slot;
            cur.adv();
            if (v) {
                row_inv(l, inv);
                wg_wait<0>();
                release(c, BAR_EMPTY + 8 * vslot, 1);
                fence_regs(o);
                tile_out(out, g_ctx + (size_t)((2 * team + 1) * 32 + 4 * k + (w ? 3 - (rank ^ SWAPT) : rank ^ SWAPT)) * 16384, 0, 2, c);
#pragma unroll
                for (int i = 0; i < 64; i++) wf[i] = 0u;
                continue;
            }
            cw = cur_at(80);
            mbar_wait_hot(misc + BAR_FULL + 8 * slot_of(76), cur_at(76).ph);
            mbar_wait_hot(misc + BAR_FULL + 8 * slot_of(78), cur_at(78).ph);
            load_afrag<8, 32>(wf, ring + slot_of(78) * SLOT_BYTES + w * 16384, c);
            const uint32_t z = load_afrag<8, 0>(wf, ring + slot_of(76) * SLOT_BYTES + w * 16384, c);
            row_inv(l, inv);
            release(c, BAR_EMPTY + 8 * slot_of(76) + z, 1);
            asm volatile("{\n.reg .pred p;\nsetp.eq.u32 p, %0, 0;\n@p bar.sync 4, 128;\n@!p bar.sync 5, 128;\n}\n" ::"r"(w) : "memory");
            wg_wait<0>();
            release(c, BAR_EMPTY + 8 * vslot, 1);
            fence_regs(o);
            {
                const int g = c.lane >> 2, r7 = ((g & 1) << 2) | (g >> 1);
                const uint32_t base = ring + slot_of(78) * SLOT_BYTES + w * 16384 + (16 * c.warp + r7) * 128 + (((c.lane & 3) ^ r7) << 4);
#pragma unroll
                for (int i = 0; i < 2; i++)
#pragma unroll
                    for (int qq = 0; qq < 4; qq++)
                        asm volatile("st.shared.v4.b32 [%0], {%1,%2,%3,%4};" ::"r"((base ^ ((qq & 1) << 6)) + (qq >> 1) * 8192 + i * 1024),
                                     "r"(pack_bf16(o[16 * qq + 2 * i] * inv[i], o[16 * qq + 2 * i + 1] * inv[i])),
                                     "r"(pack_bf16(o[16 * qq + 4 + 2 * i] * inv[i], o[16 * qq + 4 + 2 * i + 1] * inv[i])),
                                     "r"(pack_bf16(o[16 * qq + 8 + 2 * i] * inv[i], o[16 * qq + 8 + 2 * i + 1] * inv[i])),
                                     "r"(pack_bf16(o[16 * qq + 12 + 2 * i] * inv[i], o[16 * qq + 12 + 2 * i + 1] * inv[i])) : "memory");
                asm volatile("fence.proxy.async.shared::cta;" ::: "memory");
                signal_event(c, EV_CTX + 1);
            }
        }
        }
        {
            float acc[80];
            undef_regs(acc);
            int st = 0, prev = 0; uint32_t ph3 = 0;
            auto op_stage = [&](int i) {
                mbar_wait(misc + BAR_FULL3 + 8 * st, ph3);
                PROF_EV(44);
                uint32_t base = ring + st * ST3_BYTES;
                uint64_t da = mkdesc(base + w * 8192, 16, 1024, 1);
                uint64_t db = mkdesc(base + 16384, 2048, 512, 2);
                wg_fence();
#pragma unroll
                for (int k = 0; k < 4; k++) wgmma_ss_n160_ta0_tb1(acc, da + 2 * k, db + (k >> 1) * 640 + (k & 1) * 64, k ? 1 : i);
                wg_commit();
                if (i > 0) { wg_wait<1>(); if (i <= 32 - NST3) release(c, BAR_EMPTY3 + 8 * prev, 1); }
                prev = st;
                if (++st == NST3) { st = 0; ph3 ^= 1; }
            };
            PROF_EV(40); PROF_GT(65);
#pragma unroll
            for (int i = 0; i < 4; i++) { op_stage(i); store_pair(o, i, out, 8192, inv); }
            signal_event(c, EV_CTX + 3);
#pragma unroll 1
            for (int i = 4; i < 12; i++) op_stage(i);
            mbar_wait(misc + BAR_SEL, 0);
            const uint32_t tag = lds32(misc + MISC_EPOCH) & 1;
            const int g = c.lane >> 2, t = c.lane & 3;
            const int row = (2 * u3 + rank) * 128 + 64 * w + perm32(16 * c.warp + 8 * kap + (((g & 3) << 1) | (g >> 2)));
            const int col = 160 * s3 + 8 * t;
            int sel = -1;
#pragma unroll
            for (int i = 0; i < TOPC; i++) if ((int)lds32(misc + MISC_SEL + 4 * i) == row) sel = i;
            const int t256 = tid - 128;
            uint4* sendp = g_part + (size_t)cta * 2560 + t256;
            if (!PREW && c.lane >= 30) stg128(sendp + 9 * 256, tag ^ 1, tag ^ 1, tag ^ 1, tag ^ 1);
#pragma unroll 1
            for (int i = 12; i < 32; i++) {
                op_stage(i);
                if (PREW && i >= 16 && i < 26) stg128(sendp + (i - 16) * 256, tag ^ 1, tag ^ 1, tag ^ 1, tag ^ 1);
            }
            uint4 xv[5], bv[5];
#pragma unroll
            for (int i = 0; i < 5; i++) xv[i] = ldg128(P.x + (size_t)row * DM + col + 32 * i);
            uint2 stat;
            asm volatile("ld.global.cg.v2.b32 {%0,%1}, [%2];" : "=r"(stat.x), "=r"(stat.y) : "l"(g_stats + row) : "memory");
            wg_wait<0>();
            fence_regs(acc);
            PROF_EV(41); PROF_GT(66);
            float keep[40];
#pragma unroll
            for (int j = 0; j < 10; j++) {
                uint32_t v0 = __float_as_uint(kap ? acc[8 * j + 0] : acc[8 * j + 2]), v1 = __float_as_uint(kap ? acc[8 * j + 1] : acc[8 * j + 3]);
                uint32_t v2 = __float_as_uint(kap ? acc[8 * j + 4] : acc[8 * j + 6]), v3 = __float_as_uint(kap ? acc[8 * j + 5] : acc[8 * j + 7]);
                asm volatile("st.relaxed.gpu.global.v4.b32 [%0], {%1,%2,%3,%4};" ::"l"(sendp + j * 256),
                             "r"((v0 & ~1u) | tag), "r"((v1 & ~1u) | tag), "r"((v2 & ~1u) | tag), "r"((v3 & ~1u) | tag) : "memory");
                keep[4 * j + 0] = kap ? acc[8 * j + 2] : acc[8 * j + 0]; keep[4 * j + 1] = kap ? acc[8 * j + 3] : acc[8 * j + 1];
                keep[4 * j + 2] = kap ? acc[8 * j + 6] : acc[8 * j + 4]; keep[4 * j + 3] = kap ? acc[8 * j + 7] : acc[8 * j + 5];
            }
            PROF_GT(67);
#pragma unroll
            for (int i = 0; i < 5; i++) {
                uint32_t xx[4] = {xv[i].x, xv[i].y, xv[i].z, xv[i].w};
#pragma unroll
                for (int e = 0; e < 4; e++) {
                    asm("sub.rn.bf16x2 %0, %0, %1;" : "+r"(xx[e]) : "r"(stat.x));
                    xx[e] = pack_bf16(bf_lo(xx[e]) * __uint_as_float(stat.y), bf_hi(xx[e]) * __uint_as_float(stat.y));
                }
                bv[i] = make_uint4(xx[0], xx[1], xx[2], xx[3]);
            }
            if (sel >= 0) {
#pragma unroll
                for (int i = 0; i < 5; i++) bv[i] = ldg128(g_brow + sel * DM + col + 32 * i);
            }
            const uint4* recvp = g_part + (size_t)partner * 2560 + t256;
            uint4 rv[10];
            int spins = 0;
            while (POLL1) {
                uint32_t v;
                asm volatile("ld.relaxed.gpu.global.b32 %0, [%1];" : "=r"(v) : "l"(recvp + 9 * 256 + (31 - c.lane)) : "memory");
                if (__all_sync(0xffffffffu, (v & 1u) == tag) || ++spins > 2000000) break;
            }
            PROF_GT(68);
            while (true) {
                uint32_t bad = 0u;
#pragma unroll
                for (int j = 0; j < 10; j++) {
                    asm volatile("ld.relaxed.gpu.global.v4.b32 {%0,%1,%2,%3}, [%4];"
                                 : "=r"(rv[j].x), "=r"(rv[j].y), "=r"(rv[j].z), "=r"(rv[j].w) : "l"(recvp + j * 256) : "memory");
                }
#pragma unroll
                for (int j = 0; j < 10; j++) {
                    rv[j].x ^= tag; rv[j].y ^= tag; rv[j].z ^= tag; rv[j].w ^= tag;
                    bad |= rv[j].x | rv[j].y | rv[j].z | rv[j].w;
                }
                if (__all_sync(0xffffffffu, (bad & 1u) == 0) || ++spins > 2000000) break;
            }
            PROF_GT(69);
            uint32_t pk[20];
#pragma unroll
            for (int j = 0; j < 10; j++) {
                pk[2 * j] = pack_bf16(keep[4 * j] + __uint_as_float(rv[j].x), keep[4 * j + 1] + __uint_as_float(rv[j].y));
                pk[2 * j + 1] = pack_bf16(keep[4 * j + 2] + __uint_as_float(rv[j].z), keep[4 * j + 3] + __uint_as_float(rv[j].w));
            }
#pragma unroll
            for (int i = 0; i < 5; i++) {
                uint32_t a0 = pk[4 * i], a1 = pk[4 * i + 1], a2 = pk[4 * i + 2], a3 = pk[4 * i + 3];
                uint32_t x0 = (t & 1) ? a0 : a1, x1 = (t & 1) ? a2 : a3;
                x0 = __shfl_xor_sync(0xffffffffu, x0, 1); x1 = __shfl_xor_sync(0xffffffffu, x1, 1);
                if (t & 1) { a0 = x0; a2 = x1; } else { a1 = x0; a3 = x1; }
                x0 = (t & 2) ? a0 : a2; x1 = (t & 2) ? a1 : a3;
                x0 = __shfl_xor_sync(0xffffffffu, x0, 2); x1 = __shfl_xor_sync(0xffffffffu, x1, 2);
                if (t & 2) { a0 = x0; a1 = x1; } else { a2 = x0; a3 = x1; }
                uint32_t av[4] = {a0, a1, a2, a3};
                uint32_t xx[4] = {xv[i].x, xv[i].y, xv[i].z, xv[i].w}, bb[4] = {bv[i].x, bv[i].y, bv[i].z, bv[i].w};
                uint32_t ov[4];
#pragma unroll
                for (int e = 0; e < 4; e++) {
                    asm("add.rn.bf16x2 %0, %1, %2;" : "=r"(ov[e]) : "r"(xx[e]), "r"(av[e]));
                    asm("add.rn.bf16x2 %0, %0, %1;" : "+r"(ov[e]) : "r"(bb[e]));
                }
                stg128(P.out + (size_t)row * DM + col + 32 * i, ov[0], ov[1], ov[2], ov[3]);
            }
            PROF_EV(42); PROF_GT(43);
        }
    }
}

typedef CUresult (*EncodeFn)(CUtensorMap*, CUtensorMapDataType, cuuint32_t, void*, const cuuint64_t*, const cuuint64_t*, const cuuint32_t*,
                             const cuuint32_t*, CUtensorMapInterleave, CUtensorMapSwizzle, CUtensorMapL2promotion, CUtensorMapFloatOOBfill);

void make_map2d(EncodeFn enc, CUtensorMap* tm, const void* p, uint64_t cols, uint64_t rows, uint32_t box_rows = 128) {
    cuuint64_t gd[2] = {cols, rows}, gs[1] = {cols * 2};
    cuuint32_t box[2] = {64, box_rows}, es[2] = {1, 1};
    enc(tm, CU_TENSOR_MAP_DATA_TYPE_BFLOAT16, 2, const_cast<void*>(p), gd, gs, box, es, CU_TENSOR_MAP_INTERLEAVE_NONE,
        CU_TENSOR_MAP_SWIZZLE_128B, CU_TENSOR_MAP_L2_PROMOTION_L2_128B, CU_TENSOR_MAP_FLOAT_OOB_FILL_NONE);
}

void make_map3d(EncodeFn enc, CUtensorMap* tm, const void* p, uint64_t cols, uint64_t rows, uint32_t bw, uint32_t nb) {
    cuuint64_t gd[3] = {bw, rows, cols / bw}, gs[2] = {cols * 2, bw * 2};
    cuuint32_t box[3] = {bw, 32, nb}, es[3] = {1, 1, 1};
    enc(tm, CU_TENSOR_MAP_DATA_TYPE_BFLOAT16, 3, const_cast<void*>(p), gd, gs, box, es, CU_TENSOR_MAP_INTERLEAVE_NONE,
        bw == 64 ? CU_TENSOR_MAP_SWIZZLE_128B : CU_TENSOR_MAP_SWIZZLE_64B, CU_TENSOR_MAP_L2_PROMOTION_L2_128B, CU_TENSOR_MAP_FLOAT_OOB_FILL_NONE);
}

}

extern "C" void kernel_launch(void* const* d_in, const int* in_sizes, int n_in, void* d_out, int out_size) {
    (void)in_sizes; (void)n_in; (void)out_size;
    static EncodeFn enc = nullptr;
    if (!enc) {
        void* fn = nullptr;
        cudaDriverEntryPointQueryResult qr;
        cudaGetDriverEntryPoint("cuTensorMapEncodeTiled", &fn, cudaEnableDefault, &qr);
        enc = (EncodeFn)fn;
        cudaFuncSetAttribute(fused_kernel, cudaFuncAttributeMaxDynamicSharedMemorySize, SMEM_BYTES);
    }
    CUtensorMap tmC, tmWk, tmWv, tmWq, tmWo, tmG, tmU, tmD;
    make_map2d(enc, &tmC, d_in[1], DC, SEQ);
    make_map2d(enc, &tmWq, d_in[2], 4096, DM, 64);
    make_map2d(enc, &tmWk, d_in[3], 4096, DC);
    make_map2d(enc, &tmWv, d_in[4], 4096, DC);
    make_map3d(enc, &tmWo, d_in[5], DM, 4096, 32, 5);
    make_map3d(enc, &tmG, d_in[8], FF, DM, 64, 7);
    make_map3d(enc, &tmU, d_in[9], FF, DM, 64, 7);
    make_map3d(enc, &tmD, d_in[10], DM, FF, 64, 10);
    Params P;
    P.x = (const __nv_bfloat16*)d_in[0];
    P.c = (const __nv_bfloat16*)d_in[1];
    P.wk = (const __nv_bfloat16*)d_in[3];
    P.wv = (const __nv_bfloat16*)d_in[4];
    P.wo = (const __nv_bfloat16*)d_in[5];
    P.wr = (const __nv_bfloat16*)d_in[7];
    P.out = (__nv_bfloat16*)d_out;
    fused_kernel<<<132, 384, SMEM_BYTES>>>(tmC, tmWk, tmWv, tmWq, tmWo, tmG, tmU, tmD, P);
}
```

```cpp
#include <cuda_runtime.h>
#include <cuda_bf16.h>
#include <cuda.h>
#include <stdint.h>

#define SWAPT 1
#define DEFER 1
#define HOLD0 6
#define HM 513
#define OP_PF 8
#define PF_START 9
#define LATE_AT 18
#define CDELAY 500
#define AUXDELAY 1000
namespace {

constexpr int SEQ = 2048, NH = 32, DM = 640, DC = 512, FF = 1728, TOPC = 8;
constexpr int NSLOT = 7, SLOT_BYTES = 32768;
constexpr int NST3 = 6, ST3_BYTES = 36864;
constexpr int RING_BYTES = NSLOT * SLOT_BYTES;
constexpr int SMEM_BYTES = RING_BYTES + 3072;

constexpr int BAR_FULL = 96  , BAR_FULL3 = 152  , BAR_DEP = 200  , BAR_SEL = 464,
              BAR_LN = 472  , BAR_EV = 504  , BAR_EMPTY = 760  , BAR_EMPTY3 = 816  ,
              BAR_PROG = 864  , MISC_EPOCH = 896, MISC_SMID = 900  , MISC_SEL = 912, MISC_WR = 1024  ;
constexpr int D_LN = 0  , D_KV = 4  , D_WAR = 14  , D_CTX = 16  ;
constexpr int EV_KV = 0  , EV_CTX = 12  ;

constexpr int FL_MOE_CNT = 0, FL_MOE_DONE = 1, FL_LN = 16  , FL_KV = 32  , FL_CTX = 416  , FL_WAR = 672  , FL_TOTAL = 704;

__device__ __align__(1024) unsigned char g_K[16 * 32 * 16384];
__device__ __align__(1024) unsigned char g_V[16 * 32 * 16384];
__device__ __align__(1024) unsigned char g_ctx[NH * 32 * 16384];
__device__ __align__(1024) unsigned char g_xn[16 * 10 * 16384];
__device__ __align__(1024) uint4 g_part[128 * 10 * 256];
__device__ float g_router[SEQ];
__device__ uint2 g_stats[SEQ];
__device__ __align__(16) float g_moe_part[4 * TOPC * DM];
__device__ __align__(16) __nv_bfloat16 g_brow[TOPC * DM];
__device__ __align__(16) int g_sel[TOPC];
__device__ unsigned g_flags[FL_TOTAL * 8];
__device__ unsigned g_epoch;
__device__ unsigned g_roleq[130];

struct Params {
    const __nv_bfloat16 *x, *c, *wr, *wk, *wv, *wo;
    __nv_bfloat16* out;
};

__device__ __forceinline__ uint32_t smem_u32(const void* p) { return (uint32_t)__cvta_generic_to_shared(p); }
__device__ __forceinline__ void mbar_init(uint32_t bar, int cnt) { asm volatile("mbarrier.init.shared::cta.b64 [%0], %1;" ::"r"(bar), "r"(cnt)); }
__device__ __forceinline__ void mbar_expect_tx(uint32_t bar, uint32_t bytes) {
    asm volatile("mbarrier.arrive.expect_tx.shared::cta.b64 _, [%0], %1;" ::"r"(bar), "r"(bytes) : "memory");
}
__device__ __forceinline__ void mbar_arrive(uint32_t bar) { asm volatile("mbarrier.arrive.shared::cta.b64 _, [%0];" ::"r"(bar) : "memory"); }
__device__ __forceinline__ void mbar_arrive_cluster(uint32_t cluster_addr, uint32_t cnt) {
    asm volatile("mbarrier.arrive.shared::cluster.b64 _, [%0], %1;" ::"r"(cluster_addr), "r"(cnt) : "memory");
}
__device__ __forceinline__ uint32_t mapa(uint32_t addr, uint32_t cta) {
    uint32_t r; asm("mapa.shared::cluster.u32 %0, %1, %2;" : "=r"(r) : "r"(addr), "r"(cta)); return r;
}
__device__ __forceinline__ void mbar_wait(uint32_t bar, uint32_t parity) {
    asm volatile(
        "{\n.reg .pred p;\n.reg .u32 n;\n"
        "mbarrier.try_wait.parity.shared::cta.b64 p, [%0], %1;\n"
        "@p bra DONE;\n"
        "mov.u32 n, 0;\n"
        "LAB_WAIT:\n"
        "mbarrier.try_wait.parity.shared::cta.b64 p, [%0], %1, 100000;\n"
        "@p bra DONE;\n"
        "add.u32 n, n, 1;\n"
        "setp.lt.u32 p, n, 200000;\n"
        "@p bra LAB_WAIT;\n"
        "trap;\n"
        "DONE:\n}\n" ::"r"(bar), "r"(parity) : "memory");
}
__device__ __forceinline__ void mbar_wait_hot(uint32_t bar, uint32_t parity) {
    asm volatile("{\n.reg .pred p;\nLAB_WAIT:\nmbarrier.try_wait.parity.shared::cta.b64 p, [%0], %1;\n@!p bra LAB_WAIT;\n}\n" ::"r"(bar), "r"(parity) : "memory");
}
__device__ __forceinline__ void flag_wait(const unsigned* flag, unsigned target) {
    asm volatile(
        "{\n.reg .pred p;\n.reg .u32 n, v;\n.reg .s32 d;\n"
        "mov.u32 n, 0;\n"
        "LAB_WAIT:\n"
        "ld.acquire.gpu.global.u32 v, [%0];\n"
        "sub.s32 d, v, %1;\n"
        "setp.ge.s32 p, d, 0;\n"
        "@p bra DONE;\n"
        "nanosleep.u32 40;\n"
        "add.u32 n, n, 1;\n"
        "setp.lt.u32 p, n, 3000000;\n"
        "@p bra LAB_WAIT;\n"
        "trap;\n"
        "DONE:\n}\n" ::"l"(flag), "r"(target) : "memory");
}
__device__ __forceinline__ void flag_signal(unsigned* flag) {
    asm volatile("red.release.gpu.global.add.u32 [%0], 1;" ::"l"(flag) : "memory");
}
__device__ __forceinline__ void fence_async_global() { asm volatile("fence.proxy.async.global;" ::: "memory"); }
__device__ __forceinline__ unsigned* flag_ptr(int idx) { return g_flags + idx * 8; }

__device__ __forceinline__ uint64_t policy_stream() {
    uint64_t p; asm("createpolicy.fractional.L2::evict_first.b64 %0, 1.0;" : "=l"(p)); return p;
}
__device__ __forceinline__ uint64_t policy_normal() { return 0x1000000000000000ull; }
__device__ __forceinline__ uint64_t policy(bool stream) { return stream ? policy_stream() : policy_normal(); }
__device__ __forceinline__ void bulk_load(uint32_t dst, const void* src, uint32_t bytes, uint32_t bar, uint64_t pol) {
    asm volatile("cp.async.bulk.shared::cluster.global.mbarrier::complete_tx::bytes.L2::cache_hint [%0], [%1], %2, [%3], %4;"
                 ::"r"(dst), "l"(src), "r"(bytes), "r"(bar), "l"(pol) : "memory");
}
__device__ __forceinline__ void bulk_load_mc(uint32_t dst, const void* src, uint32_t bytes, uint32_t bar, uint64_t pol) {
    asm volatile("cp.async.bulk.shared::cluster.global.mbarrier::complete_tx::bytes.multicast::cluster.L2::cache_hint [%0], [%1], %2, [%3], %4, %5;"
                 ::"r"(dst), "l"(src), "r"(bytes), "r"(bar), "h"((uint16_t)3), "l"(pol) : "memory");
}
__device__ __forceinline__ void tma2d(uint32_t dst, const CUtensorMap* tm, int c0, int c1, uint32_t bar, uint64_t pol) {
    asm volatile("cp.async.bulk.tensor.2d.shared::cluster.global.mbarrier::complete_tx::bytes.L2::cache_hint [%0], [%1, {%3, %4}], [%2], %5;"
                 ::"r"(dst), "l"(tm), "r"(bar), "r"(c0), "r"(c1), "l"(pol) : "memory");
}
__device__ __forceinline__ void tma2d_mc(uint32_t dst, const CUtensorMap* tm, int c0, int c1, uint32_t bar, uint64_t pol) {
    asm volatile("cp.async.bulk.tensor.2d.shared::cluster.global.mbarrier::complete_tx::bytes.multicast::cluster.L2::cache_hint [%0], [%1, {%3, %4}], [%2], %5, %6;"
                 ::"r"(dst), "l"(tm), "r"(bar), "r"(c0), "r"(c1), "h"((uint16_t)3), "l"(pol) : "memory");
}
__device__ __forceinline__ void tma3d_mc(uint32_t dst, const CUtensorMap* tm, int c0, int c1, int c2, uint32_t bar, uint64_t pol) {
    asm volatile("cp.async.bulk.tensor.3d.shared::cluster.global.mbarrier::complete_tx::bytes.multicast::cluster.L2::cache_hint [%0], [%1, {%3, %4, %5}], [%2], %6, %7;"
                 ::"r"(dst), "l"(tm), "r"(bar), "r"(c0), "r"(c1), "r"(c2), "h"((uint16_t)3), "l"(pol) : "memory");
}
__device__ __forceinline__ void tma3d(uint32_t dst, const CUtensorMap* tm, int c0, int c1, int c2, uint32_t bar) {
    asm volatile("cp.async.bulk.tensor.3d.shared::cluster.global.mbarrier::complete_tx::bytes.L2::cache_hint [%0], [%1, {%3, %4, %5}], [%2], %6;"
                 ::"r"(dst), "l"(tm), "r"(bar), "r"(c0), "r"(c1), "r"(c2), "l"(policy_stream()) : "memory");
}
__device__ __forceinline__ void tma2d_prefetch(const CUtensorMap* tm, int c0, int c1) {
    asm volatile("cp.async.bulk.prefetch.tensor.2d.L2.global [%0, {%1, %2}];" ::"l"(tm), "r"(c0), "r"(c1) : "memory");
}
__device__ __forceinline__ void tma3d_prefetch(const CUtensorMap* tm, int c0, int c1, int c2) {
    asm volatile("cp.async.bulk.prefetch.tensor.3d.L2.global [%0, {%1, %2, %3}];" ::"l"(tm), "r"(c0), "r"(c1), "r"(c2) : "memory");
}
__device__ __forceinline__ void l2_prefetch(const void* p, uint32_t bytes) {
    asm volatile("cp.async.bulk.prefetch.L2.global [%0], %1;" ::"l"(p), "r"(bytes) : "memory");
}
__device__ __forceinline__ bool elect_one() {
    uint32_t r; asm volatile("{\n.reg .pred p;\nelect.sync _|p, 0xffffffff;\nselp.u32 %0, 1, 0, p;\n}\n" : "=r"(r)); return r != 0;
}
__device__ __forceinline__ void wg_fence() { asm volatile("wgmma.fence.sync.aligned;" ::: "memory"); }
__device__ __forceinline__ void wg_commit() { asm volatile("wgmma.commit_group.sync.aligned;" ::: "memory"); }
template <int N> __device__ __forceinline__ void wg_wait() { asm volatile("wgmma.wait_group.sync.aligned %0;" ::"n"(N) : "memory"); }
__device__ __forceinline__ void bar_sync(int id, int n) { asm volatile("bar.sync %0, %1;" ::"r"(id), "r"(n) : "memory"); }
__device__ __forceinline__ void bar_arrive(int id, int n) { asm volatile("bar.arrive %0, %1;" ::"r"(id), "r"(n) : "memory"); }
__device__ __forceinline__ void token_wait(int w) {
    asm volatile("{\n.reg .pred p;\nsetp.eq.u32 p, %0, 0;\n@p bar.sync 1, 256;\n@!p bar.sync 2, 256;\n}\n" ::"r"(w) : "memory");
}
__device__ __forceinline__ void token_pass(int w) {
    asm volatile("{\n.reg .pred p;\nsetp.eq.u32 p, %0, 0;\n@p bar.arrive 2, 256;\n@!p bar.arrive 1, 256;\n}\n" ::"r"(w) : "memory");
}
template <int N> __device__ __forceinline__ void fence_regs(float (&a)[N]) {
#pragma unroll
    for (int i = 0; i < N; i++) asm volatile("" : "+f"(a[i])::"memory");
}
template <int N> __device__ __forceinline__ void undef_regs(float (&a)[N]) {
#pragma unroll
    for (int i = 0; i < N; i++) asm volatile("" : "=f"(a[i]));
}
__device__ __forceinline__ void ldsm4t(uint32_t& r0, uint32_t& r1, uint32_t& r2, uint32_t& r3, uint32_t addr) {
    asm volatile("ldmatrix.sync.aligned.m8n8.x4.trans.shared.b16 {%0,%1,%2,%3}, [%4];"
                 : "=r"(r0), "=r"(r1), "=r"(r2), "=r"(r3) : "r"(addr) : "memory");
}
__device__ __forceinline__ uint32_t pack_bf16(float lo, float hi) {
    uint32_t r; asm("cvt.rn.bf16x2.f32 %0, %1, %2;" : "=r"(r) : "f"(hi), "f"(lo)); return r;
}
__device__ __forceinline__ float bf_lo(uint32_t v) { return __uint_as_float(v << 16); }
__device__ __forceinline__ float bf_hi(uint32_t v) { return __uint_as_float(v & 0xffff0000u); }
__device__ __forceinline__ float bf_round(float v) { return __bfloat162float(__float2bfloat16_rn(v)); }
__device__ __forceinline__ float ex2(float v) { float r; asm("ex2.approx.ftz.f32 %0, %1;" : "=f"(r) : "f"(v)); return r; }
__device__ __forceinline__ void ex2v(float& v) { asm volatile("ex2.approx.ftz.f32 %0, %0;" : "+f"(v)); }
__device__ __forceinline__ float rcp_fast(float v) { float r; asm("rcp.approx.ftz.f32 %0, %1;" : "=f"(r) : "f"(v)); return r; }
__device__ __forceinline__ float sqrt_fast(float v) { float r; asm("sqrt.approx.ftz.f32 %0, %1;" : "=f"(r) : "f"(v)); return r; }
__device__ __forceinline__ void stg128(void* p, uint32_t a, uint32_t b, uint32_t c, uint32_t d) {
    asm volatile("st.global.v4.b32 [%0], {%1,%2,%3,%4};" ::"l"(p), "r"(a), "r"(b), "r"(c), "r"(d) : "memory");
}
__device__ __forceinline__ uint4 ldg128(const void* p) {
    uint4 v; asm volatile("ld.global.cg.v4.b32 {%0,%1,%2,%3}, [%4];" : "=r"(v.x), "=r"(v.y), "=r"(v.z), "=r"(v.w) : "l"(p) : "memory"); return v;
}
__device__ __forceinline__ uint64_t mkdesc(uint32_t addr, uint32_t lbo, uint32_t sbo, uint32_t swz) {
    uint32_t lo = ((addr & 0x3FFFF) >> 4) | ((lbo >> 4) << 16);
    uint32_t hi = (sbo >> 4) | (swz << 30);
    return ((uint64_t)hi << 32) | lo;
}
__device__ __forceinline__ int perm32(int v) { return (v & ~30) | ((v >> 2) & 6) | ((v << 2) & 24); }

__device__ __forceinline__ void wgmma_rs_n128_ta0_tb0(float (&d)[64], uint32_t a0, uint32_t a1, uint32_t a2, uint32_t a3, uint64_t descB, int scaleD) {
  asm volatile("{\n.reg .pred p;\nsetp.ne.b32 p, %69, 0;\n"
    "wgmma.mma_async.sync.aligned.m64n128k16.f32.bf16.bf16 "
    "{%0, %1, %2, %3, %4, %5, %6, %7, %8, %9, %10, %11, %12, %13, %14, %15, %16, %17, %18, %19, %20, %21, %22, %23, %24, %25, %26, %27, %28, %29, %30, %31, %32, %33, %34, %35, %36, %37, %38, %39, %40, %41, %42, %43, %44, %45, %46, %47, %48, %49, %50, %51, %52, %53, %54, %55, %56, %57, %58, %59, %60, %61, %62, %63}, "
    "{%64, %65, %66, %67}, %68, p, 1, 1, 0;\n}\n"
    : "+f"(d[0]), "+f"(d[1]), "+f"(d[2]), "+f"(d[3]), "+f"(d[4]), "+f"(d[5]), "+f"(d[6]), "+f"(d[7]), "+f"(d[8]), "+f"(d[9]), "+f"(d[10]), "+f"(d[11]), "+f"(d[12]), "+f"(d[13]), "+f"(d[14]), "+f"(d[15]), "+f"(d[16]), "+f"(d[17]), "+f"(d[18]), "+f"(d[19]), "+f"(d[20]), "+f"(d[21]), "+f"(d[22]), "+f"(d[23]), "+f"(d[24]), "+f"(d[25]), "+f"(d[26]), "+f"(d[27]), "+f"(d[28]), "+f"(d[29]), "+f"(d[30]), "+f"(d[31]), "+f"(d[32]), "+f"(d[33]), "+f"(d[34]), "+f"(d[35]), "+f"(d[36]), "+f"(d[37]), "+f"(d[38]), "+f"(d[39]), "+f"(d[40]), "+f"(d[41]), "+f"(d[42]), "+f"(d[43]), "+f"(d[44]), "+f"(d[45]), "+f"(d[46]), "+f"(d[47]), "+f"(d[48]), "+f"(d[49]), "+f"(d[50]), "+f"(d[51]), "+f"(d[52]), "+f"(d[53]), "+f"(d[54]), "+f"(d[55]), "+f"(d[56]), "+f"(d[57]), "+f"(d[58]), "+f"(d[59]), "+f"(d[60]), "+f"(d[61]), "+f"(d[62]), "+f"(d[63])
    : "r"(a0), "r"(a1), "r"(a2), "r"(a3), "l"(descB), "r"(scaleD));
}
__device__ __forceinline__ void wgmma_rs_n128_ta0_tb1(float (&d)[64], uint32_t a0, uint32_t a1, uint32_t a2, uint32_t a3, uint64_t descB, int scaleD) {
  asm volatile("{\n.reg .pred p;\nsetp.ne.b32 p, %69, 0;\n"
    "wgmma.mma_async.sync.aligned.m64n128k16.f32.bf16.bf16 "
    "{%0, %1, %2, %3, %4, %5, %6, %7, %8, %9, %10, %11, %12, %13, %14, %15, %16, %17, %18, %19, %20, %21, %22, %23, %24, %25, %26, %27, %28, %29, %30, %31, %32, %33, %34, %35, %36, %37, %38, %39, %40, %41, %42, %43, %44, %45, %46, %47, %48, %49, %50, %51, %52, %53, %54, %55, %56, %57, %58, %59, %60, %61, %62, %63}, "
    "{%64, %65, %66, %67}, %68, p, 1, 1, 1;\n}\n"
    : "+f"(d[0]), "+f"(d[1]), "+f"(d[2]), "+f"(d[3]), "+f"(d[4]), "+f"(d[5]), "+f"(d[6]), "+f"(d[7]), "+f"(d[8]), "+f"(d[9]), "+f"(d[10]), "+f"(d[11]), "+f"(d[12]), "+f"(d[13]), "+f"(d[14]), "+f"(d[15]), "+f"(d[16]), "+f"(d[17]), "+f"(d[18]), "+f"(d[19]), "+f"(d[20]), "+f"(d[21]), "+f"(d[22]), "+f"(d[23]), "+f"(d[24]), "+f"(d[25]), "+f"(d[26]), "+f"(d[27]), "+f"(d[28]), "+f"(d[29]), "+f"(d[30]), "+f"(d[31]), "+f"(d[32]), "+f"(d[33]), "+f"(d[34]), "+f"(d[35]), "+f"(d[36]), "+f"(d[37]), "+f"(d[38]), "+f"(d[39]), "+f"(d[40]), "+f"(d[41]), "+f"(d[42]), "+f"(d[43]), "+f"(d[44]), "+f"(d[45]), "+f"(d[46]), "+f"(d[47]), "+f"(d[48]), "+f"(d[49]), "+f"(d[50]), "+f"(d[51]), "+f"(d[52]), "+f"(d[53]), "+f"(d[54]), "+f"(d[55]), "+f"(d[56]), "+f"(d[57]), "+f"(d[58]), "+f"(d[59]), "+f"(d[60]), "+f"(d[61]), "+f"(d[62]), "+f"(d[63])
    : "r"(a0), "r"(a1), "r"(a2), "r"(a3), "l"(descB), "r"(scaleD));
}
__device__ __forceinline__ void wgmma_rs_n64_ta0_tb1(float (&d)[32], uint32_t a0, uint32_t a1, uint32_t a2, uint32_t a3, uint64_t descB, int scaleD) {
  asm volatile("{\n.reg .pred p;\nsetp.ne.b32 p, %37, 0;\n"
    "wgmma.mma_async.sync.aligned.m64n64k16.f32.bf16.bf16 "
    "{%0, %1, %2, %3, %4, %5, %6, %7, %8, %9, %10, %11, %12, %13, %14, %15, %16, %17, %18, %19, %20, %21, %22, %23, %24, %25, %26, %27, %28, %29, %30, %31}, "
    "{%32, %33, %34, %35}, %36, p, 1, 1, 1;\n}\n"
    : "+f"(d[0]), "+f"(d[1]), "+f"(d[2]), "+f"(d[3]), "+f"(d[4]), "+f"(d[5]), "+f"(d[6]), "+f"(d[7]), "+f"(d[8]), "+f"(d[9]), "+f"(d[10]), "+f"(d[11]), "+f"(d[12]), "+f"(d[13]), "+f"(d[14]), "+f"(d[15]), "+f"(d[16]), "+f"(d[17]), "+f"(d[18]), "+f"(d[19]), "+f"(d[20]), "+f"(d[21]), "+f"(d[22]), "+f"(d[23]), "+f"(d[24]), "+f"(d[25]), "+f"(d[26]), "+f"(d[27]), "+f"(d[28]), "+f"(d[29]), "+f"(d[30]), "+f"(d[31])
    : "r"(a0), "r"(a1), "r"(a2), "r"(a3), "l"(descB), "r"(scaleD));
}
__device__ __forceinline__ void wgmma_ss_n128_ta0_tb1(float (&d)[64], uint64_t descA, uint64_t descB, int scaleD) {
  asm volatile("{\n.reg .pred p;\nsetp.ne.b32 p, %66, 0;\n"
    "wgmma.mma_async.sync.aligned.m64n128k16.f32.bf16.bf16 "
    "{%0, %1, %2, %3, %4, %5, %6, %7, %8, %9, %10, %11, %12, %13, %14, %15, %16, %17, %18, %19, %20, %21, %22, %23, %24, %25, %26, %27, %28, %29, %30, %31, %32, %33, %34, %35, %36, %37, %38, %39, %40, %41, %42, %43, %44, %45, %46, %47, %48, %49, %50, %51, %52, %53, %54, %55, %56, %57, %58, %59, %60, %61, %62, %63}, "
    "%64, %65, p, 1, 1, 0, 1;\n}\n"
    : "+f"(d[0]), "+f"(d[1]), "+f"(d[2]), "+f"(d[3]), "+f"(d[4]), "+f"(d[5]), "+f"(d[6]), "+f"(d[7]), "+f"(d[8]), "+f"(d[9]), "+f"(d[10]), "+f"(d[11]), "+f"(d[12]), "+f"(d[13]), "+f"(d[14]), "+f"(d[15]), "+f"(d[16]), "+f"(d[17]), "+f"(d[18]), "+f"(d[19]), "+f"(d[20]), "+f"(d[21]), "+f"(d[22]), "+f"(d[23]), "+f"(d[24]), "+f"(d[25]), "+f"(d[26]), "+f"(d[27]), "+f"(d[28]), "+f"(d[29]), "+f"(d[30]), "+f"(d[31]), "+f"(d[32]), "+f"(d[33]), "+f"(d[34]), "+f"(d[35]), "+f"(d[36]), "+f"(d[37]), "+f"(d[38]), "+f"(d[39]), "+f"(d[40]), "+f"(d[41]), "+f"(d[42]), "+f"(d[43]), "+f"(d[44]), "+f"(d[45]), "+f"(d[46]), "+f"(d[47]), "+f"(d[48]), "+f"(d[49]), "+f"(d[50]), "+f"(d[51]), "+f"(d[52]), "+f"(d[53]), "+f"(d[54]), "+f"(d[55]), "+f"(d[56]), "+f"(d[57]), "+f"(d[58]), "+f"(d[59]), "+f"(d[60]), "+f"(d[61]), "+f"(d[62]), "+f"(d[63])
    : "l"(descA), "l"(descB), "r"(scaleD));
}
__device__ __forceinline__ void wgmma_ss_n160_ta0_tb1(float (&d)[80], uint64_t descA, uint64_t descB, int scaleD) {
  asm volatile("{\n.reg .pred p;\nsetp.ne.b32 p, %82, 0;\n"
    "wgmma.mma_async.sync.aligned.m64n160k16.f32.bf16.bf16 "
    "{%0, %1, %2, %3, %4, %5, %6, %7, %8, %9, %10, %11, %12, %13, %14, %15, %16, %17, %18, %19, %20, %21, %22, %23, %24, %25, %26, %27, %28, %29, %30, %31, %32, %33, %34, %35, %36, %37, %38, %39, %40, %41, %42, %43, %44, %45, %46, %47, %48, %49, %50, %51, %52, %53, %54, %55, %56, %57, %58, %59, %60, %61, %62, %63, %64, %65, %66, %67, %68, %69, %70, %71, %72, %73, %74, %75, %76, %77, %78, %79}, "
    "%80, %81, p, 1, 1, 0, 1;\n}\n"
    : "+f"(d[0]), "+f"(d[1]), "+f"(d[2]), "+f"(d[3]), "+f"(d[4]), "+f"(d[5]), "+f"(d[6]), "+f"(d[7]), "+f"(d[8]), "+f"(d[9]), "+f"(d[10]), "+f"(d[11]), "+f"(d[12]), "+f"(d[13]), "+f"(d[14]), "+f"(d[15]), "+f"(d[16]), "+f"(d[17]), "+f"(d[18]), "+f"(d[19]), "+f"(d[20]), "+f"(d[21]), "+f"(d[22]), "+f"(d[23]), "+f"(d[24]), "+f"(d[25]), "+f"(d[26]), "+f"(d[27]), "+f"(d[28]), "+f"(d[29]), "+f"(d[30]), "+f"(d[31]), "+f"(d[32]), "+f"(d[33]), "+f"(d[34]), "+f"(d[35]), "+f"(d[36]), "+f"(d[37]), "+f"(d[38]), "+f"(d[39]), "+f"(d[40]), "+f"(d[41]), "+f"(d[42]), "+f"(d[43]), "+f"(d[44]), "+f"(d[45]), "+f"(d[46]), "+f"(d[47]), "+f"(d[48]), "+f"(d[49]), "+f"(d[50]), "+f"(d[51]), "+f"(d[52]), "+f"(d[53]), "+f"(d[54]), "+f"(d[55]), "+f"(d[56]), "+f"(d[57]), "+f"(d[58]), "+f"(d[59]), "+f"(d[60]), "+f"(d[61]), "+f"(d[62]), "+f"(d[63]), "+f"(d[64]), "+f"(d[65]), "+f"(d[66]), "+f"(d[67]), "+f"(d[68]), "+f"(d[69]), "+f"(d[70]), "+f"(d[71]), "+f"(d[72]), "+f"(d[73]), "+f"(d[74]), "+f"(d[75]), "+f"(d[76]), "+f"(d[77]), "+f"(d[78]), "+f"(d[79])
    : "l"(descA), "l"(descB), "r"(scaleD));
}

#define PROF_DECL(b)
#define PROF_EV(tag)
#define PROF_GT(tag)

template <int N> struct IC { static constexpr int value = N; };
struct Cur {
    uint32_t slot, ph;
    __device__ __forceinline__ void adv() { if (++slot == NSLOT) { slot = 0; ph ^= 1; } }
};
constexpr int E0 = 2;
__host__ __device__ constexpr uint32_t slot_of(int e) { return (e + E0) % NSLOT; }
__device__ __forceinline__ Cur cur_at(int e) { Cur c; c.slot = (e + E0) % NSLOT; c.ph = ((e + E0) / NSLOT) & 1; return c; }

__device__ __forceinline__ int op_head(int i, int kap) { return 16 * kap + 2 * (i & 7) + (i >> 3); }

constexpr float SM_SCALE = 0.08838834764831845f * 1.4426950408889634f;

struct Ctx {
    uint32_t ring, misc;
    uint32_t rel;
    int w, warp, lane;
};
__device__ __forceinline__ void release(const Ctx& c, uint32_t off, uint32_t cnt) {
    if (c.lane < 2) mbar_arrive_cluster(c.rel + off, cnt);
}
__device__ __forceinline__ void signal_event(const Ctx& c, int ev) {
    __syncwarp();
    if (c.lane == 0) mbar_arrive(c.misc + BAR_EV + (c.w * 16 + ev) * 8);
}
template <int NK, int OFF, int N>
__device__ __forceinline__ uint32_t load_afrag(uint32_t (&a)[N], uint32_t base, const Ctx& c) {
    int r = c.lane & 7, mat = c.lane >> 3;
    uint32_t addr = base + (8 * (mat >> 1) + r) * 128 + (((2 * c.warp + (mat & 1)) ^ r) << 4);
#pragma unroll
    for (int k = 0; k < NK; k++) ldsm4t(a[OFF + 4 * k], a[OFF + 4 * k + 1], a[OFF + 4 * k + 2], a[OFF + 4 * k + 3], addr + k * 2048);
    uint32_t dep = 0;
#pragma unroll
    for (int k = 0; k < NK; k++) dep |= a[OFF + 4 * k];
    return dep & blockIdx.y;
}
__device__ __forceinline__ void tile_out(unsigned char* (&out)[2], unsigned char* dst, int row0, int perm, const Ctx& c) {
#pragma unroll
    for (int i = 0; i < 2; i++) {
        int row = row0 + 16 * c.warp + 8 * i + (c.lane >> 2);
        if (perm) row = perm32(row);
        out[i] = dst + row * 64 + (((c.lane ^ (row >> 1)) & 3) << 4);
    }
}
__device__ __forceinline__ void store_pair(const float (&a)[64], int q, unsigned char* const (&out)[2], int quarter_stride, const float (&f)[2]) {
#pragma unroll
    for (int i = 0; i < 2; i++)
        stg128(out[i] + q * quarter_stride,
               pack_bf16(a[16 * q + 2 * i] * f[i], a[16 * q + 2 * i + 1] * f[i]), pack_bf16(a[16 * q + 4 + 2 * i] * f[i], a[16 * q + 4 + 2 * i + 1] * f[i]),
               pack_bf16(a[16 * q + 8 + 2 * i] * f[i], a[16 * q + 8 + 2 * i + 1] * f[i]), pack_bf16(a[16 * q + 12 + 2 * i] * f[i], a[16 * q + 12 + 2 * i + 1] * f[i]));
}

constexpr float SAFE_SUM = 1099511627776.0f;
template <int NJ>
__device__ __forceinline__ void row_max(const float (&s)[4 * NJ], float (&mx)[2]) {
#pragma unroll
    for (int i = 0; i < 2; i++) {
        float a = fmaxf(s[2 * i], s[2 * i + 1]), b = fmaxf(s[4 + 2 * i], s[4 + 2 * i + 1]);
#pragma unroll
        for (int j = 2; j < NJ; j += 2) {
            a = fmaxf(a, fmaxf(s[4 * j + 2 * i], s[4 * j + 2 * i + 1]));
            b = fmaxf(b, fmaxf(s[4 * j + 4 + 2 * i], s[4 * j + 4 + 2 * i + 1]));
        }
        a = fmaxf(a, b);
        a = fmaxf(a, __shfl_xor_sync(0xffffffffu, a, 1));
        mx[i] = fmaxf(a, __shfl_xor_sync(0xffffffffu, a, 2));
    }
}
template <int NJ, bool SHIFT>
__device__ __forceinline__ void exp_sum(float (&s)[4 * NJ], const float (&m)[2], float& l0, float& l1) {
#pragma unroll
    for (int j = 0; j < NJ; j++) {
#pragma unroll
        for (int e = 0; e < 4; e++) s[4 * j + e] = ex2(SHIFT ? s[4 * j + e] - m[e >> 1] : s[4 * j + e]);
        l0 += s[4 * j + 0] + s[4 * j + 1]; l1 += s[4 * j + 2] + s[4 * j + 3];
    }
}
__device__ __forceinline__ void recompute_scores(float (&s)[64], const uint32_t (&q)[32], uint32_t kaddr, const Ctx& c) {
    const int r = c.lane & 7, mat = c.lane >> 3;
    const uint32_t a0 = kaddr + (8 * (mat & 1) + r) * 64 + (((mat >> 1) ^ (r >> 1)) << 4);
#pragma unroll
    for (int i = 0; i < 64; i++) s[i] = 0.f;
#pragma unroll
    for (int jp = 0; jp < 8; jp++) {
#pragma unroll
        for (int k = 0; k < 8; k++) {
            asm volatile(
                "{\n.reg .b32 b0, b1, b2, b3;\n"
                "ldmatrix.sync.aligned.m8n8.x4.trans.shared.b16 {b0,b1,b2,b3}, [%12];\n"
                "mma.sync.aligned.m16n8k16.row.col.f32.bf16.bf16.f32 {%0,%1,%2,%3}, {%8,%9,%10,%11}, {b0,b1}, {%0,%1,%2,%3};\n"
                "mma.sync.aligned.m16n8k16.row.col.f32.bf16.bf16.f32 {%4,%5,%6,%7}, {%8,%9,%10,%11}, {b2,b3}, {%4,%5,%6,%7};\n}\n"
                : "+f"(s[8 * jp]), "+f"(s[8 * jp + 1]), "+f"(s[8 * jp + 2]), "+f"(s[8 * jp + 3]),
                  "+f"(s[8 * jp + 4]), "+f"(s[8 * jp + 5]), "+f"(s[8 * jp + 6]), "+f"(s[8 * jp + 7])
                : "r"(q[4 * k]), "r"(q[4 * k + 1]), "r"(q[4 * k + 2]), "r"(q[4 * k + 3]),
                  "r"((a0 ^ ((jp & 1) << 5)) + (jp >> 1) * 8192 + k * 1024) : "memory");
        }
    }
}
__device__ __forceinline__ int mask_lim(const Ctx& c) { return perm32(16 * c.warp + (c.lane >> 2)) - 8 * (c.lane & 3); }
template <int J0>
__device__ __forceinline__ void mask_diag(float (&s)[4 * J0 + 32], const Ctx& c) {
    const int lim = mask_lim(c);
    if (c.warp < 2) {
#pragma unroll
        for (int x = 0; x < 16; x++) {
            if (2 * (x >> 2) + (x & 1) - (x & 2) > lim) s[4 * J0 + x] = -INFINITY;
            s[4 * J0 + 16 + x] = -INFINITY;
        }
    } else {
#pragma unroll
        for (int x = 0; x < 16; x++)
            if (32 + 2 * (x >> 2) + (x & 1) - (x & 2) > lim) s[4 * J0 + 16 + x] = -INFINITY;
    }
}
__device__ __forceinline__ void mask_any(float (&s)[64], int hh, const Ctx& c) {
    const int lim = mask_lim(c) + 64 * hh;
#pragma unroll
    for (int x = 0; x < 64; x++)
        if (32 * (x >> 4) + 2 * ((x >> 2) & 3) + (x & 1) - (x & 2) > lim) s[x] = -INFINITY;
}
__device__ __forceinline__ void issue_pv(float (&o)[64], const uint32_t (&p)[32], uint32_t vaddr, int acc, int mode  ) {
    uint64_t d = mkdesc(vaddr, 16, 512, 2);
    if (mode == 0) {
        wg_fence();
#pragma unroll
        for (int k = 0; k < 8; k++)
            wgmma_rs_n128_ta0_tb0(o, p[4 * k], p[4 * k + 1], p[4 * k + 2], p[4 * k + 3], d + (k >> 1) * 512 + 2 * (k & 1), k ? 1 : acc);
        wg_commit();
    } else if (mode == 1) {
        wg_fence();
#pragma unroll
        for (int k = 0; k < 4; k++) wgmma_rs_n128_ta0_tb0(o, p[4 * k], p[4 * k + 1], p[4 * k + 2], p[4 * k + 3], d + (k >> 1) * 512 + 2 * (k & 1), k != 0);
        wg_commit();
    } else {
        wg_fence();
        wgmma_rs_n128_ta0_tb0(o, p[0], p[1], p[2], p[3], d, acc);
        wg_commit();
    }
}
__device__ __forceinline__ void issue_qk(float (&s)[64], const uint32_t (&q)[32], uint32_t kaddr) {
    uint64_t d = mkdesc(kaddr, 8192, 512, 2);
    wg_fence();
#pragma unroll
    for (int k = 0; k < 8; k++) wgmma_rs_n128_ta0_tb1(s, q[4 * k], q[4 * k + 1], q[4 * k + 2], q[4 * k + 3], d + 64 * k, k != 0);
    wg_commit();
}
__device__ __forceinline__ void issue_qk_half(float (&s32)[32], const uint32_t (&q)[32], uint32_t kaddr) {
    uint64_t d = mkdesc(kaddr, 8192, 512, 2);
    wg_fence();
#pragma unroll
    for (int k = 0; k < 8; k++) wgmma_rs_n64_ta0_tb1(s32, q[4 * k], q[4 * k + 1], q[4 * k + 2], q[4 * k + 3], d + 64 * k, k != 0);
    wg_commit();
}
__device__ __forceinline__ void row_inv(const float (&l)[2], float (&inv)[2]) {
#pragma unroll
    for (int i = 0; i < 2; i++) {
        float sum = l[i];
        sum += __shfl_xor_sync(0xffffffffu, sum, 1);
        sum += __shfl_xor_sync(0xffffffffu, sum, 2);
        inv[i] = rcp_fast(sum);
    }
}

__device__ __forceinline__ const unsigned char* xn_addr(int row, int col) {
    row = perm32(row);
    return g_xn + ((row >> 7) * 10 + (col >> 6)) * 16384 + (row & 127) * 128 + ((((col & 63) >> 3) ^ (row & 7)) << 4);
}
__device__ __forceinline__ void mma16816(float (&d)[4], uint32_t a0, uint32_t a1, uint32_t a2, uint32_t a3, uint32_t b0, uint32_t b1) {
    asm volatile("mma.sync.aligned.m16n8k16.row.col.f32.bf16.bf16.f32 {%0,%1,%2,%3}, {%4,%5,%6,%7}, {%8,%9}, {%0,%1,%2,%3};"
                 : "+f"(d[0]), "+f"(d[1]), "+f"(d[2]), "+f"(d[3]) : "r"(a0), "r"(a1), "r"(a2), "r"(a3), "r"(b0), "r"(b1));
}
__device__ __forceinline__ uint32_t lds32(uint32_t addr) { uint32_t v; asm volatile("ld.shared.u32 %0, [%1];" : "=r"(v) : "r"(addr)); return v; }

__device__ __forceinline__ void ln_rows(const Params& P, int row0, int lane, uint32_t wr_s) {
    const int hl = lane & 15, row = row0 + (lane >> 4);
    uint32_t v[20];
#pragma unroll
    for (int i = 0; i < 5; i++) {
        uint4 u;
        asm("ld.global.nc.L2::cache_hint.v4.b32 {%0,%1,%2,%3}, [%4], %5;" : "=r"(u.x), "=r"(u.y), "=r"(u.z), "=r"(u.w)
            : "l"(P.x + (size_t)row * DM + 128 * i + 8 * hl), "l"(policy(HM & 512)));
        v[4 * i] = u.x; v[4 * i + 1] = u.y; v[4 * i + 2] = u.z; v[4 * i + 3] = u.w;
    }
    float mean = 0.f, m2 = 0.f, acc2 = 0.f;
#pragma unroll
    for (int i = 0; i < 20; i++) { mean += bf_lo(v[i]); acc2 += bf_hi(v[i]); }
    mean = (mean + acc2) * (1.0f / 40);
    acc2 = 0.f;
#pragma unroll
    for (int i = 0; i < 20; i++) {
        float d0 = __uint_as_float(__byte_perm(v[i], 0, 0x1044)) - mean, d1 = __uint_as_float(__byte_perm(v[i], 0, 0x3244)) - mean;
        m2 = fmaf(d0, d0, m2); acc2 = fmaf(d1, d1, acc2);
    }
    m2 += acc2;
    acc2 = 0.f;
#pragma unroll
    for (int o = 1; o < 16; o <<= 1) {
        float mo = __shfl_xor_sync(0xffffffffu, mean, o), qo = __shfl_xor_sync(0xffffffffu, m2, o), d = mo - mean;
        m2 = fmaf(d * d, 20.0f * o, m2 + qo);
        mean = 0.5f * (mean + mo);
    }
    const uint32_t mb2 = pack_bf16(mean, mean);
    const float inv = rcp_fast(bf_round(sqrt_fast(bf_round(bf_round(m2 * (1.0f / DM)) + 1e-5f))));
    float dot = 0.f;
    unsigned char* xp = const_cast<unsigned char*>(xn_addr(row, 8 * hl));
#pragma unroll
    for (int i = 0; i < 5; i++) {
        uint32_t ww[4];
        asm volatile("ld.shared.v4.b32 {%0,%1,%2,%3}, [%4];" : "=r"(ww[0]), "=r"(ww[1]), "=r"(ww[2]), "=r"(ww[3]) : "r"(wr_s + 256 * i + 16 * hl) : "memory");
#pragma unroll
        for (int e = 0; e < 4; e++) {
            uint32_t d;
            asm("sub.rn.bf16x2 %0, %1, %2;" : "=r"(d) : "r"(v[4 * i + e]), "r"(mb2));
            d = pack_bf16(bf_lo(d) * inv, bf_hi(d) * inv);
            v[4 * i + e] = d;
            dot = fmaf(bf_lo(d), bf_lo(ww[e]), dot);
            acc2 = fmaf(bf_hi(d), bf_hi(ww[e]), acc2);
        }
        stg128(xp + i * 32768, v[4 * i], v[4 * i + 1], v[4 * i + 2], v[4 * i + 3]);
    }
    dot += acc2;
#pragma unroll
    for (int o = 8; o > 0; o >>= 1) dot += __shfl_xor_sync(0xffffffffu, dot, o);
    if (hl == 0) { g_router[row] = bf_round(dot); g_stats[row] = make_uint2(mb2, __float_as_uint(inv)); }
}

__device__ __forceinline__ void aux_cta(const Params& P, const CUtensorMap* tmG, const CUtensorMap* tmU, const CUtensorMap* tmD, unsigned char* sm, int a) {
    constexpr int STG = 57344, XS = 3 * STG, HS = XS + 8 * 1296, KEY = HS + 8 * 912, MI = KEY + 8192;
    const int tid = threadIdx.x, warp = __shfl_sync(0xffffffffu, tid >> 5, 0), lane = tid & 31;
    const uint32_t sb = smem_u32(sm);
    const uint32_t full = sb + MI, empty = sb + MI + 32;
    int* s_sel = reinterpret_cast<int*>(sm + MI + 64);
    float* s_r = reinterpret_cast<float*>(sm + MI + 96);
    volatile unsigned* s_misc = reinterpret_cast<volatile unsigned*>(sm + MI + 128);
    uint32_t* s_key = reinterpret_cast<uint32_t*>(sm + KEY);
    PROF_DECL(128 + a)
    PROF_GT(0);
    if (tid == 0) {
        for (int i = 0; i < 3; i++) { mbar_init(full + 8 * i, 1); mbar_init(empty + 8 * i, 10); }
        asm volatile("fence.mbarrier_init.release.cluster;" ::: "memory");
    }
    __syncthreads();
    if (warp == 11) {
        if (elect_one()) {
            int st = 0; uint32_t ph = 0;
#pragma unroll 1
            for (int s = 0; s < 34; s++) {
                mbar_wait(empty + 8 * st, ph ^ 1);
                const uint32_t dst = sb + st * STG, fb = full + 8 * st;
                if (s < 20) {
                    mbar_expect_tx(fb, 57344);
                    tma3d(dst, tmG, 0, 32 * s, 7 * a, fb);
                    tma3d(dst + 28672, tmU, 0, 32 * s, 7 * a, fb);
                } else {
                    mbar_expect_tx(fb, 40960);
                    tma3d(dst, tmD, 0, 448 * a + 32 * (s - 20), 0, fb);
                }
                if (s >= 3) {
#pragma unroll 1
                    for (int f = (s == 3 ? 4 : s + 6); f <= s + 6 && f < 34; f++) {
                        if (f < 20) { tma3d_prefetch(tmG, 0, 32 * f, 7 * a); tma3d_prefetch(tmU, 0, 32 * f, 7 * a); }
                        else tma3d_prefetch(tmD, 0, 448 * a + 32 * (f - 20), 0);
                    }
                }
                if (++st == 3) { st = 0; ph ^= 1; }
            }
        }
        return;
    }
    if (tid < 80) *reinterpret_cast<uint4*>(sm + KEY + 1024 + tid * 16) = __ldg(reinterpret_cast<const uint4*>(P.wr) + tid);
    __nanosleep(AUXDELAY);
#pragma unroll 1
    for (int i = tid; i < 64 * 40; i += 352) asm volatile("prefetch.global.L2 [%0];" ::"l"(P.x + (size_t)((4 + a) * 256 + 192) * DM + i * 16));
    bar_sync(2, 352);
#pragma unroll 1
    for (int i = warp; i < 32; i += 11) ln_rows(P, (4 + a) * 256 + 192 + 2 * i, lane, sb + KEY + 1024);
    bar_sync(2, 352);
    if (tid == 320) flag_signal(flag_ptr(FL_LN + 4 + a));
    PROF_GT(49);
    if (warp == 10) return;
    if (tid < 8) {
        unsigned e = *reinterpret_cast<volatile unsigned*>(&g_epoch);
        if (tid == 0) s_misc[0] = e;
        flag_wait(flag_ptr(FL_LN + tid), (e + 1) * (32u + (tid >> 2)));
    }
    bar_sync(1, 320);
    PROF_GT(50);
    const unsigned ep = s_misc[0];
    auto top8 = [&](uint32_t (&key)[8]) {
        uint32_t mine = 0;
#pragma unroll 1
        for (int r = 0; r < TOPC; r++) {
            uint32_t best = 0;
#pragma unroll
            for (int i = 0; i < 8; i++) best = max(best, key[i]);
            best = __reduce_max_sync(0xffffffffu, best);
#pragma unroll
            for (int i = 0; i < 8; i++) if (key[i] == best) key[i] = 0;
            if (lane == r) mine = best;
        }
        return mine;
    };
#pragma unroll 1
    for (int pass = 0; pass < 2; pass++) {
        if (warp < (pass ? 1 : 8)) {
            uint32_t key[8];
#pragma unroll
            for (int i = 0; i < 8; i++) {
                if (pass == 0) {
                    int idx = warp * 256 + i * 32 + lane;
                    uint32_t b = __float_as_uint(__ldcg(g_router + idx)) >> 16;
                    b = (b & 0x8000u) ? (~b & 0xffffu) : (b | 0x8000u);
                    key[i] = (b << 16) | (uint32_t)(0xffff - idx);
                } else key[i] = i < 2 ? s_key[i * 32 + lane] : 0u;
            }
            uint32_t best = top8(key);
            if (lane < TOPC) {
                if (pass == 0) s_key[warp * 8 + lane] = best;
                else {
                    uint32_t b = best >> 16;
                    b = (b & 0x8000u) ? (b & 0x7fffu) : (~b & 0xffffu);
                    s_sel[lane] = 0xffff - (int)(best & 0xffffu);
                    s_r[lane] = __uint_as_float(b << 16);
                }
            }
        }
        bar_sync(1, 320);
    }
#pragma unroll
    for (int it = 0; it < 2; it++) {
        int i = tid + it * 320, tk = i / 80, ch = i % 80;
        *reinterpret_cast<uint4*>(sm + XS + tk * 1296 + ch * 16) = __ldcg(reinterpret_cast<const uint4*>(xn_addr(s_sel[tk], ch * 8)));
    }
    bar_sync(1, 320);
    PROF_GT(51);
    const int g = lane >> 2, t = lane & 3;
    const uint32_t woff = warp * 4096 + (8 * (lane >> 4) + (lane & 7)) * 128 + ((((lane >> 3) & 1) ^ (lane & 7)) << 4);
    int st = 0; uint32_t ph = 0;
    float ga[4][4], ua[4][4];
#pragma unroll
    for (int i = 0; i < 4; i++)
#pragma unroll
        for (int e = 0; e < 4; e++) { ga[i][e] = 0.f; ua[i][e] = 0.f; }
#pragma unroll 1
    for (int s = 0; s < 34; s++) {
        if (s == 20) {
            if (warp < 7) {
#pragma unroll
                for (int i = 0; i < 4; i++)
#pragma unroll
                    for (int e = 0; e < 4; e++) {
                        float gv = bf_round(ga[i][e]), uv = bf_round(ua[i][e]);
                        float sg = bf_round(__fdividef(gv, 1.0f + __expf(fminf(-gv, 80.f))));
                        int f = warp * 64 + i * 16 + g + 8 * (e >> 1), tk = 2 * t + (e & 1);
                        *reinterpret_cast<__nv_bfloat16*>(sm + HS + tk * 912 + f * 2) = __float2bfloat16_rn(sg * uv);
                        ga[i][e] = 0.f;
                    }
            }
            bar_sync(1, 320);
            PROF_GT(52);
        }
        mbar_wait(full + 8 * st, ph);
        if (s >= 20 || warp < 7) {
#pragma unroll
            for (int kk = 0; kk < 2; kk++) {
                uint32_t xb = sb + (s < 20 ? XS + g * 1296 + s * 64 : HS + g * 912 + (s - 20) * 64) + 32 * kk + 4 * t;
                uint32_t b0 = lds32(xb), b1 = lds32(xb + 16);
                uint32_t wa = sb + st * STG + woff + kk * 2048;
#pragma unroll
                for (int i = 0; i < 4; i++) {
                    uint32_t a0, a1, a2, a3;
                    ldsm4t(a0, a1, a2, a3, wa ^ (i << 5));
                    mma16816(ga[i], a0, a1, a2, a3, b0, b1);
                    if (s < 20) {
                        ldsm4t(a0, a1, a2, a3, (wa ^ (i << 5)) + 28672);
                        mma16816(ua[i], a0, a1, a2, a3, b0, b1);
                    }
                }
            }
        }
        asm volatile("fence.proxy.async.shared::cta;" ::: "memory");
        __syncwarp();
        if (lane == 0) mbar_arrive(empty + 8 * st);
        if (++st == 3) { st = 0; ph ^= 1; }
    }
#pragma unroll
    for (int i = 0; i < 4; i++)
#pragma unroll
        for (int e = 0; e < 4; e += 2)
            *reinterpret_cast<float2*>(g_moe_part + (a * DM + warp * 64 + i * 16 + g + 4 * e) * 8 + 2 * t) = make_float2(ga[i][e], ga[i][e + 1]);
    bar_sync(1, 320);
    if (tid == 0) {
        __threadfence();
        unsigned old = atomicAdd(flag_ptr(FL_MOE_CNT), 1u);
        s_misc[1] = (old == ep * 4u + 3u);
        __threadfence();
    }
    bar_sync(1, 320);
    PROF_GT(53);
    if (s_misc[1]) {
        const float4* pp = reinterpret_cast<const float4*>(g_moe_part);
#pragma unroll 2
        for (int i = tid; i < DM * 2; i += 320) {
            float4 v0 = __ldcg(pp + i), v1 = __ldcg(pp + DM * 2 + i), v2 = __ldcg(pp + DM * 4 + i), v3 = __ldcg(pp + DM * 6 + i);
            float y[4] = {v0.x + v1.x + v2.x + v3.x, v0.y + v1.y + v2.y + v3.y, v0.z + v1.z + v2.z + v3.z, v0.w + v1.w + v2.w + v3.w};
#pragma unroll
            for (int e = 0; e < 4; e++) {
                int col = i >> 1, tk = (i & 1) * 4 + e;
                float sg = bf_round(__fdividef(1.0f, 1.0f + __expf(fminf(-s_r[tk], 80.f))));
                float upd = bf_round(bf_round(y[e]) * sg);
                float xn = __bfloat162float(*reinterpret_cast<const __nv_bfloat16*>(sm + XS + tk * 1296 + col * 2));
                g_brow[tk * DM + col] = __float2bfloat16_rn(xn + upd);
            }
        }
        if (tid < TOPC) g_sel[tid] = s_sel[tid];
        bar_sync(1, 320);
        if (tid == 0) {
            flag_signal(flag_ptr(FL_MOE_DONE));
            *reinterpret_cast<volatile unsigned*>(&g_epoch) = ep + 1;
        }
        PROF_GT(54);
    }
}

__global__ void __cluster_dims__(2, 1, 1) __launch_bounds__(384, 1)
fused_kernel(const __grid_constant__ CUtensorMap tmC, const __grid_constant__ CUtensorMap tmWk, const __grid_constant__ CUtensorMap tmWv,
             const __grid_constant__ CUtensorMap tmWq, const __grid_constant__ CUtensorMap tmWo,
             const __grid_constant__ CUtensorMap tmG, const __grid_constant__ CUtensorMap tmU, const __grid_constant__ CUtensorMap tmD, const Params P) {
    extern __shared__ __align__(1024) unsigned char smem_raw[];
    const uint32_t ring = smem_u32(smem_raw);
    const uint32_t misc = ring + RING_BYTES;
    const int tid = threadIdx.x;
    const int rank = blockIdx.x & 1;
    uint32_t smid, nsm;
    asm("mov.u32 %0, %%smid;" : "=r"(smid));
    asm("mov.u32 %0, %%nsmid;" : "=r"(nsm));
    if (nsm != 132) smid = blockIdx.x;
    auto role_of = [](int tpc) {
        return tpc < 32 ? (tpc & 7) * 8 + (tpc >> 3) : tpc < 60 ? (1 + (tpc - 32) % 7) * 8 + 4 + (tpc - 32) / 7 : tpc < 64 ? tpc - 56 : tpc;
    };
    int mc = role_of(smid >> 1);
    PROF_DECL(mc * 2 + rank)
    PROF_GT(0); PROF_EV(1);

    auto prefetch_w = [&](int ch) {
        const int i = tid - 128;
        asm volatile("prefetch.global.L2 [%0];" ::"l"((rank ? P.wv : P.wk) + (size_t)(ch * 128 + (mc & 3) * 32 + (i >> 3)) * 4096 + (mc >> 2) * 256 + (i & 7) * 16));
    };
    if (tid >= 128 && mc < 64) {
        if (tid < 256) asm volatile("prefetch.global.L2 [%0];" ::"l"(P.c + (size_t)((12 + (mc & 3)) * 128 + ((mc >> 2) * 2 + rank) * 4) * DC + (tid - 128) * 16));
        prefetch_w(0);
    }
    auto load_w0 = [&]() {
        const CUtensorMap* tw = rank ? &tmWv : &tmWk;
        mbar_expect_tx(misc + BAR_FULL + 8 * slot_of(0), SLOT_BYTES);
        tma2d(ring + slot_of(0) * SLOT_BYTES, tw, (mc >> 2) * 256, 0, misc + BAR_FULL + 8 * slot_of(0), policy(HM & 1));
        tma2d(ring + slot_of(0) * SLOT_BYTES + 16384, tw, (mc >> 2) * 256 + 64, 0, misc + BAR_FULL + 8 * slot_of(0), policy(HM & 1));
    };
    if (tid == 0) {
#pragma unroll
        for (int i = 0; i < NSLOT; i++) mbar_init(misc + BAR_FULL + 8 * i, 1);
#pragma unroll
        for (int i = 0; i < E0; i++) mbar_arrive(misc + BAR_FULL + 8 * i);
        asm volatile("fence.mbarrier_init.release.cluster;" ::: "memory");
        if (mc < 64) load_w0();
    }
    if (tid == 160) {
        asm volatile("st.shared.u32 [%0], %1;" ::"r"(misc + MISC_SMID), "r"(smid) : "memory");
        asm volatile("fence.release.sync_restrict::shared::cta.cluster;" ::: "memory");
    }
    if (tid == 32) {
        asm volatile("prefetch.tensormap [%0];" ::"l"(&tmC) : "memory");
#pragma unroll
        for (int i = 0; i < NSLOT; i++) mbar_init(misc + BAR_EMPTY + 8 * i, 16);
#pragma unroll
        for (int i = 0; i < E0; i++) mbar_arrive_cluster(misc + BAR_EMPTY + 8 * i, 16);
        asm volatile("fence.mbarrier_init.release.cluster;" ::: "memory");
    }
    if (tid == 64) {
#pragma unroll
        for (int i = 0; i < NST3; i++) { mbar_init(misc + BAR_FULL3 + 8 * i, 1); mbar_init(misc + BAR_EMPTY3 + 8 * i, 16); }
#pragma unroll
        for (int i = 0; i < 4; i++) mbar_init(misc + BAR_LN + 8 * i, 2);
        mbar_init(misc + BAR_PROG, 1); mbar_init(misc + BAR_PROG + 8, 1); mbar_init(misc + BAR_PROG + 16, 1);
        asm volatile("fence.mbarrier_init.release.cluster;" ::: "memory");
    }
    if (tid == 96) {
#pragma unroll
        for (int i = 0; i < 34; i++) mbar_init(misc + BAR_DEP + 8 * i, 1);
    }
    if (tid == 128) {
#pragma unroll
        for (int i = 0; i < 32; i++) mbar_init(misc + BAR_EV + 8 * i, 4);
    }
    __syncthreads();
    asm volatile("barrier.cluster.arrive.relaxed.aligned;\nbarrier.cluster.wait.aligned;" ::: "memory");
    {
        uint32_t peer;
        asm volatile("ld.shared::cluster.u32 %0, [%1];" : "=r"(peer) : "r"(mapa(misc + MISC_SMID, rank ^ 1)) : "memory");
        if ((__shfl_sync(0xffffffffu, peer, 0) ^ smid) != 1) {
            if (tid == 0) {
                const unsigned ep1 = *reinterpret_cast<volatile unsigned*>(&g_epoch) + 1;
                if ((smid & 1) == 0) atomicExch(g_roleq + 2 + (atomicAdd(g_roleq, 1u) & 127), (ep1 << 8) | (smid >> 1));
                if (rank == 0) {
                    unsigned* slot = g_roleq + 2 + (atomicAdd(g_roleq + 1, 1u) & 127);
                    unsigned v = 0;
                    for (int spin = 0; spin < 4000000 && ((v = atomicAdd(slot, 0u)) >> 8) != (ep1 & 0xffffffu); spin++) {}
                    asm volatile("st.shared::cluster.u32 [%0], %1;" ::"r"(mapa(misc + MISC_SMID + 4, 0)), "r"(v & 255) : "memory");
                    asm volatile("st.shared::cluster.u32 [%0], %1;" ::"r"(mapa(misc + MISC_SMID + 4, 1)), "r"(v & 255) : "memory");
                }
                if (mc < 64) {
                    mbar_wait(misc + BAR_FULL + 8 * slot_of(0), 0);
                    asm volatile("mbarrier.inval.shared::cta.b64 [%0];" ::"r"(misc + BAR_FULL + 8 * slot_of(0)) : "memory");
                    mbar_init(misc + BAR_FULL + 8 * slot_of(0), 1);
                    asm volatile("fence.mbarrier_init.release.cluster;" ::: "memory");
                }
            }
            __syncwarp();
            asm volatile("barrier.cluster.arrive.aligned;\nbarrier.cluster.wait.aligned;" ::: "memory");
            mc = role_of(__shfl_sync(0xffffffffu, lds32(misc + MISC_SMID + 4), 0));
            if (tid == 0 && mc < 64) load_w0();
            __syncwarp();
        }
    }
    const int cta = mc * 2 + rank;
    if (mc >= 64) { aux_cta(P, &tmG, &tmU, &tmD, smem_raw, cta - 128); return; }
    const int team = mc >> 2, k = mc & 3;
    const int u3 = (mc >> 4) * 2 + (team & 1), s3 = k, kap = (mc >> 3) & 1;
    const int partner = cta ^ 16;
    if (tid >= 128) prefetch_w(1);
    if (tid == 256) {
        const CUtensorMap* tw = rank ? &tmWv : &tmWk;
#pragma unroll
        for (int e = 1; e < NSLOT; e++) {
            const uint32_t fb = misc + BAR_FULL + 8 * slot_of(e), dst = ring + slot_of(e) * SLOT_BYTES;
            mbar_expect_tx(fb, SLOT_BYTES);
            if (e & 1) tma2d_mc(dst + rank * 16384, &tmC, (e >> 1) * 128 + rank * 64, (12 + k) * 128, fb, policy(false));
            else { tma2d(dst, tw, team * 256, e * 64, fb, policy(false)); tma2d(dst + 16384, tw, team * 256 + 64, e * 64, fb, policy(false)); }
        }
    }
    PROF_EV(5);
    const int wg = __shfl_sync(0xffffffffu, tid >> 7, 0);

    if (wg == 0) {
        asm volatile("setmaxnreg.dec.sync.aligned.u32 40;");
        const int warp = __shfl_sync(0xffffffffu, tid >> 5, 0), lane = tid & 31;
        if (warp == 0) {
            const bool lead = elect_one();
            Cur c = cur_at(NSLOT);
            uint32_t dst, fb;
            auto acquire = [&]() {
                mbar_wait(misc + BAR_EMPTY + 8 * c.slot, c.ph ^ 1);
                fb = misc + BAR_FULL + 8 * c.slot; dst = ring + c.slot * SLOT_BYTES;
                if (lead) mbar_expect_tx(fb, SLOT_BYTES);
                c.adv();
            };
            auto load_w = [&](const CUtensorMap* tm, int col, int row, bool stream) {
                acquire();
                if (lead) { tma2d(dst, tm, col, row, fb, policy(stream)); tma2d(dst + 16384, tm, col + 64, row, fb, policy(stream)); }
            };
            auto load_half = [&](const unsigned char* src, bool stream) {
                acquire();
                if (lead) bulk_load_mc(dst + rank * 16384, src, 16384, fb, policy(stream));
            };
            auto dep_wait = [&](int d) { mbar_wait(misc + BAR_DEP + 8 * d, 0); fence_async_global(); };
            auto op_prefetch = [&](int i) {
                const int head = op_head(i, kap);
                l2_prefetch(reinterpret_cast<const unsigned char*>(P.wo) + head * 163840 + (u3 * 8 + s3 * 2 + rank) * 2560, 2560);
                if (i < 8) l2_prefetch(g_ctx + (size_t)(head * 32 + 4 * u3 + 2 * rank) * 16384 + s3 * 8192, 8192);
            };
            __nanosleep(CDELAY);
            if (lead) l2_prefetch(reinterpret_cast<const unsigned char*>(P.c) + (size_t)cta * 12288, 12288);
            const CUtensorMap* tw = rank ? &tmWv : &tmWk;
            const unsigned char* Kh = g_K + (size_t)team * 32 * 16384 + rank * 16384;
            const unsigned char* Vh = g_V + (size_t)team * 32 * 16384 + rank * 16384;
#pragma unroll 1
            for (int v = 0; v < 2; v++) {
                const int h = 2 * team + v;
#pragma unroll 1
                for (int i = v ? 0 : 3; i < 16; i++) {
                    if (i < 4 && v) load_w(tw, h * 128, i * 128, HM & 1);
                    if (v && i == 3 && lead) mbar_arrive(misc + BAR_PROG + 8);
                    if (v && (i & 7) == 3) dep_wait(D_WAR + (i >> 3));
                    acquire();
                    if (lead) tma2d_mc(dst + rank * 16384, &tmC, (i & 3) * 128 + rank * 64, (12 - (i & 12) + k) * 128, fb, policy(HM & 2));
                    if (i == 8 && lead) {
                        tma2d_prefetch(&tmWq, h * 128 + rank * 64, k * 64); tma2d_prefetch(&tmWq, h * 128 + rank * 64, k * 64 + 256);
                        if (k < 2) tma2d_prefetch(&tmWq, h * 128 + rank * 64, k * 64 + 512);
                        if (v) l2_prefetch(g_xn + 8 * 163840 + cta * 10240, 10240);
                    }
                }
                int togo = v ? PF_START : 11;
#pragma unroll 1
                for (int r = 0; r < 2; r++) {
                    const int p = r ? k : 7 - k, n = 2 * p + 1;
                    if (v == 0) dep_wait(D_LN + r);
                    const int g0 = r ? rank ^ SWAPT : 3 - rank, g1 = 3 - g0;
                    const unsigned char* x0 = g_xn + (2 * p + (g0 >> 1)) * 163840 + (g0 & 1) * 8192;
                    const unsigned char* x1 = g_xn + (2 * p + (g1 >> 1)) * 163840 + (g1 & 1) * 8192;
#pragma unroll 1
                    for (int kc = 0; kc < 10; kc++) {
                        acquire();
                        if (lead) {
                            tma2d_mc(dst + 16384 + rank * 8192, &tmWq, h * 128 + rank * 64, kc * 64, fb, policy(false));
                            bulk_load(dst, x0 + kc * 16384, 8192, fb, policy(false));
                            bulk_load(dst + 8192, x1 + kc * 16384, 8192, fb, policy(false));
                        }
                    }
                    if (r == 0) dep_wait(D_KV + 3 * v);
                    load_half(Kh + n * 32768, HM & 16);
#pragma unroll 1
                    for (int j = n - 1; j >= 0; j--) {
                        if (r == 0 && (j == 7 || j == 3)) dep_wait(D_KV + 3 * v + 2 - (j >> 2));
                        load_half(Kh + j * 32768, HM & 16); load_half(Vh + (j + 1) * 32768, HM & 16);
                        if (v == 0 && r == 0 && j == 3 && lead) mbar_arrive(misc + BAR_PROG);
                        --togo;
                        if (v == 0 && togo == 0 && lead) {
                            tma2d_prefetch(tw, h * 128 + 128, k * 128); tma2d_prefetch(tw, h * 128 + 192, k * 128);
                            l2_prefetch(reinterpret_cast<const unsigned char*>(P.c) + (size_t)cta * 16384, 16384);
                        }
                        if (v && togo <= 0 && togo > -OP_PF && lead) op_prefetch(-togo);
                    }
                    load_half(Vh, HM & 16);
                }
            }
            mbar_wait(misc + BAR_EMPTY + 8 * c.slot, c.ph ^ 1); c.adv();
            int st = 0; uint32_t ph3 = 0;
#pragma unroll 1
            for (int i = 0; i < 32; i++) {
                const int head = op_head(i >> 1, kap);
                if ((i & 1) == 0) dep_wait(D_CTX + (i >> 1));
                if (i < NST3) { mbar_wait(misc + BAR_EMPTY + 8 * c.slot, c.ph ^ 1); c.adv(); }
                else mbar_wait(misc + BAR_EMPTY3 + 8 * st, ph3 ^ 1);
                fb = misc + BAR_FULL3 + 8 * st; dst = ring + st * ST3_BYTES;
                if (i == LATE_AT && lead) mbar_arrive(misc + BAR_PROG + 16);
                if (lead) {
                    mbar_expect_tx(fb, ST3_BYTES);
                    const unsigned char* src = g_ctx + (size_t)(head * 32 + 4 * u3 + 2 * rank) * 16384 + (i & 1) * 8192;
                    bulk_load(dst, src, 8192, fb, policy(HM & 32));
                    bulk_load(dst + 8192, src + 16384, 8192, fb, policy(HM & 32));
                    tma3d_mc(dst + 16384 + rank * 10240, &tmWo, 0, head * 128 + (i & 1) * 64 + rank * 32, 5 * s3, fb, policy(HM & 32));
                    if ((i & 1) && (i >> 1) + OP_PF < 16) op_prefetch((i >> 1) + OP_PF);
                }
                if (++st == NST3) { st = 0; ph3 ^= 1; }
            }
        } else {
        if (lane < 27 && (warp - 1) * 27 + lane < 80) {
            const int ch = (warp - 1) * 27 + lane;
            uint4 u = __ldg(reinterpret_cast<const uint4*>(P.wr) + ch);
            asm volatile("st.shared.v4.b32 [%0], {%1,%2,%3,%4};" ::"r"(misc + MISC_WR + 16 * ch), "r"(u.x), "r"(u.y), "r"(u.z), "r"(u.w) : "memory");
        }
        bar_sync(3, 96);
#pragma unroll 1
        for (int t = 0; t < (warp == 3 ? 1 : 3); t++) {
            const int row2 = (cta >> 5) * 256 + (cta & 31) * 8 + (warp - 1) * 4;
            if (t < 2 && warp < 3) {
#pragma unroll
                for (int i = 0; i < 3; i++)
                    if (i * 32 + lane < 80) asm volatile("prefetch.global.L2 [%0];" ::"l"(P.x + (size_t)(row2 + 2 * t) * DM + (i * 32 + lane) * 16));
            }
            ln_rows(P, t ? row2 + 2 * t - 2 : (4 + (cta >> 5)) * 256 + (cta & 31) * 6 + (warp - 1) * 2, lane, misc + MISC_WR);
            __syncwarp();
            if (lane == 0 && warp < 3 && t != 1) mbar_arrive(misc + BAR_LN + 4 * t);
        }
        if (warp == 3) {
            const unsigned ep1 = *reinterpret_cast<volatile unsigned*>(&g_epoch) + 1;
            if (lane == 0) {
                asm volatile("st.shared.u32 [%0], %1;" ::"r"(misc + MISC_EPOCH), "r"(ep1) : "memory");
                mbar_wait(misc + BAR_LN, 0);
                flag_signal(flag_ptr(FL_LN + 4 + (cta >> 5)));
                flag_wait(flag_ptr(FL_LN + 7 - k), ep1 * 33u);
                mbar_arrive(misc + BAR_DEP + 8 * D_LN);
#pragma unroll 1
                for (int v = 0; v < 2; v++) {
#pragma unroll 1
                    for (int i = 3 * v; i < 3 * v + 3; i++) {
                        mbar_wait(misc + BAR_EV + 8 * (16 + EV_KV + i), 0);
                        if (v == 0) {
                            mbar_wait(misc + BAR_EV + 8 * (EV_KV + i), 0);
                            asm volatile("red.release.gpu.global.add.u32 [%0], 2;" ::"l"(flag_ptr(FL_KV + team * 8 + i)) : "memory");
                        }
                        flag_wait(flag_ptr(FL_KV + team * 8 + i), ep1 * 16u);
                        mbar_arrive(misc + BAR_DEP + 8 * (D_KV + i));
                    }
                    if (v) break;
                    mbar_wait(misc + BAR_LN + 8, 0);
                    flag_signal(flag_ptr(FL_LN + (cta >> 5)));
                    flag_wait(flag_ptr(FL_LN + k), ep1 * 32u);
                    mbar_arrive(misc + BAR_DEP + 8 * (D_LN + 1));
#pragma unroll 1
                    for (int i = 0; i < 2; i++) {
                        mbar_wait(misc + BAR_PROG + 8 * i, 0);
                        flag_signal(flag_ptr(FL_WAR + 2 * team + i));
                        flag_wait(flag_ptr(FL_WAR + 2 * team + i), ep1 * 8u);
                        mbar_arrive(misc + BAR_DEP + 8 * (D_WAR + i));
                    }
                }
                flag_wait(flag_ptr(FL_MOE_DONE), ep1);
                int4 s0 = __ldcg(reinterpret_cast<const int4*>(g_sel)), s1 = __ldcg(reinterpret_cast<const int4*>(g_sel) + 1);
                asm volatile("st.shared.v4.u32 [%0], {%1,%2,%3,%4};" ::"r"(misc + MISC_SEL), "r"(s0.x), "r"(s0.y), "r"(s0.z), "r"(s0.w) : "memory");
                asm volatile("st.shared.v4.u32 [%0], {%1,%2,%3,%4};" ::"r"(misc + MISC_SEL + 16), "r"(s1.x), "r"(s1.y), "r"(s1.z), "r"(s1.w) : "memory");
                mbar_arrive(misc + BAR_SEL);
            }
            __syncwarp();
            const unsigned* cf = flag_ptr(FL_CTX + op_head(lane & 15, kap) * 8 + u3);
#pragma unroll 1
            for (int half = 0; half < 2; half++) {
                if (half) mbar_wait(misc + BAR_EV + 8 * (EV_CTX + 3), 0);
                bool done = (lane >> 3) != half;
                for (int spin = 0; spin < 4000000; spin++) {
                    if (!done) {
                        unsigned v;
                        asm volatile("ld.acquire.gpu.global.u32 %0, [%1];" : "=r"(v) : "l"(cf) : "memory");
                        if ((int)(v - ep1 * 4u) >= 0) { mbar_arrive(misc + BAR_DEP + 8 * (D_CTX + lane)); done = true; }
                    }
                    if (__all_sync(0xffffffffu, done)) break;
                    __nanosleep(64);
                }
            }
        } else {
            const int w = warp - 1;
            if (lane == 0) {
                const uint32_t eb = misc + BAR_EV + w * 128;
#pragma unroll 1
                for (int i = 0; i < 7; i++) {
                    const bool kv = i >= 2 && i < 5;
                    const int ci = i < 2 ? i : i - 3;
                    mbar_wait(eb + 8 * (kv ? EV_KV + i + 1 : EV_CTX + ci), 0);
                    if (i == 1) {
                        asm volatile("cp.async.bulk.global.shared::cta.bulk_group [%0], [%1], 16384;"
                                     ::"l"(g_ctx + (size_t)(2 * team * 32 + 4 * k + (w ? 3 - (rank ^ SWAPT) : rank ^ SWAPT)) * 16384),
                                       "r"(ring + slot_of(78) * SLOT_BYTES + w * 16384) : "memory");
                        asm volatile("cp.async.bulk.commit_group;" ::: "memory");
                        asm volatile("cp.async.bulk.wait_group.read 0;" ::: "memory");
                        mbar_arrive_cluster(mapa(misc + BAR_EMPTY + 8 * slot_of(78), 0), 4);
                        mbar_arrive_cluster(mapa(misc + BAR_EMPTY + 8 * slot_of(78), 1), 4);
                        asm volatile("cp.async.bulk.wait_group 0;" ::: "memory");
                        fence_async_global();
                    }
                    flag_signal(flag_ptr(kv ? FL_KV + team * 8 + i + 1 : FL_CTX + (2 * team + (ci >> 1)) * 8 + ((ci & 1) ? k : 7 - k)));
                }
            }
            __syncwarp();
            mbar_wait(misc + BAR_PROG + 16, 0);
            const int row = (2 * u3 + rank) * 128 + 64 * w + perm32(16 * (lane >> 3) + 8 * kap + (lane & 7));
#pragma unroll
            for (int i = 0; i < 10; i++) asm volatile("prefetch.global.L2 [%0];" ::"l"(P.x + (size_t)row * DM + 160 * s3 + 16 * i));
            asm volatile("prefetch.global.L2 [%0];" ::"l"(g_stats + row));
        }
        }
    } else {
        asm volatile("setmaxnreg.inc.sync.aligned.u32 232;");
        Ctx c;
        c.ring = ring; c.misc = misc; c.w = wg - 1; c.warp = __shfl_sync(0xffffffffu, (tid >> 5) & 3, 0); c.lane = tid & 31;
        c.rel = mapa(misc, tid & 1);
        const int w = c.w;
        if (w == 1) bar_arrive(1, 256);
        prefetch_w(2); prefetch_w(3);
        Cur cur = cur_at(0);
        float o[64], inv[2];
        unsigned char* out[2];
        uint32_t wf[128];
        Cur cw = cur;
        auto load_wchunk = [&](auto CH) {
            constexpr int ch = decltype(CH)::value;
            mbar_wait_hot(misc + BAR_FULL + 8 * cw.slot, cw.ph);
            const uint32_t z = load_afrag<8, 32 * ch>(wf, ring + cw.slot * SLOT_BYTES + w * 16384, c);
            release(c, BAR_EMPTY + 8 * cw.slot + z, 1);
            cw.adv(); cw.adv();
        };
#pragma unroll
        for (int i = 32; i < 64; i++) wf[i] = 0u;
        load_wchunk(IC<0>{});
#pragma unroll 1
        for (int v = 0; v < 2; v++) {
        {
            float (&acc)[64] = o;
#pragma unroll
            for (int i = 64; i < 128; i++) wf[i] = 0u;
            cur.adv();
            inv[0] = inv[1] = rank ? 1.0f : SM_SCALE;
            PROF_EV(2); PROF_GT(60);
#pragma unroll 1
            for (int t = 0; t < 4; t++) {
                uint32_t last = 0;
                token_wait(w);
                PROF_EV(10);
                undef_regs(acc);
                auto chunk = [&](auto CH) {
                    constexpr int ch = decltype(CH)::value;
                    mbar_wait_hot(misc + BAR_FULL + 8 * cur.slot, cur.ph);
                    if (t == 0) { PROF_EV(12 + ch); }
                    uint64_t d = mkdesc(ring + cur.slot * SLOT_BYTES, 16, 1024, 1);
                    wg_fence();
#pragma unroll
                    for (int ks = 0; ks < 8; ks++)
                        wgmma_rs_n128_ta0_tb0(acc, wf[32 * ch + 4 * ks], wf[32 * ch + 4 * ks + 1], wf[32 * ch + 4 * ks + 2], wf[32 * ch + 4 * ks + 3],
                                              d + (ks >> 2) * 1024 + (ks & 3) * 2, (ch | ks) != 0);
                    wg_commit();
                    if (ch == 3 || (ch < 2 && t == 0)) token_pass(w);
                    if constexpr (ch == 0) { if (t == 0) { if (v) load_wchunk(IC<2>{}); else load_wchunk(IC<1>{}); } }
                    if constexpr (ch == 1) { if (t == 0 && !v) load_wchunk(IC<2>{}); }
                    if constexpr (ch == 2) { if (t == 0 && !(w | v)) load_wchunk(IC<3>{}); }
                    if (ch > 0) { wg_wait<1>(); release(c, BAR_EMPTY + 8 * last, 1); }
                    last = cur.slot;
                    cur.adv();
                    if (ch < 3 && t == 0) cur.adv();
                    if constexpr (ch == 1) { if (t == 0 && (w | v)) load_wchunk(IC<3>{}); }
                    if (ch < 2 && t == 0) token_wait(w);
                };
                chunk(IC<0>{}); chunk(IC<1>{}); chunk(IC<2>{}); chunk(IC<3>{});
                wg_wait<0>();
                release(c, BAR_EMPTY + 8 * last, 1);
                PROF_EV(11);
                fence_regs(acc);
                tile_out(out, (rank ? g_V : g_K) + (size_t)(team * 32 + 24 + 2 * k - 8 * t) * 16384, 64 * w, rank, c);
                if (DEFER && t == 3 && w) break;
#pragma unroll
                for (int i = 0; i < 4; i++) store_pair(acc, i, out, 8192, inv);
                if (t) signal_event(c, EV_KV + 3 * v + t - 1);
            }
            PROF_EV(61); PROF_GT(62);
        }
        PROF_EV(63); PROF_GT(64);
        {
            uint32_t q[32], p[32];
            float m[2], l[2];
#pragma unroll
            for (int i = 0; i < 32; i++) p[i] = 0u;
            l[0] = l[1] = 1.f;
            int pv_acc = 0, pv_mode = 2;
#pragma unroll 1
            for (int r = 0; r < 2; r++) {
                const int heavy = 1 ^ r ^ w;
                const int half = 1 ^ heavy ^ rank ^ (r & SWAPT);
                int left = 2 * (r ? k : 7 - k) + 1 + heavy;
                Cur ck, cv = cur;
                {
                    float s[64];
                    if (r) cur.adv();
                    mbar_wait_hot(misc + BAR_FULL + 8 * cv.slot, cv.ph);
                    token_wait(w);
                    PROF_EV(20);
                    issue_pv(o, p, ring + cv.slot * SLOT_BYTES, 1, r ? 0 : 2);
                    undef_regs(s);
                    uint32_t prev;
                    auto qchunk = [&](int acc) {
                        mbar_wait_hot(misc + BAR_FULL + 8 * cur.slot, cur.ph);
                        const uint64_t da = mkdesc(ring + cur.slot * SLOT_BYTES + w * 8192, 16, 1024, 1);
                        const uint64_t db = mkdesc(ring + cur.slot * SLOT_BYTES + 16384, 8192, 1024, 1);
                        wg_fence();
#pragma unroll
                        for (int ks = 0; ks < 4; ks++) wgmma_ss_n128_ta0_tb1(s, da + 2 * ks, db + 128 * ks, ks ? 1 : acc);
                        wg_commit();
                    };
                    qchunk(0);
                    prev = cur.slot; cur.adv();
                    token_pass(w);
                    if (r) {
                        row_inv(l, inv);
                        tile_out(out, g_ctx + (size_t)((2 * team + v) * 32 + 4 * (7 - k) + (w ? rank : 3 - rank)) * 16384, 0, 0, c);
                    }
                    const int epi = r | (w & DEFER), hs = r ? 4096 : 8192;
                    const int hold = heavy ? -10 : half ? HOLD0 : 8;
#pragma unroll
                    for (int kc = 1; kc < 10; kc++) {
                        if (HOLD0 && kc >= HOLD0 && (kc == hold || kc == hold + 2)) token_wait(w);
                        qchunk(1);
                        if (HOLD0 && kc > HOLD0 && kc == hold + 1) token_pass(w);
                        if (HOLD0 && kc == 9 && heavy) { token_wait(w); token_pass(w); }
                        wg_wait<1>();
                        release(c, BAR_EMPTY + 8 * prev, 1);
                        prev = cur.slot; cur.adv();
                        if (kc == 1) { fence_regs(o); if (r) release(c, BAR_EMPTY + 8 * cv.slot, 1); }
                        if (kc <= 4 && epi) {
                            store_pair(o, kc - 1, out, hs, inv);
                            if (kc == 4) signal_event(c, r ? EV_CTX + 2 * v : EV_KV + 3 * v + 2);
                        }
                    }
                    if (!heavy) cur.adv();
                    ck = cur;
                    cur.adv();
                    if (!heavy) cur.adv();
                    wg_wait<0>();
                    release(c, BAR_EMPTY + 8 * prev, 1);
                    PROF_EV(21);
                    fence_regs(s);
#pragma unroll
                    for (int i = 0; i < 32; i++) q[i] = pack_bf16(s[2 * i], s[2 * i + 1]);
                }
                cv = ck;
                int first = 1, gen = 0;
                uint32_t pv_cnt = 0;
                pv_acc = 0; pv_mode = 2;
                l[0] = l[1] = m[0] = m[1] = 0.f;
                mbar_wait_hot(misc + BAR_FULL + 8 * ck.slot, ck.ph);
#pragma unroll 1
                while (true) {
                    float s[64];
                    if (half & first) {
                        if (heavy || HOLD0 == 0 || HOLD0 == 8) token_wait(w);
                        PROF_EV(30);
                        float sh[32];
                        undef_regs(sh);
                        issue_qk_half(sh, q, ring + ck.slot * SLOT_BYTES);
                        token_pass(w);
                        --left;
                        wg_wait<0>();
                        PROF_EV(34);
                        fence_regs(sh);
                        mask_diag<0>(sh, c);
                        float l0 = 0.f, l1 = 0.f;
#pragma unroll
                        for (int j = 0; j < 8; j++) {
#pragma unroll
                            for (int e = 0; e < 4; e++) ex2v(sh[4 * j + e]);
                            l0 += sh[4 * j] + sh[4 * j + 1]; l1 += sh[4 * j + 2] + sh[4 * j + 3];
                        }
#pragma unroll
                        for (int i = 0; i < 16; i++) p[i] = pack_bf16(sh[2 * i], sh[2 * i + 1]);
                        const int lim = mask_lim(c);
                        if (__any_sync(0xffffffffu, !(l0 <= SAFE_SUM && l1 <= SAFE_SUM && (l0 >= 1.0f / SAFE_SUM || lim < 0) &&
                                                      (l1 >= 1.0f / SAFE_SUM || lim < -2)))) goto redo;
                        l[0] = l0; l[1] = l1;
                        goto tail;
                    }
#pragma unroll 1
                    while (true) {
                        token_wait(w);
                        PROF_EV(first ? 30 : 31);
                        undef_regs(s);
                        issue_qk(s, q, ring + ck.slot * SLOT_BYTES);
                        Cur nck = cur, ncv = cur, ncur;
                        ncv.adv(); ncur = ncv; ncur.adv();
                        --left;
                        mbar_wait_hot(misc + BAR_FULL + 8 * cv.slot, cv.ph);
                        issue_pv(o, p, ring + cv.slot * SLOT_BYTES, pv_acc, pv_mode);
                        token_pass(w);
                        wg_wait<1>();
                        PROF_EV(33);
                        fence_regs(s);
                        float lo = 0.f;
                        if (first) {
                            lo = 1.0f / SAFE_SUM;
                            mask_diag<8>(s, c);
                        }
                        constexpr int JB = 11;
                        float l0 = l[0], l1 = l[1];
                        if (!gen) {
#pragma unroll
                            for (int j = 0; j < JB; j++) {
#pragma unroll
                                for (int e = 0; e < 4; e++) ex2v(s[4 * j + e]);
                                if (j < JB - 1) { l0 += s[4 * j] + s[4 * j + 1]; l1 += s[4 * j + 2] + s[4 * j + 3]; }
                            }
                        }
                        wg_wait<0>();
                        fence_regs(o);
                        if (gen) goto general;
#pragma unroll
                        for (int j = JB - 1; j < 16; j++) {
                            if (j >= JB) {
#pragma unroll
                                for (int e = 0; e < 4; e++) ex2v(s[4 * j + e]);
                            }
                            l0 += s[4 * j] + s[4 * j + 1]; l1 += s[4 * j + 2] + s[4 * j + 3];
                        }
#pragma unroll
                        for (int i = 0; i < 32; i++) p[i] = pack_bf16(s[2 * i], s[2 * i + 1]);
                        if (__any_sync(0xffffffffu, !(l0 <= SAFE_SUM && l1 <= SAFE_SUM && l0 >= lo && l1 >= lo))) goto redo;
                        l[0] = l0; l[1] = l1;
                        if (left == 0) goto tail;
                        release(c, BAR_EMPTY + 8 * ck.slot, 1 + (first & heavy));
                        if (pv_cnt) release(c, BAR_EMPTY + 8 * cv.slot, pv_cnt);
                        pv_acc = first ^ 1; pv_mode = 0; pv_cnt = 1 + (first & heavy); first = 0;
                        ck = nck; cv = ncv; cur = ncur;
                        mbar_wait_hot(misc + BAR_FULL + 8 * ck.slot, ck.ph);
                    }
                redo:
                    recompute_scores(s, q, ring + ck.slot * SLOT_BYTES, c);
                    if (first) { mask_any(s, half ^ 1, c); m[0] = m[1] = -INFINITY; }
                    gen = 1;
                general:
                    {
                        float mx[2], alpha[2];
                        row_max<16>(s, mx);
#pragma unroll
                        for (int i = 0; i < 2; i++) {
                            mx[i] = fmaxf(mx[i], m[i]);
                            alpha[i] = ex2(m[i] - mx[i]);
                            m[i] = mx[i];
                            l[i] *= alpha[i];
                        }
                        exp_sum<16, true>(s, m, l[0], l[1]);
#pragma unroll
                        for (int i = 0; i < 64; i++) o[i] *= alpha[(i >> 1) & 1];
#pragma unroll
                        for (int i = 0; i < 32; i++) p[i] = pack_bf16(s[2 * i], s[2 * i + 1]);
                    }
                tail:
                    release(c, BAR_EMPTY + 8 * ck.slot, 1 + (first & heavy));
                    if (pv_cnt) release(c, BAR_EMPTY + 8 * cv.slot, pv_cnt);
                    pv_acc = first ^ 1; pv_mode = first & half; pv_cnt = 1 + (first & heavy); first = 0;
                    if (left == 0) break;
                    ck = cur; cur.adv(); cv = cur; cur.adv();
                    mbar_wait_hot(misc + BAR_FULL + 8 * ck.slot, ck.ph);
                }
            }
            mbar_wait_hot(misc + BAR_FULL + 8 * cur.slot, cur.ph);
            token_wait(w);
            PROF_EV(32);
            issue_pv(o, p, ring + cur.slot * SLOT_BYTES, pv_acc, pv_mode);
            if (w == 0 || v == 0) token_pass(w);
            const uint32_t vslot = cur.slot;
            cur.adv();
            if (v) {
                row_inv(l, inv);
                wg_wait<0>();
                release(c, BAR_EMPTY + 8 * vslot, 1);
                fence_regs(o);
                tile_out(out, g_ctx + (size_t)((2 * team + 1) * 32 + 4 * k + (w ? 3 - (rank ^ SWAPT) : rank ^ SWAPT)) * 16384, 0, 0, c);
#pragma unroll
                for (int i = 0; i < 64; i++) wf[i] = 0u;
                continue;
            }
            cw = cur_at(80);
            mbar_wait_hot(misc + BAR_FULL + 8 * slot_of(76), cur_at(76).ph);
            mbar_wait_hot(misc + BAR_FULL + 8 * slot_of(78), cur_at(78).ph);
            load_afrag<8, 32>(wf, ring + slot_of(78) * SLOT_BYTES + w * 16384, c);
            const uint32_t z = load_afrag<8, 0>(wf, ring + slot_of(76) * SLOT_BYTES + w * 16384, c);
            row_inv(l, inv);
            release(c, BAR_EMPTY + 8 * slot_of(76) + z, 1);
            asm volatile("{\n.reg .pred p;\nsetp.eq.u32 p, %0, 0;\n@p bar.sync 4, 128;\n@!p bar.sync 5, 128;\n}\n" ::"r"(w) : "memory");
            wg_wait<0>();
            release(c, BAR_EMPTY + 8 * vslot, 1);
            fence_regs(o);
            {
                const uint32_t base = ring + slot_of(78) * SLOT_BYTES + w * 16384 + (16 * c.warp + (c.lane >> 2)) * 64 + (((c.lane ^ (c.lane >> 3)) & 3) << 4);
#pragma unroll
                for (int i = 0; i < 2; i++)
#pragma unroll
                    for (int qq = 0; qq < 4; qq++)
                        asm volatile("st.shared.v4.b32 [%0], {%1,%2,%3,%4};" ::"r"(base + qq * 4096 + i * 512),
                                     "r"(pack_bf16(o[16 * qq + 2 * i] * inv[i], o[16 * qq + 2 * i + 1] * inv[i])),
                                     "r"(pack_bf16(o[16 * qq + 4 + 2 * i] * inv[i], o[16 * qq + 4 + 2 * i + 1] * inv[i])),
                                     "r"(pack_bf16(o[16 * qq + 8 + 2 * i] * inv[i], o[16 * qq + 8 + 2 * i + 1] * inv[i])),
                                     "r"(pack_bf16(o[16 * qq + 12 + 2 * i] * inv[i], o[16 * qq + 12 + 2 * i + 1] * inv[i])) : "memory");
                asm volatile("fence.proxy.async.shared::cta;" ::: "memory");
                signal_event(c, EV_CTX + 1);
            }
        }
        }
        {
            float acc[80];
            undef_regs(acc);
            int st = 0, prev = 0; uint32_t ph3 = 0;
            auto op_stage = [&](int i) {
                mbar_wait(misc + BAR_FULL3 + 8 * st, ph3);
                PROF_EV(44);
                uint32_t base = ring + st * ST3_BYTES;
                uint64_t da = mkdesc(base + w * 8192, 16, 512, 2);
                uint64_t db = mkdesc(base + 16384, 2048, 512, 2);
                wg_fence();
#pragma unroll
                for (int k = 0; k < 4; k++) wgmma_ss_n160_ta0_tb1(acc, da + (k >> 1) * 256 + 2 * (k & 1), db + (k >> 1) * 640 + (k & 1) * 64, k ? 1 : i);
                wg_commit();
                if (i > 0) { wg_wait<1>(); if (i <= 32 - NST3) release(c, BAR_EMPTY3 + 8 * prev, 1); }
                prev = st;
                if (++st == NST3) { st = 0; ph3 ^= 1; }
            };
            PROF_EV(40); PROF_GT(65);
#pragma unroll
            for (int i = 0; i < 4; i++) { op_stage(i); store_pair(o, i, out, 4096, inv); }
            signal_event(c, EV_CTX + 3);
#pragma unroll 1
            for (int i = 4; i < 12; i++) op_stage(i);
            mbar_wait(misc + BAR_SEL, 0);
            const uint32_t tag = lds32(misc + MISC_EPOCH) & 1;
            const int g = c.lane >> 2, t = c.lane & 3;
            const int row = (2 * u3 + rank) * 128 + 64 * w + perm32(16 * c.warp + 8 * kap + g);
            const int col = 160 * s3 + 8 * t;
            int sel = -1;
#pragma unroll
            for (int i = 0; i < TOPC; i++) if ((int)lds32(misc + MISC_SEL + 4 * i) == row) sel = i;
            const int t256 = tid - 128;
            uint4* sendp = g_part + (size_t)cta * 2560 + t256;
            if (c.lane >= 30) stg128(sendp + 9 * 256, tag ^ 1, tag ^ 1, tag ^ 1, tag ^ 1);
#pragma unroll 1
            for (int i = 12; i < 32; i++) op_stage(i);
            uint4 xv[5], bv[5];
#pragma unroll
            for (int i = 0; i < 5; i++) xv[i] = ldg128(P.x + (size_t)row * DM + col + 32 * i);
            uint2 stat;
            asm volatile("ld.global.cg.v2.b32 {%0,%1}, [%2];" : "=r"(stat.x), "=r"(stat.y) : "l"(g_stats + row) : "memory");
            wg_wait<0>();
            fence_regs(acc);
            PROF_EV(41); PROF_GT(66);
            float keep[40];
#pragma unroll
            for (int j = 0; j < 10; j++) {
                uint32_t v0 = __float_as_uint(kap ? acc[8 * j + 0] : acc[8 * j + 2]), v1 = __float_as_uint(kap ? acc[8 * j + 1] : acc[8 * j + 3]);
                uint32_t v2 = __float_as_uint(kap ? acc[8 * j + 4] : acc[8 * j + 6]), v3 = __float_as_uint(kap ? acc[8 * j + 5] : acc[8 * j + 7]);
                asm volatile("st.relaxed.gpu.global.v4.b32 [%0], {%1,%2,%3,%4};" ::"l"(sendp + j * 256),
                             "r"((v0 & ~1u) | tag), "r"((v1 & ~1u) | tag), "r"((v2 & ~1u) | tag), "r"((v3 & ~1u) | tag) : "memory");
                keep[4 * j + 0] = kap ? acc[8 * j + 2] : acc[8 * j + 0]; keep[4 * j + 1] = kap ? acc[8 * j + 3] : acc[8 * j + 1];
                keep[4 * j + 2] = kap ? acc[8 * j + 6] : acc[8 * j + 4]; keep[4 * j + 3] = kap ? acc[8 * j + 7] : acc[8 * j + 5];
            }
            PROF_GT(67);
#pragma unroll
            for (int i = 0; i < 5; i++) {
                uint32_t xx[4] = {xv[i].x, xv[i].y, xv[i].z, xv[i].w};
#pragma unroll
                for (int e = 0; e < 4; e++) {
                    asm("sub.rn.bf16x2 %0, %0, %1;" : "+r"(xx[e]) : "r"(stat.x));
                    xx[e] = pack_bf16(bf_lo(xx[e]) * __uint_as_float(stat.y), bf_hi(xx[e]) * __uint_as_float(stat.y));
                }
                bv[i] = make_uint4(xx[0], xx[1], xx[2], xx[3]);
            }
            if (sel >= 0) {
#pragma unroll
                for (int i = 0; i < 5; i++) bv[i] = ldg128(g_brow + sel * DM + col + 32 * i);
            }
            const uint4* recvp = g_part + (size_t)partner * 2560 + t256;
            uint4 rv[10];
            int spins = 0;
            while (true) {
                uint32_t v;
                asm volatile("ld.relaxed.gpu.global.b32 %0, [%1];" : "=r"(v) : "l"(recvp + 9 * 256 + (31 - c.lane)) : "memory");
                if (__all_sync(0xffffffffu, (v & 1u) == tag) || ++spins > 2000000) break;
            }
            PROF_GT(68);
            while (true) {
                uint32_t bad = 0u;
#pragma unroll
                for (int j = 0; j < 10; j++) {
                    asm volatile("ld.relaxed.gpu.global.v4.b32 {%0,%1,%2,%3}, [%4];"
                                 : "=r"(rv[j].x), "=r"(rv[j].y), "=r"(rv[j].z), "=r"(rv[j].w) : "l"(recvp + j * 256) : "memory");
                }
#pragma unroll
                for (int j = 0; j < 10; j++) {
                    rv[j].x ^= tag; rv[j].y ^= tag; rv[j].z ^= tag; rv[j].w ^= tag;
                    bad |= rv[j].x | rv[j].y | rv[j].z | rv[j].w;
                }
                if (__all_sync(0xffffffffu, (bad & 1u) == 0) || ++spins > 2000000) break;
            }
            PROF_GT(69);
            uint32_t pk[20];
#pragma unroll
            for (int j = 0; j < 10; j++) {
                pk[2 * j] = pack_bf16(keep[4 * j] + __uint_as_float(rv[j].x), keep[4 * j + 1] + __uint_as_float(rv[j].y));
                pk[2 * j + 1] = pack_bf16(keep[4 * j + 2] + __uint_as_float(rv[j].z), keep[4 * j + 3] + __uint_as_float(rv[j].w));
            }
#pragma unroll
            for (int i = 0; i < 5; i++) {
                uint32_t a0 = pk[4 * i], a1 = pk[4 * i + 1], a2 = pk[4 * i + 2], a3 = pk[4 * i + 3];
                uint32_t x0 = (t & 1) ? a0 : a1, x1 = (t & 1) ? a2 : a3;
                x0 = __shfl_xor_sync(0xffffffffu, x0, 1); x1 = __shfl_xor_sync(0xffffffffu, x1, 1);
                if (t & 1) { a0 = x0; a2 = x1; } else { a1 = x0; a3 = x1; }
                x0 = (t & 2) ? a0 : a2; x1 = (t & 2) ? a1 : a3;
                x0 = __shfl_xor_sync(0xffffffffu, x0, 2); x1 = __shfl_xor_sync(0xffffffffu, x1, 2);
                if (t & 2) { a0 = x0; a1 = x1; } else { a2 = x0; a3 = x1; }
                uint32_t av[4] = {a0, a1, a2, a3};
                uint32_t xx[4] = {xv[i].x, xv[i].y, xv[i].z, xv[i].w}, bb[4] = {bv[i].x, bv[i].y, bv[i].z, bv[i].w};
                uint32_t ov[4];
#pragma unroll
                for (int e = 0; e < 4; e++) {
                    asm("add.rn.bf16x2 %0, %1, %2;" : "=r"(ov[e]) : "r"(xx[e]), "r"(av[e]));
                    asm("add.rn.bf16x2 %0, %0, %1;" : "+r"(ov[e]) : "r"(bb[e]));
                }
                stg128(P.out + (size_t)row * DM + col + 32 * i, ov[0], ov[1], ov[2], ov[3]);
            }
            PROF_EV(42); PROF_GT(43);
        }
    }
}

typedef CUresult (*EncodeFn)(CUtensorMap*, CUtensorMapDataType, cuuint32_t, void*, const cuuint64_t*, const cuuint64_t*, const cuuint32_t*,
                             const cuuint32_t*, CUtensorMapInterleave, CUtensorMapSwizzle, CUtensorMapL2promotion, CUtensorMapFloatOOBfill);

void make_map2d(EncodeFn enc, CUtensorMap* tm, const void* p, uint64_t cols, uint64_t rows, uint32_t box_rows = 128) {
    cuuint64_t gd[2] = {cols, rows}, gs[1] = {cols * 2};
    cuuint32_t box[2] = {64, box_rows}, es[2] = {1, 1};
    enc(tm, CU_TENSOR_MAP_DATA_TYPE_BFLOAT16, 2, const_cast<void*>(p), gd, gs, box, es, CU_TENSOR_MAP_INTERLEAVE_NONE,
        CU_TENSOR_MAP_SWIZZLE_128B, CU_TENSOR_MAP_L2_PROMOTION_L2_128B, CU_TENSOR_MAP_FLOAT_OOB_FILL_NONE);
}

void make_map3d(EncodeFn enc, CUtensorMap* tm, const void* p, uint64_t cols, uint64_t rows, uint32_t bw, uint32_t nb) {
    cuuint64_t gd[3] = {bw, rows, cols / bw}, gs[2] = {cols * 2, bw * 2};
    cuuint32_t box[3] = {bw, 32, nb}, es[3] = {1, 1, 1};
    enc(tm, CU_TENSOR_MAP_DATA_TYPE_BFLOAT16, 3, const_cast<void*>(p), gd, gs, box, es, CU_TENSOR_MAP_INTERLEAVE_NONE,
        bw == 64 ? CU_TENSOR_MAP_SWIZZLE_128B : CU_TENSOR_MAP_SWIZZLE_64B, CU_TENSOR_MAP_L2_PROMOTION_L2_128B, CU_TENSOR_MAP_FLOAT_OOB_FILL_NONE);
}

}

extern "C" void kernel_launch(void* const* d_in, const int* in_sizes, int n_in, void* d_out, int out_size) {
    (void)in_sizes; (void)n_in; (void)out_size;
    static EncodeFn enc = nullptr;
    if (!enc) {
        void* fn = nullptr;
        cudaDriverEntryPointQueryResult qr;
        cudaGetDriverEntryPoint("cuTensorMapEncodeTiled", &fn, cudaEnableDefault, &qr);
        enc = (EncodeFn)fn;
        cudaFuncSetAttribute(fused_kernel, cudaFuncAttributeMaxDynamicSharedMemorySize, SMEM_BYTES);
    }
    CUtensorMap tmC, tmWk, tmWv, tmWq, tmWo, tmG, tmU, tmD;
    make_map2d(enc, &tmC, d_in[1], DC, SEQ);
    make_map2d(enc, &tmWq, d_in[2], 4096, DM, 64);
    make_map2d(enc, &tmWk, d_in[3], 4096, DC);
    make_map2d(enc, &tmWv, d_in[4], 4096, DC);
    make_map3d(enc, &tmWo, d_in[5], DM, 4096, 32, 5);
    make_map3d(enc, &tmG, d_in[8], FF, DM, 64, 7);
    make_map3d(enc, &tmU, d_in[9], FF, DM, 64, 7);
    make_map3d(enc, &tmD, d_in[10], DM, FF, 64, 10);
    Params P;
    P.x = (const __nv_bfloat16*)d_in[0];
    P.c = (const __nv_bfloat16*)d_in[1];
    P.wk = (const __nv_bfloat16*)d_in[3];
    P.wv = (const __nv_bfloat16*)d_in[4];
    P.wo = (const __nv_bfloat16*)d_in[5];
    P.wr = (const __nv_bfloat16*)d_in[7];
    P.out = (__nv_bfloat16*)d_out;
    fused_kernel<<<132, 384, SMEM_BYTES>>>(tmC, tmWk, tmWv, tmWq, tmWo, tmG, tmU, tmD, P);
}
```

```cpp
#include <cuda_runtime.h>
#include <cuda_bf16.h>
#include <cuda.h>
#include <stdint.h>

#define SWAPT 1
#define DEFER 1
#define HOLD0 6
#define LNINL __noinline__
#define HM 513
#define OP_PF 8
#define PF_START 9
#define LATE_AT 18
#define CDELAY 500
#define AUXDELAY 1000
namespace {

constexpr int SEQ = 2048, NH = 32, DM = 640, DC = 512, FF = 1728, TOPC = 8;
constexpr int NSLOT = 7, SLOT_BYTES = 32768;
constexpr int NST3 = 6, ST3_BYTES = 36864;
constexpr int RING_BYTES = NSLOT * SLOT_BYTES;
constexpr int SMEM_BYTES = RING_BYTES + 3072;

constexpr int BAR_FULL = 96  , BAR_FULL3 = 152  , BAR_DEP = 200  , BAR_SEL = 464,
              BAR_LN = 472  , BAR_EV = 504  , BAR_EMPTY = 760  , BAR_EMPTY3 = 816  ,
              BAR_PROG = 864  , MISC_EPOCH = 896, MISC_SMID = 900  , MISC_SEL = 912, MISC_WR = 1024  ;
constexpr int D_LN = 0  , D_KV = 4  , D_WAR = 14  , D_CTX = 16  ;
constexpr int EV_KV = 0  , EV_END = 11, EV_CTX = 12  ;

constexpr int FL_MOE_CNT = 0, FL_MOE_DONE = 1, FL_LN = 16  , FL_KV = 32  , FL_CTX = 416  , FL_WAR = 672  , FL_TOTAL = 704;

__device__ __align__(1024) unsigned char g_K[16 * 32 * 16384];
__device__ __align__(1024) unsigned char g_V[16 * 32 * 16384];
__device__ __align__(1024) unsigned char g_ctx[NH * 32 * 16384];
__device__ __align__(1024) unsigned char g_xn[16 * 10 * 16384];
__device__ __align__(1024) uint4 g_part[128 * 10 * 256];
__device__ float g_router[SEQ];
__device__ uint2 g_stats[SEQ];
__device__ __align__(16) float g_moe_part[4 * TOPC * DM];
__device__ __align__(16) __nv_bfloat16 g_brow[TOPC * DM];
__device__ __align__(16) int g_sel[TOPC];
__device__ unsigned g_flags[FL_TOTAL * 8];
__device__ unsigned g_epoch;
__device__ unsigned g_roleq[130];

struct Params {
    const __nv_bfloat16 *x, *c, *wr, *wk, *wv, *wo;
    __nv_bfloat16* out;
};

__device__ __forceinline__ uint32_t smem_u32(const void* p) { return (uint32_t)__cvta_generic_to_shared(p); }
__device__ __forceinline__ void mbar_init(uint32_t bar, int cnt) { asm volatile("mbarrier.init.shared::cta.b64 [%0], %1;" ::"r"(bar), "r"(cnt)); }
__device__ __forceinline__ void mbar_expect_tx(uint32_t bar, uint32_t bytes) {
    asm volatile("mbarrier.arrive.expect_tx.shared::cta.b64 _, [%0], %1;" ::"r"(bar), "r"(bytes) : "memory");
}
__device__ __forceinline__ void mbar_arrive(uint32_t bar) { asm volatile("mbarrier.arrive.shared::cta.b64 _, [%0];" ::"r"(bar) : "memory"); }
__device__ __forceinline__ void mbar_arrive_cluster(uint32_t cluster_addr, uint32_t cnt) {
    asm volatile("mbarrier.arrive.shared::cluster.b64 _, [%0], %1;" ::"r"(cluster_addr), "r"(cnt) : "memory");
}
__device__ __forceinline__ uint32_t mapa(uint32_t addr, uint32_t cta) {
    uint32_t r; asm("mapa.shared::cluster.u32 %0, %1, %2;" : "=r"(r) : "r"(addr), "r"(cta)); return r;
}
__device__ __forceinline__ void mbar_wait(uint32_t bar, uint32_t parity) {
    asm volatile(
        "{\n.reg .pred p;\n.reg .u32 n;\n"
        "mov.u32 n, 0;\n"
        "LAB_WAIT:\n"
        "mbarrier.try_wait.parity.shared::cta.b64 p, [%0], %1, 100000;\n"
        "@p bra DONE;\n"
        "add.u32 n, n, 1;\n"
        "setp.lt.u32 p, n, 50000;\n"
        "@p bra LAB_WAIT;\n"
        "trap;\n"
        "DONE:\n}\n" ::"r"(bar), "r"(parity) : "memory");
}
__device__ __forceinline__ void mbar_wait_hot(uint32_t bar, uint32_t parity) {
    asm volatile("{\n.reg .pred p;\nLAB_WAIT:\nmbarrier.try_wait.parity.shared::cta.b64 p, [%0], %1;\n@!p bra LAB_WAIT;\n}\n" ::"r"(bar), "r"(parity) : "memory");
}
__device__ __forceinline__ void mbar_wait_sleep(uint32_t bar, uint32_t parity) {
    asm volatile("{\n.reg .pred p;\nLAB_WAIT:\nmbarrier.try_wait.parity.shared::cta.b64 p, [%0], %1, 100000;\n@!p bra LAB_WAIT;\n}\n" ::"r"(bar), "r"(parity) : "memory");
}
__device__ __forceinline__ void flag_wait(const unsigned* flag, unsigned target) {
    asm volatile(
        "{\n.reg .pred p;\n.reg .u32 n, v;\n.reg .s32 d;\n"
        "mov.u32 n, 0;\n"
        "LAB_WAIT:\n"
        "ld.acquire.gpu.global.u32 v, [%0];\n"
        "sub.s32 d, v, %1;\n"
        "setp.ge.s32 p, d, 0;\n"
        "@p bra DONE;\n"
        "nanosleep.u32 40;\n"
        "add.u32 n, n, 1;\n"
        "setp.lt.u32 p, n, 3000000;\n"
        "@p bra LAB_WAIT;\n"
        "trap;\n"
        "DONE:\n}\n" ::"l"(flag), "r"(target) : "memory");
}
__device__ __forceinline__ void flag_signal(unsigned* flag) {
    asm volatile("red.release.gpu.global.add.u32 [%0], 1;" ::"l"(flag) : "memory");
}
__device__ __forceinline__ void fence_async_global() { asm volatile("fence.proxy.async.global;" ::: "memory"); }
__device__ __forceinline__ unsigned* flag_ptr(int idx) { return g_flags + idx * 8; }

__device__ __forceinline__ uint64_t policy_stream() {
    uint64_t p; asm("createpolicy.fractional.L2::evict_first.b64 %0, 1.0;" : "=l"(p)); return p;
}
__device__ __forceinline__ uint64_t policy_normal() { return 0x1000000000000000ull; }
__device__ __forceinline__ uint64_t policy(bool stream) { return stream ? policy_stream() : policy_normal(); }
__device__ __forceinline__ void bulk_load(uint32_t dst, const void* src, uint32_t bytes, uint32_t bar, uint64_t pol) {
    asm volatile("cp.async.bulk.shared::cluster.global.mbarrier::complete_tx::bytes.L2::cache_hint [%0], [%1], %2, [%3], %4;"
                 ::"r"(dst), "l"(src), "r"(bytes), "r"(bar), "l"(pol) : "memory");
}
__device__ __forceinline__ void bulk_load_mc(uint32_t dst, const void* src, uint32_t bytes, uint32_t bar, uint64_t pol) {
    asm volatile("cp.async.bulk.shared::cluster.global.mbarrier::complete_tx::bytes.multicast::cluster.L2::cache_hint [%0], [%1], %2, [%3], %4, %5;"
                 ::"r"(dst), "l"(src), "r"(bytes), "r"(bar), "h"((uint16_t)3), "l"(pol) : "memory");
}
__device__ __forceinline__ void tma2d(uint32_t dst, const CUtensorMap* tm, int c0, int c1, uint32_t bar, uint64_t pol) {
    asm volatile("cp.async.bulk.tensor.2d.shared::cluster.global.mbarrier::complete_tx::bytes.L2::cache_hint [%0], [%1, {%3, %4}], [%2], %5;"
                 ::"r"(dst), "l"(tm), "r"(bar), "r"(c0), "r"(c1), "l"(pol) : "memory");
}
__device__ __forceinline__ void tma2d_mc(uint32_t dst, const CUtensorMap* tm, int c0, int c1, uint32_t bar, uint64_t pol) {
    asm volatile("cp.async.bulk.tensor.2d.shared::cluster.global.mbarrier::complete_tx::bytes.multicast::cluster.L2::cache_hint [%0], [%1, {%3, %4}], [%2], %5, %6;"
                 ::"r"(dst), "l"(tm), "r"(bar), "r"(c0), "r"(c1), "h"((uint16_t)3), "l"(pol) : "memory");
}
__device__ __forceinline__ void tma3d_mc(uint32_t dst, const CUtensorMap* tm, int c0, int c1, int c2, uint32_t bar, uint64_t pol) {
    asm volatile("cp.async.bulk.tensor.3d.shared::cluster.global.mbarrier::complete_tx::bytes.multicast::cluster.L2::cache_hint [%0], [%1, {%3, %4, %5}], [%2], %6, %7;"
                 ::"r"(dst), "l"(tm), "r"(bar), "r"(c0), "r"(c1), "r"(c2), "h"((uint16_t)3), "l"(pol) : "memory");
}
__device__ __forceinline__ void tma3d(uint32_t dst, const CUtensorMap* tm, int c0, int c1, int c2, uint32_t bar) {
    asm volatile("cp.async.bulk.tensor.3d.shared::cluster.global.mbarrier::complete_tx::bytes.L2::cache_hint [%0], [%1, {%3, %4, %5}], [%2], %6;"
                 ::"r"(dst), "l"(tm), "r"(bar), "r"(c0), "r"(c1), "r"(c2), "l"(policy_stream()) : "memory");
}
__device__ __forceinline__ void tma2d_prefetch(const CUtensorMap* tm, int c0, int c1) {
    asm volatile("cp.async.bulk.prefetch.tensor.2d.L2.global [%0, {%1, %2}];" ::"l"(tm), "r"(c0), "r"(c1) : "memory");
}
__device__ __forceinline__ void tma3d_prefetch(const CUtensorMap* tm, int c0, int c1, int c2) {
    asm volatile("cp.async.bulk.prefetch.tensor.3d.L2.global [%0, {%1, %2, %3}];" ::"l"(tm), "r"(c0), "r"(c1), "r"(c2) : "memory");
}
__device__ __forceinline__ void l2_prefetch(const void* p, uint32_t bytes) {
    asm volatile("cp.async.bulk.prefetch.L2.global [%0], %1;" ::"l"(p), "r"(bytes) : "memory");
}
__device__ __forceinline__ bool elect_one() {
    uint32_t r; asm volatile("{\n.reg .pred p;\nelect.sync _|p, 0xffffffff;\nselp.u32 %0, 1, 0, p;\n}\n" : "=r"(r)); return r != 0;
}
__device__ __forceinline__ void wg_fence() { asm volatile("wgmma.fence.sync.aligned;" ::: "memory"); }
__device__ __forceinline__ void wg_commit() { asm volatile("wgmma.commit_group.sync.aligned;" ::: "memory"); }
template <int N> __device__ __forceinline__ void wg_wait() { asm volatile("wgmma.wait_group.sync.aligned %0;" ::"n"(N) : "memory"); }
__device__ __forceinline__ void bar_sync(int id, int n) { asm volatile("bar.sync %0, %1;" ::"r"(id), "r"(n) : "memory"); }
__device__ __forceinline__ void bar_arrive(int id, int n) { asm volatile("bar.arrive %0, %1;" ::"r"(id), "r"(n) : "memory"); }
__device__ __forceinline__ void token_wait(int w) {
    asm volatile("{\n.reg .pred p;\nsetp.eq.u32 p, %0, 0;\n@p bar.sync 1, 256;\n@!p bar.sync 2, 256;\n}\n" ::"r"(w) : "memory");
}
__device__ __forceinline__ void token_pass(int w) {
    asm volatile("{\n.reg .pred p;\nsetp.eq.u32 p, %0, 0;\n@p bar.arrive 2, 256;\n@!p bar.arrive 1, 256;\n}\n" ::"r"(w) : "memory");
}
template <int N> __device__ __forceinline__ void fence_regs(float (&a)[N]) {
#pragma unroll
    for (int i = 0; i < N; i++) asm volatile("" : "+f"(a[i])::"memory");
}
template <int N> __device__ __forceinline__ void undef_regs(float (&a)[N]) {
#pragma unroll
    for (int i = 0; i < N; i++) asm volatile("" : "=f"(a[i]));
}
__device__ __forceinline__ void ldsm4t(uint32_t& r0, uint32_t& r1, uint32_t& r2, uint32_t& r3, uint32_t addr) {
    asm volatile("ldmatrix.sync.aligned.m8n8.x4.trans.shared.b16 {%0,%1,%2,%3}, [%4];"
                 : "=r"(r0), "=r"(r1), "=r"(r2), "=r"(r3) : "r"(addr) : "memory");
}
__device__ __forceinline__ uint32_t pack_bf16(float lo, float hi) {
    uint32_t r; asm("cvt.rn.bf16x2.f32 %0, %1, %2;" : "=r"(r) : "f"(hi), "f"(lo)); return r;
}
__device__ __forceinline__ float bf_lo(uint32_t v) { return __uint_as_float(v << 16); }
__device__ __forceinline__ float bf_hi(uint32_t v) { return __uint_as_float(v & 0xffff0000u); }
__device__ __forceinline__ float bf_round(float v) { return __bfloat162float(__float2bfloat16_rn(v)); }
__device__ __forceinline__ float ex2(float v) { float r; asm("ex2.approx.ftz.f32 %0, %1;" : "=f"(r) : "f"(v)); return r; }
__device__ __forceinline__ void ex2v(float& v) { asm volatile("ex2.approx.ftz.f32 %0, %0;" : "+f"(v)); }
__device__ __forceinline__ float rcp_fast(float v) { float r; asm("rcp.approx.ftz.f32 %0, %1;" : "=f"(r) : "f"(v)); return r; }
__device__ __forceinline__ float sqrt_fast(float v) { float r; asm("sqrt.approx.ftz.f32 %0, %1;" : "=f"(r) : "f"(v)); return r; }
__device__ __forceinline__ void stg128(void* p, uint32_t a, uint32_t b, uint32_t c, uint32_t d) {
    asm volatile("st.global.v4.b32 [%0], {%1,%2,%3,%4};" ::"l"(p), "r"(a), "r"(b), "r"(c), "r"(d) : "memory");
}
__device__ __forceinline__ uint4 ldg128(const void* p) {
    uint4 v; asm volatile("ld.global.cg.v4.b32 {%0,%1,%2,%3}, [%4];" : "=r"(v.x), "=r"(v.y), "=r"(v.z), "=r"(v.w) : "l"(p) : "memory"); return v;
}
__device__ __forceinline__ uint64_t mkdesc(uint32_t addr, uint32_t lbo, uint32_t sbo, uint32_t swz) {
    uint32_t lo = ((addr & 0x3FFFF) >> 4) | ((lbo >> 4) << 16);
    uint32_t hi = (sbo >> 4) | (swz << 30);
    return ((uint64_t)hi << 32) | lo;
}
__device__ __forceinline__ int perm32(int v) { return (v & ~30) | ((v >> 2) & 6) | ((v << 2) & 24); }

__device__ __forceinline__ void wgmma_rs_n128_ta0_tb0(float (&d)[64], uint32_t a0, uint32_t a1, uint32_t a2, uint32_t a3, uint64_t descB, int scaleD) {
  asm volatile("{\n.reg .pred p;\nsetp.ne.b32 p, %69, 0;\n"
    "wgmma.mma_async.sync.aligned.m64n128k16.f32.bf16.bf16 "
    "{%0, %1, %2, %3, %4, %5, %6, %7, %8, %9, %10, %11, %12, %13, %14, %15, %16, %17, %18, %19, %20, %21, %22, %23, %24, %25, %26, %27, %28, %29, %30, %31, %32, %33, %34, %35, %36, %37, %38, %39, %40, %41, %42, %43, %44, %45, %46, %47, %48, %49, %50, %51, %52, %53, %54, %55, %56, %57, %58, %59, %60, %61, %62, %63}, "
    "{%64, %65, %66, %67}, %68, p, 1, 1, 0;\n}\n"
    : "+f"(d[0]), "+f"(d[1]), "+f"(d[2]), "+f"(d[3]), "+f"(d[4]), "+f"(d[5]), "+f"(d[6]), "+f"(d[7]), "+f"(d[8]), "+f"(d[9]), "+f"(d[10]), "+f"(d[11]), "+f"(d[12]), "+f"(d[13]), "+f"(d[14]), "+f"(d[15]), "+f"(d[16]), "+f"(d[17]), "+f"(d[18]), "+f"(d[19]), "+f"(d[20]), "+f"(d[21]), "+f"(d[22]), "+f"(d[23]), "+f"(d[24]), "+f"(d[25]), "+f"(d[26]), "+f"(d[27]), "+f"(d[28]), "+f"(d[29]), "+f"(d[30]), "+f"(d[31]), "+f"(d[32]), "+f"(d[33]), "+f"(d[34]), "+f"(d[35]), "+f"(d[36]), "+f"(d[37]), "+f"(d[38]), "+f"(d[39]), "+f"(d[40]), "+f"(d[41]), "+f"(d[42]), "+f"(d[43]), "+f"(d[44]), "+f"(d[45]), "+f"(d[46]), "+f"(d[47]), "+f"(d[48]), "+f"(d[49]), "+f"(d[50]), "+f"(d[51]), "+f"(d[52]), "+f"(d[53]), "+f"(d[54]), "+f"(d[55]), "+f"(d[56]), "+f"(d[57]), "+f"(d[58]), "+f"(d[59]), "+f"(d[60]), "+f"(d[61]), "+f"(d[62]), "+f"(d[63])
    : "r"(a0), "r"(a1), "r"(a2), "r"(a3), "l"(descB), "r"(scaleD));
}
__device__ __forceinline__ void wgmma_rs_n128_ta0_tb1(float (&d)[64], uint32_t a0, uint32_t a1, uint32_t a2, uint32_t a3, uint64_t descB, int scaleD) {
  asm volatile("{\n.reg .pred p;\nsetp.ne.b32 p, %69, 0;\n"
    "wgmma.mma_async.sync.aligned.m64n128k16.f32.bf16.bf16 "
    "{%0, %1, %2, %3, %4, %5, %6, %7, %8, %9, %10, %11, %12, %13, %14, %15, %16, %17, %18, %19, %20, %21, %22, %23, %24, %25, %26, %27, %28, %29, %30, %31, %32, %33, %34, %35, %36, %37, %38, %39, %40, %41, %42, %43, %44, %45, %46, %47, %48, %49, %50, %51, %52, %53, %54, %55, %56, %57, %58, %59, %60, %61, %62, %63}, "
    "{%64, %65, %66, %67}, %68, p, 1, 1, 1;\n}\n"
    : "+f"(d[0]), "+f"(d[1]), "+f"(d[2]), "+f"(d[3]), "+f"(d[4]), "+f"(d[5]), "+f"(d[6]), "+f"(d[7]), "+f"(d[8]), "+f"(d[9]), "+f"(d[10]), "+f"(d[11]), "+f"(d[12]), "+f"(d[13]), "+f"(d[14]), "+f"(d[15]), "+f"(d[16]), "+f"(d[17]), "+f"(d[18]), "+f"(d[19]), "+f"(d[20]), "+f"(d[21]), "+f"(d[22]), "+f"(d[23]), "+f"(d[24]), "+f"(d[25]), "+f"(d[26]), "+f"(d[27]), "+f"(d[28]), "+f"(d[29]), "+f"(d[30]), "+f"(d[31]), "+f"(d[32]), "+f"(d[33]), "+f"(d[34]), "+f"(d[35]), "+f"(d[36]), "+f"(d[37]), "+f"(d[38]), "+f"(d[39]), "+f"(d[40]), "+f"(d[41]), "+f"(d[42]), "+f"(d[43]), "+f"(d[44]), "+f"(d[45]), "+f"(d[46]), "+f"(d[47]), "+f"(d[48]), "+f"(d[49]), "+f"(d[50]), "+f"(d[51]), "+f"(d[52]), "+f"(d[53]), "+f"(d[54]), "+f"(d[55]), "+f"(d[56]), "+f"(d[57]), "+f"(d[58]), "+f"(d[59]), "+f"(d[60]), "+f"(d[61]), "+f"(d[62]), "+f"(d[63])
    : "r"(a0), "r"(a1), "r"(a2), "r"(a3), "l"(descB), "r"(scaleD));
}
__device__ __forceinline__ void wgmma_rs_n64_ta0_tb1(float (&d)[32], uint32_t a0, uint32_t a1, uint32_t a2, uint32_t a3, uint64_t descB, int scaleD) {
  asm volatile("{\n.reg .pred p;\nsetp.ne.b32 p, %37, 0;\n"
    "wgmma.mma_async.sync.aligned.m64n64k16.f32.bf16.bf16 "
    "{%0, %1, %2, %3, %4, %5, %6, %7, %8, %9, %10, %11, %12, %13, %14, %15, %16, %17, %18, %19, %20, %21, %22, %23, %24, %25, %26, %27, %28, %29, %30, %31}, "
    "{%32, %33, %34, %35}, %36, p, 1, 1, 1;\n}\n"
    : "+f"(d[0]), "+f"(d[1]), "+f"(d[2]), "+f"(d[3]), "+f"(d[4]), "+f"(d[5]), "+f"(d[6]), "+f"(d[7]), "+f"(d[8]), "+f"(d[9]), "+f"(d[10]), "+f"(d[11]), "+f"(d[12]), "+f"(d[13]), "+f"(d[14]), "+f"(d[15]), "+f"(d[16]), "+f"(d[17]), "+f"(d[18]), "+f"(d[19]), "+f"(d[20]), "+f"(d[21]), "+f"(d[22]), "+f"(d[23]), "+f"(d[24]), "+f"(d[25]), "+f"(d[26]), "+f"(d[27]), "+f"(d[28]), "+f"(d[29]), "+f"(d[30]), "+f"(d[31])
    : "r"(a0), "r"(a1), "r"(a2), "r"(a3), "l"(descB), "r"(scaleD));
}
__device__ __forceinline__ void wgmma_ss_n128_ta0_tb1(float (&d)[64], uint64_t descA, uint64_t descB, int scaleD) {
  asm volatile("{\n.reg .pred p;\nsetp.ne.b32 p, %66, 0;\n"
    "wgmma.mma_async.sync.aligned.m64n128k16.f32.bf16.bf16 "
    "{%0, %1, %2, %3, %4, %5, %6, %7, %8, %9, %10, %11, %12, %13, %14, %15, %16, %17, %18, %19, %20, %21, %22, %23, %24, %25, %26, %27, %28, %29, %30, %31, %32, %33, %34, %35, %36, %37, %38, %39, %40, %41, %42, %43, %44, %45, %46, %47, %48, %49, %50, %51, %52, %53, %54, %55, %56, %57, %58, %59, %60, %61, %62, %63}, "
    "%64, %65, p, 1, 1, 0, 1;\n}\n"
    : "+f"(d[0]), "+f"(d[1]), "+f"(d[2]), "+f"(d[3]), "+f"(d[4]), "+f"(d[5]), "+f"(d[6]), "+f"(d[7]), "+f"(d[8]), "+f"(d[9]), "+f"(d[10]), "+f"(d[11]), "+f"(d[12]), "+f"(d[13]), "+f"(d[14]), "+f"(d[15]), "+f"(d[16]), "+f"(d[17]), "+f"(d[18]), "+f"(d[19]), "+f"(d[20]), "+f"(d[21]), "+f"(d[22]), "+f"(d[23]), "+f"(d[24]), "+f"(d[25]), "+f"(d[26]), "+f"(d[27]), "+f"(d[28]), "+f"(d[29]), "+f"(d[30]), "+f"(d[31]), "+f"(d[32]), "+f"(d[33]), "+f"(d[34]), "+f"(d[35]), "+f"(d[36]), "+f"(d[37]), "+f"(d[38]), "+f"(d[39]), "+f"(d[40]), "+f"(d[41]), "+f"(d[42]), "+f"(d[43]), "+f"(d[44]), "+f"(d[45]), "+f"(d[46]), "+f"(d[47]), "+f"(d[48]), "+f"(d[49]), "+f"(d[50]), "+f"(d[51]), "+f"(d[52]), "+f"(d[53]), "+f"(d[54]), "+f"(d[55]), "+f"(d[56]), "+f"(d[57]), "+f"(d[58]), "+f"(d[59]), "+f"(d[60]), "+f"(d[61]), "+f"(d[62]), "+f"(d[63])
    : "l"(descA), "l"(descB), "r"(scaleD));
}
__device__ __forceinline__ void wgmma_ss_n160_ta0_tb1(float (&d)[80], uint64_t descA, uint64_t descB, int scaleD) {
  asm volatile("{\n.reg .pred p;\nsetp.ne.b32 p, %82, 0;\n"
    "wgmma.mma_async.sync.aligned.m64n160k16.f32.bf16.bf16 "
    "{%0, %1, %2, %3, %4, %5, %6, %7, %8, %9, %10, %11, %12, %13, %14, %15, %16, %17, %18, %19, %20, %21, %22, %23, %24, %25, %26, %27, %28, %29, %30, %31, %32, %33, %34, %35, %36, %37, %38, %39, %40, %41, %42, %43, %44, %45, %46, %47, %48, %49, %50, %51, %52, %53, %54, %55, %56, %57, %58, %59, %60, %61, %62, %63, %64, %65, %66, %67, %68, %69, %70, %71, %72, %73, %74, %75, %76, %77, %78, %79}, "
    "%80, %81, p, 1, 1, 0, 1;\n}\n"
    : "+f"(d[0]), "+f"(d[1]), "+f"(d[2]), "+f"(d[3]), "+f"(d[4]), "+f"(d[5]), "+f"(d[6]), "+f"(d[7]), "+f"(d[8]), "+f"(d[9]), "+f"(d[10]), "+f"(d[11]), "+f"(d[12]), "+f"(d[13]), "+f"(d[14]), "+f"(d[15]), "+f"(d[16]), "+f"(d[17]), "+f"(d[18]), "+f"(d[19]), "+f"(d[20]), "+f"(d[21]), "+f"(d[22]), "+f"(d[23]), "+f"(d[24]), "+f"(d[25]), "+f"(d[26]), "+f"(d[27]), "+f"(d[28]), "+f"(d[29]), "+f"(d[30]), "+f"(d[31]), "+f"(d[32]), "+f"(d[33]), "+f"(d[34]), "+f"(d[35]), "+f"(d[36]), "+f"(d[37]), "+f"(d[38]), "+f"(d[39]), "+f"(d[40]), "+f"(d[41]), "+f"(d[42]), "+f"(d[43]), "+f"(d[44]), "+f"(d[45]), "+f"(d[46]), "+f"(d[47]), "+f"(d[48]), "+f"(d[49]), "+f"(d[50]), "+f"(d[51]), "+f"(d[52]), "+f"(d[53]), "+f"(d[54]), "+f"(d[55]), "+f"(d[56]), "+f"(d[57]), "+f"(d[58]), "+f"(d[59]), "+f"(d[60]), "+f"(d[61]), "+f"(d[62]), "+f"(d[63]), "+f"(d[64]), "+f"(d[65]), "+f"(d[66]), "+f"(d[67]), "+f"(d[68]), "+f"(d[69]), "+f"(d[70]), "+f"(d[71]), "+f"(d[72]), "+f"(d[73]), "+f"(d[74]), "+f"(d[75]), "+f"(d[76]), "+f"(d[77]), "+f"(d[78]), "+f"(d[79])
    : "l"(descA), "l"(descB), "r"(scaleD));
}

#define PROF_DECL(b)
#define PROF_EV(tag)
#define PROF_GT(tag)

template <int N> struct IC { static constexpr int value = N; };
struct Cur {
    uint32_t slot, ph;
    __device__ __forceinline__ void adv() { if (++slot == NSLOT) { slot = 0; ph ^= 1; } }
};
constexpr int E0 = 2;
__host__ __device__ constexpr uint32_t slot_of(int e) { return (e + E0) % NSLOT; }
__device__ __forceinline__ Cur cur_at(int e) { Cur c; c.slot = (e + E0) % NSLOT; c.ph = ((e + E0) / NSLOT) & 1; return c; }

__device__ __forceinline__ int op_head(int i, int kap) { return 16 * kap + 2 * (i & 7) + (i >> 3); }

constexpr float SM_SCALE = 0.08838834764831845f * 1.4426950408889634f;

struct Ctx {
    uint32_t ring, misc;
    uint32_t rel;
    int w, warp, lane;
};
__device__ __forceinline__ void release(const Ctx& c, uint32_t off, uint32_t cnt) {
    if (c.lane < 2) mbar_arrive_cluster(c.rel + off, cnt);
}
__device__ __forceinline__ void signal_event(const Ctx& c, int ev) {
    __syncwarp();
    if (c.lane == 0) mbar_arrive(c.misc + BAR_EV + (c.w * 16 + ev) * 8);
}
template <int NK, int OFF, int N>
__device__ __forceinline__ uint32_t load_afrag(uint32_t (&a)[N], uint32_t base, const Ctx& c) {
    int r = c.lane & 7, mat = c.lane >> 3;
    uint32_t addr = base + (8 * (mat >> 1) + r) * 128 + (((2 * c.warp + (mat & 1)) ^ r) << 4);
#pragma unroll
    for (int k = 0; k < NK; k++) ldsm4t(a[OFF + 4 * k], a[OFF + 4 * k + 1], a[OFF + 4 * k + 2], a[OFF + 4 * k + 3], addr + k * 2048);
    uint32_t dep = 0;
#pragma unroll
    for (int k = 0; k < NK; k++) dep |= a[OFF + 4 * k];
    return dep & blockIdx.y;
}
__device__ __forceinline__ void tile_out(unsigned char* (&out)[2], unsigned char* dst, int row0, int perm, const Ctx& c) {
#pragma unroll
    for (int i = 0; i < 2; i++) {
        int row = row0 + 16 * c.warp + 8 * i + (c.lane >> 2);
        if (perm) row = perm32(row);
        out[i] = dst + row * 64 + (((c.lane ^ (row >> 1)) & 3) << 4);
    }
}
__device__ __forceinline__ void store_pair(const float (&a)[64], int q, unsigned char* const (&out)[2], int quarter_stride, const float (&f)[2]) {
#pragma unroll
    for (int i = 0; i < 2; i++)
        stg128(out[i] + q * quarter_stride,
               pack_bf16(a[16 * q + 2 * i] * f[i], a[16 * q + 2 * i + 1] * f[i]), pack_bf16(a[16 * q + 4 + 2 * i] * f[i], a[16 * q + 4 + 2 * i + 1] * f[i]),
               pack_bf16(a[16 * q + 8 + 2 * i] * f[i], a[16 * q + 8 + 2 * i + 1] * f[i]), pack_bf16(a[16 * q + 12 + 2 * i] * f[i], a[16 * q + 12 + 2 * i + 1] * f[i]));
}

constexpr float SAFE_SUM = 1099511627776.0f;
template <int NJ>
__device__ __forceinline__ void row_max(const float (&s)[4 * NJ], float (&mx)[2]) {
#pragma unroll
    for (int i = 0; i < 2; i++) {
        float a = fmaxf(s[2 * i], s[2 * i + 1]), b = fmaxf(s[4 + 2 * i], s[4 + 2 * i + 1]);
#pragma unroll
        for (int j = 2; j < NJ; j += 2) {
            a = fmaxf(a, fmaxf(s[4 * j + 2 * i], s[4 * j + 2 * i + 1]));
            b = fmaxf(b, fmaxf(s[4 * j + 4 + 2 * i], s[4 * j + 4 + 2 * i + 1]));
        }
        a = fmaxf(a, b);
        a = fmaxf(a, __shfl_xor_sync(0xffffffffu, a, 1));
        mx[i] = fmaxf(a, __shfl_xor_sync(0xffffffffu, a, 2));
    }
}
template <int NJ, bool SHIFT>
__device__ __forceinline__ void exp_sum(float (&s)[4 * NJ], const float (&m)[2], float& l0, float& l1) {
#pragma unroll
    for (int j = 0; j < NJ; j++) {
#pragma unroll
        for (int e = 0; e < 4; e++) s[4 * j + e] = ex2(SHIFT ? s[4 * j + e] - m[e >> 1] : s[4 * j + e]);
        l0 += s[4 * j + 0] + s[4 * j + 1]; l1 += s[4 * j + 2] + s[4 * j + 3];
    }
}
__device__ __forceinline__ void recompute_scores(float (&s)[64], const uint32_t (&q)[32], uint32_t kaddr, const Ctx& c) {
    const int r = c.lane & 7, mat = c.lane >> 3;
    const uint32_t a0 = kaddr + (8 * (mat & 1) + r) * 64 + (((mat >> 1) ^ (r >> 1)) << 4);
#pragma unroll
    for (int i = 0; i < 64; i++) s[i] = 0.f;
#pragma unroll
    for (int jp = 0; jp < 8; jp++) {
#pragma unroll
        for (int k = 0; k < 8; k++) {
            asm volatile(
                "{\n.reg .b32 b0, b1, b2, b3;\n"
                "ldmatrix.sync.aligned.m8n8.x4.trans.shared.b16 {b0,b1,b2,b3}, [%12];\n"
                "mma.sync.aligned.m16n8k16.row.col.f32.bf16.bf16.f32 {%0,%1,%2,%3}, {%8,%9,%10,%11}, {b0,b1}, {%0,%1,%2,%3};\n"
                "mma.sync.aligned.m16n8k16.row.col.f32.bf16.bf16.f32 {%4,%5,%6,%7}, {%8,%9,%10,%11}, {b2,b3}, {%4,%5,%6,%7};\n}\n"
                : "+f"(s[8 * jp]), "+f"(s[8 * jp + 1]), "+f"(s[8 * jp + 2]), "+f"(s[8 * jp + 3]),
                  "+f"(s[8 * jp + 4]), "+f"(s[8 * jp + 5]), "+f"(s[8 * jp + 6]), "+f"(s[8 * jp + 7])
                : "r"(q[4 * k]), "r"(q[4 * k + 1]), "r"(q[4 * k + 2]), "r"(q[4 * k + 3]),
                  "r"((a0 ^ ((jp & 1) << 5)) + (jp >> 1) * 8192 + k * 1024) : "memory");
        }
    }
}
__device__ __forceinline__ int mask_lim(const Ctx& c) { return perm32(16 * c.warp + (c.lane >> 2)) - 8 * (c.lane & 3); }
template <int J0>
__device__ __forceinline__ void mask_diag(float (&s)[4 * J0 + 32], const Ctx& c) {
    const int lim = mask_lim(c);
    if (c.warp < 2) {
#pragma unroll
        for (int x = 0; x < 16; x++) {
            if (2 * (x >> 2) + (x & 1) - (x & 2) > lim) s[4 * J0 + x] = -INFINITY;
            s[4 * J0 + 16 + x] = -INFINITY;
        }
    } else {
#pragma unroll
        for (int x = 0; x < 16; x++)
            if (32 + 2 * (x >> 2) + (x & 1) - (x & 2) > lim) s[4 * J0 + 16 + x] = -INFINITY;
    }
}
__device__ __forceinline__ void mask_any(float (&s)[64], int hh, const Ctx& c) {
    const int lim = mask_lim(c) + 64 * hh;
#pragma unroll
    for (int x = 0; x < 64; x++)
        if (32 * (x >> 4) + 2 * ((x >> 2) & 3) + (x & 1) - (x & 2) > lim) s[x] = -INFINITY;
}
__device__ __forceinline__ void issue_pv(float (&o)[64], const uint32_t (&p)[32], uint32_t vaddr, int acc, int mode  ) {
    uint64_t d = mkdesc(vaddr, 16, 512, 2);
    if (mode == 0) {
        wg_fence();
#pragma unroll
        for (int k = 0; k < 8; k++)
            wgmma_rs_n128_ta0_tb0(o, p[4 * k], p[4 * k + 1], p[4 * k + 2], p[4 * k + 3], d + (k >> 1) * 512 + 2 * (k & 1), k ? 1 : acc);
        wg_commit();
    } else if (mode == 1) {
        wg_fence();
#pragma unroll
        for (int k = 0; k < 4; k++) wgmma_rs_n128_ta0_tb0(o, p[4 * k], p[4 * k + 1], p[4 * k + 2], p[4 * k + 3], d + (k >> 1) * 512 + 2 * (k & 1), k != 0);
        wg_commit();
    } else {
        wg_fence();
        wgmma_rs_n128_ta0_tb0(o, p[0], p[1], p[2], p[3], d, acc);
        wg_commit();
    }
}
__device__ __forceinline__ void issue_qk(float (&s)[64], const uint32_t (&q)[32], uint32_t kaddr) {
    uint64_t d = mkdesc(kaddr, 8192, 512, 2);
    wg_fence();
#pragma unroll
    for (int k = 0; k < 8; k++) wgmma_rs_n128_ta0_tb1(s, q[4 * k], q[4 * k + 1], q[4 * k + 2], q[4 * k + 3], d + 64 * k, k != 0);
    wg_commit();
}
__device__ __forceinline__ void issue_qk_half(float (&s32)[32], const uint32_t (&q)[32], uint32_t kaddr) {
    uint64_t d = mkdesc(kaddr, 8192, 512, 2);
    wg_fence();
#pragma unroll
    for (int k = 0; k < 8; k++) wgmma_rs_n64_ta0_tb1(s32, q[4 * k], q[4 * k + 1], q[4 * k + 2], q[4 * k + 3], d + 64 * k, k != 0);
    wg_commit();
}
__device__ __forceinline__ void row_inv(const float (&l)[2], float (&inv)[2]) {
#pragma unroll
    for (int i = 0; i < 2; i++) {
        float sum = l[i];
        sum += __shfl_xor_sync(0xffffffffu, sum, 1);
        sum += __shfl_xor_sync(0xffffffffu, sum, 2);
        inv[i] = rcp_fast(sum);
    }
}

__device__ __forceinline__ const unsigned char* xn_addr(int row, int col) {
    row = perm32(row);
    return g_xn + ((row >> 7) * 10 + (col >> 6)) * 16384 + (row & 127) * 128 + ((((col & 63) >> 3) ^ (row & 7)) << 4);
}
__device__ __forceinline__ void mma16816(float (&d)[4], uint32_t a0, uint32_t a1, uint32_t a2, uint32_t a3, uint32_t b0, uint32_t b1) {
    asm volatile("mma.sync.aligned.m16n8k16.row.col.f32.bf16.bf16.f32 {%0,%1,%2,%3}, {%4,%5,%6,%7}, {%8,%9}, {%0,%1,%2,%3};"
                 : "+f"(d[0]), "+f"(d[1]), "+f"(d[2]), "+f"(d[3]) : "r"(a0), "r"(a1), "r"(a2), "r"(a3), "r"(b0), "r"(b1));
}
__device__ __forceinline__ uint32_t lds32(uint32_t addr) { uint32_t v; asm volatile("ld.shared.u32 %0, [%1];" : "=r"(v) : "r"(addr)); return v; }

__device__ LNINL void ln_rows(const __nv_bfloat16* x, int row0, int lane, uint32_t wr_s) {
    const int hl = lane & 15, row = row0 + (lane >> 4);
    uint32_t v[20];
#pragma unroll
    for (int i = 0; i < 5; i++) {
        uint4 u;
        asm("ld.global.nc.L2::cache_hint.v4.b32 {%0,%1,%2,%3}, [%4], %5;" : "=r"(u.x), "=r"(u.y), "=r"(u.z), "=r"(u.w)
            : "l"(x + (size_t)row * DM + 128 * i + 8 * hl), "l"(policy(HM & 512)));
        v[4 * i] = u.x; v[4 * i + 1] = u.y; v[4 * i + 2] = u.z; v[4 * i + 3] = u.w;
    }
    float mean = 0.f, m2 = 0.f, acc2 = 0.f;
#pragma unroll
    for (int i = 0; i < 20; i++) { mean += bf_lo(v[i]); acc2 += bf_hi(v[i]); }
    mean = (mean + acc2) * (1.0f / 40);
    acc2 = 0.f;
#pragma unroll
    for (int i = 0; i < 20; i++) {
        float d0 = __uint_as_float(__byte_perm(v[i], 0, 0x1044)) - mean, d1 = __uint_as_float(__byte_perm(v[i], 0, 0x3244)) - mean;
        m2 = fmaf(d0, d0, m2); acc2 = fmaf(d1, d1, acc2);
    }
    m2 += acc2;
    acc2 = 0.f;
#pragma unroll
    for (int o = 1; o < 16; o <<= 1) {
        float mo = __shfl_xor_sync(0xffffffffu, mean, o), qo = __shfl_xor_sync(0xffffffffu, m2, o), d = mo - mean;
        m2 = fmaf(d * d, 20.0f * o, m2 + qo);
        mean = 0.5f * (mean + mo);
    }
    const uint32_t mb2 = pack_bf16(mean, mean);
    const float inv = rcp_fast(bf_round(sqrt_fast(bf_round(bf_round(m2 * (1.0f / DM)) + 1e-5f))));
    float dot = 0.f;
    unsigned char* xp = const_cast<unsigned char*>(xn_addr(row, 8 * hl));
#pragma unroll
    for (int i = 0; i < 5; i++) {
        uint32_t ww[4];
        asm volatile("ld.shared.v4.b32 {%0,%1,%2,%3}, [%4];" : "=r"(ww[0]), "=r"(ww[1]), "=r"(ww[2]), "=r"(ww[3]) : "r"(wr_s + 256 * i + 16 * hl) : "memory");
#pragma unroll
        for (int e = 0; e < 4; e++) {
            uint32_t d;
            asm("sub.rn.bf16x2 %0, %1, %2;" : "=r"(d) : "r"(v[4 * i + e]), "r"(mb2));
            d = pack_bf16(bf_lo(d) * inv, bf_hi(d) * inv);
            v[4 * i + e] = d;
            dot = fmaf(bf_lo(d), bf_lo(ww[e]), dot);
            acc2 = fmaf(bf_hi(d), bf_hi(ww[e]), acc2);
        }
        stg128(xp + i * 32768, v[4 * i], v[4 * i + 1], v[4 * i + 2], v[4 * i + 3]);
    }
    dot += acc2;
#pragma unroll
    for (int o = 8; o > 0; o >>= 1) dot += __shfl_xor_sync(0xffffffffu, dot, o);
    if (hl == 0) { g_router[row] = bf_round(dot); g_stats[row] = make_uint2(mb2, __float_as_uint(inv)); }
}

__device__ __forceinline__ void aux_cta(const CUtensorMap* tmG, const CUtensorMap* tmU, const CUtensorMap* tmD, unsigned char* sm, int a) {
    constexpr int STG = 57344, XS = 3 * STG, HS = XS + 8 * 1296, KEY = HS + 8 * 912, MI = KEY + 8192;
    const int tid = threadIdx.x, warp = __shfl_sync(0xffffffffu, tid >> 5, 0), lane = tid & 31;
    const uint32_t sb = smem_u32(sm);
    const uint32_t full = sb + MI, empty = sb + MI + 32;
    int* s_sel = reinterpret_cast<int*>(sm + MI + 64);
    float* s_r = reinterpret_cast<float*>(sm + MI + 96);
    volatile unsigned* s_misc = reinterpret_cast<volatile unsigned*>(sm + MI + 128);
    uint32_t* s_key = reinterpret_cast<uint32_t*>(sm + KEY);
    PROF_DECL(128 + a)
    PROF_GT(0);
    if (tid == 0) {
        for (int i = 0; i < 3; i++) { mbar_init(full + 8 * i, 1); mbar_init(empty + 8 * i, 10); }
        asm volatile("fence.mbarrier_init.release.cluster;" ::: "memory");
    }
    __syncthreads();
    if (warp == 11) {
        if (elect_one()) {
            int st = 0; uint32_t ph = 0;
#pragma unroll 1
            for (int s = 0; s < 34; s++) {
                mbar_wait(empty + 8 * st, ph ^ 1);
                const uint32_t dst = sb + st * STG, fb = full + 8 * st;
                if (s < 20) {
                    mbar_expect_tx(fb, 57344);
                    tma3d(dst, tmG, 0, 32 * s, 7 * a, fb);
                    tma3d(dst + 28672, tmU, 0, 32 * s, 7 * a, fb);
                } else {
                    mbar_expect_tx(fb, 40960);
                    tma3d(dst, tmD, 0, 448 * a + 32 * (s - 20), 0, fb);
                }
                if (s >= 3) {
#pragma unroll 1
                    for (int f = (s == 3 ? 4 : s + 6); f <= s + 6 && f < 34; f++) {
                        if (f < 20) { tma3d_prefetch(tmG, 0, 32 * f, 7 * a); tma3d_prefetch(tmU, 0, 32 * f, 7 * a); }
                        else tma3d_prefetch(tmD, 0, 448 * a + 32 * (f - 20), 0);
                    }
                }
                if (++st == 3) { st = 0; ph ^= 1; }
            }
        }
        return;
    }
    PROF_GT(49);
    if (warp == 10) return;
    if (tid < 8) {
        unsigned e = *reinterpret_cast<volatile unsigned*>(&g_epoch);
        if (tid == 0) s_misc[0] = e;
        flag_wait(flag_ptr(FL_LN + tid), (e + 1) * (32u + (tid >> 2)));
    }
    bar_sync(1, 320);
    PROF_GT(50);
    const unsigned ep = s_misc[0];
    auto top8 = [&](uint32_t (&key)[8]) {
        uint32_t mine = 0;
#pragma unroll 1
        for (int r = 0; r < TOPC; r++) {
            uint32_t best = 0;
#pragma unroll
            for (int i = 0; i < 8; i++) best = max(best, key[i]);
            best = __reduce_max_sync(0xffffffffu, best);
#pragma unroll
            for (int i = 0; i < 8; i++) if (key[i] == best) key[i] = 0;
            if (lane == r) mine = best;
        }
        return mine;
    };
#pragma unroll 1
    for (int pass = 0; pass < 2; pass++) {
        if (warp < (pass ? 1 : 8)) {
            uint32_t key[8];
#pragma unroll
            for (int i = 0; i < 8; i++) {
                if (pass == 0) {
                    int idx = warp * 256 + i * 32 + lane;
                    uint32_t b = __float_as_uint(__ldcg(g_router + idx)) >> 16;
                    b = (b & 0x8000u) ? (~b & 0xffffu) : (b | 0x8000u);
                    key[i] = (b << 16) | (uint32_t)(0xffff - idx);
                } else key[i] = i < 2 ? s_key[i * 32 + lane] : 0u;
            }
            uint32_t best = top8(key);
            if (lane < TOPC) {
                if (pass == 0) s_key[warp * 8 + lane] = best;
                else {
                    uint32_t b = best >> 16;
                    b = (b & 0x8000u) ? (b & 0x7fffu) : (~b & 0xffffu);
                    s_sel[lane] = 0xffff - (int)(best & 0xffffu);
                    s_r[lane] = bf_round(rcp_fast(1.0f + __expf(fminf(-__uint_as_float(b << 16), 80.f))));
                }
            }
        }
        bar_sync(1, 320);
    }
#pragma unroll 1
    for (int it = 0; it < 2; it++) {
        int i = tid + it * 320, tk = i / 80, ch = i % 80;
        *reinterpret_cast<uint4*>(sm + XS + tk * 1296 + ch * 16) = __ldcg(reinterpret_cast<const uint4*>(xn_addr(s_sel[tk], ch * 8)));
    }
    bar_sync(1, 320);
    PROF_GT(51);
    const int g = lane >> 2, t = lane & 3;
    const uint32_t woff = warp * 4096 + (8 * (lane >> 4) + (lane & 7)) * 128 + ((((lane >> 3) & 1) ^ (lane & 7)) << 4);
    int st = 0; uint32_t ph = 0;
    float ga[4][4], ua[4][4];
#pragma unroll
    for (int i = 0; i < 4; i++)
#pragma unroll
        for (int e = 0; e < 4; e++) { ga[i][e] = 0.f; ua[i][e] = 0.f; }
#pragma unroll 1
    for (int s = 0; s < 34; s++) {
        if (s == 20) {
            if (warp < 7) {
#pragma unroll 1
                for (int i = 0; i < 4; i++) {
#pragma unroll
                    for (int e = 0; e < 4; e++) {
                        float gv = bf_round(ga[0][e]), uv = bf_round(ua[0][e]);
                        float sg = bf_round(gv * rcp_fast(1.0f + __expf(fminf(-gv, 80.f))));
                        int f = warp * 64 + i * 16 + g + 8 * (e >> 1), tk = 2 * t + (e & 1);
                        *reinterpret_cast<__nv_bfloat16*>(sm + HS + tk * 912 + f * 2) = __float2bfloat16_rn(sg * uv);
                        ga[0][e] = ga[1][e]; ga[1][e] = ga[2][e]; ga[2][e] = ga[3][e]; ga[3][e] = 0.f;
                        ua[0][e] = ua[1][e]; ua[1][e] = ua[2][e]; ua[2][e] = ua[3][e];
                    }
                }
            }
            bar_sync(1, 320);
            PROF_GT(52);
        }
        mbar_wait(full + 8 * st, ph);
        if (s >= 20 || warp < 7) {
#pragma unroll
            for (int kk = 0; kk < 2; kk++) {
                uint32_t xb = sb + (s < 20 ? XS + g * 1296 + s * 64 : HS + g * 912 + (s - 20) * 64) + 32 * kk + 4 * t;
                uint32_t b0 = lds32(xb), b1 = lds32(xb + 16);
                uint32_t wa = sb + st * STG + woff + kk * 2048;
#pragma unroll
                for (int i = 0; i < 4; i++) {
                    uint32_t a0, a1, a2, a3;
                    ldsm4t(a0, a1, a2, a3, wa ^ (i << 5));
                    mma16816(ga[i], a0, a1, a2, a3, b0, b1);
                    if (s < 20) {
                        ldsm4t(a0, a1, a2, a3, (wa ^ (i << 5)) + 28672);
                        mma16816(ua[i], a0, a1, a2, a3, b0, b1);
                    }
                }
            }
        }
        asm volatile("fence.proxy.async.shared::cta;" ::: "memory");
        __syncwarp();
        if (lane == 0) mbar_arrive(empty + 8 * st);
        if (++st == 3) { st = 0; ph ^= 1; }
    }
#pragma unroll
    for (int i = 0; i < 4; i++)
#pragma unroll
        for (int e = 0; e < 4; e += 2)
            *reinterpret_cast<float2*>(g_moe_part + (a * DM + warp * 64 + i * 16 + g + 4 * e) * 8 + 2 * t) = make_float2(ga[i][e], ga[i][e + 1]);
    bar_sync(1, 320);
    if (tid == 0) {
        __threadfence();
        unsigned old = atomicAdd(flag_ptr(FL_MOE_CNT), 1u);
        s_misc[1] = (old == ep * 4u + 3u);
        __threadfence();
    }
    bar_sync(1, 320);
    PROF_GT(53);
    if (s_misc[1]) {
        const float4* pp = reinterpret_cast<const float4*>(g_moe_part);
#pragma unroll 1
        for (int i = tid; i < DM * 2; i += 320) {
            float4 v0 = __ldcg(pp + i), v1 = __ldcg(pp + DM * 2 + i), v2 = __ldcg(pp + DM * 4 + i), v3 = __ldcg(pp + DM * 6 + i);
            float y[4] = {v0.x + v1.x + v2.x + v3.x, v0.y + v1.y + v2.y + v3.y, v0.z + v1.z + v2.z + v3.z, v0.w + v1.w + v2.w + v3.w};
#pragma unroll
            for (int e = 0; e < 4; e++) {
                int col = i >> 1, tk = (i & 1) * 4 + e;
                float upd = bf_round(bf_round(y[e]) * s_r[tk]);
                float xn = __bfloat162float(*reinterpret_cast<const __nv_bfloat16*>(sm + XS + tk * 1296 + col * 2));
                g_brow[tk * DM + col] = __float2bfloat16_rn(xn + upd);
            }
        }
        if (tid < TOPC) g_sel[tid] = s_sel[tid];
        bar_sync(1, 320);
        if (tid == 0) {
            flag_signal(flag_ptr(FL_MOE_DONE));
            *reinterpret_cast<volatile unsigned*>(&g_epoch) = ep + 1;
        }
        PROF_GT(54);
    }
}

__global__ void __cluster_dims__(2, 1, 1) __launch_bounds__(384, 1)
fused_kernel(const __grid_constant__ CUtensorMap tmC, const __grid_constant__ CUtensorMap tmWk, const __grid_constant__ CUtensorMap tmWv,
             const __grid_constant__ CUtensorMap tmWq, const __grid_constant__ CUtensorMap tmWo,
             const __grid_constant__ CUtensorMap tmG, const __grid_constant__ CUtensorMap tmU, const __grid_constant__ CUtensorMap tmD, const Params P) {
    extern __shared__ __align__(1024) unsigned char smem_raw[];
    const uint32_t ring = smem_u32(smem_raw);
    const uint32_t misc = ring + RING_BYTES;
    const int tid = threadIdx.x;
    const int rank = blockIdx.x & 1;
    uint32_t smid, nsm;
    asm("mov.u32 %0, %%smid;" : "=r"(smid));
    asm("mov.u32 %0, %%nsmid;" : "=r"(nsm));
    if (nsm != 132) smid = blockIdx.x;
    auto role_of = [](int tpc) {
        return tpc < 32 ? (tpc & 7) * 8 + (tpc >> 3) : tpc < 60 ? (1 + (tpc - 32) % 7) * 8 + 4 + (tpc - 32) / 7 : tpc < 64 ? tpc - 56 : tpc;
    };
    int mc = role_of(smid >> 1);
    PROF_DECL(mc * 2 + rank)
    PROF_GT(0); PROF_EV(1);

    auto prefetch_w = [&](int ch) {
        const int i = tid - 128;
        asm volatile("prefetch.global.L2 [%0];" ::"l"((rank ? P.wv : P.wk) + (size_t)(ch * 128 + (mc & 3) * 32 + (i >> 3)) * 4096 + (mc >> 2) * 256 + (i & 7) * 16));
    };
    if (tid >= 128 && mc < 64) {
        if (tid < 256) asm volatile("prefetch.global.L2 [%0];" ::"l"(P.c + (size_t)((12 + (mc & 3)) * 128 + ((mc >> 2) * 2 + rank) * 4) * DC + (tid - 128) * 16));
        prefetch_w(0);
    }
    auto load_w0 = [&]() {
        const CUtensorMap* tw = rank ? &tmWv : &tmWk;
        mbar_expect_tx(misc + BAR_FULL + 8 * slot_of(0), SLOT_BYTES);
        tma2d(ring + slot_of(0) * SLOT_BYTES, tw, (mc >> 2) * 256, 0, misc + BAR_FULL + 8 * slot_of(0), policy(HM & 1));
        tma2d(ring + slot_of(0) * SLOT_BYTES + 16384, tw, (mc >> 2) * 256 + 64, 0, misc + BAR_FULL + 8 * slot_of(0), policy(HM & 1));
    };
    if (tid == 0) {
#pragma unroll
        for (int i = 0; i < NSLOT; i++) mbar_init(misc + BAR_FULL + 8 * i, 1);
#pragma unroll
        for (int i = 0; i < E0; i++) mbar_arrive(misc + BAR_FULL + 8 * i);
        asm volatile("fence.mbarrier_init.release.cluster;" ::: "memory");
        if (mc < 64) load_w0();
    }
    if (tid == 160) {
        asm volatile("st.shared.u32 [%0], %1;" ::"r"(misc + MISC_SMID), "r"(smid) : "memory");
        asm volatile("fence.release.sync_restrict::shared::cta.cluster;" ::: "memory");
    }
    if (tid == 32) {
        asm volatile("prefetch.tensormap [%0];" ::"l"(&tmC) : "memory");
#pragma unroll
        for (int i = 0; i < NSLOT; i++) mbar_init(misc + BAR_EMPTY + 8 * i, 16);
#pragma unroll
        for (int i = 0; i < E0; i++) mbar_arrive_cluster(misc + BAR_EMPTY + 8 * i, 16);
        asm volatile("fence.mbarrier_init.release.cluster;" ::: "memory");
    }
    if (tid == 64) {
#pragma unroll
        for (int i = 0; i < NST3; i++) { mbar_init(misc + BAR_FULL3 + 8 * i, 1); mbar_init(misc + BAR_EMPTY3 + 8 * i, 16); }
#pragma unroll
        for (int i = 0; i < 4; i++) mbar_init(misc + BAR_LN + 8 * i, 2);
        mbar_init(misc + BAR_PROG, 1); mbar_init(misc + BAR_PROG + 8, 1); mbar_init(misc + BAR_PROG + 16, 1);
        asm volatile("fence.mbarrier_init.release.cluster;" ::: "memory");
    }
    if (tid == 96) {
#pragma unroll
        for (int i = 0; i < 34; i++) mbar_init(misc + BAR_DEP + 8 * i, 1);
    }
    if (tid == 128) {
#pragma unroll
        for (int i = 0; i < 32; i++) mbar_init(misc + BAR_EV + 8 * i, 4);
    }
    __syncthreads();
    asm volatile("barrier.cluster.arrive.relaxed.aligned;\nbarrier.cluster.wait.aligned;" ::: "memory");
    {
        uint32_t peer;
        asm volatile("ld.shared::cluster.u32 %0, [%1];" : "=r"(peer) : "r"(mapa(misc + MISC_SMID, rank ^ 1)) : "memory");
        if ((__shfl_sync(0xffffffffu, peer, 0) ^ smid) != 1) {
            if (tid == 0) {
                const unsigned ep1 = *reinterpret_cast<volatile unsigned*>(&g_epoch) + 1;
                if ((smid & 1) == 0) atomicExch(g_roleq + 2 + (atomicAdd(g_roleq, 1u) & 127), (ep1 << 8) | (smid >> 1));
                if (rank == 0) {
                    unsigned* slot = g_roleq + 2 + (atomicAdd(g_roleq + 1, 1u) & 127);
                    unsigned v = 0;
                    for (int spin = 0; spin < 4000000 && ((v = atomicAdd(slot, 0u)) >> 8) != (ep1 & 0xffffffu); spin++) {}
                    asm volatile("st.shared::cluster.u32 [%0], %1;" ::"r"(mapa(misc + MISC_SMID + 4, 0)), "r"(v & 255) : "memory");
                    asm volatile("st.shared::cluster.u32 [%0], %1;" ::"r"(mapa(misc + MISC_SMID + 4, 1)), "r"(v & 255) : "memory");
                }
                if (mc < 64) {
                    mbar_wait(misc + BAR_FULL + 8 * slot_of(0), 0);
                    asm volatile("mbarrier.inval.shared::cta.b64 [%0];" ::"r"(misc + BAR_FULL + 8 * slot_of(0)) : "memory");
                    mbar_init(misc + BAR_FULL + 8 * slot_of(0), 1);
                    asm volatile("fence.mbarrier_init.release.cluster;" ::: "memory");
                }
            }
            __syncwarp();
            asm volatile("barrier.cluster.arrive.aligned;\nbarrier.cluster.wait.aligned;" ::: "memory");
            mc = role_of(__shfl_sync(0xffffffffu, lds32(misc + MISC_SMID + 4), 0));
            if (tid == 0 && mc < 64) load_w0();
            __syncwarp();
        }
    }
    const int cta = mc * 2 + rank;
    const bool aux = mc >= 64;
    const int team = mc >> 2, k = mc & 3;
    const int u3 = (mc >> 4) * 2 + (team & 1), s3 = k, kap = (mc >> 3) & 1;
    const int partner = cta ^ 16;
    if (tid >= 128 && !aux) prefetch_w(1);
    if (tid == 256 && !aux) {
        const CUtensorMap* tw = rank ? &tmWv : &tmWk;
#pragma unroll
        for (int e = 1; e < NSLOT; e++) {
            const uint32_t fb = misc + BAR_FULL + 8 * slot_of(e), dst = ring + slot_of(e) * SLOT_BYTES;
            mbar_expect_tx(fb, SLOT_BYTES);
            if (e & 1) tma2d_mc(dst + rank * 16384, &tmC, (e >> 1) * 128 + rank * 64, (12 + k) * 128, fb, policy(false));
            else { tma2d(dst, tw, team * 256, e * 64, fb, policy(false)); tma2d(dst + 16384, tw, team * 256 + 64, e * 64, fb, policy(false)); }
        }
    }
    PROF_EV(5);
    const int wg = __shfl_sync(0xffffffffu, tid >> 7, 0);

    if (wg == 0 || aux) {
        asm volatile("setmaxnreg.dec.sync.aligned.u32 40;");
        const int warp = __shfl_sync(0xffffffffu, tid >> 5, 0), lane = tid & 31;
        if (warp == 0 && !aux) {
            const bool lead = elect_one();
            Cur c = cur_at(NSLOT);
            uint32_t dst, fb;
            auto acquire = [&]() {
                mbar_wait_sleep(misc + BAR_EMPTY + 8 * c.slot, c.ph ^ 1);
                fb = misc + BAR_FULL + 8 * c.slot; dst = ring + c.slot * SLOT_BYTES;
                if (lead) mbar_expect_tx(fb, SLOT_BYTES);
                c.adv();
            };
            auto load_w = [&](const CUtensorMap* tm, int col, int row, bool stream) {
                acquire();
                if (lead) { tma2d(dst, tm, col, row, fb, policy(stream)); tma2d(dst + 16384, tm, col + 64, row, fb, policy(stream)); }
            };
            auto load_half = [&](const unsigned char* src, bool stream) {
                acquire();
                if (lead) bulk_load_mc(dst + rank * 16384, src, 16384, fb, policy(stream));
            };
            auto dep_wait = [&](int d) { mbar_wait_sleep(misc + BAR_DEP + 8 * d, 0); fence_async_global(); };
            auto op_prefetch = [&](int i) {
                const int head = op_head(i, kap);
                l2_prefetch(reinterpret_cast<const unsigned char*>(P.wo) + head * 163840 + (u3 * 8 + s3 * 2 + rank) * 2560, 2560);
                if (i < 8) l2_prefetch(g_ctx + (size_t)(head * 32 + 4 * u3 + 2 * rank) * 16384 + s3 * 8192, 8192);
            };
            __nanosleep(CDELAY);
            if (lead) l2_prefetch(reinterpret_cast<const unsigned char*>(P.c) + (size_t)cta * 12288, 12288);
            const CUtensorMap* tw = rank ? &tmWv : &tmWk;
            const unsigned char* Kh = g_K + (size_t)team * 32 * 16384 + rank * 16384;
            const unsigned char* Vh = g_V + (size_t)team * 32 * 16384 + rank * 16384;
#pragma unroll 1
            for (int v = 0; v < 2; v++) {
                const int h = 2 * team + v;
#pragma unroll 1
                for (int i = v ? 0 : 3; i < 16; i++) {
                    if (i < 4 && v) load_w(tw, h * 128, i * 128, HM & 1);
                    if (v && i == 3 && lead) mbar_arrive(misc + BAR_PROG + 8);
                    if (v && (i & 7) == 3) dep_wait(D_WAR + (i >> 3));
                    acquire();
                    if (lead) tma2d_mc(dst + rank * 16384, &tmC, (i & 3) * 128 + rank * 64, (12 - (i & 12) + k) * 128, fb, policy(HM & 2));
                    if (i == 8 && lead) {
                        tma2d_prefetch(&tmWq, h * 128 + rank * 64, k * 64); tma2d_prefetch(&tmWq, h * 128 + rank * 64, k * 64 + 256);
                        if (k < 2) tma2d_prefetch(&tmWq, h * 128 + rank * 64, k * 64 + 512);
                        if (v) l2_prefetch(g_xn + 8 * 163840 + cta * 10240, 10240);
                    }
                }
                int togo = v ? PF_START : 11;
#pragma unroll 1
                for (int r = 0; r < 2; r++) {
                    const int p = r ? k : 7 - k, n = 2 * p + 1;
                    if (v == 0) dep_wait(D_LN + r);
                    const int g0 = r ? rank ^ SWAPT : 3 - rank, g1 = 3 - g0;
                    const unsigned char* x0 = g_xn + (2 * p + (g0 >> 1)) * 163840 + (g0 & 1) * 8192;
                    const unsigned char* x1 = g_xn + (2 * p + (g1 >> 1)) * 163840 + (g1 & 1) * 8192;
#pragma unroll 1
                    for (int kc = 0; kc < 10; kc++) {
                        acquire();
                        if (lead) {
                            tma2d_mc(dst + 16384 + rank * 8192, &tmWq, h * 128 + rank * 64, kc * 64, fb, policy(false));
                            bulk_load(dst, x0 + kc * 16384, 8192, fb, policy(false));
                            bulk_load(dst + 8192, x1 + kc * 16384, 8192, fb, policy(false));
                        }
                    }
                    if (r == 0) dep_wait(D_KV + 3 * v);
                    load_half(Kh + n * 32768, HM & 16);
#pragma unroll 1
                    for (int j = n - 1; j >= 0; j--) {
                        if (r == 0 && (j == 7 || j == 3)) dep_wait(D_KV + 3 * v + 2 - (j >> 2));
                        load_half(Kh + j * 32768, HM & 16); load_half(Vh + (j + 1) * 32768, HM & 16);
                        if (v == 0 && r == 0 && j == 3 && lead) mbar_arrive(misc + BAR_PROG);
                        --togo;
                        if (v == 0 && togo == 0 && lead) {
                            tma2d_prefetch(tw, h * 128 + 128, k * 128); tma2d_prefetch(tw, h * 128 + 192, k * 128);
                            l2_prefetch(reinterpret_cast<const unsigned char*>(P.c) + (size_t)cta * 16384, 16384);
                        }
                        if (v && togo <= 0 && togo > -OP_PF && lead) op_prefetch(-togo);
                    }
                    load_half(Vh, HM & 16);
                }
            }
            mbar_wait_sleep(misc + BAR_EMPTY + 8 * c.slot, c.ph ^ 1); c.adv();
            int st = 0; uint32_t ph3 = 0;
#pragma unroll 1
            for (int i = 0; i < 32; i++) {
                const int head = op_head(i >> 1, kap);
                if ((i & 1) == 0) dep_wait(D_CTX + (i >> 1));
                if (i < NST3) { mbar_wait_sleep(misc + BAR_EMPTY + 8 * c.slot, c.ph ^ 1); c.adv(); }
                else mbar_wait_sleep(misc + BAR_EMPTY3 + 8 * st, ph3 ^ 1);
                fb = misc + BAR_FULL3 + 8 * st; dst = ring + st * ST3_BYTES;
                if (i == LATE_AT && lead) mbar_arrive(misc + BAR_PROG + 16);
                if (lead) {
                    mbar_expect_tx(fb, ST3_BYTES);
                    const unsigned char* src = g_ctx + (size_t)(head * 32 + 4 * u3 + 2 * rank) * 16384 + (i & 1) * 8192;
                    bulk_load(dst, src, 8192, fb, policy(HM & 32));
                    bulk_load(dst + 8192, src + 16384, 8192, fb, policy(HM & 32));
                    tma3d_mc(dst + 16384 + rank * 10240, &tmWo, 0, head * 128 + (i & 1) * 64 + rank * 32, 5 * s3, fb, policy(HM & 32));
                    if ((i & 1) && (i >> 1) + OP_PF < 16) op_prefetch((i >> 1) + OP_PF);
                }
                if (++st == NST3) { st = 0; ph3 ^= 1; }
            }
        } else {
        if (warp >= 1 && warp <= 3 && lane < 27 && (warp - 1) * 27 + lane < 80) {
            const int ch = (warp - 1) * 27 + lane;
            uint4 u = __ldg(reinterpret_cast<const uint4*>(P.wr) + ch);
            asm volatile("st.shared.v4.b32 [%0], {%1,%2,%3,%4};" ::"r"(misc + MISC_WR + 16 * ch), "r"(u.x), "r"(u.y), "r"(u.z), "r"(u.w) : "memory");
        }
        if (aux) __nanosleep(AUXDELAY);
        bar_sync(3, aux ? 384 : 96);
        const int nln = aux ? (warp < 8 ? 3 : 2) : (warp == 3 ? 1 : 3), rstep = aux ? 24 : 2;
        int lrow = aux ? (cta - 124) * 256 + 192 + 2 * warp : (4 + (cta >> 5)) * 256 + (cta & 31) * 6 + (warp - 1) * 2;
        int lnext = aux ? lrow + 24 : (cta >> 5) * 256 + (cta & 31) * 8 + (warp - 1) * 4;
#pragma unroll 1
        for (int t = 0; t < nln; t++) {
            if (t + 1 < nln) {
#pragma unroll
                for (int i = 0; i < 3; i++)
                    if (i * 32 + lane < 80) asm volatile("prefetch.global.L2 [%0];" ::"l"(P.x + (size_t)lnext * DM + (i * 32 + lane) * 16));
            }
            ln_rows(P.x, lrow, lane, misc + MISC_WR);
            lrow = lnext; lnext += rstep;
            __syncwarp();
            if (lane == 0 && warp < 3 && t != 1 && !aux) mbar_arrive(misc + BAR_LN + 4 * t);
        }
        if (aux) {
            bar_sync(3, 384);
            if (tid == 320) flag_signal(flag_ptr(FL_LN + cta - 124));
            __syncwarp();
            asm volatile("setmaxnreg.inc.sync.aligned.u32 128;");
            aux_cta(&tmG, &tmU, &tmD, smem_raw, cta - 128);
        } else
        if (warp == 3) {
            const unsigned ep1 = *reinterpret_cast<volatile unsigned*>(&g_epoch) + 1;
            if (lane == 0) {
                asm volatile("st.shared.u32 [%0], %1;" ::"r"(misc + MISC_EPOCH), "r"(ep1) : "memory");
                mbar_wait(misc + BAR_LN, 0);
                flag_signal(flag_ptr(FL_LN + 4 + (cta >> 5)));
                flag_wait(flag_ptr(FL_LN + 7 - k), ep1 * 33u);
                mbar_arrive(misc + BAR_DEP + 8 * D_LN);
#pragma unroll 1
                for (int v = 0; v < 2; v++) {
#pragma unroll 1
                    for (int i = 3 * v; i < 3 * v + 3; i++) {
                        mbar_wait(misc + BAR_EV + 8 * (16 + EV_KV + i), 0);
                        if (v == 0) {
                            mbar_wait(misc + BAR_EV + 8 * (EV_KV + i), 0);
                            asm volatile("red.release.gpu.global.add.u32 [%0], 2;" ::"l"(flag_ptr(FL_KV + team * 8 + i)) : "memory");
                        }
                        flag_wait(flag_ptr(FL_KV + team * 8 + i), ep1 * 16u);
                        mbar_arrive(misc + BAR_DEP + 8 * (D_KV + i));
                    }
                    if (v) break;
                    mbar_wait(misc + BAR_LN + 8, 0);
                    flag_signal(flag_ptr(FL_LN + (cta >> 5)));
                    flag_wait(flag_ptr(FL_LN + k), ep1 * 32u);
                    mbar_arrive(misc + BAR_DEP + 8 * (D_LN + 1));
#pragma unroll 1
                    for (int i = 0; i < 2; i++) {
                        mbar_wait(misc + BAR_PROG + 8 * i, 0);
                        flag_signal(flag_ptr(FL_WAR + 2 * team + i));
                        flag_wait(flag_ptr(FL_WAR + 2 * team + i), ep1 * 8u);
                        mbar_arrive(misc + BAR_DEP + 8 * (D_WAR + i));
                    }
                }
                flag_wait(flag_ptr(FL_MOE_DONE), ep1);
                int4 s0 = __ldcg(reinterpret_cast<const int4*>(g_sel)), s1 = __ldcg(reinterpret_cast<const int4*>(g_sel) + 1);
                asm volatile("st.shared.v4.u32 [%0], {%1,%2,%3,%4};" ::"r"(misc + MISC_SEL), "r"(s0.x), "r"(s0.y), "r"(s0.z), "r"(s0.w) : "memory");
                asm volatile("st.shared.v4.u32 [%0], {%1,%2,%3,%4};" ::"r"(misc + MISC_SEL + 16), "r"(s1.x), "r"(s1.y), "r"(s1.z), "r"(s1.w) : "memory");
                mbar_arrive(misc + BAR_SEL);
            }
            __syncwarp();
            const unsigned* cf = flag_ptr(FL_CTX + op_head(lane & 15, kap) * 8 + u3);
#pragma unroll 1
            for (int half = 0; half < 2; half++) {
                if (half) mbar_wait(misc + BAR_EV + 8 * (EV_CTX + 3), 0);
                bool done = (lane >> 3) != half;
                for (int spin = 0; spin < 4000000; spin++) {
                    if (!done) {
                        unsigned v;
                        asm volatile("ld.acquire.gpu.global.u32 %0, [%1];" : "=r"(v) : "l"(cf) : "memory");
                        if ((int)(v - ep1 * 4u) >= 0) { mbar_arrive(misc + BAR_DEP + 8 * (D_CTX + lane)); done = true; }
                    }
                    if (__all_sync(0xffffffffu, done)) break;
                    __nanosleep(64);
                }
            }
        } else {
            const int w = warp - 1;
            if (lane == 0) {
                const uint32_t eb = misc + BAR_EV + w * 128;
#pragma unroll 1
                for (int i = 0; i < 7; i++) {
                    const bool kv = i >= 2 && i < 5;
                    const int ci = i < 2 ? i : i - 3;
                    mbar_wait(eb + 8 * (kv ? EV_KV + i + 1 : EV_CTX + ci), 0);
                    if (i == 1) {
                        asm volatile("cp.async.bulk.global.shared::cta.bulk_group [%0], [%1], 16384;"
                                     ::"l"(g_ctx + (size_t)(2 * team * 32 + 4 * k + (w ? 3 - (rank ^ SWAPT) : rank ^ SWAPT)) * 16384),
                                       "r"(ring + slot_of(78) * SLOT_BYTES + w * 16384) : "memory");
                        asm volatile("cp.async.bulk.commit_group;" ::: "memory");
                        asm volatile("cp.async.bulk.wait_group.read 0;" ::: "memory");
                        mbar_arrive_cluster(mapa(misc + BAR_EMPTY + 8 * slot_of(78), 0), 4);
                        mbar_arrive_cluster(mapa(misc + BAR_EMPTY + 8 * slot_of(78), 1), 4);
                        asm volatile("cp.async.bulk.wait_group 0;" ::: "memory");
                        fence_async_global();
                    }
                    flag_signal(flag_ptr(kv ? FL_KV + team * 8 + i + 1 : FL_CTX + (2 * team + (ci >> 1)) * 8 + ((ci & 1) ? k : 7 - k)));
                }
            }
            __syncwarp();
            mbar_wait(misc + BAR_PROG + 16, 0);
            const int row = (2 * u3 + rank) * 128 + 64 * w + perm32(16 * (lane >> 3) + 8 * kap + (lane & 7));
#pragma unroll
            for (int i = 0; i < 10; i++) asm volatile("prefetch.global.L2 [%0];" ::"l"(P.x + (size_t)row * DM + 160 * s3 + 16 * i));
            asm volatile("prefetch.global.L2 [%0];" ::"l"(g_stats + row));
            mbar_wait(misc + BAR_EV + w * 128 + 8 * EV_END, 0);
        }
        }
    } else {
        asm volatile("setmaxnreg.inc.sync.aligned.u32 232;");
        Ctx c;
        c.ring = ring; c.misc = misc; c.w = wg - 1; c.warp = __shfl_sync(0xffffffffu, (tid >> 5) & 3, 0); c.lane = tid & 31;
        c.rel = mapa(misc, tid & 1);
        const int w = c.w;
        if (w == 1) bar_arrive(1, 256);
        prefetch_w(2); prefetch_w(3);
        Cur cur = cur_at(0);
        float o[64], inv[2];
        unsigned char* out[2];
        uint32_t wf[128];
        Cur cw = cur;
        auto load_wchunk = [&](auto CH) {
            constexpr int ch = decltype(CH)::value;
            mbar_wait_hot(misc + BAR_FULL + 8 * cw.slot, cw.ph);
            const uint32_t z = load_afrag<8, 32 * ch>(wf, ring + cw.slot * SLOT_BYTES + w * 16384, c);
            release(c, BAR_EMPTY + 8 * cw.slot + z, 1);
            cw.adv(); cw.adv();
        };
#pragma unroll
        for (int i = 32; i < 64; i++) wf[i] = 0u;
        load_wchunk(IC<0>{});
#pragma unroll 1
        for (int v = 0; v < 2; v++) {
        {
            float (&acc)[64] = o;
#pragma unroll
            for (int i = 64; i < 128; i++) wf[i] = 0u;
            cur.adv();
            inv[0] = inv[1] = rank ? 1.0f : SM_SCALE;
            PROF_EV(2); PROF_GT(60);
#pragma unroll 1
            for (int t = 0; t < 4; t++) {
                uint32_t last = 0;
                token_wait(w);
                PROF_EV(10);
                undef_regs(acc);
                auto chunk = [&](auto CH) {
                    constexpr int ch = decltype(CH)::value;
                    mbar_wait_hot(misc + BAR_FULL + 8 * cur.slot, cur.ph);
                    if (t == 0) { PROF_EV(12 + ch); }
                    uint64_t d = mkdesc(ring + cur.slot * SLOT_BYTES, 16, 1024, 1);
                    wg_fence();
#pragma unroll
                    for (int ks = 0; ks < 8; ks++)
                        wgmma_rs_n128_ta0_tb0(acc, wf[32 * ch + 4 * ks], wf[32 * ch + 4 * ks + 1], wf[32 * ch + 4 * ks + 2], wf[32 * ch + 4 * ks + 3],
                                              d + (ks >> 2) * 1024 + (ks & 3) * 2, (ch | ks) != 0);
                    wg_commit();
                    if (ch == 3 || (ch < 2 && t == 0)) token_pass(w);
                    if constexpr (ch == 0) { if (t == 0) { if (v) load_wchunk(IC<2>{}); else load_wchunk(IC<1>{}); } }
                    if constexpr (ch == 1) { if (t == 0 && !v) load_wchunk(IC<2>{}); }
                    if constexpr (ch == 2) { if (t == 0 && !(w | v)) load_wchunk(IC<3>{}); }
                    if (ch > 0) { wg_wait<1>(); release(c, BAR_EMPTY + 8 * last, 1); }
                    last = cur.slot;
                    cur.adv();
                    if (ch < 3 && t == 0) cur.adv();
                    if constexpr (ch == 1) { if (t == 0 && (w | v)) load_wchunk(IC<3>{}); }
                    if (ch < 2 && t == 0) token_wait(w);
                };
                chunk(IC<0>{}); chunk(IC<1>{}); chunk(IC<2>{}); chunk(IC<3>{});
                wg_wait<0>();
                release(c, BAR_EMPTY + 8 * last, 1);
                PROF_EV(11);
                fence_regs(acc);
                tile_out(out, (rank ? g_V : g_K) + (size_t)(team * 32 + 24 + 2 * k - 8 * t) * 16384, 64 * w, rank, c);
                if (DEFER && t == 3 && w) break;
#pragma unroll
                for (int i = 0; i < 4; i++) store_pair(acc, i, out, 8192, inv);
                if (t) signal_event(c, EV_KV + 3 * v + t - 1);
            }
            PROF_EV(61); PROF_GT(62);
        }
        PROF_EV(63); PROF_GT(64);
        {
            uint32_t q[32], p[32];
            float m[2], l[2];
#pragma unroll
            for (int i = 0; i < 32; i++) p[i] = 0u;
            l[0] = l[1] = 1.f;
            int pv_acc = 0, pv_mode = 2;
#pragma unroll 1
            for (int r = 0; r < 2; r++) {
                const int heavy = 1 ^ r ^ w;
                const int half = 1 ^ heavy ^ rank ^ (r & SWAPT);
                int left = 2 * (r ? k : 7 - k) + 1 + heavy;
                Cur ck, cv = cur;
                {
                    float s[64];
                    if (r) cur.adv();
                    mbar_wait_hot(misc + BAR_FULL + 8 * cv.slot, cv.ph);
                    token_wait(w);
                    PROF_EV(20);
                    issue_pv(o, p, ring + cv.slot * SLOT_BYTES, 1, r ? 0 : 2);
                    undef_regs(s);
                    uint32_t prev;
                    auto qchunk = [&](int acc) {
                        mbar_wait_hot(misc + BAR_FULL + 8 * cur.slot, cur.ph);
                        const uint64_t da = mkdesc(ring + cur.slot * SLOT_BYTES + w * 8192, 16, 1024, 1);
                        const uint64_t db = mkdesc(ring + cur.slot * SLOT_BYTES + 16384, 8192, 1024, 1);
                        wg_fence();
#pragma unroll
                        for (int ks = 0; ks < 4; ks++) wgmma_ss_n128_ta0_tb1(s, da + 2 * ks, db + 128 * ks, ks ? 1 : acc);
                        wg_commit();
                    };
                    qchunk(0);
                    prev = cur.slot; cur.adv();
                    token_pass(w);
                    if (r) {
                        row_inv(l, inv);
                        tile_out(out, g_ctx + (size_t)((2 * team + v) * 32 + 4 * (7 - k) + (w ? rank : 3 - rank)) * 16384, 0, 0, c);
                    }
                    const int epi = r | (w & DEFER), hs = r ? 4096 : 8192;
                    const int hold = heavy ? -10 : half ? HOLD0 : 8;
#pragma unroll
                    for (int kc = 1; kc < 10; kc++) {
                        if (HOLD0 && kc >= HOLD0 && (kc == hold || kc == hold + 2)) token_wait(w);
                        qchunk(1);
                        if (HOLD0 && kc > HOLD0 && kc == hold + 1) token_pass(w);
                        if (HOLD0 && kc == 9 && heavy) { token_wait(w); token_pass(w); }
                        wg_wait<1>();
                        release(c, BAR_EMPTY + 8 * prev, 1);
                        prev = cur.slot; cur.adv();
                        if (kc == 1) { fence_regs(o); if (r) release(c, BAR_EMPTY + 8 * cv.slot, 1); }
                        if (kc <= 4 && epi) {
                            store_pair(o, kc - 1, out, hs, inv);
                            if (kc == 4) signal_event(c, r ? EV_CTX + 2 * v : EV_KV + 3 * v + 2);
                        }
                    }
                    if (!heavy) cur.adv();
                    ck = cur;
                    cur.adv();
                    if (!heavy) cur.adv();
                    wg_wait<0>();
                    release(c, BAR_EMPTY + 8 * prev, 1);
                    PROF_EV(21);
                    fence_regs(s);
#pragma unroll
                    for (int i = 0; i < 32; i++) q[i] = pack_bf16(s[2 * i], s[2 * i + 1]);
                }
                cv = ck;
                int first = 1, gen = 0;
                uint32_t pv_cnt = 0;
                pv_acc = 0; pv_mode = 2;
                l[0] = l[1] = m[0] = m[1] = 0.f;
                mbar_wait_hot(misc + BAR_FULL + 8 * ck.slot, ck.ph);
#pragma unroll 1
                while (true) {
                    float s[64];
                    if (half & first) {
                        if (heavy || HOLD0 == 0 || HOLD0 == 8) token_wait(w);
                        PROF_EV(30);
                        float sh[32];
                        undef_regs(sh);
                        issue_qk_half(sh, q, ring + ck.slot * SLOT_BYTES);
                        token_pass(w);
                        --left;
                        wg_wait<0>();
                        PROF_EV(34);
                        fence_regs(sh);
                        mask_diag<0>(sh, c);
                        float l0 = 0.f, l1 = 0.f;
#pragma unroll
                        for (int j = 0; j < 8; j++) {
#pragma unroll
                            for (int e = 0; e < 4; e++) ex2v(sh[4 * j + e]);
                            l0 += sh[4 * j] + sh[4 * j + 1]; l1 += sh[4 * j + 2] + sh[4 * j + 3];
                        }
#pragma unroll
                        for (int i = 0; i < 16; i++) p[i] = pack_bf16(sh[2 * i], sh[2 * i + 1]);
                        const int lim = mask_lim(c);
                        if (__any_sync(0xffffffffu, !(l0 <= SAFE_SUM && l1 <= SAFE_SUM && (l0 >= 1.0f / SAFE_SUM || lim < 0) &&
                                                      (l1 >= 1.0f / SAFE_SUM || lim < -2)))) goto redo;
                        l[0] = l0; l[1] = l1;
                        goto tail;
                    }
#pragma unroll 1
                    while (true) {
                        token_wait(w);
                        PROF_EV(first ? 30 : 31);
                        undef_regs(s);
                        issue_qk(s, q, ring + ck.slot * SLOT_BYTES);
                        Cur nck = cur, ncv = cur, ncur;
                        ncv.adv(); ncur = ncv; ncur.adv();
                        --left;
                        mbar_wait_hot(misc + BAR_FULL + 8 * cv.slot, cv.ph);
                        issue_pv(o, p, ring + cv.slot * SLOT_BYTES, pv_acc, pv_mode);
                        token_pass(w);
                        wg_wait<1>();
                        PROF_EV(33);
                        fence_regs(s);
                        float lo = 0.f;
                        if (first) {
                            lo = 1.0f / SAFE_SUM;
                            mask_diag<8>(s, c);
                        }
                        constexpr int JB = 11;
                        float l0 = l[0], l1 = l[1];
                        if (!gen) {
#pragma unroll
                            for (int j = 0; j < JB; j++) {
#pragma unroll
                                for (int e = 0; e < 4; e++) ex2v(s[4 * j + e]);
                                if (j < JB - 1) { l0 += s[4 * j] + s[4 * j + 1]; l1 += s[4 * j + 2] + s[4 * j + 3]; }
                            }
                        }
                        wg_wait<0>();
                        fence_regs(o);
                        if (gen) goto general;
#pragma unroll
                        for (int j = JB - 1; j < 16; j++) {
                            if (j >= JB) {
#pragma unroll
                                for (int e = 0; e < 4; e++) ex2v(s[4 * j + e]);
                            }
                            l0 += s[4 * j] + s[4 * j + 1]; l1 += s[4 * j + 2] + s[4 * j + 3];
                        }
#pragma unroll
                        for (int i = 0; i < 32; i++) p[i] = pack_bf16(s[2 * i], s[2 * i + 1]);
                        if (__any_sync(0xffffffffu, !(l0 <= SAFE_SUM && l1 <= SAFE_SUM && l0 >= lo && l1 >= lo))) goto redo;
                        l[0] = l0; l[1] = l1;
                        if (left == 0) goto tail;
                        release(c, BAR_EMPTY + 8 * ck.slot, 1 + (first & heavy));
                        if (pv_cnt) release(c, BAR_EMPTY + 8 * cv.slot, pv_cnt);
                        pv_acc = first ^ 1; pv_mode = 0; pv_cnt = 1 + (first & heavy); first = 0;
                        ck = nck; cv = ncv; cur = ncur;
                        mbar_wait_hot(misc + BAR_FULL + 8 * ck.slot, ck.ph);
                    }
                redo:
                    recompute_scores(s, q, ring + ck.slot * SLOT_BYTES, c);
                    if (first) { mask_any(s, half ^ 1, c); m[0] = m[1] = -INFINITY; }
                    gen = 1;
                general:
                    {
                        float mx[2], alpha[2];
                        row_max<16>(s, mx);
#pragma unroll
                        for (int i = 0; i < 2; i++) {
                            mx[i] = fmaxf(mx[i], m[i]);
                            alpha[i] = ex2(m[i] - mx[i]);
                            m[i] = mx[i];
                            l[i] *= alpha[i];
                        }
                        exp_sum<16, true>(s, m, l[0], l[1]);
#pragma unroll
                        for (int i = 0; i < 64; i++) o[i] *= alpha[(i >> 1) & 1];
#pragma unroll
                        for (int i = 0; i < 32; i++) p[i] = pack_bf16(s[2 * i], s[2 * i + 1]);
                    }
                tail:
                    release(c, BAR_EMPTY + 8 * ck.slot, 1 + (first & heavy));
                    if (pv_cnt) release(c, BAR_EMPTY + 8 * cv.slot, pv_cnt);
                    pv_acc = first ^ 1; pv_mode = first & half; pv_cnt = 1 + (first & heavy); first = 0;
                    if (left == 0) break;
                    ck = cur; cur.adv(); cv = cur; cur.adv();
                    mbar_wait_hot(misc + BAR_FULL + 8 * ck.slot, ck.ph);
                }
            }
            mbar_wait_hot(misc + BAR_FULL + 8 * cur.slot, cur.ph);
            token_wait(w);
            PROF_EV(32);
            issue_pv(o, p, ring + cur.slot * SLOT_BYTES, pv_acc, pv_mode);
            if (w == 0 || v == 0) token_pass(w);
            const uint32_t vslot = cur.slot;
            cur.adv();
            if (v) {
                row_inv(l, inv);
                wg_wait<0>();
                release(c, BAR_EMPTY + 8 * vslot, 1);
                fence_regs(o);
                tile_out(out, g_ctx + (size_t)((2 * team + 1) * 32 + 4 * k + (w ? 3 - (rank ^ SWAPT) : rank ^ SWAPT)) * 16384, 0, 0, c);
#pragma unroll
                for (int i = 0; i < 64; i++) wf[i] = 0u;
                continue;
            }
            cw = cur_at(80);
            mbar_wait_hot(misc + BAR_FULL + 8 * slot_of(76), cur_at(76).ph);
            mbar_wait_hot(misc + BAR_FULL + 8 * slot_of(78), cur_at(78).ph);
            load_afrag<8, 32>(wf, ring + slot_of(78) * SLOT_BYTES + w * 16384, c);
            const uint32_t z = load_afrag<8, 0>(wf, ring + slot_of(76) * SLOT_BYTES + w * 16384, c);
            row_inv(l, inv);
            release(c, BAR_EMPTY + 8 * slot_of(76) + z, 1);
            asm volatile("{\n.reg .pred p;\nsetp.eq.u32 p, %0, 0;\n@p bar.sync 4, 128;\n@!p bar.sync 5, 128;\n}\n" ::"r"(w) : "memory");
            wg_wait<0>();
            release(c, BAR_EMPTY + 8 * vslot, 1);
            fence_regs(o);
            {
                const uint32_t base = ring + slot_of(78) * SLOT_BYTES + w * 16384 + (16 * c.warp + (c.lane >> 2)) * 64 + (((c.lane ^ (c.lane >> 3)) & 3) << 4);
#pragma unroll
                for (int i = 0; i < 2; i++)
#pragma unroll
                    for (int qq = 0; qq < 4; qq++)
                        asm volatile("st.shared.v4.b32 [%0], {%1,%2,%3,%4};" ::"r"(base + qq * 4096 + i * 512),
                                     "r"(pack_bf16(o[16 * qq + 2 * i] * inv[i], o[16 * qq + 2 * i + 1] * inv[i])),
                                     "r"(pack_bf16(o[16 * qq + 4 + 2 * i] * inv[i], o[16 * qq + 4 + 2 * i + 1] * inv[i])),
                                     "r"(pack_bf16(o[16 * qq + 8 + 2 * i] * inv[i], o[16 * qq + 8 + 2 * i + 1] * inv[i])),
                                     "r"(pack_bf16(o[16 * qq + 12 + 2 * i] * inv[i], o[16 * qq + 12 + 2 * i + 1] * inv[i])) : "memory");
                asm volatile("fence.proxy.async.shared::cta;" ::: "memory");
                signal_event(c, EV_CTX + 1);
            }
        }
        }
        {
            float acc[80];
            undef_regs(acc);
            int st = 0, prev = 0; uint32_t ph3 = 0;
            auto op_stage = [&](int i) {
                mbar_wait_hot(misc + BAR_FULL3 + 8 * st, ph3);
                PROF_EV(44);
                uint32_t base = ring + st * ST3_BYTES;
                uint64_t da = mkdesc(base + w * 8192, 16, 512, 2);
                uint64_t db = mkdesc(base + 16384, 2048, 512, 2);
                wg_fence();
#pragma unroll
                for (int k = 0; k < 4; k++) wgmma_ss_n160_ta0_tb1(acc, da + (k >> 1) * 256 + 2 * (k & 1), db + (k >> 1) * 640 + (k & 1) * 64, k ? 1 : i);
                wg_commit();
                if (i > 0) { wg_wait<1>(); if (i <= 32 - NST3) release(c, BAR_EMPTY3 + 8 * prev, 1); }
                prev = st;
                if (++st == NST3) { st = 0; ph3 ^= 1; }
            };
            PROF_EV(40); PROF_GT(65);
#pragma unroll
            for (int i = 0; i < 4; i++) { op_stage(i); store_pair(o, i, out, 4096, inv); }
            signal_event(c, EV_CTX + 3);
#pragma unroll 1
            for (int i = 4; i < 12; i++) op_stage(i);
            mbar_wait(misc + BAR_SEL, 0);
            const uint32_t tag = lds32(misc + MISC_EPOCH) & 1;
            const int g = c.lane >> 2, t = c.lane & 3;
            const int row = (2 * u3 + rank) * 128 + 64 * w + perm32(16 * c.warp + 8 * kap + g);
            const int col = 160 * s3 + 8 * t;
            int sel = -1;
#pragma unroll
            for (int i = 0; i < TOPC; i++) if ((int)lds32(misc + MISC_SEL + 4 * i) == row) sel = i;
            const int t256 = tid - 128;
            uint4* sendp = g_part + (size_t)cta * 2560 + t256;
            if (c.lane >= 30) stg128(sendp + 9 * 256, tag ^ 1, tag ^ 1, tag ^ 1, tag ^ 1);
#pragma unroll 1
            for (int i = 12; i < 32; i++) op_stage(i);
            uint4 xv[5], bv[5];
#pragma unroll
            for (int i = 0; i < 5; i++) xv[i] = ldg128(P.x + (size_t)row * DM + col + 32 * i);
            uint2 stat;
            asm volatile("ld.global.cg.v2.b32 {%0,%1}, [%2];" : "=r"(stat.x), "=r"(stat.y) : "l"(g_stats + row) : "memory");
            wg_wait<0>();
            fence_regs(acc);
            PROF_EV(41); PROF_GT(66);
            float keep[40];
#pragma unroll
            for (int j = 0; j < 10; j++) {
                uint32_t v0 = __float_as_uint(kap ? acc[8 * j + 0] : acc[8 * j + 2]), v1 = __float_as_uint(kap ? acc[8 * j + 1] : acc[8 * j + 3]);
                uint32_t v2 = __float_as_uint(kap ? acc[8 * j + 4] : acc[8 * j + 6]), v3 = __float_as_uint(kap ? acc[8 * j + 5] : acc[8 * j + 7]);
                asm volatile("st.relaxed.gpu.global.v4.b32 [%0], {%1,%2,%3,%4};" ::"l"(sendp + j * 256),
                             "r"((v0 & ~1u) | tag), "r"((v1 & ~1u) | tag), "r"((v2 & ~1u) | tag), "r"((v3 & ~1u) | tag) : "memory");
                keep[4 * j + 0] = kap ? acc[8 * j + 2] : acc[8 * j + 0]; keep[4 * j + 1] = kap ? acc[8 * j + 3] : acc[8 * j + 1];
                keep[4 * j + 2] = kap ? acc[8 * j + 6] : acc[8 * j + 4]; keep[4 * j + 3] = kap ? acc[8 * j + 7] : acc[8 * j + 5];
            }
            PROF_GT(67);
            signal_event(c, EV_END);
#pragma unroll
            for (int i = 0; i < 5; i++) {
                uint32_t xx[4] = {xv[i].x, xv[i].y, xv[i].z, xv[i].w};
#pragma unroll
                for (int e = 0; e < 4; e++) {
                    asm("sub.rn.bf16x2 %0, %0, %1;" : "+r"(xx[e]) : "r"(stat.x));
                    xx[e] = pack_bf16(bf_lo(xx[e]) * __uint_as_float(stat.y), bf_hi(xx[e]) * __uint_as_float(stat.y));
                }
                bv[i] = make_uint4(xx[0], xx[1], xx[2], xx[3]);
            }
            if (sel >= 0) {
#pragma unroll
                for (int i = 0; i < 5; i++) bv[i] = ldg128(g_brow + sel * DM + col + 32 * i);
            }
            const uint4* recvp = g_part + (size_t)partner * 2560 + t256;
            uint4 rv[10];
            int spins = 0;
            while (true) {
                uint32_t v;
                asm volatile("ld.relaxed.gpu.global.b32 %0, [%1];" : "=r"(v) : "l"(recvp + 9 * 256 + (31 - c.lane)) : "memory");
                if (__all_sync(0xffffffffu, (v & 1u) == tag) || ++spins > 2000000) break;
            }
            PROF_GT(68);
            while (true) {
                uint32_t bad = 0u;
#pragma unroll
                for (int j = 0; j < 10; j++) {
                    asm volatile("ld.relaxed.gpu.global.v4.b32 {%0,%1,%2,%3}, [%4];"
                                 : "=r"(rv[j].x), "=r"(rv[j].y), "=r"(rv[j].z), "=r"(rv[j].w) : "l"(recvp + j * 256) : "memory");
                }
#pragma unroll
                for (int j = 0; j < 10; j++) {
                    rv[j].x ^= tag; rv[j].y ^= tag; rv[j].z ^= tag; rv[j].w ^= tag;
                    bad |= rv[j].x | rv[j].y | rv[j].z | rv[j].w;
                }
                if (__all_sync(0xffffffffu, (bad & 1u) == 0) || ++spins > 2000000) break;
            }
            PROF_GT(69);
            uint32_t pk[20];
#pragma unroll
            for (int j = 0; j < 10; j++) {
                pk[2 * j] = pack_bf16(keep[4 * j] + __uint_as_float(rv[j].x), keep[4 * j + 1] + __uint_as_float(rv[j].y));
                pk[2 * j + 1] = pack_bf16(keep[4 * j + 2] + __uint_as_float(rv[j].z), keep[4 * j + 3] + __uint_as_float(rv[j].w));
            }
#pragma unroll
            for (int i = 0; i < 5; i++) {
                uint32_t a0 = pk[4 * i], a1 = pk[4 * i + 1], a2 = pk[4 * i + 2], a3 = pk[4 * i + 3];
                uint32_t x0 = (t & 1) ? a0 : a1, x1 = (t & 1) ? a2 : a3;
                x0 = __shfl_xor_sync(0xffffffffu, x0, 1); x1 = __shfl_xor_sync(0xffffffffu, x1, 1);
                if (t & 1) { a0 = x0; a2 = x1; } else { a1 = x0; a3 = x1; }
                x0 = (t & 2) ? a0 : a2; x1 = (t & 2) ? a1 : a3;
                x0 = __shfl_xor_sync(0xffffffffu, x0, 2); x1 = __shfl_xor_sync(0xffffffffu, x1, 2);
                if (t & 2) { a0 = x0; a1 = x1; } else { a2 = x0; a3 = x1; }
                uint32_t av[4] = {a0, a1, a2, a3};
                uint32_t xx[4] = {xv[i].x, xv[i].y, xv[i].z, xv[i].w}, bb[4] = {bv[i].x, bv[i].y, bv[i].z, bv[i].w};
                uint32_t ov[4];
#pragma unroll
                for (int e = 0; e < 4; e++) {
                    asm("add.rn.bf16x2 %0, %1, %2;" : "=r"(ov[e]) : "r"(xx[e]), "r"(av[e]));
                    asm("add.rn.bf16x2 %0, %0, %1;" : "+r"(ov[e]) : "r"(bb[e]));
                }
                stg128(P.out + (size_t)row * DM + col + 32 * i, ov[0], ov[1], ov[2], ov[3]);
            }
            PROF_EV(42); PROF_GT(43);
        }
    }
}

typedef CUresult (*EncodeFn)(CUtensorMap*, CUtensorMapDataType, cuuint32_t, void*, const cuuint64_t*, const cuuint64_t*, const cuuint32_t*,
                             const cuuint32_t*, CUtensorMapInterleave, CUtensorMapSwizzle, CUtensorMapL2promotion, CUtensorMapFloatOOBfill);

void make_map2d(EncodeFn enc, CUtensorMap* tm, const void* p, uint64_t cols, uint64_t rows, uint32_t box_rows = 128) {
    cuuint64_t gd[2] = {cols, rows}, gs[1] = {cols * 2};
    cuuint32_t box[2] = {64, box_rows}, es[2] = {1, 1};
    enc(tm, CU_TENSOR_MAP_DATA_TYPE_BFLOAT16, 2, const_cast<void*>(p), gd, gs, box, es, CU_TENSOR_MAP_INTERLEAVE_NONE,
        CU_TENSOR_MAP_SWIZZLE_128B, CU_TENSOR_MAP_L2_PROMOTION_L2_128B, CU_TENSOR_MAP_FLOAT_OOB_FILL_NONE);
}

void make_map3d(EncodeFn enc, CUtensorMap* tm, const void* p, uint64_t cols, uint64_t rows, uint32_t bw, uint32_t nb) {
    cuuint64_t gd[3] = {bw, rows, cols / bw}, gs[2] = {cols * 2, bw * 2};
    cuuint32_t box[3] = {bw, 32, nb}, es[3] = {1, 1, 1};
    enc(tm, CU_TENSOR_MAP_DATA_TYPE_BFLOAT16, 3, const_cast<void*>(p), gd, gs, box, es, CU_TENSOR_MAP_INTERLEAVE_NONE,
        bw == 64 ? CU_TENSOR_MAP_SWIZZLE_128B : CU_TENSOR_MAP_SWIZZLE_64B, CU_TENSOR_MAP_L2_PROMOTION_L2_128B, CU_TENSOR_MAP_FLOAT_OOB_FILL_NONE);
}

}

extern "C" void kernel_launch(void* const* d_in, const int* in_sizes, int n_in, void* d_out, int out_size) {
    (void)in_sizes; (void)n_in; (void)out_size;
    static EncodeFn enc = nullptr;
    if (!enc) {
        void* fn = nullptr;
        cudaDriverEntryPointQueryResult qr;
        cudaGetDriverEntryPoint("cuTensorMapEncodeTiled", &fn, cudaEnableDefault, &qr);
        enc = (EncodeFn)fn;
        cudaFuncSetAttribute(fused_kernel, cudaFuncAttributeMaxDynamicSharedMemorySize, SMEM_BYTES);
    }
    CUtensorMap tmC, tmWk, tmWv, tmWq, tmWo, tmG, tmU, tmD;
    make_map2d(enc, &tmC, d_in[1], DC, SEQ);
    make_map2d(enc, &tmWq, d_in[2], 4096, DM, 64);
    make_map2d(enc, &tmWk, d_in[3], 4096, DC);
    make_map2d(enc, &tmWv, d_in[4], 4096, DC);
    make_map3d(enc, &tmWo, d_in[5], DM, 4096, 32, 5);
    make_map3d(enc, &tmG, d_in[8], FF, DM, 64, 7);
    make_map3d(enc, &tmU, d_in[9], FF, DM, 64, 7);
    make_map3d(enc, &tmD, d_in[10], DM, FF, 64, 10);
    Params P;
    P.x = (const __nv_bfloat16*)d_in[0];
    P.c = (const __nv_bfloat16*)d_in[1];
    P.wk = (const __nv_bfloat16*)d_in[3];
    P.wv = (const __nv_bfloat16*)d_in[4];
    P.wo = (const __nv_bfloat16*)d_in[5];
    P.wr = (const __nv_bfloat16*)d_in[7];
    P.out = (__nv_bfloat16*)d_out;
    fused_kernel<<<132, 384, SMEM_BYTES>>>(tmC, tmWk, tmWv, tmWq, tmWo, tmG, tmU, tmD, P);
}
```

```cpp
#include <cuda_runtime.h>
#include <cuda_bf16.h>
#include <cuda.h>
#include <stdint.h>

#define SWAPT 1
#define DEFER 1
#define HOLD0 6
#define LNINL __noinline__
#define HM 0
#define OP_PF 8
#define PF_START 9
#define LATE_AT 18
#define CDELAY 500
#define AUXDELAY 1000
namespace {

constexpr int SEQ = 2048, NH = 32, DM = 640, DC = 512, FF = 1728, TOPC = 8;
constexpr int NSLOT = 7, SLOT_BYTES = 32768;
constexpr int NST3 = 6, ST3_BYTES = 36864;
constexpr int RING_BYTES = NSLOT * SLOT_BYTES;
constexpr int SMEM_BYTES = RING_BYTES + 3072;

constexpr int BAR_FULL = 96  , BAR_FULL3 = 152  , BAR_DEP = 200  , BAR_SEL = 464,
              BAR_LN = 472  , BAR_EV = 504  , BAR_EMPTY = 760  , BAR_EMPTY3 = 816  ,
              BAR_PROG = 864  , MISC_EPOCH = 896, MISC_SMID = 900  , MISC_SEL = 912, MISC_WR = 1024  ;
constexpr int D_LN = 0  , D_KV = 4  , D_WAR = 14  , D_CTX = 16  ;
constexpr int EV_KV = 0  , EV_END = 11, EV_CTX = 12  ;

constexpr int FL_MOE_CNT = 0, FL_MOE_DONE = 1, FL_LN = 16  , FL_KV = 32  , FL_CTX = 416  , FL_WAR = 672  , FL_TOTAL = 704;

__device__ __align__(1024) unsigned char g_K[16 * 32 * 16384];
__device__ __align__(1024) unsigned char g_V[16 * 32 * 16384];
__device__ __align__(1024) unsigned char g_ctx[NH * 32 * 16384];
__device__ __align__(1024) unsigned char g_xn[16 * 10 * 16384];
__device__ __align__(1024) uint4 g_part[128 * 10 * 256];
__device__ float g_router[SEQ];
__device__ uint2 g_stats[SEQ];
__device__ __align__(16) float g_moe_part[4 * TOPC * DM];
__device__ __align__(16) __nv_bfloat16 g_brow[TOPC * DM];
__device__ __align__(16) int g_sel[TOPC];
__device__ unsigned g_flags[FL_TOTAL * 8];
__device__ unsigned g_epoch;
__device__ unsigned g_roleq[130];

struct Params {
    const __nv_bfloat16 *x, *c, *wr, *wk, *wv, *wo;
    __nv_bfloat16* out;
};

__device__ __forceinline__ uint32_t smem_u32(const void* p) { return (uint32_t)__cvta_generic_to_shared(p); }
__device__ __forceinline__ void mbar_init(uint32_t bar, int cnt) { asm volatile("mbarrier.init.shared::cta.b64 [%0], %1;" ::"r"(bar), "r"(cnt)); }
__device__ __forceinline__ void mbar_expect_tx(uint32_t bar, uint32_t bytes) {
    asm volatile("mbarrier.arrive.expect_tx.shared::cta.b64 _, [%0], %1;" ::"r"(bar), "r"(bytes) : "memory");
}
__device__ __forceinline__ void mbar_arrive(uint32_t bar) { asm volatile("mbarrier.arrive.shared::cta.b64 _, [%0];" ::"r"(bar) : "memory"); }
__device__ __forceinline__ void mbar_arrive_cluster(uint32_t cluster_addr, uint32_t cnt) {
    asm volatile("mbarrier.arrive.shared::cluster.b64 _, [%0], %1;" ::"r"(cluster_addr), "r"(cnt) : "memory");
}
__device__ __forceinline__ uint32_t mapa(uint32_t addr, uint32_t cta) {
    uint32_t r; asm("mapa.shared::cluster.u32 %0, %1, %2;" : "=r"(r) : "r"(addr), "r"(cta)); return r;
}
__device__ __forceinline__ void mbar_wait(uint32_t bar, uint32_t parity) {
    asm volatile(
        "{\n.reg .pred p;\n.reg .u32 n;\n"
        "mov.u32 n, 0;\n"
        "LAB_WAIT:\n"
        "mbarrier.try_wait.parity.shared::cta.b64 p, [%0], %1, 100000;\n"
        "@p bra DONE;\n"
        "add.u32 n, n, 1;\n"
        "setp.lt.u32 p, n, 50000;\n"
        "@p bra LAB_WAIT;\n"
        "trap;\n"
        "DONE:\n}\n" ::"r"(bar), "r"(parity) : "memory");
}
__device__ __forceinline__ void mbar_wait_hot(uint32_t bar, uint32_t parity) {
    asm volatile("{\n.reg .pred p;\nLAB_WAIT:\nmbarrier.try_wait.parity.shared::cta.b64 p, [%0], %1;\n@!p bra LAB_WAIT;\n}\n" ::"r"(bar), "r"(parity) : "memory");
}
__device__ __forceinline__ void mbar_wait_sleep(uint32_t bar, uint32_t parity) {
    asm volatile("{\n.reg .pred p;\nLAB_WAIT:\nmbarrier.try_wait.parity.shared::cta.b64 p, [%0], %1, 100000;\n@!p bra LAB_WAIT;\n}\n" ::"r"(bar), "r"(parity) : "memory");
}
__device__ __forceinline__ void flag_wait(const unsigned* flag, unsigned target) {
    asm volatile(
        "{\n.reg .pred p;\n.reg .u32 n, v;\n.reg .s32 d;\n"
        "mov.u32 n, 0;\n"
        "LAB_WAIT:\n"
        "ld.acquire.gpu.global.u32 v, [%0];\n"
        "sub.s32 d, v, %1;\n"
        "setp.ge.s32 p, d, 0;\n"
        "@p bra DONE;\n"
        "nanosleep.u32 40;\n"
        "add.u32 n, n, 1;\n"
        "setp.lt.u32 p, n, 3000000;\n"
        "@p bra LAB_WAIT;\n"
        "trap;\n"
        "DONE:\n}\n" ::"l"(flag), "r"(target) : "memory");
}
__device__ __forceinline__ void flag_signal(unsigned* flag) {
    asm volatile("red.release.gpu.global.add.u32 [%0], 1;" ::"l"(flag) : "memory");
}
__device__ __forceinline__ void fence_async_global() { asm volatile("fence.proxy.async.global;" ::: "memory"); }
__device__ __forceinline__ unsigned* flag_ptr(int idx) { return g_flags + idx * 8; }

__device__ __forceinline__ uint64_t policy_stream() {
    uint64_t p; asm("createpolicy.fractional.L2::evict_first.b64 %0, 1.0;" : "=l"(p)); return p;
}
__device__ __forceinline__ uint64_t policy_normal() { return 0x1000000000000000ull; }
__device__ __forceinline__ uint64_t policy(bool stream) { return stream ? policy_stream() : policy_normal(); }
__device__ __forceinline__ void bulk_load(uint32_t dst, const void* src, uint32_t bytes, uint32_t bar, uint64_t pol) {
    asm volatile("cp.async.bulk.shared::cluster.global.mbarrier::complete_tx::bytes.L2::cache_hint [%0], [%1], %2, [%3], %4;"
                 ::"r"(dst), "l"(src), "r"(bytes), "r"(bar), "l"(pol) : "memory");
}
__device__ __forceinline__ void bulk_load_mc(uint32_t dst, const void* src, uint32_t bytes, uint32_t bar, uint64_t pol) {
    asm volatile("cp.async.bulk.shared::cluster.global.mbarrier::complete_tx::bytes.multicast::cluster.L2::cache_hint [%0], [%1], %2, [%3], %4, %5;"
                 ::"r"(dst), "l"(src), "r"(bytes), "r"(bar), "h"((uint16_t)3), "l"(pol) : "memory");
}
__device__ __forceinline__ void tma2d(uint32_t dst, const CUtensorMap* tm, int c0, int c1, uint32_t bar, uint64_t pol) {
    asm volatile("cp.async.bulk.tensor.2d.shared::cluster.global.mbarrier::complete_tx::bytes.L2::cache_hint [%0], [%1, {%3, %4}], [%2], %5;"
                 ::"r"(dst), "l"(tm), "r"(bar), "r"(c0), "r"(c1), "l"(pol) : "memory");
}
__device__ __forceinline__ void tma2d_mc(uint32_t dst, const CUtensorMap* tm, int c0, int c1, uint32_t bar, uint64_t pol) {
    asm volatile("cp.async.bulk.tensor.2d.shared::cluster.global.mbarrier::complete_tx::bytes.multicast::cluster.L2::cache_hint [%0], [%1, {%3, %4}], [%2], %5, %6;"
                 ::"r"(dst), "l"(tm), "r"(bar), "r"(c0), "r"(c1), "h"((uint16_t)3), "l"(pol) : "memory");
}
__device__ __forceinline__ void tma3d_mc(uint32_t dst, const CUtensorMap* tm, int c0, int c1, int c2, uint32_t bar, uint64_t pol) {
    asm volatile("cp.async.bulk.tensor.3d.shared::cluster.global.mbarrier::complete_tx::bytes.multicast::cluster.L2::cache_hint [%0], [%1, {%3, %4, %5}], [%2], %6, %7;"
                 ::"r"(dst), "l"(tm), "r"(bar), "r"(c0), "r"(c1), "r"(c2), "h"((uint16_t)3), "l"(pol) : "memory");
}
__device__ __forceinline__ void tma3d(uint32_t dst, const CUtensorMap* tm, int c0, int c1, int c2, uint32_t bar) {
    asm volatile("cp.async.bulk.tensor.3d.shared::cluster.global.mbarrier::complete_tx::bytes.L2::cache_hint [%0], [%1, {%3, %4, %5}], [%2], %6;"
                 ::"r"(dst), "l"(tm), "r"(bar), "r"(c0), "r"(c1), "r"(c2), "l"(policy_stream()) : "memory");
}
__device__ __forceinline__ void tma2d_prefetch(const CUtensorMap* tm, int c0, int c1) {
    asm volatile("cp.async.bulk.prefetch.tensor.2d.L2.global [%0, {%1, %2}];" ::"l"(tm), "r"(c0), "r"(c1) : "memory");
}
__device__ __forceinline__ void tma3d_prefetch(const CUtensorMap* tm, int c0, int c1, int c2) {
    asm volatile("cp.async.bulk.prefetch.tensor.3d.L2.global [%0, {%1, %2, %3}];" ::"l"(tm), "r"(c0), "r"(c1), "r"(c2) : "memory");
}
__device__ __forceinline__ void l2_prefetch(const void* p, uint32_t bytes) {
    asm volatile("cp.async.bulk.prefetch.L2.global [%0], %1;" ::"l"(p), "r"(bytes) : "memory");
}
__device__ __forceinline__ bool elect_one() {
    uint32_t r; asm volatile("{\n.reg .pred p;\nelect.sync _|p, 0xffffffff;\nselp.u32 %0, 1, 0, p;\n}\n" : "=r"(r)); return r != 0;
}
__device__ __forceinline__ void wg_fence() { asm volatile("wgmma.fence.sync.aligned;" ::: "memory"); }
__device__ __forceinline__ void wg_commit() { asm volatile("wgmma.commit_group.sync.aligned;" ::: "memory"); }
template <int N> __device__ __forceinline__ void wg_wait() { asm volatile("wgmma.wait_group.sync.aligned %0;" ::"n"(N) : "memory"); }
__device__ __forceinline__ void bar_sync(int id, int n) { asm volatile("bar.sync %0, %1;" ::"r"(id), "r"(n) : "memory"); }
__device__ __forceinline__ void bar_arrive(int id, int n) { asm volatile("bar.arrive %0, %1;" ::"r"(id), "r"(n) : "memory"); }
__device__ __forceinline__ void token_wait(int w) {
    asm volatile("{\n.reg .pred p;\nsetp.eq.u32 p, %0, 0;\n@p bar.sync 1, 256;\n@!p bar.sync 2, 256;\n}\n" ::"r"(w) : "memory");
}
__device__ __forceinline__ void token_pass(int w) {
    asm volatile("{\n.reg .pred p;\nsetp.eq.u32 p, %0, 0;\n@p bar.arrive 2, 256;\n@!p bar.arrive 1, 256;\n}\n" ::"r"(w) : "memory");
}
template <int N> __device__ __forceinline__ void fence_regs(float (&a)[N]) {
#pragma unroll
    for (int i = 0; i < N; i++) asm volatile("" : "+f"(a[i])::"memory");
}
template <int N> __device__ __forceinline__ void undef_regs(float (&a)[N]) {
#pragma unroll
    for (int i = 0; i < N; i++) asm volatile("" : "=f"(a[i]));
}
__device__ __forceinline__ void ldsm4t(uint32_t& r0, uint32_t& r1, uint32_t& r2, uint32_t& r3, uint32_t addr) {
    asm volatile("ldmatrix.sync.aligned.m8n8.x4.trans.shared.b16 {%0,%1,%2,%3}, [%4];"
                 : "=r"(r0), "=r"(r1), "=r"(r2), "=r"(r3) : "r"(addr) : "memory");
}
__device__ __forceinline__ uint32_t pack_bf16(float lo, float hi) {
    uint32_t r; asm("cvt.rn.bf16x2.f32 %0, %1, %2;" : "=r"(r) : "f"(hi), "f"(lo)); return r;
}
__device__ __forceinline__ float bf_lo(uint32_t v) { return __uint_as_float(v << 16); }
__device__ __forceinline__ float bf_hi(uint32_t v) { return __uint_as_float(v & 0xffff0000u); }
__device__ __forceinline__ float bf_round(float v) { return __bfloat162float(__float2bfloat16_rn(v)); }
__device__ __forceinline__ float ex2(float v) { float r; asm("ex2.approx.ftz.f32 %0, %1;" : "=f"(r) : "f"(v)); return r; }
__device__ __forceinline__ void ex2v(float& v) { asm volatile("ex2.approx.ftz.f32 %0, %0;" : "+f"(v)); }
__device__ __forceinline__ float rcp_fast(float v) { float r; asm("rcp.approx.ftz.f32 %0, %1;" : "=f"(r) : "f"(v)); return r; }
__device__ __forceinline__ float sqrt_fast(float v) { float r; asm("sqrt.approx.ftz.f32 %0, %1;" : "=f"(r) : "f"(v)); return r; }
__device__ __forceinline__ void stg128(void* p, uint32_t a, uint32_t b, uint32_t c, uint32_t d) {
    asm volatile("st.global.v4.b32 [%0], {%1,%2,%3,%4};" ::"l"(p), "r"(a), "r"(b), "r"(c), "r"(d) : "memory");
}
__device__ __forceinline__ uint4 ldg128(const void* p) {
    uint4 v; asm volatile("ld.global.cg.v4.b32 {%0,%1,%2,%3}, [%4];" : "=r"(v.x), "=r"(v.y), "=r"(v.z), "=r"(v.w) : "l"(p) : "memory"); return v;
}
__device__ __forceinline__ uint64_t mkdesc(uint32_t addr, uint32_t lbo, uint32_t sbo, uint32_t swz) {
    uint32_t lo = ((addr & 0x3FFFF) >> 4) | ((lbo >> 4) << 16);
    uint32_t hi = (sbo >> 4) | (swz << 30);
    return ((uint64_t)hi << 32) | lo;
}
__device__ __forceinline__ int perm32(int v) { return (v & ~30) | ((v >> 2) & 6) | ((v << 2) & 24); }

__device__ __forceinline__ void wgmma_rs_n128_ta0_tb0(float (&d)[64], uint32_t a0, uint32_t a1, uint32_t a2, uint32_t a3, uint64_t descB, int scaleD) {
  asm volatile("{\n.reg .pred p;\nsetp.ne.b32 p, %69, 0;\n"
    "wgmma.mma_async.sync.aligned.m64n128k16.f32.bf16.bf16 "
    "{%0, %1, %2, %3, %4, %5, %6, %7, %8, %9, %10, %11, %12, %13, %14, %15, %16, %17, %18, %19, %20, %21, %22, %23, %24, %25, %26, %27, %28, %29, %30, %31, %32, %33, %34, %35, %36, %37, %38, %39, %40, %41, %42, %43, %44, %45, %46, %47, %48, %49, %50, %51, %52, %53, %54, %55, %56, %57, %58, %59, %60, %61, %62, %63}, "
    "{%64, %65, %66, %67}, %68, p, 1, 1, 0;\n}\n"
    : "+f"(d[0]), "+f"(d[1]), "+f"(d[2]), "+f"(d[3]), "+f"(d[4]), "+f"(d[5]), "+f"(d[6]), "+f"(d[7]), "+f"(d[8]), "+f"(d[9]), "+f"(d[10]), "+f"(d[11]), "+f"(d[12]), "+f"(d[13]), "+f"(d[14]), "+f"(d[15]), "+f"(d[16]), "+f"(d[17]), "+f"(d[18]), "+f"(d[19]), "+f"(d[20]), "+f"(d[21]), "+f"(d[22]), "+f"(d[23]), "+f"(d[24]), "+f"(d[25]), "+f"(d[26]), "+f"(d[27]), "+f"(d[28]), "+f"(d[29]), "+f"(d[30]), "+f"(d[31]), "+f"(d[32]), "+f"(d[33]), "+f"(d[34]), "+f"(d[35]), "+f"(d[36]), "+f"(d[37]), "+f"(d[38]), "+f"(d[39]), "+f"(d[40]), "+f"(d[41]), "+f"(d[42]), "+f"(d[43]), "+f"(d[44]), "+f"(d[45]), "+f"(d[46]), "+f"(d[47]), "+f"(d[48]), "+f"(d[49]), "+f"(d[50]), "+f"(d[51]), "+f"(d[52]), "+f"(d[53]), "+f"(d[54]), "+f"(d[55]), "+f"(d[56]), "+f"(d[57]), "+f"(d[58]), "+f"(d[59]), "+f"(d[60]), "+f"(d[61]), "+f"(d[62]), "+f"(d[63])
    : "r"(a0), "r"(a1), "r"(a2), "r"(a3), "l"(descB), "r"(scaleD));
}
__device__ __forceinline__ void wgmma_rs_n128_ta0_tb1(float (&d)[64], uint32_t a0, uint32_t a1, uint32_t a2, uint32_t a3, uint64_t descB, int scaleD) {
  asm volatile("{\n.reg .pred p;\nsetp.ne.b32 p, %69, 0;\n"
    "wgmma.mma_async.sync.aligned.m64n128k16.f32.bf16.bf16 "
    "{%0, %1, %2, %3, %4, %5, %6, %7, %8, %9, %10, %11, %12, %13, %14, %15, %16, %17, %18, %19, %20, %21, %22, %23, %24, %25, %26, %27, %28, %29, %30, %31, %32, %33, %34, %35, %36, %37, %38, %39, %40, %41, %42, %43, %44, %45, %46, %47, %48, %49, %50, %51, %52, %53, %54, %55, %56, %57, %58, %59, %60, %61, %62, %63}, "
    "{%64, %65, %66, %67}, %68, p, 1, 1, 1;\n}\n"
    : "+f"(d[0]), "+f"(d[1]), "+f"(d[2]), "+f"(d[3]), "+f"(d[4]), "+f"(d[5]), "+f"(d[6]), "+f"(d[7]), "+f"(d[8]), "+f"(d[9]), "+f"(d[10]), "+f"(d[11]), "+f"(d[12]), "+f"(d[13]), "+f"(d[14]), "+f"(d[15]), "+f"(d[16]), "+f"(d[17]), "+f"(d[18]), "+f"(d[19]), "+f"(d[20]), "+f"(d[21]), "+f"(d[22]), "+f"(d[23]), "+f"(d[24]), "+f"(d[25]), "+f"(d[26]), "+f"(d[27]), "+f"(d[28]), "+f"(d[29]), "+f"(d[30]), "+f"(d[31]), "+f"(d[32]), "+f"(d[33]), "+f"(d[34]), "+f"(d[35]), "+f"(d[36]), "+f"(d[37]), "+f"(d[38]), "+f"(d[39]), "+f"(d[40]), "+f"(d[41]), "+f"(d[42]), "+f"(d[43]), "+f"(d[44]), "+f"(d[45]), "+f"(d[46]), "+f"(d[47]), "+f"(d[48]), "+f"(d[49]), "+f"(d[50]), "+f"(d[51]), "+f"(d[52]), "+f"(d[53]), "+f"(d[54]), "+f"(d[55]), "+f"(d[56]), "+f"(d[57]), "+f"(d[58]), "+f"(d[59]), "+f"(d[60]), "+f"(d[61]), "+f"(d[62]), "+f"(d[63])
    : "r"(a0), "r"(a1), "r"(a2), "r"(a3), "l"(descB), "r"(scaleD));
}
__device__ __forceinline__ void wgmma_rs_n64_ta0_tb1(float (&d)[32], uint32_t a0, uint32_t a1, uint32_t a2, uint32_t a3, uint64_t descB, int scaleD) {
  asm volatile("{\n.reg .pred p;\nsetp.ne.b32 p, %37, 0;\n"
    "wgmma.mma_async.sync.aligned.m64n64k16.f32.bf16.bf16 "
    "{%0, %1, %2, %3, %4, %5, %6, %7, %8, %9, %10, %11, %12, %13, %14, %15, %16, %17, %18, %19, %20, %21, %22, %23, %24, %25, %26, %27, %28, %29, %30, %31}, "
    "{%32, %33, %34, %35}, %36, p, 1, 1, 1;\n}\n"
    : "+f"(d[0]), "+f"(d[1]), "+f"(d[2]), "+f"(d[3]), "+f"(d[4]), "+f"(d[5]), "+f"(d[6]), "+f"(d[7]), "+f"(d[8]), "+f"(d[9]), "+f"(d[10]), "+f"(d[11]), "+f"(d[12]), "+f"(d[13]), "+f"(d[14]), "+f"(d[15]), "+f"(d[16]), "+f"(d[17]), "+f"(d[18]), "+f"(d[19]), "+f"(d[20]), "+f"(d[21]), "+f"(d[22]), "+f"(d[23]), "+f"(d[24]), "+f"(d[25]), "+f"(d[26]), "+f"(d[27]), "+f"(d[28]), "+f"(d[29]), "+f"(d[30]), "+f"(d[31])
    : "r"(a0), "r"(a1), "r"(a2), "r"(a3), "l"(descB), "r"(scaleD));
}
__device__ __forceinline__ void wgmma_ss_n128_ta0_tb1(float (&d)[64], uint64_t descA, uint64_t descB, int scaleD) {
  asm volatile("{\n.reg .pred p;\nsetp.ne.b32 p, %66, 0;\n"
    "wgmma.mma_async.sync.aligned.m64n128k16.f32.bf16.bf16 "
    "{%0, %1, %2, %3, %4, %5, %6, %7, %8, %9, %10, %11, %12, %13, %14, %15, %16, %17, %18, %19, %20, %21, %22, %23, %24, %25, %26, %27, %28, %29, %30, %31, %32, %33, %34, %35, %36, %37, %38, %39, %40, %41, %42, %43, %44, %45, %46, %47, %48, %49, %50, %51, %52, %53, %54, %55, %56, %57, %58, %59, %60, %61, %62, %63}, "
    "%64, %65, p, 1, 1, 0, 1;\n}\n"
    : "+f"(d[0]), "+f"(d[1]), "+f"(d[2]), "+f"(d[3]), "+f"(d[4]), "+f"(d[5]), "+f"(d[6]), "+f"(d[7]), "+f"(d[8]), "+f"(d[9]), "+f"(d[10]), "+f"(d[11]), "+f"(d[12]), "+f"(d[13]), "+f"(d[14]), "+f"(d[15]), "+f"(d[16]), "+f"(d[17]), "+f"(d[18]), "+f"(d[19]), "+f"(d[20]), "+f"(d[21]), "+f"(d[22]), "+f"(d[23]), "+f"(d[24]), "+f"(d[25]), "+f"(d[26]), "+f"(d[27]), "+f"(d[28]), "+f"(d[29]), "+f"(d[30]), "+f"(d[31]), "+f"(d[32]), "+f"(d[33]), "+f"(d[34]), "+f"(d[35]), "+f"(d[36]), "+f"(d[37]), "+f"(d[38]), "+f"(d[39]), "+f"(d[40]), "+f"(d[41]), "+f"(d[42]), "+f"(d[43]), "+f"(d[44]), "+f"(d[45]), "+f"(d[46]), "+f"(d[47]), "+f"(d[48]), "+f"(d[49]), "+f"(d[50]), "+f"(d[51]), "+f"(d[52]), "+f"(d[53]), "+f"(d[54]), "+f"(d[55]), "+f"(d[56]), "+f"(d[57]), "+f"(d[58]), "+f"(d[59]), "+f"(d[60]), "+f"(d[61]), "+f"(d[62]), "+f"(d[63])
    : "l"(descA), "l"(descB), "r"(scaleD));
}
__device__ __forceinline__ void wgmma_ss_n160_ta0_tb1(float (&d)[80], uint64_t descA, uint64_t descB, int scaleD) {
  asm volatile("{\n.reg .pred p;\nsetp.ne.b32 p, %82, 0;\n"
    "wgmma.mma_async.sync.aligned.m64n160k16.f32.bf16.bf16 "
    "{%0, %1, %2, %3, %4, %5, %6, %7, %8, %9, %10, %11, %12, %13, %14, %15, %16, %17, %18, %19, %20, %21, %22, %23, %24, %25, %26, %27, %28, %29, %30, %31, %32, %33, %34, %35, %36, %37, %38, %39, %40, %41, %42, %43, %44, %45, %46, %47, %48, %49, %50, %51, %52, %53, %54, %55, %56, %57, %58, %59, %60, %61, %62, %63, %64, %65, %66, %67, %68, %69, %70, %71, %72, %73, %74, %75, %76, %77, %78, %79}, "
    "%80, %81, p, 1, 1, 0, 1;\n}\n"
    : "+f"(d[0]), "+f"(d[1]), "+f"(d[2]), "+f"(d[3]), "+f"(d[4]), "+f"(d[5]), "+f"(d[6]), "+f"(d[7]), "+f"(d[8]), "+f"(d[9]), "+f"(d[10]), "+f"(d[11]), "+f"(d[12]), "+f"(d[13]), "+f"(d[14]), "+f"(d[15]), "+f"(d[16]), "+f"(d[17]), "+f"(d[18]), "+f"(d[19]), "+f"(d[20]), "+f"(d[21]), "+f"(d[22]), "+f"(d[23]), "+f"(d[24]), "+f"(d[25]), "+f"(d[26]), "+f"(d[27]), "+f"(d[28]), "+f"(d[29]), "+f"(d[30]), "+f"(d[31]), "+f"(d[32]), "+f"(d[33]), "+f"(d[34]), "+f"(d[35]), "+f"(d[36]), "+f"(d[37]), "+f"(d[38]), "+f"(d[39]), "+f"(d[40]), "+f"(d[41]), "+f"(d[42]), "+f"(d[43]), "+f"(d[44]), "+f"(d[45]), "+f"(d[46]), "+f"(d[47]), "+f"(d[48]), "+f"(d[49]), "+f"(d[50]), "+f"(d[51]), "+f"(d[52]), "+f"(d[53]), "+f"(d[54]), "+f"(d[55]), "+f"(d[56]), "+f"(d[57]), "+f"(d[58]), "+f"(d[59]), "+f"(d[60]), "+f"(d[61]), "+f"(d[62]), "+f"(d[63]), "+f"(d[64]), "+f"(d[65]), "+f"(d[66]), "+f"(d[67]), "+f"(d[68]), "+f"(d[69]), "+f"(d[70]), "+f"(d[71]), "+f"(d[72]), "+f"(d[73]), "+f"(d[74]), "+f"(d[75]), "+f"(d[76]), "+f"(d[77]), "+f"(d[78]), "+f"(d[79])
    : "l"(descA), "l"(descB), "r"(scaleD));
}

#define PROF_DECL(b)
#define PROF_EV(tag)
#define PROF_GT(tag)

template <int N> struct IC { static constexpr int value = N; };
struct Cur {
    uint32_t slot, ph;
    __device__ __forceinline__ void adv() { if (++slot == NSLOT) { slot = 0; ph ^= 1; } }
};
constexpr int E0 = 2;
__host__ __device__ constexpr uint32_t slot_of(int e) { return (e + E0) % NSLOT; }
__device__ __forceinline__ Cur cur_at(int e) { Cur c; c.slot = (e + E0) % NSLOT; c.ph = ((e + E0) / NSLOT) & 1; return c; }

__device__ __forceinline__ int kv_tile(int s) { return (0x804Cu >> (4 * s)) & 15; }
__device__ __forceinline__ int op_head(int i, int kap) { return 16 * kap + 2 * (i & 7) + (i >> 3); }

constexpr float SM_SCALE = 0.08838834764831845f * 1.4426950408889634f;

struct Ctx {
    uint32_t ring, misc;
    uint32_t rel;
    int w, warp, lane;
};
__device__ __forceinline__ void release(const Ctx& c, uint32_t off, uint32_t cnt) {
    if (c.lane < 2) mbar_arrive_cluster(c.rel + off, cnt);
}
__device__ __forceinline__ void signal_event(const Ctx& c, int ev) {
    __syncwarp();
    if (c.lane == 0) mbar_arrive(c.misc + BAR_EV + (c.w * 16 + ev) * 8);
}
template <int NK, int OFF, int N>
__device__ __forceinline__ uint32_t load_afrag(uint32_t (&a)[N], uint32_t base, const Ctx& c) {
    int r = c.lane & 7, mat = c.lane >> 3;
    uint32_t addr = base + (8 * (mat >> 1) + r) * 128 + (((2 * c.warp + (mat & 1)) ^ r) << 4);
#pragma unroll
    for (int k = 0; k < NK; k++) ldsm4t(a[OFF + 4 * k], a[OFF + 4 * k + 1], a[OFF + 4 * k + 2], a[OFF + 4 * k + 3], addr + k * 2048);
    uint32_t dep = 0;
#pragma unroll
    for (int k = 0; k < NK; k++) dep |= a[OFF + 4 * k];
    return dep & blockIdx.y;
}
__device__ __forceinline__ void tile_out(unsigned char* (&out)[2], unsigned char* dst, int row0, int perm, const Ctx& c) {
#pragma unroll
    for (int i = 0; i < 2; i++) {
        int row = row0 + 16 * c.warp + 8 * i + (c.lane >> 2);
        if (perm) row = perm32(row);
        out[i] = dst + row * 64 + (((c.lane ^ (row >> 1)) & 3) << 4);
    }
}
__device__ __forceinline__ void store_pair(const float (&a)[64], int q, unsigned char* const (&out)[2], int quarter_stride, const float (&f)[2]) {
#pragma unroll
    for (int i = 0; i < 2; i++)
        stg128(out[i] + q * quarter_stride,
               pack_bf16(a[16 * q + 2 * i] * f[i], a[16 * q + 2 * i + 1] * f[i]), pack_bf16(a[16 * q + 4 + 2 * i] * f[i], a[16 * q + 4 + 2 * i + 1] * f[i]),
               pack_bf16(a[16 * q + 8 + 2 * i] * f[i], a[16 * q + 8 + 2 * i + 1] * f[i]), pack_bf16(a[16 * q + 12 + 2 * i] * f[i], a[16 * q + 12 + 2 * i + 1] * f[i]));
}

constexpr float SAFE_SUM = 1099511627776.0f;
template <int NJ>
__device__ __forceinline__ void row_max(const float (&s)[4 * NJ], float (&mx)[2]) {
#pragma unroll
    for (int i = 0; i < 2; i++) {
        float a = fmaxf(s[2 * i], s[2 * i + 1]), b = fmaxf(s[4 + 2 * i], s[4 + 2 * i + 1]);
#pragma unroll
        for (int j = 2; j < NJ; j += 2) {
            a = fmaxf(a, fmaxf(s[4 * j + 2 * i], s[4 * j + 2 * i + 1]));
            b = fmaxf(b, fmaxf(s[4 * j + 4 + 2 * i], s[4 * j + 4 + 2 * i + 1]));
        }
        a = fmaxf(a, b);
        a = fmaxf(a, __shfl_xor_sync(0xffffffffu, a, 1));
        mx[i] = fmaxf(a, __shfl_xor_sync(0xffffffffu, a, 2));
    }
}
template <int NJ, bool SHIFT>
__device__ __forceinline__ void exp_sum(float (&s)[4 * NJ], const float (&m)[2], float& l0, float& l1) {
#pragma unroll
    for (int j = 0; j < NJ; j++) {
#pragma unroll
        for (int e = 0; e < 4; e++) s[4 * j + e] = ex2(SHIFT ? s[4 * j + e] - m[e >> 1] : s[4 * j + e]);
        l0 += s[4 * j + 0] + s[4 * j + 1]; l1 += s[4 * j + 2] + s[4 * j + 3];
    }
}
__device__ __forceinline__ void recompute_scores(float (&s)[64], const uint32_t (&q)[32], uint32_t kaddr, const Ctx& c) {
    const int r = c.lane & 7, mat = c.lane >> 3;
    const uint32_t a0 = kaddr + (8 * (mat & 1) + r) * 64 + (((mat >> 1) ^ (r >> 1)) << 4);
#pragma unroll
    for (int i = 0; i < 64; i++) s[i] = 0.f;
#pragma unroll
    for (int jp = 0; jp < 8; jp++) {
#pragma unroll
        for (int k = 0; k < 8; k++) {
            asm volatile(
                "{\n.reg .b32 b0, b1, b2, b3;\n"
                "ldmatrix.sync.aligned.m8n8.x4.trans.shared.b16 {b0,b1,b2,b3}, [%12];\n"
                "mma.sync.aligned.m16n8k16.row.col.f32.bf16.bf16.f32 {%0,%1,%2,%3}, {%8,%9,%10,%11}, {b0,b1}, {%0,%1,%2,%3};\n"
                "mma.sync.aligned.m16n8k16.row.col.f32.bf16.bf16.f32 {%4,%5,%6,%7}, {%8,%9,%10,%11}, {b2,b3}, {%4,%5,%6,%7};\n}\n"
                : "+f"(s[8 * jp]), "+f"(s[8 * jp + 1]), "+f"(s[8 * jp + 2]), "+f"(s[8 * jp + 3]),
                  "+f"(s[8 * jp + 4]), "+f"(s[8 * jp + 5]), "+f"(s[8 * jp + 6]), "+f"(s[8 * jp + 7])
                : "r"(q[4 * k]), "r"(q[4 * k + 1]), "r"(q[4 * k + 2]), "r"(q[4 * k + 3]),
                  "r"((a0 ^ ((jp & 1) << 5)) + (jp >> 1) * 8192 + k * 1024) : "memory");
        }
    }
}
__device__ __forceinline__ int mask_lim(const Ctx& c) { return perm32(16 * c.warp + (c.lane >> 2)) - 8 * (c.lane & 3); }
template <int J0>
__device__ __forceinline__ void mask_diag(float (&s)[4 * J0 + 32], const Ctx& c) {
    const int lim = mask_lim(c);
    if (c.warp < 2) {
#pragma unroll
        for (int x = 0; x < 16; x++) {
            if (2 * (x >> 2) + (x & 1) - (x & 2) > lim) s[4 * J0 + x] = -INFINITY;
            s[4 * J0 + 16 + x] = -INFINITY;
        }
    } else {
#pragma unroll
        for (int x = 0; x < 16; x++)
            if (32 + 2 * (x >> 2) + (x & 1) - (x & 2) > lim) s[4 * J0 + 16 + x] = -INFINITY;
    }
}
__device__ __forceinline__ void mask_any(float (&s)[64], int hh, const Ctx& c) {
    const int lim = mask_lim(c) + 64 * hh;
#pragma unroll
    for (int x = 0; x < 64; x++)
        if (32 * (x >> 4) + 2 * ((x >> 2) & 3) + (x & 1) - (x & 2) > lim) s[x] = -INFINITY;
}
__device__ __forceinline__ void issue_pv(float (&o)[64], const uint32_t (&p)[32], uint32_t vaddr, int acc, int mode  ) {
    uint64_t d = mkdesc(vaddr, 16, 512, 2);
    if (mode == 0) {
        wg_fence();
#pragma unroll
        for (int k = 0; k < 8; k++)
            wgmma_rs_n128_ta0_tb0(o, p[4 * k], p[4 * k + 1], p[4 * k + 2], p[4 * k + 3], d + (k >> 1) * 512 + 2 * (k & 1), k ? 1 : acc);
        wg_commit();
    } else if (mode == 1) {
        wg_fence();
#pragma unroll
        for (int k = 0; k < 4; k++) wgmma_rs_n128_ta0_tb0(o, p[4 * k], p[4 * k + 1], p[4 * k + 2], p[4 * k + 3], d + (k >> 1) * 512 + 2 * (k & 1), k != 0);
        wg_commit();
    } else {
        wg_fence();
        wgmma_rs_n128_ta0_tb0(o, p[0], p[1], p[2], p[3], d, acc);
        wg_commit();
    }
}
__device__ __forceinline__ void issue_qk(float (&s)[64], const uint32_t (&q)[32], uint32_t kaddr) {
    uint64_t d = mkdesc(kaddr, 8192, 512, 2);
    wg_fence();
#pragma unroll
    for (int k = 0; k < 8; k++) wgmma_rs_n128_ta0_tb1(s, q[4 * k], q[4 * k + 1], q[4 * k + 2], q[4 * k + 3], d + 64 * k, k != 0);
    wg_commit();
}
__device__ __forceinline__ void issue_qk_half(float (&s32)[32], const uint32_t (&q)[32], uint32_t kaddr) {
    uint64_t d = mkdesc(kaddr, 8192, 512, 2);
    wg_fence();
#pragma unroll
    for (int k = 0; k < 8; k++) wgmma_rs_n64_ta0_tb1(s32, q[4 * k], q[4 * k + 1], q[4 * k + 2], q[4 * k + 3], d + 64 * k, k != 0);
    wg_commit();
}
__device__ __forceinline__ void row_inv(const float (&l)[2], float (&inv)[2]) {
#pragma unroll
    for (int i = 0; i < 2; i++) {
        float sum = l[i];
        sum += __shfl_xor_sync(0xffffffffu, sum, 1);
        sum += __shfl_xor_sync(0xffffffffu, sum, 2);
        inv[i] = rcp_fast(sum);
    }
}

__device__ __forceinline__ const unsigned char* xn_addr(int row, int col) {
    row = perm32(row);
    return g_xn + ((row >> 7) * 10 + (col >> 6)) * 16384 + (row & 127) * 128 + ((((col & 63) >> 3) ^ (row & 7)) << 4);
}
__device__ __forceinline__ void mma16816(float (&d)[4], uint32_t a0, uint32_t a1, uint32_t a2, uint32_t a3, uint32_t b0, uint32_t b1) {
    asm volatile("mma.sync.aligned.m16n8k16.row.col.f32.bf16.bf16.f32 {%0,%1,%2,%3}, {%4,%5,%6,%7}, {%8,%9}, {%0,%1,%2,%3};"
                 : "+f"(d[0]), "+f"(d[1]), "+f"(d[2]), "+f"(d[3]) : "r"(a0), "r"(a1), "r"(a2), "r"(a3), "r"(b0), "r"(b1));
}
__device__ __forceinline__ uint32_t lds32(uint32_t addr) { uint32_t v; asm volatile("ld.shared.u32 %0, [%1];" : "=r"(v) : "r"(addr)); return v; }

__device__ LNINL void ln_rows(const __nv_bfloat16* x, int row0, int lane, uint32_t wr_s) {
    const int hl = lane & 15, row = row0 + (lane >> 4);
    uint32_t v[20];
#pragma unroll
    for (int i = 0; i < 5; i++) {
        uint4 u;
        asm("ld.global.nc.L2::cache_hint.v4.b32 {%0,%1,%2,%3}, [%4], %5;" : "=r"(u.x), "=r"(u.y), "=r"(u.z), "=r"(u.w)
            : "l"(x + (size_t)row * DM + 128 * i + 8 * hl), "l"(policy(HM & 512)));
        v[4 * i] = u.x; v[4 * i + 1] = u.y; v[4 * i + 2] = u.z; v[4 * i + 3] = u.w;
    }
    float mean = 0.f, m2 = 0.f, acc2 = 0.f;
#pragma unroll
    for (int i = 0; i < 20; i++) { mean += bf_lo(v[i]); acc2 += bf_hi(v[i]); }
    mean = (mean + acc2) * (1.0f / 40);
    acc2 = 0.f;
#pragma unroll
    for (int i = 0; i < 20; i++) {
        float d0 = __uint_as_float(__byte_perm(v[i], 0, 0x1044)) - mean, d1 = __uint_as_float(__byte_perm(v[i], 0, 0x3244)) - mean;
        m2 = fmaf(d0, d0, m2); acc2 = fmaf(d1, d1, acc2);
    }
    m2 += acc2;
    acc2 = 0.f;
#pragma unroll
    for (int o = 1; o < 16; o <<= 1) {
        float mo = __shfl_xor_sync(0xffffffffu, mean, o), qo = __shfl_xor_sync(0xffffffffu, m2, o), d = mo - mean;
        m2 = fmaf(d * d, 20.0f * o, m2 + qo);
        mean = 0.5f * (mean + mo);
    }
    const uint32_t mb2 = pack_bf16(mean, mean);
    const float inv = rcp_fast(bf_round(sqrt_fast(bf_round(bf_round(m2 * (1.0f / DM)) + 1e-5f))));
    float dot = 0.f;
    unsigned char* xp = const_cast<unsigned char*>(xn_addr(row, 8 * hl));
#pragma unroll
    for (int i = 0; i < 5; i++) {
        uint32_t ww[4];
        asm volatile("ld.shared.v4.b32 {%0,%1,%2,%3}, [%4];" : "=r"(ww[0]), "=r"(ww[1]), "=r"(ww[2]), "=r"(ww[3]) : "r"(wr_s + 256 * i + 16 * hl) : "memory");
#pragma unroll
        for (int e = 0; e < 4; e++) {
            uint32_t d;
            asm("sub.rn.bf16x2 %0, %1, %2;" : "=r"(d) : "r"(v[4 * i + e]), "r"(mb2));
            d = pack_bf16(bf_lo(d) * inv, bf_hi(d) * inv);
            v[4 * i + e] = d;
            dot = fmaf(bf_lo(d), bf_lo(ww[e]), dot);
            acc2 = fmaf(bf_hi(d), bf_hi(ww[e]), acc2);
        }
        stg128(xp + i * 32768, v[4 * i], v[4 * i + 1], v[4 * i + 2], v[4 * i + 3]);
    }
    dot += acc2;
#pragma unroll
    for (int o = 8; o > 0; o >>= 1) dot += __shfl_xor_sync(0xffffffffu, dot, o);
    if (hl == 0) { g_router[row] = bf_round(dot); g_stats[row] = make_uint2(mb2, __float_as_uint(inv)); }
}

__device__ __forceinline__ void aux_cta(const CUtensorMap* tmG, const CUtensorMap* tmU, const CUtensorMap* tmD, unsigned char* sm, int a) {
    constexpr int STG = 57344, XS = 3 * STG, HS = XS + 8 * 1296, KEY = HS + 8 * 912, MI = KEY + 8192;
    const int tid = threadIdx.x, warp = __shfl_sync(0xffffffffu, tid >> 5, 0), lane = tid & 31;
    const uint32_t sb = smem_u32(sm);
    const uint32_t full = sb + MI, empty = sb + MI + 32;
    int* s_sel = reinterpret_cast<int*>(sm + MI + 64);
    float* s_r = reinterpret_cast<float*>(sm + MI + 96);
    volatile unsigned* s_misc = reinterpret_cast<volatile unsigned*>(sm + MI + 128);
    uint32_t* s_key = reinterpret_cast<uint32_t*>(sm + KEY);
    PROF_DECL(128 + a)
    PROF_GT(0);
    if (tid == 0) {
        for (int i = 0; i < 3; i++) { mbar_init(full + 8 * i, 1); mbar_init(empty + 8 * i, 10); }
        asm volatile("fence.mbarrier_init.release.cluster;" ::: "memory");
    }
    __syncthreads();
    if (warp == 11) {
        if (elect_one()) {
            int st = 0; uint32_t ph = 0;
#pragma unroll 1
            for (int s = 0; s < 34; s++) {
                mbar_wait(empty + 8 * st, ph ^ 1);
                const uint32_t dst = sb + st * STG, fb = full + 8 * st;
                if (s < 20) {
                    mbar_expect_tx(fb, 57344);
                    tma3d(dst, tmG, 0, 32 * s, 7 * a, fb);
                    tma3d(dst + 28672, tmU, 0, 32 * s, 7 * a, fb);
                } else {
                    mbar_expect_tx(fb, 40960);
                    tma3d(dst, tmD, 0, 448 * a + 32 * (s - 20), 0, fb);
                }
                if (s >= 3) {
#pragma unroll 1
                    for (int f = (s == 3 ? 4 : s + 6); f <= s + 6 && f < 34; f++) {
                        if (f < 20) { tma3d_prefetch(tmG, 0, 32 * f, 7 * a); tma3d_prefetch(tmU, 0, 32 * f, 7 * a); }
                        else tma3d_prefetch(tmD, 0, 448 * a + 32 * (f - 20), 0);
                    }
                }
                if (++st == 3) { st = 0; ph ^= 1; }
            }
        }
        return;
    }
    PROF_GT(49);
    if (warp == 10) return;
    if (tid < 8) {
        unsigned e = *reinterpret_cast<volatile unsigned*>(&g_epoch);
        if (tid == 0) s_misc[0] = e;
        flag_wait(flag_ptr(FL_LN + tid), (e + 1) * (tid < 4 ? 33u : 128u));
    }
    bar_sync(1, 320);
    PROF_GT(50);
    const unsigned ep = s_misc[0];
    auto top8 = [&](uint32_t (&key)[8]) {
        uint32_t mine = 0;
#pragma unroll 1
        for (int r = 0; r < TOPC; r++) {
            uint32_t best = 0;
#pragma unroll
            for (int i = 0; i < 8; i++) best = max(best, key[i]);
            best = __reduce_max_sync(0xffffffffu, best);
#pragma unroll
            for (int i = 0; i < 8; i++) if (key[i] == best) key[i] = 0;
            if (lane == r) mine = best;
        }
        return mine;
    };
#pragma unroll 1
    for (int pass = 0; pass < 2; pass++) {
        if (warp < (pass ? 1 : 8)) {
            uint32_t key[8];
#pragma unroll
            for (int i = 0; i < 8; i++) {
                if (pass == 0) {
                    int idx = warp * 256 + i * 32 + lane;
                    uint32_t b = __float_as_uint(__ldcg(g_router + idx)) >> 16;
                    b = (b & 0x8000u) ? (~b & 0xffffu) : (b | 0x8000u);
                    key[i] = (b << 16) | (uint32_t)(0xffff - idx);
                } else key[i] = i < 2 ? s_key[i * 32 + lane] : 0u;
            }
            uint32_t best = top8(key);
            if (lane < TOPC) {
                if (pass == 0) s_key[warp * 8 + lane] = best;
                else {
                    uint32_t b = best >> 16;
                    b = (b & 0x8000u) ? (b & 0x7fffu) : (~b & 0xffffu);
                    s_sel[lane] = 0xffff - (int)(best & 0xffffu);
                    s_r[lane] = bf_round(rcp_fast(1.0f + __expf(fminf(-__uint_as_float(b << 16), 80.f))));
                }
            }
        }
        bar_sync(1, 320);
    }
#pragma unroll 1
    for (int it = 0; it < 2; it++) {
        int i = tid + it * 320, tk = i / 80, ch = i % 80;
        *reinterpret_cast<uint4*>(sm + XS + tk * 1296 + ch * 16) = __ldcg(reinterpret_cast<const uint4*>(xn_addr(s_sel[tk], ch * 8)));
    }
    bar_sync(1, 320);
    PROF_GT(51);
    const int g = lane >> 2, t = lane & 3;
    const uint32_t woff = warp * 4096 + (8 * (lane >> 4) + (lane & 7)) * 128 + ((((lane >> 3) & 1) ^ (lane & 7)) << 4);
    int st = 0; uint32_t ph = 0;
    float ga[4][4], ua[4][4];
#pragma unroll
    for (int i = 0; i < 4; i++)
#pragma unroll
        for (int e = 0; e < 4; e++) { ga[i][e] = 0.f; ua[i][e] = 0.f; }
#pragma unroll 1
    for (int s = 0; s < 34; s++) {
        if (s == 20) {
            if (warp < 7) {
#pragma unroll 1
                for (int i = 0; i < 4; i++) {
#pragma unroll
                    for (int e = 0; e < 4; e++) {
                        float gv = bf_round(ga[0][e]), uv = bf_round(ua[0][e]);
                        float sg = bf_round(gv * rcp_fast(1.0f + __expf(fminf(-gv, 80.f))));
                        int f = warp * 64 + i * 16 + g + 8 * (e >> 1), tk = 2 * t + (e & 1);
                        *reinterpret_cast<__nv_bfloat16*>(sm + HS + tk * 912 + f * 2) = __float2bfloat16_rn(sg * uv);
                        ga[0][e] = ga[1][e]; ga[1][e] = ga[2][e]; ga[2][e] = ga[3][e]; ga[3][e] = 0.f;
                        ua[0][e] = ua[1][e]; ua[1][e] = ua[2][e]; ua[2][e] = ua[3][e];
                    }
                }
            }
            bar_sync(1, 320);
            PROF_GT(52);
        }
        mbar_wait(full + 8 * st, ph);
        if (s >= 20 || warp < 7) {
#pragma unroll
            for (int kk = 0; kk < 2; kk++) {
                uint32_t xb = sb + (s < 20 ? XS + g * 1296 + s * 64 : HS + g * 912 + (s - 20) * 64) + 32 * kk + 4 * t;
                uint32_t b0 = lds32(xb), b1 = lds32(xb + 16);
                uint32_t wa = sb + st * STG + woff + kk * 2048;
#pragma unroll
                for (int i = 0; i < 4; i++) {
                    uint32_t a0, a1, a2, a3;
                    ldsm4t(a0, a1, a2, a3, wa ^ (i << 5));
                    mma16816(ga[i], a0, a1, a2, a3, b0, b1);
                    if (s < 20) {
                        ldsm4t(a0, a1, a2, a3, (wa ^ (i << 5)) + 28672);
                        mma16816(ua[i], a0, a1, a2, a3, b0, b1);
                    }
                }
            }
        }
        asm volatile("fence.proxy.async.shared::cta;" ::: "memory");
        __syncwarp();
        if (lane == 0) mbar_arrive(empty + 8 * st);
        if (++st == 3) { st = 0; ph ^= 1; }
    }
#pragma unroll
    for (int i = 0; i < 4; i++)
#pragma unroll
        for (int e = 0; e < 4; e += 2)
            *reinterpret_cast<float2*>(g_moe_part + (a * DM + warp * 64 + i * 16 + g + 4 * e) * 8 + 2 * t) = make_float2(ga[i][e], ga[i][e + 1]);
    bar_sync(1, 320);
    if (tid == 0) {
        __threadfence();
        unsigned old = atomicAdd(flag_ptr(FL_MOE_CNT), 1u);
        s_misc[1] = (old == ep * 4u + 3u);
        __threadfence();
    }
    bar_sync(1, 320);
    PROF_GT(53);
    if (s_misc[1]) {
        const float4* pp = reinterpret_cast<const float4*>(g_moe_part);
#pragma unroll 1
        for (int i = tid; i < DM * 2; i += 320) {
            float4 v0 = __ldcg(pp + i), v1 = __ldcg(pp + DM * 2 + i), v2 = __ldcg(pp + DM * 4 + i), v3 = __ldcg(pp + DM * 6 + i);
            float y[4] = {v0.x + v1.x + v2.x + v3.x, v0.y + v1.y + v2.y + v3.y, v0.z + v1.z + v2.z + v3.z, v0.w + v1.w + v2.w + v3.w};
#pragma unroll
            for (int e = 0; e < 4; e++) {
                int col = i >> 1, tk = (i & 1) * 4 + e;
                float upd = bf_round(bf_round(y[e]) * s_r[tk]);
                float xn = __bfloat162float(*reinterpret_cast<const __nv_bfloat16*>(sm + XS + tk * 1296 + col * 2));
                g_brow[tk * DM + col] = __float2bfloat16_rn(xn + upd);
            }
        }
        if (tid < TOPC) g_sel[tid] = s_sel[tid];
        bar_sync(1, 320);
        if (tid == 0) {
            flag_signal(flag_ptr(FL_MOE_DONE));
            *reinterpret_cast<volatile unsigned*>(&g_epoch) = ep + 1;
        }
        PROF_GT(54);
    }
}

__global__ void __cluster_dims__(2, 1, 1) __launch_bounds__(384, 1)
fused_kernel(const __grid_constant__ CUtensorMap tmC, const __grid_constant__ CUtensorMap tmWk, const __grid_constant__ CUtensorMap tmWv,
             const __grid_constant__ CUtensorMap tmWq, const __grid_constant__ CUtensorMap tmWo,
             const __grid_constant__ CUtensorMap tmG, const __grid_constant__ CUtensorMap tmU, const __grid_constant__ CUtensorMap tmD, const Params P) {
    extern __shared__ __align__(1024) unsigned char smem_raw[];
    const uint32_t ring = smem_u32(smem_raw);
    const uint32_t misc = ring + RING_BYTES;
    const int tid = threadIdx.x;
    const int rank = blockIdx.x & 1;
    uint32_t smid, nsm;
    asm("mov.u32 %0, %%smid;" : "=r"(smid));
    asm("mov.u32 %0, %%nsmid;" : "=r"(nsm));
    if (nsm != 132) smid = blockIdx.x;
    auto role_of = [](int tpc) {
        return tpc < 32 ? (tpc & 7) * 8 + (tpc >> 3) : tpc < 60 ? (1 + (tpc - 32) % 7) * 8 + 4 + (tpc - 32) / 7 : tpc < 64 ? tpc - 56 : tpc;
    };
    int mc = role_of(smid >> 1);
    PROF_DECL(mc * 2 + rank)
    PROF_GT(0); PROF_EV(1);

    auto prefetch_w = [&](int ch) {
        const int i = tid - 128;
        asm volatile("prefetch.global.L2 [%0];" ::"l"((rank ? P.wv : P.wk) + (size_t)(ch * 128 + (mc & 3) * 32 + (i >> 3)) * 4096 + (mc >> 2) * 256 + (i & 7) * 16));
    };
    if (tid >= 128 && mc < 64) {
        if (tid < 256) asm volatile("prefetch.global.L2 [%0];" ::"l"(P.c + (size_t)((12 + (mc & 3)) * 128 + ((mc >> 2) * 2 + rank) * 4) * DC + (tid - 128) * 16));
        prefetch_w(0);
    }
    auto load_w0 = [&]() {
        const CUtensorMap* tw = rank ? &tmWv : &tmWk;
        mbar_expect_tx(misc + BAR_FULL + 8 * slot_of(0), SLOT_BYTES);
        tma2d(ring + slot_of(0) * SLOT_BYTES, tw, (mc >> 2) * 256, 0, misc + BAR_FULL + 8 * slot_of(0), policy(HM & 1));
        tma2d(ring + slot_of(0) * SLOT_BYTES + 16384, tw, (mc >> 2) * 256 + 64, 0, misc + BAR_FULL + 8 * slot_of(0), policy(HM & 1));
    };
    if (tid == 0) {
#pragma unroll
        for (int i = 0; i < NSLOT; i++) mbar_init(misc + BAR_FULL + 8 * i, 1);
#pragma unroll
        for (int i = 0; i < E0; i++) mbar_arrive(misc + BAR_FULL + 8 * i);
        asm volatile("fence.mbarrier_init.release.cluster;" ::: "memory");
        if (mc < 64) load_w0();
    }
    if (tid == 160) {
        asm volatile("st.shared.u32 [%0], %1;" ::"r"(misc + MISC_SMID), "r"(smid) : "memory");
        asm volatile("fence.release.sync_restrict::shared::cta.cluster;" ::: "memory");
    }
    if (tid == 32) {
        asm volatile("prefetch.tensormap [%0];" ::"l"(&tmC) : "memory");
#pragma unroll
        for (int i = 0; i < NSLOT; i++) mbar_init(misc + BAR_EMPTY + 8 * i, 16);
#pragma unroll
        for (int i = 0; i < E0; i++) mbar_arrive_cluster(misc + BAR_EMPTY + 8 * i, 16);
        asm volatile("fence.mbarrier_init.release.cluster;" ::: "memory");
    }
    if (tid == 64) {
#pragma unroll
        for (int i = 0; i < NST3; i++) { mbar_init(misc + BAR_FULL3 + 8 * i, 1); mbar_init(misc + BAR_EMPTY3 + 8 * i, 16); }
#pragma unroll
        for (int i = 0; i < 4; i++) mbar_init(misc + BAR_LN + 8 * i, 2);
        mbar_init(misc + BAR_PROG, 1); mbar_init(misc + BAR_PROG + 8, 1); mbar_init(misc + BAR_PROG + 16, 1);
        asm volatile("fence.mbarrier_init.release.cluster;" ::: "memory");
    }
    if (tid == 96) {
#pragma unroll
        for (int i = 0; i < 34; i++) mbar_init(misc + BAR_DEP + 8 * i, 1);
    }
    if (tid == 128) {
#pragma unroll
        for (int i = 0; i < 32; i++) mbar_init(misc + BAR_EV + 8 * i, 4);
    }
    __syncthreads();
    asm volatile("barrier.cluster.arrive.relaxed.aligned;\nbarrier.cluster.wait.aligned;" ::: "memory");
    {
        uint32_t peer;
        asm volatile("ld.shared::cluster.u32 %0, [%1];" : "=r"(peer) : "r"(mapa(misc + MISC_SMID, rank ^ 1)) : "memory");
        if ((__shfl_sync(0xffffffffu, peer, 0) ^ smid) != 1) {
            if (tid == 0) {
                const unsigned ep1 = *reinterpret_cast<volatile unsigned*>(&g_epoch) + 1;
                if ((smid & 1) == 0) atomicExch(g_roleq + 2 + (atomicAdd(g_roleq, 1u) & 127), (ep1 << 8) | (smid >> 1));
                if (rank == 0) {
                    unsigned* slot = g_roleq + 2 + (atomicAdd(g_roleq + 1, 1u) & 127);
                    unsigned v = 0;
                    for (int spin = 0; spin < 4000000 && ((v = atomicAdd(slot, 0u)) >> 8) != (ep1 & 0xffffffu); spin++) {}
                    asm volatile("st.shared::cluster.u32 [%0], %1;" ::"r"(mapa(misc + MISC_SMID + 4, 0)), "r"(v & 255) : "memory");
                    asm volatile("st.shared::cluster.u32 [%0], %1;" ::"r"(mapa(misc + MISC_SMID + 4, 1)), "r"(v & 255) : "memory");
                }
                if (mc < 64) {
                    mbar_wait(misc + BAR_FULL + 8 * slot_of(0), 0);
                    asm volatile("mbarrier.inval.shared::cta.b64 [%0];" ::"r"(misc + BAR_FULL + 8 * slot_of(0)) : "memory");
                    mbar_init(misc + BAR_FULL + 8 * slot_of(0), 1);
                    asm volatile("fence.mbarrier_init.release.cluster;" ::: "memory");
                }
            }
            __syncwarp();
            asm volatile("barrier.cluster.arrive.aligned;\nbarrier.cluster.wait.aligned;" ::: "memory");
            mc = role_of(__shfl_sync(0xffffffffu, lds32(misc + MISC_SMID + 4), 0));
            if (tid == 0 && mc < 64) load_w0();
            __syncwarp();
        }
    }
    const int cta = mc * 2 + rank;
    const bool aux = mc >= 64;
    const int team = mc >> 2, k = mc & 3;
    const int u3 = (mc >> 4) * 2 + (team & 1), s3 = k, kap = (mc >> 3) & 1;
    const int partner = cta ^ 16;
    const int b0 = k, b1 = 7 - k;
    if (tid >= 128 && !aux) prefetch_w(1);
    if (tid == 256 && !aux) {
        const CUtensorMap* tw = rank ? &tmWv : &tmWk;
#pragma unroll
        for (int e = 1; e < NSLOT; e++) {
            const uint32_t fb = misc + BAR_FULL + 8 * slot_of(e), dst = ring + slot_of(e) * SLOT_BYTES;
            mbar_expect_tx(fb, SLOT_BYTES);
            if (e & 1) tma2d_mc(dst + rank * 16384, &tmC, (e >> 1) * 128 + rank * 64, (12 + k) * 128, fb, policy(false));
            else { tma2d(dst, tw, team * 256, e * 64, fb, policy(false)); tma2d(dst + 16384, tw, team * 256 + 64, e * 64, fb, policy(false)); }
        }
    }
    PROF_EV(5);
    const int wg = __shfl_sync(0xffffffffu, tid >> 7, 0);

    if (wg == 0 || aux) {
        asm volatile("setmaxnreg.dec.sync.aligned.u32 40;");
        const int warp = __shfl_sync(0xffffffffu, tid >> 5, 0), lane = tid & 31;
        if (warp == 0 && !aux) {
            const bool lead = elect_one();
            Cur c = cur_at(NSLOT);
            uint32_t dst, fb;
            auto acquire = [&]() {
                mbar_wait_sleep(misc + BAR_EMPTY + 8 * c.slot, c.ph ^ 1);
                fb = misc + BAR_FULL + 8 * c.slot; dst = ring + c.slot * SLOT_BYTES;
                if (lead) mbar_expect_tx(fb, SLOT_BYTES);
                c.adv();
            };
            auto load_w = [&](const CUtensorMap* tm, int col, int row, bool stream) {
                acquire();
                if (lead) { tma2d(dst, tm, col, row, fb, policy(stream)); tma2d(dst + 16384, tm, col + 64, row, fb, policy(stream)); }
            };
            auto load_half = [&](const unsigned char* src, bool stream) {
                acquire();
                if (lead) bulk_load_mc(dst + rank * 16384, src, 16384, fb, policy(stream));
            };
            auto dep_wait = [&](int d) { mbar_wait_sleep(misc + BAR_DEP + 8 * d, 0); fence_async_global(); };
            auto op_prefetch = [&](int i) {
                const int head = op_head(i, kap);
                l2_prefetch(reinterpret_cast<const unsigned char*>(P.wo) + head * 163840 + (u3 * 8 + s3 * 2 + rank) * 2560, 2560);
                if (i < 8) l2_prefetch(g_ctx + (size_t)(head * 32 + 4 * u3 + 2 * rank) * 16384 + s3 * 8192, 8192);
            };
            __nanosleep(CDELAY);
            if (lead) l2_prefetch(reinterpret_cast<const unsigned char*>(P.c) + (size_t)cta * 12288, 12288);
            const CUtensorMap* tw = rank ? &tmWv : &tmWk;
            const unsigned char* Kh = g_K + (size_t)team * 32 * 16384 + rank * 16384;
            const unsigned char* Vh = g_V + (size_t)team * 32 * 16384 + rank * 16384;
#pragma unroll 1
            for (int v = 0; v < 2; v++) {
                const int h = 2 * team + v;
#pragma unroll 1
                for (int i = v ? 0 : 3; i < 16; i++) {
                    if (i < 4 && v) load_w(tw, h * 128, i * 128, HM & 1);
                    if (v && i == 3 && lead) mbar_arrive(misc + BAR_PROG + 8);
                    if (v && (i == 3 || i == 7)) dep_wait(D_WAR + (i > 3));
                    acquire();
                    if (lead) tma2d_mc(dst + rank * 16384, &tmC, (i & 3) * 128 + rank * 64, (kv_tile(i >> 2) + k) * 128, fb, policy(HM & 2));
                    if (i == 8 && lead) {
                        tma2d_prefetch(&tmWq, h * 128 + rank * 64, k * 64); tma2d_prefetch(&tmWq, h * 128 + rank * 64, k * 64 + 256);
                        if (k < 2) tma2d_prefetch(&tmWq, h * 128 + rank * 64, k * 64 + 512);
                        if (v) l2_prefetch(g_xn + cta * 10240, 10240);
                    }
                }
                int togo = v ? PF_START : 11;
#pragma unroll 1
                for (int r = 0; r < 2; r++) {
                    const int p = r ? b1 : b0, n = 2 * p + 1;
                    if (v == 0) dep_wait(D_LN + r);
                    const int g0 = r ? rank ^ SWAPT : 3 - rank, g1 = 3 - g0;
                    const unsigned char* x0 = g_xn + (2 * p + (g0 >> 1)) * 163840 + (g0 & 1) * 8192;
                    const unsigned char* x1 = g_xn + (2 * p + (g1 >> 1)) * 163840 + (g1 & 1) * 8192;
#pragma unroll 1
                    for (int kc = 0; kc < 10; kc++) {
                        acquire();
                        if (lead) {
                            tma2d_mc(dst + 16384 + rank * 8192, &tmWq, h * 128 + rank * 64, kc * 64, fb, policy(false));
                            bulk_load(dst, x0 + kc * 16384, 8192, fb, policy(false));
                            bulk_load(dst + 8192, x1 + kc * 16384, 8192, fb, policy(false));
                        }
                    }
                    dep_wait(D_KV + 2 * v + r);
                    load_half(Kh + n * 32768, HM & 16);
#pragma unroll 1
                    for (int j = n - 1; j >= 0; j--) {
                        load_half(Kh + j * 32768, HM & 16); load_half(Vh + (j + 1) * 32768, HM & 16);
                        if (v == 0 && r && j == 7 && lead) mbar_arrive(misc + BAR_PROG);
                        --togo;
                        if (v == 0 && togo == 0 && lead) {
                            tma2d_prefetch(tw, h * 128 + 128, k * 128); tma2d_prefetch(tw, h * 128 + 192, k * 128);
                            l2_prefetch(reinterpret_cast<const unsigned char*>(P.c) + (size_t)cta * 16384, 16384);
                        }
                        if (v && togo <= 0 && togo > -OP_PF && lead) op_prefetch(-togo);
                    }
                    load_half(Vh, HM & 16);
                }
            }
            mbar_wait_sleep(misc + BAR_EMPTY + 8 * c.slot, c.ph ^ 1); c.adv();
            int st = 0; uint32_t ph3 = 0;
#pragma unroll 1
            for (int i = 0; i < 32; i++) {
                const int head = op_head(i >> 1, kap);
                if ((i & 1) == 0) dep_wait(D_CTX + (i >> 1));
                if (i < NST3) { mbar_wait_sleep(misc + BAR_EMPTY + 8 * c.slot, c.ph ^ 1); c.adv(); }
                else mbar_wait_sleep(misc + BAR_EMPTY3 + 8 * st, ph3 ^ 1);
                fb = misc + BAR_FULL3 + 8 * st; dst = ring + st * ST3_BYTES;
                if (i == LATE_AT && lead) mbar_arrive(misc + BAR_PROG + 16);
                if (lead) {
                    mbar_expect_tx(fb, ST3_BYTES);
                    const unsigned char* src = g_ctx + (size_t)(head * 32 + 4 * u3 + 2 * rank) * 16384 + (i & 1) * 8192;
                    bulk_load(dst, src, 8192, fb, policy(HM & 32));
                    bulk_load(dst + 8192, src + 16384, 8192, fb, policy(HM & 32));
                    tma3d_mc(dst + 16384 + rank * 10240, &tmWo, 0, head * 128 + (i & 1) * 64 + rank * 32, 5 * s3, fb, policy(HM & 32));
                    if ((i & 1) && (i >> 1) + OP_PF < 16) op_prefetch((i >> 1) + OP_PF);
                }
                if (++st == NST3) { st = 0; ph3 ^= 1; }
            }
        } else {
        if (warp >= 1 && warp <= 3 && lane < 27 && (warp - 1) * 27 + lane < 80) {
            const int ch = (warp - 1) * 27 + lane;
            uint4 u = __ldg(reinterpret_cast<const uint4*>(P.wr) + ch);
            asm volatile("st.shared.v4.b32 [%0], {%1,%2,%3,%4};" ::"r"(misc + MISC_WR + 16 * ch), "r"(u.x), "r"(u.y), "r"(u.z), "r"(u.w) : "memory");
        }
        if (aux) __nanosleep(AUXDELAY);
        bar_sync(3, aux ? 384 : 96);
        const int nln = aux ? (warp < 8 ? 3 : 2) : (warp == 3 ? 1 : 3), rstep = aux ? 24 : -512;
        int lrow = aux ? (cta - 128) * 256 + 192 + 2 * warp : (cta >> 5) * 256 + (cta & 31) * 6 + (warp - 1) * 2;
        int lnext = aux ? lrow + 24 : 1536 + cta * 4 + (warp - 1) * 2;
#pragma unroll 1
        for (int t = 0; t < nln; t++) {
            if (t + 1 < nln) {
#pragma unroll
                for (int i = 0; i < 3; i++)
                    if (i * 32 + lane < 80) asm volatile("prefetch.global.L2 [%0];" ::"l"(P.x + (size_t)lnext * DM + (i * 32 + lane) * 16));
            }
            ln_rows(P.x, lrow, lane, misc + MISC_WR);
            __syncwarp();
            if (lane == 0 && warp < 3 && !aux) {
                if (t) flag_signal(flag_ptr(FL_LN + (lrow >> 8))); else mbar_arrive(misc + BAR_LN);
            }
            lrow = lnext; lnext += rstep;
        }
        if (aux) {
            bar_sync(3, 384);
            if (tid == 320) flag_signal(flag_ptr(FL_LN + cta - 128));
            __syncwarp();
            asm volatile("setmaxnreg.inc.sync.aligned.u32 128;");
            aux_cta(&tmG, &tmU, &tmD, smem_raw, cta - 128);
        } else
        if (warp == 3) {
            const unsigned ep1 = *reinterpret_cast<volatile unsigned*>(&g_epoch) + 1;
            if (lane == 0) {
                asm volatile("st.shared.u32 [%0], %1;" ::"r"(misc + MISC_EPOCH), "r"(ep1) : "memory");
                mbar_wait(misc + BAR_LN, 0);
                flag_signal(flag_ptr(FL_LN + (cta >> 5)));
                flag_wait(flag_ptr(FL_LN + b0), ep1 * 33u);
                mbar_arrive(misc + BAR_DEP + 8 * D_LN);
#pragma unroll 1
                for (int i = 0; i < 4; i++) {
                    mbar_wait(misc + BAR_EV + 8 * (16 + EV_KV + i), 0);
                    if (i < 2) {
                        mbar_wait(misc + BAR_EV + 8 * (EV_KV + i), 0);
                        asm volatile("red.release.gpu.global.add.u32 [%0], 2;" ::"l"(flag_ptr(FL_KV + team * 8 + i)) : "memory");
                    }
                    if (i == 1) {
                        flag_wait(flag_ptr(FL_LN + b1), ep1 * 128u);
                        mbar_arrive(misc + BAR_DEP + 8 * (D_LN + 1));
                    }
                    flag_wait(flag_ptr(FL_KV + team * 8 + i), ep1 * 16u);
                    mbar_arrive(misc + BAR_DEP + 8 * (D_KV + i));
                    if (i == 1) {
#pragma unroll 1
                        for (int j = 0; j < 2; j++) {
                            mbar_wait(misc + BAR_PROG + 8 * j, 0);
                            asm volatile("red.relaxed.gpu.global.add.u32 [%0], 1;" ::"l"(flag_ptr(FL_WAR + 2 * team + j)) : "memory");
                            flag_wait(flag_ptr(FL_WAR + 2 * team + j), ep1 * 8u);
                            mbar_arrive(misc + BAR_DEP + 8 * (D_WAR + j));
                        }
                    }
                }
                flag_wait(flag_ptr(FL_MOE_DONE), ep1);
                int4 s0 = __ldcg(reinterpret_cast<const int4*>(g_sel)), s1 = __ldcg(reinterpret_cast<const int4*>(g_sel) + 1);
                asm volatile("st.shared.v4.u32 [%0], {%1,%2,%3,%4};" ::"r"(misc + MISC_SEL), "r"(s0.x), "r"(s0.y), "r"(s0.z), "r"(s0.w) : "memory");
                asm volatile("st.shared.v4.u32 [%0], {%1,%2,%3,%4};" ::"r"(misc + MISC_SEL + 16), "r"(s1.x), "r"(s1.y), "r"(s1.z), "r"(s1.w) : "memory");
                mbar_arrive(misc + BAR_SEL);
            }
            __syncwarp();
            const unsigned* cf = flag_ptr(FL_CTX + op_head(lane & 15, kap) * 8 + u3);
#pragma unroll 1
            for (int half = 0; half < 2; half++) {
                if (half) mbar_wait(misc + BAR_EV + 8 * (EV_CTX + 3), 0);
                bool done = (lane >> 3) != half;
                for (int spin = 0; spin < 4000000; spin++) {
                    if (!done) {
                        unsigned v;
                        asm volatile("ld.acquire.gpu.global.u32 %0, [%1];" : "=r"(v) : "l"(cf) : "memory");
                        if ((int)(v - ep1 * 4u) >= 0) { mbar_arrive(misc + BAR_DEP + 8 * (D_CTX + lane)); done = true; }
                    }
                    if (__all_sync(0xffffffffu, done)) break;
                    __nanosleep(64);
                }
            }
        } else {
            const int w = warp - 1;
            if (lane == 0) {
                const uint32_t eb = misc + BAR_EV + w * 128;
#pragma unroll 1
                for (int i = 0; i < 6; i++) {
                    const bool kv = (i >> 1) == 1;
                    const int ci = i < 2 ? i : i - 2;
                    mbar_wait(eb + 8 * (kv ? EV_KV + i : EV_CTX + ci), 0);
                    if (i == 1) {
                        asm volatile("cp.async.bulk.global.shared::cta.bulk_group [%0], [%1], 16384;"
                                     ::"l"(g_ctx + (size_t)(2 * team * 32 + 4 * b1 + (w ? 3 - (rank ^ SWAPT) : rank ^ SWAPT)) * 16384),
                                       "r"(ring + slot_of(78) * SLOT_BYTES + w * 16384) : "memory");
                        asm volatile("cp.async.bulk.commit_group;" ::: "memory");
                        asm volatile("cp.async.bulk.wait_group.read 0;" ::: "memory");
                        mbar_arrive_cluster(mapa(misc + BAR_EMPTY + 8 * slot_of(78), 0), 4);
                        mbar_arrive_cluster(mapa(misc + BAR_EMPTY + 8 * slot_of(78), 1), 4);
                        asm volatile("cp.async.bulk.wait_group 0;" ::: "memory");
                        fence_async_global();
                    }
                    flag_signal(flag_ptr(kv ? FL_KV + team * 8 + i : FL_CTX + (2 * team + (ci >> 1)) * 8 + ((ci & 1) ? b1 : b0)));
                }
            }
            __syncwarp();
            mbar_wait(misc + BAR_PROG + 16, 0);
            const int row = (2 * u3 + rank) * 128 + 64 * w + perm32(16 * (lane >> 3) + 8 * kap + (lane & 7));
#pragma unroll
            for (int i = 0; i < 10; i++) asm volatile("prefetch.global.L2 [%0];" ::"l"(P.x + (size_t)row * DM + 160 * s3 + 16 * i));
            asm volatile("prefetch.global.L2 [%0];" ::"l"(g_stats + row));
            mbar_wait(misc + BAR_EV + w * 128 + 8 * EV_END, 0);
        }
        }
    } else {
        asm volatile("setmaxnreg.inc.sync.aligned.u32 232;");
        Ctx c;
        c.ring = ring; c.misc = misc; c.w = wg - 1; c.warp = __shfl_sync(0xffffffffu, (tid >> 5) & 3, 0); c.lane = tid & 31;
        c.rel = mapa(misc, tid & 1);
        const int w = c.w;
        if (w == 1) bar_arrive(1, 256);
        prefetch_w(2); prefetch_w(3);
        Cur cur = cur_at(0);
        float o[64], inv[2];
        unsigned char* out[2];
        uint32_t wf[128];
        Cur cw = cur;
        auto load_wchunk = [&](auto CH) {
            constexpr int ch = decltype(CH)::value;
            mbar_wait_hot(misc + BAR_FULL + 8 * cw.slot, cw.ph);
            const uint32_t z = load_afrag<8, 32 * ch>(wf, ring + cw.slot * SLOT_BYTES + w * 16384, c);
            release(c, BAR_EMPTY + 8 * cw.slot + z, 1);
            cw.adv(); cw.adv();
        };
#pragma unroll
        for (int i = 32; i < 64; i++) wf[i] = 0u;
        load_wchunk(IC<0>{});
#pragma unroll 1
        for (int v = 0; v < 2; v++) {
        {
            float (&acc)[64] = o;
#pragma unroll
            for (int i = 64; i < 128; i++) wf[i] = 0u;
            cur.adv();
            inv[0] = inv[1] = rank ? 1.0f : SM_SCALE;
            PROF_EV(2); PROF_GT(60);
#pragma unroll 1
            for (int t = 0; t < 4; t++) {
                uint32_t last = 0;
                token_wait(w);
                PROF_EV(10);
                undef_regs(acc);
                auto chunk = [&](auto CH) {
                    constexpr int ch = decltype(CH)::value;
                    mbar_wait_hot(misc + BAR_FULL + 8 * cur.slot, cur.ph);
                    if (t == 0) { PROF_EV(12 + ch); }
                    uint64_t d = mkdesc(ring + cur.slot * SLOT_BYTES, 16, 1024, 1);
                    wg_fence();
#pragma unroll
                    for (int ks = 0; ks < 8; ks++)
                        wgmma_rs_n128_ta0_tb0(acc, wf[32 * ch + 4 * ks], wf[32 * ch + 4 * ks + 1], wf[32 * ch + 4 * ks + 2], wf[32 * ch + 4 * ks + 3],
                                              d + (ks >> 2) * 1024 + (ks & 3) * 2, (ch | ks) != 0);
                    wg_commit();
                    if (ch == 3 || (ch < 2 && t == 0)) token_pass(w);
                    if constexpr (ch == 0) { if (t == 0) { if (v) load_wchunk(IC<2>{}); else load_wchunk(IC<1>{}); } }
                    if constexpr (ch == 1) { if (t == 0 && !v) load_wchunk(IC<2>{}); }
                    if constexpr (ch == 2) { if (t == 0 && !(w | v)) load_wchunk(IC<3>{}); }
                    if (ch > 0) { wg_wait<1>(); release(c, BAR_EMPTY + 8 * last, 1); }
                    last = cur.slot;
                    cur.adv();
                    if (ch < 3 && t == 0) cur.adv();
                    if constexpr (ch == 1) { if (t == 0 && (w | v)) load_wchunk(IC<3>{}); }
                    if (ch < 2 && t == 0) token_wait(w);
                };
                chunk(IC<0>{}); chunk(IC<1>{}); chunk(IC<2>{}); chunk(IC<3>{});
                wg_wait<0>();
                release(c, BAR_EMPTY + 8 * last, 1);
                PROF_EV(11);
                fence_regs(acc);
                tile_out(out, (rank ? g_V : g_K) + (size_t)(team * 32 + 2 * (kv_tile(t) + k)) * 16384, 64 * w, rank, c);
                if (DEFER && t == 3 && w) break;
#pragma unroll
                for (int i = 0; i < 4; i++) store_pair(acc, i, out, 8192, inv);
                if (t >= 2) signal_event(c, EV_KV + 2 * v + t - 2);
            }
            PROF_EV(61); PROF_GT(62);
        }
        PROF_EV(63); PROF_GT(64);
        {
            uint32_t q[32], p[32];
            float m[2], l[2];
#pragma unroll
            for (int i = 0; i < 32; i++) p[i] = 0u;
            l[0] = l[1] = 1.f;
            int pv_acc = 1, pv_mode = 2;
#pragma unroll 1
            for (int r = 0; r < 2; r++) {
                const int heavy = 1 ^ r ^ w;
                const int half = 1 ^ heavy ^ rank ^ (r & SWAPT);
                int left = 2 * (r ? b1 : b0) + 1 + heavy;
                Cur ck, cv = cur;
                {
                    float s[64];
                    if (r) cur.adv();
                    mbar_wait_hot(misc + BAR_FULL + 8 * cv.slot, cv.ph);
                    token_wait(w);
                    PROF_EV(20);
                    issue_pv(o, p, ring + cv.slot * SLOT_BYTES, pv_acc, pv_mode);
                    undef_regs(s);
                    uint32_t prev;
                    auto qchunk = [&](int acc) {
                        mbar_wait_hot(misc + BAR_FULL + 8 * cur.slot, cur.ph);
                        const uint64_t da = mkdesc(ring + cur.slot * SLOT_BYTES + w * 8192, 16, 1024, 1);
                        const uint64_t db = mkdesc(ring + cur.slot * SLOT_BYTES + 16384, 8192, 1024, 1);
                        wg_fence();
#pragma unroll
                        for (int ks = 0; ks < 4; ks++) wgmma_ss_n128_ta0_tb1(s, da + 2 * ks, db + 128 * ks, ks ? 1 : acc);
                        wg_commit();
                    };
                    qchunk(0);
                    prev = cur.slot; cur.adv();
                    token_pass(w);
                    if (r) {
                        row_inv(l, inv);
                        tile_out(out, g_ctx + (size_t)((2 * team + v) * 32 + 4 * b0 + (w ? rank : 3 - rank)) * 16384, 0, 0, c);
                    }
                    const int epi = r | (w & DEFER), hs = r ? 4096 : 8192;
                    const int hold = heavy ? -10 : half ? HOLD0 : 8;
#pragma unroll
                    for (int kc = 1; kc < 10; kc++) {
                        if (HOLD0 && kc >= HOLD0 && (kc == hold || kc == hold + 2)) token_wait(w);
                        qchunk(1);
                        if (HOLD0 && kc > HOLD0 && kc == hold + 1) token_pass(w);
                        if (HOLD0 && kc == 9 && heavy) { token_wait(w); token_pass(w); }
                        wg_wait<1>();
                        release(c, BAR_EMPTY + 8 * prev, 1);
                        prev = cur.slot; cur.adv();
                        if (kc == 1) { fence_regs(o); if (r) release(c, BAR_EMPTY + 8 * cv.slot, 1); }
                        if (kc <= 4 && epi) {
                            store_pair(o, kc - 1, out, hs, inv);
                            if (kc == 4) signal_event(c, r ? EV_CTX + 2 * v : EV_KV + 2 * v + 1);
                        }
                    }
                    if (!heavy) cur.adv();
                    ck = cur;
                    cur.adv();
                    if (!heavy) cur.adv();
                    wg_wait<0>();
                    release(c, BAR_EMPTY + 8 * prev, 1);
                    PROF_EV(21);
                    fence_regs(s);
#pragma unroll
                    for (int i = 0; i < 32; i++) q[i] = pack_bf16(s[2 * i], s[2 * i + 1]);
                }
                cv = ck;
                int first = 1, gen = 0;
                uint32_t pv_cnt = 0;
                pv_acc = 0; pv_mode = 2;
                l[0] = l[1] = m[0] = m[1] = 0.f;
                mbar_wait_hot(misc + BAR_FULL + 8 * ck.slot, ck.ph);
#pragma unroll 1
                while (true) {
                    float s[64];
                    if (half & first) {
                        if (heavy || HOLD0 == 0 || HOLD0 == 8) token_wait(w);
                        PROF_EV(30);
                        float sh[32];
                        undef_regs(sh);
                        issue_qk_half(sh, q, ring + ck.slot * SLOT_BYTES);
                        token_pass(w);
                        --left;
                        wg_wait<0>();
                        PROF_EV(34);
                        fence_regs(sh);
                        mask_diag<0>(sh, c);
                        float l0 = 0.f, l1 = 0.f;
#pragma unroll
                        for (int j = 0; j < 8; j++) {
#pragma unroll
                            for (int e = 0; e < 4; e++) ex2v(sh[4 * j + e]);
                            l0 += sh[4 * j] + sh[4 * j + 1]; l1 += sh[4 * j + 2] + sh[4 * j + 3];
                        }
#pragma unroll
                        for (int i = 0; i < 16; i++) p[i] = pack_bf16(sh[2 * i], sh[2 * i + 1]);
                        const int lim = mask_lim(c);
                        if (__any_sync(0xffffffffu, !(l0 <= SAFE_SUM && l1 <= SAFE_SUM && (l0 >= 1.0f / SAFE_SUM || lim < 0) &&
                                                      (l1 >= 1.0f / SAFE_SUM || lim < -2)))) goto redo;
                        l[0] = l0; l[1] = l1;
                        goto tail;
                    }
#pragma unroll 1
                    while (true) {
                        token_wait(w);
                        PROF_EV(first ? 30 : 31);
                        undef_regs(s);
                        issue_qk(s, q, ring + ck.slot * SLOT_BYTES);
                        Cur nck = cur, ncv = cur, ncur;
                        ncv.adv(); ncur = ncv; ncur.adv();
                        --left;
                        mbar_wait_hot(misc + BAR_FULL + 8 * cv.slot, cv.ph);
                        issue_pv(o, p, ring + cv.slot * SLOT_BYTES, pv_acc, pv_mode);
                        token_pass(w);
                        wg_wait<1>();
                        PROF_EV(33);
                        fence_regs(s);
                        float lo = 0.f;
                        if (first) {
                            lo = 1.0f / SAFE_SUM;
                            mask_diag<8>(s, c);
                        }
                        constexpr int JB = 11;
                        float l0 = l[0], l1 = l[1];
                        if (!gen) {
#pragma unroll
                            for (int j = 0; j < JB; j++) {
#pragma unroll
                                for (int e = 0; e < 4; e++) ex2v(s[4 * j + e]);
                                if (j < JB - 1) { l0 += s[4 * j] + s[4 * j + 1]; l1 += s[4 * j + 2] + s[4 * j + 3]; }
                            }
                        }
                        wg_wait<0>();
                        fence_regs(o);
                        if (gen) goto general;
#pragma unroll
                        for (int j = JB - 1; j < 16; j++) {
                            if (j >= JB) {
#pragma unroll
                                for (int e = 0; e < 4; e++) ex2v(s[4 * j + e]);
                            }
                            l0 += s[4 * j] + s[4 * j + 1]; l1 += s[4 * j + 2] + s[4 * j + 3];
                        }
#pragma unroll
                        for (int i = 0; i < 32; i++) p[i] = pack_bf16(s[2 * i], s[2 * i + 1]);
                        if (__any_sync(0xffffffffu, !(l0 <= SAFE_SUM && l1 <= SAFE_SUM && l0 >= lo && l1 >= lo))) goto redo;
                        l[0] = l0; l[1] = l1;
                        if (left == 0) goto tail;
                        release(c, BAR_EMPTY + 8 * ck.slot, 1 + (first & heavy));
                        if (pv_cnt) release(c, BAR_EMPTY + 8 * cv.slot, pv_cnt);
                        pv_acc = first ^ 1; pv_mode = 0; pv_cnt = 1 + (first & heavy); first = 0;
                        ck = nck; cv = ncv; cur = ncur;
                        mbar_wait_hot(misc + BAR_FULL + 8 * ck.slot, ck.ph);
                    }
                redo:
                    recompute_scores(s, q, ring + ck.slot * SLOT_BYTES, c);
                    if (first) { mask_any(s, half ^ 1, c); m[0] = m[1] = -INFINITY; }
                    gen = 1;
                general:
                    {
                        float mx[2], alpha[2];
                        row_max<16>(s, mx);
#pragma unroll
                        for (int i = 0; i < 2; i++) {
                            mx[i] = fmaxf(mx[i], m[i]);
                            alpha[i] = ex2(m[i] - mx[i]);
                            m[i] = mx[i];
                            l[i] *= alpha[i];
                        }
                        exp_sum<16, true>(s, m, l[0], l[1]);
#pragma unroll
                        for (int i = 0; i < 64; i++) o[i] *= alpha[(i >> 1) & 1];
#pragma unroll
                        for (int i = 0; i < 32; i++) p[i] = pack_bf16(s[2 * i], s[2 * i + 1]);
                    }
                tail:
                    release(c, BAR_EMPTY + 8 * ck.slot, 1 + (first & heavy));
                    if (pv_cnt) release(c, BAR_EMPTY + 8 * cv.slot, pv_cnt);
                    pv_acc = first ^ 1; pv_mode = first & half; pv_cnt = 1 + (first & heavy); first = 0;
                    if (left == 0) break;
                    ck = cur; cur.adv(); cv = cur; cur.adv();
                    mbar_wait_hot(misc + BAR_FULL + 8 * ck.slot, ck.ph);
                }
            }
            mbar_wait_hot(misc + BAR_FULL + 8 * cur.slot, cur.ph);
            token_wait(w);
            PROF_EV(32);
            issue_pv(o, p, ring + cur.slot * SLOT_BYTES, 1, 0);
            if (w == 0 || v == 0) token_pass(w);
            const uint32_t vslot = cur.slot;
            cur.adv();
            if (v) {
                row_inv(l, inv);
                wg_wait<0>();
                release(c, BAR_EMPTY + 8 * vslot, 1);
                fence_regs(o);
                tile_out(out, g_ctx + (size_t)((2 * team + 1) * 32 + 4 * b1 + (w ? 3 - (rank ^ SWAPT) : rank ^ SWAPT)) * 16384, 0, 0, c);
#pragma unroll
                for (int i = 0; i < 64; i++) wf[i] = 0u;
                continue;
            }
            cw = cur_at(80);
            mbar_wait_hot(misc + BAR_FULL + 8 * slot_of(76), cur_at(76).ph);
            mbar_wait_hot(misc + BAR_FULL + 8 * slot_of(78), cur_at(78).ph);
            load_afrag<8, 32>(wf, ring + slot_of(78) * SLOT_BYTES + w * 16384, c);
            const uint32_t z = load_afrag<8, 0>(wf, ring + slot_of(76) * SLOT_BYTES + w * 16384, c);
            row_inv(l, inv);
            release(c, BAR_EMPTY + 8 * slot_of(76) + z, 1);
            asm volatile("{\n.reg .pred p;\nsetp.eq.u32 p, %0, 0;\n@p bar.sync 4, 128;\n@!p bar.sync 5, 128;\n}\n" ::"r"(w) : "memory");
            wg_wait<0>();
            release(c, BAR_EMPTY + 8 * vslot, 1);
            fence_regs(o);
            {
                const uint32_t base = ring + slot_of(78) * SLOT_BYTES + w * 16384 + (16 * c.warp + (c.lane >> 2)) * 64 + (((c.lane ^ (c.lane >> 3)) & 3) << 4);
#pragma unroll
                for (int i = 0; i < 2; i++)
#pragma unroll
                    for (int qq = 0; qq < 4; qq++)
                        asm volatile("st.shared.v4.b32 [%0], {%1,%2,%3,%4};" ::"r"(base + qq * 4096 + i * 512),
                                     "r"(pack_bf16(o[16 * qq + 2 * i] * inv[i], o[16 * qq + 2 * i + 1] * inv[i])),
                                     "r"(pack_bf16(o[16 * qq + 4 + 2 * i] * inv[i], o[16 * qq + 4 + 2 * i + 1] * inv[i])),
                                     "r"(pack_bf16(o[16 * qq + 8 + 2 * i] * inv[i], o[16 * qq + 8 + 2 * i + 1] * inv[i])),
                                     "r"(pack_bf16(o[16 * qq + 12 + 2 * i] * inv[i], o[16 * qq + 12 + 2 * i + 1] * inv[i])) : "memory");
                asm volatile("fence.proxy.async.shared::cta;" ::: "memory");
                signal_event(c, EV_CTX + 1);
            }
        }
        }
        {
            float acc[80];
            undef_regs(acc);
            int st = 0, prev = 0; uint32_t ph3 = 0;
            auto op_stage = [&](int i) {
                mbar_wait_hot(misc + BAR_FULL3 + 8 * st, ph3);
                PROF_EV(44);
                uint32_t base = ring + st * ST3_BYTES;
                uint64_t da = mkdesc(base + w * 8192, 16, 512, 2);
                uint64_t db = mkdesc(base + 16384, 2048, 512, 2);
                wg_fence();
#pragma unroll
                for (int k = 0; k < 4; k++) wgmma_ss_n160_ta0_tb1(acc, da + (k >> 1) * 256 + 2 * (k & 1), db + (k >> 1) * 640 + (k & 1) * 64, k ? 1 : i);
                wg_commit();
                if (i > 0) { wg_wait<1>(); if (i <= 32 - NST3) release(c, BAR_EMPTY3 + 8 * prev, 1); }
                prev = st;
                if (++st == NST3) { st = 0; ph3 ^= 1; }
            };
            PROF_EV(40); PROF_GT(65);
#pragma unroll
            for (int i = 0; i < 4; i++) { op_stage(i); store_pair(o, i, out, 4096, inv); }
            signal_event(c, EV_CTX + 3);
#pragma unroll 1
            for (int i = 4; i < 12; i++) op_stage(i);
            mbar_wait(misc + BAR_SEL, 0);
            const uint32_t tag = lds32(misc + MISC_EPOCH) & 1;
            const int g = c.lane >> 2, t = c.lane & 3;
            const int row = (2 * u3 + rank) * 128 + 64 * w + perm32(16 * c.warp + 8 * kap + g);
            const int col = 160 * s3 + 8 * t;
            int sel = -1;
#pragma unroll
            for (int i = 0; i < TOPC; i++) if ((int)lds32(misc + MISC_SEL + 4 * i) == row) sel = i;
            const int t256 = tid - 128;
            uint4* sendp = g_part + (size_t)cta * 2560 + t256;
            if (c.lane >= 30) stg128(sendp + 9 * 256, tag ^ 1, tag ^ 1, tag ^ 1, tag ^ 1);
#pragma unroll 1
            for (int i = 12; i < 32; i++) op_stage(i);
            uint4 xv[5], bv[5];
#pragma unroll
            for (int i = 0; i < 5; i++) xv[i] = ldg128(P.x + (size_t)row * DM + col + 32 * i);
            uint2 stat;
            asm volatile("ld.global.cg.v2.b32 {%0,%1}, [%2];" : "=r"(stat.x), "=r"(stat.y) : "l"(g_stats + row) : "memory");
            wg_wait<0>();
            fence_regs(acc);
            PROF_EV(41); PROF_GT(66);
            float keep[40];
#pragma unroll
            for (int j = 0; j < 10; j++) {
                uint32_t v0 = __float_as_uint(kap ? acc[8 * j + 0] : acc[8 * j + 2]), v1 = __float_as_uint(kap ? acc[8 * j + 1] : acc[8 * j + 3]);
                uint32_t v2 = __float_as_uint(kap ? acc[8 * j + 4] : acc[8 * j + 6]), v3 = __float_as_uint(kap ? acc[8 * j + 5] : acc[8 * j + 7]);
                asm volatile("st.relaxed.gpu.global.v4.b32 [%0], {%1,%2,%3,%4};" ::"l"(sendp + j * 256),
                             "r"((v0 & ~1u) | tag), "r"((v1 & ~1u) | tag), "r"((v2 & ~1u) | tag), "r"((v3 & ~1u) | tag) : "memory");
                keep[4 * j + 0] = kap ? acc[8 * j + 2] : acc[8 * j + 0]; keep[4 * j + 1] = kap ? acc[8 * j + 3] : acc[8 * j + 1];
                keep[4 * j + 2] = kap ? acc[8 * j + 6] : acc[8 * j + 4]; keep[4 * j + 3] = kap ? acc[8 * j + 7] : acc[8 * j + 5];
            }
            PROF_GT(67);
            signal_event(c, EV_END);
#pragma unroll
            for (int i = 0; i < 5; i++) {
                uint32_t xx[4] = {xv[i].x, xv[i].y, xv[i].z, xv[i].w};
#pragma unroll
                for (int e = 0; e < 4; e++) {
                    asm("sub.rn.bf16x2 %0, %0, %1;" : "+r"(xx[e]) : "r"(stat.x));
                    xx[e] = pack_bf16(bf_lo(xx[e]) * __uint_as_float(stat.y), bf_hi(xx[e]) * __uint_as_float(stat.y));
                }
                bv[i] = make_uint4(xx[0], xx[1], xx[2], xx[3]);
            }
            if (sel >= 0) {
#pragma unroll
                for (int i = 0; i < 5; i++) bv[i] = ldg128(g_brow + sel * DM + col + 32 * i);
            }
            const uint4* recvp = g_part + (size_t)partner * 2560 + t256;
            uint4 rv[10];
            int spins = 0;
            while (true) {
                uint32_t v;
                asm volatile("ld.relaxed.gpu.global.b32 %0, [%1];" : "=r"(v) : "l"(recvp + 9 * 256 + (31 - c.lane)) : "memory");
                if (__all_sync(0xffffffffu, (v & 1u) == tag) || ++spins > 2000000) break;
            }
            PROF_GT(68);
            while (true) {
                uint32_t bad = 0u;
#pragma unroll
                for (int j = 0; j < 10; j++) {
                    asm volatile("ld.relaxed.gpu.global.v4.b32 {%0,%1,%2,%3}, [%4];"
                                 : "=r"(rv[j].x), "=r"(rv[j].y), "=r"(rv[j].z), "=r"(rv[j].w) : "l"(recvp + j * 256) : "memory");
                }
#pragma unroll
                for (int j = 0; j < 10; j++) {
                    rv[j].x ^= tag; rv[j].y ^= tag; rv[j].z ^= tag; rv[j].w ^= tag;
                    bad |= rv[j].x | rv[j].y | rv[j].z | rv[j].w;
                }
                if (__all_sync(0xffffffffu, (bad & 1u) == 0) || ++spins > 2000000) break;
            }
            PROF_GT(69);
            uint32_t pk[20];
#pragma unroll
            for (int j = 0; j < 10; j++) {
                pk[2 * j] = pack_bf16(keep[4 * j] + __uint_as_float(rv[j].x), keep[4 * j + 1] + __uint_as_float(rv[j].y));
                pk[2 * j + 1] = pack_bf16(keep[4 * j + 2] + __uint_as_float(rv[j].z), keep[4 * j + 3] + __uint_as_float(rv[j].w));
            }
#pragma unroll
            for (int i = 0; i < 5; i++) {
                uint32_t a0 = pk[4 * i], a1 = pk[4 * i + 1], a2 = pk[4 * i + 2], a3 = pk[4 * i + 3];
                uint32_t x0 = (t & 1) ? a0 : a1, x1 = (t & 1) ? a2 : a3;
                x0 = __shfl_xor_sync(0xffffffffu, x0, 1); x1 = __shfl_xor_sync(0xffffffffu, x1, 1);
                if (t & 1) { a0 = x0; a2 = x1; } else { a1 = x0; a3 = x1; }
                x0 = (t & 2) ? a0 : a2; x1 = (t & 2) ? a1 : a3;
                x0 = __shfl_xor_sync(0xffffffffu, x0, 2); x1 = __shfl_xor_sync(0xffffffffu, x1, 2);
                if (t & 2) { a0 = x0; a1 = x1; } else { a2 = x0; a3 = x1; }
                uint32_t av[4] = {a0, a1, a2, a3};
                uint32_t xx[4] = {xv[i].x, xv[i].y, xv[i].z, xv[i].w}, bb[4] = {bv[i].x, bv[i].y, bv[i].z, bv[i].w};
                uint32_t ov[4];
#pragma unroll
                for (int e = 0; e < 4; e++) {
                    asm("add.rn.bf16x2 %0, %1, %2;" : "=r"(ov[e]) : "r"(xx[e]), "r"(av[e]));
                    asm("add.rn.bf16x2 %0, %0, %1;" : "+r"(ov[e]) : "r"(bb[e]));
                }
                stg128(P.out + (size_t)row * DM + col + 32 * i, ov[0], ov[1], ov[2], ov[3]);
            }
            PROF_EV(42); PROF_GT(43);
        }
    }
}

typedef CUresult (*EncodeFn)(CUtensorMap*, CUtensorMapDataType, cuuint32_t, void*, const cuuint64_t*, const cuuint64_t*, const cuuint32_t*,
                             const cuuint32_t*, CUtensorMapInterleave, CUtensorMapSwizzle, CUtensorMapL2promotion, CUtensorMapFloatOOBfill);

void make_map2d(EncodeFn enc, CUtensorMap* tm, const void* p, uint64_t cols, uint64_t rows, uint32_t box_rows = 128) {
    cuuint64_t gd[2] = {cols, rows}, gs[1] = {cols * 2};
    cuuint32_t box[2] = {64, box_rows}, es[2] = {1, 1};
    enc(tm, CU_TENSOR_MAP_DATA_TYPE_BFLOAT16, 2, const_cast<void*>(p), gd, gs, box, es, CU_TENSOR_MAP_INTERLEAVE_NONE,
        CU_TENSOR_MAP_SWIZZLE_128B, CU_TENSOR_MAP_L2_PROMOTION_L2_128B, CU_TENSOR_MAP_FLOAT_OOB_FILL_NONE);
}

void make_map3d(EncodeFn enc, CUtensorMap* tm, const void* p, uint64_t cols, uint64_t rows, uint32_t bw, uint32_t nb) {
    cuuint64_t gd[3] = {bw, rows, cols / bw}, gs[2] = {cols * 2, bw * 2};
    cuuint32_t box[3] = {bw, 32, nb}, es[3] = {1, 1, 1};
    enc(tm, CU_TENSOR_MAP_DATA_TYPE_BFLOAT16, 3, const_cast<void*>(p), gd, gs, box, es, CU_TENSOR_MAP_INTERLEAVE_NONE,
        bw == 64 ? CU_TENSOR_MAP_SWIZZLE_128B : CU_TENSOR_MAP_SWIZZLE_64B, CU_TENSOR_MAP_L2_PROMOTION_L2_128B, CU_TENSOR_MAP_FLOAT_OOB_FILL_NONE);
}

}

extern "C" void kernel_launch(void* const* d_in, const int* in_sizes, int n_in, void* d_out, int out_size) {
    (void)in_sizes; (void)n_in; (void)out_size;
    static EncodeFn enc = nullptr;
    if (!enc) {
        void* fn = nullptr;
        cudaDriverEntryPointQueryResult qr;
        cudaGetDriverEntryPoint("cuTensorMapEncodeTiled", &fn, cudaEnableDefault, &qr);
        enc = (EncodeFn)fn;
        cudaFuncSetAttribute(fused_kernel, cudaFuncAttributeMaxDynamicSharedMemorySize, SMEM_BYTES);
    }
    CUtensorMap tmC, tmWk, tmWv, tmWq, tmWo, tmG, tmU, tmD;
    make_map2d(enc, &tmC, d_in[1], DC, SEQ);
    make_map2d(enc, &tmWq, d_in[2], 4096, DM, 64);
    make_map2d(enc, &tmWk, d_in[3], 4096, DC);
    make_map2d(enc, &tmWv, d_in[4], 4096, DC);
    make_map3d(enc, &tmWo, d_in[5], DM, 4096, 32, 5);
    make_map3d(enc, &tmG, d_in[8], FF, DM, 64, 7);
    make_map3d(enc, &tmU, d_in[9], FF, DM, 64, 7);
    make_map3d(enc, &tmD, d_in[10], DM, FF, 64, 10);
    Params P;
    P.x = (const __nv_bfloat16*)d_in[0];
    P.c = (const __nv_bfloat16*)d_in[1];
    P.wk = (const __nv_bfloat16*)d_in[3];
    P.wv = (const __nv_bfloat16*)d_in[4];
    P.wo = (const __nv_bfloat16*)d_in[5];
    P.wr = (const __nv_bfloat16*)d_in[7];
    P.out = (__nv_bfloat16*)d_out;
    fused_kernel<<<132, 384, SMEM_BYTES>>>(tmC, tmWk, tmWv, tmWq, tmWo, tmG, tmU, tmD, P);
}
```

```cpp
#include <cuda_runtime.h>
#include <cuda_bf16.h>
#include <cuda.h>
#include <stdint.h>

#define SWAPT 1
#define DEFER 1
#define HOLD0 6
#define LNINL __noinline__
#define WQPF 8
#define RES_AT 23
#define HM 0
#define OP_PF 8
#define PF_START 9
#define LATE_AT 18
namespace {

constexpr int SEQ = 2048, NH = 32, DM = 640, DC = 512, FF = 1728, TOPC = 8;
constexpr int NSLOT = 7, SLOT_BYTES = 32768;
constexpr int NST3 = 6, ST3_BYTES = 36864;
constexpr int RING_BYTES = NSLOT * SLOT_BYTES;
constexpr int SMEM_BYTES = RING_BYTES + 3072;

constexpr int BAR_FULL = 96  , BAR_FULL3 = 152  , BAR_DEP = 200  , BAR_SEL = 464,
              BAR_LN = 472  , BAR_EV = 504  , BAR_EMPTY = 760  , BAR_EMPTY3 = 816  ,
              BAR_PROG = 864  , MISC_EPOCH = 896, MISC_SMID = 900  , MISC_SEL = 912, MISC_WR = 1024  ;
constexpr int D_LN = 0  , D_KV = 4  , D_WAR = 14  , D_CTX = 16  ;
constexpr int EV_KV = 0  , EV_END = 11, EV_CTX = 12  ;

constexpr int FL_MOE_CNT = 0, FL_MOE_DONE = 1, FL_LN = 16  , FL_KV = 32  , FL_CTX = 416  , FL_WAR = 672  , FL_TOTAL = 704;

__device__ __align__(1024) unsigned char g_K[16 * 32 * 16384];
__device__ __align__(1024) unsigned char g_V[16 * 32 * 16384];
__device__ __align__(1024) unsigned char g_ctx[NH * 32 * 16384];
__device__ __align__(1024) unsigned char g_xn[16 * 10 * 16384];
__device__ __align__(1024) uint4 g_part[128 * 10 * 256];
__device__ float g_router[SEQ];
__device__ uint2 g_stats[SEQ];
__device__ __align__(16) float g_moe_part[4 * TOPC * DM];
__device__ __align__(16) __nv_bfloat16 g_brow[TOPC * DM];
__device__ __align__(16) int g_sel[TOPC];
__device__ unsigned g_flags[FL_TOTAL * 8];
__device__ unsigned g_epoch;
__device__ unsigned g_roleq[130];

struct Params {
    const __nv_bfloat16 *x, *c, *wr, *wk, *wv, *wo;
    __nv_bfloat16* out;
};

__device__ __forceinline__ uint32_t smem_u32(const void* p) { return (uint32_t)__cvta_generic_to_shared(p); }
__device__ __forceinline__ void mbar_init(uint32_t bar, int cnt) { asm volatile("mbarrier.init.shared::cta.b64 [%0], %1;" ::"r"(bar), "r"(cnt)); }
__device__ __forceinline__ void mbar_expect_tx(uint32_t bar, uint32_t bytes) {
    asm volatile("mbarrier.arrive.expect_tx.shared::cta.b64 _, [%0], %1;" ::"r"(bar), "r"(bytes) : "memory");
}
__device__ __forceinline__ void mbar_arrive(uint32_t bar) { asm volatile("mbarrier.arrive.shared::cta.b64 _, [%0];" ::"r"(bar) : "memory"); }
__device__ __forceinline__ void mbar_arrive_cluster(uint32_t cluster_addr, uint32_t cnt) {
    asm volatile("mbarrier.arrive.shared::cluster.b64 _, [%0], %1;" ::"r"(cluster_addr), "r"(cnt) : "memory");
}
__device__ __forceinline__ uint32_t mapa(uint32_t addr, uint32_t cta) {
    uint32_t r; asm("mapa.shared::cluster.u32 %0, %1, %2;" : "=r"(r) : "r"(addr), "r"(cta)); return r;
}
__device__ __forceinline__ void mbar_wait(uint32_t bar, uint32_t parity) {
    asm volatile(
        "{\n.reg .pred p;\n.reg .u32 n;\n"
        "mov.u32 n, 0;\n"
        "LAB_WAIT:\n"
        "mbarrier.try_wait.parity.shared::cta.b64 p, [%0], %1, 100000;\n"
        "@p bra DONE;\n"
        "add.u32 n, n, 1;\n"
        "setp.lt.u32 p, n, 50000;\n"
        "@p bra LAB_WAIT;\n"
        "trap;\n"
        "DONE:\n}\n" ::"r"(bar), "r"(parity) : "memory");
}
__device__ __forceinline__ void mbar_wait_hot(uint32_t bar, uint32_t parity) {
    asm volatile("{\n.reg .pred p;\nLAB_WAIT:\nmbarrier.try_wait.parity.shared::cta.b64 p, [%0], %1;\n@!p bra LAB_WAIT;\n}\n" ::"r"(bar), "r"(parity) : "memory");
}
__device__ __forceinline__ void mbar_wait_sleep(uint32_t bar, uint32_t parity) {
    asm volatile("{\n.reg .pred p;\nLAB_WAIT:\nmbarrier.try_wait.parity.shared::cta.b64 p, [%0], %1, 100000;\n@!p bra LAB_WAIT;\n}\n" ::"r"(bar), "r"(parity) : "memory");
}
__device__ __forceinline__ void flag_wait(const unsigned* flag, unsigned target) {
    asm volatile(
        "{\n.reg .pred p;\n.reg .u32 n, v;\n.reg .s32 d;\n"
        "mov.u32 n, 0;\n"
        "LAB_WAIT:\n"
        "ld.acquire.gpu.global.u32 v, [%0];\n"
        "sub.s32 d, v, %1;\n"
        "setp.ge.s32 p, d, 0;\n"
        "@p bra DONE;\n"
        "nanosleep.u32 40;\n"
        "add.u32 n, n, 1;\n"
        "setp.lt.u32 p, n, 3000000;\n"
        "@p bra LAB_WAIT;\n"
        "trap;\n"
        "DONE:\n}\n" ::"l"(flag), "r"(target) : "memory");
}
__device__ __forceinline__ void flag_signal(unsigned* flag) {
    asm volatile("red.release.gpu.global.add.u32 [%0], 1;" ::"l"(flag) : "memory");
}
__device__ __forceinline__ void fence_async_global() { asm volatile("fence.proxy.async.global;" ::: "memory"); }
__device__ __forceinline__ unsigned* flag_ptr(int idx) { return g_flags + idx * 8; }

__device__ __forceinline__ uint64_t policy_stream() {
    uint64_t p; asm("createpolicy.fractional.L2::evict_first.b64 %0, 1.0;" : "=l"(p)); return p;
}
__device__ __forceinline__ uint64_t policy_normal() { return 0x1000000000000000ull; }
__device__ __forceinline__ uint64_t policy(bool stream) { return stream ? policy_stream() : policy_normal(); }
__device__ __forceinline__ void bulk_load(uint32_t dst, const void* src, uint32_t bytes, uint32_t bar, uint64_t pol) {
    asm volatile("cp.async.bulk.shared::cluster.global.mbarrier::complete_tx::bytes.L2::cache_hint [%0], [%1], %2, [%3], %4;"
                 ::"r"(dst), "l"(src), "r"(bytes), "r"(bar), "l"(pol) : "memory");
}
__device__ __forceinline__ void bulk_load_mc(uint32_t dst, const void* src, uint32_t bytes, uint32_t bar, uint64_t pol) {
    asm volatile("cp.async.bulk.shared::cluster.global.mbarrier::complete_tx::bytes.multicast::cluster.L2::cache_hint [%0], [%1], %2, [%3], %4, %5;"
                 ::"r"(dst), "l"(src), "r"(bytes), "r"(bar), "h"((uint16_t)3), "l"(pol) : "memory");
}
__device__ __forceinline__ void tma2d(uint32_t dst, const CUtensorMap* tm, int c0, int c1, uint32_t bar, uint64_t pol) {
    asm volatile("cp.async.bulk.tensor.2d.shared::cluster.global.mbarrier::complete_tx::bytes.L2::cache_hint [%0], [%1, {%3, %4}], [%2], %5;"
                 ::"r"(dst), "l"(tm), "r"(bar), "r"(c0), "r"(c1), "l"(pol) : "memory");
}
__device__ __forceinline__ void tma2d_mc(uint32_t dst, const CUtensorMap* tm, int c0, int c1, uint32_t bar, uint64_t pol) {
    asm volatile("cp.async.bulk.tensor.2d.shared::cluster.global.mbarrier::complete_tx::bytes.multicast::cluster.L2::cache_hint [%0], [%1, {%3, %4}], [%2], %5, %6;"
                 ::"r"(dst), "l"(tm), "r"(bar), "r"(c0), "r"(c1), "h"((uint16_t)3), "l"(pol) : "memory");
}
__device__ __forceinline__ void tma3d_mc(uint32_t dst, const CUtensorMap* tm, int c0, int c1, int c2, uint32_t bar, uint64_t pol) {
    asm volatile("cp.async.bulk.tensor.3d.shared::cluster.global.mbarrier::complete_tx::bytes.multicast::cluster.L2::cache_hint [%0], [%1, {%3, %4, %5}], [%2], %6, %7;"
                 ::"r"(dst), "l"(tm), "r"(bar), "r"(c0), "r"(c1), "r"(c2), "h"((uint16_t)3), "l"(pol) : "memory");
}
__device__ __forceinline__ void tma3d(uint32_t dst, const CUtensorMap* tm, int c0, int c1, int c2, uint32_t bar) {
    asm volatile("cp.async.bulk.tensor.3d.shared::cluster.global.mbarrier::complete_tx::bytes.L2::cache_hint [%0], [%1, {%3, %4, %5}], [%2], %6;"
                 ::"r"(dst), "l"(tm), "r"(bar), "r"(c0), "r"(c1), "r"(c2), "l"(policy_stream()) : "memory");
}
__device__ __forceinline__ void tma2d_prefetch(const CUtensorMap* tm, int c0, int c1) {
    asm volatile("cp.async.bulk.prefetch.tensor.2d.L2.global [%0, {%1, %2}];" ::"l"(tm), "r"(c0), "r"(c1) : "memory");
}
__device__ __forceinline__ void tma3d_prefetch(const CUtensorMap* tm, int c0, int c1, int c2) {
    asm volatile("cp.async.bulk.prefetch.tensor.3d.L2.global [%0, {%1, %2, %3}];" ::"l"(tm), "r"(c0), "r"(c1), "r"(c2) : "memory");
}
__device__ __forceinline__ void l2_prefetch(const void* p, uint32_t bytes) {
    asm volatile("cp.async.bulk.prefetch.L2.global [%0], %1;" ::"l"(p), "r"(bytes) : "memory");
}
__device__ __forceinline__ bool elect_one() {
    uint32_t r; asm volatile("{\n.reg .pred p;\nelect.sync _|p, 0xffffffff;\nselp.u32 %0, 1, 0, p;\n}\n" : "=r"(r)); return r != 0;
}
__device__ __forceinline__ void wg_fence() { asm volatile("wgmma.fence.sync.aligned;" ::: "memory"); }
__device__ __forceinline__ void wg_commit() { asm volatile("wgmma.commit_group.sync.aligned;" ::: "memory"); }
template <int N> __device__ __forceinline__ void wg_wait() { asm volatile("wgmma.wait_group.sync.aligned %0;" ::"n"(N) : "memory"); }
__device__ __forceinline__ void bar_sync(int id, int n) { asm volatile("bar.sync %0, %1;" ::"r"(id), "r"(n) : "memory"); }
__device__ __forceinline__ void bar_arrive(int id, int n) { asm volatile("bar.arrive %0, %1;" ::"r"(id), "r"(n) : "memory"); }
__device__ __forceinline__ void token_wait(int w) {
    asm volatile("{\n.reg .pred p;\nsetp.eq.u32 p, %0, 0;\n@p bar.sync 1, 256;\n@!p bar.sync 2, 256;\n}\n" ::"r"(w) : "memory");
}
__device__ __forceinline__ void token_pass(int w) {
    asm volatile("{\n.reg .pred p;\nsetp.eq.u32 p, %0, 0;\n@p bar.arrive 2, 256;\n@!p bar.arrive 1, 256;\n}\n" ::"r"(w) : "memory");
}
template <int N> __device__ __forceinline__ void fence_regs(float (&a)[N]) {
#pragma unroll
    for (int i = 0; i < N; i++) asm volatile("" : "+f"(a[i])::"memory");
}
template <int N> __device__ __forceinline__ void undef_regs(float (&a)[N]) {
#pragma unroll
    for (int i = 0; i < N; i++) asm volatile("" : "=f"(a[i]));
}
__device__ __forceinline__ void ldsm4t(uint32_t& r0, uint32_t& r1, uint32_t& r2, uint32_t& r3, uint32_t addr) {
    asm volatile("ldmatrix.sync.aligned.m8n8.x4.trans.shared.b16 {%0,%1,%2,%3}, [%4];"
                 : "=r"(r0), "=r"(r1), "=r"(r2), "=r"(r3) : "r"(addr) : "memory");
}
__device__ __forceinline__ uint32_t pack_bf16(float lo, float hi) {
    uint32_t r; asm("cvt.rn.bf16x2.f32 %0, %1, %2;" : "=r"(r) : "f"(hi), "f"(lo)); return r;
}
__device__ __forceinline__ float bf_lo(uint32_t v) { return __uint_as_float(v << 16); }
__device__ __forceinline__ float bf_hi(uint32_t v) { return __uint_as_float(v & 0xffff0000u); }
__device__ __forceinline__ float bf_round(float v) { return __bfloat162float(__float2bfloat16_rn(v)); }
__device__ __forceinline__ float ex2(float v) { float r; asm("ex2.approx.ftz.f32 %0, %1;" : "=f"(r) : "f"(v)); return r; }
__device__ __forceinline__ void ex2v(float& v) { asm volatile("ex2.approx.ftz.f32 %0, %0;" : "+f"(v)); }
__device__ __forceinline__ float rcp_fast(float v) { float r; asm("rcp.approx.ftz.f32 %0, %1;" : "=f"(r) : "f"(v)); return r; }
__device__ __forceinline__ float sqrt_fast(float v) { float r; asm("sqrt.approx.ftz.f32 %0, %1;" : "=f"(r) : "f"(v)); return r; }
__device__ __forceinline__ void stg128(void* p, uint32_t a, uint32_t b, uint32_t c, uint32_t d) {
    asm volatile("st.global.v4.b32 [%0], {%1,%2,%3,%4};" ::"l"(p), "r"(a), "r"(b), "r"(c), "r"(d) : "memory");
}
__device__ __forceinline__ uint4 ldg128(const void* p) {
    uint4 v; asm volatile("ld.global.cg.v4.b32 {%0,%1,%2,%3}, [%4];" : "=r"(v.x), "=r"(v.y), "=r"(v.z), "=r"(v.w) : "l"(p) : "memory"); return v;
}
__device__ __forceinline__ uint64_t mkdesc(uint32_t addr, uint32_t lbo, uint32_t sbo, uint32_t swz) {
    uint32_t lo = ((addr & 0x3FFFF) >> 4) | ((lbo >> 4) << 16);
    uint32_t hi = (sbo >> 4) | (swz << 30);
    return ((uint64_t)hi << 32) | lo;
}
__device__ __forceinline__ int perm32(int v) { return (v & ~30) | ((v >> 2) & 6) | ((v << 2) & 24); }

__device__ __forceinline__ void wgmma_rs_n128_ta0_tb0(float (&d)[64], uint32_t a0, uint32_t a1, uint32_t a2, uint32_t a3, uint64_t descB, int scaleD) {
  asm volatile("{\n.reg .pred p;\nsetp.ne.b32 p, %69, 0;\n"
    "wgmma.mma_async.sync.aligned.m64n128k16.f32.bf16.bf16 "
    "{%0, %1, %2, %3, %4, %5, %6, %7, %8, %9, %10, %11, %12, %13, %14, %15, %16, %17, %18, %19, %20, %21, %22, %23, %24, %25, %26, %27, %28, %29, %30, %31, %32, %33, %34, %35, %36, %37, %38, %39, %40, %41, %42, %43, %44, %45, %46, %47, %48, %49, %50, %51, %52, %53, %54, %55, %56, %57, %58, %59, %60, %61, %62, %63}, "
    "{%64, %65, %66, %67}, %68, p, 1, 1, 0;\n}\n"
    : "+f"(d[0]), "+f"(d[1]), "+f"(d[2]), "+f"(d[3]), "+f"(d[4]), "+f"(d[5]), "+f"(d[6]), "+f"(d[7]), "+f"(d[8]), "+f"(d[9]), "+f"(d[10]), "+f"(d[11]), "+f"(d[12]), "+f"(d[13]), "+f"(d[14]), "+f"(d[15]), "+f"(d[16]), "+f"(d[17]), "+f"(d[18]), "+f"(d[19]), "+f"(d[20]), "+f"(d[21]), "+f"(d[22]), "+f"(d[23]), "+f"(d[24]), "+f"(d[25]), "+f"(d[26]), "+f"(d[27]), "+f"(d[28]), "+f"(d[29]), "+f"(d[30]), "+f"(d[31]), "+f"(d[32]), "+f"(d[33]), "+f"(d[34]), "+f"(d[35]), "+f"(d[36]), "+f"(d[37]), "+f"(d[38]), "+f"(d[39]), "+f"(d[40]), "+f"(d[41]), "+f"(d[42]), "+f"(d[43]), "+f"(d[44]), "+f"(d[45]), "+f"(d[46]), "+f"(d[47]), "+f"(d[48]), "+f"(d[49]), "+f"(d[50]), "+f"(d[51]), "+f"(d[52]), "+f"(d[53]), "+f"(d[54]), "+f"(d[55]), "+f"(d[56]), "+f"(d[57]), "+f"(d[58]), "+f"(d[59]), "+f"(d[60]), "+f"(d[61]), "+f"(d[62]), "+f"(d[63])
    : "r"(a0), "r"(a1), "r"(a2), "r"(a3), "l"(descB), "r"(scaleD));
}
__device__ __forceinline__ void wgmma_rs_n128_ta0_tb1(float (&d)[64], uint32_t a0, uint32_t a1, uint32_t a2, uint32_t a3, uint64_t descB, int scaleD) {
  asm volatile("{\n.reg .pred p;\nsetp.ne.b32 p, %69, 0;\n"
    "wgmma.mma_async.sync.aligned.m64n128k16.f32.bf16.bf16 "
    "{%0, %1, %2, %3, %4, %5, %6, %7, %8, %9, %10, %11, %12, %13, %14, %15, %16, %17, %18, %19, %20, %21, %22, %23, %24, %25, %26, %27, %28, %29, %30, %31, %32, %33, %34, %35, %36, %37, %38, %39, %40, %41, %42, %43, %44, %45, %46, %47, %48, %49, %50, %51, %52, %53, %54, %55, %56, %57, %58, %59, %60, %61, %62, %63}, "
    "{%64, %65, %66, %67}, %68, p, 1, 1, 1;\n}\n"
    : "+f"(d[0]), "+f"(d[1]), "+f"(d[2]), "+f"(d[3]), "+f"(d[4]), "+f"(d[5]), "+f"(d[6]), "+f"(d[7]), "+f"(d[8]), "+f"(d[9]), "+f"(d[10]), "+f"(d[11]), "+f"(d[12]), "+f"(d[13]), "+f"(d[14]), "+f"(d[15]), "+f"(d[16]), "+f"(d[17]), "+f"(d[18]), "+f"(d[19]), "+f"(d[20]), "+f"(d[21]), "+f"(d[22]), "+f"(d[23]), "+f"(d[24]), "+f"(d[25]), "+f"(d[26]), "+f"(d[27]), "+f"(d[28]), "+f"(d[29]), "+f"(d[30]), "+f"(d[31]), "+f"(d[32]), "+f"(d[33]), "+f"(d[34]), "+f"(d[35]), "+f"(d[36]), "+f"(d[37]), "+f"(d[38]), "+f"(d[39]), "+f"(d[40]), "+f"(d[41]), "+f"(d[42]), "+f"(d[43]), "+f"(d[44]), "+f"(d[45]), "+f"(d[46]), "+f"(d[47]), "+f"(d[48]), "+f"(d[49]), "+f"(d[50]), "+f"(d[51]), "+f"(d[52]), "+f"(d[53]), "+f"(d[54]), "+f"(d[55]), "+f"(d[56]), "+f"(d[57]), "+f"(d[58]), "+f"(d[59]), "+f"(d[60]), "+f"(d[61]), "+f"(d[62]), "+f"(d[63])
    : "r"(a0), "r"(a1), "r"(a2), "r"(a3), "l"(descB), "r"(scaleD));
}
__device__ __forceinline__ void wgmma_rs_n64_ta0_tb1(float (&d)[32], uint32_t a0, uint32_t a1, uint32_t a2, uint32_t a3, uint64_t descB, int scaleD) {
  asm volatile("{\n.reg .pred p;\nsetp.ne.b32 p, %37, 0;\n"
    "wgmma.mma_async.sync.aligned.m64n64k16.f32.bf16.bf16 "
    "{%0, %1, %2, %3, %4, %5, %6, %7, %8, %9, %10, %11, %12, %13, %14, %15, %16, %17, %18, %19, %20, %21, %22, %23, %24, %25, %26, %27, %28, %29, %30, %31}, "
    "{%32, %33, %34, %35}, %36, p, 1, 1, 1;\n}\n"
    : "+f"(d[0]), "+f"(d[1]), "+f"(d[2]), "+f"(d[3]), "+f"(d[4]), "+f"(d[5]), "+f"(d[6]), "+f"(d[7]), "+f"(d[8]), "+f"(d[9]), "+f"(d[10]), "+f"(d[11]), "+f"(d[12]), "+f"(d[13]), "+f"(d[14]), "+f"(d[15]), "+f"(d[16]), "+f"(d[17]), "+f"(d[18]), "+f"(d[19]), "+f"(d[20]), "+f"(d[21]), "+f"(d[22]), "+f"(d[23]), "+f"(d[24]), "+f"(d[25]), "+f"(d[26]), "+f"(d[27]), "+f"(d[28]), "+f"(d[29]), "+f"(d[30]), "+f"(d[31])
    : "r"(a0), "r"(a1), "r"(a2), "r"(a3), "l"(descB), "r"(scaleD));
}
__device__ __forceinline__ void wgmma_ss_n128_ta0_tb1(float (&d)[64], uint64_t descA, uint64_t descB, int scaleD) {
  asm volatile("{\n.reg .pred p;\nsetp.ne.b32 p, %66, 0;\n"
    "wgmma.mma_async.sync.aligned.m64n128k16.f32.bf16.bf16 "
    "{%0, %1, %2, %3, %4, %5, %6, %7, %8, %9, %10, %11, %12, %13, %14, %15, %16, %17, %18, %19, %20, %21, %22, %23, %24, %25, %26, %27, %28, %29, %30, %31, %32, %33, %34, %35, %36, %37, %38, %39, %40, %41, %42, %43, %44, %45, %46, %47, %48, %49, %50, %51, %52, %53, %54, %55, %56, %57, %58, %59, %60, %61, %62, %63}, "
    "%64, %65, p, 1, 1, 0, 1;\n}\n"
    : "+f"(d[0]), "+f"(d[1]), "+f"(d[2]), "+f"(d[3]), "+f"(d[4]), "+f"(d[5]), "+f"(d[6]), "+f"(d[7]), "+f"(d[8]), "+f"(d[9]), "+f"(d[10]), "+f"(d[11]), "+f"(d[12]), "+f"(d[13]), "+f"(d[14]), "+f"(d[15]), "+f"(d[16]), "+f"(d[17]), "+f"(d[18]), "+f"(d[19]), "+f"(d[20]), "+f"(d[21]), "+f"(d[22]), "+f"(d[23]), "+f"(d[24]), "+f"(d[25]), "+f"(d[26]), "+f"(d[27]), "+f"(d[28]), "+f"(d[29]), "+f"(d[30]), "+f"(d[31]), "+f"(d[32]), "+f"(d[33]), "+f"(d[34]), "+f"(d[35]), "+f"(d[36]), "+f"(d[37]), "+f"(d[38]), "+f"(d[39]), "+f"(d[40]), "+f"(d[41]), "+f"(d[42]), "+f"(d[43]), "+f"(d[44]), "+f"(d[45]), "+f"(d[46]), "+f"(d[47]), "+f"(d[48]), "+f"(d[49]), "+f"(d[50]), "+f"(d[51]), "+f"(d[52]), "+f"(d[53]), "+f"(d[54]), "+f"(d[55]), "+f"(d[56]), "+f"(d[57]), "+f"(d[58]), "+f"(d[59]), "+f"(d[60]), "+f"(d[61]), "+f"(d[62]), "+f"(d[63])
    : "l"(descA), "l"(descB), "r"(scaleD));
}
__device__ __forceinline__ void wgmma_ss_n160_ta0_tb1(float (&d)[80], uint64_t descA, uint64_t descB, int scaleD) {
  asm volatile("{\n.reg .pred p;\nsetp.ne.b32 p, %82, 0;\n"
    "wgmma.mma_async.sync.aligned.m64n160k16.f32.bf16.bf16 "
    "{%0, %1, %2, %3, %4, %5, %6, %7, %8, %9, %10, %11, %12, %13, %14, %15, %16, %17, %18, %19, %20, %21, %22, %23, %24, %25, %26, %27, %28, %29, %30, %31, %32, %33, %34, %35, %36, %37, %38, %39, %40, %41, %42, %43, %44, %45, %46, %47, %48, %49, %50, %51, %52, %53, %54, %55, %56, %57, %58, %59, %60, %61, %62, %63, %64, %65, %66, %67, %68, %69, %70, %71, %72, %73, %74, %75, %76, %77, %78, %79}, "
    "%80, %81, p, 1, 1, 0, 1;\n}\n"
    : "+f"(d[0]), "+f"(d[1]), "+f"(d[2]), "+f"(d[3]), "+f"(d[4]), "+f"(d[5]), "+f"(d[6]), "+f"(d[7]), "+f"(d[8]), "+f"(d[9]), "+f"(d[10]), "+f"(d[11]), "+f"(d[12]), "+f"(d[13]), "+f"(d[14]), "+f"(d[15]), "+f"(d[16]), "+f"(d[17]), "+f"(d[18]), "+f"(d[19]), "+f"(d[20]), "+f"(d[21]), "+f"(d[22]), "+f"(d[23]), "+f"(d[24]), "+f"(d[25]), "+f"(d[26]), "+f"(d[27]), "+f"(d[28]), "+f"(d[29]), "+f"(d[30]), "+f"(d[31]), "+f"(d[32]), "+f"(d[33]), "+f"(d[34]), "+f"(d[35]), "+f"(d[36]), "+f"(d[37]), "+f"(d[38]), "+f"(d[39]), "+f"(d[40]), "+f"(d[41]), "+f"(d[42]), "+f"(d[43]), "+f"(d[44]), "+f"(d[45]), "+f"(d[46]), "+f"(d[47]), "+f"(d[48]), "+f"(d[49]), "+f"(d[50]), "+f"(d[51]), "+f"(d[52]), "+f"(d[53]), "+f"(d[54]), "+f"(d[55]), "+f"(d[56]), "+f"(d[57]), "+f"(d[58]), "+f"(d[59]), "+f"(d[60]), "+f"(d[61]), "+f"(d[62]), "+f"(d[63]), "+f"(d[64]), "+f"(d[65]), "+f"(d[66]), "+f"(d[67]), "+f"(d[68]), "+f"(d[69]), "+f"(d[70]), "+f"(d[71]), "+f"(d[72]), "+f"(d[73]), "+f"(d[74]), "+f"(d[75]), "+f"(d[76]), "+f"(d[77]), "+f"(d[78]), "+f"(d[79])
    : "l"(descA), "l"(descB), "r"(scaleD));
}

#define PROF_DECL(b)
#define PROF_EV(tag)
#define PROF_GT(tag)

template <int N> struct IC { static constexpr int value = N; };
struct Cur {
    uint32_t slot, ph;
    __device__ __forceinline__ void adv() { if (++slot == NSLOT) { slot = 0; ph ^= 1; } }
};
constexpr int E0 = 2;
__host__ __device__ constexpr uint32_t slot_of(int e) { return (e + E0) % NSLOT; }
__device__ __forceinline__ Cur cur_at(int e) { Cur c; c.slot = (e + E0) % NSLOT; c.ph = ((e + E0) / NSLOT) & 1; return c; }

__device__ __forceinline__ int kv_tile(int s) { return (0x804Cu >> (4 * s)) & 15; }
__device__ __forceinline__ int op_head(int i, int kap) { return 16 * kap + 2 * (i & 7) + (i >> 3); }

constexpr float SM_SCALE = 0.08838834764831845f * 1.4426950408889634f;

struct Ctx {
    uint32_t ring, misc;
    uint32_t rel;
    int w, warp, lane;
};
__device__ __forceinline__ void release(const Ctx& c, uint32_t off, uint32_t cnt) {
    if (c.lane < 2) mbar_arrive_cluster(c.rel + off, cnt);
}
__device__ __forceinline__ void signal_event(const Ctx& c, int ev) {
    __syncwarp();
    if (c.lane == 0) mbar_arrive(c.misc + BAR_EV + (c.w * 16 + ev) * 8);
}
template <int NK, int OFF, int N>
__device__ __forceinline__ uint32_t load_afrag(uint32_t (&a)[N], uint32_t base, const Ctx& c) {
    int r = c.lane & 7, mat = c.lane >> 3;
    uint32_t addr = base + (8 * (mat >> 1) + r) * 128 + (((2 * c.warp + (mat & 1)) ^ r) << 4);
#pragma unroll
    for (int k = 0; k < NK; k++) ldsm4t(a[OFF + 4 * k], a[OFF + 4 * k + 1], a[OFF + 4 * k + 2], a[OFF + 4 * k + 3], addr + k * 2048);
    uint32_t dep = 0;
#pragma unroll
    for (int k = 0; k < NK; k++) dep |= a[OFF + 4 * k];
    return dep & blockIdx.y;
}
__device__ __forceinline__ void tile_out(unsigned char* (&out)[2], unsigned char* dst, int row0, int perm, const Ctx& c) {
#pragma unroll
    for (int i = 0; i < 2; i++) {
        int row = row0 + 16 * c.warp + 8 * i + (c.lane >> 2);
        if (perm) row = perm32(row);
        out[i] = dst + row * 64 + (((c.lane ^ (row >> 1)) & 3) << 4);
    }
}
__device__ __forceinline__ void store_pair(const float (&a)[64], int q, unsigned char* const (&out)[2], int quarter_stride, const float (&f)[2]) {
#pragma unroll
    for (int i = 0; i < 2; i++)
        stg128(out[i] + q * quarter_stride,
               pack_bf16(a[16 * q + 2 * i] * f[i], a[16 * q + 2 * i + 1] * f[i]), pack_bf16(a[16 * q + 4 + 2 * i] * f[i], a[16 * q + 4 + 2 * i + 1] * f[i]),
               pack_bf16(a[16 * q + 8 + 2 * i] * f[i], a[16 * q + 8 + 2 * i + 1] * f[i]), pack_bf16(a[16 * q + 12 + 2 * i] * f[i], a[16 * q + 12 + 2 * i + 1] * f[i]));
}

constexpr float SAFE_SUM = 1099511627776.0f;
template <int NJ>
__device__ __forceinline__ void row_max(const float (&s)[4 * NJ], float (&mx)[2]) {
#pragma unroll
    for (int i = 0; i < 2; i++) {
        float a = fmaxf(s[2 * i], s[2 * i + 1]), b = fmaxf(s[4 + 2 * i], s[4 + 2 * i + 1]);
#pragma unroll
        for (int j = 2; j < NJ; j += 2) {
            a = fmaxf(a, fmaxf(s[4 * j + 2 * i], s[4 * j + 2 * i + 1]));
            b = fmaxf(b, fmaxf(s[4 * j + 4 + 2 * i], s[4 * j + 4 + 2 * i + 1]));
        }
        a = fmaxf(a, b);
        a = fmaxf(a, __shfl_xor_sync(0xffffffffu, a, 1));
        mx[i] = fmaxf(a, __shfl_xor_sync(0xffffffffu, a, 2));
    }
}
template <int NJ, bool SHIFT>
__device__ __forceinline__ void exp_sum(float (&s)[4 * NJ], const float (&m)[2], float& l0, float& l1) {
#pragma unroll
    for (int j = 0; j < NJ; j++) {
#pragma unroll
        for (int e = 0; e < 4; e++) s[4 * j + e] = ex2(SHIFT ? s[4 * j + e] - m[e >> 1] : s[4 * j + e]);
        l0 += s[4 * j + 0] + s[4 * j + 1]; l1 += s[4 * j + 2] + s[4 * j + 3];
    }
}
__device__ __forceinline__ void recompute_scores(float (&s)[64], const uint32_t (&q)[32], uint32_t kaddr, const Ctx& c) {
    const int r = c.lane & 7, mat = c.lane >> 3;
    const uint32_t a0 = kaddr + (8 * (mat & 1) + r) * 64 + (((mat >> 1) ^ (r >> 1)) << 4);
#pragma unroll
    for (int i = 0; i < 64; i++) s[i] = 0.f;
#pragma unroll
    for (int jp = 0; jp < 8; jp++) {
#pragma unroll
        for (int k = 0; k < 8; k++) {
            asm volatile(
                "{\n.reg .b32 b0, b1, b2, b3;\n"
                "ldmatrix.sync.aligned.m8n8.x4.trans.shared.b16 {b0,b1,b2,b3}, [%12];\n"
                "mma.sync.aligned.m16n8k16.row.col.f32.bf16.bf16.f32 {%0,%1,%2,%3}, {%8,%9,%10,%11}, {b0,b1}, {%0,%1,%2,%3};\n"
                "mma.sync.aligned.m16n8k16.row.col.f32.bf16.bf16.f32 {%4,%5,%6,%7}, {%8,%9,%10,%11}, {b2,b3}, {%4,%5,%6,%7};\n}\n"
                : "+f"(s[8 * jp]), "+f"(s[8 * jp + 1]), "+f"(s[8 * jp + 2]), "+f"(s[8 * jp + 3]),
                  "+f"(s[8 * jp + 4]), "+f"(s[8 * jp + 5]), "+f"(s[8 * jp + 6]), "+f"(s[8 * jp + 7])
                : "r"(q[4 * k]), "r"(q[4 * k + 1]), "r"(q[4 * k + 2]), "r"(q[4 * k + 3]),
                  "r"((a0 ^ ((jp & 1) << 5)) + (jp >> 1) * 8192 + k * 1024) : "memory");
        }
    }
}
__device__ __forceinline__ int mask_lim(const Ctx& c) { return perm32(16 * c.warp + (c.lane >> 2)) - 8 * (c.lane & 3); }
template <int J0>
__device__ __forceinline__ void mask_diag(float (&s)[4 * J0 + 32], const Ctx& c) {
    const int lim = mask_lim(c);
    if (c.warp < 2) {
#pragma unroll
        for (int x = 0; x < 16; x++) {
            if (2 * (x >> 2) + (x & 1) - (x & 2) > lim) s[4 * J0 + x] = -INFINITY;
            s[4 * J0 + 16 + x] = -INFINITY;
        }
    } else {
#pragma unroll
        for (int x = 0; x < 16; x++)
            if (32 + 2 * (x >> 2) + (x & 1) - (x & 2) > lim) s[4 * J0 + 16 + x] = -INFINITY;
    }
}
__device__ __forceinline__ void mask_any(float (&s)[64], int hh, const Ctx& c) {
    const int lim = mask_lim(c) + 64 * hh;
#pragma unroll
    for (int x = 0; x < 64; x++)
        if (32 * (x >> 4) + 2 * ((x >> 2) & 3) + (x & 1) - (x & 2) > lim) s[x] = -INFINITY;
}
__device__ __forceinline__ void issue_pv(float (&o)[64], const uint32_t (&p)[32], uint32_t vaddr, int acc, int mode  ) {
    uint64_t d = mkdesc(vaddr, 16, 512, 2);
    if (mode == 0) {
        wg_fence();
#pragma unroll
        for (int k = 0; k < 8; k++)
            wgmma_rs_n128_ta0_tb0(o, p[4 * k], p[4 * k + 1], p[4 * k + 2], p[4 * k + 3], d + (k >> 1) * 512 + 2 * (k & 1), k ? 1 : acc);
        wg_commit();
    } else if (mode == 1) {
        wg_fence();
#pragma unroll
        for (int k = 0; k < 4; k++) wgmma_rs_n128_ta0_tb0(o, p[4 * k], p[4 * k + 1], p[4 * k + 2], p[4 * k + 3], d + (k >> 1) * 512 + 2 * (k & 1), k != 0);
        wg_commit();
    } else {
        wg_fence();
        wgmma_rs_n128_ta0_tb0(o, p[0], p[1], p[2], p[3], d, acc);
        wg_commit();
    }
}
__device__ __forceinline__ void issue_qk(float (&s)[64], const uint32_t (&q)[32], uint32_t kaddr) {
    uint64_t d = mkdesc(kaddr, 8192, 512, 2);
    wg_fence();
#pragma unroll
    for (int k = 0; k < 8; k++) wgmma_rs_n128_ta0_tb1(s, q[4 * k], q[4 * k + 1], q[4 * k + 2], q[4 * k + 3], d + 64 * k, k != 0);
    wg_commit();
}
__device__ __forceinline__ void issue_qk_half(float (&s32)[32], const uint32_t (&q)[32], uint32_t kaddr) {
    uint64_t d = mkdesc(kaddr, 8192, 512, 2);
    wg_fence();
#pragma unroll
    for (int k = 0; k < 8; k++) wgmma_rs_n64_ta0_tb1(s32, q[4 * k], q[4 * k + 1], q[4 * k + 2], q[4 * k + 3], d + 64 * k, k != 0);
    wg_commit();
}
__device__ __forceinline__ void row_inv(const float (&l)[2], float (&inv)[2]) {
#pragma unroll
    for (int i = 0; i < 2; i++) {
        float sum = l[i];
        sum += __shfl_xor_sync(0xffffffffu, sum, 1);
        sum += __shfl_xor_sync(0xffffffffu, sum, 2);
        inv[i] = rcp_fast(sum);
    }
}

__device__ __forceinline__ const unsigned char* xn_addr(int row, int col) {
    row = perm32(row);
    return g_xn + ((row >> 7) * 10 + (col >> 6)) * 16384 + (row & 127) * 128 + ((((col & 63) >> 3) ^ (row & 7)) << 4);
}
__device__ __forceinline__ void mma16816(float (&d)[4], uint32_t a0, uint32_t a1, uint32_t a2, uint32_t a3, uint32_t b0, uint32_t b1) {
    asm volatile("mma.sync.aligned.m16n8k16.row.col.f32.bf16.bf16.f32 {%0,%1,%2,%3}, {%4,%5,%6,%7}, {%8,%9}, {%0,%1,%2,%3};"
                 : "+f"(d[0]), "+f"(d[1]), "+f"(d[2]), "+f"(d[3]) : "r"(a0), "r"(a1), "r"(a2), "r"(a3), "r"(b0), "r"(b1));
}
__device__ __forceinline__ uint32_t lds32(uint32_t addr) { uint32_t v; asm volatile("ld.shared.u32 %0, [%1];" : "=r"(v) : "r"(addr)); return v; }

__device__ LNINL void ln_rows(const __nv_bfloat16* x, int row0, int lane, uint32_t wr_s) {
    const int hl = lane & 15, row = row0 + (lane >> 4);
    uint32_t v[20];
#pragma unroll
    for (int i = 0; i < 5; i++) {
        uint4 u;
        asm("ld.global.nc.L2::cache_hint.v4.b32 {%0,%1,%2,%3}, [%4], %5;" : "=r"(u.x), "=r"(u.y), "=r"(u.z), "=r"(u.w)
            : "l"(x + (size_t)row * DM + 128 * i + 8 * hl), "l"(policy(HM & 512)));
        v[4 * i] = u.x; v[4 * i + 1] = u.y; v[4 * i + 2] = u.z; v[4 * i + 3] = u.w;
    }
    float mean = 0.f, m2 = 0.f, acc2 = 0.f;
#pragma unroll
    for (int i = 0; i < 20; i++) { mean += bf_lo(v[i]); acc2 += bf_hi(v[i]); }
    mean = (mean + acc2) * (1.0f / 40);
    acc2 = 0.f;
#pragma unroll
    for (int i = 0; i < 20; i++) {
        float d0 = __uint_as_float(__byte_perm(v[i], 0, 0x1044)) - mean, d1 = __uint_as_float(__byte_perm(v[i], 0, 0x3244)) - mean;
        m2 = fmaf(d0, d0, m2); acc2 = fmaf(d1, d1, acc2);
    }
    m2 += acc2;
    acc2 = 0.f;
#pragma unroll
    for (int o = 1; o < 16; o <<= 1) {
        float mo = __shfl_xor_sync(0xffffffffu, mean, o), qo = __shfl_xor_sync(0xffffffffu, m2, o), d = mo - mean;
        m2 = fmaf(d * d, 20.0f * o, m2 + qo);
        mean = 0.5f * (mean + mo);
    }
    const uint32_t mb2 = pack_bf16(mean, mean);
    const float inv = rcp_fast(bf_round(sqrt_fast(bf_round(bf_round(m2 * (1.0f / DM)) + 1e-5f))));
    float dot = 0.f;
    unsigned char* xp = const_cast<unsigned char*>(xn_addr(row, 8 * hl));
#pragma unroll
    for (int i = 0; i < 5; i++) {
        uint32_t ww[4];
        asm volatile("ld.shared.v4.b32 {%0,%1,%2,%3}, [%4];" : "=r"(ww[0]), "=r"(ww[1]), "=r"(ww[2]), "=r"(ww[3]) : "r"(wr_s + 256 * i + 16 * hl) : "memory");
#pragma unroll
        for (int e = 0; e < 4; e++) {
            uint32_t d;
            asm("sub.rn.bf16x2 %0, %1, %2;" : "=r"(d) : "r"(v[4 * i + e]), "r"(mb2));
            d = pack_bf16(bf_lo(d) * inv, bf_hi(d) * inv);
            v[4 * i + e] = d;
            dot = fmaf(bf_lo(d), bf_lo(ww[e]), dot);
            acc2 = fmaf(bf_hi(d), bf_hi(ww[e]), acc2);
        }
        stg128(xp + i * 32768, v[4 * i], v[4 * i + 1], v[4 * i + 2], v[4 * i + 3]);
    }
    dot += acc2;
#pragma unroll
    for (int o = 8; o > 0; o >>= 1) dot += __shfl_xor_sync(0xffffffffu, dot, o);
    if (hl == 0) { g_router[row] = bf_round(dot); g_stats[row] = make_uint2(mb2, __float_as_uint(inv)); }
}

__device__ __forceinline__ void aux_cta(const CUtensorMap* tmG, const CUtensorMap* tmU, const CUtensorMap* tmD, unsigned char* sm, int a) {
    constexpr int STG = 57344, XS = 3 * STG, HS = XS + 8 * 1296, KEY = HS + 8 * 912, MI = KEY + 8192;
    const int tid = threadIdx.x, warp = __shfl_sync(0xffffffffu, tid >> 5, 0), lane = tid & 31;
    const uint32_t sb = smem_u32(sm);
    const uint32_t full = sb + MI, empty = sb + MI + 32;
    int* s_sel = reinterpret_cast<int*>(sm + MI + 64);
    float* s_r = reinterpret_cast<float*>(sm + MI + 96);
    volatile unsigned* s_misc = reinterpret_cast<volatile unsigned*>(sm + MI + 128);
    uint32_t* s_key = reinterpret_cast<uint32_t*>(sm + KEY);
    PROF_DECL(128 + a)
    PROF_GT(0);
    if (tid == 0) {
        for (int i = 0; i < 3; i++) { mbar_init(full + 8 * i, 1); mbar_init(empty + 8 * i, 10); }
        asm volatile("fence.mbarrier_init.release.cluster;" ::: "memory");
    }
    __syncthreads();
    if (warp == 11) {
        if (elect_one()) {
            int st = 0; uint32_t ph = 0;
#pragma unroll 1
            for (int s = 0; s < 34; s++) {
                mbar_wait(empty + 8 * st, ph ^ 1);
                const uint32_t dst = sb + st * STG, fb = full + 8 * st;
                if (s < 20) {
                    mbar_expect_tx(fb, 57344);
                    tma3d(dst, tmG, 0, 32 * s, 7 * a, fb);
                    tma3d(dst + 28672, tmU, 0, 32 * s, 7 * a, fb);
                } else {
                    mbar_expect_tx(fb, 40960);
                    tma3d(dst, tmD, 0, 448 * a + 32 * (s - 20), 0, fb);
                }
                if (s >= 3) {
#pragma unroll 1
                    for (int f = (s == 3 ? 4 : s + 6); f <= s + 6 && f < 34; f++) {
                        if (f < 20) { tma3d_prefetch(tmG, 0, 32 * f, 7 * a); tma3d_prefetch(tmU, 0, 32 * f, 7 * a); }
                        else tma3d_prefetch(tmD, 0, 448 * a + 32 * (f - 20), 0);
                    }
                }
                if (++st == 3) { st = 0; ph ^= 1; }
            }
        }
        return;
    }
    PROF_GT(49);
    if (warp == 10) return;
    if (tid < 8) {
        unsigned e = *reinterpret_cast<volatile unsigned*>(&g_epoch);
        if (tid == 0) s_misc[0] = e;
        flag_wait(flag_ptr(FL_LN + tid), (e + 1) * (tid < 4 ? 33u : 128u));
    }
    bar_sync(1, 320);
    PROF_GT(50);
    const unsigned ep = s_misc[0];
    auto top8 = [&](uint32_t (&key)[8]) {
        uint32_t mine = 0;
#pragma unroll 1
        for (int r = 0; r < TOPC; r++) {
            uint32_t best = 0;
#pragma unroll
            for (int i = 0; i < 8; i++) best = max(best, key[i]);
            best = __reduce_max_sync(0xffffffffu, best);
#pragma unroll
            for (int i = 0; i < 8; i++) if (key[i] == best) key[i] = 0;
            if (lane == r) mine = best;
        }
        return mine;
    };
#pragma unroll 1
    for (int pass = 0; pass < 2; pass++) {
        if (warp < (pass ? 1 : 8)) {
            uint32_t key[8];
#pragma unroll
            for (int i = 0; i < 8; i++) {
                if (pass == 0) {
                    int idx = warp * 256 + i * 32 + lane;
                    uint32_t b = __float_as_uint(__ldcg(g_router + idx)) >> 16;
                    b = (b & 0x8000u) ? (~b & 0xffffu) : (b | 0x8000u);
                    key[i] = (b << 16) | (uint32_t)(0xffff - idx);
                } else key[i] = i < 2 ? s_key[i * 32 + lane] : 0u;
            }
            uint32_t best = top8(key);
            if (lane < TOPC) {
                if (pass == 0) s_key[warp * 8 + lane] = best;
                else {
                    uint32_t b = best >> 16;
                    b = (b & 0x8000u) ? (b & 0x7fffu) : (~b & 0xffffu);
                    s_sel[lane] = 0xffff - (int)(best & 0xffffu);
                    s_r[lane] = bf_round(rcp_fast(1.0f + __expf(fminf(-__uint_as_float(b << 16), 80.f))));
                }
            }
        }
        bar_sync(1, 320);
    }
#pragma unroll 1
    for (int it = 0; it < 2; it++) {
        int i = tid + it * 320, tk = i / 80, ch = i % 80;
        *reinterpret_cast<uint4*>(sm + XS + tk * 1296 + ch * 16) = __ldcg(reinterpret_cast<const uint4*>(xn_addr(s_sel[tk], ch * 8)));
    }
    bar_sync(1, 320);
    PROF_GT(51);
    const int g = lane >> 2, t = lane & 3;
    const uint32_t woff = warp * 4096 + (8 * (lane >> 4) + (lane & 7)) * 128 + ((((lane >> 3) & 1) ^ (lane & 7)) << 4);
    int st = 0; uint32_t ph = 0;
    float ga[4][4], ua[4][4];
#pragma unroll
    for (int i = 0; i < 4; i++)
#pragma unroll
        for (int e = 0; e < 4; e++) { ga[i][e] = 0.f; ua[i][e] = 0.f; }
#pragma unroll 1
    for (int s = 0; s < 34; s++) {
        if (s == 20) {
            if (warp < 7) {
#pragma unroll 1
                for (int i = 0; i < 4; i++) {
#pragma unroll
                    for (int e = 0; e < 4; e++) {
                        float gv = bf_round(ga[0][e]), uv = bf_round(ua[0][e]);
                        float sg = bf_round(gv * rcp_fast(1.0f + __expf(fminf(-gv, 80.f))));
                        int f = warp * 64 + i * 16 + g + 8 * (e >> 1), tk = 2 * t + (e & 1);
                        *reinterpret_cast<__nv_bfloat16*>(sm + HS + tk * 912 + f * 2) = __float2bfloat16_rn(sg * uv);
                        ga[0][e] = ga[1][e]; ga[1][e] = ga[2][e]; ga[2][e] = ga[3][e]; ga[3][e] = 0.f;
                        ua[0][e] = ua[1][e]; ua[1][e] = ua[2][e]; ua[2][e] = ua[3][e];
                    }
                }
            }
            bar_sync(1, 320);
            PROF_GT(52);
        }
        mbar_wait(full + 8 * st, ph);
        if (s >= 20 || warp < 7) {
#pragma unroll
            for (int kk = 0; kk < 2; kk++) {
                uint32_t xb = sb + (s < 20 ? XS + g * 1296 + s * 64 : HS + g * 912 + (s - 20) * 64) + 32 * kk + 4 * t;
                uint32_t b0 = lds32(xb), b1 = lds32(xb + 16);
                uint32_t wa = sb + st * STG + woff + kk * 2048;
#pragma unroll
                for (int i = 0; i < 4; i++) {
                    uint32_t a0, a1, a2, a3;
                    ldsm4t(a0, a1, a2, a3, wa ^ (i << 5));
                    mma16816(ga[i], a0, a1, a2, a3, b0, b1);
                    if (s < 20) {
                        ldsm4t(a0, a1, a2, a3, (wa ^ (i << 5)) + 28672);
                        mma16816(ua[i], a0, a1, a2, a3, b0, b1);
                    }
                }
            }
        }
        asm volatile("fence.proxy.async.shared::cta;" ::: "memory");
        __syncwarp();
        if (lane == 0) mbar_arrive(empty + 8 * st);
        if (++st == 3) { st = 0; ph ^= 1; }
    }
#pragma unroll
    for (int i = 0; i < 4; i++)
#pragma unroll
        for (int e = 0; e < 4; e += 2)
            *reinterpret_cast<float2*>(g_moe_part + (a * DM + warp * 64 + i * 16 + g + 4 * e) * 8 + 2 * t) = make_float2(ga[i][e], ga[i][e + 1]);
    bar_sync(1, 320);
    if (tid == 0) {
        __threadfence();
        unsigned old = atomicAdd(flag_ptr(FL_MOE_CNT), 1u);
        s_misc[1] = (old == ep * 4u + 3u);
        __threadfence();
    }
    bar_sync(1, 320);
    PROF_GT(53);
    if (s_misc[1]) {
        const float4* pp = reinterpret_cast<const float4*>(g_moe_part);
#pragma unroll 1
        for (int i = tid; i < DM * 2; i += 320) {
            float4 v0 = __ldcg(pp + i), v1 = __ldcg(pp + DM * 2 + i), v2 = __ldcg(pp + DM * 4 + i), v3 = __ldcg(pp + DM * 6 + i);
            float y[4] = {v0.x + v1.x + v2.x + v3.x, v0.y + v1.y + v2.y + v3.y, v0.z + v1.z + v2.z + v3.z, v0.w + v1.w + v2.w + v3.w};
#pragma unroll
            for (int e = 0; e < 4; e++) {
                int col = i >> 1, tk = (i & 1) * 4 + e;
                float upd = bf_round(bf_round(y[e]) * s_r[tk]);
                float xn = __bfloat162float(*reinterpret_cast<const __nv_bfloat16*>(sm + XS + tk * 1296 + col * 2));
                g_brow[tk * DM + col] = __float2bfloat16_rn(xn + upd);
            }
        }
        if (tid < TOPC) g_sel[tid] = s_sel[tid];
        bar_sync(1, 320);
        if (tid == 0) {
            flag_signal(flag_ptr(FL_MOE_DONE));
            *reinterpret_cast<volatile unsigned*>(&g_epoch) = ep + 1;
        }
        PROF_GT(54);
    }
}

__global__ void __cluster_dims__(2, 1, 1) __launch_bounds__(384, 1)
fused_kernel(const __grid_constant__ CUtensorMap tmC, const __grid_constant__ CUtensorMap tmWk, const __grid_constant__ CUtensorMap tmWv,
             const __grid_constant__ CUtensorMap tmWq, const __grid_constant__ CUtensorMap tmWo,
             const __grid_constant__ CUtensorMap tmG, const __grid_constant__ CUtensorMap tmU, const __grid_constant__ CUtensorMap tmD, const Params P) {
    extern __shared__ __align__(1024) unsigned char smem_raw[];
    const uint32_t ring = smem_u32(smem_raw);
    const uint32_t misc = ring + RING_BYTES;
    const int tid = threadIdx.x;
    const int rank = blockIdx.x & 1;
    uint32_t smid, nsm;
    asm("mov.u32 %0, %%smid;" : "=r"(smid));
    asm("mov.u32 %0, %%nsmid;" : "=r"(nsm));
    if (nsm != 132) smid = blockIdx.x;
    auto role_of = [](int tpc) {
        return tpc < 32 ? (tpc & 7) * 8 + (tpc >> 3) : tpc < 60 ? (1 + (tpc - 32) % 7) * 8 + 4 + (tpc - 32) / 7 : tpc < 64 ? tpc - 56 : tpc;
    };
    int mc = role_of(smid >> 1);
    PROF_DECL(mc * 2 + rank)
    PROF_GT(0); PROF_EV(1);

    auto prefetch_w = [&](int ch) {
        const int i = tid - 128;
        asm volatile("prefetch.global.L2 [%0];" ::"l"((rank ? P.wv : P.wk) + (size_t)(ch * 128 + (mc & 3) * 32 + (i >> 3)) * 4096 + (mc >> 2) * 256 + (i & 7) * 16));
    };
    if (tid >= 128 && mc < 64) {
        if (tid < 256) asm volatile("prefetch.global.L2 [%0];" ::"l"(P.c + (size_t)((12 + (mc & 3)) * 128 + ((mc >> 2) * 2 + rank) * 4) * DC + (tid - 128) * 16));
        prefetch_w(0);
    }
    auto load_w0 = [&]() {
        const CUtensorMap* tw = rank ? &tmWv : &tmWk;
        mbar_expect_tx(misc + BAR_FULL + 8 * slot_of(0), SLOT_BYTES);
        tma2d(ring + slot_of(0) * SLOT_BYTES, tw, (mc >> 2) * 256, 0, misc + BAR_FULL + 8 * slot_of(0), policy(HM & 1));
        tma2d(ring + slot_of(0) * SLOT_BYTES + 16384, tw, (mc >> 2) * 256 + 64, 0, misc + BAR_FULL + 8 * slot_of(0), policy(HM & 1));
    };
    if (tid == 0) {
#pragma unroll
        for (int i = 0; i < NSLOT; i++) mbar_init(misc + BAR_FULL + 8 * i, 1);
#pragma unroll
        for (int i = 0; i < E0; i++) mbar_arrive(misc + BAR_FULL + 8 * i);
        asm volatile("fence.mbarrier_init.release.cluster;" ::: "memory");
        if (mc < 64) load_w0();
    }
    if (tid == 160) {
        asm volatile("st.shared.u32 [%0], %1;" ::"r"(misc + MISC_SMID), "r"(smid) : "memory");
        asm volatile("fence.release.sync_restrict::shared::cta.cluster;" ::: "memory");
    }
    if (tid == 32) {
        asm volatile("prefetch.tensormap [%0];" ::"l"(&tmC) : "memory");
#pragma unroll
        for (int i = 0; i < NSLOT; i++) mbar_init(misc + BAR_EMPTY + 8 * i, 16);
#pragma unroll
        for (int i = 0; i < E0; i++) mbar_arrive_cluster(misc + BAR_EMPTY + 8 * i, 16);
        asm volatile("fence.mbarrier_init.release.cluster;" ::: "memory");
    }
    if (tid == 64) {
#pragma unroll
        for (int i = 0; i < NST3; i++) { mbar_init(misc + BAR_FULL3 + 8 * i, 1); mbar_init(misc + BAR_EMPTY3 + 8 * i, 16); }
#pragma unroll
        for (int i = 0; i < 4; i++) mbar_init(misc + BAR_LN + 8 * i, 2);
        mbar_init(misc + BAR_PROG, 1); mbar_init(misc + BAR_PROG + 8, 1); mbar_init(misc + BAR_PROG + 16, 1);
        asm volatile("fence.mbarrier_init.release.cluster;" ::: "memory");
    }
    if (tid == 96) {
#pragma unroll
        for (int i = 0; i < 34; i++) mbar_init(misc + BAR_DEP + 8 * i, 1);
    }
    if (tid == 128) {
#pragma unroll
        for (int i = 0; i < 32; i++) mbar_init(misc + BAR_EV + 8 * i, 4);
    }
    __syncthreads();
    asm volatile("barrier.cluster.arrive.relaxed.aligned;\nbarrier.cluster.wait.aligned;" ::: "memory");
    {
        uint32_t peer;
        asm volatile("ld.shared::cluster.u32 %0, [%1];" : "=r"(peer) : "r"(mapa(misc + MISC_SMID, rank ^ 1)) : "memory");
        if ((__shfl_sync(0xffffffffu, peer, 0) ^ smid) != 1) {
            if (tid == 0) {
                const unsigned ep1 = *reinterpret_cast<volatile unsigned*>(&g_epoch) + 1;
                if ((smid & 1) == 0) atomicExch(g_roleq + 2 + (atomicAdd(g_roleq, 1u) & 127), (ep1 << 8) | (smid >> 1));
                if (rank == 0) {
                    unsigned* slot = g_roleq + 2 + (atomicAdd(g_roleq + 1, 1u) & 127);
                    unsigned v = 0;
                    for (int spin = 0; spin < 4000000 && ((v = atomicAdd(slot, 0u)) >> 8) != (ep1 & 0xffffffu); spin++) {}
                    asm volatile("st.shared::cluster.u32 [%0], %1;" ::"r"(mapa(misc + MISC_SMID + 4, 0)), "r"(v & 255) : "memory");
                    asm volatile("st.shared::cluster.u32 [%0], %1;" ::"r"(mapa(misc + MISC_SMID + 4, 1)), "r"(v & 255) : "memory");
                }
                if (mc < 64) {
                    mbar_wait(misc + BAR_FULL + 8 * slot_of(0), 0);
                    asm volatile("mbarrier.inval.shared::cta.b64 [%0];" ::"r"(misc + BAR_FULL + 8 * slot_of(0)) : "memory");
                    mbar_init(misc + BAR_FULL + 8 * slot_of(0), 1);
                    asm volatile("fence.mbarrier_init.release.cluster;" ::: "memory");
                }
            }
            __syncwarp();
            asm volatile("barrier.cluster.arrive.aligned;\nbarrier.cluster.wait.aligned;" ::: "memory");
            mc = role_of(__shfl_sync(0xffffffffu, lds32(misc + MISC_SMID + 4), 0));
            if (tid == 0 && mc < 64) load_w0();
            __syncwarp();
        }
    }
    const int cta = mc * 2 + rank;
    const bool aux = mc >= 64;
    const int team = mc >> 2, k = mc & 3;
    const int u3 = (mc >> 4) * 2 + (team & 1), s3 = k, kap = (mc >> 3) & 1;
    const int partner = cta ^ 16;
    const int b0 = k, b1 = 7 - k;
    if (tid >= 128 && !aux) prefetch_w(1);
    if (tid == 256 && !aux) {
        const CUtensorMap* tw = rank ? &tmWv : &tmWk;
#pragma unroll
        for (int e = 1; e < NSLOT; e++) {
            const uint32_t fb = misc + BAR_FULL + 8 * slot_of(e), dst = ring + slot_of(e) * SLOT_BYTES;
            mbar_expect_tx(fb, SLOT_BYTES);
            if (e & 1) tma2d_mc(dst + rank * 16384, &tmC, (e >> 1) * 128 + rank * 64, (12 + k) * 128, fb, policy(false));
            else { tma2d(dst, tw, team * 256, e * 64, fb, policy(false)); tma2d(dst + 16384, tw, team * 256 + 64, e * 64, fb, policy(false)); }
        }
    }
    PROF_EV(5);
    const int wg = __shfl_sync(0xffffffffu, tid >> 7, 0);

    if (wg == 0 || aux) {
        asm volatile("setmaxnreg.dec.sync.aligned.u32 40;");
        const int warp = __shfl_sync(0xffffffffu, tid >> 5, 0), lane = tid & 31;
        if (warp == 0 && !aux) {
            const bool lead = elect_one();
            Cur c = cur_at(NSLOT);
            uint32_t dst, fb;
            auto acquire = [&]() {
                mbar_wait_sleep(misc + BAR_EMPTY + 8 * c.slot, c.ph ^ 1);
                fb = misc + BAR_FULL + 8 * c.slot; dst = ring + c.slot * SLOT_BYTES;
                if (lead) mbar_expect_tx(fb, SLOT_BYTES);
                c.adv();
            };
            auto load_w = [&](const CUtensorMap* tm, int col, int row, bool stream) {
                acquire();
                if (lead) { tma2d(dst, tm, col, row, fb, policy(stream)); tma2d(dst + 16384, tm, col + 64, row, fb, policy(stream)); }
            };
            auto load_half = [&](const unsigned char* src, bool stream) {
                acquire();
                if (lead) bulk_load_mc(dst + rank * 16384, src, 16384, fb, policy(stream));
            };
            auto dep_wait = [&](int d) { mbar_wait_sleep(misc + BAR_DEP + 8 * d, 0); fence_async_global(); };
            auto op_prefetch = [&](int i) {
                const int head = op_head(i, kap);
                l2_prefetch(reinterpret_cast<const unsigned char*>(P.wo) + head * 163840 + (u3 * 8 + s3 * 2 + rank) * 2560, 2560);
                if (i < 8) l2_prefetch(g_ctx + (size_t)(head * 32 + 4 * u3 + 2 * rank) * 16384 + s3 * 8192, 8192);
            };
            if (lead) l2_prefetch(reinterpret_cast<const unsigned char*>(P.c) + (size_t)cta * 12288, 12288);
            const CUtensorMap* tw = rank ? &tmWv : &tmWk;
            const unsigned char* Kh = g_K + (size_t)team * 32 * 16384 + rank * 16384;
            const unsigned char* Vh = g_V + (size_t)team * 32 * 16384 + rank * 16384;
#pragma unroll 1
            for (int v = 0; v < 2; v++) {
                const int h = 2 * team + v;
#pragma unroll 1
                for (int i = v ? 0 : 3; i < 16; i++) {
                    if (i < 4 && v) load_w(tw, h * 128, i * 128, HM & 1);
                    if (v && i == 3 && lead) mbar_arrive(misc + BAR_PROG + 8);
                    if (v && (i == 3 || i == 7)) dep_wait(D_WAR + (i > 3));
                    acquire();
                    if (lead) tma2d_mc(dst + rank * 16384, &tmC, (i & 3) * 128 + rank * 64, (kv_tile(i >> 2) + k) * 128, fb, policy(HM & 2));
                    if (i == WQPF && lead) {
                        tma2d_prefetch(&tmWq, h * 128 + rank * 64, k * 64); tma2d_prefetch(&tmWq, h * 128 + rank * 64, k * 64 + 256);
                        if (k < 2) tma2d_prefetch(&tmWq, h * 128 + rank * 64, k * 64 + 512);
                        if (v) l2_prefetch(g_xn + cta * 10240, 10240);
                    }
                }
                int togo = v ? PF_START : 11;
#pragma unroll 1
                for (int r = 0; r < 2; r++) {
                    const int p = r ? b1 : b0, n = 2 * p + 1;
                    if (v == 0) dep_wait(D_LN + r);
                    const int g0 = r ? rank ^ SWAPT : 3 - rank, g1 = 3 - g0;
                    const unsigned char* x0 = g_xn + (2 * p + (g0 >> 1)) * 163840 + (g0 & 1) * 8192;
                    const unsigned char* x1 = g_xn + (2 * p + (g1 >> 1)) * 163840 + (g1 & 1) * 8192;
#pragma unroll 1
                    for (int kc = 0; kc < 10; kc++) {
                        acquire();
                        if (lead) {
                            tma2d_mc(dst + 16384 + rank * 8192, &tmWq, h * 128 + rank * 64, kc * 64, fb, policy(false));
                            bulk_load(dst, x0 + kc * 16384, 8192, fb, policy(false));
                            bulk_load(dst + 8192, x1 + kc * 16384, 8192, fb, policy(false));
                        }
                    }
                    dep_wait(D_KV + 2 * v + r);
                    load_half(Kh + n * 32768, HM & 16);
#pragma unroll 1
                    for (int j = n - 1; j >= 0; j--) {
                        load_half(Kh + j * 32768, HM & 16); load_half(Vh + (j + 1) * 32768, HM & 16);
                        if (v == 0 && r && j == 7 && lead) mbar_arrive(misc + BAR_PROG);
                        --togo;
                        if (v == 0 && togo == 0 && lead) {
                            tma2d_prefetch(tw, h * 128 + 128, k * 128); tma2d_prefetch(tw, h * 128 + 192, k * 128);
                            l2_prefetch(reinterpret_cast<const unsigned char*>(P.c) + (size_t)cta * 16384, 16384);
                        }
                        if (v && togo <= 0 && togo > -OP_PF && lead) op_prefetch(-togo);
                    }
                    load_half(Vh, HM & 16);
                }
            }
            mbar_wait_sleep(misc + BAR_EMPTY + 8 * c.slot, c.ph ^ 1); c.adv();
            int st = 0; uint32_t ph3 = 0;
#pragma unroll 1
            for (int i = 0; i < 32; i++) {
                const int head = op_head(i >> 1, kap);
                if ((i & 1) == 0) dep_wait(D_CTX + (i >> 1));
                if (i < NST3) { mbar_wait_sleep(misc + BAR_EMPTY + 8 * c.slot, c.ph ^ 1); c.adv(); }
                else mbar_wait_sleep(misc + BAR_EMPTY3 + 8 * st, ph3 ^ 1);
                fb = misc + BAR_FULL3 + 8 * st; dst = ring + st * ST3_BYTES;
                if (i == LATE_AT && lead) mbar_arrive(misc + BAR_PROG + 16);
                if (lead) {
                    mbar_expect_tx(fb, ST3_BYTES);
                    const unsigned char* src = g_ctx + (size_t)(head * 32 + 4 * u3 + 2 * rank) * 16384 + (i & 1) * 8192;
                    bulk_load(dst, src, 8192, fb, policy(HM & 32));
                    bulk_load(dst + 8192, src + 16384, 8192, fb, policy(HM & 32));
                    tma3d_mc(dst + 16384 + rank * 10240, &tmWo, 0, head * 128 + (i & 1) * 64 + rank * 32, 5 * s3, fb, policy(HM & 32));
                    if ((i & 1) && (i >> 1) + OP_PF < 16) op_prefetch((i >> 1) + OP_PF);
                }
                if (++st == NST3) { st = 0; ph3 ^= 1; }
            }
        } else {
        if (warp >= 1 && warp <= 3 && lane < 27 && (warp - 1) * 27 + lane < 80) {
            const int ch = (warp - 1) * 27 + lane;
            uint4 u = __ldg(reinterpret_cast<const uint4*>(P.wr) + ch);
            asm volatile("st.shared.v4.b32 [%0], {%1,%2,%3,%4};" ::"r"(misc + MISC_WR + 16 * ch), "r"(u.x), "r"(u.y), "r"(u.z), "r"(u.w) : "memory");
        }
        bar_sync(3, aux ? 384 : 96);
        const int nln = aux ? (warp < 8 ? 3 : 2) : (warp == 3 ? 1 : 3), rstep = aux ? 24 : -512;
        int lrow = aux ? (cta - 128) * 256 + 192 + 2 * warp : (cta >> 5) * 256 + (cta & 31) * 6 + (warp - 1) * 2;
        int lnext = aux ? lrow + 24 : 1536 + cta * 4 + (warp - 1) * 2;
#pragma unroll 1
        for (int t = 0; t < nln; t++) {
            if (t + 1 < nln) {
#pragma unroll
                for (int i = 0; i < 3; i++)
                    if (i * 32 + lane < 80) asm volatile("prefetch.global.L2 [%0];" ::"l"(P.x + (size_t)lnext * DM + (i * 32 + lane) * 16));
            }
            ln_rows(P.x, lrow, lane, misc + MISC_WR);
            __syncwarp();
            if (lane == 0 && warp < 3 && !aux) {
                if (t) flag_signal(flag_ptr(FL_LN + (lrow >> 8))); else mbar_arrive(misc + BAR_LN);
            }
            lrow = lnext; lnext += rstep;
        }
        if (aux) {
            bar_sync(3, 384);
            if (tid == 320) flag_signal(flag_ptr(FL_LN + cta - 128));
            __syncwarp();
            asm volatile("setmaxnreg.inc.sync.aligned.u32 128;");
            aux_cta(&tmG, &tmU, &tmD, smem_raw, cta - 128);
        } else
        if (warp == 3) {
            const unsigned ep1 = *reinterpret_cast<volatile unsigned*>(&g_epoch) + 1;
            if (lane == 0) {
                asm volatile("st.shared.u32 [%0], %1;" ::"r"(misc + MISC_EPOCH), "r"(ep1) : "memory");
                mbar_wait(misc + BAR_LN, 0);
                flag_signal(flag_ptr(FL_LN + (cta >> 5)));
                flag_wait(flag_ptr(FL_LN + b0), ep1 * 33u);
                mbar_arrive(misc + BAR_DEP + 8 * D_LN);
#pragma unroll 1
                for (int i = 0; i < 4; i++) {
                    mbar_wait(misc + BAR_EV + 8 * (16 + EV_KV + i), 0);
                    if (i < 2) {
                        mbar_wait(misc + BAR_EV + 8 * (EV_KV + i), 0);
                        asm volatile("red.release.gpu.global.add.u32 [%0], 2;" ::"l"(flag_ptr(FL_KV + team * 8 + i)) : "memory");
                    }
                    if (i == 1) {
                        flag_wait(flag_ptr(FL_LN + b1), ep1 * 128u);
                        mbar_arrive(misc + BAR_DEP + 8 * (D_LN + 1));
                    }
                    flag_wait(flag_ptr(FL_KV + team * 8 + i), ep1 * 16u);
                    mbar_arrive(misc + BAR_DEP + 8 * (D_KV + i));
                    if (i == 1) {
#pragma unroll 1
                        for (int j = 0; j < 2; j++) {
                            mbar_wait(misc + BAR_PROG + 8 * j, 0);
                            asm volatile("red.relaxed.gpu.global.add.u32 [%0], 1;" ::"l"(flag_ptr(FL_WAR + 2 * team + j)) : "memory");
                            flag_wait(flag_ptr(FL_WAR + 2 * team + j), ep1 * 8u);
                            mbar_arrive(misc + BAR_DEP + 8 * (D_WAR + j));
                        }
                    }
                }
                flag_wait(flag_ptr(FL_MOE_DONE), ep1);
                int4 s0 = __ldcg(reinterpret_cast<const int4*>(g_sel)), s1 = __ldcg(reinterpret_cast<const int4*>(g_sel) + 1);
                asm volatile("st.shared.v4.u32 [%0], {%1,%2,%3,%4};" ::"r"(misc + MISC_SEL), "r"(s0.x), "r"(s0.y), "r"(s0.z), "r"(s0.w) : "memory");
                asm volatile("st.shared.v4.u32 [%0], {%1,%2,%3,%4};" ::"r"(misc + MISC_SEL + 16), "r"(s1.x), "r"(s1.y), "r"(s1.z), "r"(s1.w) : "memory");
                mbar_arrive(misc + BAR_SEL);
            }
            __syncwarp();
            const unsigned* cf = flag_ptr(FL_CTX + op_head(lane & 15, kap) * 8 + u3);
#pragma unroll 1
            for (int half = 0; half < 2; half++) {
                if (half) mbar_wait(misc + BAR_EV + 8 * (EV_CTX + 3), 0);
                bool done = (lane >> 3) != half;
                for (int spin = 0; spin < 4000000; spin++) {
                    if (!done) {
                        unsigned v;
                        asm volatile("ld.acquire.gpu.global.u32 %0, [%1];" : "=r"(v) : "l"(cf) : "memory");
                        if ((int)(v - ep1 * 4u) >= 0) { mbar_arrive(misc + BAR_DEP + 8 * (D_CTX + lane)); done = true; }
                    }
                    if (__all_sync(0xffffffffu, done)) break;
                    __nanosleep(64);
                }
            }
        } else {
            const int w = warp - 1;
            if (lane == 0) {
                const uint32_t eb = misc + BAR_EV + w * 128;
#pragma unroll 1
                for (int i = 0; i < 6; i++) {
                    const bool kv = (i >> 1) == 1;
                    const int ci = i < 2 ? i : i - 2;
                    mbar_wait(eb + 8 * (kv ? EV_KV + i : EV_CTX + ci), 0);
                    if (i == 1) {
                        asm volatile("cp.async.bulk.global.shared::cta.bulk_group [%0], [%1], 16384;"
                                     ::"l"(g_ctx + (size_t)(2 * team * 32 + 4 * b1 + (w ? 3 - (rank ^ SWAPT) : rank ^ SWAPT)) * 16384),
                                       "r"(ring + slot_of(78) * SLOT_BYTES + w * 16384) : "memory");
                        asm volatile("cp.async.bulk.commit_group;" ::: "memory");
                        asm volatile("cp.async.bulk.wait_group.read 0;" ::: "memory");
                        mbar_arrive_cluster(mapa(misc + BAR_EMPTY + 8 * slot_of(78), 0), 4);
                        mbar_arrive_cluster(mapa(misc + BAR_EMPTY + 8 * slot_of(78), 1), 4);
                        asm volatile("cp.async.bulk.wait_group 0;" ::: "memory");
                        fence_async_global();
                    }
                    flag_signal(flag_ptr(kv ? FL_KV + team * 8 + i : FL_CTX + (2 * team + (ci >> 1)) * 8 + ((ci & 1) ? b1 : b0)));
                }
            }
            __syncwarp();
            mbar_wait(misc + BAR_PROG + 16, 0);
            const int row = (2 * u3 + rank) * 128 + 64 * w + perm32(16 * (lane >> 3) + 8 * kap + (lane & 7));
#pragma unroll
            for (int i = 0; i < 10; i++) asm volatile("prefetch.global.L2 [%0];" ::"l"(P.x + (size_t)row * DM + 160 * s3 + 16 * i));
            asm volatile("prefetch.global.L2 [%0];" ::"l"(g_stats + row));
            if (lane < 5) asm volatile("prefetch.global.L2 [%0];" ::"l"(g_brow + ((cta & 31) * 10 + w * 5 + lane) * 16));
            mbar_wait(misc + BAR_EV + w * 128 + 8 * EV_END, 0);
        }
        }
    } else {
        asm volatile("setmaxnreg.inc.sync.aligned.u32 232;");
        Ctx c;
        c.ring = ring; c.misc = misc; c.w = wg - 1; c.warp = __shfl_sync(0xffffffffu, (tid >> 5) & 3, 0); c.lane = tid & 31;
        c.rel = mapa(misc, tid & 1);
        const int w = c.w;
        if (w == 1) bar_arrive(1, 256);
        prefetch_w(2); prefetch_w(3);
        Cur cur = cur_at(0);
        float o[64], inv[2];
        unsigned char* out[2];
        uint32_t wf[128];
        Cur cw = cur;
        auto load_wchunk = [&](auto CH) {
            constexpr int ch = decltype(CH)::value;
            mbar_wait_hot(misc + BAR_FULL + 8 * cw.slot, cw.ph);
            const uint32_t z = load_afrag<8, 32 * ch>(wf, ring + cw.slot * SLOT_BYTES + w * 16384, c);
            release(c, BAR_EMPTY + 8 * cw.slot + z, 1);
            cw.adv(); cw.adv();
        };
#pragma unroll
        for (int i = 32; i < 64; i++) wf[i] = 0u;
        load_wchunk(IC<0>{});
#pragma unroll 1
        for (int v = 0; v < 2; v++) {
        {
            float (&acc)[64] = o;
#pragma unroll
            for (int i = 64; i < 128; i++) wf[i] = 0u;
            cur.adv();
            inv[0] = inv[1] = rank ? 1.0f : SM_SCALE;
            PROF_EV(2); PROF_GT(60);
#pragma unroll 1
            for (int t = 0; t < 4; t++) {
                uint32_t last = 0;
                token_wait(w);
                PROF_EV(10);
                undef_regs(acc);
                auto chunk = [&](auto CH) {
                    constexpr int ch = decltype(CH)::value;
                    mbar_wait_hot(misc + BAR_FULL + 8 * cur.slot, cur.ph);
                    if (t == 0) { PROF_EV(12 + ch); }
                    uint64_t d = mkdesc(ring + cur.slot * SLOT_BYTES, 16, 1024, 1);
                    wg_fence();
#pragma unroll
                    for (int ks = 0; ks < 8; ks++)
                        wgmma_rs_n128_ta0_tb0(acc, wf[32 * ch + 4 * ks], wf[32 * ch + 4 * ks + 1], wf[32 * ch + 4 * ks + 2], wf[32 * ch + 4 * ks + 3],
                                              d + (ks >> 2) * 1024 + (ks & 3) * 2, (ch | ks) != 0);
                    wg_commit();
                    if (ch == 3 || (ch < 2 && t == 0)) token_pass(w);
                    if constexpr (ch == 0) { if (t == 0) { if (v) load_wchunk(IC<2>{}); else load_wchunk(IC<1>{}); } }
                    if constexpr (ch == 1) { if (t == 0 && !v) load_wchunk(IC<2>{}); }
                    if constexpr (ch == 2) { if (t == 0 && !(w | v)) load_wchunk(IC<3>{}); }
                    if (ch > 0) { wg_wait<1>(); release(c, BAR_EMPTY + 8 * last, 1); }
                    last = cur.slot;
                    cur.adv();
                    if (ch < 3 && t == 0) cur.adv();
                    if constexpr (ch == 1) { if (t == 0 && (w | v)) load_wchunk(IC<3>{}); }
                    if (ch < 2 && t == 0) token_wait(w);
                };
                chunk(IC<0>{}); chunk(IC<1>{}); chunk(IC<2>{}); chunk(IC<3>{});
                wg_wait<0>();
                release(c, BAR_EMPTY + 8 * last, 1);
                PROF_EV(11);
                fence_regs(acc);
                tile_out(out, (rank ? g_V : g_K) + (size_t)(team * 32 + 2 * (kv_tile(t) + k)) * 16384, 64 * w, rank, c);
                if (DEFER && t == 3 && w) break;
#pragma unroll
                for (int i = 0; i < 4; i++) store_pair(acc, i, out, 8192, inv);
                if (t >= 2) signal_event(c, EV_KV + 2 * v + t - 2);
            }
            PROF_EV(61); PROF_GT(62);
        }
        PROF_EV(63); PROF_GT(64);
        {
            uint32_t q[32], p[32];
            float m[2], l[2];
#pragma unroll
            for (int i = 0; i < 32; i++) p[i] = 0u;
            l[0] = l[1] = 1.f;
            int pv_acc = 1, pv_mode = 2;
#pragma unroll 1
            for (int r = 0; r < 2; r++) {
                const int heavy = 1 ^ r ^ w;
                const int half = 1 ^ heavy ^ rank ^ (r & SWAPT);
                int left = 2 * (r ? b1 : b0) + 1 + heavy;
                Cur ck, cv = cur;
                {
                    float s[64];
                    if (r) cur.adv();
                    mbar_wait_hot(misc + BAR_FULL + 8 * cv.slot, cv.ph);
                    token_wait(w);
                    PROF_EV(20);
                    issue_pv(o, p, ring + cv.slot * SLOT_BYTES, pv_acc, pv_mode);
                    undef_regs(s);
                    uint32_t prev;
                    auto qchunk = [&](int acc) {
                        mbar_wait_hot(misc + BAR_FULL + 8 * cur.slot, cur.ph);
                        const uint64_t da = mkdesc(ring + cur.slot * SLOT_BYTES + w * 8192, 16, 1024, 1);
                        const uint64_t db = mkdesc(ring + cur.slot * SLOT_BYTES + 16384, 8192, 1024, 1);
                        wg_fence();
#pragma unroll
                        for (int ks = 0; ks < 4; ks++) wgmma_ss_n128_ta0_tb1(s, da + 2 * ks, db + 128 * ks, ks ? 1 : acc);
                        wg_commit();
                    };
                    qchunk(0);
                    prev = cur.slot; cur.adv();
                    token_pass(w);
                    if (r) {
                        row_inv(l, inv);
                        tile_out(out, g_ctx + (size_t)((2 * team + v) * 32 + 4 * b0 + (w ? rank : 3 - rank)) * 16384, 0, 0, c);
                    }
                    const int epi = r | (w & DEFER), hs = r ? 4096 : 8192;
                    const int hold = heavy ? -10 : half ? HOLD0 : 8;
#pragma unroll
                    for (int kc = 1; kc < 10; kc++) {
                        if (HOLD0 && kc >= HOLD0 && (kc == hold || kc == hold + 2)) token_wait(w);
                        qchunk(1);
                        if (HOLD0 && kc > HOLD0 && kc == hold + 1) token_pass(w);
                        if (HOLD0 && kc == 9 && heavy) { token_wait(w); token_pass(w); }
                        wg_wait<1>();
                        release(c, BAR_EMPTY + 8 * prev, 1);
                        prev = cur.slot; cur.adv();
                        if (kc == 1) { fence_regs(o); if (r) release(c, BAR_EMPTY + 8 * cv.slot, 1); }
                        if (kc <= 4 && epi) {
                            store_pair(o, kc - 1, out, hs, inv);
                            if (kc == 4) signal_event(c, r ? EV_CTX + 2 * v : EV_KV + 2 * v + 1);
                        }
                    }
                    if (!heavy) cur.adv();
                    ck = cur;
                    cur.adv();
                    if (!heavy) cur.adv();
                    wg_wait<0>();
                    release(c, BAR_EMPTY + 8 * prev, 1);
                    PROF_EV(21);
                    fence_regs(s);
#pragma unroll
                    for (int i = 0; i < 32; i++) q[i] = pack_bf16(s[2 * i], s[2 * i + 1]);
                }
                cv = ck;
                int first = 1, gen = 0;
                uint32_t pv_cnt = 0;
                pv_acc = 0; pv_mode = 2;
                l[0] = l[1] = m[0] = m[1] = 0.f;
                mbar_wait_hot(misc + BAR_FULL + 8 * ck.slot, ck.ph);
#pragma unroll 1
                while (true) {
                    float s[64];
                    if (half & first) {
                        if (heavy || HOLD0 == 0 || HOLD0 == 8) token_wait(w);
                        PROF_EV(30);
                        float sh[32];
                        undef_regs(sh);
                        issue_qk_half(sh, q, ring + ck.slot * SLOT_BYTES);
                        token_pass(w);
                        --left;
                        wg_wait<0>();
                        PROF_EV(34);
                        fence_regs(sh);
                        mask_diag<0>(sh, c);
                        float l0 = 0.f, l1 = 0.f;
#pragma unroll
                        for (int j = 0; j < 8; j++) {
#pragma unroll
                            for (int e = 0; e < 4; e++) ex2v(sh[4 * j + e]);
                            l0 += sh[4 * j] + sh[4 * j + 1]; l1 += sh[4 * j + 2] + sh[4 * j + 3];
                        }
#pragma unroll
                        for (int i = 0; i < 16; i++) p[i] = pack_bf16(sh[2 * i], sh[2 * i + 1]);
                        const int lim = mask_lim(c);
                        if (__any_sync(0xffffffffu, !(l0 <= SAFE_SUM && l1 <= SAFE_SUM && (l0 >= 1.0f / SAFE_SUM || lim < 0) &&
                                                      (l1 >= 1.0f / SAFE_SUM || lim < -2)))) goto redo;
                        l[0] = l0; l[1] = l1;
                        goto tail;
                    }
#pragma unroll 1
                    while (true) {
                        token_wait(w);
                        PROF_EV(first ? 30 : 31);
                        undef_regs(s);
                        issue_qk(s, q, ring + ck.slot * SLOT_BYTES);
                        Cur nck = cur, ncv = cur, ncur;
                        ncv.adv(); ncur = ncv; ncur.adv();
                        --left;
                        mbar_wait_hot(misc + BAR_FULL + 8 * cv.slot, cv.ph);
                        issue_pv(o, p, ring + cv.slot * SLOT_BYTES, pv_acc, pv_mode);
                        token_pass(w);
                        wg_wait<1>();
                        PROF_EV(33);
                        fence_regs(s);
                        float lo = 0.f;
                        if (first) {
                            lo = 1.0f / SAFE_SUM;
                            mask_diag<8>(s, c);
                        }
                        constexpr int JB = 11;
                        float l0 = l[0], l1 = l[1];
                        if (!gen) {
#pragma unroll
                            for (int j = 0; j < JB; j++) {
#pragma unroll
                                for (int e = 0; e < 4; e++) ex2v(s[4 * j + e]);
                                if (j < JB - 1) { l0 += s[4 * j] + s[4 * j + 1]; l1 += s[4 * j + 2] + s[4 * j + 3]; }
                            }
                        }
                        wg_wait<0>();
                        fence_regs(o);
                        if (gen) goto general;
#pragma unroll
                        for (int j = JB - 1; j < 16; j++) {
                            if (j >= JB) {
#pragma unroll
                                for (int e = 0; e < 4; e++) ex2v(s[4 * j + e]);
                            }
                            l0 += s[4 * j] + s[4 * j + 1]; l1 += s[4 * j + 2] + s[4 * j + 3];
                        }
#pragma unroll
                        for (int i = 0; i < 32; i++) p[i] = pack_bf16(s[2 * i], s[2 * i + 1]);
                        if (__any_sync(0xffffffffu, !(l0 <= SAFE_SUM && l1 <= SAFE_SUM && l0 >= lo && l1 >= lo))) goto redo;
                        l[0] = l0; l[1] = l1;
                        if (left == 0) goto tail;
                        release(c, BAR_EMPTY + 8 * ck.slot, 1 + (first & heavy));
                        if (pv_cnt) release(c, BAR_EMPTY + 8 * cv.slot, pv_cnt);
                        pv_acc = first ^ 1; pv_mode = 0; pv_cnt = 1 + (first & heavy); first = 0;
                        ck = nck; cv = ncv; cur = ncur;
                        mbar_wait_hot(misc + BAR_FULL + 8 * ck.slot, ck.ph);
                    }
                redo:
                    recompute_scores(s, q, ring + ck.slot * SLOT_BYTES, c);
                    if (first) { mask_any(s, half ^ 1, c); m[0] = m[1] = -INFINITY; }
                    gen = 1;
                general:
                    {
                        float mx[2], alpha[2];
                        row_max<16>(s, mx);
#pragma unroll
                        for (int i = 0; i < 2; i++) {
                            mx[i] = fmaxf(mx[i], m[i]);
                            alpha[i] = ex2(m[i] - mx[i]);
                            m[i] = mx[i];
                            l[i] *= alpha[i];
                        }
                        exp_sum<16, true>(s, m, l[0], l[1]);
#pragma unroll
                        for (int i = 0; i < 64; i++) o[i] *= alpha[(i >> 1) & 1];
#pragma unroll
                        for (int i = 0; i < 32; i++) p[i] = pack_bf16(s[2 * i], s[2 * i + 1]);
                    }
                tail:
                    release(c, BAR_EMPTY + 8 * ck.slot, 1 + (first & heavy));
                    if (pv_cnt) release(c, BAR_EMPTY + 8 * cv.slot, pv_cnt);
                    pv_acc = first ^ 1; pv_mode = first & half; pv_cnt = 1 + (first & heavy); first = 0;
                    if (left == 0) break;
                    ck = cur; cur.adv(); cv = cur; cur.adv();
                    mbar_wait_hot(misc + BAR_FULL + 8 * ck.slot, ck.ph);
                }
            }
            mbar_wait_hot(misc + BAR_FULL + 8 * cur.slot, cur.ph);
            token_wait(w);
            PROF_EV(32);
            issue_pv(o, p, ring + cur.slot * SLOT_BYTES, 1, 0);
            if (w == 0 || v == 0) token_pass(w);
            const uint32_t vslot = cur.slot;
            cur.adv();
            if (v) {
                row_inv(l, inv);
                wg_wait<0>();
                release(c, BAR_EMPTY + 8 * vslot, 1);
                fence_regs(o);
                tile_out(out, g_ctx + (size_t)((2 * team + 1) * 32 + 4 * b1 + (w ? 3 - (rank ^ SWAPT) : rank ^ SWAPT)) * 16384, 0, 0, c);
#pragma unroll
                for (int i = 0; i < 64; i++) wf[i] = 0u;
                continue;
            }
            cw = cur_at(80);
            mbar_wait_hot(misc + BAR_FULL + 8 * slot_of(76), cur_at(76).ph);
            mbar_wait_hot(misc + BAR_FULL + 8 * slot_of(78), cur_at(78).ph);
            load_afrag<8, 32>(wf, ring + slot_of(78) * SLOT_BYTES + w * 16384, c);
            const uint32_t z = load_afrag<8, 0>(wf, ring + slot_of(76) * SLOT_BYTES + w * 16384, c);
            row_inv(l, inv);
            release(c, BAR_EMPTY + 8 * slot_of(76) + z, 1);
            asm volatile("{\n.reg .pred p;\nsetp.eq.u32 p, %0, 0;\n@p bar.sync 4, 128;\n@!p bar.sync 5, 128;\n}\n" ::"r"(w) : "memory");
            wg_wait<0>();
            release(c, BAR_EMPTY + 8 * vslot, 1);
            fence_regs(o);
            {
                const uint32_t base = ring + slot_of(78) * SLOT_BYTES + w * 16384 + (16 * c.warp + (c.lane >> 2)) * 64 + (((c.lane ^ (c.lane >> 3)) & 3) << 4);
#pragma unroll
                for (int i = 0; i < 2; i++)
#pragma unroll
                    for (int qq = 0; qq < 4; qq++)
                        asm volatile("st.shared.v4.b32 [%0], {%1,%2,%3,%4};" ::"r"(base + qq * 4096 + i * 512),
                                     "r"(pack_bf16(o[16 * qq + 2 * i] * inv[i], o[16 * qq + 2 * i + 1] * inv[i])),
                                     "r"(pack_bf16(o[16 * qq + 4 + 2 * i] * inv[i], o[16 * qq + 4 + 2 * i + 1] * inv[i])),
                                     "r"(pack_bf16(o[16 * qq + 8 + 2 * i] * inv[i], o[16 * qq + 8 + 2 * i + 1] * inv[i])),
                                     "r"(pack_bf16(o[16 * qq + 12 + 2 * i] * inv[i], o[16 * qq + 12 + 2 * i + 1] * inv[i])) : "memory");
                asm volatile("fence.proxy.async.shared::cta;" ::: "memory");
                signal_event(c, EV_CTX + 1);
            }
        }
        }
        {
            float acc[80];
            undef_regs(acc);
            int st = 0, prev = 0; uint32_t ph3 = 0;
            auto op_stage = [&](int i) {
                mbar_wait_hot(misc + BAR_FULL3 + 8 * st, ph3);
                PROF_EV(44);
                uint32_t base = ring + st * ST3_BYTES;
                uint64_t da = mkdesc(base + w * 8192, 16, 512, 2);
                uint64_t db = mkdesc(base + 16384, 2048, 512, 2);
                wg_fence();
#pragma unroll
                for (int k = 0; k < 4; k++) wgmma_ss_n160_ta0_tb1(acc, da + (k >> 1) * 256 + 2 * (k & 1), db + (k >> 1) * 640 + (k & 1) * 64, k ? 1 : i);
                wg_commit();
                if (i > 0) { wg_wait<1>(); if (i <= 32 - NST3) release(c, BAR_EMPTY3 + 8 * prev, 1); }
                prev = st;
                if (++st == NST3) { st = 0; ph3 ^= 1; }
            };
            PROF_EV(40); PROF_GT(65);
#pragma unroll
            for (int i = 0; i < 4; i++) { op_stage(i); store_pair(o, i, out, 4096, inv); }
            signal_event(c, EV_CTX + 3);
            const int split = RES_AT + 3 * w;
#pragma unroll 1
            for (int i = 4; i < split; i++) op_stage(i);
            mbar_wait(misc + BAR_SEL, 0);
            const uint32_t tag = lds32(misc + MISC_EPOCH) & 1;
            const int g = c.lane >> 2, t = c.lane & 3;
            const int row = (2 * u3 + rank) * 128 + 64 * w + perm32(16 * c.warp + 8 * kap + g);
            const int col = 160 * s3 + 8 * t;
            int sel = -1;
#pragma unroll
            for (int i = 0; i < TOPC; i++) if ((int)lds32(misc + MISC_SEL + 4 * i) == row) sel = i;
            const int t256 = tid - 128;
            uint4* sendp = g_part + (size_t)cta * 2560 + t256;
            if (c.lane >= 30) stg128(sendp + 9 * 256, tag ^ 1, tag ^ 1, tag ^ 1, tag ^ 1);
            uint4 xv[5], bv[5];
#pragma unroll
            for (int i = 0; i < 5; i++) xv[i] = ldg128(P.x + (size_t)row * DM + col + 32 * i);
            uint2 stat;
            asm volatile("ld.global.cg.v2.b32 {%0,%1}, [%2];" : "=r"(stat.x), "=r"(stat.y) : "l"(g_stats + row) : "memory");
#pragma unroll
            for (int i = 0; i < 5; i++) {
                uint32_t xx[4] = {xv[i].x, xv[i].y, xv[i].z, xv[i].w};
#pragma unroll
                for (int e = 0; e < 4; e++) {
                    asm("sub.rn.bf16x2 %0, %0, %1;" : "+r"(xx[e]) : "r"(stat.x));
                    xx[e] = pack_bf16(bf_lo(xx[e]) * __uint_as_float(stat.y), bf_hi(xx[e]) * __uint_as_float(stat.y));
                }
                bv[i] = make_uint4(xx[0], xx[1], xx[2], xx[3]);
            }
            if (sel >= 0) {
#pragma unroll
                for (int i = 0; i < 5; i++) bv[i] = ldg128(g_brow + sel * DM + col + 32 * i);
            }
#pragma unroll
            for (int i = 0; i < 5; i++) asm volatile("" : "+r"(bv[i].x), "+r"(bv[i].y), "+r"(bv[i].z), "+r"(bv[i].w));
#pragma unroll 1
            for (int i = split; i < 32; i++) op_stage(i);
            wg_wait<0>();
            fence_regs(acc);
            PROF_EV(41); PROF_GT(66);
            float keep[40];
#pragma unroll
            for (int j = 0; j < 10; j++) {
                uint32_t v0 = __float_as_uint(kap ? acc[8 * j + 0] : acc[8 * j + 2]), v1 = __float_as_uint(kap ? acc[8 * j + 1] : acc[8 * j + 3]);
                uint32_t v2 = __float_as_uint(kap ? acc[8 * j + 4] : acc[8 * j + 6]), v3 = __float_as_uint(kap ? acc[8 * j + 5] : acc[8 * j + 7]);
                asm volatile("st.relaxed.gpu.global.v4.b32 [%0], {%1,%2,%3,%4};" ::"l"(sendp + j * 256),
                             "r"((v0 & ~1u) | tag), "r"((v1 & ~1u) | tag), "r"((v2 & ~1u) | tag), "r"((v3 & ~1u) | tag) : "memory");
                keep[4 * j + 0] = kap ? acc[8 * j + 2] : acc[8 * j + 0]; keep[4 * j + 1] = kap ? acc[8 * j + 3] : acc[8 * j + 1];
                keep[4 * j + 2] = kap ? acc[8 * j + 6] : acc[8 * j + 4]; keep[4 * j + 3] = kap ? acc[8 * j + 7] : acc[8 * j + 5];
            }
            PROF_GT(67);
            signal_event(c, EV_END);
            const uint4* recvp = g_part + (size_t)partner * 2560 + t256;
            uint4 rv[10];
            int spins = 0;
            while (true) {
                uint32_t v;
                asm volatile("ld.relaxed.gpu.global.b32 %0, [%1];" : "=r"(v) : "l"(recvp + 9 * 256 + (31 - c.lane)) : "memory");
                if (__all_sync(0xffffffffu, (v & 1u) == tag) || ++spins > 2000000) break;
            }
            PROF_GT(68);
            while (true) {
                uint32_t bad = 0u;
#pragma unroll
                for (int j = 0; j < 10; j++) {
                    asm volatile("ld.relaxed.gpu.global.v4.b32 {%0,%1,%2,%3}, [%4];"
                                 : "=r"(rv[j].x), "=r"(rv[j].y), "=r"(rv[j].z), "=r"(rv[j].w) : "l"(recvp + j * 256) : "memory");
                }
#pragma unroll
                for (int j = 0; j < 10; j++) {
                    rv[j].x ^= tag; rv[j].y ^= tag; rv[j].z ^= tag; rv[j].w ^= tag;
                    bad |= rv[j].x | rv[j].y | rv[j].z | rv[j].w;
                }
                if (__all_sync(0xffffffffu, (bad & 1u) == 0) || ++spins > 2000000) break;
            }
            PROF_GT(69);
            uint32_t pk[20];
#pragma unroll
            for (int j = 0; j < 10; j++) {
                pk[2 * j] = pack_bf16(keep[4 * j] + __uint_as_float(rv[j].x), keep[4 * j + 1] + __uint_as_float(rv[j].y));
                pk[2 * j + 1] = pack_bf16(keep[4 * j + 2] + __uint_as_float(rv[j].z), keep[4 * j + 3] + __uint_as_float(rv[j].w));
            }
#pragma unroll
            for (int i = 0; i < 5; i++) {
                uint32_t a0 = pk[4 * i], a1 = pk[4 * i + 1], a2 = pk[4 * i + 2], a3 = pk[4 * i + 3];
                uint32_t x0 = (t & 1) ? a0 : a1, x1 = (t & 1) ? a2 : a3;
                x0 = __shfl_xor_sync(0xffffffffu, x0, 1); x1 = __shfl_xor_sync(0xffffffffu, x1, 1);
                if (t & 1) { a0 = x0; a2 = x1; } else { a1 = x0; a3 = x1; }
                x0 = (t & 2) ? a0 : a2; x1 = (t & 2) ? a1 : a3;
                x0 = __shfl_xor_sync(0xffffffffu, x0, 2); x1 = __shfl_xor_sync(0xffffffffu, x1, 2);
                if (t & 2) { a0 = x0; a1 = x1; } else { a2 = x0; a3 = x1; }
                uint32_t av[4] = {a0, a1, a2, a3};
                uint32_t xx[4] = {xv[i].x, xv[i].y, xv[i].z, xv[i].w}, bb[4] = {bv[i].x, bv[i].y, bv[i].z, bv[i].w};
                uint32_t ov[4];
#pragma unroll
                for (int e = 0; e < 4; e++) {
                    asm("add.rn.bf16x2 %0, %1, %2;" : "=r"(ov[e]) : "r"(xx[e]), "r"(av[e]));
                    asm("add.rn.bf16x2 %0, %0, %1;" : "+r"(ov[e]) : "r"(bb[e]));
                }
                stg128(P.out + (size_t)row * DM + col + 32 * i, ov[0], ov[1], ov[2], ov[3]);
            }
            PROF_EV(42); PROF_GT(43);
        }
    }
}

typedef CUresult (*EncodeFn)(CUtensorMap*, CUtensorMapDataType, cuuint32_t, void*, const cuuint64_t*, const cuuint64_t*, const cuuint32_t*,
                             const cuuint32_t*, CUtensorMapInterleave, CUtensorMapSwizzle, CUtensorMapL2promotion, CUtensorMapFloatOOBfill);

void make_map2d(EncodeFn enc, CUtensorMap* tm, const void* p, uint64_t cols, uint64_t rows, uint32_t box_rows = 128) {
    cuuint64_t gd[2] = {cols, rows}, gs[1] = {cols * 2};
    cuuint32_t box[2] = {64, box_rows}, es[2] = {1, 1};
    enc(tm, CU_TENSOR_MAP_DATA_TYPE_BFLOAT16, 2, const_cast<void*>(p), gd, gs, box, es, CU_TENSOR_MAP_INTERLEAVE_NONE,
        CU_TENSOR_MAP_SWIZZLE_128B, CU_TENSOR_MAP_L2_PROMOTION_L2_128B, CU_TENSOR_MAP_FLOAT_OOB_FILL_NONE);
}

void make_map3d(EncodeFn enc, CUtensorMap* tm, const void* p, uint64_t cols, uint64_t rows, uint32_t bw, uint32_t nb) {
    cuuint64_t gd[3] = {bw, rows, cols / bw}, gs[2] = {cols * 2, bw * 2};
    cuuint32_t box[3] = {bw, 32, nb}, es[3] = {1, 1, 1};
    enc(tm, CU_TENSOR_MAP_DATA_TYPE_BFLOAT16, 3, const_cast<void*>(p), gd, gs, box, es, CU_TENSOR_MAP_INTERLEAVE_NONE,
        bw == 64 ? CU_TENSOR_MAP_SWIZZLE_128B : CU_TENSOR_MAP_SWIZZLE_64B, CU_TENSOR_MAP_L2_PROMOTION_L2_128B, CU_TENSOR_MAP_FLOAT_OOB_FILL_NONE);
}

}

extern "C" void kernel_launch(void* const* d_in, const int* in_sizes, int n_in, void* d_out, int out_size) {
    (void)in_sizes; (void)n_in; (void)out_size;
    static EncodeFn enc = nullptr;
    if (!enc) {
        void* fn = nullptr;
        cudaDriverEntryPointQueryResult qr;
        cudaGetDriverEntryPoint("cuTensorMapEncodeTiled", &fn, cudaEnableDefault, &qr);
        enc = (EncodeFn)fn;
        cudaFuncSetAttribute(fused_kernel, cudaFuncAttributeMaxDynamicSharedMemorySize, SMEM_BYTES);
    }
    CUtensorMap tmC, tmWk, tmWv, tmWq, tmWo, tmG, tmU, tmD;
    make_map2d(enc, &tmC, d_in[1], DC, SEQ);
    make_map2d(enc, &tmWq, d_in[2], 4096, DM, 64);
    make_map2d(enc, &tmWk, d_in[3], 4096, DC);
    make_map2d(enc, &tmWv, d_in[4], 4096, DC);
    make_map3d(enc, &tmWo, d_in[5], DM, 4096, 32, 5);
    make_map3d(enc, &tmG, d_in[8], FF, DM, 64, 7);
    make_map3d(enc, &tmU, d_in[9], FF, DM, 64, 7);
    make_map3d(enc, &tmD, d_in[10], DM, FF, 64, 10);
    Params P;
    P.x = (const __nv_bfloat16*)d_in[0];
    P.c = (const __nv_bfloat16*)d_in[1];
    P.wk = (const __nv_bfloat16*)d_in[3];
    P.wv = (const __nv_bfloat16*)d_in[4];
    P.wo = (const __nv_bfloat16*)d_in[5];
    P.wr = (const __nv_bfloat16*)d_in[7];
    P.out = (__nv_bfloat16*)d_out;
    fused_kernel<<<132, 384, SMEM_BYTES>>>(tmC, tmWk, tmWv, tmWq, tmWo, tmG, tmU, tmD, P);
}
```

```cpp
#include <cuda_runtime.h>
#include <cuda_bf16.h>
#include <cuda.h>
#include <stdint.h>

#define SWAPT 1
#define DEFER 1
#define HOLD0 6
#define LNINL __noinline__
#define WQPF 8
#define RES_AT 23
#define HM 0
#define OP_PF 8
#define PF_START 9
#define LATE_AT 18
namespace {

constexpr int SEQ = 2048, NH = 32, DM = 640, DC = 512, FF = 1728, TOPC = 8;
constexpr int NSLOT = 7, SLOT_BYTES = 32768;
constexpr int NST3 = 6, ST3_BYTES = 36864;
constexpr int RING_BYTES = NSLOT * SLOT_BYTES;
constexpr int SMEM_BYTES = RING_BYTES + 3072;

constexpr int BAR_FULL = 96  , BAR_FULL3 = 152  , BAR_DEP = 200  , BAR_SEL = 464,
              BAR_LN = 472  , BAR_EV = 504  , BAR_EMPTY = 760  , BAR_EMPTY3 = 816  ,
              BAR_PROG = 864  , MISC_EPOCH = 896, MISC_SMID = 900  , MISC_SEL = 912, MISC_WR = 1024  ;
constexpr int D_LN = 0  , D_KV = 4  , D_WAR = 14  , D_CTX = 16  ;
constexpr int EV_KV = 0  , EV_END = 11, EV_CTX = 12  ;

constexpr int FL_MOE_CNT = 0, FL_MOE_DONE = 1, FL_LN = 16  , FL_KV = 32  , FL_CTX = 416  , FL_WAR = 672  , FL_TOTAL = 704;

__device__ __align__(1024) unsigned char g_K[16 * 32 * 16384];
__device__ __align__(1024) unsigned char g_V[16 * 32 * 16384];
__device__ __align__(1024) unsigned char g_ctx[NH * 32 * 16384];
__device__ __align__(1024) unsigned char g_xn[16 * 10 * 16384];
__device__ __align__(1024) uint4 g_part[128 * 10 * 256];
__device__ float g_router[SEQ];
__device__ uint2 g_stats[SEQ];
__device__ __align__(16) float g_moe_part[4 * TOPC * DM];
__device__ __align__(16) __nv_bfloat16 g_brow[TOPC * DM];
__device__ __align__(16) int g_sel[TOPC];
__device__ unsigned g_flags[FL_TOTAL * 8];
__device__ unsigned g_epoch;
__device__ unsigned g_roleq[130];

struct Params {
    const __nv_bfloat16 *x, *c, *wr, *wk, *wv, *wo;
    __nv_bfloat16* out;
};

__device__ __forceinline__ uint32_t smem_u32(const void* p) { return (uint32_t)__cvta_generic_to_shared(p); }
__device__ __forceinline__ void mbar_init(uint32_t bar, int cnt) { asm volatile("mbarrier.init.shared::cta.b64 [%0], %1;" ::"r"(bar), "r"(cnt)); }
__device__ __forceinline__ void mbar_expect_tx(uint32_t bar, uint32_t bytes) {
    asm volatile("mbarrier.arrive.expect_tx.shared::cta.b64 _, [%0], %1;" ::"r"(bar), "r"(bytes) : "memory");
}
__device__ __forceinline__ void mbar_arrive(uint32_t bar) { asm volatile("mbarrier.arrive.shared::cta.b64 _, [%0];" ::"r"(bar) : "memory"); }
__device__ __forceinline__ void mbar_arrive_cluster(uint32_t cluster_addr, uint32_t cnt) {
    asm volatile("mbarrier.arrive.shared::cluster.b64 _, [%0], %1;" ::"r"(cluster_addr), "r"(cnt) : "memory");
}
__device__ __forceinline__ uint32_t mapa(uint32_t addr, uint32_t cta) {
    uint32_t r; asm("mapa.shared::cluster.u32 %0, %1, %2;" : "=r"(r) : "r"(addr), "r"(cta)); return r;
}
__device__ __forceinline__ void mbar_wait(uint32_t bar, uint32_t parity) {
    asm volatile(
        "{\n.reg .pred p;\n.reg .u32 n;\n"
        "mov.u32 n, 0;\n"
        "LAB_WAIT:\n"
        "mbarrier.try_wait.parity.shared::cta.b64 p, [%0], %1, 100000;\n"
        "@p bra DONE;\n"
        "add.u32 n, n, 1;\n"
        "setp.lt.u32 p, n, 50000;\n"
        "@p bra LAB_WAIT;\n"
        "trap;\n"
        "DONE:\n}\n" ::"r"(bar), "r"(parity) : "memory");
}
__device__ __forceinline__ void mbar_wait_hot(uint32_t bar, uint32_t parity) {
    asm volatile("{\n.reg .pred p;\nLAB_WAIT:\nmbarrier.try_wait.parity.shared::cta.b64 p, [%0], %1;\n@!p bra LAB_WAIT;\n}\n" ::"r"(bar), "r"(parity) : "memory");
}
__device__ __forceinline__ void mbar_wait_sleep(uint32_t bar, uint32_t parity) {
    asm volatile("{\n.reg .pred p;\nLAB_WAIT:\nmbarrier.try_wait.parity.shared::cta.b64 p, [%0], %1, 100000;\n@!p bra LAB_WAIT;\n}\n" ::"r"(bar), "r"(parity) : "memory");
}
__device__ __forceinline__ void flag_wait(const unsigned* flag, unsigned target) {
    asm volatile(
        "{\n.reg .pred p;\n.reg .u32 n, v;\n.reg .s32 d;\n"
        "mov.u32 n, 0;\n"
        "LAB_WAIT:\n"
        "ld.acquire.gpu.global.u32 v, [%0];\n"
        "sub.s32 d, v, %1;\n"
        "setp.ge.s32 p, d, 0;\n"
        "@p bra DONE;\n"
        "nanosleep.u32 40;\n"
        "add.u32 n, n, 1;\n"
        "setp.lt.u32 p, n, 3000000;\n"
        "@p bra LAB_WAIT;\n"
        "trap;\n"
        "DONE:\n}\n" ::"l"(flag), "r"(target) : "memory");
}
__device__ __forceinline__ void flag_signal(unsigned* flag) {
    asm volatile("red.release.gpu.global.add.u32 [%0], 1;" ::"l"(flag) : "memory");
}
__device__ __forceinline__ void fence_async_global() { asm volatile("fence.proxy.async.global;" ::: "memory"); }
__device__ __forceinline__ unsigned* flag_ptr(int idx) { return g_flags + idx * 8; }

__device__ __forceinline__ uint64_t policy_stream() {
    uint64_t p; asm("createpolicy.fractional.L2::evict_first.b64 %0, 1.0;" : "=l"(p)); return p;
}
__device__ __forceinline__ uint64_t policy_normal() { return 0x1000000000000000ull; }
__device__ __forceinline__ uint64_t policy(bool stream) { return stream ? policy_stream() : policy_normal(); }
__device__ __forceinline__ void bulk_load(uint32_t dst, const void* src, uint32_t bytes, uint32_t bar, uint64_t pol) {
    asm volatile("cp.async.bulk.shared::cluster.global.mbarrier::complete_tx::bytes.L2::cache_hint [%0], [%1], %2, [%3], %4;"
                 ::"r"(dst), "l"(src), "r"(bytes), "r"(bar), "l"(pol) : "memory");
}
__device__ __forceinline__ void bulk_load_mc(uint32_t dst, const void* src, uint32_t bytes, uint32_t bar, uint64_t pol) {
    asm volatile("cp.async.bulk.shared::cluster.global.mbarrier::complete_tx::bytes.multicast::cluster.L2::cache_hint [%0], [%1], %2, [%3], %4, %5;"
                 ::"r"(dst), "l"(src), "r"(bytes), "r"(bar), "h"((uint16_t)3), "l"(pol) : "memory");
}
__device__ __forceinline__ void tma2d(uint32_t dst, const CUtensorMap* tm, int c0, int c1, uint32_t bar, uint64_t pol) {
    asm volatile("cp.async.bulk.tensor.2d.shared::cluster.global.mbarrier::complete_tx::bytes.L2::cache_hint [%0], [%1, {%3, %4}], [%2], %5;"
                 ::"r"(dst), "l"(tm), "r"(bar), "r"(c0), "r"(c1), "l"(pol) : "memory");
}
__device__ __forceinline__ void tma2d_mc(uint32_t dst, const CUtensorMap* tm, int c0, int c1, uint32_t bar, uint64_t pol) {
    asm volatile("cp.async.bulk.tensor.2d.shared::cluster.global.mbarrier::complete_tx::bytes.multicast::cluster.L2::cache_hint [%0], [%1, {%3, %4}], [%2], %5, %6;"
                 ::"r"(dst), "l"(tm), "r"(bar), "r"(c0), "r"(c1), "h"((uint16_t)3), "l"(pol) : "memory");
}
__device__ __forceinline__ void tma3d_mc(uint32_t dst, const CUtensorMap* tm, int c0, int c1, int c2, uint32_t bar, uint64_t pol) {
    asm volatile("cp.async.bulk.tensor.3d.shared::cluster.global.mbarrier::complete_tx::bytes.multicast::cluster.L2::cache_hint [%0], [%1, {%3, %4, %5}], [%2], %6, %7;"
                 ::"r"(dst), "l"(tm), "r"(bar), "r"(c0), "r"(c1), "r"(c2), "h"((uint16_t)3), "l"(pol) : "memory");
}
__device__ __forceinline__ void tma3d(uint32_t dst, const CUtensorMap* tm, int c0, int c1, int c2, uint32_t bar) {
    asm volatile("cp.async.bulk.tensor.3d.shared::cluster.global.mbarrier::complete_tx::bytes.L2::cache_hint [%0], [%1, {%3, %4, %5}], [%2], %6;"
                 ::"r"(dst), "l"(tm), "r"(bar), "r"(c0), "r"(c1), "r"(c2), "l"(policy_stream()) : "memory");
}
__device__ __forceinline__ void tma2d_prefetch(const CUtensorMap* tm, int c0, int c1) {
    asm volatile("cp.async.bulk.prefetch.tensor.2d.L2.global [%0, {%1, %2}];" ::"l"(tm), "r"(c0), "r"(c1) : "memory");
}
__device__ __forceinline__ void tma3d_prefetch(const CUtensorMap* tm, int c0, int c1, int c2) {
    asm volatile("cp.async.bulk.prefetch.tensor.3d.L2.global [%0, {%1, %2, %3}];" ::"l"(tm), "r"(c0), "r"(c1), "r"(c2) : "memory");
}
__device__ __forceinline__ void l2_prefetch(const void* p, uint32_t bytes) {
    asm volatile("cp.async.bulk.prefetch.L2.global [%0], %1;" ::"l"(p), "r"(bytes) : "memory");
}
__device__ __forceinline__ bool elect_one() {
    uint32_t r; asm volatile("{\n.reg .pred p;\nelect.sync _|p, 0xffffffff;\nselp.u32 %0, 1, 0, p;\n}\n" : "=r"(r)); return r != 0;
}
__device__ __forceinline__ void wg_fence() { asm volatile("wgmma.fence.sync.aligned;" ::: "memory"); }
__device__ __forceinline__ void wg_commit() { asm volatile("wgmma.commit_group.sync.aligned;" ::: "memory"); }
template <int N> __device__ __forceinline__ void wg_wait() { asm volatile("wgmma.wait_group.sync.aligned %0;" ::"n"(N) : "memory"); }
__device__ __forceinline__ void bar_sync(int id, int n) { asm volatile("bar.sync %0, %1;" ::"r"(id), "r"(n) : "memory"); }
__device__ __forceinline__ void bar_arrive(int id, int n) { asm volatile("bar.arrive %0, %1;" ::"r"(id), "r"(n) : "memory"); }
__device__ __forceinline__ void token_wait(int w) {
    asm volatile("{\n.reg .pred p;\nsetp.eq.u32 p, %0, 0;\n@p bar.sync 1, 256;\n@!p bar.sync 2, 256;\n}\n" ::"r"(w) : "memory");
}
__device__ __forceinline__ void token_pass(int w) {
    asm volatile("{\n.reg .pred p;\nsetp.eq.u32 p, %0, 0;\n@p bar.arrive 2, 256;\n@!p bar.arrive 1, 256;\n}\n" ::"r"(w) : "memory");
}
template <int N> __device__ __forceinline__ void fence_regs(float (&a)[N]) {
#pragma unroll
    for (int i = 0; i < N; i++) asm volatile("" : "+f"(a[i])::"memory");
}
template <int N> __device__ __forceinline__ void undef_regs(float (&a)[N]) {
#pragma unroll
    for (int i = 0; i < N; i++) asm volatile("" : "=f"(a[i]));
}
__device__ __forceinline__ void ldsm4t(uint32_t& r0, uint32_t& r1, uint32_t& r2, uint32_t& r3, uint32_t addr) {
    asm volatile("ldmatrix.sync.aligned.m8n8.x4.trans.shared.b16 {%0,%1,%2,%3}, [%4];"
                 : "=r"(r0), "=r"(r1), "=r"(r2), "=r"(r3) : "r"(addr) : "memory");
}
__device__ __forceinline__ uint32_t pack_bf16(float lo, float hi) {
    uint32_t r; asm("cvt.rn.bf16x2.f32 %0, %1, %2;" : "=r"(r) : "f"(hi), "f"(lo)); return r;
}
__device__ __forceinline__ float bf_lo(uint32_t v) { return __uint_as_float(v << 16); }
__device__ __forceinline__ float bf_hi(uint32_t v) { return __uint_as_float(v & 0xffff0000u); }
__device__ __forceinline__ float bf_round(float v) { return __bfloat162float(__float2bfloat16_rn(v)); }
__device__ __forceinline__ float ex2(float v) { float r; asm("ex2.approx.ftz.f32 %0, %1;" : "=f"(r) : "f"(v)); return r; }
__device__ __forceinline__ void ex2v(float& v) { asm volatile("ex2.approx.ftz.f32 %0, %0;" : "+f"(v)); }
__device__ __forceinline__ float rcp_fast(float v) { float r; asm("rcp.approx.ftz.f32 %0, %1;" : "=f"(r) : "f"(v)); return r; }
__device__ __forceinline__ float sqrt_fast(float v) { float r; asm("sqrt.approx.ftz.f32 %0, %1;" : "=f"(r) : "f"(v)); return r; }
__device__ __forceinline__ void stg128(void* p, uint32_t a, uint32_t b, uint32_t c, uint32_t d) {
    asm volatile("st.global.v4.b32 [%0], {%1,%2,%3,%4};" ::"l"(p), "r"(a), "r"(b), "r"(c), "r"(d) : "memory");
}
__device__ __forceinline__ uint4 ldg128(const void* p) {
    uint4 v; asm volatile("ld.global.cg.v4.b32 {%0,%1,%2,%3}, [%4];" : "=r"(v.x), "=r"(v.y), "=r"(v.z), "=r"(v.w) : "l"(p) : "memory"); return v;
}
__device__ __forceinline__ uint64_t mkdesc(uint32_t addr, uint32_t lbo, uint32_t sbo, uint32_t swz) {
    uint32_t lo = ((addr & 0x3FFFF) >> 4) | ((lbo >> 4) << 16);
    uint32_t hi = (sbo >> 4) | (swz << 30);
    return ((uint64_t)hi << 32) | lo;
}
__device__ __forceinline__ int perm32(int v) { return (v & ~30) | ((v >> 2) & 6) | ((v << 2) & 24); }

__device__ __forceinline__ void wgmma_rs_n128_ta0_tb0(float (&d)[64], uint32_t a0, uint32_t a1, uint32_t a2, uint32_t a3, uint64_t descB, int scaleD) {
  asm volatile("{\n.reg .pred p;\nsetp.ne.b32 p, %69, 0;\n"
    "wgmma.mma_async.sync.aligned.m64n128k16.f32.bf16.bf16 "
    "{%0, %1, %2, %3, %4, %5, %6, %7, %8, %9, %10, %11, %12, %13, %14, %15, %16, %17, %18, %19, %20, %21, %22, %23, %24, %25, %26, %27, %28, %29, %30, %31, %32, %33, %34, %35, %36, %37, %38, %39, %40, %41, %42, %43, %44, %45, %46, %47, %48, %49, %50, %51, %52, %53, %54, %55, %56, %57, %58, %59, %60, %61, %62, %63}, "
    "{%64, %65, %66, %67}, %68, p, 1, 1, 0;\n}\n"
    : "+f"(d[0]), "+f"(d[1]), "+f"(d[2]), "+f"(d[3]), "+f"(d[4]), "+f"(d[5]), "+f"(d[6]), "+f"(d[7]), "+f"(d[8]), "+f"(d[9]), "+f"(d[10]), "+f"(d[11]), "+f"(d[12]), "+f"(d[13]), "+f"(d[14]), "+f"(d[15]), "+f"(d[16]), "+f"(d[17]), "+f"(d[18]), "+f"(d[19]), "+f"(d[20]), "+f"(d[21]), "+f"(d[22]), "+f"(d[23]), "+f"(d[24]), "+f"(d[25]), "+f"(d[26]), "+f"(d[27]), "+f"(d[28]), "+f"(d[29]), "+f"(d[30]), "+f"(d[31]), "+f"(d[32]), "+f"(d[33]), "+f"(d[34]), "+f"(d[35]), "+f"(d[36]), "+f"(d[37]), "+f"(d[38]), "+f"(d[39]), "+f"(d[40]), "+f"(d[41]), "+f"(d[42]), "+f"(d[43]), "+f"(d[44]), "+f"(d[45]), "+f"(d[46]), "+f"(d[47]), "+f"(d[48]), "+f"(d[49]), "+f"(d[50]), "+f"(d[51]), "+f"(d[52]), "+f"(d[53]), "+f"(d[54]), "+f"(d[55]), "+f"(d[56]), "+f"(d[57]), "+f"(d[58]), "+f"(d[59]), "+f"(d[60]), "+f"(d[61]), "+f"(d[62]), "+f"(d[63])
    : "r"(a0), "r"(a1), "r"(a2), "r"(a3), "l"(descB), "r"(scaleD));
}
__device__ __forceinline__ void wgmma_rs_n128_ta0_tb1(float (&d)[64], uint32_t a0, uint32_t a1, uint32_t a2, uint32_t a3, uint64_t descB, int scaleD) {
  asm volatile("{\n.reg .pred p;\nsetp.ne.b32 p, %69, 0;\n"
    "wgmma.mma_async.sync.aligned.m64n128k16.f32.bf16.bf16 "
    "{%0, %1, %2, %3, %4, %5, %6, %7, %8, %9, %10, %11, %12, %13, %14, %15, %16, %17, %18, %19, %20, %21, %22, %23, %24, %25, %26, %27, %28, %29, %30, %31, %32, %33, %34, %35, %36, %37, %38, %39, %40, %41, %42, %43, %44, %45, %46, %47, %48, %49, %50, %51, %52, %53, %54, %55, %56, %57, %58, %59, %60, %61, %62, %63}, "
    "{%64, %65, %66, %67}, %68, p, 1, 1, 1;\n}\n"
    : "+f"(d[0]), "+f"(d[1]), "+f"(d[2]), "+f"(d[3]), "+f"(d[4]), "+f"(d[5]), "+f"(d[6]), "+f"(d[7]), "+f"(d[8]), "+f"(d[9]), "+f"(d[10]), "+f"(d[11]), "+f"(d[12]), "+f"(d[13]), "+f"(d[14]), "+f"(d[15]), "+f"(d[16]), "+f"(d[17]), "+f"(d[18]), "+f"(d[19]), "+f"(d[20]), "+f"(d[21]), "+f"(d[22]), "+f"(d[23]), "+f"(d[24]), "+f"(d[25]), "+f"(d[26]), "+f"(d[27]), "+f"(d[28]), "+f"(d[29]), "+f"(d[30]), "+f"(d[31]), "+f"(d[32]), "+f"(d[33]), "+f"(d[34]), "+f"(d[35]), "+f"(d[36]), "+f"(d[37]), "+f"(d[38]), "+f"(d[39]), "+f"(d[40]), "+f"(d[41]), "+f"(d[42]), "+f"(d[43]), "+f"(d[44]), "+f"(d[45]), "+f"(d[46]), "+f"(d[47]), "+f"(d[48]), "+f"(d[49]), "+f"(d[50]), "+f"(d[51]), "+f"(d[52]), "+f"(d[53]), "+f"(d[54]), "+f"(d[55]), "+f"(d[56]), "+f"(d[57]), "+f"(d[58]), "+f"(d[59]), "+f"(d[60]), "+f"(d[61]), "+f"(d[62]), "+f"(d[63])
    : "r"(a0), "r"(a1), "r"(a2), "r"(a3), "l"(descB), "r"(scaleD));
}
__device__ __forceinline__ void wgmma_rs_n64_ta0_tb1(float (&d)[32], uint32_t a0, uint32_t a1, uint32_t a2, uint32_t a3, uint64_t descB, int scaleD) {
  asm volatile("{\n.reg .pred p;\nsetp.ne.b32 p, %37, 0;\n"
    "wgmma.mma_async.sync.aligned.m64n64k16.f32.bf16.bf16 "
    "{%0, %1, %2, %3, %4, %5, %6, %7, %8, %9, %10, %11, %12, %13, %14, %15, %16, %17, %18, %19, %20, %21, %22, %23, %24, %25, %26, %27, %28, %29, %30, %31}, "
    "{%32, %33, %34, %35}, %36, p, 1, 1, 1;\n}\n"
    : "+f"(d[0]), "+f"(d[1]), "+f"(d[2]), "+f"(d[3]), "+f"(d[4]), "+f"(d[5]), "+f"(d[6]), "+f"(d[7]), "+f"(d[8]), "+f"(d[9]), "+f"(d[10]), "+f"(d[11]), "+f"(d[12]), "+f"(d[13]), "+f"(d[14]), "+f"(d[15]), "+f"(d[16]), "+f"(d[17]), "+f"(d[18]), "+f"(d[19]), "+f"(d[20]), "+f"(d[21]), "+f"(d[22]), "+f"(d[23]), "+f"(d[24]), "+f"(d[25]), "+f"(d[26]), "+f"(d[27]), "+f"(d[28]), "+f"(d[29]), "+f"(d[30]), "+f"(d[31])
    : "r"(a0), "r"(a1), "r"(a2), "r"(a3), "l"(descB), "r"(scaleD));
}
__device__ __forceinline__ void wgmma_ss_n128_ta0_tb1(float (&d)[64], uint64_t descA, uint64_t descB, int scaleD) {
  asm volatile("{\n.reg .pred p;\nsetp.ne.b32 p, %66, 0;\n"
    "wgmma.mma_async.sync.aligned.m64n128k16.f32.bf16.bf16 "
    "{%0, %1, %2, %3, %4, %5, %6, %7, %8, %9, %10, %11, %12, %13, %14, %15, %16, %17, %18, %19, %20, %21, %22, %23, %24, %25, %26, %27, %28, %29, %30, %31, %32, %33, %34, %35, %36, %37, %38, %39, %40, %41, %42, %43, %44, %45, %46, %47, %48, %49, %50, %51, %52, %53, %54, %55, %56, %57, %58, %59, %60, %61, %62, %63}, "
    "%64, %65, p, 1, 1, 0, 1;\n}\n"
    : "+f"(d[0]), "+f"(d[1]), "+f"(d[2]), "+f"(d[3]), "+f"(d[4]), "+f"(d[5]), "+f"(d[6]), "+f"(d[7]), "+f"(d[8]), "+f"(d[9]), "+f"(d[10]), "+f"(d[11]), "+f"(d[12]), "+f"(d[13]), "+f"(d[14]), "+f"(d[15]), "+f"(d[16]), "+f"(d[17]), "+f"(d[18]), "+f"(d[19]), "+f"(d[20]), "+f"(d[21]), "+f"(d[22]), "+f"(d[23]), "+f"(d[24]), "+f"(d[25]), "+f"(d[26]), "+f"(d[27]), "+f"(d[28]), "+f"(d[29]), "+f"(d[30]), "+f"(d[31]), "+f"(d[32]), "+f"(d[33]), "+f"(d[34]), "+f"(d[35]), "+f"(d[36]), "+f"(d[37]), "+f"(d[38]), "+f"(d[39]), "+f"(d[40]), "+f"(d[41]), "+f"(d[42]), "+f"(d[43]), "+f"(d[44]), "+f"(d[45]), "+f"(d[46]), "+f"(d[47]), "+f"(d[48]), "+f"(d[49]), "+f"(d[50]), "+f"(d[51]), "+f"(d[52]), "+f"(d[53]), "+f"(d[54]), "+f"(d[55]), "+f"(d[56]), "+f"(d[57]), "+f"(d[58]), "+f"(d[59]), "+f"(d[60]), "+f"(d[61]), "+f"(d[62]), "+f"(d[63])
    : "l"(descA), "l"(descB), "r"(scaleD));
}
__device__ __forceinline__ void wgmma_ss_n160_ta0_tb1(float (&d)[80], uint64_t descA, uint64_t descB, int scaleD) {
  asm volatile("{\n.reg .pred p;\nsetp.ne.b32 p, %82, 0;\n"
    "wgmma.mma_async.sync.aligned.m64n160k16.f32.bf16.bf16 "
    "{%0, %1, %2, %3, %4, %5, %6, %7, %8, %9, %10, %11, %12, %13, %14, %15, %16, %17, %18, %19, %20, %21, %22, %23, %24, %25, %26, %27, %28, %29, %30, %31, %32, %33, %34, %35, %36, %37, %38, %39, %40, %41, %42, %43, %44, %45, %46, %47, %48, %49, %50, %51, %52, %53, %54, %55, %56, %57, %58, %59, %60, %61, %62, %63, %64, %65, %66, %67, %68, %69, %70, %71, %72, %73, %74, %75, %76, %77, %78, %79}, "
    "%80, %81, p, 1, 1, 0, 1;\n}\n"
    : "+f"(d[0]), "+f"(d[1]), "+f"(d[2]), "+f"(d[3]), "+f"(d[4]), "+f"(d[5]), "+f"(d[6]), "+f"(d[7]), "+f"(d[8]), "+f"(d[9]), "+f"(d[10]), "+f"(d[11]), "+f"(d[12]), "+f"(d[13]), "+f"(d[14]), "+f"(d[15]), "+f"(d[16]), "+f"(d[17]), "+f"(d[18]), "+f"(d[19]), "+f"(d[20]), "+f"(d[21]), "+f"(d[22]), "+f"(d[23]), "+f"(d[24]), "+f"(d[25]), "+f"(d[26]), "+f"(d[27]), "+f"(d[28]), "+f"(d[29]), "+f"(d[30]), "+f"(d[31]), "+f"(d[32]), "+f"(d[33]), "+f"(d[34]), "+f"(d[35]), "+f"(d[36]), "+f"(d[37]), "+f"(d[38]), "+f"(d[39]), "+f"(d[40]), "+f"(d[41]), "+f"(d[42]), "+f"(d[43]), "+f"(d[44]), "+f"(d[45]), "+f"(d[46]), "+f"(d[47]), "+f"(d[48]), "+f"(d[49]), "+f"(d[50]), "+f"(d[51]), "+f"(d[52]), "+f"(d[53]), "+f"(d[54]), "+f"(d[55]), "+f"(d[56]), "+f"(d[57]), "+f"(d[58]), "+f"(d[59]), "+f"(d[60]), "+f"(d[61]), "+f"(d[62]), "+f"(d[63]), "+f"(d[64]), "+f"(d[65]), "+f"(d[66]), "+f"(d[67]), "+f"(d[68]), "+f"(d[69]), "+f"(d[70]), "+f"(d[71]), "+f"(d[72]), "+f"(d[73]), "+f"(d[74]), "+f"(d[75]), "+f"(d[76]), "+f"(d[77]), "+f"(d[78]), "+f"(d[79])
    : "l"(descA), "l"(descB), "r"(scaleD));
}

#define PROF_DECL(b)
#define PROF_EV(tag)
#define PROF_GT(tag)

template <int N> struct IC { static constexpr int value = N; };
struct Cur {
    uint32_t slot, ph;
    __device__ __forceinline__ void adv() { if (++slot == NSLOT) { slot = 0; ph ^= 1; } }
};
constexpr int E0 = 2;
__host__ __device__ constexpr uint32_t slot_of(int e) { return (e + E0) % NSLOT; }
__device__ __forceinline__ Cur cur_at(int e) { Cur c; c.slot = (e + E0) % NSLOT; c.ph = ((e + E0) / NSLOT) & 1; return c; }

__device__ __forceinline__ int kv_tile(int s) { return (0x804Cu >> (4 * s)) & 15; }
__device__ __forceinline__ int op_head(int i, int kap) { return 8 * kap + (i & 7) + 16 * (i >> 3); }

constexpr float SM_SCALE = 0.08838834764831845f * 1.4426950408889634f;

struct Ctx {
    uint32_t ring, misc;
    uint32_t rel;
    int w, warp, lane;
};
__device__ __forceinline__ void release(const Ctx& c, uint32_t off, uint32_t cnt) {
    if (c.lane < 2) mbar_arrive_cluster(c.rel + off, cnt);
}
__device__ __forceinline__ void signal_event(const Ctx& c, int ev) {
    __syncwarp();
    if (c.lane == 0) mbar_arrive(c.misc + BAR_EV + (c.w * 16 + ev) * 8);
}
template <int NK, int OFF, int N>
__device__ __forceinline__ uint32_t load_afrag(uint32_t (&a)[N], uint32_t base, const Ctx& c) {
    int r = c.lane & 7, mat = c.lane >> 3;
    uint32_t addr = base + (8 * (mat >> 1) + r) * 128 + (((2 * c.warp + (mat & 1)) ^ r) << 4);
#pragma unroll
    for (int k = 0; k < NK; k++) ldsm4t(a[OFF + 4 * k], a[OFF + 4 * k + 1], a[OFF + 4 * k + 2], a[OFF + 4 * k + 3], addr + k * 2048);
    uint32_t dep = 0;
#pragma unroll
    for (int k = 0; k < NK; k++) dep |= a[OFF + 4 * k];
    return dep & blockIdx.y;
}
__device__ __forceinline__ void tile_out(unsigned char* (&out)[2], unsigned char* dst, int row0, int perm, const Ctx& c) {
#pragma unroll
    for (int i = 0; i < 2; i++) {
        int row = row0 + 16 * c.warp + 8 * i + (c.lane >> 2);
        if (perm) row = perm32(row);
        out[i] = dst + row * 64 + (((c.lane ^ (row >> 1)) & 3) << 4);
    }
}
__device__ __forceinline__ void store_pair(const float (&a)[64], int q, unsigned char* const (&out)[2], int quarter_stride, const float (&f)[2]) {
#pragma unroll
    for (int i = 0; i < 2; i++)
        stg128(out[i] + q * quarter_stride,
               pack_bf16(a[16 * q + 2 * i] * f[i], a[16 * q + 2 * i + 1] * f[i]), pack_bf16(a[16 * q + 4 + 2 * i] * f[i], a[16 * q + 4 + 2 * i + 1] * f[i]),
               pack_bf16(a[16 * q + 8 + 2 * i] * f[i], a[16 * q + 8 + 2 * i + 1] * f[i]), pack_bf16(a[16 * q + 12 + 2 * i] * f[i], a[16 * q + 12 + 2 * i + 1] * f[i]));
}

constexpr float SAFE_SUM = 1099511627776.0f;
template <int NJ>
__device__ __forceinline__ void row_max(const float (&s)[4 * NJ], float (&mx)[2]) {
#pragma unroll
    for (int i = 0; i < 2; i++) {
        float a = fmaxf(s[2 * i], s[2 * i + 1]), b = fmaxf(s[4 + 2 * i], s[4 + 2 * i + 1]);
#pragma unroll
        for (int j = 2; j < NJ; j += 2) {
            a = fmaxf(a, fmaxf(s[4 * j + 2 * i], s[4 * j + 2 * i + 1]));
            b = fmaxf(b, fmaxf(s[4 * j + 4 + 2 * i], s[4 * j + 4 + 2 * i + 1]));
        }
        a = fmaxf(a, b);
        a = fmaxf(a, __shfl_xor_sync(0xffffffffu, a, 1));
        mx[i] = fmaxf(a, __shfl_xor_sync(0xffffffffu, a, 2));
    }
}
template <int NJ, bool SHIFT>
__device__ __forceinline__ void exp_sum(float (&s)[4 * NJ], const float (&m)[2], float& l0, float& l1) {
#pragma unroll
    for (int j = 0; j < NJ; j++) {
#pragma unroll
        for (int e = 0; e < 4; e++) s[4 * j + e] = ex2(SHIFT ? s[4 * j + e] - m[e >> 1] : s[4 * j + e]);
        l0 += s[4 * j + 0] + s[4 * j + 1]; l1 += s[4 * j + 2] + s[4 * j + 3];
    }
}
__device__ __forceinline__ void recompute_scores(float (&s)[64], const uint32_t (&q)[32], uint32_t kaddr, const Ctx& c) {
    const int r = c.lane & 7, mat = c.lane >> 3;
    const uint32_t a0 = kaddr + (8 * (mat & 1) + r) * 64 + (((mat >> 1) ^ (r >> 1)) << 4);
#pragma unroll
    for (int i = 0; i < 64; i++) s[i] = 0.f;
#pragma unroll
    for (int jp = 0; jp < 8; jp++) {
#pragma unroll
        for (int k = 0; k < 8; k++) {
            asm volatile(
                "{\n.reg .b32 b0, b1, b2, b3;\n"
                "ldmatrix.sync.aligned.m8n8.x4.trans.shared.b16 {b0,b1,b2,b3}, [%12];\n"
                "mma.sync.aligned.m16n8k16.row.col.f32.bf16.bf16.f32 {%0,%1,%2,%3}, {%8,%9,%10,%11}, {b0,b1}, {%0,%1,%2,%3};\n"
                "mma.sync.aligned.m16n8k16.row.col.f32.bf16.bf16.f32 {%4,%5,%6,%7}, {%8,%9,%10,%11}, {b2,b3}, {%4,%5,%6,%7};\n}\n"
                : "+f"(s[8 * jp]), "+f"(s[8 * jp + 1]), "+f"(s[8 * jp + 2]), "+f"(s[8 * jp + 3]),
                  "+f"(s[8 * jp + 4]), "+f"(s[8 * jp + 5]), "+f"(s[8 * jp + 6]), "+f"(s[8 * jp + 7])
                : "r"(q[4 * k]), "r"(q[4 * k + 1]), "r"(q[4 * k + 2]), "r"(q[4 * k + 3]),
                  "r"((a0 ^ ((jp & 1) << 5)) + (jp >> 1) * 8192 + k * 1024) : "memory");
        }
    }
}
__device__ __forceinline__ int mask_lim(const Ctx& c) { return perm32(16 * c.warp + (c.lane >> 2)) - 8 * (c.lane & 3); }
template <int J0>
__device__ __forceinline__ void mask_diag(float (&s)[4 * J0 + 32], const Ctx& c) {
    const int lim = mask_lim(c);
    if (c.warp < 2) {
#pragma unroll
        for (int x = 0; x < 16; x++) {
            if (2 * (x >> 2) + (x & 1) - (x & 2) > lim) s[4 * J0 + x] = -INFINITY;
            s[4 * J0 + 16 + x] = -INFINITY;
        }
    } else {
#pragma unroll
        for (int x = 0; x < 16; x++)
            if (32 + 2 * (x >> 2) + (x & 1) - (x & 2) > lim) s[4 * J0 + 16 + x] = -INFINITY;
    }
}
__device__ __forceinline__ void mask_any(float (&s)[64], int hh, const Ctx& c) {
    const int lim = mask_lim(c) + 64 * hh;
#pragma unroll
    for (int x = 0; x < 64; x++)
        if (32 * (x >> 4) + 2 * ((x >> 2) & 3) + (x & 1) - (x & 2) > lim) s[x] = -INFINITY;
}
__device__ __forceinline__ void issue_pv(float (&o)[64], const uint32_t (&p)[32], uint32_t vaddr, int acc, int mode  ) {
    uint64_t d = mkdesc(vaddr, 16, 512, 2);
    if (mode == 0) {
        wg_fence();
#pragma unroll
        for (int k = 0; k < 8; k++)
            wgmma_rs_n128_ta0_tb0(o, p[4 * k], p[4 * k + 1], p[4 * k + 2], p[4 * k + 3], d + (k >> 1) * 512 + 2 * (k & 1), k ? 1 : acc);
        wg_commit();
    } else if (mode == 1) {
        wg_fence();
#pragma unroll
        for (int k = 0; k < 4; k++) wgmma_rs_n128_ta0_tb0(o, p[4 * k], p[4 * k + 1], p[4 * k + 2], p[4 * k + 3], d + (k >> 1) * 512 + 2 * (k & 1), k != 0);
        wg_commit();
    } else {
        wg_fence();
        wgmma_rs_n128_ta0_tb0(o, p[0], p[1], p[2], p[3], d, acc);
        wg_commit();
    }
}
__device__ __forceinline__ void issue_qk(float (&s)[64], const uint32_t (&q)[32], uint32_t kaddr) {
    uint64_t d = mkdesc(kaddr, 8192, 512, 2);
    wg_fence();
#pragma unroll
    for (int k = 0; k < 8; k++) wgmma_rs_n128_ta0_tb1(s, q[4 * k], q[4 * k + 1], q[4 * k + 2], q[4 * k + 3], d + 64 * k, k != 0);
    wg_commit();
}
__device__ __forceinline__ void issue_qk_half(float (&s32)[32], const uint32_t (&q)[32], uint32_t kaddr) {
    uint64_t d = mkdesc(kaddr, 8192, 512, 2);
    wg_fence();
#pragma unroll
    for (int k = 0; k < 8; k++) wgmma_rs_n64_ta0_tb1(s32, q[4 * k], q[4 * k + 1], q[4 * k + 2], q[4 * k + 3], d + 64 * k, k != 0);
    wg_commit();
}
__device__ __forceinline__ void row_inv(const float (&l)[2], float (&inv)[2]) {
#pragma unroll
    for (int i = 0; i < 2; i++) {
        float sum = l[i];
        sum += __shfl_xor_sync(0xffffffffu, sum, 1);
        sum += __shfl_xor_sync(0xffffffffu, sum, 2);
        inv[i] = rcp_fast(sum);
    }
}

__device__ __forceinline__ const unsigned char* xn_addr(int row, int col) {
    row = perm32(row);
    return g_xn + ((row >> 7) * 10 + (col >> 6)) * 16384 + (row & 127) * 128 + ((((col & 63) >> 3) ^ (row & 7)) << 4);
}
__device__ __forceinline__ void mma16816(float (&d)[4], uint32_t a0, uint32_t a1, uint32_t a2, uint32_t a3, uint32_t b0, uint32_t b1) {
    asm volatile("mma.sync.aligned.m16n8k16.row.col.f32.bf16.bf16.f32 {%0,%1,%2,%3}, {%4,%5,%6,%7}, {%8,%9}, {%0,%1,%2,%3};"
                 : "+f"(d[0]), "+f"(d[1]), "+f"(d[2]), "+f"(d[3]) : "r"(a0), "r"(a1), "r"(a2), "r"(a3), "r"(b0), "r"(b1));
}
__device__ __forceinline__ uint32_t lds32(uint32_t addr) { uint32_t v; asm volatile("ld.shared.u32 %0, [%1];" : "=r"(v) : "r"(addr)); return v; }

__device__ LNINL void ln_rows(const __nv_bfloat16* x, int row0, int lane, uint32_t wr_s) {
    const int hl = lane & 15, row = row0 + (lane >> 4);
    uint32_t v[20];
#pragma unroll
    for (int i = 0; i < 5; i++) {
        uint4 u;
        asm("ld.global.nc.L2::cache_hint.v4.b32 {%0,%1,%2,%3}, [%4], %5;" : "=r"(u.x), "=r"(u.y), "=r"(u.z), "=r"(u.w)
            : "l"(x + (size_t)row * DM + 128 * i + 8 * hl), "l"(policy(HM & 512)));
        v[4 * i] = u.x; v[4 * i + 1] = u.y; v[4 * i + 2] = u.z; v[4 * i + 3] = u.w;
    }
    float mean = 0.f, m2 = 0.f, acc2 = 0.f;
#pragma unroll
    for (int i = 0; i < 20; i++) { mean += bf_lo(v[i]); acc2 += bf_hi(v[i]); }
    mean = (mean + acc2) * (1.0f / 40);
    acc2 = 0.f;
#pragma unroll
    for (int i = 0; i < 20; i++) {
        float d0 = __uint_as_float(__byte_perm(v[i], 0, 0x1044)) - mean, d1 = __uint_as_float(__byte_perm(v[i], 0, 0x3244)) - mean;
        m2 = fmaf(d0, d0, m2); acc2 = fmaf(d1, d1, acc2);
    }
    m2 += acc2;
    acc2 = 0.f;
#pragma unroll
    for (int o = 1; o < 16; o <<= 1) {
        float mo = __shfl_xor_sync(0xffffffffu, mean, o), qo = __shfl_xor_sync(0xffffffffu, m2, o), d = mo - mean;
        m2 = fmaf(d * d, 20.0f * o, m2 + qo);
        mean = 0.5f * (mean + mo);
    }
    const uint32_t mb2 = pack_bf16(mean, mean);
    const float inv = rcp_fast(bf_round(sqrt_fast(bf_round(bf_round(m2 * (1.0f / DM)) + 1e-5f))));
    float dot = 0.f;
    unsigned char* xp = const_cast<unsigned char*>(xn_addr(row, 8 * hl));
#pragma unroll
    for (int i = 0; i < 5; i++) {
        uint32_t ww[4];
        asm volatile("ld.shared.v4.b32 {%0,%1,%2,%3}, [%4];" : "=r"(ww[0]), "=r"(ww[1]), "=r"(ww[2]), "=r"(ww[3]) : "r"(wr_s + 256 * i + 16 * hl) : "memory");
#pragma unroll
        for (int e = 0; e < 4; e++) {
            uint32_t d;
            asm("sub.rn.bf16x2 %0, %1, %2;" : "=r"(d) : "r"(v[4 * i + e]), "r"(mb2));
            d = pack_bf16(bf_lo(d) * inv, bf_hi(d) * inv);
            v[4 * i + e] = d;
            dot = fmaf(bf_lo(d), bf_lo(ww[e]), dot);
            acc2 = fmaf(bf_hi(d), bf_hi(ww[e]), acc2);
        }
        stg128(xp + i * 32768, v[4 * i], v[4 * i + 1], v[4 * i + 2], v[4 * i + 3]);
    }
    dot += acc2;
#pragma unroll
    for (int o = 8; o > 0; o >>= 1) dot += __shfl_xor_sync(0xffffffffu, dot, o);
    if (hl == 0) { g_router[row] = bf_round(dot); g_stats[row] = make_uint2(mb2, __float_as_uint(inv)); }
}

__device__ __forceinline__ void aux_cta(const CUtensorMap* tmG, const CUtensorMap* tmU, const CUtensorMap* tmD, unsigned char* sm, int a) {
    constexpr int STG = 57344, XS = 3 * STG, HS = XS + 8 * 1296, KEY = HS + 8 * 912, MI = KEY + 8192;
    const int tid = threadIdx.x, warp = __shfl_sync(0xffffffffu, tid >> 5, 0), lane = tid & 31;
    const uint32_t sb = smem_u32(sm);
    const uint32_t full = sb + MI, empty = sb + MI + 32;
    int* s_sel = reinterpret_cast<int*>(sm + MI + 64);
    float* s_r = reinterpret_cast<float*>(sm + MI + 96);
    volatile unsigned* s_misc = reinterpret_cast<volatile unsigned*>(sm + MI + 128);
    uint32_t* s_key = reinterpret_cast<uint32_t*>(sm + KEY);
    PROF_DECL(128 + a)
    PROF_GT(0);
    if (tid == 0) {
        for (int i = 0; i < 3; i++) { mbar_init(full + 8 * i, 1); mbar_init(empty + 8 * i, 10); }
        asm volatile("fence.mbarrier_init.release.cluster;" ::: "memory");
    }
    __syncthreads();
    if (warp == 11) {
        if (elect_one()) {
            int st = 0; uint32_t ph = 0;
#pragma unroll 1
            for (int s = 0; s < 34; s++) {
                mbar_wait(empty + 8 * st, ph ^ 1);
                const uint32_t dst = sb + st * STG, fb = full + 8 * st;
                if (s < 20) {
                    mbar_expect_tx(fb, 57344);
                    tma3d(dst, tmG, 0, 32 * s, 7 * a, fb);
                    tma3d(dst + 28672, tmU, 0, 32 * s, 7 * a, fb);
                } else {
                    mbar_expect_tx(fb, 40960);
                    tma3d(dst, tmD, 0, 448 * a + 32 * (s - 20), 0, fb);
                }
                if (s >= 3) {
#pragma unroll 1
                    for (int f = (s == 3 ? 4 : s + 6); f <= s + 6 && f < 34; f++) {
                        if (f < 20) { tma3d_prefetch(tmG, 0, 32 * f, 7 * a); tma3d_prefetch(tmU, 0, 32 * f, 7 * a); }
                        else tma3d_prefetch(tmD, 0, 448 * a + 32 * (f - 20), 0);
                    }
                }
                if (++st == 3) { st = 0; ph ^= 1; }
            }
        }
        return;
    }
    PROF_GT(49);
    if (warp == 10) return;
    if (tid < 8) {
        unsigned e = *reinterpret_cast<volatile unsigned*>(&g_epoch);
        if (tid == 0) s_misc[0] = e;
        flag_wait(flag_ptr(FL_LN + tid), (e + 1) * (tid < 4 ? 33u : 128u));
    }
    bar_sync(1, 320);
    PROF_GT(50);
    const unsigned ep = s_misc[0];
    auto top8 = [&](uint32_t (&key)[8]) {
        uint32_t mine = 0;
#pragma unroll 1
        for (int r = 0; r < TOPC; r++) {
            uint32_t best = 0;
#pragma unroll
            for (int i = 0; i < 8; i++) best = max(best, key[i]);
            best = __reduce_max_sync(0xffffffffu, best);
#pragma unroll
            for (int i = 0; i < 8; i++) if (key[i] == best) key[i] = 0;
            if (lane == r) mine = best;
        }
        return mine;
    };
#pragma unroll 1
    for (int pass = 0; pass < 2; pass++) {
        if (warp < (pass ? 1 : 8)) {
            uint32_t key[8];
#pragma unroll
            for (int i = 0; i < 8; i++) {
                if (pass == 0) {
                    int idx = warp * 256 + i * 32 + lane;
                    uint32_t b = __float_as_uint(__ldcg(g_router + idx)) >> 16;
                    b = (b & 0x8000u) ? (~b & 0xffffu) : (b | 0x8000u);
                    key[i] = (b << 16) | (uint32_t)(0xffff - idx);
                } else key[i] = i < 2 ? s_key[i * 32 + lane] : 0u;
            }
            uint32_t best = top8(key);
            if (lane < TOPC) {
                if (pass == 0) s_key[warp * 8 + lane] = best;
                else {
                    uint32_t b = best >> 16;
                    b = (b & 0x8000u) ? (b & 0x7fffu) : (~b & 0xffffu);
                    s_sel[lane] = 0xffff - (int)(best & 0xffffu);
                    s_r[lane] = bf_round(rcp_fast(1.0f + __expf(fminf(-__uint_as_float(b << 16), 80.f))));
                }
            }
        }
        bar_sync(1, 320);
    }
#pragma unroll 1
    for (int it = 0; it < 2; it++) {
        int i = tid + it * 320, tk = i / 80, ch = i % 80;
        *reinterpret_cast<uint4*>(sm + XS + tk * 1296 + ch * 16) = __ldcg(reinterpret_cast<const uint4*>(xn_addr(s_sel[tk], ch * 8)));
    }
    bar_sync(1, 320);
    PROF_GT(51);
    const int g = lane >> 2, t = lane & 3;
    const uint32_t woff = warp * 4096 + (8 * (lane >> 4) + (lane & 7)) * 128 + ((((lane >> 3) & 1) ^ (lane & 7)) << 4);
    int st = 0; uint32_t ph = 0;
    float ga[4][4], ua[4][4];
#pragma unroll
    for (int i = 0; i < 4; i++)
#pragma unroll
        for (int e = 0; e < 4; e++) { ga[i][e] = 0.f; ua[i][e] = 0.f; }
#pragma unroll 1
    for (int s = 0; s < 34; s++) {
        if (s == 20) {
            if (warp < 7) {
#pragma unroll 1
                for (int i = 0; i < 4; i++) {
#pragma unroll
                    for (int e = 0; e < 4; e++) {
                        float gv = bf_round(ga[0][e]), uv = bf_round(ua[0][e]);
                        float sg = bf_round(gv * rcp_fast(1.0f + __expf(fminf(-gv, 80.f))));
                        int f = warp * 64 + i * 16 + g + 8 * (e >> 1), tk = 2 * t + (e & 1);
                        *reinterpret_cast<__nv_bfloat16*>(sm + HS + tk * 912 + f * 2) = __float2bfloat16_rn(sg * uv);
                        ga[0][e] = ga[1][e]; ga[1][e] = ga[2][e]; ga[2][e] = ga[3][e]; ga[3][e] = 0.f;
                        ua[0][e] = ua[1][e]; ua[1][e] = ua[2][e]; ua[2][e] = ua[3][e];
                    }
                }
            }
            bar_sync(1, 320);
            PROF_GT(52);
        }
        mbar_wait(full + 8 * st, ph);
        if (s >= 20 || warp < 7) {
#pragma unroll
            for (int kk = 0; kk < 2; kk++) {
                uint32_t xb = sb + (s < 20 ? XS + g * 1296 + s * 64 : HS + g * 912 + (s - 20) * 64) + 32 * kk + 4 * t;
                uint32_t b0 = lds32(xb), b1 = lds32(xb + 16);
                uint32_t wa = sb + st * STG + woff + kk * 2048;
#pragma unroll
                for (int i = 0; i < 4; i++) {
                    uint32_t a0, a1, a2, a3;
                    ldsm4t(a0, a1, a2, a3, wa ^ (i << 5));
                    mma16816(ga[i], a0, a1, a2, a3, b0, b1);
                    if (s < 20) {
                        ldsm4t(a0, a1, a2, a3, (wa ^ (i << 5)) + 28672);
                        mma16816(ua[i], a0, a1, a2, a3, b0, b1);
                    }
                }
            }
        }
        asm volatile("fence.proxy.async.shared::cta;" ::: "memory");
        __syncwarp();
        if (lane == 0) mbar_arrive(empty + 8 * st);
        if (++st == 3) { st = 0; ph ^= 1; }
    }
#pragma unroll
    for (int i = 0; i < 4; i++)
#pragma unroll
        for (int e = 0; e < 4; e += 2)
            *reinterpret_cast<float2*>(g_moe_part + (a * DM + warp * 64 + i * 16 + g + 4 * e) * 8 + 2 * t) = make_float2(ga[i][e], ga[i][e + 1]);
    bar_sync(1, 320);
    if (tid == 0) {
        __threadfence();
        unsigned old = atomicAdd(flag_ptr(FL_MOE_CNT), 1u);
        s_misc[1] = (old == ep * 4u + 3u);
        __threadfence();
    }
    bar_sync(1, 320);
    PROF_GT(53);
    if (s_misc[1]) {
        const float4* pp = reinterpret_cast<const float4*>(g_moe_part);
#pragma unroll 1
        for (int i = tid; i < DM * 2; i += 320) {
            float4 v0 = __ldcg(pp + i), v1 = __ldcg(pp + DM * 2 + i), v2 = __ldcg(pp + DM * 4 + i), v3 = __ldcg(pp + DM * 6 + i);
            float y[4] = {v0.x + v1.x + v2.x + v3.x, v0.y + v1.y + v2.y + v3.y, v0.z + v1.z + v2.z + v3.z, v0.w + v1.w + v2.w + v3.w};
#pragma unroll
            for (int e = 0; e < 4; e++) {
                int col = i >> 1, tk = (i & 1) * 4 + e;
                float upd = bf_round(bf_round(y[e]) * s_r[tk]);
                float xn = __bfloat162float(*reinterpret_cast<const __nv_bfloat16*>(sm + XS + tk * 1296 + col * 2));
                g_brow[tk * DM + col] = __float2bfloat16_rn(xn + upd);
            }
        }
        if (tid < TOPC) g_sel[tid] = s_sel[tid];
        bar_sync(1, 320);
        if (tid == 0) {
            flag_signal(flag_ptr(FL_MOE_DONE));
            *reinterpret_cast<volatile unsigned*>(&g_epoch) = ep + 1;
        }
        PROF_GT(54);
    }
}

__global__ void __cluster_dims__(2, 1, 1) __launch_bounds__(384, 1)
fused_kernel(const __grid_constant__ CUtensorMap tmC, const __grid_constant__ CUtensorMap tmWk, const __grid_constant__ CUtensorMap tmWv,
             const __grid_constant__ CUtensorMap tmWq, const __grid_constant__ CUtensorMap tmWo,
             const __grid_constant__ CUtensorMap tmG, const __grid_constant__ CUtensorMap tmU, const __grid_constant__ CUtensorMap tmD, const Params P) {
    extern __shared__ __align__(1024) unsigned char smem_raw[];
    const uint32_t ring = smem_u32(smem_raw);
    const uint32_t misc = ring + RING_BYTES;
    const int tid = threadIdx.x;
    const int rank = blockIdx.x & 1;
    uint32_t smid, nsm;
    asm("mov.u32 %0, %%smid;" : "=r"(smid));
    asm("mov.u32 %0, %%nsmid;" : "=r"(nsm));
    if (nsm != 132) smid = blockIdx.x;
    auto role_of = [](int tpc) {
        return tpc < 32 ? (tpc & 7) * 8 + (tpc >> 3) : tpc < 60 ? (1 + (tpc - 32) % 7) * 8 + 4 + (tpc - 32) / 7 : tpc < 64 ? tpc - 56 : tpc;
    };
    int mc = role_of(smid >> 1);
    PROF_DECL(mc * 2 + rank)
    PROF_GT(0); PROF_EV(1);

    auto prefetch_w = [&](int ch) {
        const int i = tid - 128;
        asm volatile("prefetch.global.L2 [%0];" ::"l"((rank ? P.wv : P.wk) + (size_t)(ch * 128 + (mc & 3) * 32 + (i >> 3)) * 4096 + (mc >> 2) * 128 + (i & 7) * 16));
    };
    if (tid >= 128 && mc < 64) {
        if (tid < 256) asm volatile("prefetch.global.L2 [%0];" ::"l"(P.c + (size_t)((12 + (mc & 3)) * 128 + ((mc >> 2) * 2 + rank) * 4) * DC + (tid - 128) * 16));
        prefetch_w(0);
    }
    auto load_w0 = [&]() {
        const CUtensorMap* tw = rank ? &tmWv : &tmWk;
        mbar_expect_tx(misc + BAR_FULL + 8 * slot_of(0), SLOT_BYTES);
        tma2d(ring + slot_of(0) * SLOT_BYTES, tw, (mc >> 2) * 128, 0, misc + BAR_FULL + 8 * slot_of(0), policy(HM & 1));
        tma2d(ring + slot_of(0) * SLOT_BYTES + 16384, tw, (mc >> 2) * 128 + 64, 0, misc + BAR_FULL + 8 * slot_of(0), policy(HM & 1));
    };
    if (tid == 0) {
#pragma unroll
        for (int i = 0; i < NSLOT; i++) mbar_init(misc + BAR_FULL + 8 * i, 1);
#pragma unroll
        for (int i = 0; i < E0; i++) mbar_arrive(misc + BAR_FULL + 8 * i);
        asm volatile("fence.mbarrier_init.release.cluster;" ::: "memory");
        if (mc < 64) load_w0();
    }
    if (tid == 160) {
        asm volatile("st.shared.u32 [%0], %1;" ::"r"(misc + MISC_SMID), "r"(smid) : "memory");
        asm volatile("fence.release.sync_restrict::shared::cta.cluster;" ::: "memory");
    }
    if (tid == 32) {
        asm volatile("prefetch.tensormap [%0];" ::"l"(&tmC) : "memory");
#pragma unroll
        for (int i = 0; i < NSLOT; i++) mbar_init(misc + BAR_EMPTY + 8 * i, 16);
#pragma unroll
        for (int i = 0; i < E0; i++) mbar_arrive_cluster(misc + BAR_EMPTY + 8 * i, 16);
        asm volatile("fence.mbarrier_init.release.cluster;" ::: "memory");
    }
    if (tid == 64) {
#pragma unroll
        for (int i = 0; i < NST3; i++) { mbar_init(misc + BAR_FULL3 + 8 * i, 1); mbar_init(misc + BAR_EMPTY3 + 8 * i, 16); }
#pragma unroll
        for (int i = 0; i < 4; i++) mbar_init(misc + BAR_LN + 8 * i, 2);
        mbar_init(misc + BAR_PROG, 1); mbar_init(misc + BAR_PROG + 8, 1); mbar_init(misc + BAR_PROG + 16, 1);
        asm volatile("fence.mbarrier_init.release.cluster;" ::: "memory");
    }
    if (tid == 96) {
#pragma unroll
        for (int i = 0; i < 34; i++) mbar_init(misc + BAR_DEP + 8 * i, 1);
    }
    if (tid == 128) {
#pragma unroll
        for (int i = 0; i < 32; i++) mbar_init(misc + BAR_EV + 8 * i, 4);
    }
    __syncthreads();
    asm volatile("barrier.cluster.arrive.relaxed.aligned;\nbarrier.cluster.wait.aligned;" ::: "memory");
    {
        uint32_t peer;
        asm volatile("ld.shared::cluster.u32 %0, [%1];" : "=r"(peer) : "r"(mapa(misc + MISC_SMID, rank ^ 1)) : "memory");
        if ((__shfl_sync(0xffffffffu, peer, 0) ^ smid) != 1) {
            if (tid == 0) {
                const unsigned ep1 = *reinterpret_cast<volatile unsigned*>(&g_epoch) + 1;
                if ((smid & 1) == 0) atomicExch(g_roleq + 2 + (atomicAdd(g_roleq, 1u) & 127), (ep1 << 8) | (smid >> 1));
                if (rank == 0) {
                    unsigned* slot = g_roleq + 2 + (atomicAdd(g_roleq + 1, 1u) & 127);
                    unsigned v = 0;
                    for (int spin = 0; spin < 4000000 && ((v = atomicAdd(slot, 0u)) >> 8) != (ep1 & 0xffffffu); spin++) {}
                    asm volatile("st.shared::cluster.u32 [%0], %1;" ::"r"(mapa(misc + MISC_SMID + 4, 0)), "r"(v & 255) : "memory");
                    asm volatile("st.shared::cluster.u32 [%0], %1;" ::"r"(mapa(misc + MISC_SMID + 4, 1)), "r"(v & 255) : "memory");
                }
                if (mc < 64) {
                    mbar_wait(misc + BAR_FULL + 8 * slot_of(0), 0);
                    asm volatile("mbarrier.inval.shared::cta.b64 [%0];" ::"r"(misc + BAR_FULL + 8 * slot_of(0)) : "memory");
                    mbar_init(misc + BAR_FULL + 8 * slot_of(0), 1);
                    asm volatile("fence.mbarrier_init.release.cluster;" ::: "memory");
                }
            }
            __syncwarp();
            asm volatile("barrier.cluster.arrive.aligned;\nbarrier.cluster.wait.aligned;" ::: "memory");
            mc = role_of(__shfl_sync(0xffffffffu, lds32(misc + MISC_SMID + 4), 0));
            if (tid == 0 && mc < 64) load_w0();
            __syncwarp();
        }
    }
    const int cta = mc * 2 + rank;
    const bool aux = mc >= 64;
    const int team = mc >> 2, k = mc & 3;
    const int u3 = (mc >> 4) * 2 + (team & 1), s3 = k, kap = (mc >> 3) & 1;
    const int partner = cta ^ 16;
    const int b0 = k, b1 = 7 - k;
    if (tid >= 128 && !aux) prefetch_w(1);
    if (tid == 256 && !aux) {
        const CUtensorMap* tw = rank ? &tmWv : &tmWk;
#pragma unroll
        for (int e = 1; e < NSLOT; e++) {
            const uint32_t fb = misc + BAR_FULL + 8 * slot_of(e), dst = ring + slot_of(e) * SLOT_BYTES;
            mbar_expect_tx(fb, SLOT_BYTES);
            if (e & 1) tma2d_mc(dst + rank * 16384, &tmC, (e >> 1) * 128 + rank * 64, (12 + k) * 128, fb, policy(false));
            else { tma2d(dst, tw, team * 128, e * 64, fb, policy(false)); tma2d(dst + 16384, tw, team * 128 + 64, e * 64, fb, policy(false)); }
        }
    }
    PROF_EV(5);
    const int wg = __shfl_sync(0xffffffffu, tid >> 7, 0);

    if (wg == 0 || aux) {
        asm volatile("setmaxnreg.dec.sync.aligned.u32 40;");
        const int warp = __shfl_sync(0xffffffffu, tid >> 5, 0), lane = tid & 31;
        if (warp == 0 && !aux) {
            const bool lead = elect_one();
            Cur c = cur_at(NSLOT);
            uint32_t dst, fb;
            auto acquire = [&]() {
                mbar_wait_sleep(misc + BAR_EMPTY + 8 * c.slot, c.ph ^ 1);
                fb = misc + BAR_FULL + 8 * c.slot; dst = ring + c.slot * SLOT_BYTES;
                if (lead) mbar_expect_tx(fb, SLOT_BYTES);
                c.adv();
            };
            auto load_w = [&](const CUtensorMap* tm, int col, int row, bool stream) {
                acquire();
                if (lead) { tma2d(dst, tm, col, row, fb, policy(stream)); tma2d(dst + 16384, tm, col + 64, row, fb, policy(stream)); }
            };
            auto load_half = [&](const unsigned char* src, bool stream) {
                acquire();
                if (lead) bulk_load_mc(dst + rank * 16384, src, 16384, fb, policy(stream));
            };
            auto dep_wait = [&](int d) { mbar_wait_sleep(misc + BAR_DEP + 8 * d, 0); fence_async_global(); };
            auto op_prefetch = [&](int i) {
                const int head = op_head(i, kap);
                l2_prefetch(reinterpret_cast<const unsigned char*>(P.wo) + head * 163840 + (u3 * 8 + s3 * 2 + rank) * 2560, 2560);
                if (i < 8) l2_prefetch(g_ctx + (size_t)(head * 32 + 4 * u3 + 2 * rank) * 16384 + s3 * 8192, 8192);
            };
            if (lead) l2_prefetch(reinterpret_cast<const unsigned char*>(P.c) + (size_t)cta * 12288, 12288);
            const CUtensorMap* tw = rank ? &tmWv : &tmWk;
            const unsigned char* Kh = g_K + (size_t)team * 32 * 16384 + rank * 16384;
            const unsigned char* Vh = g_V + (size_t)team * 32 * 16384 + rank * 16384;
#pragma unroll 1
            for (int v = 0; v < 2; v++) {
                const int h = team + 16 * v;
#pragma unroll 1
                for (int i = v ? 0 : 3; i < 16; i++) {
                    if (i < 4 && v) load_w(tw, h * 128, i * 128, HM & 1);
                    if (v && i == 3 && lead) mbar_arrive(misc + BAR_PROG + 8);
                    if (v && (i == 3 || i == 7)) dep_wait(D_WAR + (i > 3));
                    acquire();
                    if (lead) tma2d_mc(dst + rank * 16384, &tmC, (i & 3) * 128 + rank * 64, (kv_tile(i >> 2) + k) * 128, fb, policy(HM & 2));
                    if (i == WQPF && lead) {
                        tma2d_prefetch(&tmWq, h * 128 + rank * 64, k * 64); tma2d_prefetch(&tmWq, h * 128 + rank * 64, k * 64 + 256);
                        if (k < 2) tma2d_prefetch(&tmWq, h * 128 + rank * 64, k * 64 + 512);
                        if (v) l2_prefetch(g_xn + cta * 10240, 10240);
                    }
                }
                int togo = v ? PF_START : 11;
#pragma unroll 1
                for (int r = 0; r < 2; r++) {
                    const int p = r ? b1 : b0, n = 2 * p + 1;
                    if (v == 0) dep_wait(D_LN + r);
                    const int g0 = r ? rank ^ SWAPT : 3 - rank, g1 = 3 - g0;
                    const unsigned char* x0 = g_xn + (2 * p + (g0 >> 1)) * 163840 + (g0 & 1) * 8192;
                    const unsigned char* x1 = g_xn + (2 * p + (g1 >> 1)) * 163840 + (g1 & 1) * 8192;
#pragma unroll 1
                    for (int kc = 0; kc < 10; kc++) {
                        acquire();
                        if (lead) {
                            tma2d_mc(dst + 16384 + rank * 8192, &tmWq, h * 128 + rank * 64, kc * 64, fb, policy(false));
                            bulk_load(dst, x0 + kc * 16384, 8192, fb, policy(false));
                            bulk_load(dst + 8192, x1 + kc * 16384, 8192, fb, policy(false));
                        }
                    }
                    dep_wait(D_KV + 2 * v + r);
                    load_half(Kh + n * 32768, HM & 16);
#pragma unroll 1
                    for (int j = n - 1; j >= 0; j--) {
                        load_half(Kh + j * 32768, HM & 16); load_half(Vh + (j + 1) * 32768, HM & 16);
                        if (v == 0 && r && j == 7 && lead) mbar_arrive(misc + BAR_PROG);
                        --togo;
                        if (v == 0 && togo == 0 && lead) {
                            tma2d_prefetch(tw, h * 128 + 2048, k * 128); tma2d_prefetch(tw, h * 128 + 2112, k * 128);
                            l2_prefetch(reinterpret_cast<const unsigned char*>(P.c) + (size_t)cta * 16384, 16384);
                        }
                        if (v && togo <= 0 && togo > -OP_PF && lead) op_prefetch(-togo);
                    }
                    load_half(Vh, HM & 16);
                }
            }
            mbar_wait_sleep(misc + BAR_EMPTY + 8 * c.slot, c.ph ^ 1); c.adv();
            int st = 0; uint32_t ph3 = 0;
#pragma unroll 1
            for (int i = 0; i < 32; i++) {
                const int head = op_head(i >> 1, kap);
                if ((i & 1) == 0) dep_wait(D_CTX + (i >> 1));
                if (i < NST3) { mbar_wait_sleep(misc + BAR_EMPTY + 8 * c.slot, c.ph ^ 1); c.adv(); }
                else mbar_wait_sleep(misc + BAR_EMPTY3 + 8 * st, ph3 ^ 1);
                fb = misc + BAR_FULL3 + 8 * st; dst = ring + st * ST3_BYTES;
                if (i == LATE_AT && lead) mbar_arrive(misc + BAR_PROG + 16);
                if (lead) {
                    mbar_expect_tx(fb, ST3_BYTES);
                    const unsigned char* src = g_ctx + (size_t)(head * 32 + 4 * u3 + 2 * rank) * 16384 + (i & 1) * 8192;
                    bulk_load(dst, src, 8192, fb, policy(HM & 32));
                    bulk_load(dst + 8192, src + 16384, 8192, fb, policy(HM & 32));
                    tma3d_mc(dst + 16384 + rank * 10240, &tmWo, 0, head * 128 + (i & 1) * 64 + rank * 32, 5 * s3, fb, policy(HM & 32));
                    if ((i & 1) && (i >> 1) + OP_PF < 16) op_prefetch((i >> 1) + OP_PF);
                }
                if (++st == NST3) { st = 0; ph3 ^= 1; }
            }
        } else {
        if (warp >= 1 && warp <= 3 && lane < 27 && (warp - 1) * 27 + lane < 80) {
            const int ch = (warp - 1) * 27 + lane;
            uint4 u = __ldg(reinterpret_cast<const uint4*>(P.wr) + ch);
            asm volatile("st.shared.v4.b32 [%0], {%1,%2,%3,%4};" ::"r"(misc + MISC_WR + 16 * ch), "r"(u.x), "r"(u.y), "r"(u.z), "r"(u.w) : "memory");
        }
        bar_sync(3, aux ? 384 : 96);
        const int nln = aux ? (warp < 8 ? 3 : 2) : (warp == 3 ? 1 : 3), rstep = aux ? 24 : -512;
        int lrow = aux ? (cta - 128) * 256 + 192 + 2 * warp : (cta >> 5) * 256 + (cta & 31) * 6 + (warp - 1) * 2;
        int lnext = aux ? lrow + 24 : 1536 + cta * 4 + (warp - 1) * 2;
#pragma unroll 1
        for (int t = 0; t < nln; t++) {
            if (t + 1 < nln) {
#pragma unroll
                for (int i = 0; i < 3; i++)
                    if (i * 32 + lane < 80) asm volatile("prefetch.global.L2 [%0];" ::"l"(P.x + (size_t)lnext * DM + (i * 32 + lane) * 16));
            }
            ln_rows(P.x, lrow, lane, misc + MISC_WR);
            __syncwarp();
            if (lane == 0 && warp < 3 && !aux) {
                if (t) flag_signal(flag_ptr(FL_LN + (lrow >> 8))); else mbar_arrive(misc + BAR_LN);
            }
            lrow = lnext; lnext += rstep;
        }
        if (aux) {
            bar_sync(3, 384);
            if (tid == 320) flag_signal(flag_ptr(FL_LN + cta - 128));
            __syncwarp();
            asm volatile("setmaxnreg.inc.sync.aligned.u32 128;");
            aux_cta(&tmG, &tmU, &tmD, smem_raw, cta - 128);
        } else
        if (warp == 3) {
            const unsigned ep1 = *reinterpret_cast<volatile unsigned*>(&g_epoch) + 1;
            if (lane == 0) {
                asm volatile("st.shared.u32 [%0], %1;" ::"r"(misc + MISC_EPOCH), "r"(ep1) : "memory");
                mbar_wait(misc + BAR_LN, 0);
                flag_signal(flag_ptr(FL_LN + (cta >> 5)));
                flag_wait(flag_ptr(FL_LN + b0), ep1 * 33u);
                mbar_arrive(misc + BAR_DEP + 8 * D_LN);
#pragma unroll 1
                for (int i = 0; i < 4; i++) {
                    mbar_wait(misc + BAR_EV + 8 * (16 + EV_KV + i), 0);
                    if (i < 2) {
                        mbar_wait(misc + BAR_EV + 8 * (EV_KV + i), 0);
                        asm volatile("red.release.gpu.global.add.u32 [%0], 2;" ::"l"(flag_ptr(FL_KV + team * 8 + i)) : "memory");
                    }
                    if (i == 1) {
                        flag_wait(flag_ptr(FL_LN + b1), ep1 * 128u);
                        mbar_arrive(misc + BAR_DEP + 8 * (D_LN + 1));
                    }
                    flag_wait(flag_ptr(FL_KV + team * 8 + i), ep1 * 16u);
                    mbar_arrive(misc + BAR_DEP + 8 * (D_KV + i));
                    if (i == 1) {
#pragma unroll 1
                        for (int j = 0; j < 2; j++) {
                            mbar_wait(misc + BAR_PROG + 8 * j, 0);
                            asm volatile("red.relaxed.gpu.global.add.u32 [%0], 1;" ::"l"(flag_ptr(FL_WAR + 2 * team + j)) : "memory");
                            flag_wait(flag_ptr(FL_WAR + 2 * team + j), ep1 * 8u);
                            mbar_arrive(misc + BAR_DEP + 8 * (D_WAR + j));
                        }
                    }
                }
                flag_wait(flag_ptr(FL_MOE_DONE), ep1);
                int4 s0 = __ldcg(reinterpret_cast<const int4*>(g_sel)), s1 = __ldcg(reinterpret_cast<const int4*>(g_sel) + 1);
                asm volatile("st.shared.v4.u32 [%0], {%1,%2,%3,%4};" ::"r"(misc + MISC_SEL), "r"(s0.x), "r"(s0.y), "r"(s0.z), "r"(s0.w) : "memory");
                asm volatile("st.shared.v4.u32 [%0], {%1,%2,%3,%4};" ::"r"(misc + MISC_SEL + 16), "r"(s1.x), "r"(s1.y), "r"(s1.z), "r"(s1.w) : "memory");
                mbar_arrive(misc + BAR_SEL);
            }
            __syncwarp();
            const unsigned* cf = flag_ptr(FL_CTX + op_head(lane & 15, kap) * 8 + u3);
#pragma unroll 1
            for (int half = 0; half < 2; half++) {
                if (half) mbar_wait(misc + BAR_EV + 8 * (EV_CTX + 3), 0);
                bool done = (lane >> 3) != half;
                for (int spin = 0; spin < 4000000; spin++) {
                    if (!done) {
                        unsigned v;
                        asm volatile("ld.acquire.gpu.global.u32 %0, [%1];" : "=r"(v) : "l"(cf) : "memory");
                        if ((int)(v - ep1 * 4u) >= 0) { mbar_arrive(misc + BAR_DEP + 8 * (D_CTX + lane)); done = true; }
                    }
                    if (__all_sync(0xffffffffu, done)) break;
                    __nanosleep(64);
                }
            }
        } else {
            const int w = warp - 1;
            if (lane == 0) {
                const uint32_t eb = misc + BAR_EV + w * 128;
#pragma unroll 1
                for (int i = 0; i < 6; i++) {
                    const bool kv = (i >> 1) == 1;
                    const int ci = i < 2 ? i : i - 2;
                    mbar_wait(eb + 8 * (kv ? EV_KV + i : EV_CTX + ci), 0);
                    if (i == 1) {
                        asm volatile("cp.async.bulk.global.shared::cta.bulk_group [%0], [%1], 16384;"
                                     ::"l"(g_ctx + (size_t)(team * 32 + 4 * b1 + (w ? 3 - (rank ^ SWAPT) : rank ^ SWAPT)) * 16384),
                                       "r"(ring + slot_of(78) * SLOT_BYTES + w * 16384) : "memory");
                        asm volatile("cp.async.bulk.commit_group;" ::: "memory");
                        asm volatile("cp.async.bulk.wait_group.read 0;" ::: "memory");
                        mbar_arrive_cluster(mapa(misc + BAR_EMPTY + 8 * slot_of(78), 0), 4);
                        mbar_arrive_cluster(mapa(misc + BAR_EMPTY + 8 * slot_of(78), 1), 4);
                        asm volatile("cp.async.bulk.wait_group 0;" ::: "memory");
                        fence_async_global();
                    }
                    flag_signal(flag_ptr(kv ? FL_KV + team * 8 + i : FL_CTX + (team + 16 * (ci >> 1)) * 8 + ((ci & 1) ? b1 : b0)));
                }
            }
            __syncwarp();
            mbar_wait(misc + BAR_PROG + 16, 0);
            const int row = (2 * u3 + rank) * 128 + 64 * w + perm32(16 * (lane >> 3) + 8 * kap + (lane & 7));
#pragma unroll
            for (int i = 0; i < 10; i++) asm volatile("prefetch.global.L2 [%0];" ::"l"(P.x + (size_t)row * DM + 160 * s3 + 16 * i));
            asm volatile("prefetch.global.L2 [%0];" ::"l"(g_stats + row));
            if (lane < 5) asm volatile("prefetch.global.L2 [%0];" ::"l"(g_brow + ((cta & 31) * 10 + w * 5 + lane) * 16));
            mbar_wait(misc + BAR_EV + w * 128 + 8 * EV_END, 0);
        }
        }
    } else {
        asm volatile("setmaxnreg.inc.sync.aligned.u32 232;");
        Ctx c;
        c.ring = ring; c.misc = misc; c.w = wg - 1; c.warp = __shfl_sync(0xffffffffu, (tid >> 5) & 3, 0); c.lane = tid & 31;
        c.rel = mapa(misc, tid & 1);
        const int w = c.w;
        if (w == 1) bar_arrive(1, 256);
        prefetch_w(2); prefetch_w(3);
        Cur cur = cur_at(0);
        float o[64], inv[2];
        unsigned char* out[2];
        uint32_t wf[128];
        Cur cw = cur;
        auto load_wchunk = [&](auto CH) {
            constexpr int ch = decltype(CH)::value;
            mbar_wait_hot(misc + BAR_FULL + 8 * cw.slot, cw.ph);
            const uint32_t z = load_afrag<8, 32 * ch>(wf, ring + cw.slot * SLOT_BYTES + w * 16384, c);
            release(c, BAR_EMPTY + 8 * cw.slot + z, 1);
            cw.adv(); cw.adv();
        };
#pragma unroll
        for (int i = 32; i < 64; i++) wf[i] = 0u;
        load_wchunk(IC<0>{});
#pragma unroll 1
        for (int v = 0; v < 2; v++) {
        {
            float (&acc)[64] = o;
#pragma unroll
            for (int i = 64; i < 128; i++) wf[i] = 0u;
            cur.adv();
            inv[0] = inv[1] = rank ? 1.0f : SM_SCALE;
            PROF_EV(2); PROF_GT(60);
#pragma unroll 1
            for (int t = 0; t < 4; t++) {
                uint32_t last = 0;
                token_wait(w);
                PROF_EV(10);
                undef_regs(acc);
                auto chunk = [&](auto CH) {
                    constexpr int ch = decltype(CH)::value;
                    mbar_wait_hot(misc + BAR_FULL + 8 * cur.slot, cur.ph);
                    if (t == 0) { PROF_EV(12 + ch); }
                    uint64_t d = mkdesc(ring + cur.slot * SLOT_BYTES, 16, 1024, 1);
                    wg_fence();
#pragma unroll
                    for (int ks = 0; ks < 8; ks++)
                        wgmma_rs_n128_ta0_tb0(acc, wf[32 * ch + 4 * ks], wf[32 * ch + 4 * ks + 1], wf[32 * ch + 4 * ks + 2], wf[32 * ch + 4 * ks + 3],
                                              d + (ks >> 2) * 1024 + (ks & 3) * 2, (ch | ks) != 0);
                    wg_commit();
                    if (ch == 3 || (ch < 2 && t == 0)) token_pass(w);
                    if constexpr (ch == 0) { if (t == 0) { if (v) load_wchunk(IC<2>{}); else load_wchunk(IC<1>{}); } }
                    if constexpr (ch == 1) { if (t == 0 && !v) load_wchunk(IC<2>{}); }
                    if constexpr (ch == 2) { if (t == 0 && !(w | v)) load_wchunk(IC<3>{}); }
                    if (ch > 0) { wg_wait<1>(); release(c, BAR_EMPTY + 8 * last, 1); }
                    last = cur.slot;
                    cur.adv();
                    if (ch < 3 && t == 0) cur.adv();
                    if constexpr (ch == 1) { if (t == 0 && (w | v)) load_wchunk(IC<3>{}); }
                    if (ch < 2 && t == 0) token_wait(w);
                };
                chunk(IC<0>{}); chunk(IC<1>{}); chunk(IC<2>{}); chunk(IC<3>{});
                wg_wait<0>();
                release(c, BAR_EMPTY + 8 * last, 1);
                PROF_EV(11);
                fence_regs(acc);
                tile_out(out, (rank ? g_V : g_K) + (size_t)(team * 32 + 2 * (kv_tile(t) + k)) * 16384, 64 * w, rank, c);
                if (DEFER && t == 3 && w) break;
#pragma unroll
                for (int i = 0; i < 4; i++) store_pair(acc, i, out, 8192, inv);
                if (t >= 2) signal_event(c, EV_KV + 2 * v + t - 2);
            }
            PROF_EV(61); PROF_GT(62);
        }
        PROF_EV(63); PROF_GT(64);
        {
            uint32_t q[32], p[32];
            float m[2], l[2];
#pragma unroll
            for (int i = 0; i < 32; i++) p[i] = 0u;
            l[0] = l[1] = 1.f;
            int pv_acc = 1, pv_mode = 2;
#pragma unroll 1
            for (int r = 0; r < 2; r++) {
                const int heavy = 1 ^ r ^ w;
                const int half = 1 ^ heavy ^ rank ^ (r & SWAPT);
                int left = 2 * (r ? b1 : b0) + 1 + heavy;
                Cur ck, cv = cur;
                {
                    float s[64];
                    if (r) cur.adv();
                    mbar_wait_hot(misc + BAR_FULL + 8 * cv.slot, cv.ph);
                    token_wait(w);
                    PROF_EV(20);
                    issue_pv(o, p, ring + cv.slot * SLOT_BYTES, pv_acc, pv_mode);
                    undef_regs(s);
                    uint32_t prev;
                    auto qchunk = [&](int acc) {
                        mbar_wait_hot(misc + BAR_FULL + 8 * cur.slot, cur.ph);
                        const uint64_t da = mkdesc(ring + cur.slot * SLOT_BYTES + w * 8192, 16, 1024, 1);
                        const uint64_t db = mkdesc(ring + cur.slot * SLOT_BYTES + 16384, 8192, 1024, 1);
                        wg_fence();
#pragma unroll
                        for (int ks = 0; ks < 4; ks++) wgmma_ss_n128_ta0_tb1(s, da + 2 * ks, db + 128 * ks, ks ? 1 : acc);
                        wg_commit();
                    };
                    qchunk(0);
                    prev = cur.slot; cur.adv();
                    token_pass(w);
                    if (r) {
                        row_inv(l, inv);
                        tile_out(out, g_ctx + (size_t)((team + 16 * v) * 32 + 4 * b0 + (w ? rank : 3 - rank)) * 16384, 0, 0, c);
                    }
                    const int epi = r | (w & DEFER), hs = r ? 4096 : 8192;
                    const int hold = heavy ? -10 : half ? HOLD0 : 8;
#pragma unroll
                    for (int kc = 1; kc < 10; kc++) {
                        if (HOLD0 && kc >= HOLD0 && (kc == hold || kc == hold + 2)) token_wait(w);
                        qchunk(1);
                        if (HOLD0 && kc > HOLD0 && kc == hold + 1) token_pass(w);
                        if (HOLD0 && kc == 9 && heavy) { token_wait(w); token_pass(w); }
                        wg_wait<1>();
                        release(c, BAR_EMPTY + 8 * prev, 1);
                        prev = cur.slot; cur.adv();
                        if (kc == 1) { fence_regs(o); if (r) release(c, BAR_EMPTY + 8 * cv.slot, 1); }
                        if (kc <= 4 && epi) {
                            store_pair(o, kc - 1, out, hs, inv);
                            if (kc == 4) signal_event(c, r ? EV_CTX + 2 * v : EV_KV + 2 * v + 1);
                        }
                    }
                    if (!heavy) cur.adv();
                    ck = cur;
                    cur.adv();
                    if (!heavy) cur.adv();
                    wg_wait<0>();
                    release(c, BAR_EMPTY + 8 * prev, 1);
                    PROF_EV(21);
                    fence_regs(s);
#pragma unroll
                    for (int i = 0; i < 32; i++) q[i] = pack_bf16(s[2 * i], s[2 * i + 1]);
                }
                cv = ck;
                int first = 1, gen = 0;
                uint32_t pv_cnt = 0;
                pv_acc = 0; pv_mode = 2;
                l[0] = l[1] = m[0] = m[1] = 0.f;
                mbar_wait_hot(misc + BAR_FULL + 8 * ck.slot, ck.ph);
#pragma unroll 1
                while (true) {
                    float s[64];
                    if (half & first) {
                        if (heavy || HOLD0 == 0 || HOLD0 == 8) token_wait(w);
                        PROF_EV(30);
                        float sh[32];
                        undef_regs(sh);
                        issue_qk_half(sh, q, ring + ck.slot * SLOT_BYTES);
                        token_pass(w);
                        --left;
                        wg_wait<0>();
                        PROF_EV(34);
                        fence_regs(sh);
                        mask_diag<0>(sh, c);
                        float l0 = 0.f, l1 = 0.f;
#pragma unroll
                        for (int j = 0; j < 8; j++) {
#pragma unroll
                            for (int e = 0; e < 4; e++) ex2v(sh[4 * j + e]);
                            l0 += sh[4 * j] + sh[4 * j + 1]; l1 += sh[4 * j + 2] + sh[4 * j + 3];
                        }
#pragma unroll
                        for (int i = 0; i < 16; i++) p[i] = pack_bf16(sh[2 * i], sh[2 * i + 1]);
                        const int lim = mask_lim(c);
                        if (__any_sync(0xffffffffu, !(l0 <= SAFE_SUM && l1 <= SAFE_SUM && (l0 >= 1.0f / SAFE_SUM || lim < 0) &&
                                                      (l1 >= 1.0f / SAFE_SUM || lim < -2)))) goto redo;
                        l[0] = l0; l[1] = l1;
                        goto tail;
                    }
#pragma unroll 1
                    while (true) {
                        token_wait(w);
                        PROF_EV(first ? 30 : 31);
                        undef_regs(s);
                        issue_qk(s, q, ring + ck.slot * SLOT_BYTES);
                        Cur nck = cur, ncv = cur, ncur;
                        ncv.adv(); ncur = ncv; ncur.adv();
                        --left;
                        mbar_wait_hot(misc + BAR_FULL + 8 * cv.slot, cv.ph);
                        issue_pv(o, p, ring + cv.slot * SLOT_BYTES, pv_acc, pv_mode);
                        token_pass(w);
                        wg_wait<1>();
                        PROF_EV(33);
                        fence_regs(s);
                        float lo = 0.f;
                        if (first) {
                            lo = 1.0f / SAFE_SUM;
                            mask_diag<8>(s, c);
                        }
                        constexpr int JB = 11;
                        float l0 = l[0], l1 = l[1];
                        if (!gen) {
#pragma unroll
                            for (int j = 0; j < JB; j++) {
#pragma unroll
                                for (int e = 0; e < 4; e++) ex2v(s[4 * j + e]);
                                if (j < JB - 1) { l0 += s[4 * j] + s[4 * j + 1]; l1 += s[4 * j + 2] + s[4 * j + 3]; }
                            }
                        }
                        wg_wait<0>();
                        fence_regs(o);
                        if (gen) goto general;
#pragma unroll
                        for (int j = JB - 1; j < 16; j++) {
                            if (j >= JB) {
#pragma unroll
                                for (int e = 0; e < 4; e++) ex2v(s[4 * j + e]);
                            }
                            l0 += s[4 * j] + s[4 * j + 1]; l1 += s[4 * j + 2] + s[4 * j + 3];
                        }
#pragma unroll
                        for (int i = 0; i < 32; i++) p[i] = pack_bf16(s[2 * i], s[2 * i + 1]);
                        if (__any_sync(0xffffffffu, !(l0 <= SAFE_SUM && l1 <= SAFE_SUM && l0 >= lo && l1 >= lo))) goto redo;
                        l[0] = l0; l[1] = l1;
                        if (left == 0) goto tail;
                        release(c, BAR_EMPTY + 8 * ck.slot, 1 + (first & heavy));
                        if (pv_cnt) release(c, BAR_EMPTY + 8 * cv.slot, pv_cnt);
                        pv_acc = first ^ 1; pv_mode = 0; pv_cnt = 1 + (first & heavy); first = 0;
                        ck = nck; cv = ncv; cur = ncur;
                        mbar_wait_hot(misc + BAR_FULL + 8 * ck.slot, ck.ph);
                    }
                redo:
                    recompute_scores(s, q, ring + ck.slot * SLOT_BYTES, c);
                    if (first) { mask_any(s, half ^ 1, c); m[0] = m[1] = -INFINITY; }
                    gen = 1;
                general:
                    {
                        float mx[2], alpha[2];
                        row_max<16>(s, mx);
#pragma unroll
                        for (int i = 0; i < 2; i++) {
                            mx[i] = fmaxf(mx[i], m[i]);
                            alpha[i] = ex2(m[i] - mx[i]);
                            m[i] = mx[i];
                            l[i] *= alpha[i];
                        }
                        exp_sum<16, true>(s, m, l[0], l[1]);
#pragma unroll
                        for (int i = 0; i < 64; i++) o[i] *= alpha[(i >> 1) & 1];
#pragma unroll
                        for (int i = 0; i < 32; i++) p[i] = pack_bf16(s[2 * i], s[2 * i + 1]);
                    }
                tail:
                    release(c, BAR_EMPTY + 8 * ck.slot, 1 + (first & heavy));
                    if (pv_cnt) release(c, BAR_EMPTY + 8 * cv.slot, pv_cnt);
                    pv_acc = first ^ 1; pv_mode = first & half; pv_cnt = 1 + (first & heavy); first = 0;
                    if (left == 0) break;
                    ck = cur; cur.adv(); cv = cur; cur.adv();
                    mbar_wait_hot(misc + BAR_FULL + 8 * ck.slot, ck.ph);
                }
            }
            mbar_wait_hot(misc + BAR_FULL + 8 * cur.slot, cur.ph);
            token_wait(w);
            PROF_EV(32);
            issue_pv(o, p, ring + cur.slot * SLOT_BYTES, 1, 0);
            if (w == 0 || v == 0) token_pass(w);
            const uint32_t vslot = cur.slot;
            cur.adv();
            if (v) {
                row_inv(l, inv);
                wg_wait<0>();
                release(c, BAR_EMPTY + 8 * vslot, 1);
                fence_regs(o);
                tile_out(out, g_ctx + (size_t)((team + 16) * 32 + 4 * b1 + (w ? 3 - (rank ^ SWAPT) : rank ^ SWAPT)) * 16384, 0, 0, c);
#pragma unroll
                for (int i = 0; i < 64; i++) wf[i] = 0u;
                continue;
            }
            cw = cur_at(80);
            mbar_wait_hot(misc + BAR_FULL + 8 * slot_of(76), cur_at(76).ph);
            mbar_wait_hot(misc + BAR_FULL + 8 * slot_of(78), cur_at(78).ph);
            load_afrag<8, 32>(wf, ring + slot_of(78) * SLOT_BYTES + w * 16384, c);
            const uint32_t z = load_afrag<8, 0>(wf, ring + slot_of(76) * SLOT_BYTES + w * 16384, c);
            row_inv(l, inv);
            release(c, BAR_EMPTY + 8 * slot_of(76) + z, 1);
            asm volatile("{\n.reg .pred p;\nsetp.eq.u32 p, %0, 0;\n@p bar.sync 4, 128;\n@!p bar.sync 5, 128;\n}\n" ::"r"(w) : "memory");
            wg_wait<0>();
            release(c, BAR_EMPTY + 8 * vslot, 1);
            fence_regs(o);
            {
                const uint32_t base = ring + slot_of(78) * SLOT_BYTES + w * 16384 + (16 * c.warp + (c.lane >> 2)) * 64 + (((c.lane ^ (c.lane >> 3)) & 3) << 4);
#pragma unroll
                for (int i = 0; i < 2; i++)
#pragma unroll
                    for (int qq = 0; qq < 4; qq++)
                        asm volatile("st.shared.v4.b32 [%0], {%1,%2,%3,%4};" ::"r"(base + qq * 4096 + i * 512),
                                     "r"(pack_bf16(o[16 * qq + 2 * i] * inv[i], o[16 * qq + 2 * i + 1] * inv[i])),
                                     "r"(pack_bf16(o[16 * qq + 4 + 2 * i] * inv[i], o[16 * qq + 4 + 2 * i + 1] * inv[i])),
                                     "r"(pack_bf16(o[16 * qq + 8 + 2 * i] * inv[i], o[16 * qq + 8 + 2 * i + 1] * inv[i])),
                                     "r"(pack_bf16(o[16 * qq + 12 + 2 * i] * inv[i], o[16 * qq + 12 + 2 * i + 1] * inv[i])) : "memory");
                asm volatile("fence.proxy.async.shared::cta;" ::: "memory");
                signal_event(c, EV_CTX + 1);
            }
        }
        }
        {
            float acc[80];
            undef_regs(acc);
            int st = 0, prev = 0; uint32_t ph3 = 0;
            auto op_stage = [&](int i) {
                mbar_wait_hot(misc + BAR_FULL3 + 8 * st, ph3);
                PROF_EV(44);
                uint32_t base = ring + st * ST3_BYTES;
                uint64_t da = mkdesc(base + w * 8192, 16, 512, 2);
                uint64_t db = mkdesc(base + 16384, 2048, 512, 2);
                wg_fence();
#pragma unroll
                for (int k = 0; k < 4; k++) wgmma_ss_n160_ta0_tb1(acc, da + (k >> 1) * 256 + 2 * (k & 1), db + (k >> 1) * 640 + (k & 1) * 64, k ? 1 : i);
                wg_commit();
                if (i > 0) { wg_wait<1>(); if (i <= 32 - NST3) release(c, BAR_EMPTY3 + 8 * prev, 1); }
                prev = st;
                if (++st == NST3) { st = 0; ph3 ^= 1; }
            };
            PROF_EV(40); PROF_GT(65);
#pragma unroll
            for (int i = 0; i < 4; i++) { op_stage(i); store_pair(o, i, out, 4096, inv); }
            signal_event(c, EV_CTX + 3);
            const int split = RES_AT + 3 * w;
#pragma unroll 1
            for (int i = 4; i < split; i++) op_stage(i);
            mbar_wait(misc + BAR_SEL, 0);
            const uint32_t tag = lds32(misc + MISC_EPOCH) & 1;
            const int g = c.lane >> 2, t = c.lane & 3;
            const int row = (2 * u3 + rank) * 128 + 64 * w + perm32(16 * c.warp + 8 * kap + g);
            const int col = 160 * s3 + 8 * t;
            int sel = -1;
#pragma unroll
            for (int i = 0; i < TOPC; i++) if ((int)lds32(misc + MISC_SEL + 4 * i) == row) sel = i;
            const int t256 = tid - 128;
            uint4* sendp = g_part + (size_t)cta * 2560 + t256;
            if (c.lane >= 30) stg128(sendp + 9 * 256, tag ^ 1, tag ^ 1, tag ^ 1, tag ^ 1);
            uint4 xv[5], bv[5];
#pragma unroll
            for (int i = 0; i < 5; i++) xv[i] = ldg128(P.x + (size_t)row * DM + col + 32 * i);
            uint2 stat;
            asm volatile("ld.global.cg.v2.b32 {%0,%1}, [%2];" : "=r"(stat.x), "=r"(stat.y) : "l"(g_stats + row) : "memory");
#pragma unroll
            for (int i = 0; i < 5; i++) {
                uint32_t xx[4] = {xv[i].x, xv[i].y, xv[i].z, xv[i].w};
#pragma unroll
                for (int e = 0; e < 4; e++) {
                    asm("sub.rn.bf16x2 %0, %0, %1;" : "+r"(xx[e]) : "r"(stat.x));
                    xx[e] = pack_bf16(bf_lo(xx[e]) * __uint_as_float(stat.y), bf_hi(xx[e]) * __uint_as_float(stat.y));
                }
                bv[i] = make_uint4(xx[0], xx[1], xx[2], xx[3]);
            }
            if (sel >= 0) {
#pragma unroll
                for (int i = 0; i < 5; i++) bv[i] = ldg128(g_brow + sel * DM + col + 32 * i);
            }
#pragma unroll
            for (int i = 0; i < 5; i++) asm volatile("" : "+r"(bv[i].x), "+r"(bv[i].y), "+r"(bv[i].z), "+r"(bv[i].w));
#pragma unroll 1
            for (int i = split; i < 32; i++) op_stage(i);
            wg_wait<0>();
            fence_regs(acc);
            PROF_EV(41); PROF_GT(66);
            float keep[40];
#pragma unroll
            for (int j = 0; j < 10; j++) {
                uint32_t v0 = __float_as_uint(kap ? acc[8 * j + 0] : acc[8 * j + 2]), v1 = __float_as_uint(kap ? acc[8 * j + 1] : acc[8 * j + 3]);
                uint32_t v2 = __float_as_uint(kap ? acc[8 * j + 4] : acc[8 * j + 6]), v3 = __float_as_uint(kap ? acc[8 * j + 5] : acc[8 * j + 7]);
                asm volatile("st.relaxed.gpu.global.v4.b32 [%0], {%1,%2,%3,%4};" ::"l"(sendp + j * 256),
                             "r"((v0 & ~1u) | tag), "r"((v1 & ~1u) | tag), "r"((v2 & ~1u) | tag), "r"((v3 & ~1u) | tag) : "memory");
                keep[4 * j + 0] = kap ? acc[8 * j + 2] : acc[8 * j + 0]; keep[4 * j + 1] = kap ? acc[8 * j + 3] : acc[8 * j + 1];
                keep[4 * j + 2] = kap ? acc[8 * j + 6] : acc[8 * j + 4]; keep[4 * j + 3] = kap ? acc[8 * j + 7] : acc[8 * j + 5];
            }
            PROF_GT(67);
            signal_event(c, EV_END);
            const uint4* recvp = g_part + (size_t)partner * 2560 + t256;
            uint4 rv[10];
            int spins = 0;
            while (true) {
                uint32_t v;
                asm volatile("ld.relaxed.gpu.global.b32 %0, [%1];" : "=r"(v) : "l"(recvp + 9 * 256 + (31 - c.lane)) : "memory");
                if (__all_sync(0xffffffffu, (v & 1u) == tag) || ++spins > 2000000) break;
            }
            PROF_GT(68);
            while (true) {
                uint32_t bad = 0u;
#pragma unroll
                for (int j = 0; j < 10; j++) {
                    asm volatile("ld.relaxed.gpu.global.v4.b32 {%0,%1,%2,%3}, [%4];"
                                 : "=r"(rv[j].x), "=r"(rv[j].y), "=r"(rv[j].z), "=r"(rv[j].w) : "l"(recvp + j * 256) : "memory");
                }
#pragma unroll
                for (int j = 0; j < 10; j++) {
                    rv[j].x ^= tag; rv[j].y ^= tag; rv[j].z ^= tag; rv[j].w ^= tag;
                    bad |= rv[j].x | rv[j].y | rv[j].z | rv[j].w;
                }
                if (__all_sync(0xffffffffu, (bad & 1u) == 0) || ++spins > 2000000) break;
            }
            PROF_GT(69);
            uint32_t pk[20];
#pragma unroll
            for (int j = 0; j < 10; j++) {
                pk[2 * j] = pack_bf16(keep[4 * j] + __uint_as_float(rv[j].x), keep[4 * j + 1] + __uint_as_float(rv[j].y));
                pk[2 * j + 1] = pack_bf16(keep[4 * j + 2] + __uint_as_float(rv[j].z), keep[4 * j + 3] + __uint_as_float(rv[j].w));
            }
#pragma unroll
            for (int i = 0; i < 5; i++) {
                uint32_t a0 = pk[4 * i], a1 = pk[4 * i + 1], a2 = pk[4 * i + 2], a3 = pk[4 * i + 3];
                uint32_t x0 = (t & 1) ? a0 : a1, x1 = (t & 1) ? a2 : a3;
                x0 = __shfl_xor_sync(0xffffffffu, x0, 1); x1 = __shfl_xor_sync(0xffffffffu, x1, 1);
                if (t & 1) { a0 = x0; a2 = x1; } else { a1 = x0; a3 = x1; }
                x0 = (t & 2) ? a0 : a2; x1 = (t & 2) ? a1 : a3;
                x0 = __shfl_xor_sync(0xffffffffu, x0, 2); x1 = __shfl_xor_sync(0xffffffffu, x1, 2);
                if (t & 2) { a0 = x0; a1 = x1; } else { a2 = x0; a3 = x1; }
                uint32_t av[4] = {a0, a1, a2, a3};
                uint32_t xx[4] = {xv[i].x, xv[i].y, xv[i].z, xv[i].w}, bb[4] = {bv[i].x, bv[i].y, bv[i].z, bv[i].w};
                uint32_t ov[4];
#pragma unroll
                for (int e = 0; e < 4; e++) {
                    asm("add.rn.bf16x2 %0, %1, %2;" : "=r"(ov[e]) : "r"(xx[e]), "r"(av[e]));
                    asm("add.rn.bf16x2 %0, %0, %1;" : "+r"(ov[e]) : "r"(bb[e]));
                }
                stg128(P.out + (size_t)row * DM + col + 32 * i, ov[0], ov[1], ov[2], ov[3]);
            }
            PROF_EV(42); PROF_GT(43);
        }
    }
}

typedef CUresult (*EncodeFn)(CUtensorMap*, CUtensorMapDataType, cuuint32_t, void*, const cuuint64_t*, const cuuint64_t*, const cuuint32_t*,
                             const cuuint32_t*, CUtensorMapInterleave, CUtensorMapSwizzle, CUtensorMapL2promotion, CUtensorMapFloatOOBfill);

void make_map2d(EncodeFn enc, CUtensorMap* tm, const void* p, uint64_t cols, uint64_t rows, uint32_t box_rows = 128) {
    cuuint64_t gd[2] = {cols, rows}, gs[1] = {cols * 2};
    cuuint32_t box[2] = {64, box_rows}, es[2] = {1, 1};
    enc(tm, CU_TENSOR_MAP_DATA_TYPE_BFLOAT16, 2, const_cast<void*>(p), gd, gs, box, es, CU_TENSOR_MAP_INTERLEAVE_NONE,
        CU_TENSOR_MAP_SWIZZLE_128B, CU_TENSOR_MAP_L2_PROMOTION_L2_128B, CU_TENSOR_MAP_FLOAT_OOB_FILL_NONE);
}

void make_map3d(EncodeFn enc, CUtensorMap* tm, const void* p, uint64_t cols, uint64_t rows, uint32_t bw, uint32_t nb) {
    cuuint64_t gd[3] = {bw, rows, cols / bw}, gs[2] = {cols * 2, bw * 2};
    cuuint32_t box[3] = {bw, 32, nb}, es[3] = {1, 1, 1};
    enc(tm, CU_TENSOR_MAP_DATA_TYPE_BFLOAT16, 3, const_cast<void*>(p), gd, gs, box, es, CU_TENSOR_MAP_INTERLEAVE_NONE,
        bw == 64 ? CU_TENSOR_MAP_SWIZZLE_128B : CU_TENSOR_MAP_SWIZZLE_64B, CU_TENSOR_MAP_L2_PROMOTION_L2_128B, CU_TENSOR_MAP_FLOAT_OOB_FILL_NONE);
}

}

extern "C" void kernel_launch(void* const* d_in, const int* in_sizes, int n_in, void* d_out, int out_size) {
    (void)in_sizes; (void)n_in; (void)out_size;
    static EncodeFn enc = nullptr;
    if (!enc) {
        void* fn = nullptr;
        cudaDriverEntryPointQueryResult qr;
        cudaGetDriverEntryPoint("cuTensorMapEncodeTiled", &fn, cudaEnableDefault, &qr);
        enc = (EncodeFn)fn;
        cudaFuncSetAttribute(fused_kernel, cudaFuncAttributeMaxDynamicSharedMemorySize, SMEM_BYTES);
    }
    CUtensorMap tmC, tmWk, tmWv, tmWq, tmWo, tmG, tmU, tmD;
    make_map2d(enc, &tmC, d_in[1], DC, SEQ);
    make_map2d(enc, &tmWq, d_in[2], 4096, DM, 64);
    make_map2d(enc, &tmWk, d_in[3], 4096, DC);
    make_map2d(enc, &tmWv, d_in[4], 4096, DC);
    make_map3d(enc, &tmWo, d_in[5], DM, 4096, 32, 5);
    make_map3d(enc, &tmG, d_in[8], FF, DM, 64, 7);
    make_map3d(enc, &tmU, d_in[9], FF, DM, 64, 7);
    make_map3d(enc, &tmD, d_in[10], DM, FF, 64, 10);
    Params P;
    P.x = (const __nv_bfloat16*)d_in[0];
    P.c = (const __nv_bfloat16*)d_in[1];
    P.wk = (const __nv_bfloat16*)d_in[3];
    P.wv = (const __nv_bfloat16*)d_in[4];
    P.wo = (const __nv_bfloat16*)d_in[5];
    P.wr = (const __nv_bfloat16*)d_in[7];
    P.out = (__nv_bfloat16*)d_out;
    fused_kernel<<<132, 384, SMEM_BYTES>>>(tmC, tmWk, tmWv, tmWq, tmWo, tmG, tmU, tmD, P);
}
```

```cpp
#include <cuda_runtime.h>
#include <cuda_bf16.h>
#include <cuda.h>
#include <stdint.h>

namespace {

constexpr int SEQ = 2048, NH = 32, DM = 640, DC = 512, FF = 1728, TOPC = 8;
constexpr int NSLOT = 7, SLOT_BYTES = 32768;
constexpr int NST3 = 6, ST3_BYTES = 36864;
constexpr int RING_BYTES = NSLOT * SLOT_BYTES;
constexpr int SMEM_BYTES = RING_BYTES + 3072;
constexpr int OP_PF = 8, PF_START = 9, LATE_AT = 18, RES_AT = 23, OP_HOLD = 4;

constexpr int BAR_FULL = 0  , BAR_EMPTY = 64  , BAR_FULL3 = 128  , BAR_EMPTY3 = 192  , BAR_DEP = 256  ,
              BAR_EV = 448  , BAR_PROG = 592  , BAR_SEL = 616, BAR_LN = 624,
              MISC_EPOCH = 640, MISC_SMID = 644  , MISC_SEL = 656, MISC_WR = 1024  ;
constexpr int D_LN = 0  , D_KV = 2  , D_WAR = 6  , D_CTX = 8  ;
constexpr int EV_KV = 0  , EV_CTX = 4  , EV_END = 8, NEV = 9;

constexpr int FL_MOE_CNT = 0, FL_MOE_DONE = 1, FL_LN = 16  , FL_KV = 32  , FL_CTX = 160  , FL_WAR = 416  , FL_TOTAL = 448;

__device__ __align__(1024) unsigned char g_K[16 * 32 * 16384];
__device__ __align__(1024) unsigned char g_V[16 * 32 * 16384];
__device__ __align__(1024) unsigned char g_ctx[NH * 32 * 16384];
__device__ __align__(1024) unsigned char g_xn[16 * 10 * 16384];
__device__ __align__(1024) uint4 g_part[128 * 10 * 256];
__device__ float g_router[SEQ];
__device__ uint2 g_stats[SEQ];
__device__ __align__(16) float g_moe_part[4 * TOPC * DM];
__device__ __align__(16) __nv_bfloat16 g_brow[TOPC * DM];
__device__ __align__(16) int g_sel[TOPC];
__device__ unsigned g_flags[FL_TOTAL * 8];
__device__ unsigned g_epoch;
__device__ unsigned g_roleq[130];
struct Params {
    const __nv_bfloat16 *x, *c, *wr, *wk, *wv, *wo;
    __nv_bfloat16* out;
};

__device__ __forceinline__ uint32_t smem_u32(const void* p) { return (uint32_t)__cvta_generic_to_shared(p); }
__device__ __forceinline__ void mbar_init(uint32_t bar, int cnt) { asm volatile("mbarrier.init.shared::cta.b64 [%0], %1;" ::"r"(bar), "r"(cnt)); }
__device__ __forceinline__ void mbar_expect_tx(uint32_t bar, uint32_t bytes) {
    asm volatile("mbarrier.arrive.expect_tx.shared::cta.b64 _, [%0], %1;" ::"r"(bar), "r"(bytes) : "memory");
}
__device__ __forceinline__ void mbar_arrive(uint32_t bar) { asm volatile("mbarrier.arrive.shared::cta.b64 _, [%0];" ::"r"(bar) : "memory"); }
__device__ __forceinline__ void mbar_arrive_cluster(uint32_t cluster_addr, uint32_t cnt) {
    asm volatile("mbarrier.arrive.shared::cluster.b64 _, [%0], %1;" ::"r"(cluster_addr), "r"(cnt) : "memory");
}
__device__ __forceinline__ uint32_t mapa(uint32_t addr, uint32_t cta) {
    uint32_t r; asm("mapa.shared::cluster.u32 %0, %1, %2;" : "=r"(r) : "r"(addr), "r"(cta)); return r;
}
__device__ __forceinline__ void mbar_wait(uint32_t bar, uint32_t parity) {
    asm volatile(
        "{\n.reg .pred p;\n.reg .u32 n;\n"
        "mov.u32 n, 0;\n"
        "LAB_WAIT:\n"
        "mbarrier.try_wait.parity.shared::cta.b64 p, [%0], %1, 100000;\n"
        "@p bra DONE;\n"
        "add.u32 n, n, 1;\n"
        "setp.lt.u32 p, n, 50000;\n"
        "@p bra LAB_WAIT;\n"
        "trap;\n"
        "DONE:\n}\n" ::"r"(bar), "r"(parity) : "memory");
}
__device__ __forceinline__ void mbar_wait_hot(uint32_t bar, uint32_t parity) {
    asm volatile("{\n.reg .pred p;\nLAB_WAIT:\nmbarrier.try_wait.parity.shared::cta.b64 p, [%0], %1;\n@!p bra LAB_WAIT;\n}\n" ::"r"(bar), "r"(parity) : "memory");
}
__device__ __forceinline__ void mbar_wait_sleep(uint32_t bar, uint32_t parity) {
    asm volatile("{\n.reg .pred p;\nLAB_WAIT:\nmbarrier.try_wait.parity.shared::cta.b64 p, [%0], %1, 100000;\n@!p bra LAB_WAIT;\n}\n" ::"r"(bar), "r"(parity) : "memory");
}
__device__ __forceinline__ void flag_wait(const unsigned* flag, unsigned target) {
    asm volatile(
        "{\n.reg .pred p;\n.reg .u32 n, v;\n.reg .s32 d;\n"
        "mov.u32 n, 0;\n"
        "LAB_WAIT:\n"
        "ld.acquire.gpu.global.u32 v, [%0];\n"
        "sub.s32 d, v, %1;\n"
        "setp.ge.s32 p, d, 0;\n"
        "@p bra DONE;\n"
        "nanosleep.u32 40;\n"
        "add.u32 n, n, 1;\n"
        "setp.lt.u32 p, n, 3000000;\n"
        "@p bra LAB_WAIT;\n"
        "trap;\n"
        "DONE:\n}\n" ::"l"(flag), "r"(target) : "memory");
}
__device__ __forceinline__ void flag_signal(unsigned* flag) {
    asm volatile("red.release.gpu.global.add.u32 [%0], 1;" ::"l"(flag) : "memory");
}
__device__ __forceinline__ void fence_async_global() { asm volatile("fence.proxy.async.global;" ::: "memory"); }
__device__ __forceinline__ unsigned* flag_ptr(int idx) { return g_flags + idx * 8; }

__device__ __forceinline__ uint64_t policy_stream() {
    uint64_t p; asm("createpolicy.fractional.L2::evict_first.b64 %0, 1.0;" : "=l"(p)); return p;
}
__device__ __forceinline__ void bulk_load(uint32_t dst, const void* src, uint32_t bytes, uint32_t bar) {
    asm volatile("cp.async.bulk.shared::cluster.global.mbarrier::complete_tx::bytes [%0], [%1], %2, [%3];"
                 ::"r"(dst), "l"(src), "r"(bytes), "r"(bar) : "memory");
}
__device__ __forceinline__ void bulk_load_mc(uint32_t dst, const void* src, uint32_t bytes, uint32_t bar) {
    asm volatile("cp.async.bulk.shared::cluster.global.mbarrier::complete_tx::bytes.multicast::cluster [%0], [%1], %2, [%3], %4;"
                 ::"r"(dst), "l"(src), "r"(bytes), "r"(bar), "h"((uint16_t)3) : "memory");
}
__device__ __forceinline__ void tma2d(uint32_t dst, const CUtensorMap* tm, int c0, int c1, uint32_t bar) {
    asm volatile("cp.async.bulk.tensor.2d.shared::cluster.global.mbarrier::complete_tx::bytes [%0], [%1, {%3, %4}], [%2];"
                 ::"r"(dst), "l"(tm), "r"(bar), "r"(c0), "r"(c1) : "memory");
}
__device__ __forceinline__ void tma2d_mc(uint32_t dst, const CUtensorMap* tm, int c0, int c1, uint32_t bar) {
    asm volatile("cp.async.bulk.tensor.2d.shared::cluster.global.mbarrier::complete_tx::bytes.multicast::cluster [%0], [%1, {%3, %4}], [%2], %5;"
                 ::"r"(dst), "l"(tm), "r"(bar), "r"(c0), "r"(c1), "h"((uint16_t)3) : "memory");
}
__device__ __forceinline__ void tma3d_mc(uint32_t dst, const CUtensorMap* tm, int c0, int c1, int c2, uint32_t bar) {
    asm volatile("cp.async.bulk.tensor.3d.shared::cluster.global.mbarrier::complete_tx::bytes.multicast::cluster [%0], [%1, {%3, %4, %5}], [%2], %6;"
                 ::"r"(dst), "l"(tm), "r"(bar), "r"(c0), "r"(c1), "r"(c2), "h"((uint16_t)3) : "memory");
}
__device__ __forceinline__ void tma3d(uint32_t dst, const CUtensorMap* tm, int c0, int c1, int c2, uint32_t bar) {
    asm volatile("cp.async.bulk.tensor.3d.shared::cluster.global.mbarrier::complete_tx::bytes.L2::cache_hint [%0], [%1, {%3, %4, %5}], [%2], %6;"
                 ::"r"(dst), "l"(tm), "r"(bar), "r"(c0), "r"(c1), "r"(c2), "l"(policy_stream()) : "memory");
}
__device__ __forceinline__ void tma2d_prefetch(const CUtensorMap* tm, int c0, int c1) {
    asm volatile("cp.async.bulk.prefetch.tensor.2d.L2.global [%0, {%1, %2}];" ::"l"(tm), "r"(c0), "r"(c1) : "memory");
}
__device__ __forceinline__ void tma3d_prefetch(const CUtensorMap* tm, int c0, int c1, int c2) {
    asm volatile("cp.async.bulk.prefetch.tensor.3d.L2.global [%0, {%1, %2, %3}];" ::"l"(tm), "r"(c0), "r"(c1), "r"(c2) : "memory");
}
__device__ __forceinline__ void l2_prefetch(const void* p, uint32_t bytes) {
    asm volatile("cp.async.bulk.prefetch.L2.global [%0], %1;" ::"l"(p), "r"(bytes) : "memory");
}
__device__ __forceinline__ bool elect_one() {
    uint32_t r; asm volatile("{\n.reg .pred p;\nelect.sync _|p, 0xffffffff;\nselp.u32 %0, 1, 0, p;\n}\n" : "=r"(r)); return r != 0;
}
__device__ __forceinline__ void wg_fence() { asm volatile("wgmma.fence.sync.aligned;" ::: "memory"); }
__device__ __forceinline__ void wg_commit() { asm volatile("wgmma.commit_group.sync.aligned;" ::: "memory"); }
template <int N> __device__ __forceinline__ void wg_wait() { asm volatile("wgmma.wait_group.sync.aligned %0;" ::"n"(N) : "memory"); }
__device__ __forceinline__ void bar_sync(int id, int n) { asm volatile("bar.sync %0, %1;" ::"r"(id), "r"(n) : "memory"); }
__device__ __forceinline__ void bar_arrive(int id, int n) { asm volatile("bar.arrive %0, %1;" ::"r"(id), "r"(n) : "memory"); }
__device__ __forceinline__ void token_wait(int w) {
    asm volatile("{\n.reg .pred p;\nsetp.eq.u32 p, %0, 0;\n@p bar.sync 1, 256;\n@!p bar.sync 2, 256;\n}\n" ::"r"(w) : "memory");
}
__device__ __forceinline__ void token_pass(int w) {
    asm volatile("{\n.reg .pred p;\nsetp.eq.u32 p, %0, 0;\n@p bar.arrive 2, 256;\n@!p bar.arrive 1, 256;\n}\n" ::"r"(w) : "memory");
}
template <int N> __device__ __forceinline__ void fence_regs(float (&a)[N]) {
#pragma unroll
    for (int i = 0; i < N; i++) asm volatile("" : "+f"(a[i])::"memory");
}
template <int N> __device__ __forceinline__ void undef_regs(float (&a)[N]) {
#pragma unroll
    for (int i = 0; i < N; i++) asm volatile("" : "=f"(a[i]));
}
__device__ __forceinline__ void ldsm4t(uint32_t& r0, uint32_t& r1, uint32_t& r2, uint32_t& r3, uint32_t addr) {
    asm volatile("ldmatrix.sync.aligned.m8n8.x4.trans.shared.b16 {%0,%1,%2,%3}, [%4];"
                 : "=r"(r0), "=r"(r1), "=r"(r2), "=r"(r3) : "r"(addr) : "memory");
}
__device__ __forceinline__ uint32_t pack_bf16(float lo, float hi) {
    uint32_t r; asm("cvt.rn.bf16x2.f32 %0, %1, %2;" : "=r"(r) : "f"(hi), "f"(lo)); return r;
}
__device__ __forceinline__ float bf_lo(uint32_t v) { return __uint_as_float(v << 16); }
__device__ __forceinline__ float bf_hi(uint32_t v) { return __uint_as_float(v & 0xffff0000u); }
__device__ __forceinline__ float bf_round(float v) { return __bfloat162float(__float2bfloat16_rn(v)); }
__device__ __forceinline__ float ex2(float v) { float r; asm("ex2.approx.ftz.f32 %0, %1;" : "=f"(r) : "f"(v)); return r; }
__device__ __forceinline__ void ex2v(float& v) { asm volatile("ex2.approx.ftz.f32 %0, %0;" : "+f"(v)); }
__device__ __forceinline__ float rcp_fast(float v) { float r; asm("rcp.approx.ftz.f32 %0, %1;" : "=f"(r) : "f"(v)); return r; }
__device__ __forceinline__ float sqrt_fast(float v) { float r; asm("sqrt.approx.ftz.f32 %0, %1;" : "=f"(r) : "f"(v)); return r; }
__device__ __forceinline__ void stg128(void* p, uint32_t a, uint32_t b, uint32_t c, uint32_t d) {
    asm volatile("st.global.v4.b32 [%0], {%1,%2,%3,%4};" ::"l"(p), "r"(a), "r"(b), "r"(c), "r"(d) : "memory");
}
__device__ __forceinline__ uint4 ldg128(const void* p) {
    uint4 v; asm volatile("ld.global.cg.v4.b32 {%0,%1,%2,%3}, [%4];" : "=r"(v.x), "=r"(v.y), "=r"(v.z), "=r"(v.w) : "l"(p) : "memory"); return v;
}
__device__ __forceinline__ uint64_t mkdesc(uint32_t addr, uint32_t lbo, uint32_t sbo, uint32_t swz) {
    uint32_t lo = ((addr & 0x3FFFF) >> 4) | ((lbo >> 4) << 16);
    uint32_t hi = (sbo >> 4) | (swz << 30);
    return ((uint64_t)hi << 32) | lo;
}
__device__ __forceinline__ int perm32(int v) { return (v & ~30) | ((v >> 2) & 6) | ((v << 2) & 24); }

__device__ __forceinline__ void wgmma_rs_n128_ta0_tb0(float (&d)[64], uint32_t a0, uint32_t a1, uint32_t a2, uint32_t a3, uint64_t descB, int scaleD) {
  asm volatile("{\n.reg .pred p;\nsetp.ne.b32 p, %69, 0;\n"
    "wgmma.mma_async.sync.aligned.m64n128k16.f32.bf16.bf16 "
    "{%0, %1, %2, %3, %4, %5, %6, %7, %8, %9, %10, %11, %12, %13, %14, %15, %16, %17, %18, %19, %20, %21, %22, %23, %24, %25, %26, %27, %28, %29, %30, %31, %32, %33, %34, %35, %36, %37, %38, %39, %40, %41, %42, %43, %44, %45, %46, %47, %48, %49, %50, %51, %52, %53, %54, %55, %56, %57, %58, %59, %60, %61, %62, %63}, "
    "{%64, %65, %66, %67}, %68, p, 1, 1, 0;\n}\n"
    : "+f"(d[0]), "+f"(d[1]), "+f"(d[2]), "+f"(d[3]), "+f"(d[4]), "+f"(d[5]), "+f"(d[6]), "+f"(d[7]), "+f"(d[8]), "+f"(d[9]), "+f"(d[10]), "+f"(d[11]), "+f"(d[12]), "+f"(d[13]), "+f"(d[14]), "+f"(d[15]), "+f"(d[16]), "+f"(d[17]), "+f"(d[18]), "+f"(d[19]), "+f"(d[20]), "+f"(d[21]), "+f"(d[22]), "+f"(d[23]), "+f"(d[24]), "+f"(d[25]), "+f"(d[26]), "+f"(d[27]), "+f"(d[28]), "+f"(d[29]), "+f"(d[30]), "+f"(d[31]), "+f"(d[32]), "+f"(d[33]), "+f"(d[34]), "+f"(d[35]), "+f"(d[36]), "+f"(d[37]), "+f"(d[38]), "+f"(d[39]), "+f"(d[40]), "+f"(d[41]), "+f"(d[42]), "+f"(d[43]), "+f"(d[44]), "+f"(d[45]), "+f"(d[46]), "+f"(d[47]), "+f"(d[48]), "+f"(d[49]), "+f"(d[50]), "+f"(d[51]), "+f"(d[52]), "+f"(d[53]), "+f"(d[54]), "+f"(d[55]), "+f"(d[56]), "+f"(d[57]), "+f"(d[58]), "+f"(d[59]), "+f"(d[60]), "+f"(d[61]), "+f"(d[62]), "+f"(d[63])
    : "r"(a0), "r"(a1), "r"(a2), "r"(a3), "l"(descB), "r"(scaleD));
}
__device__ __forceinline__ void wgmma_rs_n128_ta0_tb1(float (&d)[64], uint32_t a0, uint32_t a1, uint32_t a2, uint32_t a3, uint64_t descB, int scaleD) {
  asm volatile("{\n.reg .pred p;\nsetp.ne.b32 p, %69, 0;\n"
    "wgmma.mma_async.sync.aligned.m64n128k16.f32.bf16.bf16 "
    "{%0, %1, %2, %3, %4, %5, %6, %7, %8, %9, %10, %11, %12, %13, %14, %15, %16, %17, %18, %19, %20, %21, %22, %23, %24, %25, %26, %27, %28, %29, %30, %31, %32, %33, %34, %35, %36, %37, %38, %39, %40, %41, %42, %43, %44, %45, %46, %47, %48, %49, %50, %51, %52, %53, %54, %55, %56, %57, %58, %59, %60, %61, %62, %63}, "
    "{%64, %65, %66, %67}, %68, p, 1, 1, 1;\n}\n"
    : "+f"(d[0]), "+f"(d[1]), "+f"(d[2]), "+f"(d[3]), "+f"(d[4]), "+f"(d[5]), "+f"(d[6]), "+f"(d[7]), "+f"(d[8]), "+f"(d[9]), "+f"(d[10]), "+f"(d[11]), "+f"(d[12]), "+f"(d[13]), "+f"(d[14]), "+f"(d[15]), "+f"(d[16]), "+f"(d[17]), "+f"(d[18]), "+f"(d[19]), "+f"(d[20]), "+f"(d[21]), "+f"(d[22]), "+f"(d[23]), "+f"(d[24]), "+f"(d[25]), "+f"(d[26]), "+f"(d[27]), "+f"(d[28]), "+f"(d[29]), "+f"(d[30]), "+f"(d[31]), "+f"(d[32]), "+f"(d[33]), "+f"(d[34]), "+f"(d[35]), "+f"(d[36]), "+f"(d[37]), "+f"(d[38]), "+f"(d[39]), "+f"(d[40]), "+f"(d[41]), "+f"(d[42]), "+f"(d[43]), "+f"(d[44]), "+f"(d[45]), "+f"(d[46]), "+f"(d[47]), "+f"(d[48]), "+f"(d[49]), "+f"(d[50]), "+f"(d[51]), "+f"(d[52]), "+f"(d[53]), "+f"(d[54]), "+f"(d[55]), "+f"(d[56]), "+f"(d[57]), "+f"(d[58]), "+f"(d[59]), "+f"(d[60]), "+f"(d[61]), "+f"(d[62]), "+f"(d[63])
    : "r"(a0), "r"(a1), "r"(a2), "r"(a3), "l"(descB), "r"(scaleD));
}
__device__ __forceinline__ void wgmma_rs_n64_ta0_tb1(float (&d)[32], uint32_t a0, uint32_t a1, uint32_t a2, uint32_t a3, uint64_t descB, int scaleD) {
  asm volatile("{\n.reg .pred p;\nsetp.ne.b32 p, %37, 0;\n"
    "wgmma.mma_async.sync.aligned.m64n64k16.f32.bf16.bf16 "
    "{%0, %1, %2, %3, %4, %5, %6, %7, %8, %9, %10, %11, %12, %13, %14, %15, %16, %17, %18, %19, %20, %21, %22, %23, %24, %25, %26, %27, %28, %29, %30, %31}, "
    "{%32, %33, %34, %35}, %36, p, 1, 1, 1;\n}\n"
    : "+f"(d[0]), "+f"(d[1]), "+f"(d[2]), "+f"(d[3]), "+f"(d[4]), "+f"(d[5]), "+f"(d[6]), "+f"(d[7]), "+f"(d[8]), "+f"(d[9]), "+f"(d[10]), "+f"(d[11]), "+f"(d[12]), "+f"(d[13]), "+f"(d[14]), "+f"(d[15]), "+f"(d[16]), "+f"(d[17]), "+f"(d[18]), "+f"(d[19]), "+f"(d[20]), "+f"(d[21]), "+f"(d[22]), "+f"(d[23]), "+f"(d[24]), "+f"(d[25]), "+f"(d[26]), "+f"(d[27]), "+f"(d[28]), "+f"(d[29]), "+f"(d[30]), "+f"(d[31])
    : "r"(a0), "r"(a1), "r"(a2), "r"(a3), "l"(descB), "r"(scaleD));
}
__device__ __forceinline__ void wgmma_ss_n128_ta0_tb1(float (&d)[64], uint64_t descA, uint64_t descB, int scaleD) {
  asm volatile("{\n.reg .pred p;\nsetp.ne.b32 p, %66, 0;\n"
    "wgmma.mma_async.sync.aligned.m64n128k16.f32.bf16.bf16 "
    "{%0, %1, %2, %3, %4, %5, %6, %7, %8, %9, %10, %11, %12, %13, %14, %15, %16, %17, %18, %19, %20, %21, %22, %23, %24, %25, %26, %27, %28, %29, %30, %31, %32, %33, %34, %35, %36, %37, %38, %39, %40, %41, %42, %43, %44, %45, %46, %47, %48, %49, %50, %51, %52, %53, %54, %55, %56, %57, %58, %59, %60, %61, %62, %63}, "
    "%64, %65, p, 1, 1, 0, 1;\n}\n"
    : "+f"(d[0]), "+f"(d[1]), "+f"(d[2]), "+f"(d[3]), "+f"(d[4]), "+f"(d[5]), "+f"(d[6]), "+f"(d[7]), "+f"(d[8]), "+f"(d[9]), "+f"(d[10]), "+f"(d[11]), "+f"(d[12]), "+f"(d[13]), "+f"(d[14]), "+f"(d[15]), "+f"(d[16]), "+f"(d[17]), "+f"(d[18]), "+f"(d[19]), "+f"(d[20]), "+f"(d[21]), "+f"(d[22]), "+f"(d[23]), "+f"(d[24]), "+f"(d[25]), "+f"(d[26]), "+f"(d[27]), "+f"(d[28]), "+f"(d[29]), "+f"(d[30]), "+f"(d[31]), "+f"(d[32]), "+f"(d[33]), "+f"(d[34]), "+f"(d[35]), "+f"(d[36]), "+f"(d[37]), "+f"(d[38]), "+f"(d[39]), "+f"(d[40]), "+f"(d[41]), "+f"(d[42]), "+f"(d[43]), "+f"(d[44]), "+f"(d[45]), "+f"(d[46]), "+f"(d[47]), "+f"(d[48]), "+f"(d[49]), "+f"(d[50]), "+f"(d[51]), "+f"(d[52]), "+f"(d[53]), "+f"(d[54]), "+f"(d[55]), "+f"(d[56]), "+f"(d[57]), "+f"(d[58]), "+f"(d[59]), "+f"(d[60]), "+f"(d[61]), "+f"(d[62]), "+f"(d[63])
    : "l"(descA), "l"(descB), "r"(scaleD));
}
__device__ __forceinline__ void wgmma_ss_n160_ta0_tb1(float (&d)[80], uint64_t descA, uint64_t descB, int scaleD) {
  asm volatile("{\n.reg .pred p;\nsetp.ne.b32 p, %82, 0;\n"
    "wgmma.mma_async.sync.aligned.m64n160k16.f32.bf16.bf16 "
    "{%0, %1, %2, %3, %4, %5, %6, %7, %8, %9, %10, %11, %12, %13, %14, %15, %16, %17, %18, %19, %20, %21, %22, %23, %24, %25, %26, %27, %28, %29, %30, %31, %32, %33, %34, %35, %36, %37, %38, %39, %40, %41, %42, %43, %44, %45, %46, %47, %48, %49, %50, %51, %52, %53, %54, %55, %56, %57, %58, %59, %60, %61, %62, %63, %64, %65, %66, %67, %68, %69, %70, %71, %72, %73, %74, %75, %76, %77, %78, %79}, "
    "%80, %81, p, 1, 1, 0, 1;\n}\n"
    : "+f"(d[0]), "+f"(d[1]), "+f"(d[2]), "+f"(d[3]), "+f"(d[4]), "+f"(d[5]), "+f"(d[6]), "+f"(d[7]), "+f"(d[8]), "+f"(d[9]), "+f"(d[10]), "+f"(d[11]), "+f"(d[12]), "+f"(d[13]), "+f"(d[14]), "+f"(d[15]), "+f"(d[16]), "+f"(d[17]), "+f"(d[18]), "+f"(d[19]), "+f"(d[20]), "+f"(d[21]), "+f"(d[22]), "+f"(d[23]), "+f"(d[24]), "+f"(d[25]), "+f"(d[26]), "+f"(d[27]), "+f"(d[28]), "+f"(d[29]), "+f"(d[30]), "+f"(d[31]), "+f"(d[32]), "+f"(d[33]), "+f"(d[34]), "+f"(d[35]), "+f"(d[36]), "+f"(d[37]), "+f"(d[38]), "+f"(d[39]), "+f"(d[40]), "+f"(d[41]), "+f"(d[42]), "+f"(d[43]), "+f"(d[44]), "+f"(d[45]), "+f"(d[46]), "+f"(d[47]), "+f"(d[48]), "+f"(d[49]), "+f"(d[50]), "+f"(d[51]), "+f"(d[52]), "+f"(d[53]), "+f"(d[54]), "+f"(d[55]), "+f"(d[56]), "+f"(d[57]), "+f"(d[58]), "+f"(d[59]), "+f"(d[60]), "+f"(d[61]), "+f"(d[62]), "+f"(d[63]), "+f"(d[64]), "+f"(d[65]), "+f"(d[66]), "+f"(d[67]), "+f"(d[68]), "+f"(d[69]), "+f"(d[70]), "+f"(d[71]), "+f"(d[72]), "+f"(d[73]), "+f"(d[74]), "+f"(d[75]), "+f"(d[76]), "+f"(d[77]), "+f"(d[78]), "+f"(d[79])
    : "l"(descA), "l"(descB), "r"(scaleD));
}


template <int N> struct IC { static constexpr int value = N; };
struct Cur {
    uint32_t slot, ph;
    __device__ __forceinline__ void adv() { if (++slot == NSLOT) { slot = 0; ph ^= 1; } }
};
constexpr int E0 = 2;
__host__ __device__ constexpr uint32_t slot_of(int e) { return (e + E0) % NSLOT; }
__device__ __forceinline__ Cur cur_at(int e) { Cur c; c.slot = (e + E0) % NSLOT; c.ph = ((e + E0) / NSLOT) & 1; return c; }

__device__ __forceinline__ int kv_tile(int s) { return (0x804Cu >> (4 * s)) & 15; }
__device__ __forceinline__ int op_head(int i, int kap) { return 8 * kap + (i & 7) + 16 * (i >> 3); }

constexpr float SM_SCALE = 0.08838834764831845f * 1.4426950408889634f;

struct Ctx {
    uint32_t ring, misc;
    uint32_t rel;
    int w, warp, lane;
};
__device__ __forceinline__ void release(const Ctx& c, uint32_t off, uint32_t cnt) {
    if (c.lane < 2) mbar_arrive_cluster(c.rel + off, cnt);
}
__device__ __forceinline__ void signal_event(const Ctx& c, int ev) {
    __syncwarp();
    if (c.lane == 0) mbar_arrive(c.misc + BAR_EV + (c.w * NEV + ev) * 8);
}
template <int NK, int OFF, int N>
__device__ __forceinline__ uint32_t load_afrag(uint32_t (&a)[N], uint32_t base, const Ctx& c) {
    int r = c.lane & 7, mat = c.lane >> 3;
    uint32_t addr = base + (8 * (mat >> 1) + r) * 128 + (((2 * c.warp + (mat & 1)) ^ r) << 4);
#pragma unroll
    for (int k = 0; k < NK; k++) ldsm4t(a[OFF + 4 * k], a[OFF + 4 * k + 1], a[OFF + 4 * k + 2], a[OFF + 4 * k + 3], addr + k * 2048);
    uint32_t dep = 0;
#pragma unroll
    for (int k = 0; k < NK; k++) dep |= a[OFF + 4 * k];
    return dep & blockIdx.y;
}
__device__ __forceinline__ void tile_out(unsigned char* (&out)[2], unsigned char* dst, int row0, int perm, const Ctx& c) {
#pragma unroll
    for (int i = 0; i < 2; i++) {
        int row = row0 + 16 * c.warp + 8 * i + (c.lane >> 2);
        if (perm) row = perm32(row);
        out[i] = dst + row * 64 + (((c.lane ^ (row >> 1)) & 3) << 4);
    }
}
__device__ __forceinline__ void store_pair(const float (&a)[64], int q, unsigned char* const (&out)[2], int quarter_stride, const float (&f)[2]) {
#pragma unroll
    for (int i = 0; i < 2; i++)
        stg128(out[i] + q * quarter_stride,
               pack_bf16(a[16 * q + 2 * i] * f[i], a[16 * q + 2 * i + 1] * f[i]), pack_bf16(a[16 * q + 4 + 2 * i] * f[i], a[16 * q + 4 + 2 * i + 1] * f[i]),
               pack_bf16(a[16 * q + 8 + 2 * i] * f[i], a[16 * q + 8 + 2 * i + 1] * f[i]), pack_bf16(a[16 * q + 12 + 2 * i] * f[i], a[16 * q + 12 + 2 * i + 1] * f[i]));
}

constexpr float SAFE_SUM = 1099511627776.0f;
template <int NJ>
__device__ __forceinline__ void row_max(const float (&s)[4 * NJ], float (&mx)[2]) {
#pragma unroll
    for (int i = 0; i < 2; i++) {
        float a = fmaxf(s[2 * i], s[2 * i + 1]), b = fmaxf(s[4 + 2 * i], s[4 + 2 * i + 1]);
#pragma unroll
        for (int j = 2; j < NJ; j += 2) {
            a = fmaxf(a, fmaxf(s[4 * j + 2 * i], s[4 * j + 2 * i + 1]));
            b = fmaxf(b, fmaxf(s[4 * j + 4 + 2 * i], s[4 * j + 4 + 2 * i + 1]));
        }
        a = fmaxf(a, b);
        a = fmaxf(a, __shfl_xor_sync(0xffffffffu, a, 1));
        mx[i] = fmaxf(a, __shfl_xor_sync(0xffffffffu, a, 2));
    }
}
template <int NJ, bool SHIFT>
__device__ __forceinline__ void exp_sum(float (&s)[4 * NJ], const float (&m)[2], float& l0, float& l1) {
#pragma unroll
    for (int j = 0; j < NJ; j++) {
#pragma unroll
        for (int e = 0; e < 4; e++) s[4 * j + e] = ex2(SHIFT ? s[4 * j + e] - m[e >> 1] : s[4 * j + e]);
        l0 += s[4 * j + 0] + s[4 * j + 1]; l1 += s[4 * j + 2] + s[4 * j + 3];
    }
}
__device__ __forceinline__ void recompute_scores(float (&s)[64], const uint32_t (&q)[32], uint32_t kaddr, const Ctx& c) {
    const int r = c.lane & 7, mat = c.lane >> 3;
    const uint32_t a0 = kaddr + (8 * (mat & 1) + r) * 64 + (((mat >> 1) ^ (r >> 1)) << 4);
#pragma unroll
    for (int i = 0; i < 64; i++) s[i] = 0.f;
#pragma unroll
    for (int jp = 0; jp < 8; jp++) {
#pragma unroll
        for (int k = 0; k < 8; k++) {
            asm volatile(
                "{\n.reg .b32 b0, b1, b2, b3;\n"
                "ldmatrix.sync.aligned.m8n8.x4.trans.shared.b16 {b0,b1,b2,b3}, [%12];\n"
                "mma.sync.aligned.m16n8k16.row.col.f32.bf16.bf16.f32 {%0,%1,%2,%3}, {%8,%9,%10,%11}, {b0,b1}, {%0,%1,%2,%3};\n"
                "mma.sync.aligned.m16n8k16.row.col.f32.bf16.bf16.f32 {%4,%5,%6,%7}, {%8,%9,%10,%11}, {b2,b3}, {%4,%5,%6,%7};\n}\n"
                : "+f"(s[8 * jp]), "+f"(s[8 * jp + 1]), "+f"(s[8 * jp + 2]), "+f"(s[8 * jp + 3]),
                  "+f"(s[8 * jp + 4]), "+f"(s[8 * jp + 5]), "+f"(s[8 * jp + 6]), "+f"(s[8 * jp + 7])
                : "r"(q[4 * k]), "r"(q[4 * k + 1]), "r"(q[4 * k + 2]), "r"(q[4 * k + 3]),
                  "r"((a0 ^ ((jp & 1) << 5)) + (jp >> 1) * 8192 + k * 1024) : "memory");
        }
    }
}
__device__ __forceinline__ int mask_lim(const Ctx& c) { return perm32(16 * c.warp + (c.lane >> 2)) - 8 * (c.lane & 3); }
template <int J0>
__device__ __forceinline__ void mask_diag(float (&s)[4 * J0 + 32], const Ctx& c) {
    const int lim = mask_lim(c);
    if (c.warp < 2) {
#pragma unroll
        for (int x = 0; x < 16; x++) {
            if (2 * (x >> 2) + (x & 1) - (x & 2) > lim) s[4 * J0 + x] = -INFINITY;
            s[4 * J0 + 16 + x] = -INFINITY;
        }
    } else {
#pragma unroll
        for (int x = 0; x < 16; x++)
            if (32 + 2 * (x >> 2) + (x & 1) - (x & 2) > lim) s[4 * J0 + 16 + x] = -INFINITY;
    }
}
__device__ __forceinline__ void mask_any(float (&s)[64], int hh, const Ctx& c) {
    const int lim = mask_lim(c) + 64 * hh;
#pragma unroll
    for (int x = 0; x < 64; x++)
        if (32 * (x >> 4) + 2 * ((x >> 2) & 3) + (x & 1) - (x & 2) > lim) s[x] = -INFINITY;
}
__device__ __forceinline__ void issue_pv(float (&o)[64], const uint32_t (&p)[32], uint32_t vaddr, int acc, int mode  ) {
    uint64_t d = mkdesc(vaddr, 16, 512, 2);
    if (mode == 0) {
        wg_fence();
#pragma unroll
        for (int k = 0; k < 8; k++)
            wgmma_rs_n128_ta0_tb0(o, p[4 * k], p[4 * k + 1], p[4 * k + 2], p[4 * k + 3], d + (k >> 1) * 512 + 2 * (k & 1), k ? 1 : acc);
        wg_commit();
    } else if (mode == 1) {
        wg_fence();
#pragma unroll
        for (int k = 0; k < 4; k++) wgmma_rs_n128_ta0_tb0(o, p[4 * k], p[4 * k + 1], p[4 * k + 2], p[4 * k + 3], d + (k >> 1) * 512 + 2 * (k & 1), k != 0);
        wg_commit();
    } else {
        wg_fence();
        wgmma_rs_n128_ta0_tb0(o, p[0], p[1], p[2], p[3], d, acc);
        wg_commit();
    }
}
__device__ __forceinline__ void issue_qk(float (&s)[64], const uint32_t (&q)[32], uint32_t kaddr) {
    uint64_t d = mkdesc(kaddr, 8192, 512, 2);
    wg_fence();
#pragma unroll
    for (int k = 0; k < 8; k++) wgmma_rs_n128_ta0_tb1(s, q[4 * k], q[4 * k + 1], q[4 * k + 2], q[4 * k + 3], d + 64 * k, k != 0);
    wg_commit();
}
__device__ __forceinline__ void issue_qk_half(float (&s32)[32], const uint32_t (&q)[32], uint32_t kaddr) {
    uint64_t d = mkdesc(kaddr, 8192, 512, 2);
    wg_fence();
#pragma unroll
    for (int k = 0; k < 8; k++) wgmma_rs_n64_ta0_tb1(s32, q[4 * k], q[4 * k + 1], q[4 * k + 2], q[4 * k + 3], d + 64 * k, k != 0);
    wg_commit();
}
__device__ __forceinline__ void row_inv(const float (&l)[2], float (&inv)[2]) {
#pragma unroll
    for (int i = 0; i < 2; i++) {
        float sum = l[i];
        sum += __shfl_xor_sync(0xffffffffu, sum, 1);
        sum += __shfl_xor_sync(0xffffffffu, sum, 2);
        inv[i] = rcp_fast(sum);
    }
}

__device__ __forceinline__ const unsigned char* xn_addr(int row, int col) {
    row = perm32(row);
    return g_xn + ((row >> 7) * 10 + (col >> 6)) * 16384 + (row & 127) * 128 + ((((col & 63) >> 3) ^ (row & 7)) << 4);
}
__device__ __forceinline__ void mma16816(float (&d)[4], uint32_t a0, uint32_t a1, uint32_t a2, uint32_t a3, uint32_t b0, uint32_t b1) {
    asm volatile("mma.sync.aligned.m16n8k16.row.col.f32.bf16.bf16.f32 {%0,%1,%2,%3}, {%4,%5,%6,%7}, {%8,%9}, {%0,%1,%2,%3};"
                 : "+f"(d[0]), "+f"(d[1]), "+f"(d[2]), "+f"(d[3]) : "r"(a0), "r"(a1), "r"(a2), "r"(a3), "r"(b0), "r"(b1));
}
__device__ __forceinline__ uint32_t lds32(uint32_t addr) { uint32_t v; asm volatile("ld.shared.u32 %0, [%1];" : "=r"(v) : "r"(addr)); return v; }

__device__ __noinline__ void ln_rows(const __nv_bfloat16* x, int row0, int lane, uint32_t wr_s) {
    const int hl = lane & 15, row = row0 + (lane >> 4);
    uint32_t v[20];
#pragma unroll
    for (int i = 0; i < 5; i++) {
        const uint4 u = __ldg(reinterpret_cast<const uint4*>(x + (size_t)row * DM + 128 * i + 8 * hl));
        v[4 * i] = u.x; v[4 * i + 1] = u.y; v[4 * i + 2] = u.z; v[4 * i + 3] = u.w;
    }
    float mean = 0.f, m2 = 0.f, acc2 = 0.f;
#pragma unroll
    for (int i = 0; i < 20; i++) { mean += bf_lo(v[i]); acc2 += bf_hi(v[i]); }
    mean = (mean + acc2) * (1.0f / 40);
    acc2 = 0.f;
#pragma unroll
    for (int i = 0; i < 20; i++) {
        float d0 = __uint_as_float(__byte_perm(v[i], 0, 0x1044)) - mean, d1 = __uint_as_float(__byte_perm(v[i], 0, 0x3244)) - mean;
        m2 = fmaf(d0, d0, m2); acc2 = fmaf(d1, d1, acc2);
    }
    m2 += acc2;
    acc2 = 0.f;
#pragma unroll
    for (int o = 1; o < 16; o <<= 1) {
        float mo = __shfl_xor_sync(0xffffffffu, mean, o), qo = __shfl_xor_sync(0xffffffffu, m2, o), d = mo - mean;
        m2 = fmaf(d * d, 20.0f * o, m2 + qo);
        mean = 0.5f * (mean + mo);
    }
    const uint32_t mb2 = pack_bf16(mean, mean);
    const float inv = rcp_fast(bf_round(sqrt_fast(bf_round(bf_round(m2 * (1.0f / DM)) + 1e-5f))));
    float dot = 0.f;
    unsigned char* xp = const_cast<unsigned char*>(xn_addr(row, 8 * hl));
#pragma unroll
    for (int i = 0; i < 5; i++) {
        uint32_t ww[4];
        asm volatile("ld.shared.v4.b32 {%0,%1,%2,%3}, [%4];" : "=r"(ww[0]), "=r"(ww[1]), "=r"(ww[2]), "=r"(ww[3]) : "r"(wr_s + 256 * i + 16 * hl) : "memory");
#pragma unroll
        for (int e = 0; e < 4; e++) {
            uint32_t d;
            asm("sub.rn.bf16x2 %0, %1, %2;" : "=r"(d) : "r"(v[4 * i + e]), "r"(mb2));
            d = pack_bf16(bf_lo(d) * inv, bf_hi(d) * inv);
            v[4 * i + e] = d;
            dot = fmaf(bf_lo(d), bf_lo(ww[e]), dot);
            acc2 = fmaf(bf_hi(d), bf_hi(ww[e]), acc2);
        }
        stg128(xp + i * 32768, v[4 * i], v[4 * i + 1], v[4 * i + 2], v[4 * i + 3]);
    }
    dot += acc2;
#pragma unroll
    for (int o = 8; o > 0; o >>= 1) dot += __shfl_xor_sync(0xffffffffu, dot, o);
    if (hl == 0) { g_router[row] = bf_round(dot); g_stats[row] = make_uint2(mb2, __float_as_uint(inv)); }
}

__device__ __forceinline__ void aux_cta(const CUtensorMap* tmG, const CUtensorMap* tmU, const CUtensorMap* tmD, unsigned char* sm, int a) {
    constexpr int STG = 57344, XS = 3 * STG, HS = XS + 8 * 1296, KEY = HS + 8 * 912, MI = KEY + 8192;
    const int tid = threadIdx.x, warp = __shfl_sync(0xffffffffu, tid >> 5, 0), lane = tid & 31;
    const uint32_t sb = smem_u32(sm);
    const uint32_t full = sb + MI, empty = sb + MI + 32;
    int* s_sel = reinterpret_cast<int*>(sm + MI + 64);
    float* s_r = reinterpret_cast<float*>(sm + MI + 96);
    volatile unsigned* s_misc = reinterpret_cast<volatile unsigned*>(sm + MI + 128);
    uint32_t* s_key = reinterpret_cast<uint32_t*>(sm + KEY);
    if (tid == 0) {
        for (int i = 0; i < 3; i++) { mbar_init(full + 8 * i, 1); mbar_init(empty + 8 * i, 10); }
        asm volatile("fence.mbarrier_init.release.cluster;" ::: "memory");
    }
    __syncthreads();
    if (warp == 11) {
        if (elect_one()) {
            int st = 0; uint32_t ph = 0;
#pragma unroll 1
            for (int s = 0; s < 34; s++) {
                mbar_wait(empty + 8 * st, ph ^ 1);
                const uint32_t dst = sb + st * STG, fb = full + 8 * st;
                if (s < 20) {
                    mbar_expect_tx(fb, 57344);
                    tma3d(dst, tmG, 0, 32 * s, 7 * a, fb);
                    tma3d(dst + 28672, tmU, 0, 32 * s, 7 * a, fb);
                } else {
                    mbar_expect_tx(fb, 40960);
                    tma3d(dst, tmD, 0, 448 * a + 32 * (s - 20), 0, fb);
                }
                if (s >= 3) {
#pragma unroll 1
                    for (int f = (s == 3 ? 4 : s + 6); f <= s + 6 && f < 34; f++) {
                        if (f < 20) { tma3d_prefetch(tmG, 0, 32 * f, 7 * a); tma3d_prefetch(tmU, 0, 32 * f, 7 * a); }
                        else tma3d_prefetch(tmD, 0, 448 * a + 32 * (f - 20), 0);
                    }
                }
                if (++st == 3) { st = 0; ph ^= 1; }
            }
        }
        return;
    }
    if (warp == 10) return;
    if (tid < 8) {
        unsigned e = *reinterpret_cast<volatile unsigned*>(&g_epoch);
        if (tid == 0) s_misc[0] = e;
        flag_wait(flag_ptr(FL_LN + tid), (e + 1) * (tid < 4 ? 33u : 128u));
    }
    bar_sync(1, 320);
    const unsigned ep = s_misc[0];
    auto top8 = [&](uint32_t (&key)[8]) {
        uint32_t mine = 0;
#pragma unroll 1
        for (int r = 0; r < TOPC; r++) {
            uint32_t best = 0;
#pragma unroll
            for (int i = 0; i < 8; i++) best = max(best, key[i]);
            best = __reduce_max_sync(0xffffffffu, best);
#pragma unroll
            for (int i = 0; i < 8; i++) if (key[i] == best) key[i] = 0;
            if (lane == r) mine = best;
        }
        return mine;
    };
#pragma unroll 1
    for (int pass = 0; pass < 2; pass++) {
        if (warp < (pass ? 1 : 8)) {
            uint32_t key[8];
#pragma unroll
            for (int i = 0; i < 8; i++) {
                if (pass == 0) {
                    int idx = warp * 256 + i * 32 + lane;
                    uint32_t b = __float_as_uint(__ldcg(g_router + idx)) >> 16;
                    b = (b & 0x8000u) ? (~b & 0xffffu) : (b | 0x8000u);
                    key[i] = (b << 16) | (uint32_t)(0xffff - idx);
                } else key[i] = i < 2 ? s_key[i * 32 + lane] : 0u;
            }
            uint32_t best = top8(key);
            if (lane < TOPC) {
                if (pass == 0) s_key[warp * 8 + lane] = best;
                else {
                    uint32_t b = best >> 16;
                    b = (b & 0x8000u) ? (b & 0x7fffu) : (~b & 0xffffu);
                    s_sel[lane] = 0xffff - (int)(best & 0xffffu);
                    s_r[lane] = bf_round(rcp_fast(1.0f + __expf(fminf(-__uint_as_float(b << 16), 80.f))));
                }
            }
        }
        bar_sync(1, 320);
    }
#pragma unroll 1
    for (int it = 0; it < 2; it++) {
        int i = tid + it * 320, tk = i / 80, ch = i % 80;
        *reinterpret_cast<uint4*>(sm + XS + tk * 1296 + ch * 16) = __ldcg(reinterpret_cast<const uint4*>(xn_addr(s_sel[tk], ch * 8)));
    }
    bar_sync(1, 320);
    const int g = lane >> 2, t = lane & 3;
    const uint32_t woff = warp * 4096 + (8 * (lane >> 4) + (lane & 7)) * 128 + ((((lane >> 3) & 1) ^ (lane & 7)) << 4);
    int st = 0; uint32_t ph = 0;
    float ga[4][4], ua[4][4];
#pragma unroll
    for (int i = 0; i < 4; i++)
#pragma unroll
        for (int e = 0; e < 4; e++) { ga[i][e] = 0.f; ua[i][e] = 0.f; }
#pragma unroll 1
    for (int s = 0; s < 34; s++) {
        if (s == 20) {
            if (warp < 7) {
#pragma unroll 1
                for (int i = 0; i < 4; i++) {
#pragma unroll
                    for (int e = 0; e < 4; e++) {
                        float gv = bf_round(ga[0][e]), uv = bf_round(ua[0][e]);
                        float sg = bf_round(gv * rcp_fast(1.0f + __expf(fminf(-gv, 80.f))));
                        int f = warp * 64 + i * 16 + g + 8 * (e >> 1), tk = 2 * t + (e & 1);
                        *reinterpret_cast<__nv_bfloat16*>(sm + HS + tk * 912 + f * 2) = __float2bfloat16_rn(sg * uv);
                        ga[0][e] = ga[1][e]; ga[1][e] = ga[2][e]; ga[2][e] = ga[3][e]; ga[3][e] = 0.f;
                        ua[0][e] = ua[1][e]; ua[1][e] = ua[2][e]; ua[2][e] = ua[3][e];
                    }
                }
            }
            bar_sync(1, 320);
        }
        mbar_wait(full + 8 * st, ph);
        if (s >= 20 || warp < 7) {
#pragma unroll
            for (int kk = 0; kk < 2; kk++) {
                uint32_t xb = sb + (s < 20 ? XS + g * 1296 + s * 64 : HS + g * 912 + (s - 20) * 64) + 32 * kk + 4 * t;
                uint32_t b0 = lds32(xb), b1 = lds32(xb + 16);
                uint32_t wa = sb + st * STG + woff + kk * 2048;
#pragma unroll
                for (int i = 0; i < 4; i++) {
                    uint32_t a0, a1, a2, a3;
                    ldsm4t(a0, a1, a2, a3, wa ^ (i << 5));
                    mma16816(ga[i], a0, a1, a2, a3, b0, b1);
                    if (s < 20) {
                        ldsm4t(a0, a1, a2, a3, (wa ^ (i << 5)) + 28672);
                        mma16816(ua[i], a0, a1, a2, a3, b0, b1);
                    }
                }
            }
        }
        asm volatile("fence.proxy.async.shared::cta;" ::: "memory");
        __syncwarp();
        if (lane == 0) mbar_arrive(empty + 8 * st);
        if (++st == 3) { st = 0; ph ^= 1; }
    }
#pragma unroll
    for (int i = 0; i < 4; i++)
#pragma unroll
        for (int e = 0; e < 4; e += 2)
            *reinterpret_cast<float2*>(g_moe_part + (a * DM + warp * 64 + i * 16 + g + 4 * e) * 8 + 2 * t) = make_float2(ga[i][e], ga[i][e + 1]);
    bar_sync(1, 320);
    if (tid == 0) {
        __threadfence();
        unsigned old = atomicAdd(flag_ptr(FL_MOE_CNT), 1u);
        s_misc[1] = (old == ep * 4u + 3u);
        __threadfence();
    }
    bar_sync(1, 320);
    if (s_misc[1]) {
        const float4* pp = reinterpret_cast<const float4*>(g_moe_part);
#pragma unroll 1
        for (int i = tid; i < DM * 2; i += 320) {
            float4 v0 = __ldcg(pp + i), v1 = __ldcg(pp + DM * 2 + i), v2 = __ldcg(pp + DM * 4 + i), v3 = __ldcg(pp + DM * 6 + i);
            float y[4] = {v0.x + v1.x + v2.x + v3.x, v0.y + v1.y + v2.y + v3.y, v0.z + v1.z + v2.z + v3.z, v0.w + v1.w + v2.w + v3.w};
#pragma unroll
            for (int e = 0; e < 4; e++) {
                int col = i >> 1, tk = (i & 1) * 4 + e;
                float upd = bf_round(bf_round(y[e]) * s_r[tk]);
                float xn = __bfloat162float(*reinterpret_cast<const __nv_bfloat16*>(sm + XS + tk * 1296 + col * 2));
                g_brow[tk * DM + col] = __float2bfloat16_rn(xn + upd);
            }
        }
        if (tid < TOPC) g_sel[tid] = s_sel[tid];
        bar_sync(1, 320);
        if (tid == 0) {
            flag_signal(flag_ptr(FL_MOE_DONE));
            *reinterpret_cast<volatile unsigned*>(&g_epoch) = ep + 1;
        }
    }
}

__global__ void __cluster_dims__(2, 1, 1) __launch_bounds__(384, 1)
fused_kernel(const __grid_constant__ CUtensorMap tmC, const __grid_constant__ CUtensorMap tmWk, const __grid_constant__ CUtensorMap tmWv,
             const __grid_constant__ CUtensorMap tmWq, const __grid_constant__ CUtensorMap tmWo,
             const __grid_constant__ CUtensorMap tmG, const __grid_constant__ CUtensorMap tmU, const __grid_constant__ CUtensorMap tmD, const Params P) {
    extern __shared__ __align__(1024) unsigned char smem_raw[];
    const uint32_t ring = smem_u32(smem_raw);
    const uint32_t misc = ring + RING_BYTES;
    const int tid = threadIdx.x;
    const int rank = blockIdx.x & 1;
    uint32_t smid, nsm;
    asm("mov.u32 %0, %%smid;" : "=r"(smid));
    asm("mov.u32 %0, %%nsmid;" : "=r"(nsm));
    if (nsm != 132) smid = blockIdx.x;
    auto role_of = [](int tpc) {
        return tpc < 32 ? (tpc & 7) * 8 + (tpc >> 3) : tpc < 60 ? (1 + (tpc - 32) % 7) * 8 + 4 + (tpc - 32) / 7 : tpc < 64 ? tpc - 56 : tpc;
    };
    int mc = role_of(smid >> 1);

    auto prefetch_w = [&](int ch) {
        const int i = tid - 128;
        asm volatile("prefetch.global.L2 [%0];" ::"l"((rank ? P.wv : P.wk) + (size_t)(ch * 128 + (mc & 3) * 32 + (i >> 3)) * 4096 + (mc >> 2) * 128 + (i & 7) * 16));
    };
    if (tid >= 128 && mc < 64) {
        if (tid < 256) asm volatile("prefetch.global.L2 [%0];" ::"l"(P.c + (size_t)((12 + (mc & 3)) * 128 + ((mc >> 2) * 2 + rank) * 4) * DC + (tid - 128) * 16));
        prefetch_w(0);
    }
    auto load_w0 = [&]() {
        const CUtensorMap* tw = rank ? &tmWv : &tmWk;
        mbar_expect_tx(misc + BAR_FULL + 8 * slot_of(0), SLOT_BYTES);
        tma2d(ring + slot_of(0) * SLOT_BYTES, tw, (mc >> 2) * 128, 0, misc + BAR_FULL + 8 * slot_of(0));
        tma2d(ring + slot_of(0) * SLOT_BYTES + 16384, tw, (mc >> 2) * 128 + 64, 0, misc + BAR_FULL + 8 * slot_of(0));
    };
    if (tid == 0) {
#pragma unroll
        for (int i = 0; i < NSLOT; i++) mbar_init(misc + BAR_FULL + 8 * i, 1);
#pragma unroll
        for (int i = 0; i < E0; i++) mbar_arrive(misc + BAR_FULL + 8 * i);
        asm volatile("fence.mbarrier_init.release.cluster;" ::: "memory");
        if (mc < 64) load_w0();
    }
    if (tid == 160) {
        asm volatile("st.shared.u32 [%0], %1;" ::"r"(misc + MISC_SMID), "r"(smid) : "memory");
        asm volatile("fence.release.sync_restrict::shared::cta.cluster;" ::: "memory");
    }
    if (tid == 32) {
        asm volatile("prefetch.tensormap [%0];" ::"l"(&tmC) : "memory");
#pragma unroll
        for (int i = 0; i < NSLOT; i++) mbar_init(misc + BAR_EMPTY + 8 * i, 16);
#pragma unroll
        for (int i = 0; i < E0; i++) mbar_arrive_cluster(misc + BAR_EMPTY + 8 * i, 16);
        asm volatile("fence.mbarrier_init.release.cluster;" ::: "memory");
    }
    if (tid == 64) {
#pragma unroll
        for (int i = 0; i < NST3; i++) { mbar_init(misc + BAR_FULL3 + 8 * i, 1); mbar_init(misc + BAR_EMPTY3 + 8 * i, 16); }
#pragma unroll
        for (int i = 0; i < 4; i++) mbar_init(misc + BAR_PROG + 8 * i, 1);
        mbar_init(misc + BAR_LN, 2);
        asm volatile("fence.mbarrier_init.release.cluster;" ::: "memory");
    }
    if (tid == 96) {
#pragma unroll
        for (int i = 0; i < 24; i++) mbar_init(misc + BAR_DEP + 8 * i, 1);
    }
    if (tid == 128) {
#pragma unroll
        for (int i = 0; i < 2 * NEV; i++) mbar_init(misc + BAR_EV + 8 * i, 4);
    }
    __syncthreads();
    asm volatile("barrier.cluster.arrive.relaxed.aligned;\nbarrier.cluster.wait.aligned;" ::: "memory");
    {
        uint32_t peer;
        asm volatile("ld.shared::cluster.u32 %0, [%1];" : "=r"(peer) : "r"(mapa(misc + MISC_SMID, rank ^ 1)) : "memory");
        if ((__shfl_sync(0xffffffffu, peer, 0) ^ smid) != 1) {
            if (tid == 0) {
                const unsigned ep1 = *reinterpret_cast<volatile unsigned*>(&g_epoch) + 1;
                if ((smid & 1) == 0) atomicExch(g_roleq + 2 + (atomicAdd(g_roleq, 1u) & 127), (ep1 << 8) | (smid >> 1));
                if (rank == 0) {
                    unsigned* slot = g_roleq + 2 + (atomicAdd(g_roleq + 1, 1u) & 127);
                    unsigned v = 0;
                    for (int spin = 0; spin < 4000000 && ((v = atomicAdd(slot, 0u)) >> 8) != (ep1 & 0xffffffu); spin++) {}
                    asm volatile("st.shared::cluster.u32 [%0], %1;" ::"r"(mapa(misc + MISC_SMID + 4, 0)), "r"(v & 255) : "memory");
                    asm volatile("st.shared::cluster.u32 [%0], %1;" ::"r"(mapa(misc + MISC_SMID + 4, 1)), "r"(v & 255) : "memory");
                }
                if (mc < 64) {
                    mbar_wait(misc + BAR_FULL + 8 * slot_of(0), 0);
                    asm volatile("mbarrier.inval.shared::cta.b64 [%0];" ::"r"(misc + BAR_FULL + 8 * slot_of(0)) : "memory");
                    mbar_init(misc + BAR_FULL + 8 * slot_of(0), 1);
                    asm volatile("fence.mbarrier_init.release.cluster;" ::: "memory");
                }
            }
            __syncwarp();
            asm volatile("barrier.cluster.arrive.aligned;\nbarrier.cluster.wait.aligned;" ::: "memory");
            mc = role_of(__shfl_sync(0xffffffffu, lds32(misc + MISC_SMID + 4), 0));
            if (tid == 0 && mc < 64) load_w0();
            __syncwarp();
        }
    }
    const int cta = mc * 2 + rank;
    const bool aux = mc >= 64;
    const int team = mc >> 2, k = mc & 3;
    const int u3 = (mc >> 4) * 2 + (team & 1), s3 = k, kap = (mc >> 3) & 1;
    const int partner = cta ^ 16;
    const int b0 = k, b1 = 7 - k;
    if (tid >= 128 && !aux) prefetch_w(1);
    if (tid == 256 && !aux) {
        const CUtensorMap* tw = rank ? &tmWv : &tmWk;
#pragma unroll
        for (int e = 1; e < NSLOT; e++) {
            const uint32_t fb = misc + BAR_FULL + 8 * slot_of(e), dst = ring + slot_of(e) * SLOT_BYTES;
            mbar_expect_tx(fb, SLOT_BYTES);
            if (e & 1) tma2d_mc(dst + rank * 16384, &tmC, (e >> 1) * 128 + rank * 64, (12 + k) * 128, fb);
            else { tma2d(dst, tw, team * 128, e * 64, fb); tma2d(dst + 16384, tw, team * 128 + 64, e * 64, fb); }
        }
    }
    const int wg = __shfl_sync(0xffffffffu, tid >> 7, 0);

    if (wg == 0 || aux) {
        asm volatile("setmaxnreg.dec.sync.aligned.u32 40;");
        const int warp = __shfl_sync(0xffffffffu, tid >> 5, 0), lane = tid & 31;
        if (warp == 0 && !aux) {
            const bool lead = elect_one();
            Cur c = cur_at(NSLOT);
            uint32_t dst, fb;
            auto acquire = [&]() {
                mbar_wait_sleep(misc + BAR_EMPTY + 8 * c.slot, c.ph ^ 1);
                fb = misc + BAR_FULL + 8 * c.slot; dst = ring + c.slot * SLOT_BYTES;
                if (lead) mbar_expect_tx(fb, SLOT_BYTES);
                c.adv();
            };
            auto load_w = [&](const CUtensorMap* tm, int col, int row) {
                acquire();
                if (lead) { tma2d(dst, tm, col, row, fb); tma2d(dst + 16384, tm, col + 64, row, fb); }
            };
            auto load_half = [&](const unsigned char* src) {
                acquire();
                if (lead) bulk_load_mc(dst + rank * 16384, src, 16384, fb);
            };
            auto dep_wait = [&](int d) { mbar_wait_sleep(misc + BAR_DEP + 8 * d, 0); fence_async_global(); };
            auto op_prefetch = [&](int i) {
                const int head = op_head(i, kap);
                l2_prefetch(reinterpret_cast<const unsigned char*>(P.wo) + head * 163840 + (u3 * 8 + s3 * 2 + rank) * 2560, 2560);
                if (i < 8) l2_prefetch(g_ctx + (size_t)(head * 32 + 4 * u3 + 2 * rank) * 16384 + s3 * 8192, 8192);
            };
            if (lead) l2_prefetch(reinterpret_cast<const unsigned char*>(P.c) + (size_t)cta * 12288, 12288);
            const CUtensorMap* tw = rank ? &tmWv : &tmWk;
            const unsigned char* Kh = g_K + (size_t)team * 32 * 16384 + rank * 16384;
            const unsigned char* Vh = g_V + (size_t)team * 32 * 16384 + rank * 16384;
#pragma unroll 1
            for (int v = 0; v < 2; v++) {
                const int h = team + 16 * v;
#pragma unroll 1
                for (int i = v ? 0 : 3; i < 16; i++) {
                    if (i < 4 && v) load_w(tw, h * 128, i * 128);
                    if (v && i == 3 && lead) mbar_arrive(misc + BAR_PROG + 8);
                    if (v && (i == 3 || i == 7)) dep_wait(D_WAR + (i > 3));
                    acquire();
                    if (lead) tma2d_mc(dst + rank * 16384, &tmC, (i & 3) * 128 + rank * 64, (kv_tile(i >> 2) + k) * 128, fb);
                    if (i == 8 && lead) {
                        tma2d_prefetch(&tmWq, h * 128 + rank * 64, k * 64); tma2d_prefetch(&tmWq, h * 128 + rank * 64, k * 64 + 256);
                        if (k < 2) tma2d_prefetch(&tmWq, h * 128 + rank * 64, k * 64 + 512);
                        if (v) l2_prefetch(g_xn + cta * 10240, 10240);
                    }
                }
                int togo = v ? PF_START : 11;
#pragma unroll 1
                for (int r = 0; r < 2; r++) {
                    const int p = r ? b1 : b0, n = 2 * p + 1;
                    if (v == 0) dep_wait(D_LN + r);
                    const int g0 = r ? rank ^ 1 : 3 - rank, g1 = 3 - g0;
                    const unsigned char* x0 = g_xn + (2 * p + (g0 >> 1)) * 163840 + (g0 & 1) * 8192;
                    const unsigned char* x1 = g_xn + (2 * p + (g1 >> 1)) * 163840 + (g1 & 1) * 8192;
#pragma unroll 1
                    for (int kc = 0; kc < 10; kc++) {
                        acquire();
                        if (lead) {
                            tma2d_mc(dst + 16384 + rank * 8192, &tmWq, h * 128 + rank * 64, kc * 64, fb);
                            bulk_load(dst, x0 + kc * 16384, 8192, fb);
                            bulk_load(dst + 8192, x1 + kc * 16384, 8192, fb);
                        }
                    }
                    dep_wait(D_KV + 2 * v + r);
                    load_half(Kh + n * 32768);
#pragma unroll 1
                    for (int j = n - 1; j >= 0; j--) {
                        load_half(Kh + j * 32768); load_half(Vh + (j + 1) * 32768);
                        if (v == 0 && r && j == 7 && lead) mbar_arrive(misc + BAR_PROG);
                        --togo;
                        if (v == 0 && togo == 0 && lead) {
                            tma2d_prefetch(tw, h * 128 + 2048, k * 128); tma2d_prefetch(tw, h * 128 + 2112, k * 128);
                            l2_prefetch(reinterpret_cast<const unsigned char*>(P.c) + (size_t)cta * 16384, 16384);
                        }
                        if (v && togo <= 0 && togo > -OP_PF && lead) op_prefetch(-togo);
                    }
                    load_half(Vh);
                }
            }
            mbar_wait_sleep(misc + BAR_EMPTY + 8 * c.slot, c.ph ^ 1); c.adv();
            int st = 0; uint32_t ph3 = 0;
#pragma unroll 1
            for (int i = 0; i < 32; i++) {
                const int head = op_head(i >> 1, kap);
                if ((i & 1) == 0) dep_wait(D_CTX + (i >> 1));
                if (i < NST3) { mbar_wait_sleep(misc + BAR_EMPTY + 8 * c.slot, c.ph ^ 1); c.adv(); }
                else mbar_wait_sleep(misc + BAR_EMPTY3 + 8 * st, ph3 ^ 1);
                fb = misc + BAR_FULL3 + 8 * st; dst = ring + st * ST3_BYTES;
                if (i == LATE_AT && lead) mbar_arrive(misc + BAR_PROG + 16);
                if (lead) {
                    mbar_expect_tx(fb, ST3_BYTES);
                    const unsigned char* src = g_ctx + (size_t)(head * 32 + 4 * u3 + 2 * rank) * 16384 + (i & 1) * 8192;
                    bulk_load(dst, src, 8192, fb);
                    bulk_load(dst + 8192, src + 16384, 8192, fb);
                    tma3d_mc(dst + 16384 + rank * 10240, &tmWo, 0, head * 128 + (i & 1) * 64 + rank * 32, 5 * s3, fb);
                    if ((i & 1) && (i >> 1) + OP_PF < 16) op_prefetch((i >> 1) + OP_PF);
                }
                if (++st == NST3) { st = 0; ph3 ^= 1; }
            }
        } else {
        if (warp >= 1 && warp <= 3 && lane < 27 && (warp - 1) * 27 + lane < 80) {
            const int ch = (warp - 1) * 27 + lane;
            uint4 u = __ldg(reinterpret_cast<const uint4*>(P.wr) + ch);
            asm volatile("st.shared.v4.b32 [%0], {%1,%2,%3,%4};" ::"r"(misc + MISC_WR + 16 * ch), "r"(u.x), "r"(u.y), "r"(u.z), "r"(u.w) : "memory");
        }
        bar_sync(3, aux ? 384 : 96);
        const int nln = aux ? (warp < 8 ? 3 : 2) : (warp == 3 ? 1 : 3), rstep = aux ? 24 : -512;
        int lrow = aux ? (cta - 128) * 256 + 192 + 2 * warp : (cta >> 5) * 256 + (cta & 31) * 6 + (warp - 1) * 2;
        int lnext = aux ? lrow + 24 : 1536 + cta * 4 + (warp - 1) * 2;
#pragma unroll 1
        for (int t = 0; t < nln; t++) {
            if (t + 1 < nln) {
#pragma unroll
                for (int i = 0; i < 3; i++)
                    if (i * 32 + lane < 80) asm volatile("prefetch.global.L2 [%0];" ::"l"(P.x + (size_t)lnext * DM + (i * 32 + lane) * 16));
            }
            ln_rows(P.x, lrow, lane, misc + MISC_WR);
            __syncwarp();
            if (lane == 0 && warp < 3 && !aux) {
                if (t) flag_signal(flag_ptr(FL_LN + (lrow >> 8))); else mbar_arrive(misc + BAR_LN);
            }
            lrow = lnext; lnext += rstep;
        }
        if (aux) {
            bar_sync(3, 384);
            if (tid == 320) flag_signal(flag_ptr(FL_LN + cta - 128));
            __syncwarp();
            asm volatile("setmaxnreg.inc.sync.aligned.u32 128;");
            aux_cta(&tmG, &tmU, &tmD, smem_raw, cta - 128);
        } else
        if (warp == 3) {
            const unsigned ep1 = *reinterpret_cast<volatile unsigned*>(&g_epoch) + 1;
            if (lane == 0) {
                asm volatile("st.shared.u32 [%0], %1;" ::"r"(misc + MISC_EPOCH), "r"(ep1) : "memory");
                mbar_wait(misc + BAR_LN, 0);
                flag_signal(flag_ptr(FL_LN + (cta >> 5)));
                flag_wait(flag_ptr(FL_LN + b0), ep1 * 33u);
                mbar_arrive(misc + BAR_DEP + 8 * D_LN);
#pragma unroll 1
                for (int i = 0; i < 4; i++) {
                    mbar_wait(misc + BAR_EV + 8 * (NEV + EV_KV + i), 0);
                    if (i < 2) {
                        mbar_wait(misc + BAR_EV + 8 * (EV_KV + i), 0);
                        asm volatile("red.release.gpu.global.add.u32 [%0], 2;" ::"l"(flag_ptr(FL_KV + team * 8 + i)) : "memory");
                    }
                    if (i == 1) {
                        flag_wait(flag_ptr(FL_LN + b1), ep1 * 128u);
                        mbar_arrive(misc + BAR_DEP + 8 * (D_LN + 1));
                    }
                    flag_wait(flag_ptr(FL_KV + team * 8 + i), ep1 * 16u);
                    mbar_arrive(misc + BAR_DEP + 8 * (D_KV + i));
                    if (i == 1) {
#pragma unroll 1
                        for (int j = 0; j < 2; j++) {
                            mbar_wait(misc + BAR_PROG + 8 * j, 0);
                            asm volatile("red.relaxed.gpu.global.add.u32 [%0], 1;" ::"l"(flag_ptr(FL_WAR + 2 * team + j)) : "memory");
                            flag_wait(flag_ptr(FL_WAR + 2 * team + j), ep1 * 8u);
                            mbar_arrive(misc + BAR_DEP + 8 * (D_WAR + j));
                        }
                    }
                }
                flag_wait(flag_ptr(FL_MOE_DONE), ep1);
                int4 s0 = __ldcg(reinterpret_cast<const int4*>(g_sel)), s1 = __ldcg(reinterpret_cast<const int4*>(g_sel) + 1);
                asm volatile("st.shared.v4.u32 [%0], {%1,%2,%3,%4};" ::"r"(misc + MISC_SEL), "r"(s0.x), "r"(s0.y), "r"(s0.z), "r"(s0.w) : "memory");
                asm volatile("st.shared.v4.u32 [%0], {%1,%2,%3,%4};" ::"r"(misc + MISC_SEL + 16), "r"(s1.x), "r"(s1.y), "r"(s1.z), "r"(s1.w) : "memory");
                mbar_arrive(misc + BAR_SEL);
            }
            __syncwarp();
            const unsigned* cf = flag_ptr(FL_CTX + op_head(lane & 15, kap) * 8 + u3);
#pragma unroll 1
            for (int half = 0; half < 2; half++) {
                if (half) mbar_wait(misc + BAR_EV + 8 * (EV_CTX + 3), 0);
                bool done = (lane >> 3) != half;
                for (int spin = 0; spin < 4000000; spin++) {
                    if (!done) {
                        unsigned v;
                        asm volatile("ld.acquire.gpu.global.u32 %0, [%1];" : "=r"(v) : "l"(cf) : "memory");
                        if ((int)(v - ep1 * 4u) >= 0) { mbar_arrive(misc + BAR_DEP + 8 * (D_CTX + lane)); done = true; }
                    }
                    if (__all_sync(0xffffffffu, done)) break;
                    __nanosleep(64);
                }
            }
        } else {
            const int w = warp - 1;
            if (lane == 0) {
                const uint32_t eb = misc + BAR_EV + w * 8 * NEV;
#pragma unroll 1
                for (int i = 0; i < 6; i++) {
                    const bool kv = (i >> 1) == 1;
                    const int ci = i < 2 ? i : i - 2;
                    mbar_wait(eb + 8 * (kv ? EV_KV + i : EV_CTX + ci), 0);
                    if (i == 1) {
                        asm volatile("cp.async.bulk.global.shared::cta.bulk_group [%0], [%1], 16384;"
                                     ::"l"(g_ctx + (size_t)(team * 32 + 4 * b1 + (w ? 3 - (rank ^ 1) : rank ^ 1)) * 16384),
                                       "r"(ring + slot_of(78) * SLOT_BYTES + w * 16384) : "memory");
                        asm volatile("cp.async.bulk.commit_group;" ::: "memory");
                        asm volatile("cp.async.bulk.wait_group.read 0;" ::: "memory");
                        mbar_arrive_cluster(mapa(misc + BAR_EMPTY + 8 * slot_of(78), 0), 4);
                        mbar_arrive_cluster(mapa(misc + BAR_EMPTY + 8 * slot_of(78), 1), 4);
                        asm volatile("cp.async.bulk.wait_group 0;" ::: "memory");
                        fence_async_global();
                    }
                    flag_signal(flag_ptr(kv ? FL_KV + team * 8 + i : FL_CTX + (team + 16 * (ci >> 1)) * 8 + ((ci & 1) ? b1 : b0)));
                }
            }
            __syncwarp();
            mbar_wait(misc + BAR_PROG + 16, 0);
            const int row = (2 * u3 + rank) * 128 + 64 * w + perm32(16 * (lane >> 3) + 8 * kap + (lane & 7));
#pragma unroll
            for (int i = 0; i < 10; i++) asm volatile("prefetch.global.L2 [%0];" ::"l"(P.x + (size_t)row * DM + 160 * s3 + 16 * i));
            asm volatile("prefetch.global.L2 [%0];" ::"l"(g_stats + row));
            if (lane < 5) asm volatile("prefetch.global.L2 [%0];" ::"l"(g_brow + ((cta & 31) * 10 + w * 5 + lane) * 16));
            mbar_wait(misc + BAR_EV + w * 8 * NEV + 8 * EV_END, 0);
        }
        }
    } else {
        asm volatile("setmaxnreg.inc.sync.aligned.u32 232;");
        Ctx c;
        c.ring = ring; c.misc = misc; c.w = wg - 1; c.warp = __shfl_sync(0xffffffffu, (tid >> 5) & 3, 0); c.lane = tid & 31;
        c.rel = mapa(misc, tid & 1);
        const int w = c.w;
        if (w == 1) bar_arrive(1, 256);
        prefetch_w(2); prefetch_w(3);
        Cur cur = cur_at(0);
        float o[64], inv[2];
        unsigned char* out[2];
        uint32_t wf[128];
        Cur cw = cur;
        auto load_wchunk = [&](auto CH) {
            constexpr int ch = decltype(CH)::value;
            mbar_wait_hot(misc + BAR_FULL + 8 * cw.slot, cw.ph);
            const uint32_t z = load_afrag<8, 32 * ch>(wf, ring + cw.slot * SLOT_BYTES + w * 16384, c);
            release(c, BAR_EMPTY + 8 * cw.slot + z, 1);
            cw.adv(); cw.adv();
        };
#pragma unroll
        for (int i = 32; i < 64; i++) wf[i] = 0u;
        load_wchunk(IC<0>{});
#pragma unroll 1
        for (int v = 0; v < 2; v++) {
        {
            float (&acc)[64] = o;
#pragma unroll
            for (int i = 64; i < 128; i++) wf[i] = 0u;
            cur.adv();
            inv[0] = inv[1] = rank ? 1.0f : SM_SCALE;
#pragma unroll 1
            for (int t = 0; t < 4; t++) {
                uint32_t last = 0;
                token_wait(w);
                undef_regs(acc);
                auto chunk = [&](auto CH) {
                    constexpr int ch = decltype(CH)::value;
                    mbar_wait_hot(misc + BAR_FULL + 8 * cur.slot, cur.ph);
                    uint64_t d = mkdesc(ring + cur.slot * SLOT_BYTES, 16, 1024, 1);
                    wg_fence();
#pragma unroll
                    for (int ks = 0; ks < 8; ks++)
                        wgmma_rs_n128_ta0_tb0(acc, wf[32 * ch + 4 * ks], wf[32 * ch + 4 * ks + 1], wf[32 * ch + 4 * ks + 2], wf[32 * ch + 4 * ks + 3],
                                              d + (ks >> 2) * 1024 + (ks & 3) * 2, (ch | ks) != 0);
                    wg_commit();
                    if (ch == 3 || (ch < 2 && t == 0)) token_pass(w);
                    if constexpr (ch == 0) { if (t == 0) { if (v) load_wchunk(IC<2>{}); else load_wchunk(IC<1>{}); } }
                    if constexpr (ch == 1) { if (t == 0 && !v) load_wchunk(IC<2>{}); }
                    if constexpr (ch == 2) { if (t == 0 && !(w | v)) load_wchunk(IC<3>{}); }
                    if (ch > 0) { wg_wait<1>(); release(c, BAR_EMPTY + 8 * last, 1); }
                    last = cur.slot;
                    cur.adv();
                    if (ch < 3 && t == 0) cur.adv();
                    if constexpr (ch == 1) { if (t == 0 && (w | v)) load_wchunk(IC<3>{}); }
                    if (ch < 2 && t == 0) token_wait(w);
                };
                chunk(IC<0>{}); chunk(IC<1>{}); chunk(IC<2>{}); chunk(IC<3>{});
                wg_wait<0>();
                release(c, BAR_EMPTY + 8 * last, 1);
                fence_regs(acc);
                tile_out(out, (rank ? g_V : g_K) + (size_t)(team * 32 + 2 * (kv_tile(t) + k)) * 16384, 64 * w, rank, c);
                if (t == 3 && w) break;
#pragma unroll
                for (int i = 0; i < 4; i++) store_pair(acc, i, out, 8192, inv);
                if (t >= 2) signal_event(c, EV_KV + 2 * v + t - 2);
            }
        }
        {
            uint32_t q[32], p[32];
            float m[2], l[2];
#pragma unroll
            for (int i = 0; i < 32; i++) p[i] = 0u;
            l[0] = l[1] = 1.f;
            int pv_acc = 1, pv_mode = 2;
#pragma unroll 1
            for (int r = 0; r < 2; r++) {
                const int heavy = 1 ^ r ^ w;
                const int half = 1 ^ heavy ^ rank ^ r;
                int left = 2 * (r ? b1 : b0) + 1 + heavy;
                Cur ck, cv = cur;
                {
                    float s[64];
                    if (r) cur.adv();
                    mbar_wait_hot(misc + BAR_FULL + 8 * cv.slot, cv.ph);
                    token_wait(w);
                    issue_pv(o, p, ring + cv.slot * SLOT_BYTES, pv_acc, pv_mode);
                    undef_regs(s);
                    uint32_t prev;
                    auto qchunk = [&](int acc) {
                        mbar_wait_hot(misc + BAR_FULL + 8 * cur.slot, cur.ph);
                        const uint64_t da = mkdesc(ring + cur.slot * SLOT_BYTES + w * 8192, 16, 1024, 1);
                        const uint64_t db = mkdesc(ring + cur.slot * SLOT_BYTES + 16384, 8192, 1024, 1);
                        wg_fence();
#pragma unroll
                        for (int ks = 0; ks < 4; ks++) wgmma_ss_n128_ta0_tb1(s, da + 2 * ks, db + 128 * ks, ks ? 1 : acc);
                        wg_commit();
                    };
                    qchunk(0);
                    prev = cur.slot; cur.adv();
                    token_pass(w);
                    if (r) {
                        row_inv(l, inv);
                        tile_out(out, g_ctx + (size_t)((team + 16 * v) * 32 + 4 * b0 + (w ? rank : 3 - rank)) * 16384, 0, 0, c);
                    }
                    const int epi = r | w, hs = r ? 4096 : 8192;
                    const int hold = heavy ? -10 : half ? 6 : 8;
#pragma unroll
                    for (int kc = 1; kc < 10; kc++) {
                        if (kc >= 6 && (kc == hold || kc == hold + 2)) token_wait(w);
                        qchunk(1);
                        if (kc > 6 && kc == hold + 1) token_pass(w);
                        if (kc == 9 && heavy) { token_wait(w); token_pass(w); }
                        wg_wait<1>();
                        release(c, BAR_EMPTY + 8 * prev, 1);
                        prev = cur.slot; cur.adv();
                        if (kc == 1) { fence_regs(o); if (r) release(c, BAR_EMPTY + 8 * cv.slot, 1); }
                        if (kc <= 4 && epi) {
                            store_pair(o, kc - 1, out, hs, inv);
                            if (kc == 4) signal_event(c, r ? EV_CTX + 2 * v : EV_KV + 2 * v + 1);
                        }
                    }
                    if (!heavy) cur.adv();
                    ck = cur;
                    cur.adv();
                    if (!heavy) cur.adv();
                    wg_wait<0>();
                    release(c, BAR_EMPTY + 8 * prev, 1);
                    fence_regs(s);
#pragma unroll
                    for (int i = 0; i < 32; i++) q[i] = pack_bf16(s[2 * i], s[2 * i + 1]);
                }
                int first = 1, gen = 0;
                uint32_t pv_cnt = 0;
                l[0] = l[1] = m[0] = m[1] = 0.f;
                mbar_wait_hot(misc + BAR_FULL + 8 * ck.slot, ck.ph);
                auto diagonal = [&](auto NJC) {
                    constexpr int NJ = decltype(NJC)::value;
                    if (NJ == 16 || heavy) token_wait(w);
                    float sd[4 * NJ];
                    undef_regs(sd);
                    if constexpr (NJ == 8) issue_qk_half(sd, q, ring + ck.slot * SLOT_BYTES); else issue_qk(sd, q, ring + ck.slot * SLOT_BYTES);
                    token_pass(w);
                    wg_wait<0>();
                    fence_regs(sd);
                    mask_diag<NJ - 8>(sd, c);
                    float l0 = 0.f, l1 = 0.f;
#pragma unroll
                    for (int j = 0; j < NJ; j++) {
#pragma unroll
                        for (int e = 0; e < 4; e++) ex2v(sd[4 * j + e]);
                        l0 += sd[4 * j] + sd[4 * j + 1]; l1 += sd[4 * j + 2] + sd[4 * j + 3];
                    }
#pragma unroll
                    for (int i = 0; i < 2 * NJ; i++) p[i] = pack_bf16(sd[2 * i], sd[2 * i + 1]);
                    const int lim = NJ == 8 ? mask_lim(c) : 0;
                    const bool bad = __any_sync(0xffffffffu, !(l0 <= SAFE_SUM && l1 <= SAFE_SUM && (l0 >= 1.0f / SAFE_SUM || lim < 0) &&
                                                               (l1 >= 1.0f / SAFE_SUM || lim < -2)));
                    if (!bad) { l[0] = l0; l[1] = l1; }
                    return bad;
                };
#pragma unroll 1
                while (true) {
                    float s[64];
                    if (first) {
                        --left;
                        if (half ? diagonal(IC<8>{}) : diagonal(IC<16>{})) goto redo;
                        if (left == 0) goto tail;
                        release(c, BAR_EMPTY + 8 * ck.slot, 1 + heavy);
                        pv_acc = 0; pv_mode = half; pv_cnt = 1 + heavy; first = 0;
                        ck = cur; cur.adv(); cv = cur; cur.adv();
                        mbar_wait_hot(misc + BAR_FULL + 8 * ck.slot, ck.ph);
                    }
#pragma unroll 1
                    while (true) {
                        token_wait(w);
                        undef_regs(s);
                        issue_qk(s, q, ring + ck.slot * SLOT_BYTES);
                        Cur nck = cur, ncv = cur, ncur;
                        ncv.adv(); ncur = ncv; ncur.adv();
                        --left;
                        mbar_wait_hot(misc + BAR_FULL + 8 * cv.slot, cv.ph);
                        issue_pv(o, p, ring + cv.slot * SLOT_BYTES, pv_acc, pv_mode & 1);
                        token_pass(w);
                        wg_wait<1>();
                        fence_regs(s);
                        constexpr int JB = 11;
                        float l0 = l[0], l1 = l[1];
                        if (!gen) {
#pragma unroll
                            for (int j = 0; j < JB; j++) {
#pragma unroll
                                for (int e = 0; e < 4; e++) ex2v(s[4 * j + e]);
                                if (j < JB - 1) { l0 += s[4 * j] + s[4 * j + 1]; l1 += s[4 * j + 2] + s[4 * j + 3]; }
                            }
                        }
                        wg_wait<0>();
                        fence_regs(o);
                        if (gen) goto general;
#pragma unroll
                        for (int j = JB - 1; j < 16; j++) {
                            if (j >= JB) {
#pragma unroll
                                for (int e = 0; e < 4; e++) ex2v(s[4 * j + e]);
                            }
                            l0 += s[4 * j] + s[4 * j + 1]; l1 += s[4 * j + 2] + s[4 * j + 3];
                        }
#pragma unroll
                        for (int i = 0; i < 32; i++) p[i] = pack_bf16(s[2 * i], s[2 * i + 1]);
                        if (__any_sync(0xffffffffu, !(l0 <= SAFE_SUM && l1 <= SAFE_SUM))) goto redo;
                        l[0] = l0; l[1] = l1;
                        if (left == 0) goto tail;
                        release(c, BAR_EMPTY + 8 * ck.slot, 1);
                        release(c, BAR_EMPTY + 8 * cv.slot, pv_cnt);
                        pv_acc = 1; pv_mode = 0; pv_cnt = 1;
                        ck = nck; cv = ncv; cur = ncur;
                        mbar_wait_hot(misc + BAR_FULL + 8 * ck.slot, ck.ph);
                    }
                redo:
                    recompute_scores(s, q, ring + ck.slot * SLOT_BYTES, c);
                    if (first) { mask_any(s, half ^ 1, c); m[0] = m[1] = -INFINITY; }
                    gen = 1;
                general:
                    {
                        float mx[2], alpha[2];
                        row_max<16>(s, mx);
#pragma unroll
                        for (int i = 0; i < 2; i++) {
                            mx[i] = fmaxf(mx[i], m[i]);
                            alpha[i] = ex2(m[i] - mx[i]);
                            m[i] = mx[i];
                            l[i] *= alpha[i];
                        }
                        exp_sum<16, true>(s, m, l[0], l[1]);
#pragma unroll
                        for (int i = 0; i < 64; i++) o[i] *= alpha[(i >> 1) & 1];
#pragma unroll
                        for (int i = 0; i < 32; i++) p[i] = pack_bf16(s[2 * i], s[2 * i + 1]);
                    }
                tail:
                    release(c, BAR_EMPTY + 8 * ck.slot, 1 + (first & heavy));
                    if (pv_cnt) release(c, BAR_EMPTY + 8 * cv.slot, pv_cnt);
                    pv_acc = first ^ 1; pv_mode = first & half; pv_cnt = 1 + (first & heavy); first = 0;
                    if (left == 0) break;
                    ck = cur; cur.adv(); cv = cur; cur.adv();
                    mbar_wait_hot(misc + BAR_FULL + 8 * ck.slot, ck.ph);
                }
            }
            mbar_wait_hot(misc + BAR_FULL + 8 * cur.slot, cur.ph);
            token_wait(w);
            issue_pv(o, p, ring + cur.slot * SLOT_BYTES, 1, 0);
            if (w == 0 || v == 0) token_pass(w);
            const uint32_t vslot = cur.slot;
            cur.adv();
            if (v) {
                row_inv(l, inv);
                wg_wait<0>();
                release(c, BAR_EMPTY + 8 * vslot, 1);
                fence_regs(o);
                tile_out(out, g_ctx + (size_t)((team + 16) * 32 + 4 * b1 + (w ? 3 - (rank ^ 1) : rank ^ 1)) * 16384, 0, 0, c);
#pragma unroll
                for (int i = 0; i < 64; i++) wf[i] = 0u;
                continue;
            }
            cw = cur_at(80);
            mbar_wait_hot(misc + BAR_FULL + 8 * slot_of(76), cur_at(76).ph);
            mbar_wait_hot(misc + BAR_FULL + 8 * slot_of(78), cur_at(78).ph);
            load_afrag<8, 32>(wf, ring + slot_of(78) * SLOT_BYTES + w * 16384, c);
            const uint32_t z = load_afrag<8, 0>(wf, ring + slot_of(76) * SLOT_BYTES + w * 16384, c);
            row_inv(l, inv);
            release(c, BAR_EMPTY + 8 * slot_of(76) + z, 1);
            asm volatile("{\n.reg .pred p;\nsetp.eq.u32 p, %0, 0;\n@p bar.sync 4, 128;\n@!p bar.sync 5, 128;\n}\n" ::"r"(w) : "memory");
            wg_wait<0>();
            release(c, BAR_EMPTY + 8 * vslot, 1);
            fence_regs(o);
            {
                const uint32_t base = ring + slot_of(78) * SLOT_BYTES + w * 16384 + (16 * c.warp + (c.lane >> 2)) * 64 + (((c.lane ^ (c.lane >> 3)) & 3) << 4);
#pragma unroll
                for (int i = 0; i < 2; i++)
#pragma unroll
                    for (int qq = 0; qq < 4; qq++)
                        asm volatile("st.shared.v4.b32 [%0], {%1,%2,%3,%4};" ::"r"(base + qq * 4096 + i * 512),
                                     "r"(pack_bf16(o[16 * qq + 2 * i] * inv[i], o[16 * qq + 2 * i + 1] * inv[i])),
                                     "r"(pack_bf16(o[16 * qq + 4 + 2 * i] * inv[i], o[16 * qq + 4 + 2 * i + 1] * inv[i])),
                                     "r"(pack_bf16(o[16 * qq + 8 + 2 * i] * inv[i], o[16 * qq + 8 + 2 * i + 1] * inv[i])),
                                     "r"(pack_bf16(o[16 * qq + 12 + 2 * i] * inv[i], o[16 * qq + 12 + 2 * i + 1] * inv[i])) : "memory");
                asm volatile("fence.proxy.async.shared::cta;" ::: "memory");
                signal_event(c, EV_CTX + 1);
            }
        }
        }
        {
            float acc[80];
            undef_regs(acc);
            int st = 0, prev = 0; uint32_t ph3 = 0;
            auto op_stage = [&](int i) {
                mbar_wait_hot(misc + BAR_FULL3 + 8 * st, ph3);
                uint32_t base = ring + st * ST3_BYTES;
                uint64_t da = mkdesc(base + w * 8192, 16, 512, 2);
                uint64_t db = mkdesc(base + 16384, 2048, 512, 2);
                wg_fence();
#pragma unroll
                for (int k = 0; k < 4; k++) wgmma_ss_n160_ta0_tb1(acc, da + (k >> 1) * 256 + 2 * (k & 1), db + (k >> 1) * 640 + (k & 1) * 64, k ? 1 : i);
                wg_commit();
                if (i > 0) { wg_wait<1>(); if (i <= 32 - NST3) release(c, BAR_EMPTY3 + 8 * prev, 1); }
                prev = st;
                if (++st == NST3) { st = 0; ph3 ^= 1; }
            };
#pragma unroll
            for (int i = 0; i < 4; i++) { op_stage(i); store_pair(o, i, out, 4096, inv); }
            signal_event(c, EV_CTX + 3);
            const int split = w ? 32 - OP_HOLD : RES_AT;
#pragma unroll 1
            for (int i = 4; i < split; i++) op_stage(i);
            mbar_wait(misc + BAR_SEL, 0);
            const uint32_t tag = lds32(misc + MISC_EPOCH) & 1;
            const int g = c.lane >> 2, t = c.lane & 3;
            const int row = (2 * u3 + rank) * 128 + 64 * w + perm32(16 * c.warp + 8 * kap + g);
            const int col = 160 * s3 + 8 * t;
            int sel = -1;
#pragma unroll
            for (int i = 0; i < TOPC; i++) if ((int)lds32(misc + MISC_SEL + 4 * i) == row) sel = i;
            const int t256 = tid - 128;
            uint4* sendp = g_part + (size_t)cta * 2560 + t256;
            if (c.lane >= 30) stg128(sendp + 9 * 256, tag ^ 1, tag ^ 1, tag ^ 1, tag ^ 1);
            uint4 xv[5], bv[5];
#pragma unroll
            for (int i = 0; i < 5; i++) xv[i] = ldg128(P.x + (size_t)row * DM + col + 32 * i);
            uint2 stat;
            asm volatile("ld.global.cg.v2.b32 {%0,%1}, [%2];" : "=r"(stat.x), "=r"(stat.y) : "l"(g_stats + row) : "memory");
#pragma unroll
            for (int i = 0; i < 5; i++) {
                uint32_t xx[4] = {xv[i].x, xv[i].y, xv[i].z, xv[i].w};
#pragma unroll
                for (int e = 0; e < 4; e++) {
                    asm("sub.rn.bf16x2 %0, %0, %1;" : "+r"(xx[e]) : "r"(stat.x));
                    xx[e] = pack_bf16(bf_lo(xx[e]) * __uint_as_float(stat.y), bf_hi(xx[e]) * __uint_as_float(stat.y));
                }
                bv[i] = make_uint4(xx[0], xx[1], xx[2], xx[3]);
            }
            if (sel >= 0) {
#pragma unroll
                for (int i = 0; i < 5; i++) bv[i] = ldg128(g_brow + sel * DM + col + 32 * i);
            }
#pragma unroll
            for (int i = 0; i < 5; i++) asm volatile("" : "+r"(bv[i].x), "+r"(bv[i].y), "+r"(bv[i].z), "+r"(bv[i].w));
            if (w) bar_sync(4, 256);
#pragma unroll 1
            for (int i = split; i < 32; i++) op_stage(i);
            if (!w) bar_arrive(4, 256);
            wg_wait<0>();
            fence_regs(acc);
            float keep[40];
#pragma unroll
            for (int j = 0; j < 10; j++) {
                uint32_t v0 = __float_as_uint(kap ? acc[8 * j + 0] : acc[8 * j + 2]), v1 = __float_as_uint(kap ? acc[8 * j + 1] : acc[8 * j + 3]);
                uint32_t v2 = __float_as_uint(kap ? acc[8 * j + 4] : acc[8 * j + 6]), v3 = __float_as_uint(kap ? acc[8 * j + 5] : acc[8 * j + 7]);
                asm volatile("st.relaxed.gpu.global.v4.b32 [%0], {%1,%2,%3,%4};" ::"l"(sendp + j * 256),
                             "r"((v0 & ~1u) | tag), "r"((v1 & ~1u) | tag), "r"((v2 & ~1u) | tag), "r"((v3 & ~1u) | tag) : "memory");
                keep[4 * j + 0] = kap ? acc[8 * j + 2] : acc[8 * j + 0]; keep[4 * j + 1] = kap ? acc[8 * j + 3] : acc[8 * j + 1];
                keep[4 * j + 2] = kap ? acc[8 * j + 6] : acc[8 * j + 4]; keep[4 * j + 3] = kap ? acc[8 * j + 7] : acc[8 * j + 5];
            }
            signal_event(c, EV_END);
            const uint4* recvp = g_part + (size_t)partner * 2560 + t256;
            uint4 rv[10];
            int spins = 0;
            while (true) {
                uint32_t v;
                asm volatile("ld.relaxed.gpu.global.b32 %0, [%1];" : "=r"(v) : "l"(recvp + 9 * 256 + (31 - c.lane)) : "memory");
                if (__all_sync(0xffffffffu, (v & 1u) == tag) || ++spins > 2000000) break;
            }
            while (true) {
                uint32_t bad = 0u;
#pragma unroll
                for (int j = 0; j < 10; j++) {
                    asm volatile("ld.relaxed.gpu.global.v4.b32 {%0,%1,%2,%3}, [%4];"
                                 : "=r"(rv[j].x), "=r"(rv[j].y), "=r"(rv[j].z), "=r"(rv[j].w) : "l"(recvp + j * 256) : "memory");
                }
#pragma unroll
                for (int j = 0; j < 10; j++) {
                    rv[j].x ^= tag; rv[j].y ^= tag; rv[j].z ^= tag; rv[j].w ^= tag;
                    bad |= rv[j].x | rv[j].y | rv[j].z | rv[j].w;
                }
                if (__all_sync(0xffffffffu, (bad & 1u) == 0) || ++spins > 2000000) break;
            }
            uint32_t pk[20];
#pragma unroll
            for (int j = 0; j < 10; j++) {
                pk[2 * j] = pack_bf16(keep[4 * j] + __uint_as_float(rv[j].x), keep[4 * j + 1] + __uint_as_float(rv[j].y));
                pk[2 * j + 1] = pack_bf16(keep[4 * j + 2] + __uint_as_float(rv[j].z), keep[4 * j + 3] + __uint_as_float(rv[j].w));
            }
#pragma unroll
            for (int i = 0; i < 5; i++) {
                uint32_t a0 = pk[4 * i], a1 = pk[4 * i + 1], a2 = pk[4 * i + 2], a3 = pk[4 * i + 3];
                uint32_t x0 = (t & 1) ? a0 : a1, x1 = (t & 1) ? a2 : a3;
                x0 = __shfl_xor_sync(0xffffffffu, x0, 1); x1 = __shfl_xor_sync(0xffffffffu, x1, 1);
                if (t & 1) { a0 = x0; a2 = x1; } else { a1 = x0; a3 = x1; }
                x0 = (t & 2) ? a0 : a2; x1 = (t & 2) ? a1 : a3;
                x0 = __shfl_xor_sync(0xffffffffu, x0, 2); x1 = __shfl_xor_sync(0xffffffffu, x1, 2);
                if (t & 2) { a0 = x0; a1 = x1; } else { a2 = x0; a3 = x1; }
                uint32_t av[4] = {a0, a1, a2, a3};
                uint32_t xx[4] = {xv[i].x, xv[i].y, xv[i].z, xv[i].w}, bb[4] = {bv[i].x, bv[i].y, bv[i].z, bv[i].w};
                uint32_t ov[4];
#pragma unroll
                for (int e = 0; e < 4; e++) {
                    asm("add.rn.bf16x2 %0, %1, %2;" : "=r"(ov[e]) : "r"(xx[e]), "r"(av[e]));
                    asm("add.rn.bf16x2 %0, %0, %1;" : "+r"(ov[e]) : "r"(bb[e]));
                }
                stg128(P.out + (size_t)row * DM + col + 32 * i, ov[0], ov[1], ov[2], ov[3]);
            }
        }
    }
}

typedef CUresult (*EncodeFn)(CUtensorMap*, CUtensorMapDataType, cuuint32_t, void*, const cuuint64_t*, const cuuint64_t*, const cuuint32_t*,
                             const cuuint32_t*, CUtensorMapInterleave, CUtensorMapSwizzle, CUtensorMapL2promotion, CUtensorMapFloatOOBfill);

void make_map2d(EncodeFn enc, CUtensorMap* tm, const void* p, uint64_t cols, uint64_t rows, uint32_t box_rows = 128) {
    cuuint64_t gd[2] = {cols, rows}, gs[1] = {cols * 2};
    cuuint32_t box[2] = {64, box_rows}, es[2] = {1, 1};
    enc(tm, CU_TENSOR_MAP_DATA_TYPE_BFLOAT16, 2, const_cast<void*>(p), gd, gs, box, es, CU_TENSOR_MAP_INTERLEAVE_NONE,
        CU_TENSOR_MAP_SWIZZLE_128B, CU_TENSOR_MAP_L2_PROMOTION_L2_128B, CU_TENSOR_MAP_FLOAT_OOB_FILL_NONE);
}

void make_map3d(EncodeFn enc, CUtensorMap* tm, const void* p, uint64_t cols, uint64_t rows, uint32_t bw, uint32_t nb) {
    cuuint64_t gd[3] = {bw, rows, cols / bw}, gs[2] = {cols * 2, bw * 2};
    cuuint32_t box[3] = {bw, 32, nb}, es[3] = {1, 1, 1};
    enc(tm, CU_TENSOR_MAP_DATA_TYPE_BFLOAT16, 3, const_cast<void*>(p), gd, gs, box, es, CU_TENSOR_MAP_INTERLEAVE_NONE,
        bw == 64 ? CU_TENSOR_MAP_SWIZZLE_128B : CU_TENSOR_MAP_SWIZZLE_64B, CU_TENSOR_MAP_L2_PROMOTION_L2_128B, CU_TENSOR_MAP_FLOAT_OOB_FILL_NONE);
}

}

extern "C" void kernel_launch(void* const* d_in, const int* in_sizes, int n_in, void* d_out, int out_size) {
    (void)in_sizes; (void)n_in; (void)out_size;
    static EncodeFn enc = nullptr;
    if (!enc) {
        void* fn = nullptr;
        cudaDriverEntryPointQueryResult qr;
        cudaGetDriverEntryPoint("cuTensorMapEncodeTiled", &fn, cudaEnableDefault, &qr);
        enc = (EncodeFn)fn;
        cudaFuncSetAttribute(fused_kernel, cudaFuncAttributeMaxDynamicSharedMemorySize, SMEM_BYTES);
    }
    CUtensorMap tmC, tmWk, tmWv, tmWq, tmWo, tmG, tmU, tmD;
    make_map2d(enc, &tmC, d_in[1], DC, SEQ);
    make_map2d(enc, &tmWq, d_in[2], 4096, DM, 64);
    make_map2d(enc, &tmWk, d_in[3], 4096, DC);
    make_map2d(enc, &tmWv, d_in[4], 4096, DC);
    make_map3d(enc, &tmWo, d_in[5], DM, 4096, 32, 5);
    make_map3d(enc, &tmG, d_in[8], FF, DM, 64, 7);
    make_map3d(enc, &tmU, d_in[9], FF, DM, 64, 7);
    make_map3d(enc, &tmD, d_in[10], DM, FF, 64, 10);
    Params P;
    P.x = (const __nv_bfloat16*)d_in[0];
    P.c = (const __nv_bfloat16*)d_in[1];
    P.wk = (const __nv_bfloat16*)d_in[3];
    P.wv = (const __nv_bfloat16*)d_in[4];
    P.wo = (const __nv_bfloat16*)d_in[5];
    P.wr = (const __nv_bfloat16*)d_in[7];
    P.out = (__nv_bfloat16*)d_out;
    fused_kernel<<<132, 384, SMEM_BYTES>>>(tmC, tmWk, tmWv, tmWq, tmWo, tmG, tmU, tmD, P);
}
```

```cpp
#include <cuda_runtime.h>
#include <cuda_bf16.h>
#include <cuda.h>
#include <stdint.h>

namespace {

constexpr int SEQ = 2048, NH = 32, DM = 640, DC = 512, FF = 1728, TOPC = 8;
constexpr int NSLOT = 7, SLOT_BYTES = 32768;
constexpr int NST3 = 6, ST3_BYTES = 36864;
constexpr int RING_BYTES = NSLOT * SLOT_BYTES;
constexpr int SMEM_BYTES = RING_BYTES + 3072;
constexpr int OP_PF = 8, PF_START = 9, LATE_AT = 18, RES_AT = 23, OP_HOLD = 4;

constexpr int BAR_FULL = 0  , BAR_EMPTY = 64  , BAR_FULL3 = 128  , BAR_EMPTY3 = 192  , BAR_DEP = 256  ,
              BAR_EV = 448  , BAR_PROG = 592  , BAR_SEL = 616, BAR_LN = 624,
              MISC_EPOCH = 640, MISC_SMID = 644  , MISC_SEL = 656, MISC_WR = 1024  ;
constexpr int D_LN = 0  , D_KV = 2  , D_WAR = 6  , D_CTX = 8  ;
constexpr int EV_KV = 0  , EV_CTX = 4  , EV_END = 8, NEV = 9;

constexpr int FL_MOE_CNT = 0, FL_MOE_DONE = 1, FL_LN = 16  , FL_KV = 32  , FL_CTX = 160  , FL_WAR = 416  , FL_TOTAL = 448;

__device__ __align__(1024) unsigned char g_K[16 * 32 * 16384];
__device__ __align__(1024) unsigned char g_V[16 * 32 * 16384];
__device__ __align__(1024) unsigned char g_ctx[NH * 32 * 16384];
__device__ __align__(1024) unsigned char g_xn[16 * 10 * 16384];
__device__ __align__(1024) uint4 g_part[128 * 10 * 256];
__device__ float g_router[SEQ];
__device__ uint2 g_stats[SEQ];
__device__ __align__(16) float g_moe_part[4 * TOPC * DM];
__device__ __align__(16) __nv_bfloat16 g_brow[TOPC * DM];
__device__ __align__(16) int g_sel[TOPC];
__device__ unsigned g_flags[FL_TOTAL * 8];
__device__ unsigned g_epoch;
__device__ unsigned g_roleq[130];
struct Params {
    const __nv_bfloat16 *x, *c, *wr, *wk, *wv, *wo;
    __nv_bfloat16* out;
};

__device__ __forceinline__ uint32_t smem_u32(const void* p) { return (uint32_t)__cvta_generic_to_shared(p); }
__device__ __forceinline__ void mbar_init(uint32_t bar, int cnt) { asm volatile("mbarrier.init.shared::cta.b64 [%0], %1;" ::"r"(bar), "r"(cnt)); }
__device__ __forceinline__ void mbar_expect_tx(uint32_t bar, uint32_t bytes) {
    asm volatile("mbarrier.arrive.expect_tx.shared::cta.b64 _, [%0], %1;" ::"r"(bar), "r"(bytes) : "memory");
}
__device__ __forceinline__ void mbar_arrive(uint32_t bar) { asm volatile("mbarrier.arrive.shared::cta.b64 _, [%0];" ::"r"(bar) : "memory"); }
__device__ __forceinline__ void mbar_arrive_cluster(uint32_t cluster_addr, uint32_t cnt) {
    asm volatile("mbarrier.arrive.shared::cluster.b64 _, [%0], %1;" ::"r"(cluster_addr), "r"(cnt) : "memory");
}
__device__ __forceinline__ uint32_t mapa(uint32_t addr, uint32_t cta) {
    uint32_t r; asm("mapa.shared::cluster.u32 %0, %1, %2;" : "=r"(r) : "r"(addr), "r"(cta)); return r;
}
__device__ __forceinline__ void mbar_wait(uint32_t bar, uint32_t parity) {
    asm volatile(
        "{\n.reg .pred p;\n.reg .u32 n;\n"
        "mov.u32 n, 0;\n"
        "LAB_WAIT:\n"
        "mbarrier.try_wait.parity.shared::cta.b64 p, [%0], %1, 100000;\n"
        "@p bra DONE;\n"
        "add.u32 n, n, 1;\n"
        "setp.lt.u32 p, n, 50000;\n"
        "@p bra LAB_WAIT;\n"
        "trap;\n"
        "DONE:\n}\n" ::"r"(bar), "r"(parity) : "memory");
}
__device__ __forceinline__ void mbar_wait_hot(uint32_t bar, uint32_t parity) {
    asm volatile("{\n.reg .pred p;\nLAB_WAIT:\nmbarrier.try_wait.parity.shared::cta.b64 p, [%0], %1;\n@!p bra LAB_WAIT;\n}\n" ::"r"(bar), "r"(parity) : "memory");
}
__device__ __forceinline__ void mbar_wait_sleep(uint32_t bar, uint32_t parity) {
    asm volatile("{\n.reg .pred p;\nLAB_WAIT:\nmbarrier.try_wait.parity.shared::cta.b64 p, [%0], %1, 100000;\n@!p bra LAB_WAIT;\n}\n" ::"r"(bar), "r"(parity) : "memory");
}
__device__ __forceinline__ void flag_wait(const unsigned* flag, unsigned target) {
    asm volatile(
        "{\n.reg .pred p;\n.reg .u32 n, v;\n.reg .s32 d;\n"
        "mov.u32 n, 0;\n"
        "LAB_WAIT:\n"
        "ld.acquire.gpu.global.u32 v, [%0];\n"
        "sub.s32 d, v, %1;\n"
        "setp.ge.s32 p, d, 0;\n"
        "@p bra DONE;\n"
        "nanosleep.u32 40;\n"
        "add.u32 n, n, 1;\n"
        "setp.lt.u32 p, n, 3000000;\n"
        "@p bra LAB_WAIT;\n"
        "trap;\n"
        "DONE:\n}\n" ::"l"(flag), "r"(target) : "memory");
}
__device__ __forceinline__ void flag_signal(unsigned* flag) {
    asm volatile("red.release.gpu.global.add.u32 [%0], 1;" ::"l"(flag) : "memory");
}
__device__ __forceinline__ void fence_async_global() { asm volatile("fence.proxy.async.global;" ::: "memory"); }
__device__ __forceinline__ unsigned* flag_ptr(int idx) { return g_flags + idx * 8; }

__device__ __forceinline__ uint64_t policy_stream() {
    uint64_t p; asm("createpolicy.fractional.L2::evict_first.b64 %0, 1.0;" : "=l"(p)); return p;
}
__device__ __forceinline__ void bulk_load(uint32_t dst, const void* src, uint32_t bytes, uint32_t bar) {
    asm volatile("cp.async.bulk.shared::cluster.global.mbarrier::complete_tx::bytes [%0], [%1], %2, [%3];"
                 ::"r"(dst), "l"(src), "r"(bytes), "r"(bar) : "memory");
}
__device__ __forceinline__ void bulk_load_mc(uint32_t dst, const void* src, uint32_t bytes, uint32_t bar) {
    asm volatile("cp.async.bulk.shared::cluster.global.mbarrier::complete_tx::bytes.multicast::cluster [%0], [%1], %2, [%3], %4;"
                 ::"r"(dst), "l"(src), "r"(bytes), "r"(bar), "h"((uint16_t)3) : "memory");
}
__device__ __forceinline__ void tma2d(uint32_t dst, const CUtensorMap* tm, int c0, int c1, uint32_t bar) {
    asm volatile("cp.async.bulk.tensor.2d.shared::cluster.global.mbarrier::complete_tx::bytes [%0], [%1, {%3, %4}], [%2];"
                 ::"r"(dst), "l"(tm), "r"(bar), "r"(c0), "r"(c1) : "memory");
}
__device__ __forceinline__ void tma2d_mc(uint32_t dst, const CUtensorMap* tm, int c0, int c1, uint32_t bar) {
    asm volatile("cp.async.bulk.tensor.2d.shared::cluster.global.mbarrier::complete_tx::bytes.multicast::cluster [%0], [%1, {%3, %4}], [%2], %5;"
                 ::"r"(dst), "l"(tm), "r"(bar), "r"(c0), "r"(c1), "h"((uint16_t)3) : "memory");
}
__device__ __forceinline__ void tma3d_mc(uint32_t dst, const CUtensorMap* tm, int c0, int c1, int c2, uint32_t bar) {
    asm volatile("cp.async.bulk.tensor.3d.shared::cluster.global.mbarrier::complete_tx::bytes.multicast::cluster [%0], [%1, {%3, %4, %5}], [%2], %6;"
                 ::"r"(dst), "l"(tm), "r"(bar), "r"(c0), "r"(c1), "r"(c2), "h"((uint16_t)3) : "memory");
}
__device__ __forceinline__ void tma3d(uint32_t dst, const CUtensorMap* tm, int c0, int c1, int c2, uint32_t bar) {
    asm volatile("cp.async.bulk.tensor.3d.shared::cluster.global.mbarrier::complete_tx::bytes.L2::cache_hint [%0], [%1, {%3, %4, %5}], [%2], %6;"
                 ::"r"(dst), "l"(tm), "r"(bar), "r"(c0), "r"(c1), "r"(c2), "l"(policy_stream()) : "memory");
}
__device__ __forceinline__ void tma2d_prefetch(const CUtensorMap* tm, int c0, int c1) {
    asm volatile("cp.async.bulk.prefetch.tensor.2d.L2.global [%0, {%1, %2}];" ::"l"(tm), "r"(c0), "r"(c1) : "memory");
}
__device__ __forceinline__ void tma3d_prefetch(const CUtensorMap* tm, int c0, int c1, int c2) {
    asm volatile("cp.async.bulk.prefetch.tensor.3d.L2.global [%0, {%1, %2, %3}];" ::"l"(tm), "r"(c0), "r"(c1), "r"(c2) : "memory");
}
__device__ __forceinline__ void l2_prefetch(const void* p, uint32_t bytes) {
    asm volatile("cp.async.bulk.prefetch.L2.global [%0], %1;" ::"l"(p), "r"(bytes) : "memory");
}
__device__ __forceinline__ bool elect_one() {
    uint32_t r; asm volatile("{\n.reg .pred p;\nelect.sync _|p, 0xffffffff;\nselp.u32 %0, 1, 0, p;\n}\n" : "=r"(r)); return r != 0;
}
__device__ __forceinline__ void wg_fence() { asm volatile("wgmma.fence.sync.aligned;" ::: "memory"); }
__device__ __forceinline__ void wg_commit() { asm volatile("wgmma.commit_group.sync.aligned;" ::: "memory"); }
template <int N> __device__ __forceinline__ void wg_wait() { asm volatile("wgmma.wait_group.sync.aligned %0;" ::"n"(N) : "memory"); }
__device__ __forceinline__ void bar_sync(int id, int n) { asm volatile("bar.sync %0, %1;" ::"r"(id), "r"(n) : "memory"); }
__device__ __forceinline__ void bar_arrive(int id, int n) { asm volatile("bar.arrive %0, %1;" ::"r"(id), "r"(n) : "memory"); }
__device__ __forceinline__ void token_wait(int w) {
    asm volatile("{\n.reg .pred p;\nsetp.eq.u32 p, %0, 0;\n@p bar.sync 1, 256;\n@!p bar.sync 2, 256;\n}\n" ::"r"(w) : "memory");
}
__device__ __forceinline__ void token_pass(int w) {
    asm volatile("{\n.reg .pred p;\nsetp.eq.u32 p, %0, 0;\n@p bar.arrive 2, 256;\n@!p bar.arrive 1, 256;\n}\n" ::"r"(w) : "memory");
}
template <int N> __device__ __forceinline__ void fence_regs(float (&a)[N]) {
#pragma unroll
    for (int i = 0; i < N; i++) asm volatile("" : "+f"(a[i])::"memory");
}
template <int N> __device__ __forceinline__ void undef_regs(float (&a)[N]) {
#pragma unroll
    for (int i = 0; i < N; i++) asm volatile("" : "=f"(a[i]));
}
__device__ __forceinline__ void ldsm4t(uint32_t& r0, uint32_t& r1, uint32_t& r2, uint32_t& r3, uint32_t addr) {
    asm volatile("ldmatrix.sync.aligned.m8n8.x4.trans.shared.b16 {%0,%1,%2,%3}, [%4];"
                 : "=r"(r0), "=r"(r1), "=r"(r2), "=r"(r3) : "r"(addr) : "memory");
}
__device__ __forceinline__ uint32_t pack_bf16(float lo, float hi) {
    uint32_t r; asm("cvt.rn.bf16x2.f32 %0, %1, %2;" : "=r"(r) : "f"(hi), "f"(lo)); return r;
}
__device__ __forceinline__ float bf_lo(uint32_t v) { return __uint_as_float(v << 16); }
__device__ __forceinline__ float bf_hi(uint32_t v) { return __uint_as_float(v & 0xffff0000u); }
__device__ __forceinline__ float bf_round(float v) { return __bfloat162float(__float2bfloat16_rn(v)); }
__device__ __forceinline__ float ex2(float v) { float r; asm("ex2.approx.ftz.f32 %0, %1;" : "=f"(r) : "f"(v)); return r; }
__device__ __forceinline__ void ex2v(float& v) { asm volatile("ex2.approx.ftz.f32 %0, %0;" : "+f"(v)); }
__device__ __forceinline__ float rcp_fast(float v) { float r; asm("rcp.approx.ftz.f32 %0, %1;" : "=f"(r) : "f"(v)); return r; }
__device__ __forceinline__ float sqrt_fast(float v) { float r; asm("sqrt.approx.ftz.f32 %0, %1;" : "=f"(r) : "f"(v)); return r; }
__device__ __forceinline__ void stg128(void* p, uint32_t a, uint32_t b, uint32_t c, uint32_t d) {
    asm volatile("st.global.v4.b32 [%0], {%1,%2,%3,%4};" ::"l"(p), "r"(a), "r"(b), "r"(c), "r"(d) : "memory");
}
__device__ __forceinline__ uint4 ldg128(const void* p) {
    uint4 v; asm volatile("ld.global.cg.v4.b32 {%0,%1,%2,%3}, [%4];" : "=r"(v.x), "=r"(v.y), "=r"(v.z), "=r"(v.w) : "l"(p) : "memory"); return v;
}
__device__ __forceinline__ uint64_t mkdesc(uint32_t addr, uint32_t lbo, uint32_t sbo, uint32_t swz) {
    uint32_t lo = ((addr & 0x3FFFF) >> 4) | ((lbo >> 4) << 16);
    uint32_t hi = (sbo >> 4) | (swz << 30);
    return ((uint64_t)hi << 32) | lo;
}
__device__ __forceinline__ int perm32(int v) { return (v & ~30) | ((v >> 2) & 6) | ((v << 2) & 24); }

__device__ __forceinline__ void wgmma_rs_n128_ta0_tb0(float (&d)[64], uint32_t a0, uint32_t a1, uint32_t a2, uint32_t a3, uint64_t descB, int scaleD) {
  asm volatile("{\n.reg .pred p;\nsetp.ne.b32 p, %69, 0;\n"
    "wgmma.mma_async.sync.aligned.m64n128k16.f32.bf16.bf16 "
    "{%0, %1, %2, %3, %4, %5, %6, %7, %8, %9, %10, %11, %12, %13, %14, %15, %16, %17, %18, %19, %20, %21, %22, %23, %24, %25, %26, %27, %28, %29, %30, %31, %32, %33, %34, %35, %36, %37, %38, %39, %40, %41, %42, %43, %44, %45, %46, %47, %48, %49, %50, %51, %52, %53, %54, %55, %56, %57, %58, %59, %60, %61, %62, %63}, "
    "{%64, %65, %66, %67}, %68, p, 1, 1, 0;\n}\n"
    : "+f"(d[0]), "+f"(d[1]), "+f"(d[2]), "+f"(d[3]), "+f"(d[4]), "+f"(d[5]), "+f"(d[6]), "+f"(d[7]), "+f"(d[8]), "+f"(d[9]), "+f"(d[10]), "+f"(d[11]), "+f"(d[12]), "+f"(d[13]), "+f"(d[14]), "+f"(d[15]), "+f"(d[16]), "+f"(d[17]), "+f"(d[18]), "+f"(d[19]), "+f"(d[20]), "+f"(d[21]), "+f"(d[22]), "+f"(d[23]), "+f"(d[24]), "+f"(d[25]), "+f"(d[26]), "+f"(d[27]), "+f"(d[28]), "+f"(d[29]), "+f"(d[30]), "+f"(d[31]), "+f"(d[32]), "+f"(d[33]), "+f"(d[34]), "+f"(d[35]), "+f"(d[36]), "+f"(d[37]), "+f"(d[38]), "+f"(d[39]), "+f"(d[40]), "+f"(d[41]), "+f"(d[42]), "+f"(d[43]), "+f"(d[44]), "+f"(d[45]), "+f"(d[46]), "+f"(d[47]), "+f"(d[48]), "+f"(d[49]), "+f"(d[50]), "+f"(d[51]), "+f"(d[52]), "+f"(d[53]), "+f"(d[54]), "+f"(d[55]), "+f"(d[56]), "+f"(d[57]), "+f"(d[58]), "+f"(d[59]), "+f"(d[60]), "+f"(d[61]), "+f"(d[62]), "+f"(d[63])
    : "r"(a0), "r"(a1), "r"(a2), "r"(a3), "l"(descB), "r"(scaleD));
}
__device__ __forceinline__ void wgmma_rs_n128_ta0_tb1(float (&d)[64], uint32_t a0, uint32_t a1, uint32_t a2, uint32_t a3, uint64_t descB, int scaleD) {
  asm volatile("{\n.reg .pred p;\nsetp.ne.b32 p, %69, 0;\n"
    "wgmma.mma_async.sync.aligned.m64n128k16.f32.bf16.bf16 "
    "{%0, %1, %2, %3, %4, %5, %6, %7, %8, %9, %10, %11, %12, %13, %14, %15, %16, %17, %18, %19, %20, %21, %22, %23, %24, %25, %26, %27, %28, %29, %30, %31, %32, %33, %34, %35, %36, %37, %38, %39, %40, %41, %42, %43, %44, %45, %46, %47, %48, %49, %50, %51, %52, %53, %54, %55, %56, %57, %58, %59, %60, %61, %62, %63}, "
    "{%64, %65, %66, %67}, %68, p, 1, 1, 1;\n}\n"
    : "+f"(d[0]), "+f"(d[1]), "+f"(d[2]), "+f"(d[3]), "+f"(d[4]), "+f"(d[5]), "+f"(d[6]), "+f"(d[7]), "+f"(d[8]), "+f"(d[9]), "+f"(d[10]), "+f"(d[11]), "+f"(d[12]), "+f"(d[13]), "+f"(d[14]), "+f"(d[15]), "+f"(d[16]), "+f"(d[17]), "+f"(d[18]), "+f"(d[19]), "+f"(d[20]), "+f"(d[21]), "+f"(d[22]), "+f"(d[23]), "+f"(d[24]), "+f"(d[25]), "+f"(d[26]), "+f"(d[27]), "+f"(d[28]), "+f"(d[29]), "+f"(d[30]), "+f"(d[31]), "+f"(d[32]), "+f"(d[33]), "+f"(d[34]), "+f"(d[35]), "+f"(d[36]), "+f"(d[37]), "+f"(d[38]), "+f"(d[39]), "+f"(d[40]), "+f"(d[41]), "+f"(d[42]), "+f"(d[43]), "+f"(d[44]), "+f"(d[45]), "+f"(d[46]), "+f"(d[47]), "+f"(d[48]), "+f"(d[49]), "+f"(d[50]), "+f"(d[51]), "+f"(d[52]), "+f"(d[53]), "+f"(d[54]), "+f"(d[55]), "+f"(d[56]), "+f"(d[57]), "+f"(d[58]), "+f"(d[59]), "+f"(d[60]), "+f"(d[61]), "+f"(d[62]), "+f"(d[63])
    : "r"(a0), "r"(a1), "r"(a2), "r"(a3), "l"(descB), "r"(scaleD));
}
__device__ __forceinline__ void wgmma_rs_n64_ta0_tb1(float (&d)[32], uint32_t a0, uint32_t a1, uint32_t a2, uint32_t a3, uint64_t descB, int scaleD) {
  asm volatile("{\n.reg .pred p;\nsetp.ne.b32 p, %37, 0;\n"
    "wgmma.mma_async.sync.aligned.m64n64k16.f32.bf16.bf16 "
    "{%0, %1, %2, %3, %4, %5, %6, %7, %8, %9, %10, %11, %12, %13, %14, %15, %16, %17, %18, %19, %20, %21, %22, %23, %24, %25, %26, %27, %28, %29, %30, %31}, "
    "{%32, %33, %34, %35}, %36, p, 1, 1, 1;\n}\n"
    : "+f"(d[0]), "+f"(d[1]), "+f"(d[2]), "+f"(d[3]), "+f"(d[4]), "+f"(d[5]), "+f"(d[6]), "+f"(d[7]), "+f"(d[8]), "+f"(d[9]), "+f"(d[10]), "+f"(d[11]), "+f"(d[12]), "+f"(d[13]), "+f"(d[14]), "+f"(d[15]), "+f"(d[16]), "+f"(d[17]), "+f"(d[18]), "+f"(d[19]), "+f"(d[20]), "+f"(d[21]), "+f"(d[22]), "+f"(d[23]), "+f"(d[24]), "+f"(d[25]), "+f"(d[26]), "+f"(d[27]), "+f"(d[28]), "+f"(d[29]), "+f"(d[30]), "+f"(d[31])
    : "r"(a0), "r"(a1), "r"(a2), "r"(a3), "l"(descB), "r"(scaleD));
}
__device__ __forceinline__ void wgmma_ss_n128_ta0_tb1(float (&d)[64], uint64_t descA, uint64_t descB, int scaleD) {
  asm volatile("{\n.reg .pred p;\nsetp.ne.b32 p, %66, 0;\n"
    "wgmma.mma_async.sync.aligned.m64n128k16.f32.bf16.bf16 "
    "{%0, %1, %2, %3, %4, %5, %6, %7, %8, %9, %10, %11, %12, %13, %14, %15, %16, %17, %18, %19, %20, %21, %22, %23, %24, %25, %26, %27, %28, %29, %30, %31, %32, %33, %34, %35, %36, %37, %38, %39, %40, %41, %42, %43, %44, %45, %46, %47, %48, %49, %50, %51, %52, %53, %54, %55, %56, %57, %58, %59, %60, %61, %62, %63}, "
    "%64, %65, p, 1, 1, 0, 1;\n}\n"
    : "+f"(d[0]), "+f"(d[1]), "+f"(d[2]), "+f"(d[3]), "+f"(d[4]), "+f"(d[5]), "+f"(d[6]), "+f"(d[7]), "+f"(d[8]), "+f"(d[9]), "+f"(d[10]), "+f"(d[11]), "+f"(d[12]), "+f"(d[13]), "+f"(d[14]), "+f"(d[15]), "+f"(d[16]), "+f"(d[17]), "+f"(d[18]), "+f"(d[19]), "+f"(d[20]), "+f"(d[21]), "+f"(d[22]), "+f"(d[23]), "+f"(d[24]), "+f"(d[25]), "+f"(d[26]), "+f"(d[27]), "+f"(d[28]), "+f"(d[29]), "+f"(d[30]), "+f"(d[31]), "+f"(d[32]), "+f"(d[33]), "+f"(d[34]), "+f"(d[35]), "+f"(d[36]), "+f"(d[37]), "+f"(d[38]), "+f"(d[39]), "+f"(d[40]), "+f"(d[41]), "+f"(d[42]), "+f"(d[43]), "+f"(d[44]), "+f"(d[45]), "+f"(d[46]), "+f"(d[47]), "+f"(d[48]), "+f"(d[49]), "+f"(d[50]), "+f"(d[51]), "+f"(d[52]), "+f"(d[53]), "+f"(d[54]), "+f"(d[55]), "+f"(d[56]), "+f"(d[57]), "+f"(d[58]), "+f"(d[59]), "+f"(d[60]), "+f"(d[61]), "+f"(d[62]), "+f"(d[63])
    : "l"(descA), "l"(descB), "r"(scaleD));
}
__device__ __forceinline__ void wgmma_ss_n160_ta0_tb1(float (&d)[80], uint64_t descA, uint64_t descB, int scaleD) {
  asm volatile("{\n.reg .pred p;\nsetp.ne.b32 p, %82, 0;\n"
    "wgmma.mma_async.sync.aligned.m64n160k16.f32.bf16.bf16 "
    "{%0, %1, %2, %3, %4, %5, %6, %7, %8, %9, %10, %11, %12, %13, %14, %15, %16, %17, %18, %19, %20, %21, %22, %23, %24, %25, %26, %27, %28, %29, %30, %31, %32, %33, %34, %35, %36, %37, %38, %39, %40, %41, %42, %43, %44, %45, %46, %47, %48, %49, %50, %51, %52, %53, %54, %55, %56, %57, %58, %59, %60, %61, %62, %63, %64, %65, %66, %67, %68, %69, %70, %71, %72, %73, %74, %75, %76, %77, %78, %79}, "
    "%80, %81, p, 1, 1, 0, 1;\n}\n"
    : "+f"(d[0]), "+f"(d[1]), "+f"(d[2]), "+f"(d[3]), "+f"(d[4]), "+f"(d[5]), "+f"(d[6]), "+f"(d[7]), "+f"(d[8]), "+f"(d[9]), "+f"(d[10]), "+f"(d[11]), "+f"(d[12]), "+f"(d[13]), "+f"(d[14]), "+f"(d[15]), "+f"(d[16]), "+f"(d[17]), "+f"(d[18]), "+f"(d[19]), "+f"(d[20]), "+f"(d[21]), "+f"(d[22]), "+f"(d[23]), "+f"(d[24]), "+f"(d[25]), "+f"(d[26]), "+f"(d[27]), "+f"(d[28]), "+f"(d[29]), "+f"(d[30]), "+f"(d[31]), "+f"(d[32]), "+f"(d[33]), "+f"(d[34]), "+f"(d[35]), "+f"(d[36]), "+f"(d[37]), "+f"(d[38]), "+f"(d[39]), "+f"(d[40]), "+f"(d[41]), "+f"(d[42]), "+f"(d[43]), "+f"(d[44]), "+f"(d[45]), "+f"(d[46]), "+f"(d[47]), "+f"(d[48]), "+f"(d[49]), "+f"(d[50]), "+f"(d[51]), "+f"(d[52]), "+f"(d[53]), "+f"(d[54]), "+f"(d[55]), "+f"(d[56]), "+f"(d[57]), "+f"(d[58]), "+f"(d[59]), "+f"(d[60]), "+f"(d[61]), "+f"(d[62]), "+f"(d[63]), "+f"(d[64]), "+f"(d[65]), "+f"(d[66]), "+f"(d[67]), "+f"(d[68]), "+f"(d[69]), "+f"(d[70]), "+f"(d[71]), "+f"(d[72]), "+f"(d[73]), "+f"(d[74]), "+f"(d[75]), "+f"(d[76]), "+f"(d[77]), "+f"(d[78]), "+f"(d[79])
    : "l"(descA), "l"(descB), "r"(scaleD));
}


template <int N> struct IC { static constexpr int value = N; };
struct Cur {
    uint32_t slot, ph;
    __device__ __forceinline__ void adv() { if (++slot == NSLOT) { slot = 0; ph ^= 1; } }
};
constexpr int E0 = 2;
__host__ __device__ constexpr uint32_t slot_of(int e) { return (e + E0) % NSLOT; }
__device__ __forceinline__ Cur cur_at(int e) { Cur c; c.slot = (e + E0) % NSLOT; c.ph = ((e + E0) / NSLOT) & 1; return c; }

__device__ __forceinline__ int kv_tile(int s) { return (0x804Cu >> (4 * s)) & 15; }
__device__ __forceinline__ int op_head(int i, int kap) { return 8 * kap + (i & 7) + 16 * (i >> 3); }

constexpr float SM_SCALE = 0.08838834764831845f * 1.4426950408889634f;

struct Ctx {
    uint32_t ring, misc;
    uint32_t rel;
    int w, warp, lane;
};
__device__ __forceinline__ void release(const Ctx& c, uint32_t off, uint32_t cnt) {
    if (c.lane < 2) mbar_arrive_cluster(c.rel + off, cnt);
}
__device__ __forceinline__ void signal_event(const Ctx& c, int ev) {
    __syncwarp();
    if (c.lane == 0) mbar_arrive(c.misc + BAR_EV + (c.w * NEV + ev) * 8);
}
template <int NK, int OFF, int N>
__device__ __forceinline__ uint32_t load_afrag(uint32_t (&a)[N], uint32_t base, const Ctx& c) {
    int r = c.lane & 7, mat = c.lane >> 3;
    uint32_t addr = base + (8 * (mat >> 1) + r) * 128 + (((2 * c.warp + (mat & 1)) ^ r) << 4);
#pragma unroll
    for (int k = 0; k < NK; k++) ldsm4t(a[OFF + 4 * k], a[OFF + 4 * k + 1], a[OFF + 4 * k + 2], a[OFF + 4 * k + 3], addr + k * 2048);
    uint32_t dep = 0;
#pragma unroll
    for (int k = 0; k < NK; k++) dep |= a[OFF + 4 * k];
    return dep & blockIdx.y;
}
__device__ __forceinline__ void tile_out(unsigned char* (&out)[2], unsigned char* dst, int row0, int perm, const Ctx& c) {
#pragma unroll
    for (int i = 0; i < 2; i++) {
        int row = row0 + 16 * c.warp + 8 * i + (c.lane >> 2);
        if (perm) row = perm32(row);
        out[i] = dst + row * 64 + (((c.lane ^ (row >> 1)) & 3) << 4);
    }
}
__device__ __forceinline__ void store_pair(const float (&a)[64], int q, unsigned char* const (&out)[2], int quarter_stride, const float (&f)[2]) {
#pragma unroll
    for (int i = 0; i < 2; i++)
        stg128(out[i] + q * quarter_stride,
               pack_bf16(a[16 * q + 2 * i] * f[i], a[16 * q + 2 * i + 1] * f[i]), pack_bf16(a[16 * q + 4 + 2 * i] * f[i], a[16 * q + 4 + 2 * i + 1] * f[i]),
               pack_bf16(a[16 * q + 8 + 2 * i] * f[i], a[16 * q + 8 + 2 * i + 1] * f[i]), pack_bf16(a[16 * q + 12 + 2 * i] * f[i], a[16 * q + 12 + 2 * i + 1] * f[i]));
}

constexpr float SAFE_SUM = 1099511627776.0f;
template <int NJ>
__device__ __forceinline__ void row_max(const float (&s)[4 * NJ], float (&mx)[2]) {
#pragma unroll
    for (int i = 0; i < 2; i++) {
        float a = fmaxf(s[2 * i], s[2 * i + 1]), b = fmaxf(s[4 + 2 * i], s[4 + 2 * i + 1]);
#pragma unroll
        for (int j = 2; j < NJ; j += 2) {
            a = fmaxf(a, fmaxf(s[4 * j + 2 * i], s[4 * j + 2 * i + 1]));
            b = fmaxf(b, fmaxf(s[4 * j + 4 + 2 * i], s[4 * j + 4 + 2 * i + 1]));
        }
        a = fmaxf(a, b);
        a = fmaxf(a, __shfl_xor_sync(0xffffffffu, a, 1));
        mx[i] = fmaxf(a, __shfl_xor_sync(0xffffffffu, a, 2));
    }
}
template <int NJ, bool SHIFT>
__device__ __forceinline__ void exp_sum(float (&s)[4 * NJ], const float (&m)[2], float& l0, float& l1) {
#pragma unroll
    for (int j = 0; j < NJ; j++) {
#pragma unroll
        for (int e = 0; e < 4; e++) s[4 * j + e] = ex2(SHIFT ? s[4 * j + e] - m[e >> 1] : s[4 * j + e]);
        l0 += s[4 * j + 0] + s[4 * j + 1]; l1 += s[4 * j + 2] + s[4 * j + 3];
    }
}
__device__ __forceinline__ void recompute_scores(float (&s)[64], const uint32_t (&q)[32], uint32_t kaddr, const Ctx& c) {
    const int r = c.lane & 7, mat = c.lane >> 3;
    const uint32_t a0 = kaddr + (8 * (mat & 1) + r) * 64 + (((mat >> 1) ^ (r >> 1)) << 4);
#pragma unroll
    for (int i = 0; i < 64; i++) s[i] = 0.f;
#pragma unroll
    for (int jp = 0; jp < 8; jp++) {
#pragma unroll
        for (int k = 0; k < 8; k++) {
            asm volatile(
                "{\n.reg .b32 b0, b1, b2, b3;\n"
                "ldmatrix.sync.aligned.m8n8.x4.trans.shared.b16 {b0,b1,b2,b3}, [%12];\n"
                "mma.sync.aligned.m16n8k16.row.col.f32.bf16.bf16.f32 {%0,%1,%2,%3}, {%8,%9,%10,%11}, {b0,b1}, {%0,%1,%2,%3};\n"
                "mma.sync.aligned.m16n8k16.row.col.f32.bf16.bf16.f32 {%4,%5,%6,%7}, {%8,%9,%10,%11}, {b2,b3}, {%4,%5,%6,%7};\n}\n"
                : "+f"(s[8 * jp]), "+f"(s[8 * jp + 1]), "+f"(s[8 * jp + 2]), "+f"(s[8 * jp + 3]),
                  "+f"(s[8 * jp + 4]), "+f"(s[8 * jp + 5]), "+f"(s[8 * jp + 6]), "+f"(s[8 * jp + 7])
                : "r"(q[4 * k]), "r"(q[4 * k + 1]), "r"(q[4 * k + 2]), "r"(q[4 * k + 3]),
                  "r"((a0 ^ ((jp & 1) << 5)) + (jp >> 1) * 8192 + k * 1024) : "memory");
        }
    }
}
__device__ __forceinline__ int mask_lim(const Ctx& c) { return perm32(16 * c.warp + (c.lane >> 2)) - 8 * (c.lane & 3); }
template <int J0>
__device__ __forceinline__ void mask_diag(float (&s)[4 * J0 + 32], const Ctx& c) {
    const int lim = mask_lim(c);
    if (c.warp < 2) {
#pragma unroll
        for (int x = 0; x < 16; x++) {
            if (2 * (x >> 2) + (x & 1) - (x & 2) > lim) s[4 * J0 + x] = -INFINITY;
            s[4 * J0 + 16 + x] = -INFINITY;
        }
    } else {
#pragma unroll
        for (int x = 0; x < 16; x++)
            if (32 + 2 * (x >> 2) + (x & 1) - (x & 2) > lim) s[4 * J0 + 16 + x] = -INFINITY;
    }
}
__device__ __forceinline__ void mask_any(float (&s)[64], int hh, const Ctx& c) {
    const int lim = mask_lim(c) + 64 * hh;
#pragma unroll
    for (int x = 0; x < 64; x++)
        if (32 * (x >> 4) + 2 * ((x >> 2) & 3) + (x & 1) - (x & 2) > lim) s[x] = -INFINITY;
}
__device__ __forceinline__ void issue_pv(float (&o)[64], const uint32_t (&p)[32], uint32_t vaddr, int acc, int mode  ) {
    uint64_t d = mkdesc(vaddr, 16, 512, 2);
    if (mode == 0) {
        wg_fence();
#pragma unroll
        for (int k = 0; k < 8; k++)
            wgmma_rs_n128_ta0_tb0(o, p[4 * k], p[4 * k + 1], p[4 * k + 2], p[4 * k + 3], d + (k >> 1) * 512 + 2 * (k & 1), k ? 1 : acc);
        wg_commit();
    } else if (mode == 1) {
        wg_fence();
#pragma unroll
        for (int k = 0; k < 4; k++) wgmma_rs_n128_ta0_tb0(o, p[4 * k], p[4 * k + 1], p[4 * k + 2], p[4 * k + 3], d + (k >> 1) * 512 + 2 * (k & 1), k != 0);
        wg_commit();
    } else {
        wg_fence();
        wgmma_rs_n128_ta0_tb0(o, p[0], p[1], p[2], p[3], d, acc);
        wg_commit();
    }
}
__device__ __forceinline__ void issue_qk(float (&s)[64], const uint32_t (&q)[32], uint32_t kaddr) {
    uint64_t d = mkdesc(kaddr, 8192, 512, 2);
    wg_fence();
#pragma unroll
    for (int k = 0; k < 8; k++) wgmma_rs_n128_ta0_tb1(s, q[4 * k], q[4 * k + 1], q[4 * k + 2], q[4 * k + 3], d + 64 * k, k != 0);
    wg_commit();
}
__device__ __forceinline__ void issue_qk_half(float (&s32)[32], const uint32_t (&q)[32], uint32_t kaddr) {
    uint64_t d = mkdesc(kaddr, 8192, 512, 2);
    wg_fence();
#pragma unroll
    for (int k = 0; k < 8; k++) wgmma_rs_n64_ta0_tb1(s32, q[4 * k], q[4 * k + 1], q[4 * k + 2], q[4 * k + 3], d + 64 * k, k != 0);
    wg_commit();
}
__device__ __forceinline__ void row_inv(const float (&l)[2], float (&inv)[2]) {
#pragma unroll
    for (int i = 0; i < 2; i++) {
        float sum = l[i];
        sum += __shfl_xor_sync(0xffffffffu, sum, 1);
        sum += __shfl_xor_sync(0xffffffffu, sum, 2);
        inv[i] = rcp_fast(sum);
    }
}

__device__ __forceinline__ const unsigned char* xn_addr(int row, int col) {
    row = perm32(row);
    return g_xn + ((row >> 7) * 10 + (col >> 6)) * 16384 + (row & 127) * 128 + ((((col & 63) >> 3) ^ (row & 7)) << 4);
}
__device__ __forceinline__ void mma16816(float (&d)[4], uint32_t a0, uint32_t a1, uint32_t a2, uint32_t a3, uint32_t b0, uint32_t b1) {
    asm volatile("mma.sync.aligned.m16n8k16.row.col.f32.bf16.bf16.f32 {%0,%1,%2,%3}, {%4,%5,%6,%7}, {%8,%9}, {%0,%1,%2,%3};"
                 : "+f"(d[0]), "+f"(d[1]), "+f"(d[2]), "+f"(d[3]) : "r"(a0), "r"(a1), "r"(a2), "r"(a3), "r"(b0), "r"(b1));
}
__device__ __forceinline__ uint32_t lds32(uint32_t addr) { uint32_t v; asm volatile("ld.shared.u32 %0, [%1];" : "=r"(v) : "r"(addr)); return v; }

__device__ __forceinline__ int fresh_lane() { int l; asm volatile("mov.u32 %0, %%laneid;" : "=r"(l)); return l; }
__device__ __forceinline__ void ln_rows(const __nv_bfloat16* x, int row0, uint32_t wr_s) {
    int lane = fresh_lane();
    int hl = lane & 15, row = row0 + (lane >> 4);
    uint32_t v[20];
#pragma unroll
    for (int i = 0; i < 5; i++) {
        const uint4 u = __ldg(reinterpret_cast<const uint4*>(x + (size_t)row * DM + 128 * i + 8 * hl));
        v[4 * i] = u.x; v[4 * i + 1] = u.y; v[4 * i + 2] = u.z; v[4 * i + 3] = u.w;
    }
    float mean = 0.f, m2 = 0.f, acc2 = 0.f;
#pragma unroll
    for (int i = 0; i < 20; i++) { mean += bf_lo(v[i]); acc2 += bf_hi(v[i]); }
    mean = (mean + acc2) * (1.0f / 40);
    acc2 = 0.f;
#pragma unroll
    for (int i = 0; i < 20; i++) {
        float d0 = __uint_as_float(__byte_perm(v[i], 0, 0x1044)) - mean, d1 = __uint_as_float(__byte_perm(v[i], 0, 0x3244)) - mean;
        m2 = fmaf(d0, d0, m2); acc2 = fmaf(d1, d1, acc2);
    }
    m2 += acc2;
    acc2 = 0.f;
#pragma unroll
    for (int o = 1; o < 16; o <<= 1) {
        float mo = __shfl_xor_sync(0xffffffffu, mean, o), qo = __shfl_xor_sync(0xffffffffu, m2, o), d = mo - mean;
        m2 = fmaf(d * d, 20.0f * o, m2 + qo);
        mean = 0.5f * (mean + mo);
    }
    const uint32_t mb2 = pack_bf16(mean, mean);
    const float inv = rcp_fast(bf_round(sqrt_fast(bf_round(bf_round(m2 * (1.0f / DM)) + 1e-5f))));
    float dot = 0.f;
    lane = fresh_lane(); hl = lane & 15; row = row0 + (lane >> 4);
    if (hl == 0) g_stats[row] = make_uint2(mb2, __float_as_uint(inv));
    unsigned char* xp = const_cast<unsigned char*>(xn_addr(row, 8 * hl));
#pragma unroll
    for (int i = 0; i < 5; i++) {
        uint32_t ww[4];
        asm volatile("ld.shared.v4.b32 {%0,%1,%2,%3}, [%4];" : "=r"(ww[0]), "=r"(ww[1]), "=r"(ww[2]), "=r"(ww[3]) : "r"(wr_s + 256 * i + 16 * hl) : "memory");
#pragma unroll
        for (int e = 0; e < 4; e++) {
            uint32_t d;
            asm("sub.rn.bf16x2 %0, %1, %2;" : "=r"(d) : "r"(v[4 * i + e]), "r"(mb2));
            d = pack_bf16(bf_lo(d) * inv, bf_hi(d) * inv);
            v[4 * i + e] = d;
            dot = fmaf(bf_lo(d), bf_lo(ww[e]), dot);
            acc2 = fmaf(bf_hi(d), bf_hi(ww[e]), acc2);
        }
        stg128(xp + i * 32768, v[4 * i], v[4 * i + 1], v[4 * i + 2], v[4 * i + 3]);
    }
    dot += acc2;
#pragma unroll
    for (int o = 8; o > 0; o >>= 1) dot += __shfl_xor_sync(0xffffffffu, dot, o);
    lane = fresh_lane();
    if ((lane & 15) == 0) g_router[row0 + (lane >> 4)] = bf_round(dot);
}

__device__ __forceinline__ void aux_cta(const CUtensorMap* tmG, const CUtensorMap* tmU, const CUtensorMap* tmD, unsigned char* sm, int a) {
    constexpr int STG = 57344, XS = 3 * STG, HS = XS + 8 * 1296, KEY = HS + 8 * 912, MI = KEY + 8192;
    const int tid = threadIdx.x, warp = __shfl_sync(0xffffffffu, tid >> 5, 0), lane = tid & 31;
    const uint32_t sb = smem_u32(sm);
    const uint32_t full = sb + MI, empty = sb + MI + 32;
    int* s_sel = reinterpret_cast<int*>(sm + MI + 64);
    float* s_r = reinterpret_cast<float*>(sm + MI + 96);
    volatile unsigned* s_misc = reinterpret_cast<volatile unsigned*>(sm + MI + 128);
    uint32_t* s_key = reinterpret_cast<uint32_t*>(sm + KEY);
    if (tid == 0) {
        for (int i = 0; i < 3; i++) { mbar_init(full + 8 * i, 1); mbar_init(empty + 8 * i, 10); }
        asm volatile("fence.mbarrier_init.release.cluster;" ::: "memory");
    }
    __syncthreads();
    if (warp == 11) {
        if (elect_one()) {
            int st = 0; uint32_t ph = 0;
#pragma unroll 1
            for (int s = 0; s < 34; s++) {
                mbar_wait(empty + 8 * st, ph ^ 1);
                const uint32_t dst = sb + st * STG, fb = full + 8 * st;
                if (s < 20) {
                    mbar_expect_tx(fb, 57344);
                    tma3d(dst, tmG, 0, 32 * s, 7 * a, fb);
                    tma3d(dst + 28672, tmU, 0, 32 * s, 7 * a, fb);
                } else {
                    mbar_expect_tx(fb, 40960);
                    tma3d(dst, tmD, 0, 448 * a + 32 * (s - 20), 0, fb);
                }
                if (s >= 3) {
#pragma unroll 1
                    for (int f = (s == 3 ? 4 : s + 6); f <= s + 6 && f < 34; f++) {
                        if (f < 20) { tma3d_prefetch(tmG, 0, 32 * f, 7 * a); tma3d_prefetch(tmU, 0, 32 * f, 7 * a); }
                        else tma3d_prefetch(tmD, 0, 448 * a + 32 * (f - 20), 0);
                    }
                }
                if (++st == 3) { st = 0; ph ^= 1; }
            }
        }
        return;
    }
    if (warp == 10) return;
    if (tid < 8) {
        unsigned e = *reinterpret_cast<volatile unsigned*>(&g_epoch);
        if (tid == 0) s_misc[0] = e;
        flag_wait(flag_ptr(FL_LN + tid), (e + 1) * (tid < 4 ? 33u : 128u));
    }
    bar_sync(1, 320);
    const unsigned ep = s_misc[0];
    auto top8 = [&](uint32_t (&key)[8]) {
        uint32_t mine = 0;
#pragma unroll 1
        for (int r = 0; r < TOPC; r++) {
            uint32_t best = 0;
#pragma unroll
            for (int i = 0; i < 8; i++) best = max(best, key[i]);
            best = __reduce_max_sync(0xffffffffu, best);
#pragma unroll
            for (int i = 0; i < 8; i++) if (key[i] == best) key[i] = 0;
            if (lane == r) mine = best;
        }
        return mine;
    };
#pragma unroll 1
    for (int pass = 0; pass < 2; pass++) {
        if (warp < (pass ? 1 : 8)) {
            uint32_t key[8];
#pragma unroll
            for (int i = 0; i < 8; i++) {
                if (pass == 0) {
                    int idx = warp * 256 + i * 32 + lane;
                    uint32_t b = __float_as_uint(__ldcg(g_router + idx)) >> 16;
                    b = (b & 0x8000u) ? (~b & 0xffffu) : (b | 0x8000u);
                    key[i] = (b << 16) | (uint32_t)(0xffff - idx);
                } else key[i] = i < 2 ? s_key[i * 32 + lane] : 0u;
            }
            uint32_t best = top8(key);
            if (lane < TOPC) {
                if (pass == 0) s_key[warp * 8 + lane] = best;
                else {
                    uint32_t b = best >> 16;
                    b = (b & 0x8000u) ? (b & 0x7fffu) : (~b & 0xffffu);
                    s_sel[lane] = 0xffff - (int)(best & 0xffffu);
                    s_r[lane] = bf_round(rcp_fast(1.0f + __expf(fminf(-__uint_as_float(b << 16), 80.f))));
                }
            }
        }
        bar_sync(1, 320);
    }
#pragma unroll 1
    for (int it = 0; it < 2; it++) {
        int i = tid + it * 320, tk = i / 80, ch = i % 80;
        *reinterpret_cast<uint4*>(sm + XS + tk * 1296 + ch * 16) = __ldcg(reinterpret_cast<const uint4*>(xn_addr(s_sel[tk], ch * 8)));
    }
    bar_sync(1, 320);
    const int g = lane >> 2, t = lane & 3;
    const uint32_t woff = warp * 4096 + (8 * (lane >> 4) + (lane & 7)) * 128 + ((((lane >> 3) & 1) ^ (lane & 7)) << 4);
    int st = 0; uint32_t ph = 0;
    float ga[4][4], ua[4][4];
#pragma unroll
    for (int i = 0; i < 4; i++)
#pragma unroll
        for (int e = 0; e < 4; e++) { ga[i][e] = 0.f; ua[i][e] = 0.f; }
#pragma unroll 1
    for (int s = 0; s < 34; s++) {
        if (s == 20) {
            if (warp < 7) {
#pragma unroll 1
                for (int i = 0; i < 4; i++) {
#pragma unroll
                    for (int e = 0; e < 4; e++) {
                        float gv = bf_round(ga[0][e]), uv = bf_round(ua[0][e]);
                        float sg = bf_round(gv * rcp_fast(1.0f + __expf(fminf(-gv, 80.f))));
                        int f = warp * 64 + i * 16 + g + 8 * (e >> 1), tk = 2 * t + (e & 1);
                        *reinterpret_cast<__nv_bfloat16*>(sm + HS + tk * 912 + f * 2) = __float2bfloat16_rn(sg * uv);
                        ga[0][e] = ga[1][e]; ga[1][e] = ga[2][e]; ga[2][e] = ga[3][e]; ga[3][e] = 0.f;
                        ua[0][e] = ua[1][e]; ua[1][e] = ua[2][e]; ua[2][e] = ua[3][e];
                    }
                }
            }
            bar_sync(1, 320);
        }
        mbar_wait(full + 8 * st, ph);
        if (s >= 20 || warp < 7) {
#pragma unroll
            for (int kk = 0; kk < 2; kk++) {
                uint32_t xb = sb + (s < 20 ? XS + g * 1296 + s * 64 : HS + g * 912 + (s - 20) * 64) + 32 * kk + 4 * t;
                uint32_t b0 = lds32(xb), b1 = lds32(xb + 16);
                uint32_t wa = sb + st * STG + woff + kk * 2048;
#pragma unroll
                for (int i = 0; i < 4; i++) {
                    uint32_t a0, a1, a2, a3;
                    ldsm4t(a0, a1, a2, a3, wa ^ (i << 5));
                    mma16816(ga[i], a0, a1, a2, a3, b0, b1);
                    if (s < 20) {
                        ldsm4t(a0, a1, a2, a3, (wa ^ (i << 5)) + 28672);
                        mma16816(ua[i], a0, a1, a2, a3, b0, b1);
                    }
                }
            }
        }
        asm volatile("fence.proxy.async.shared::cta;" ::: "memory");
        __syncwarp();
        if (lane == 0) mbar_arrive(empty + 8 * st);
        if (++st == 3) { st = 0; ph ^= 1; }
    }
#pragma unroll
    for (int i = 0; i < 4; i++)
#pragma unroll
        for (int e = 0; e < 4; e += 2)
            *reinterpret_cast<float2*>(g_moe_part + (a * DM + warp * 64 + i * 16 + g + 4 * e) * 8 + 2 * t) = make_float2(ga[i][e], ga[i][e + 1]);
    bar_sync(1, 320);
    if (tid == 0) {
        __threadfence();
        unsigned old = atomicAdd(flag_ptr(FL_MOE_CNT), 1u);
        s_misc[1] = (old == ep * 4u + 3u);
        __threadfence();
    }
    bar_sync(1, 320);
    if (s_misc[1]) {
        const float4* pp = reinterpret_cast<const float4*>(g_moe_part);
#pragma unroll 1
        for (int i = tid; i < DM * 2; i += 320) {
            float4 v0 = __ldcg(pp + i), v1 = __ldcg(pp + DM * 2 + i), v2 = __ldcg(pp + DM * 4 + i), v3 = __ldcg(pp + DM * 6 + i);
            float y[4] = {v0.x + v1.x + v2.x + v3.x, v0.y + v1.y + v2.y + v3.y, v0.z + v1.z + v2.z + v3.z, v0.w + v1.w + v2.w + v3.w};
#pragma unroll
            for (int e = 0; e < 4; e++) {
                int col = i >> 1, tk = (i & 1) * 4 + e;
                float upd = bf_round(bf_round(y[e]) * s_r[tk]);
                float xn = __bfloat162float(*reinterpret_cast<const __nv_bfloat16*>(sm + XS + tk * 1296 + col * 2));
                g_brow[tk * DM + col] = __float2bfloat16_rn(xn + upd);
            }
        }
        if (tid < TOPC) g_sel[tid] = s_sel[tid];
        bar_sync(1, 320);
        if (tid == 0) {
            flag_signal(flag_ptr(FL_MOE_DONE));
            *reinterpret_cast<volatile unsigned*>(&g_epoch) = ep + 1;
        }
    }
}

__global__ void __cluster_dims__(2, 1, 1) __launch_bounds__(384, 1)
fused_kernel(const __grid_constant__ CUtensorMap tmC, const __grid_constant__ CUtensorMap tmWk, const __grid_constant__ CUtensorMap tmWv,
             const __grid_constant__ CUtensorMap tmWq, const __grid_constant__ CUtensorMap tmWo,
             const __grid_constant__ CUtensorMap tmG, const __grid_constant__ CUtensorMap tmU, const __grid_constant__ CUtensorMap tmD, const Params P) {
    extern __shared__ __align__(1024) unsigned char smem_raw[];
    const uint32_t ring = smem_u32(smem_raw);
    const uint32_t misc = ring + RING_BYTES;
    const int tid = threadIdx.x;
    const int rank = blockIdx.x & 1;
    uint32_t smid, nsm;
    asm("mov.u32 %0, %%smid;" : "=r"(smid));
    asm("mov.u32 %0, %%nsmid;" : "=r"(nsm));
    if (nsm != 132) smid = blockIdx.x;
    auto role_of = [](int tpc) {
        return tpc < 32 ? (tpc & 7) * 8 + (tpc >> 3) : tpc < 60 ? (1 + (tpc - 32) % 7) * 8 + 4 + (tpc - 32) / 7 : tpc < 64 ? tpc - 56 : tpc;
    };
    int mc = role_of(smid >> 1);

    auto prefetch_w = [&](int ch) {
        const int i = tid - 128;
        asm volatile("prefetch.global.L2 [%0];" ::"l"((rank ? P.wv : P.wk) + (size_t)(ch * 128 + (mc & 3) * 32 + (i >> 3)) * 4096 + (mc >> 2) * 128 + (i & 7) * 16));
    };
    if (tid >= 128 && mc < 64) {
        if (tid < 256) asm volatile("prefetch.global.L2 [%0];" ::"l"(P.c + (size_t)((12 + (mc & 3)) * 128 + ((mc >> 2) * 2 + rank) * 4) * DC + (tid - 128) * 16));
        prefetch_w(0);
    }
    auto load_w0 = [&]() {
        const CUtensorMap* tw = rank ? &tmWv : &tmWk;
        mbar_expect_tx(misc + BAR_FULL + 8 * slot_of(0), SLOT_BYTES);
        tma2d(ring + slot_of(0) * SLOT_BYTES, tw, (mc >> 2) * 128, 0, misc + BAR_FULL + 8 * slot_of(0));
        tma2d(ring + slot_of(0) * SLOT_BYTES + 16384, tw, (mc >> 2) * 128 + 64, 0, misc + BAR_FULL + 8 * slot_of(0));
    };
    if (tid == 0) {
#pragma unroll
        for (int i = 0; i < NSLOT; i++) mbar_init(misc + BAR_FULL + 8 * i, 1);
#pragma unroll
        for (int i = 0; i < E0; i++) mbar_arrive(misc + BAR_FULL + 8 * i);
        asm volatile("fence.mbarrier_init.release.cluster;" ::: "memory");
        if (mc < 64) load_w0();
    }
    if (tid == 160) {
        asm volatile("st.shared.u32 [%0], %1;" ::"r"(misc + MISC_SMID), "r"(smid) : "memory");
        asm volatile("fence.release.sync_restrict::shared::cta.cluster;" ::: "memory");
    }
    if (tid == 32) {
        asm volatile("prefetch.tensormap [%0];" ::"l"(&tmC) : "memory");
#pragma unroll
        for (int i = 0; i < NSLOT; i++) mbar_init(misc + BAR_EMPTY + 8 * i, 16);
#pragma unroll
        for (int i = 0; i < E0; i++) mbar_arrive_cluster(misc + BAR_EMPTY + 8 * i, 16);
        asm volatile("fence.mbarrier_init.release.cluster;" ::: "memory");
    }
    if (tid == 64) {
#pragma unroll
        for (int i = 0; i < NST3; i++) { mbar_init(misc + BAR_FULL3 + 8 * i, 1); mbar_init(misc + BAR_EMPTY3 + 8 * i, 16); }
#pragma unroll
        for (int i = 0; i < 4; i++) mbar_init(misc + BAR_PROG + 8 * i, 1);
        mbar_init(misc + BAR_LN, 2);
        asm volatile("fence.mbarrier_init.release.cluster;" ::: "memory");
    }
    if (tid == 96) {
#pragma unroll
        for (int i = 0; i < 24; i++) mbar_init(misc + BAR_DEP + 8 * i, 1);
    }
    if (tid == 128) {
#pragma unroll
        for (int i = 0; i < 2 * NEV; i++) mbar_init(misc + BAR_EV + 8 * i, 4);
    }
    __syncthreads();
    asm volatile("barrier.cluster.arrive.relaxed.aligned;\nbarrier.cluster.wait.aligned;" ::: "memory");
    {
        uint32_t peer;
        asm volatile("{\n.reg .b32 r, a;\nmov.u32 r, %%cluster_ctarank;\nxor.b32 r, r, 1;\nmapa.shared::cluster.u32 a, %1, r;\n"
                     "ld.shared::cluster.u32 %0, [a];\n}\n" : "=r"(peer) : "r"(misc + MISC_SMID) : "memory");
        if ((__shfl_sync(0xffffffffu, peer, 0) ^ smid) != 1) {
            if (tid == 0) {
                const unsigned ep1 = *reinterpret_cast<volatile unsigned*>(&g_epoch) + 1;
                if ((smid & 1) == 0) atomicExch(g_roleq + 2 + (atomicAdd(g_roleq, 1u) & 127), (ep1 << 8) | (smid >> 1));
                if (rank == 0) {
                    unsigned* slot = g_roleq + 2 + (atomicAdd(g_roleq + 1, 1u) & 127);
                    unsigned v = 0;
                    for (int spin = 0; spin < 4000000 && ((v = atomicAdd(slot, 0u)) >> 8) != (ep1 & 0xffffffu); spin++) {}
                    asm volatile("st.shared::cluster.u32 [%0], %1;" ::"r"(mapa(misc + MISC_SMID + 4, 0)), "r"(v & 255) : "memory");
                    asm volatile("st.shared::cluster.u32 [%0], %1;" ::"r"(mapa(misc + MISC_SMID + 4, 1)), "r"(v & 255) : "memory");
                }
                if (mc < 64) {
                    mbar_wait(misc + BAR_FULL + 8 * slot_of(0), 0);
                    asm volatile("mbarrier.inval.shared::cta.b64 [%0];" ::"r"(misc + BAR_FULL + 8 * slot_of(0)) : "memory");
                    mbar_init(misc + BAR_FULL + 8 * slot_of(0), 1);
                    asm volatile("fence.mbarrier_init.release.cluster;" ::: "memory");
                }
            }
            __syncwarp();
            asm volatile("barrier.cluster.arrive.aligned;\nbarrier.cluster.wait.aligned;" ::: "memory");
            mc = role_of(__shfl_sync(0xffffffffu, lds32(misc + MISC_SMID + 4), 0));
            if (tid == 0 && mc < 64) load_w0();
            __syncwarp();
        }
    }
    const int cta = mc * 2 + rank;
    const bool aux = mc >= 64;
    const int team = mc >> 2, k = mc & 3;
    const int u3 = (mc >> 4) * 2 + (team & 1), s3 = k, kap = (mc >> 3) & 1;
    const int partner = cta ^ 16;
    const int b0 = k, b1 = 7 - k;
    if (tid >= 128 && !aux) prefetch_w(1);
    if (tid == 256 && !aux) {
        const CUtensorMap* tw = rank ? &tmWv : &tmWk;
#pragma unroll
        for (int e = 1; e < NSLOT; e++) {
            const uint32_t fb = misc + BAR_FULL + 8 * slot_of(e), dst = ring + slot_of(e) * SLOT_BYTES;
            mbar_expect_tx(fb, SLOT_BYTES);
            if (e & 1) tma2d_mc(dst + rank * 16384, &tmC, (e >> 1) * 128 + rank * 64, (12 + k) * 128, fb);
            else { tma2d(dst, tw, team * 128, e * 64, fb); tma2d(dst + 16384, tw, team * 128 + 64, e * 64, fb); }
        }
    }
    const int wg = __shfl_sync(0xffffffffu, tid >> 7, 0);

    if (wg == 0 || aux) {
        asm volatile("setmaxnreg.dec.sync.aligned.u32 40;");
        const int warp = __shfl_sync(0xffffffffu, tid >> 5, 0), lane = tid & 31;
        if (warp == 0 && !aux) {
            const bool lead = elect_one();
            Cur c = cur_at(NSLOT);
            uint32_t dst, fb;
            auto acquire = [&]() {
                mbar_wait_sleep(misc + BAR_EMPTY + 8 * c.slot, c.ph ^ 1);
                fb = misc + BAR_FULL + 8 * c.slot; dst = ring + c.slot * SLOT_BYTES;
                if (lead) mbar_expect_tx(fb, SLOT_BYTES);
                c.adv();
            };
            auto load_w = [&](const CUtensorMap* tm, int col, int row) {
                acquire();
                if (lead) { tma2d(dst, tm, col, row, fb); tma2d(dst + 16384, tm, col + 64, row, fb); }
            };
            auto load_half = [&](const unsigned char* src) {
                acquire();
                if (lead) bulk_load_mc(dst + rank * 16384, src, 16384, fb);
            };
            auto dep_wait = [&](int d) { mbar_wait_sleep(misc + BAR_DEP + 8 * d, 0); fence_async_global(); };
            auto op_prefetch = [&](int i) {
                const int head = op_head(i, kap);
                l2_prefetch(reinterpret_cast<const unsigned char*>(P.wo) + head * 163840 + (u3 * 8 + s3 * 2 + rank) * 2560, 2560);
                if (i < 8) l2_prefetch(g_ctx + (size_t)(head * 32 + 4 * u3 + 2 * rank) * 16384 + s3 * 8192, 8192);
            };
            if (lead) l2_prefetch(reinterpret_cast<const unsigned char*>(P.c) + (size_t)cta * 12288, 12288);
            const CUtensorMap* tw = rank ? &tmWv : &tmWk;
            const unsigned char* Kh = g_K + (size_t)team * 32 * 16384 + rank * 16384;
            const unsigned char* Vh = g_V + (size_t)team * 32 * 16384 + rank * 16384;
#pragma unroll 1
            for (int v = 0; v < 2; v++) {
                const int h = team + 16 * v;
#pragma unroll 1
                for (int i = v ? 0 : 3; i < 16; i++) {
                    if (i < 4 && v) load_w(tw, h * 128, i * 128);
                    if (v && i == 3 && lead) mbar_arrive(misc + BAR_PROG + 8);
                    if (v && (i == 3 || i == 7)) dep_wait(D_WAR + (i > 3));
                    acquire();
                    if (lead) tma2d_mc(dst + rank * 16384, &tmC, (i & 3) * 128 + rank * 64, (kv_tile(i >> 2) + k) * 128, fb);
                    if (i == 8 && lead) {
                        tma2d_prefetch(&tmWq, h * 128 + rank * 64, k * 64); tma2d_prefetch(&tmWq, h * 128 + rank * 64, k * 64 + 256);
                        if (k < 2) tma2d_prefetch(&tmWq, h * 128 + rank * 64, k * 64 + 512);
                    }
                }
                int togo = v ? PF_START : 11;
#pragma unroll 1
                for (int r = 0; r < 2; r++) {
                    const int p = r ? b1 : b0, n = 2 * p + 1;
                    if (v == 0) dep_wait(D_LN + r);
                    const int g0 = r ? rank ^ 1 : 3 - rank, g1 = 3 - g0;
                    const unsigned char* x0 = g_xn + (2 * p + (g0 >> 1)) * 163840 + (g0 & 1) * 8192;
                    const unsigned char* x1 = g_xn + (2 * p + (g1 >> 1)) * 163840 + (g1 & 1) * 8192;
#pragma unroll 1
                    for (int kc = 0; kc < 10; kc++) {
                        acquire();
                        if (lead) {
                            tma2d_mc(dst + 16384 + rank * 8192, &tmWq, h * 128 + rank * 64, kc * 64, fb);
                            bulk_load(dst, x0 + kc * 16384, 8192, fb);
                            bulk_load(dst + 8192, x1 + kc * 16384, 8192, fb);
                        }
                    }
                    dep_wait(D_KV + 2 * v + r);
                    load_half(Kh + n * 32768);
#pragma unroll 1
                    for (int j = n - 1; j >= 0; j--) {
                        load_half(Kh + j * 32768); load_half(Vh + (j + 1) * 32768);
                        if (v == 0 && r && j == 7 && lead) mbar_arrive(misc + BAR_PROG);
                        --togo;
                        if (v == 0 && togo == 0 && lead) {
                            tma2d_prefetch(tw, h * 128 + 2048, k * 128); tma2d_prefetch(tw, h * 128 + 2112, k * 128);
                            l2_prefetch(reinterpret_cast<const unsigned char*>(P.c) + (size_t)cta * 16384, 16384);
                        }
                        if (v && togo <= 0 && togo > -OP_PF && lead) op_prefetch(-togo);
                    }
                    load_half(Vh);
                }
            }
            mbar_wait_sleep(misc + BAR_EMPTY + 8 * c.slot, c.ph ^ 1); c.adv();
            int st = 0; uint32_t ph3 = 0;
#pragma unroll 1
            for (int i = 0; i < 32; i++) {
                const int head = op_head(i >> 1, kap);
                if ((i & 1) == 0) dep_wait(D_CTX + (i >> 1));
                if (i < NST3) { mbar_wait_sleep(misc + BAR_EMPTY + 8 * c.slot, c.ph ^ 1); c.adv(); }
                else mbar_wait_sleep(misc + BAR_EMPTY3 + 8 * st, ph3 ^ 1);
                fb = misc + BAR_FULL3 + 8 * st; dst = ring + st * ST3_BYTES;
                if (i == LATE_AT && lead) mbar_arrive(misc + BAR_PROG + 16);
                if (lead) {
                    mbar_expect_tx(fb, ST3_BYTES);
                    const unsigned char* src = g_ctx + (size_t)(head * 32 + 4 * u3 + 2 * rank) * 16384 + (i & 1) * 8192;
                    bulk_load(dst, src, 8192, fb);
                    bulk_load(dst + 8192, src + 16384, 8192, fb);
                    tma3d_mc(dst + 16384 + rank * 10240, &tmWo, 0, head * 128 + (i & 1) * 64 + rank * 32, 5 * s3, fb);
                    if ((i & 1) && (i >> 1) + OP_PF < 16) op_prefetch((i >> 1) + OP_PF);
                }
                if (++st == NST3) { st = 0; ph3 ^= 1; }
            }
        } else {
        if (warp >= 1 && warp <= 3 && lane < 27 && (warp - 1) * 27 + lane < 80) {
            const int ch = (warp - 1) * 27 + lane;
            uint4 u = __ldg(reinterpret_cast<const uint4*>(P.wr) + ch);
            asm volatile("st.shared.v4.b32 [%0], {%1,%2,%3,%4};" ::"r"(misc + MISC_WR + 16 * ch), "r"(u.x), "r"(u.y), "r"(u.z), "r"(u.w) : "memory");
        }
        bar_sync(3, aux ? 384 : 96);
        const int nln = aux ? (warp < 8 ? 3 : 2) : (warp == 3 ? 1 : 3), rstep = aux ? 24 : -512;
        int lrow = aux ? (cta - 128) * 256 + 192 + 2 * warp : (cta >> 5) * 256 + (cta & 31) * 6 + (warp - 1) * 2;
        int lnext = aux ? lrow + 24 : 1536 + cta * 4 + (warp - 1) * 2;
#pragma unroll 1
        for (int t = 0; t < nln; t++) {
            if (t + 1 < nln) {
                const int ll = fresh_lane();
#pragma unroll
                for (int i = 0; i < 3; i++)
                    if (i * 32 + ll < 80) asm volatile("prefetch.global.L2 [%0];" ::"l"(P.x + (size_t)lnext * DM + (i * 32 + ll) * 16));
            }
            ln_rows(P.x, lrow, misc + MISC_WR);
            __syncwarp();
            if (fresh_lane() == 0 && warp < 3 && !aux) {
                if (t) flag_signal(flag_ptr(FL_LN + (lrow >> 8))); else mbar_arrive(misc + BAR_LN);
            }
            lrow = lnext; lnext += rstep;
        }
        if (aux) {
            bar_sync(3, 384);
            if (tid == 320) flag_signal(flag_ptr(FL_LN + cta - 128));
            __syncwarp();
            asm volatile("setmaxnreg.inc.sync.aligned.u32 128;");
            aux_cta(&tmG, &tmU, &tmD, smem_raw, cta - 128);
        } else
        if (warp == 3) {
            const unsigned ep1 = *reinterpret_cast<volatile unsigned*>(&g_epoch) + 1;
            if (lane == 0) {
                asm volatile("st.shared.u32 [%0], %1;" ::"r"(misc + MISC_EPOCH), "r"(ep1) : "memory");
                mbar_wait(misc + BAR_LN, 0);
                flag_signal(flag_ptr(FL_LN + (cta >> 5)));
                flag_wait(flag_ptr(FL_LN + b0), ep1 * 33u);
                mbar_arrive(misc + BAR_DEP + 8 * D_LN);
#pragma unroll 1
                for (int i = 0; i < 4; i++) {
                    mbar_wait(misc + BAR_EV + 8 * (NEV + EV_KV + i), 0);
                    if (i < 2) {
                        mbar_wait(misc + BAR_EV + 8 * (EV_KV + i), 0);
                        asm volatile("red.release.gpu.global.add.u32 [%0], 2;" ::"l"(flag_ptr(FL_KV + team * 8 + i)) : "memory");
                    }
                    if (i == 1) {
                        flag_wait(flag_ptr(FL_LN + b1), ep1 * 128u);
                        mbar_arrive(misc + BAR_DEP + 8 * (D_LN + 1));
                    }
                    flag_wait(flag_ptr(FL_KV + team * 8 + i), ep1 * 16u);
                    mbar_arrive(misc + BAR_DEP + 8 * (D_KV + i));
                    if (i == 1) {
#pragma unroll 1
                        for (int j = 0; j < 2; j++) {
                            mbar_wait(misc + BAR_PROG + 8 * j, 0);
                            asm volatile("red.relaxed.gpu.global.add.u32 [%0], 1;" ::"l"(flag_ptr(FL_WAR + 2 * team + j)) : "memory");
                            flag_wait(flag_ptr(FL_WAR + 2 * team + j), ep1 * 8u);
                            mbar_arrive(misc + BAR_DEP + 8 * (D_WAR + j));
                        }
                    }
                }
                flag_wait(flag_ptr(FL_MOE_DONE), ep1);
                int4 s0 = __ldcg(reinterpret_cast<const int4*>(g_sel)), s1 = __ldcg(reinterpret_cast<const int4*>(g_sel) + 1);
                asm volatile("st.shared.v4.u32 [%0], {%1,%2,%3,%4};" ::"r"(misc + MISC_SEL), "r"(s0.x), "r"(s0.y), "r"(s0.z), "r"(s0.w) : "memory");
                asm volatile("st.shared.v4.u32 [%0], {%1,%2,%3,%4};" ::"r"(misc + MISC_SEL + 16), "r"(s1.x), "r"(s1.y), "r"(s1.z), "r"(s1.w) : "memory");
                mbar_arrive(misc + BAR_SEL);
            }
            __syncwarp();
            const unsigned* cf = flag_ptr(FL_CTX + op_head(lane & 15, kap) * 8 + u3);
#pragma unroll 1
            for (int half = 0; half < 2; half++) {
                if (half) mbar_wait(misc + BAR_EV + 8 * (EV_CTX + 3), 0);
                bool done = (lane >> 3) != half;
                for (int spin = 0; spin < 4000000; spin++) {
                    if (!done) {
                        unsigned v;
                        asm volatile("ld.acquire.gpu.global.u32 %0, [%1];" : "=r"(v) : "l"(cf) : "memory");
                        if ((int)(v - ep1 * 4u) >= 0) { mbar_arrive(misc + BAR_DEP + 8 * (D_CTX + lane)); done = true; }
                    }
                    if (__all_sync(0xffffffffu, done)) break;
                    __nanosleep(64);
                }
            }
        } else {
            const int w = warp - 1;
            if (lane == 0) {
                const uint32_t eb = misc + BAR_EV + w * 8 * NEV;
#pragma unroll 1
                for (int i = 0; i < 6; i++) {
                    const bool kv = (i >> 1) == 1;
                    const int ci = i < 2 ? i : i - 2;
                    mbar_wait(eb + 8 * (kv ? EV_KV + i : EV_CTX + ci), 0);
                    if (i == 1) {
                        asm volatile("cp.async.bulk.global.shared::cta.bulk_group [%0], [%1], 16384;"
                                     ::"l"(g_ctx + (size_t)(team * 32 + 4 * b1 + (w ? 3 - (rank ^ 1) : rank ^ 1)) * 16384),
                                       "r"(ring + slot_of(78) * SLOT_BYTES + w * 16384) : "memory");
                        asm volatile("cp.async.bulk.commit_group;" ::: "memory");
                        asm volatile("cp.async.bulk.wait_group.read 0;" ::: "memory");
                        mbar_arrive_cluster(mapa(misc + BAR_EMPTY + 8 * slot_of(78), 0), 4);
                        mbar_arrive_cluster(mapa(misc + BAR_EMPTY + 8 * slot_of(78), 1), 4);
                        asm volatile("cp.async.bulk.wait_group 0;" ::: "memory");
                        fence_async_global();
                    }
                    flag_signal(flag_ptr(kv ? FL_KV + team * 8 + i : FL_CTX + (team + 16 * (ci >> 1)) * 8 + ((ci & 1) ? b1 : b0)));
                }
            }
            __syncwarp();
            mbar_wait(misc + BAR_PROG + 16, 0);
            const int row = (2 * u3 + rank) * 128 + 64 * w + perm32(16 * (lane >> 3) + 8 * kap + (lane & 7));
#pragma unroll
            for (int i = 0; i < 10; i++) asm volatile("prefetch.global.L2 [%0];" ::"l"(P.x + (size_t)row * DM + 160 * s3 + 16 * i));
            asm volatile("prefetch.global.L2 [%0];" ::"l"(g_stats + row));
            if (lane < 5) asm volatile("prefetch.global.L2 [%0];" ::"l"(g_brow + ((cta & 31) * 10 + w * 5 + lane) * 16));
            mbar_wait(misc + BAR_EV + w * 8 * NEV + 8 * EV_END, 0);
        }
        }
    } else {
        asm volatile("setmaxnreg.inc.sync.aligned.u32 232;");
        Ctx c;
        c.ring = ring; c.misc = misc; c.w = wg - 1; c.warp = __shfl_sync(0xffffffffu, (tid >> 5) & 3, 0); c.lane = tid & 31;
        c.rel = mapa(misc, tid & 1);
        const int w = c.w;
        if (w == 1) bar_arrive(1, 256);
        prefetch_w(2); prefetch_w(3);
        Cur cur = cur_at(0);
        float o[64], inv[2];
        unsigned char* out[2];
        uint32_t wf[128];
        Cur cw = cur;
        auto load_wchunk = [&](auto CH) {
            constexpr int ch = decltype(CH)::value;
            mbar_wait_hot(misc + BAR_FULL + 8 * cw.slot, cw.ph);
            const uint32_t z = load_afrag<8, 32 * ch>(wf, ring + cw.slot * SLOT_BYTES + w * 16384, c);
            release(c, BAR_EMPTY + 8 * cw.slot + z, 1);
            cw.adv(); cw.adv();
        };
#pragma unroll
        for (int i = 32; i < 64; i++) wf[i] = 0u;
        load_wchunk(IC<0>{});
#pragma unroll 1
        for (int v = 0; v < 2; v++) {
        {
            float (&acc)[64] = o;
#pragma unroll
            for (int i = 64; i < 128; i++) wf[i] = 0u;
            cur.adv();
            inv[0] = inv[1] = rank ? 1.0f : SM_SCALE;
#pragma unroll 1
            for (int t = 0; t < 4; t++) {
                uint32_t last = 0;
                token_wait(w);
                undef_regs(acc);
                auto chunk = [&](auto CH) {
                    constexpr int ch = decltype(CH)::value;
                    mbar_wait_hot(misc + BAR_FULL + 8 * cur.slot, cur.ph);
                    uint64_t d = mkdesc(ring + cur.slot * SLOT_BYTES, 16, 1024, 1);
                    wg_fence();
#pragma unroll
                    for (int ks = 0; ks < 8; ks++)
                        wgmma_rs_n128_ta0_tb0(acc, wf[32 * ch + 4 * ks], wf[32 * ch + 4 * ks + 1], wf[32 * ch + 4 * ks + 2], wf[32 * ch + 4 * ks + 3],
                                              d + (ks >> 2) * 1024 + (ks & 3) * 2, (ch | ks) != 0);
                    wg_commit();
                    if (ch == 3 || (ch < 2 && t == 0)) token_pass(w);
                    if constexpr (ch == 0) { if (t == 0) { if (v) load_wchunk(IC<2>{}); else load_wchunk(IC<1>{}); } }
                    if constexpr (ch == 1) { if (t == 0 && !v) load_wchunk(IC<2>{}); }
                    if constexpr (ch == 2) { if (t == 0 && !(w | v)) load_wchunk(IC<3>{}); }
                    if (ch > 0) { wg_wait<1>(); release(c, BAR_EMPTY + 8 * last, 1); }
                    last = cur.slot;
                    cur.adv();
                    if (ch < 3 && t == 0) cur.adv();
                    if constexpr (ch == 1) { if (t == 0 && (w | v)) load_wchunk(IC<3>{}); }
                    if (ch < 2 && t == 0) token_wait(w);
                };
                chunk(IC<0>{}); chunk(IC<1>{}); chunk(IC<2>{}); chunk(IC<3>{});
                wg_wait<0>();
                release(c, BAR_EMPTY + 8 * last, 1);
                fence_regs(acc);
                tile_out(out, (rank ? g_V : g_K) + (size_t)(team * 32 + 2 * (kv_tile(t) + k)) * 16384, 64 * w, rank, c);
                if (t == 3 && w) break;
#pragma unroll
                for (int i = 0; i < 4; i++) store_pair(acc, i, out, 8192, inv);
                if (t >= 2) signal_event(c, EV_KV + 2 * v + t - 2);
            }
        }
        {
            uint32_t q[32], p[32];
            float m[2], l[2];
#pragma unroll
            for (int i = 0; i < 32; i++) p[i] = 0u;
            l[0] = l[1] = 1.f;
            int pv_acc = 1, pv_mode = 2;
#pragma unroll 1
            for (int r = 0; r < 2; r++) {
                const int heavy = 1 ^ r ^ w;
                const int half = 1 ^ heavy ^ rank ^ r;
                int left = 2 * (r ? b1 : b0) + 1 + heavy;
                Cur ck, cv = cur;
                {
                    float s[64];
                    if (r) cur.adv();
                    mbar_wait_hot(misc + BAR_FULL + 8 * cv.slot, cv.ph);
                    token_wait(w);
                    issue_pv(o, p, ring + cv.slot * SLOT_BYTES, pv_acc, pv_mode);
                    undef_regs(s);
                    uint32_t prev;
                    auto qchunk = [&](int acc) {
                        mbar_wait_hot(misc + BAR_FULL + 8 * cur.slot, cur.ph);
                        const uint64_t da = mkdesc(ring + cur.slot * SLOT_BYTES + w * 8192, 16, 1024, 1);
                        const uint64_t db = mkdesc(ring + cur.slot * SLOT_BYTES + 16384, 8192, 1024, 1);
                        wg_fence();
#pragma unroll
                        for (int ks = 0; ks < 4; ks++) wgmma_ss_n128_ta0_tb1(s, da + 2 * ks, db + 128 * ks, ks ? 1 : acc);
                        wg_commit();
                    };
                    qchunk(0);
                    prev = cur.slot; cur.adv();
                    token_pass(w);
                    if (r) {
                        row_inv(l, inv);
                        tile_out(out, g_ctx + (size_t)((team + 16 * v) * 32 + 4 * b0 + (w ? rank : 3 - rank)) * 16384, 0, 0, c);
                    }
                    const int epi = r | w, hs = r ? 4096 : 8192;
                    const int hold = heavy ? -10 : half ? 6 : 8;
#pragma unroll
                    for (int kc = 1; kc < 10; kc++) {
                        if (kc >= 6 && (kc == hold || kc == hold + 2)) token_wait(w);
                        qchunk(1);
                        if (kc > 6 && kc == hold + 1) token_pass(w);
                        if (kc == 9 && heavy) { token_wait(w); token_pass(w); }
                        wg_wait<1>();
                        release(c, BAR_EMPTY + 8 * prev, 1);
                        prev = cur.slot; cur.adv();
                        if (kc == 1) { fence_regs(o); if (r) release(c, BAR_EMPTY + 8 * cv.slot, 1); }
                        if (kc <= 4 && epi) {
                            store_pair(o, kc - 1, out, hs, inv);
                            if (kc == 4) signal_event(c, r ? EV_CTX + 2 * v : EV_KV + 2 * v + 1);
                        }
                    }
                    if (!heavy) cur.adv();
                    ck = cur;
                    cur.adv();
                    if (!heavy) cur.adv();
                    wg_wait<0>();
                    release(c, BAR_EMPTY + 8 * prev, 1);
                    fence_regs(s);
#pragma unroll
                    for (int i = 0; i < 32; i++) q[i] = pack_bf16(s[2 * i], s[2 * i + 1]);
                }
                int first = 1, gen = 0;
                uint32_t pv_cnt = 0;
                l[0] = l[1] = m[0] = m[1] = 0.f;
                mbar_wait_hot(misc + BAR_FULL + 8 * ck.slot, ck.ph);
                auto diagonal = [&](auto NJC) {
                    constexpr int NJ = decltype(NJC)::value;
                    if (NJ == 16 || heavy) token_wait(w);
                    float sd[4 * NJ];
                    undef_regs(sd);
                    if constexpr (NJ == 8) issue_qk_half(sd, q, ring + ck.slot * SLOT_BYTES); else issue_qk(sd, q, ring + ck.slot * SLOT_BYTES);
                    token_pass(w);
                    wg_wait<0>();
                    fence_regs(sd);
                    mask_diag<NJ - 8>(sd, c);
                    float l0 = 0.f, l1 = 0.f;
#pragma unroll
                    for (int j = 0; j < NJ; j++) {
#pragma unroll
                        for (int e = 0; e < 4; e++) ex2v(sd[4 * j + e]);
                        l0 += sd[4 * j] + sd[4 * j + 1]; l1 += sd[4 * j + 2] + sd[4 * j + 3];
                    }
#pragma unroll
                    for (int i = 0; i < 2 * NJ; i++) p[i] = pack_bf16(sd[2 * i], sd[2 * i + 1]);
                    const int lim = NJ == 8 ? mask_lim(c) : 0;
                    const bool bad = __any_sync(0xffffffffu, !(l0 <= SAFE_SUM && l1 <= SAFE_SUM && (l0 >= 1.0f / SAFE_SUM || lim < 0) &&
                                                               (l1 >= 1.0f / SAFE_SUM || lim < -2)));
                    if (!bad) { l[0] = l0; l[1] = l1; }
                    return bad;
                };
#pragma unroll 1
                while (true) {
                    float s[64];
                    if (first) {
                        --left;
                        if (half ? diagonal(IC<8>{}) : diagonal(IC<16>{})) goto redo;
                        if (left == 0) goto tail;
                        release(c, BAR_EMPTY + 8 * ck.slot, 1 + heavy);
                        pv_acc = 0; pv_mode = half; pv_cnt = 1 + heavy; first = 0;
                        ck = cur; cur.adv(); cv = cur; cur.adv();
                        mbar_wait_hot(misc + BAR_FULL + 8 * ck.slot, ck.ph);
                    }
#pragma unroll 1
                    while (true) {
                        token_wait(w);
                        undef_regs(s);
                        issue_qk(s, q, ring + ck.slot * SLOT_BYTES);
                        Cur nck = cur, ncv = cur, ncur;
                        ncv.adv(); ncur = ncv; ncur.adv();
                        --left;
                        mbar_wait_hot(misc + BAR_FULL + 8 * cv.slot, cv.ph);
                        issue_pv(o, p, ring + cv.slot * SLOT_BYTES, pv_acc, pv_mode & 1);
                        token_pass(w);
                        wg_wait<1>();
                        fence_regs(s);
                        constexpr int JB = 11;
                        float l0 = l[0], l1 = l[1];
                        if (!gen) {
#pragma unroll
                            for (int j = 0; j < JB; j++) {
#pragma unroll
                                for (int e = 0; e < 4; e++) ex2v(s[4 * j + e]);
                                if (j < JB - 1) { l0 += s[4 * j] + s[4 * j + 1]; l1 += s[4 * j + 2] + s[4 * j + 3]; }
                            }
                        }
                        wg_wait<0>();
                        fence_regs(o);
                        if (gen) goto general;
#pragma unroll
                        for (int j = JB - 1; j < 16; j++) {
                            if (j >= JB) {
#pragma unroll
                                for (int e = 0; e < 4; e++) ex2v(s[4 * j + e]);
                            }
                            l0 += s[4 * j] + s[4 * j + 1]; l1 += s[4 * j + 2] + s[4 * j + 3];
                        }
#pragma unroll
                        for (int i = 0; i < 32; i++) p[i] = pack_bf16(s[2 * i], s[2 * i + 1]);
                        if (__any_sync(0xffffffffu, !(l0 <= SAFE_SUM && l1 <= SAFE_SUM))) goto redo;
                        l[0] = l0; l[1] = l1;
                        if (left == 0) goto tail;
                        release(c, BAR_EMPTY + 8 * ck.slot, 1);
                        release(c, BAR_EMPTY + 8 * cv.slot, pv_cnt);
                        pv_acc = 1; pv_mode = 0; pv_cnt = 1;
                        ck = nck; cv = ncv; cur = ncur;
                        mbar_wait_hot(misc + BAR_FULL + 8 * ck.slot, ck.ph);
                    }
                redo:
                    recompute_scores(s, q, ring + ck.slot * SLOT_BYTES, c);
                    if (first) { mask_any(s, half ^ 1, c); m[0] = m[1] = -INFINITY; }
                    gen = 1;
                general:
                    {
                        float mx[2], alpha[2];
                        row_max<16>(s, mx);
#pragma unroll
                        for (int i = 0; i < 2; i++) {
                            mx[i] = fmaxf(mx[i], m[i]);
                            alpha[i] = ex2(m[i] - mx[i]);
                            m[i] = mx[i];
                            l[i] *= alpha[i];
                        }
                        exp_sum<16, true>(s, m, l[0], l[1]);
#pragma unroll
                        for (int i = 0; i < 64; i++) o[i] *= alpha[(i >> 1) & 1];
#pragma unroll
                        for (int i = 0; i < 32; i++) p[i] = pack_bf16(s[2 * i], s[2 * i + 1]);
                    }
                tail:
                    release(c, BAR_EMPTY + 8 * ck.slot, 1 + (first & heavy));
                    if (pv_cnt) release(c, BAR_EMPTY + 8 * cv.slot, pv_cnt);
                    pv_acc = first ^ 1; pv_mode = first & half; pv_cnt = 1 + (first & heavy); first = 0;
                    if (left == 0) break;
                    ck = cur; cur.adv(); cv = cur; cur.adv();
                    mbar_wait_hot(misc + BAR_FULL + 8 * ck.slot, ck.ph);
                }
            }
            mbar_wait_hot(misc + BAR_FULL + 8 * cur.slot, cur.ph);
            token_wait(w);
            issue_pv(o, p, ring + cur.slot * SLOT_BYTES, 1, 0);
            if (w == 0 || v == 0) token_pass(w);
            const uint32_t vslot = cur.slot;
            cur.adv();
            if (v) {
                row_inv(l, inv);
                wg_wait<0>();
                release(c, BAR_EMPTY + 8 * vslot, 1);
                fence_regs(o);
                tile_out(out, g_ctx + (size_t)((team + 16) * 32 + 4 * b1 + (w ? 3 - (rank ^ 1) : rank ^ 1)) * 16384, 0, 0, c);
#pragma unroll
                for (int i = 0; i < 64; i++) wf[i] = 0u;
                continue;
            }
            cw = cur_at(80);
            mbar_wait_hot(misc + BAR_FULL + 8 * slot_of(76), cur_at(76).ph);
            mbar_wait_hot(misc + BAR_FULL + 8 * slot_of(78), cur_at(78).ph);
            load_afrag<8, 32>(wf, ring + slot_of(78) * SLOT_BYTES + w * 16384, c);
            const uint32_t z = load_afrag<8, 0>(wf, ring + slot_of(76) * SLOT_BYTES + w * 16384, c);
            row_inv(l, inv);
            release(c, BAR_EMPTY + 8 * slot_of(76) + z, 1);
            asm volatile("{\n.reg .pred p;\nsetp.eq.u32 p, %0, 0;\n@p bar.sync 4, 128;\n@!p bar.sync 5, 128;\n}\n" ::"r"(w) : "memory");
            wg_wait<0>();
            release(c, BAR_EMPTY + 8 * vslot, 1);
            fence_regs(o);
            {
                const uint32_t base = ring + slot_of(78) * SLOT_BYTES + w * 16384 + (16 * c.warp + (c.lane >> 2)) * 64 + (((c.lane ^ (c.lane >> 3)) & 3) << 4);
#pragma unroll
                for (int i = 0; i < 2; i++)
#pragma unroll
                    for (int qq = 0; qq < 4; qq++)
                        asm volatile("st.shared.v4.b32 [%0], {%1,%2,%3,%4};" ::"r"(base + qq * 4096 + i * 512),
                                     "r"(pack_bf16(o[16 * qq + 2 * i] * inv[i], o[16 * qq + 2 * i + 1] * inv[i])),
                                     "r"(pack_bf16(o[16 * qq + 4 + 2 * i] * inv[i], o[16 * qq + 4 + 2 * i + 1] * inv[i])),
                                     "r"(pack_bf16(o[16 * qq + 8 + 2 * i] * inv[i], o[16 * qq + 8 + 2 * i + 1] * inv[i])),
                                     "r"(pack_bf16(o[16 * qq + 12 + 2 * i] * inv[i], o[16 * qq + 12 + 2 * i + 1] * inv[i])) : "memory");
                asm volatile("fence.proxy.async.shared::cta;" ::: "memory");
                signal_event(c, EV_CTX + 1);
            }
        }
        }
        {
            float acc[80];
            undef_regs(acc);
            int st = 0, prev = 0; uint32_t ph3 = 0;
            auto op_stage = [&](int i) {
                mbar_wait_hot(misc + BAR_FULL3 + 8 * st, ph3);
                uint32_t base = ring + st * ST3_BYTES;
                uint64_t da = mkdesc(base + w * 8192, 16, 512, 2);
                uint64_t db = mkdesc(base + 16384, 2048, 512, 2);
                wg_fence();
#pragma unroll
                for (int k = 0; k < 4; k++) wgmma_ss_n160_ta0_tb1(acc, da + (k >> 1) * 256 + 2 * (k & 1), db + (k >> 1) * 640 + (k & 1) * 64, k ? 1 : i);
                wg_commit();
                if (i > 0) { wg_wait<1>(); if (i <= 32 - NST3) release(c, BAR_EMPTY3 + 8 * prev, 1); }
                prev = st;
                if (++st == NST3) { st = 0; ph3 ^= 1; }
            };
#pragma unroll
            for (int i = 0; i < 4; i++) { op_stage(i); store_pair(o, i, out, 4096, inv); }
            signal_event(c, EV_CTX + 3);
            const int split = w ? 32 - OP_HOLD : RES_AT;
#pragma unroll 1
            for (int i = 4; i < split; i++) op_stage(i);
            mbar_wait(misc + BAR_SEL, 0);
            const uint32_t tag = lds32(misc + MISC_EPOCH) & 1;
            const int g = c.lane >> 2, t = c.lane & 3;
            const int row = (2 * u3 + rank) * 128 + 64 * w + perm32(16 * c.warp + 8 * kap + g);
            const int col = 160 * s3 + 8 * t;
            int sel = -1;
#pragma unroll
            for (int i = 0; i < TOPC; i++) if ((int)lds32(misc + MISC_SEL + 4 * i) == row) sel = i;
            const int t256 = tid - 128;
            uint4* sendp = g_part + (size_t)cta * 2560 + t256;
            if (c.lane >= 30) stg128(sendp + 9 * 256, tag ^ 1, tag ^ 1, tag ^ 1, tag ^ 1);
            uint4 xv[5], bv[5];
#pragma unroll
            for (int i = 0; i < 5; i++) xv[i] = ldg128(P.x + (size_t)row * DM + col + 32 * i);
            uint2 stat;
            asm volatile("ld.global.cg.v2.b32 {%0,%1}, [%2];" : "=r"(stat.x), "=r"(stat.y) : "l"(g_stats + row) : "memory");
#pragma unroll
            for (int i = 0; i < 5; i++) {
                uint32_t xx[4] = {xv[i].x, xv[i].y, xv[i].z, xv[i].w};
#pragma unroll
                for (int e = 0; e < 4; e++) {
                    asm("sub.rn.bf16x2 %0, %0, %1;" : "+r"(xx[e]) : "r"(stat.x));
                    xx[e] = pack_bf16(bf_lo(xx[e]) * __uint_as_float(stat.y), bf_hi(xx[e]) * __uint_as_float(stat.y));
                }
                bv[i] = make_uint4(xx[0], xx[1], xx[2], xx[3]);
            }
            if (sel >= 0) {
#pragma unroll
                for (int i = 0; i < 5; i++) bv[i] = ldg128(g_brow + sel * DM + col + 32 * i);
            }
#pragma unroll
            for (int i = 0; i < 5; i++) asm volatile("" : "+r"(bv[i].x), "+r"(bv[i].y), "+r"(bv[i].z), "+r"(bv[i].w));
            if (w) bar_sync(4, 256);
#pragma unroll 1
            for (int i = split; i < 32; i++) op_stage(i);
            if (!w) bar_arrive(4, 256);
            wg_wait<0>();
            fence_regs(acc);
            float keep[40];
#pragma unroll
            for (int j = 0; j < 10; j++) {
                uint32_t v0 = __float_as_uint(kap ? acc[8 * j + 0] : acc[8 * j + 2]), v1 = __float_as_uint(kap ? acc[8 * j + 1] : acc[8 * j + 3]);
                uint32_t v2 = __float_as_uint(kap ? acc[8 * j + 4] : acc[8 * j + 6]), v3 = __float_as_uint(kap ? acc[8 * j + 5] : acc[8 * j + 7]);
                asm volatile("st.relaxed.gpu.global.v4.b32 [%0], {%1,%2,%3,%4};" ::"l"(sendp + j * 256),
                             "r"((v0 & ~1u) | tag), "r"((v1 & ~1u) | tag), "r"((v2 & ~1u) | tag), "r"((v3 & ~1u) | tag) : "memory");
                keep[4 * j + 0] = kap ? acc[8 * j + 2] : acc[8 * j + 0]; keep[4 * j + 1] = kap ? acc[8 * j + 3] : acc[8 * j + 1];
                keep[4 * j + 2] = kap ? acc[8 * j + 6] : acc[8 * j + 4]; keep[4 * j + 3] = kap ? acc[8 * j + 7] : acc[8 * j + 5];
            }
            signal_event(c, EV_END);
            const uint4* recvp = g_part + (size_t)partner * 2560 + t256;
            uint4 rv[10];
            int spins = 0;
            while (true) {
                uint32_t v;
                asm volatile("ld.relaxed.gpu.global.b32 %0, [%1];" : "=r"(v) : "l"(recvp + 9 * 256 + (31 - c.lane)) : "memory");
                if (__all_sync(0xffffffffu, (v & 1u) == tag) || ++spins > 2000000) break;
            }
            while (true) {
                uint32_t bad = 0u;
#pragma unroll
                for (int j = 0; j < 10; j++) {
                    asm volatile("ld.relaxed.gpu.global.v4.b32 {%0,%1,%2,%3}, [%4];"
                                 : "=r"(rv[j].x), "=r"(rv[j].y), "=r"(rv[j].z), "=r"(rv[j].w) : "l"(recvp + j * 256) : "memory");
                }
#pragma unroll
                for (int j = 0; j < 10; j++) {
                    rv[j].x ^= tag; rv[j].y ^= tag; rv[j].z ^= tag; rv[j].w ^= tag;
                    bad |= rv[j].x | rv[j].y | rv[j].z | rv[j].w;
                }
                if (__all_sync(0xffffffffu, (bad & 1u) == 0) || ++spins > 2000000) break;
            }
            uint32_t pk[20];
#pragma unroll
            for (int j = 0; j < 10; j++) {
                pk[2 * j] = pack_bf16(keep[4 * j] + __uint_as_float(rv[j].x), keep[4 * j + 1] + __uint_as_float(rv[j].y));
                pk[2 * j + 1] = pack_bf16(keep[4 * j + 2] + __uint_as_float(rv[j].z), keep[4 * j + 3] + __uint_as_float(rv[j].w));
            }
#pragma unroll
            for (int i = 0; i < 5; i++) {
                uint32_t a0 = pk[4 * i], a1 = pk[4 * i + 1], a2 = pk[4 * i + 2], a3 = pk[4 * i + 3];
                uint32_t x0 = (t & 1) ? a0 : a1, x1 = (t & 1) ? a2 : a3;
                x0 = __shfl_xor_sync(0xffffffffu, x0, 1); x1 = __shfl_xor_sync(0xffffffffu, x1, 1);
                if (t & 1) { a0 = x0; a2 = x1; } else { a1 = x0; a3 = x1; }
                x0 = (t & 2) ? a0 : a2; x1 = (t & 2) ? a1 : a3;
                x0 = __shfl_xor_sync(0xffffffffu, x0, 2); x1 = __shfl_xor_sync(0xffffffffu, x1, 2);
                if (t & 2) { a0 = x0; a1 = x1; } else { a2 = x0; a3 = x1; }
                uint32_t av[4] = {a0, a1, a2, a3};
                uint32_t xx[4] = {xv[i].x, xv[i].y, xv[i].z, xv[i].w}, bb[4] = {bv[i].x, bv[i].y, bv[i].z, bv[i].w};
                uint32_t ov[4];
#pragma unroll
                for (int e = 0; e < 4; e++) {
                    asm("add.rn.bf16x2 %0, %1, %2;" : "=r"(ov[e]) : "r"(xx[e]), "r"(av[e]));
                    asm("add.rn.bf16x2 %0, %0, %1;" : "+r"(ov[e]) : "r"(bb[e]));
                }
                stg128(P.out + (size_t)row * DM + col + 32 * i, ov[0], ov[1], ov[2], ov[3]);
            }
        }
    }
}

typedef CUresult (*EncodeFn)(CUtensorMap*, CUtensorMapDataType, cuuint32_t, void*, const cuuint64_t*, const cuuint64_t*, const cuuint32_t*,
                             const cuuint32_t*, CUtensorMapInterleave, CUtensorMapSwizzle, CUtensorMapL2promotion, CUtensorMapFloatOOBfill);

void make_map2d(EncodeFn enc, CUtensorMap* tm, const void* p, uint64_t cols, uint64_t rows, uint32_t box_rows = 128) {
    cuuint64_t gd[2] = {cols, rows}, gs[1] = {cols * 2};
    cuuint32_t box[2] = {64, box_rows}, es[2] = {1, 1};
    enc(tm, CU_TENSOR_MAP_DATA_TYPE_BFLOAT16, 2, const_cast<void*>(p), gd, gs, box, es, CU_TENSOR_MAP_INTERLEAVE_NONE,
        CU_TENSOR_MAP_SWIZZLE_128B, CU_TENSOR_MAP_L2_PROMOTION_L2_128B, CU_TENSOR_MAP_FLOAT_OOB_FILL_NONE);
}

void make_map3d(EncodeFn enc, CUtensorMap* tm, const void* p, uint64_t cols, uint64_t rows, uint32_t bw, uint32_t nb) {
    cuuint64_t gd[3] = {bw, rows, cols / bw}, gs[2] = {cols * 2, bw * 2};
    cuuint32_t box[3] = {bw, 32, nb}, es[3] = {1, 1, 1};
    enc(tm, CU_TENSOR_MAP_DATA_TYPE_BFLOAT16, 3, const_cast<void*>(p), gd, gs, box, es, CU_TENSOR_MAP_INTERLEAVE_NONE,
        bw == 64 ? CU_TENSOR_MAP_SWIZZLE_128B : CU_TENSOR_MAP_SWIZZLE_64B, CU_TENSOR_MAP_L2_PROMOTION_L2_128B, CU_TENSOR_MAP_FLOAT_OOB_FILL_NONE);
}

}

extern "C" void kernel_launch(void* const* d_in, const int* in_sizes, int n_in, void* d_out, int out_size) {
    (void)in_sizes; (void)n_in; (void)out_size;
    static EncodeFn enc = nullptr;
    if (!enc) {
        void* fn = nullptr;
        cudaDriverEntryPointQueryResult qr;
        cudaGetDriverEntryPoint("cuTensorMapEncodeTiled", &fn, cudaEnableDefault, &qr);
        enc = (EncodeFn)fn;
        cudaFuncSetAttribute(fused_kernel, cudaFuncAttributeMaxDynamicSharedMemorySize, SMEM_BYTES);
    }
    CUtensorMap tmC, tmWk, tmWv, tmWq, tmWo, tmG, tmU, tmD;
    make_map2d(enc, &tmC, d_in[1], DC, SEQ);
    make_map2d(enc, &tmWq, d_in[2], 4096, DM, 64);
    make_map2d(enc, &tmWk, d_in[3], 4096, DC);
    make_map2d(enc, &tmWv, d_in[4], 4096, DC);
    make_map3d(enc, &tmWo, d_in[5], DM, 4096, 32, 5);
    make_map3d(enc, &tmG, d_in[8], FF, DM, 64, 7);
    make_map3d(enc, &tmU, d_in[9], FF, DM, 64, 7);
    make_map3d(enc, &tmD, d_in[10], DM, FF, 64, 10);
    Params P;
    P.x = (const __nv_bfloat16*)d_in[0];
    P.c = (const __nv_bfloat16*)d_in[1];
    P.wk = (const __nv_bfloat16*)d_in[3];
    P.wv = (const __nv_bfloat16*)d_in[4];
    P.wo = (const __nv_bfloat16*)d_in[5];
    P.wr = (const __nv_bfloat16*)d_in[7];
    P.out = (__nv_bfloat16*)d_out;
    fused_kernel<<<132, 384, SMEM_BYTES>>>(tmC, tmWk, tmWv, tmWq, tmWo, tmG, tmU, tmD, P);
}
```

```cpp
#include <cuda_runtime.h>
#include <cuda_bf16.h>
#include <cuda.h>
#include <stdint.h>

namespace {

constexpr int SEQ = 2048, NH = 32, DM = 640, DC = 512, FF = 1728, TOPC = 8;
constexpr int NSLOT = 7, SLOT_BYTES = 32768;
constexpr int NST3 = 6, ST3_BYTES = 36864;
constexpr int RING_BYTES = NSLOT * SLOT_BYTES;
constexpr int SMEM_BYTES = RING_BYTES + 3072;
constexpr int OP_PF = 8, PF_START = 9, LATE_AT = 18, RES_AT = 23, OP_HOLD = 4;

constexpr int BAR_FULL = 0  , BAR_EMPTY = 64  , BAR_FULL3 = 128  , BAR_EMPTY3 = 192  , BAR_DEP = 256  ,
              BAR_EV = 448  , BAR_PROG = 592  , BAR_SEL = 616, BAR_LN = 624,
              MISC_EPOCH = 640, MISC_SMID = 644  , MISC_SEL = 656, MISC_WR = 1024  ;
constexpr int D_LN = 0  , D_KV = 2  , D_WAR = 6  , D_CTX = 8  ;
constexpr int EV_KV = 0  , EV_CTX = 4  , EV_END = 8, NEV = 9;

constexpr int FL_MOE_CNT = 0, FL_MOE_DONE = 1, FL_LN = 16  , FL_KV = 32  , FL_CTX = 160  , FL_WAR = 416  , FL_TOTAL = 448;

__device__ __align__(1024) unsigned char g_K[16 * 32 * 16384];
__device__ __align__(1024) unsigned char g_V[16 * 32 * 16384];
__device__ __align__(1024) unsigned char g_ctx[NH * 32 * 16384];
__device__ __align__(1024) unsigned char g_xn[16 * 10 * 16384];
__device__ __align__(1024) uint4 g_part[128 * 10 * 256];
__device__ float g_router[SEQ];
__device__ uint2 g_stats[SEQ];
__device__ __align__(16) float g_moe_part[4 * TOPC * DM];
__device__ __align__(16) __nv_bfloat16 g_brow[TOPC * DM];
__device__ __align__(16) int g_sel[TOPC];
__device__ unsigned g_flags[FL_TOTAL * 8];
__device__ unsigned g_epoch;
__device__ unsigned g_roleq[130];
struct Params {
    const __nv_bfloat16 *x, *c, *wr, *wk, *wv, *wo;
    __nv_bfloat16* out;
};

__device__ __forceinline__ uint32_t smem_u32(const void* p) { return (uint32_t)__cvta_generic_to_shared(p); }
__device__ __forceinline__ void mbar_init(uint32_t bar, int cnt) { asm volatile("mbarrier.init.shared::cta.b64 [%0], %1;" ::"r"(bar), "r"(cnt)); }
__device__ __forceinline__ void mbar_expect_tx(uint32_t bar, uint32_t bytes) {
    asm volatile("mbarrier.arrive.expect_tx.shared::cta.b64 _, [%0], %1;" ::"r"(bar), "r"(bytes) : "memory");
}
__device__ __forceinline__ void mbar_arrive(uint32_t bar) { asm volatile("mbarrier.arrive.shared::cta.b64 _, [%0];" ::"r"(bar) : "memory"); }
__device__ __forceinline__ void mbar_arrive_cluster(uint32_t cluster_addr, uint32_t cnt) {
    asm volatile("mbarrier.arrive.shared::cluster.b64 _, [%0], %1;" ::"r"(cluster_addr), "r"(cnt) : "memory");
}
__device__ __forceinline__ uint32_t mapa(uint32_t addr, uint32_t cta) {
    uint32_t r; asm("mapa.shared::cluster.u32 %0, %1, %2;" : "=r"(r) : "r"(addr), "r"(cta)); return r;
}
__device__ __forceinline__ void mbar_wait(uint32_t bar, uint32_t parity) {
    asm volatile(
        "{\n.reg .pred p;\n.reg .u32 n;\n"
        "mov.u32 n, 0;\n"
        "LAB_WAIT:\n"
        "mbarrier.try_wait.parity.shared::cta.b64 p, [%0], %1, 100000;\n"
        "@p bra DONE;\n"
        "add.u32 n, n, 1;\n"
        "setp.lt.u32 p, n, 50000;\n"
        "@p bra LAB_WAIT;\n"
        "trap;\n"
        "DONE:\n}\n" ::"r"(bar), "r"(parity) : "memory");
}
__device__ __forceinline__ void mbar_wait_hot(uint32_t bar, uint32_t parity) {
    asm volatile("{\n.reg .pred p;\nLAB_WAIT:\nmbarrier.try_wait.parity.shared::cta.b64 p, [%0], %1;\n@!p bra LAB_WAIT;\n}\n" ::"r"(bar), "r"(parity) : "memory");
}
__device__ __forceinline__ void mbar_wait_sleep(uint32_t bar, uint32_t parity) {
    asm volatile("{\n.reg .pred p;\nLAB_WAIT:\nmbarrier.try_wait.parity.shared::cta.b64 p, [%0], %1, 100000;\n@!p bra LAB_WAIT;\n}\n" ::"r"(bar), "r"(parity) : "memory");
}
__device__ __forceinline__ void flag_wait(const unsigned* flag, unsigned target) {
    asm volatile(
        "{\n.reg .pred p;\n.reg .u32 n, v;\n.reg .s32 d;\n"
        "mov.u32 n, 0;\n"
        "LAB_WAIT:\n"
        "ld.acquire.gpu.global.u32 v, [%0];\n"
        "sub.s32 d, v, %1;\n"
        "setp.ge.s32 p, d, 0;\n"
        "@p bra DONE;\n"
        "nanosleep.u32 40;\n"
        "add.u32 n, n, 1;\n"
        "setp.lt.u32 p, n, 3000000;\n"
        "@p bra LAB_WAIT;\n"
        "trap;\n"
        "DONE:\n}\n" ::"l"(flag), "r"(target) : "memory");
}
__device__ __forceinline__ void flag_signal(unsigned* flag) {
    asm volatile("red.release.gpu.global.add.u32 [%0], 1;" ::"l"(flag) : "memory");
}
__device__ __forceinline__ void fence_async_global() { asm volatile("fence.proxy.async.global;" ::: "memory"); }
__device__ __forceinline__ unsigned* flag_ptr(int idx) { return g_flags + idx * 8; }

__device__ __forceinline__ uint64_t policy_stream() {
    uint64_t p; asm("createpolicy.fractional.L2::evict_first.b64 %0, 1.0;" : "=l"(p)); return p;
}
__device__ __forceinline__ void bulk_load(uint32_t dst, const void* src, uint32_t bytes, uint32_t bar) {
    asm volatile("cp.async.bulk.shared::cluster.global.mbarrier::complete_tx::bytes [%0], [%1], %2, [%3];"
                 ::"r"(dst), "l"(src), "r"(bytes), "r"(bar) : "memory");
}
__device__ __forceinline__ void bulk_load_mc(uint32_t dst, const void* src, uint32_t bytes, uint32_t bar) {
    asm volatile("cp.async.bulk.shared::cluster.global.mbarrier::complete_tx::bytes.multicast::cluster [%0], [%1], %2, [%3], %4;"
                 ::"r"(dst), "l"(src), "r"(bytes), "r"(bar), "h"((uint16_t)3) : "memory");
}
__device__ __forceinline__ void tma2d(uint32_t dst, const CUtensorMap* tm, int c0, int c1, uint32_t bar) {
    asm volatile("cp.async.bulk.tensor.2d.shared::cluster.global.mbarrier::complete_tx::bytes [%0], [%1, {%3, %4}], [%2];"
                 ::"r"(dst), "l"(tm), "r"(bar), "r"(c0), "r"(c1) : "memory");
}
__device__ __forceinline__ void tma2d_mc(uint32_t dst, const CUtensorMap* tm, int c0, int c1, uint32_t bar) {
    asm volatile("cp.async.bulk.tensor.2d.shared::cluster.global.mbarrier::complete_tx::bytes.multicast::cluster [%0], [%1, {%3, %4}], [%2], %5;"
                 ::"r"(dst), "l"(tm), "r"(bar), "r"(c0), "r"(c1), "h"((uint16_t)3) : "memory");
}
__device__ __forceinline__ void tma3d_mc(uint32_t dst, const CUtensorMap* tm, int c0, int c1, int c2, uint32_t bar) {
    asm volatile("cp.async.bulk.tensor.3d.shared::cluster.global.mbarrier::complete_tx::bytes.multicast::cluster [%0], [%1, {%3, %4, %5}], [%2], %6;"
                 ::"r"(dst), "l"(tm), "r"(bar), "r"(c0), "r"(c1), "r"(c2), "h"((uint16_t)3) : "memory");
}
__device__ __forceinline__ void tma3d(uint32_t dst, const CUtensorMap* tm, int c0, int c1, int c2, uint32_t bar) {
    asm volatile("cp.async.bulk.tensor.3d.shared::cluster.global.mbarrier::complete_tx::bytes.L2::cache_hint [%0], [%1, {%3, %4, %5}], [%2], %6;"
                 ::"r"(dst), "l"(tm), "r"(bar), "r"(c0), "r"(c1), "r"(c2), "l"(policy_stream()) : "memory");
}
__device__ __forceinline__ void tma2d_prefetch(const CUtensorMap* tm, int c0, int c1) {
    asm volatile("cp.async.bulk.prefetch.tensor.2d.L2.global [%0, {%1, %2}];" ::"l"(tm), "r"(c0), "r"(c1) : "memory");
}
__device__ __forceinline__ void tma3d_prefetch(const CUtensorMap* tm, int c0, int c1, int c2) {
    asm volatile("cp.async.bulk.prefetch.tensor.3d.L2.global [%0, {%1, %2, %3}];" ::"l"(tm), "r"(c0), "r"(c1), "r"(c2) : "memory");
}
__device__ __forceinline__ void l2_prefetch(const void* p, uint32_t bytes) {
    asm volatile("cp.async.bulk.prefetch.L2.global [%0], %1;" ::"l"(p), "r"(bytes) : "memory");
}
__device__ __forceinline__ bool elect_one() {
    uint32_t r; asm volatile("{\n.reg .pred p;\nelect.sync _|p, 0xffffffff;\nselp.u32 %0, 1, 0, p;\n}\n" : "=r"(r)); return r != 0;
}
__device__ __forceinline__ void wg_fence() { asm volatile("wgmma.fence.sync.aligned;" ::: "memory"); }
__device__ __forceinline__ void wg_commit() { asm volatile("wgmma.commit_group.sync.aligned;" ::: "memory"); }
template <int N> __device__ __forceinline__ void wg_wait() { asm volatile("wgmma.wait_group.sync.aligned %0;" ::"n"(N) : "memory"); }
__device__ __forceinline__ void bar_sync(int id, int n) { asm volatile("bar.sync %0, %1;" ::"r"(id), "r"(n) : "memory"); }
__device__ __forceinline__ void bar_arrive(int id, int n) { asm volatile("bar.arrive %0, %1;" ::"r"(id), "r"(n) : "memory"); }
__device__ __forceinline__ void token_wait(int w) {
    asm volatile("{\n.reg .pred p;\nsetp.eq.u32 p, %0, 0;\n@p bar.sync 1, 256;\n@!p bar.sync 2, 256;\n}\n" ::"r"(w) : "memory");
}
__device__ __forceinline__ void token_pass(int w) {
    asm volatile("{\n.reg .pred p;\nsetp.eq.u32 p, %0, 0;\n@p bar.arrive 2, 256;\n@!p bar.arrive 1, 256;\n}\n" ::"r"(w) : "memory");
}
template <int N> __device__ __forceinline__ void fence_regs(float (&a)[N]) {
#pragma unroll
    for (int i = 0; i < N; i++) asm volatile("" : "+f"(a[i])::"memory");
}
template <int N> __device__ __forceinline__ void undef_regs(float (&a)[N]) {
#pragma unroll
    for (int i = 0; i < N; i++) asm volatile("" : "=f"(a[i]));
}
__device__ __forceinline__ void ldsm4t(uint32_t& r0, uint32_t& r1, uint32_t& r2, uint32_t& r3, uint32_t addr) {
    asm volatile("ldmatrix.sync.aligned.m8n8.x4.trans.shared.b16 {%0,%1,%2,%3}, [%4];"
                 : "=r"(r0), "=r"(r1), "=r"(r2), "=r"(r3) : "r"(addr) : "memory");
}
__device__ __forceinline__ uint32_t pack_bf16(float lo, float hi) {
    uint32_t r; asm("cvt.rn.bf16x2.f32 %0, %1, %2;" : "=r"(r) : "f"(hi), "f"(lo)); return r;
}
__device__ __forceinline__ float bf_lo(uint32_t v) { return __uint_as_float(v << 16); }
__device__ __forceinline__ float bf_hi(uint32_t v) { return __uint_as_float(v & 0xffff0000u); }
__device__ __forceinline__ float bf_round(float v) { return __bfloat162float(__float2bfloat16_rn(v)); }
__device__ __forceinline__ float ex2(float v) { float r; asm("ex2.approx.ftz.f32 %0, %1;" : "=f"(r) : "f"(v)); return r; }
__device__ __forceinline__ void ex2v(float& v) { asm volatile("ex2.approx.ftz.f32 %0, %0;" : "+f"(v)); }
__device__ __forceinline__ float rcp_fast(float v) { float r; asm("rcp.approx.ftz.f32 %0, %1;" : "=f"(r) : "f"(v)); return r; }
__device__ __forceinline__ float sqrt_fast(float v) { float r; asm("sqrt.approx.ftz.f32 %0, %1;" : "=f"(r) : "f"(v)); return r; }
__device__ __forceinline__ void stg128(void* p, uint32_t a, uint32_t b, uint32_t c, uint32_t d) {
    asm volatile("st.global.v4.b32 [%0], {%1,%2,%3,%4};" ::"l"(p), "r"(a), "r"(b), "r"(c), "r"(d) : "memory");
}
__device__ __forceinline__ uint4 ldg128(const void* p) {
    uint4 v; asm volatile("ld.global.cg.v4.b32 {%0,%1,%2,%3}, [%4];" : "=r"(v.x), "=r"(v.y), "=r"(v.z), "=r"(v.w) : "l"(p) : "memory"); return v;
}
__device__ __forceinline__ uint64_t mkdesc(uint32_t addr, uint32_t lbo, uint32_t sbo, uint32_t swz) {
    uint32_t lo = ((addr & 0x3FFFF) >> 4) | ((lbo >> 4) << 16);
    uint32_t hi = (sbo >> 4) | (swz << 30);
    return ((uint64_t)hi << 32) | lo;
}
__device__ __forceinline__ int perm32(int v) { return (v & ~30) | ((v >> 2) & 6) | ((v << 2) & 24); }

__device__ __forceinline__ void wgmma_rs_n128_ta0_tb0(float (&d)[64], uint32_t a0, uint32_t a1, uint32_t a2, uint32_t a3, uint64_t descB, int scaleD) {
  asm volatile("{\n.reg .pred p;\nsetp.ne.b32 p, %69, 0;\n"
    "wgmma.mma_async.sync.aligned.m64n128k16.f32.bf16.bf16 "
    "{%0, %1, %2, %3, %4, %5, %6, %7, %8, %9, %10, %11, %12, %13, %14, %15, %16, %17, %18, %19, %20, %21, %22, %23, %24, %25, %26, %27, %28, %29, %30, %31, %32, %33, %34, %35, %36, %37, %38, %39, %40, %41, %42, %43, %44, %45, %46, %47, %48, %49, %50, %51, %52, %53, %54, %55, %56, %57, %58, %59, %60, %61, %62, %63}, "
    "{%64, %65, %66, %67}, %68, p, 1, 1, 0;\n}\n"
    : "+f"(d[0]), "+f"(d[1]), "+f"(d[2]), "+f"(d[3]), "+f"(d[4]), "+f"(d[5]), "+f"(d[6]), "+f"(d[7]), "+f"(d[8]), "+f"(d[9]), "+f"(d[10]), "+f"(d[11]), "+f"(d[12]), "+f"(d[13]), "+f"(d[14]), "+f"(d[15]), "+f"(d[16]), "+f"(d[17]), "+f"(d[18]), "+f"(d[19]), "+f"(d[20]), "+f"(d[21]), "+f"(d[22]), "+f"(d[23]), "+f"(d[24]), "+f"(d[25]), "+f"(d[26]), "+f"(d[27]), "+f"(d[28]), "+f"(d[29]), "+f"(d[30]), "+f"(d[31]), "+f"(d[32]), "+f"(d[33]), "+f"(d[34]), "+f"(d[35]), "+f"(d[36]), "+f"(d[37]), "+f"(d[38]), "+f"(d[39]), "+f"(d[40]), "+f"(d[41]), "+f"(d[42]), "+f"(d[43]), "+f"(d[44]), "+f"(d[45]), "+f"(d[46]), "+f"(d[47]), "+f"(d[48]), "+f"(d[49]), "+f"(d[50]), "+f"(d[51]), "+f"(d[52]), "+f"(d[53]), "+f"(d[54]), "+f"(d[55]), "+f"(d[56]), "+f"(d[57]), "+f"(d[58]), "+f"(d[59]), "+f"(d[60]), "+f"(d[61]), "+f"(d[62]), "+f"(d[63])
    : "r"(a0), "r"(a1), "r"(a2), "r"(a3), "l"(descB), "r"(scaleD));
}
__device__ __forceinline__ void wgmma_rs_n128_ta0_tb1(float (&d)[64], uint32_t a0, uint32_t a1, uint32_t a2, uint32_t a3, uint64_t descB, int scaleD) {
  asm volatile("{\n.reg .pred p;\nsetp.ne.b32 p, %69, 0;\n"
    "wgmma.mma_async.sync.aligned.m64n128k16.f32.bf16.bf16 "
    "{%0, %1, %2, %3, %4, %5, %6, %7, %8, %9, %10, %11, %12, %13, %14, %15, %16, %17, %18, %19, %20, %21, %22, %23, %24, %25, %26, %27, %28, %29, %30, %31, %32, %33, %34, %35, %36, %37, %38, %39, %40, %41, %42, %43, %44, %45, %46, %47, %48, %49, %50, %51, %52, %53, %54, %55, %56, %57, %58, %59, %60, %61, %62, %63}, "
    "{%64, %65, %66, %67}, %68, p, 1, 1, 1;\n}\n"
    : "+f"(d[0]), "+f"(d[1]), "+f"(d[2]), "+f"(d[3]), "+f"(d[4]), "+f"(d[5]), "+f"(d[6]), "+f"(d[7]), "+f"(d[8]), "+f"(d[9]), "+f"(d[10]), "+f"(d[11]), "+f"(d[12]), "+f"(d[13]), "+f"(d[14]), "+f"(d[15]), "+f"(d[16]), "+f"(d[17]), "+f"(d[18]), "+f"(d[19]), "+f"(d[20]), "+f"(d[21]), "+f"(d[22]), "+f"(d[23]), "+f"(d[24]), "+f"(d[25]), "+f"(d[26]), "+f"(d[27]), "+f"(d[28]), "+f"(d[29]), "+f"(d[30]), "+f"(d[31]), "+f"(d[32]), "+f"(d[33]), "+f"(d[34]), "+f"(d[35]), "+f"(d[36]), "+f"(d[37]), "+f"(d[38]), "+f"(d[39]), "+f"(d[40]), "+f"(d[41]), "+f"(d[42]), "+f"(d[43]), "+f"(d[44]), "+f"(d[45]), "+f"(d[46]), "+f"(d[47]), "+f"(d[48]), "+f"(d[49]), "+f"(d[50]), "+f"(d[51]), "+f"(d[52]), "+f"(d[53]), "+f"(d[54]), "+f"(d[55]), "+f"(d[56]), "+f"(d[57]), "+f"(d[58]), "+f"(d[59]), "+f"(d[60]), "+f"(d[61]), "+f"(d[62]), "+f"(d[63])
    : "r"(a0), "r"(a1), "r"(a2), "r"(a3), "l"(descB), "r"(scaleD));
}
__device__ __forceinline__ void wgmma_rs_n64_ta0_tb1(float (&d)[32], uint32_t a0, uint32_t a1, uint32_t a2, uint32_t a3, uint64_t descB, int scaleD) {
  asm volatile("{\n.reg .pred p;\nsetp.ne.b32 p, %37, 0;\n"
    "wgmma.mma_async.sync.aligned.m64n64k16.f32.bf16.bf16 "
    "{%0, %1, %2, %3, %4, %5, %6, %7, %8, %9, %10, %11, %12, %13, %14, %15, %16, %17, %18, %19, %20, %21, %22, %23, %24, %25, %26, %27, %28, %29, %30, %31}, "
    "{%32, %33, %34, %35}, %36, p, 1, 1, 1;\n}\n"
    : "+f"(d[0]), "+f"(d[1]), "+f"(d[2]), "+f"(d[3]), "+f"(d[4]), "+f"(d[5]), "+f"(d[6]), "+f"(d[7]), "+f"(d[8]), "+f"(d[9]), "+f"(d[10]), "+f"(d[11]), "+f"(d[12]), "+f"(d[13]), "+f"(d[14]), "+f"(d[15]), "+f"(d[16]), "+f"(d[17]), "+f"(d[18]), "+f"(d[19]), "+f"(d[20]), "+f"(d[21]), "+f"(d[22]), "+f"(d[23]), "+f"(d[24]), "+f"(d[25]), "+f"(d[26]), "+f"(d[27]), "+f"(d[28]), "+f"(d[29]), "+f"(d[30]), "+f"(d[31])
    : "r"(a0), "r"(a1), "r"(a2), "r"(a3), "l"(descB), "r"(scaleD));
}
__device__ __forceinline__ void wgmma_ss_n128_ta0_tb1(float (&d)[64], uint64_t descA, uint64_t descB, int scaleD) {
  asm volatile("{\n.reg .pred p;\nsetp.ne.b32 p, %66, 0;\n"
    "wgmma.mma_async.sync.aligned.m64n128k16.f32.bf16.bf16 "
    "{%0, %1, %2, %3, %4, %5, %6, %7, %8, %9, %10, %11, %12, %13, %14, %15, %16, %17, %18, %19, %20, %21, %22, %23, %24, %25, %26, %27, %28, %29, %30, %31, %32, %33, %34, %35, %36, %37, %38, %39, %40, %41, %42, %43, %44, %45, %46, %47, %48, %49, %50, %51, %52, %53, %54, %55, %56, %57, %58, %59, %60, %61, %62, %63}, "
    "%64, %65, p, 1, 1, 0, 1;\n}\n"
    : "+f"(d[0]), "+f"(d[1]), "+f"(d[2]), "+f"(d[3]), "+f"(d[4]), "+f"(d[5]), "+f"(d[6]), "+f"(d[7]), "+f"(d[8]), "+f"(d[9]), "+f"(d[10]), "+f"(d[11]), "+f"(d[12]), "+f"(d[13]), "+f"(d[14]), "+f"(d[15]), "+f"(d[16]), "+f"(d[17]), "+f"(d[18]), "+f"(d[19]), "+f"(d[20]), "+f"(d[21]), "+f"(d[22]), "+f"(d[23]), "+f"(d[24]), "+f"(d[25]), "+f"(d[26]), "+f"(d[27]), "+f"(d[28]), "+f"(d[29]), "+f"(d[30]), "+f"(d[31]), "+f"(d[32]), "+f"(d[33]), "+f"(d[34]), "+f"(d[35]), "+f"(d[36]), "+f"(d[37]), "+f"(d[38]), "+f"(d[39]), "+f"(d[40]), "+f"(d[41]), "+f"(d[42]), "+f"(d[43]), "+f"(d[44]), "+f"(d[45]), "+f"(d[46]), "+f"(d[47]), "+f"(d[48]), "+f"(d[49]), "+f"(d[50]), "+f"(d[51]), "+f"(d[52]), "+f"(d[53]), "+f"(d[54]), "+f"(d[55]), "+f"(d[56]), "+f"(d[57]), "+f"(d[58]), "+f"(d[59]), "+f"(d[60]), "+f"(d[61]), "+f"(d[62]), "+f"(d[63])
    : "l"(descA), "l"(descB), "r"(scaleD));
}
__device__ __forceinline__ void wgmma_ss_n160_ta0_tb1(float (&d)[80], uint64_t descA, uint64_t descB, int scaleD) {
  asm volatile("{\n.reg .pred p;\nsetp.ne.b32 p, %82, 0;\n"
    "wgmma.mma_async.sync.aligned.m64n160k16.f32.bf16.bf16 "
    "{%0, %1, %2, %3, %4, %5, %6, %7, %8, %9, %10, %11, %12, %13, %14, %15, %16, %17, %18, %19, %20, %21, %22, %23, %24, %25, %26, %27, %28, %29, %30, %31, %32, %33, %34, %35, %36, %37, %38, %39, %40, %41, %42, %43, %44, %45, %46, %47, %48, %49, %50, %51, %52, %53, %54, %55, %56, %57, %58, %59, %60, %61, %62, %63, %64, %65, %66, %67, %68, %69, %70, %71, %72, %73, %74, %75, %76, %77, %78, %79}, "
    "%80, %81, p, 1, 1, 0, 1;\n}\n"
    : "+f"(d[0]), "+f"(d[1]), "+f"(d[2]), "+f"(d[3]), "+f"(d[4]), "+f"(d[5]), "+f"(d[6]), "+f"(d[7]), "+f"(d[8]), "+f"(d[9]), "+f"(d[10]), "+f"(d[11]), "+f"(d[12]), "+f"(d[13]), "+f"(d[14]), "+f"(d[15]), "+f"(d[16]), "+f"(d[17]), "+f"(d[18]), "+f"(d[19]), "+f"(d[20]), "+f"(d[21]), "+f"(d[22]), "+f"(d[23]), "+f"(d[24]), "+f"(d[25]), "+f"(d[26]), "+f"(d[27]), "+f"(d[28]), "+f"(d[29]), "+f"(d[30]), "+f"(d[31]), "+f"(d[32]), "+f"(d[33]), "+f"(d[34]), "+f"(d[35]), "+f"(d[36]), "+f"(d[37]), "+f"(d[38]), "+f"(d[39]), "+f"(d[40]), "+f"(d[41]), "+f"(d[42]), "+f"(d[43]), "+f"(d[44]), "+f"(d[45]), "+f"(d[46]), "+f"(d[47]), "+f"(d[48]), "+f"(d[49]), "+f"(d[50]), "+f"(d[51]), "+f"(d[52]), "+f"(d[53]), "+f"(d[54]), "+f"(d[55]), "+f"(d[56]), "+f"(d[57]), "+f"(d[58]), "+f"(d[59]), "+f"(d[60]), "+f"(d[61]), "+f"(d[62]), "+f"(d[63]), "+f"(d[64]), "+f"(d[65]), "+f"(d[66]), "+f"(d[67]), "+f"(d[68]), "+f"(d[69]), "+f"(d[70]), "+f"(d[71]), "+f"(d[72]), "+f"(d[73]), "+f"(d[74]), "+f"(d[75]), "+f"(d[76]), "+f"(d[77]), "+f"(d[78]), "+f"(d[79])
    : "l"(descA), "l"(descB), "r"(scaleD));
}


template <int N> struct IC { static constexpr int value = N; };
struct Cur {
    uint32_t slot, ph;
    __device__ __forceinline__ void adv() { if (++slot == NSLOT) { slot = 0; ph ^= 1; } }
};
constexpr int E0 = 2;
__host__ __device__ constexpr uint32_t slot_of(int e) { return (e + E0) % NSLOT; }
__device__ __forceinline__ Cur cur_at(int e) { Cur c; c.slot = (e + E0) % NSLOT; c.ph = ((e + E0) / NSLOT) & 1; return c; }

__device__ __forceinline__ int kv_tile(int s) { return (0x804Cu >> (4 * s)) & 15; }
__device__ __forceinline__ int op_head(int i, int kap) { return 8 * kap + (i & 7) + 16 * (i >> 3); }

constexpr float SM_SCALE = 0.08838834764831845f * 1.4426950408889634f;

struct Ctx {
    uint32_t ring, misc;
    uint32_t rel;
    int w, warp, lane;
};
__device__ __forceinline__ void release(const Ctx& c, uint32_t off, uint32_t cnt) {
    if (c.lane < 2) mbar_arrive_cluster(c.rel + off, cnt);
}
__device__ __forceinline__ void signal_event(const Ctx& c, int ev) {
    __syncwarp();
    if (c.lane == 0) mbar_arrive(c.misc + BAR_EV + (c.w * NEV + ev) * 8);
}
template <int NK, int OFF, int N>
__device__ __forceinline__ uint32_t load_afrag(uint32_t (&a)[N], uint32_t base, const Ctx& c) {
    int r = c.lane & 7, mat = c.lane >> 3;
    uint32_t addr = base + (8 * (mat >> 1) + r) * 128 + (((2 * c.warp + (mat & 1)) ^ r) << 4);
#pragma unroll
    for (int k = 0; k < NK; k++) ldsm4t(a[OFF + 4 * k], a[OFF + 4 * k + 1], a[OFF + 4 * k + 2], a[OFF + 4 * k + 3], addr + k * 2048);
    uint32_t dep = 0;
#pragma unroll
    for (int k = 0; k < NK; k++) dep |= a[OFF + 4 * k];
    return dep & blockIdx.y;
}
__device__ __forceinline__ void tile_out(unsigned char* (&out)[2], unsigned char* dst, int row0, int perm, const Ctx& c) {
#pragma unroll
    for (int i = 0; i < 2; i++) {
        int row = row0 + 16 * c.warp + 8 * i + (c.lane >> 2);
        if (perm) row = perm32(row);
        out[i] = dst + row * 64 + (((c.lane ^ (row >> 1)) & 3) << 4);
    }
}
__device__ __forceinline__ void store_pair(const float (&a)[64], int q, unsigned char* const (&out)[2], int quarter_stride, const float (&f)[2]) {
#pragma unroll
    for (int i = 0; i < 2; i++)
        stg128(out[i] + q * quarter_stride,
               pack_bf16(a[16 * q + 2 * i] * f[i], a[16 * q + 2 * i + 1] * f[i]), pack_bf16(a[16 * q + 4 + 2 * i] * f[i], a[16 * q + 4 + 2 * i + 1] * f[i]),
               pack_bf16(a[16 * q + 8 + 2 * i] * f[i], a[16 * q + 8 + 2 * i + 1] * f[i]), pack_bf16(a[16 * q + 12 + 2 * i] * f[i], a[16 * q + 12 + 2 * i + 1] * f[i]));
}

constexpr float SAFE_SUM = 1099511627776.0f;
template <int NJ>
__device__ __forceinline__ void row_max(const float (&s)[4 * NJ], float (&mx)[2]) {
#pragma unroll
    for (int i = 0; i < 2; i++) {
        float a = fmaxf(s[2 * i], s[2 * i + 1]), b = fmaxf(s[4 + 2 * i], s[4 + 2 * i + 1]);
#pragma unroll
        for (int j = 2; j < NJ; j += 2) {
            a = fmaxf(a, fmaxf(s[4 * j + 2 * i], s[4 * j + 2 * i + 1]));
            b = fmaxf(b, fmaxf(s[4 * j + 4 + 2 * i], s[4 * j + 4 + 2 * i + 1]));
        }
        a = fmaxf(a, b);
        a = fmaxf(a, __shfl_xor_sync(0xffffffffu, a, 1));
        mx[i] = fmaxf(a, __shfl_xor_sync(0xffffffffu, a, 2));
    }
}
template <int NJ, bool SHIFT>
__device__ __forceinline__ void exp_sum(float (&s)[4 * NJ], const float (&m)[2], float& l0, float& l1) {
#pragma unroll
    for (int j = 0; j < NJ; j++) {
#pragma unroll
        for (int e = 0; e < 4; e++) s[4 * j + e] = ex2(SHIFT ? s[4 * j + e] - m[e >> 1] : s[4 * j + e]);
        l0 += s[4 * j + 0] + s[4 * j + 1]; l1 += s[4 * j + 2] + s[4 * j + 3];
    }
}
__device__ __forceinline__ void recompute_scores(float (&s)[64], const uint32_t (&q)[32], uint32_t kaddr, const Ctx& c) {
    const int r = c.lane & 7, mat = c.lane >> 3;
    const uint32_t a0 = kaddr + (8 * (mat & 1) + r) * 64 + (((mat >> 1) ^ (r >> 1)) << 4);
#pragma unroll
    for (int i = 0; i < 64; i++) s[i] = 0.f;
#pragma unroll
    for (int jp = 0; jp < 8; jp++) {
#pragma unroll
        for (int k = 0; k < 8; k++) {
            asm volatile(
                "{\n.reg .b32 b0, b1, b2, b3;\n"
                "ldmatrix.sync.aligned.m8n8.x4.trans.shared.b16 {b0,b1,b2,b3}, [%12];\n"
                "mma.sync.aligned.m16n8k16.row.col.f32.bf16.bf16.f32 {%0,%1,%2,%3}, {%8,%9,%10,%11}, {b0,b1}, {%0,%1,%2,%3};\n"
                "mma.sync.aligned.m16n8k16.row.col.f32.bf16.bf16.f32 {%4,%5,%6,%7}, {%8,%9,%10,%11}, {b2,b3}, {%4,%5,%6,%7};\n}\n"
                : "+f"(s[8 * jp]), "+f"(s[8 * jp + 1]), "+f"(s[8 * jp + 2]), "+f"(s[8 * jp + 3]),
                  "+f"(s[8 * jp + 4]), "+f"(s[8 * jp + 5]), "+f"(s[8 * jp + 6]), "+f"(s[8 * jp + 7])
                : "r"(q[4 * k]), "r"(q[4 * k + 1]), "r"(q[4 * k + 2]), "r"(q[4 * k + 3]),
                  "r"((a0 ^ ((jp & 1) << 5)) + (jp >> 1) * 8192 + k * 1024) : "memory");
        }
    }
}
__device__ __forceinline__ int mask_lim(const Ctx& c) { return perm32(16 * c.warp + (c.lane >> 2)) - 8 * (c.lane & 3); }
template <int J0>
__device__ __forceinline__ void mask_diag(float (&s)[4 * J0 + 32], const Ctx& c) {
    const int lim = mask_lim(c);
    if (c.warp < 2) {
#pragma unroll
        for (int x = 0; x < 16; x++) {
            if (2 * (x >> 2) + (x & 1) - (x & 2) > lim) s[4 * J0 + x] = -INFINITY;
            s[4 * J0 + 16 + x] = -INFINITY;
        }
    } else {
#pragma unroll
        for (int x = 0; x < 16; x++)
            if (32 + 2 * (x >> 2) + (x & 1) - (x & 2) > lim) s[4 * J0 + 16 + x] = -INFINITY;
    }
}
__device__ __forceinline__ void mask_any(float (&s)[64], int hh, const Ctx& c) {
    const int lim = mask_lim(c) + 64 * hh;
#pragma unroll
    for (int x = 0; x < 64; x++)
        if (32 * (x >> 4) + 2 * ((x >> 2) & 3) + (x & 1) - (x & 2) > lim) s[x] = -INFINITY;
}
__device__ __forceinline__ void issue_pv(float (&o)[64], const uint32_t (&p)[32], uint32_t vaddr, int acc, int mode  ) {
    uint64_t d = mkdesc(vaddr, 16, 512, 2);
    if (mode == 0) {
        wg_fence();
#pragma unroll
        for (int k = 0; k < 8; k++)
            wgmma_rs_n128_ta0_tb0(o, p[4 * k], p[4 * k + 1], p[4 * k + 2], p[4 * k + 3], d + (k >> 1) * 512 + 2 * (k & 1), k ? 1 : acc);
        wg_commit();
    } else if (mode == 1) {
        wg_fence();
#pragma unroll
        for (int k = 0; k < 4; k++) wgmma_rs_n128_ta0_tb0(o, p[4 * k], p[4 * k + 1], p[4 * k + 2], p[4 * k + 3], d + (k >> 1) * 512 + 2 * (k & 1), k != 0);
        wg_commit();
    } else {
        wg_fence();
        wgmma_rs_n128_ta0_tb0(o, p[0], p[1], p[2], p[3], d, acc);
        wg_commit();
    }
}
__device__ __forceinline__ void issue_qk(float (&s)[64], const uint32_t (&q)[32], uint32_t kaddr) {
    uint64_t d = mkdesc(kaddr, 8192, 512, 2);
    wg_fence();
#pragma unroll
    for (int k = 0; k < 8; k++) wgmma_rs_n128_ta0_tb1(s, q[4 * k], q[4 * k + 1], q[4 * k + 2], q[4 * k + 3], d + 64 * k, k != 0);
    wg_commit();
}
__device__ __forceinline__ void issue_qk_half(float (&s32)[32], const uint32_t (&q)[32], uint32_t kaddr) {
    uint64_t d = mkdesc(kaddr, 8192, 512, 2);
    wg_fence();
#pragma unroll
    for (int k = 0; k < 8; k++) wgmma_rs_n64_ta0_tb1(s32, q[4 * k], q[4 * k + 1], q[4 * k + 2], q[4 * k + 3], d + 64 * k, k != 0);
    wg_commit();
}
__device__ __forceinline__ void row_inv(const float (&l)[2], float (&inv)[2]) {
#pragma unroll
    for (int i = 0; i < 2; i++) {
        float sum = l[i];
        sum += __shfl_xor_sync(0xffffffffu, sum, 1);
        sum += __shfl_xor_sync(0xffffffffu, sum, 2);
        inv[i] = rcp_fast(sum);
    }
}

__device__ __forceinline__ const unsigned char* xn_addr(int row, int col) {
    row = perm32(row);
    return g_xn + ((row >> 7) * 10 + (col >> 6)) * 16384 + (row & 127) * 128 + ((((col & 63) >> 3) ^ (row & 7)) << 4);
}
__device__ __forceinline__ void mma16816(float (&d)[4], uint32_t a0, uint32_t a1, uint32_t a2, uint32_t a3, uint32_t b0, uint32_t b1) {
    asm volatile("mma.sync.aligned.m16n8k16.row.col.f32.bf16.bf16.f32 {%0,%1,%2,%3}, {%4,%5,%6,%7}, {%8,%9}, {%0,%1,%2,%3};"
                 : "+f"(d[0]), "+f"(d[1]), "+f"(d[2]), "+f"(d[3]) : "r"(a0), "r"(a1), "r"(a2), "r"(a3), "r"(b0), "r"(b1));
}
__device__ __forceinline__ uint32_t lds32(uint32_t addr) { uint32_t v; asm volatile("ld.shared.u32 %0, [%1];" : "=r"(v) : "r"(addr)); return v; }

__device__ __forceinline__ int fresh_lane() { int l; asm volatile("mov.u32 %0, %%laneid;" : "=r"(l)); return l; }
__device__ __forceinline__ void ln_rows(const __nv_bfloat16* x, int row0, uint32_t wr_s) {
    int lane = fresh_lane();
    int hl = lane & 15, row = row0 + (lane >> 4);
    uint32_t v[20];
#pragma unroll
    for (int i = 0; i < 5; i++) {
        const uint4 u = __ldg(reinterpret_cast<const uint4*>(x + (size_t)row * DM + 128 * i + 8 * hl));
        v[4 * i] = u.x; v[4 * i + 1] = u.y; v[4 * i + 2] = u.z; v[4 * i + 3] = u.w;
    }
    float mean = 0.f, m2 = 0.f, acc2 = 0.f;
#pragma unroll
    for (int i = 0; i < 20; i++) { mean += bf_lo(v[i]); acc2 += bf_hi(v[i]); }
    mean = (mean + acc2) * (1.0f / 40);
    acc2 = 0.f;
#pragma unroll
    for (int i = 0; i < 20; i++) {
        float d0 = __uint_as_float(__byte_perm(v[i], 0, 0x1044)) - mean, d1 = __uint_as_float(__byte_perm(v[i], 0, 0x3244)) - mean;
        m2 = fmaf(d0, d0, m2); acc2 = fmaf(d1, d1, acc2);
    }
    m2 += acc2;
    acc2 = 0.f;
#pragma unroll
    for (int o = 1; o < 16; o <<= 1) {
        float mo = __shfl_xor_sync(0xffffffffu, mean, o), qo = __shfl_xor_sync(0xffffffffu, m2, o), d = mo - mean;
        m2 = fmaf(d * d, 20.0f * o, m2 + qo);
        mean = 0.5f * (mean + mo);
    }
    const uint32_t mb2 = pack_bf16(mean, mean);
    const float inv = rcp_fast(bf_round(sqrt_fast(bf_round(bf_round(m2 * (1.0f / DM)) + 1e-5f))));
    float dot = 0.f;
    lane = fresh_lane(); hl = lane & 15; row = row0 + (lane >> 4);
    if (hl == 0) g_stats[row] = make_uint2(mb2, __float_as_uint(inv));
    unsigned char* xp = const_cast<unsigned char*>(xn_addr(row, 8 * hl));
#pragma unroll
    for (int i = 0; i < 5; i++) {
        uint32_t ww[4];
        asm volatile("ld.shared.v4.b32 {%0,%1,%2,%3}, [%4];" : "=r"(ww[0]), "=r"(ww[1]), "=r"(ww[2]), "=r"(ww[3]) : "r"(wr_s + 256 * i + 16 * hl) : "memory");
#pragma unroll
        for (int e = 0; e < 4; e++) {
            uint32_t d;
            asm("sub.rn.bf16x2 %0, %1, %2;" : "=r"(d) : "r"(v[4 * i + e]), "r"(mb2));
            d = pack_bf16(bf_lo(d) * inv, bf_hi(d) * inv);
            v[4 * i + e] = d;
            dot = fmaf(bf_lo(d), bf_lo(ww[e]), dot);
            acc2 = fmaf(bf_hi(d), bf_hi(ww[e]), acc2);
        }
        stg128(xp + i * 32768, v[4 * i], v[4 * i + 1], v[4 * i + 2], v[4 * i + 3]);
    }
    dot += acc2;
#pragma unroll
    for (int o = 8; o > 0; o >>= 1) dot += __shfl_xor_sync(0xffffffffu, dot, o);
    lane = fresh_lane();
    if ((lane & 15) == 0) g_router[row0 + (lane >> 4)] = bf_round(dot);
}

__device__ __forceinline__ void aux_cta(const CUtensorMap* tmG, const CUtensorMap* tmU, const CUtensorMap* tmD, unsigned char* sm, int a) {
    constexpr int STG = 57344, XS = 3 * STG, HS = XS + 8 * 1296, KEY = HS + 8 * 912, MI = KEY + 8192;
    const int tid = threadIdx.x, warp = __shfl_sync(0xffffffffu, tid >> 5, 0), lane = tid & 31;
    const uint32_t sb = smem_u32(sm);
    const uint32_t full = sb + MI, empty = sb + MI + 32;
    int* s_sel = reinterpret_cast<int*>(sm + MI + 64);
    float* s_r = reinterpret_cast<float*>(sm + MI + 96);
    volatile unsigned* s_misc = reinterpret_cast<volatile unsigned*>(sm + MI + 128);
    uint32_t* s_key = reinterpret_cast<uint32_t*>(sm + KEY);
    if (tid == 0) {
        for (int i = 0; i < 3; i++) { mbar_init(full + 8 * i, 1); mbar_init(empty + 8 * i, 10); }
        asm volatile("fence.mbarrier_init.release.cluster;" ::: "memory");
    }
    __syncthreads();
    if (warp == 11) {
        if (elect_one()) {
            int st = 0; uint32_t ph = 0;
#pragma unroll 1
            for (int s = 0; s < 34; s++) {
                mbar_wait(empty + 8 * st, ph ^ 1);
                const uint32_t dst = sb + st * STG, fb = full + 8 * st;
                if (s < 20) {
                    mbar_expect_tx(fb, 57344);
                    tma3d(dst, tmG, 0, 32 * s, 7 * a, fb);
                    tma3d(dst + 28672, tmU, 0, 32 * s, 7 * a, fb);
                } else {
                    mbar_expect_tx(fb, 40960);
                    tma3d(dst, tmD, 0, 448 * a + 32 * (s - 20), 0, fb);
                }
                if (s >= 3) {
#pragma unroll 1
                    for (int f = (s == 3 ? 4 : s + 6); f <= s + 6 && f < 34; f++) {
                        if (f < 20) { tma3d_prefetch(tmG, 0, 32 * f, 7 * a); tma3d_prefetch(tmU, 0, 32 * f, 7 * a); }
                        else tma3d_prefetch(tmD, 0, 448 * a + 32 * (f - 20), 0);
                    }
                }
                if (++st == 3) { st = 0; ph ^= 1; }
            }
        }
        return;
    }
    if (warp == 10) return;
    if (tid < 8) {
        unsigned e = *reinterpret_cast<volatile unsigned*>(&g_epoch);
        if (tid == 0) s_misc[0] = e;
        flag_wait(flag_ptr(FL_LN + tid), (e + 1) * (tid < 4 ? 33u : 128u));
    }
    bar_sync(1, 320);
    const unsigned ep = s_misc[0];
    auto top8 = [&](uint32_t (&key)[8]) {
        uint32_t mine = 0;
#pragma unroll 1
        for (int r = 0; r < TOPC; r++) {
            uint32_t best = 0;
#pragma unroll
            for (int i = 0; i < 8; i++) best = max(best, key[i]);
            best = __reduce_max_sync(0xffffffffu, best);
#pragma unroll
            for (int i = 0; i < 8; i++) if (key[i] == best) key[i] = 0;
            if (lane == r) mine = best;
        }
        return mine;
    };
#pragma unroll 1
    for (int pass = 0; pass < 2; pass++) {
        if (warp < (pass ? 1 : 8)) {
            uint32_t key[8];
#pragma unroll
            for (int i = 0; i < 8; i++) {
                if (pass == 0) {
                    int idx = warp * 256 + i * 32 + lane;
                    uint32_t b = __float_as_uint(__ldcg(g_router + idx)) >> 16;
                    b = (b & 0x8000u) ? (~b & 0xffffu) : (b | 0x8000u);
                    key[i] = (b << 16) | (uint32_t)(0xffff - idx);
                } else key[i] = i < 2 ? s_key[i * 32 + lane] : 0u;
            }
            uint32_t best = top8(key);
            if (lane < TOPC) {
                if (pass == 0) s_key[warp * 8 + lane] = best;
                else {
                    uint32_t b = best >> 16;
                    b = (b & 0x8000u) ? (b & 0x7fffu) : (~b & 0xffffu);
                    s_sel[lane] = 0xffff - (int)(best & 0xffffu);
                    s_r[lane] = bf_round(rcp_fast(1.0f + __expf(fminf(-__uint_as_float(b << 16), 80.f))));
                }
            }
        }
        bar_sync(1, 320);
    }
#pragma unroll 1
    for (int it = 0; it < 2; it++) {
        int i = tid + it * 320, tk = i / 80, ch = i % 80;
        *reinterpret_cast<uint4*>(sm + XS + tk * 1296 + ch * 16) = __ldcg(reinterpret_cast<const uint4*>(xn_addr(s_sel[tk], ch * 8)));
    }
    bar_sync(1, 320);
    const int g = lane >> 2, t = lane & 3;
    const uint32_t woff = warp * 4096 + (8 * (lane >> 4) + (lane & 7)) * 128 + ((((lane >> 3) & 1) ^ (lane & 7)) << 4);
    int st = 0; uint32_t ph = 0;
    float ga[4][4], ua[4][4];
#pragma unroll
    for (int i = 0; i < 4; i++)
#pragma unroll
        for (int e = 0; e < 4; e++) { ga[i][e] = 0.f; ua[i][e] = 0.f; }
#pragma unroll 1
    for (int s = 0; s < 34; s++) {
        if (s == 20) {
            if (warp < 7) {
#pragma unroll 1
                for (int i = 0; i < 4; i++) {
#pragma unroll
                    for (int e = 0; e < 4; e++) {
                        float gv = bf_round(ga[0][e]), uv = bf_round(ua[0][e]);
                        float sg = bf_round(gv * rcp_fast(1.0f + __expf(fminf(-gv, 80.f))));
                        int f = warp * 64 + i * 16 + g + 8 * (e >> 1), tk = 2 * t + (e & 1);
                        *reinterpret_cast<__nv_bfloat16*>(sm + HS + tk * 912 + f * 2) = __float2bfloat16_rn(sg * uv);
                        ga[0][e] = ga[1][e]; ga[1][e] = ga[2][e]; ga[2][e] = ga[3][e]; ga[3][e] = 0.f;
                        ua[0][e] = ua[1][e]; ua[1][e] = ua[2][e]; ua[2][e] = ua[3][e];
                    }
                }
            }
            bar_sync(1, 320);
        }
        mbar_wait(full + 8 * st, ph);
        if (s >= 20 || warp < 7) {
#pragma unroll
            for (int kk = 0; kk < 2; kk++) {
                uint32_t xb = sb + (s < 20 ? XS + g * 1296 + s * 64 : HS + g * 912 + (s - 20) * 64) + 32 * kk + 4 * t;
                uint32_t b0 = lds32(xb), b1 = lds32(xb + 16);
                uint32_t wa = sb + st * STG + woff + kk * 2048;
#pragma unroll
                for (int i = 0; i < 4; i++) {
                    uint32_t a0, a1, a2, a3;
                    ldsm4t(a0, a1, a2, a3, wa ^ (i << 5));
                    mma16816(ga[i], a0, a1, a2, a3, b0, b1);
                    if (s < 20) {
                        ldsm4t(a0, a1, a2, a3, (wa ^ (i << 5)) + 28672);
                        mma16816(ua[i], a0, a1, a2, a3, b0, b1);
                    }
                }
            }
        }
        asm volatile("fence.proxy.async.shared::cta;" ::: "memory");
        __syncwarp();
        if (lane == 0) mbar_arrive(empty + 8 * st);
        if (++st == 3) { st = 0; ph ^= 1; }
    }
#pragma unroll
    for (int i = 0; i < 4; i++)
#pragma unroll
        for (int e = 0; e < 4; e += 2)
            *reinterpret_cast<float2*>(g_moe_part + (a * DM + warp * 64 + i * 16 + g + 4 * e) * 8 + 2 * t) = make_float2(ga[i][e], ga[i][e + 1]);
    bar_sync(1, 320);
    if (tid == 0) {
        __threadfence();
        unsigned old = atomicAdd(flag_ptr(FL_MOE_CNT), 1u);
        s_misc[1] = (old == ep * 4u + 3u);
        __threadfence();
    }
    bar_sync(1, 320);
    if (s_misc[1]) {
        const float4* pp = reinterpret_cast<const float4*>(g_moe_part);
#pragma unroll 1
        for (int i = tid; i < DM * 2; i += 320) {
            float4 v0 = __ldcg(pp + i), v1 = __ldcg(pp + DM * 2 + i), v2 = __ldcg(pp + DM * 4 + i), v3 = __ldcg(pp + DM * 6 + i);
            float y[4] = {v0.x + v1.x + v2.x + v3.x, v0.y + v1.y + v2.y + v3.y, v0.z + v1.z + v2.z + v3.z, v0.w + v1.w + v2.w + v3.w};
#pragma unroll
            for (int e = 0; e < 4; e++) {
                int col = i >> 1, tk = (i & 1) * 4 + e;
                float upd = bf_round(bf_round(y[e]) * s_r[tk]);
                float xn = __bfloat162float(*reinterpret_cast<const __nv_bfloat16*>(sm + XS + tk * 1296 + col * 2));
                g_brow[tk * DM + col] = __float2bfloat16_rn(xn + upd);
            }
        }
        if (tid < TOPC) g_sel[tid] = s_sel[tid];
        bar_sync(1, 320);
        if (tid == 0) {
            flag_signal(flag_ptr(FL_MOE_DONE));
            *reinterpret_cast<volatile unsigned*>(&g_epoch) = ep + 1;
        }
    }
}

__global__ void __cluster_dims__(2, 1, 1) __launch_bounds__(384, 1)
fused_kernel(const __grid_constant__ CUtensorMap tmC, const __grid_constant__ CUtensorMap tmWk, const __grid_constant__ CUtensorMap tmWv,
             const __grid_constant__ CUtensorMap tmWq, const __grid_constant__ CUtensorMap tmWo,
             const __grid_constant__ CUtensorMap tmG, const __grid_constant__ CUtensorMap tmU, const __grid_constant__ CUtensorMap tmD, const Params P) {
    extern __shared__ __align__(1024) unsigned char smem_raw[];
    const uint32_t ring = smem_u32(smem_raw);
    const uint32_t misc = ring + RING_BYTES;
    const int tid = threadIdx.x;
    const int rank = blockIdx.x & 1;
    uint32_t smid, nsm;
    asm("mov.u32 %0, %%smid;" : "=r"(smid));
    asm("mov.u32 %0, %%nsmid;" : "=r"(nsm));
    if (nsm != 132) smid = blockIdx.x;
    auto role_of = [](int tpc) {
        return tpc < 32 ? (tpc & 7) * 8 + (tpc >> 3) : tpc < 60 ? (1 + (tpc - 32) % 7) * 8 + 4 + (tpc - 32) / 7 : tpc < 64 ? tpc - 56 : tpc;
    };
    int mc = role_of(smid >> 1);

    auto prefetch_w = [&](int ch) {
        const int i = tid - 128;
        asm volatile("prefetch.global.L2 [%0];" ::"l"((rank ? P.wv : P.wk) + (size_t)(ch * 128 + (mc & 3) * 32 + (i >> 3)) * 4096 + (mc >> 2) * 128 + (i & 7) * 16));
    };
    if (tid >= 128 && mc < 64) {
        if (tid < 256) asm volatile("prefetch.global.L2 [%0];" ::"l"(P.c + (size_t)((12 + (mc & 3)) * 128 + ((mc >> 2) * 2 + rank) * 4) * DC + (tid - 128) * 16));
        prefetch_w(0);
    }
    auto load_w0 = [&]() {
        const CUtensorMap* tw = rank ? &tmWv : &tmWk;
        mbar_expect_tx(misc + BAR_FULL + 8 * slot_of(0), SLOT_BYTES);
        tma2d(ring + slot_of(0) * SLOT_BYTES, tw, (mc >> 2) * 128, 0, misc + BAR_FULL + 8 * slot_of(0));
        tma2d(ring + slot_of(0) * SLOT_BYTES + 16384, tw, (mc >> 2) * 128 + 64, 0, misc + BAR_FULL + 8 * slot_of(0));
    };
    if (tid == 0) {
#pragma unroll
        for (int i = 0; i < NSLOT; i++) mbar_init(misc + BAR_FULL + 8 * i, 1);
#pragma unroll
        for (int i = 0; i < E0; i++) mbar_arrive(misc + BAR_FULL + 8 * i);
        asm volatile("fence.mbarrier_init.release.cluster;" ::: "memory");
        if (mc < 64) load_w0();
    }
    if (tid == 160) {
        asm volatile("st.shared.u32 [%0], %1;" ::"r"(misc + MISC_SMID), "r"(smid) : "memory");
        asm volatile("fence.release.sync_restrict::shared::cta.cluster;" ::: "memory");
    }
    if (tid == 32) {
        asm volatile("prefetch.tensormap [%0];" ::"l"(&tmC) : "memory");
#pragma unroll
        for (int i = 0; i < NSLOT; i++) mbar_init(misc + BAR_EMPTY + 8 * i, 16);
#pragma unroll
        for (int i = 0; i < E0; i++) mbar_arrive_cluster(misc + BAR_EMPTY + 8 * i, 16);
        asm volatile("fence.mbarrier_init.release.cluster;" ::: "memory");
    }
    if (tid == 64) {
#pragma unroll
        for (int i = 0; i < NST3; i++) { mbar_init(misc + BAR_FULL3 + 8 * i, 1); mbar_init(misc + BAR_EMPTY3 + 8 * i, 16); }
#pragma unroll
        for (int i = 0; i < 4; i++) mbar_init(misc + BAR_PROG + 8 * i, 1);
        mbar_init(misc + BAR_LN, 2);
        asm volatile("fence.mbarrier_init.release.cluster;" ::: "memory");
    }
    if (tid == 96) {
#pragma unroll
        for (int i = 0; i < 24; i++) mbar_init(misc + BAR_DEP + 8 * i, 1);
    }
    if (tid == 128) {
#pragma unroll
        for (int i = 0; i < 2 * NEV; i++) mbar_init(misc + BAR_EV + 8 * i, 4);
    }
    __syncthreads();
    asm volatile("barrier.cluster.arrive.relaxed.aligned;\nbarrier.cluster.wait.aligned;" ::: "memory");
    {
        uint32_t peer;
        asm volatile("{\n.reg .b32 r, a;\nmov.u32 r, %%cluster_ctarank;\nxor.b32 r, r, 1;\nmapa.shared::cluster.u32 a, %1, r;\n"
                     "ld.shared::cluster.u32 %0, [a];\n}\n" : "=r"(peer) : "r"(misc + MISC_SMID) : "memory");
        if ((__shfl_sync(0xffffffffu, peer, 0) ^ smid) != 1) {
            if (tid == 0) {
                const unsigned ep1 = *reinterpret_cast<volatile unsigned*>(&g_epoch) + 1;
                if ((smid & 1) == 0) atomicExch(g_roleq + 2 + (atomicAdd(g_roleq, 1u) & 127), (ep1 << 8) | (smid >> 1));
                if (rank == 0) {
                    unsigned* slot = g_roleq + 2 + (atomicAdd(g_roleq + 1, 1u) & 127);
                    unsigned v = 0;
                    for (int spin = 0; spin < 4000000 && ((v = atomicAdd(slot, 0u)) >> 8) != (ep1 & 0xffffffu); spin++) {}
                    asm volatile("st.shared::cluster.u32 [%0], %1;" ::"r"(mapa(misc + MISC_SMID + 4, 0)), "r"(v & 255) : "memory");
                    asm volatile("st.shared::cluster.u32 [%0], %1;" ::"r"(mapa(misc + MISC_SMID + 4, 1)), "r"(v & 255) : "memory");
                }
                if (mc < 64) {
                    mbar_wait(misc + BAR_FULL + 8 * slot_of(0), 0);
                    asm volatile("mbarrier.inval.shared::cta.b64 [%0];" ::"r"(misc + BAR_FULL + 8 * slot_of(0)) : "memory");
                    mbar_init(misc + BAR_FULL + 8 * slot_of(0), 1);
                    asm volatile("fence.mbarrier_init.release.cluster;" ::: "memory");
                }
            }
            __syncwarp();
            asm volatile("barrier.cluster.arrive.aligned;\nbarrier.cluster.wait.aligned;" ::: "memory");
            mc = role_of(__shfl_sync(0xffffffffu, lds32(misc + MISC_SMID + 4), 0));
            if (tid == 0 && mc < 64) load_w0();
            __syncwarp();
        }
    }
    const int cta = mc * 2 + rank;
    const bool aux = mc >= 64;
    const int team = mc >> 2, k = mc & 3;
    const int u3 = (mc >> 4) * 2 + (team & 1), s3 = k, kap = (mc >> 3) & 1;
    const int partner = cta ^ 16;
    const int b0 = k, b1 = 7 - k;
    if (tid >= 128 && !aux) prefetch_w(1);
    if (tid == 256 && !aux) {
        const CUtensorMap* tw = rank ? &tmWv : &tmWk;
#pragma unroll
        for (int e = 1; e < NSLOT; e++) {
            const uint32_t fb = misc + BAR_FULL + 8 * slot_of(e), dst = ring + slot_of(e) * SLOT_BYTES;
            mbar_expect_tx(fb, SLOT_BYTES);
            if (e & 1) tma2d_mc(dst + rank * 16384, &tmC, (e >> 1) * 128 + rank * 64, (12 + k) * 128, fb);
            else { tma2d(dst, tw, team * 128, e * 64, fb); tma2d(dst + 16384, tw, team * 128 + 64, e * 64, fb); }
        }
    }
    const int wg = __shfl_sync(0xffffffffu, tid >> 7, 0);

    if (wg == 0 || aux) {
        asm volatile("setmaxnreg.dec.sync.aligned.u32 40;");
        const int warp = __shfl_sync(0xffffffffu, tid >> 5, 0), lane = tid & 31;
        if (warp == 0 && !aux) {
            const bool lead = elect_one();
            Cur c = cur_at(NSLOT);
            uint32_t dst, fb;
            auto acquire = [&]() {
                mbar_wait_sleep(misc + BAR_EMPTY + 8 * c.slot, c.ph ^ 1);
                fb = misc + BAR_FULL + 8 * c.slot; dst = ring + c.slot * SLOT_BYTES;
                if (lead) mbar_expect_tx(fb, SLOT_BYTES);
                c.adv();
            };
            auto load_w = [&](const CUtensorMap* tm, int col, int row) {
                acquire();
                if (lead) { tma2d(dst, tm, col, row, fb); tma2d(dst + 16384, tm, col + 64, row, fb); }
            };
            auto load_half = [&](const unsigned char* src) {
                acquire();
                if (lead) bulk_load_mc(dst + rank * 16384, src, 16384, fb);
            };
            auto dep_wait = [&](int d) { mbar_wait_sleep(misc + BAR_DEP + 8 * d, 0); fence_async_global(); };
            auto op_prefetch = [&](int i) {
                const int head = op_head(i, kap);
                l2_prefetch(reinterpret_cast<const unsigned char*>(P.wo) + head * 163840 + (u3 * 8 + s3 * 2 + rank) * 2560, 2560);
                if (i < 8) l2_prefetch(g_ctx + (size_t)(head * 32 + 4 * u3 + 2 * rank) * 16384 + s3 * 8192, 8192);
            };
            if (lead) l2_prefetch(reinterpret_cast<const unsigned char*>(P.c) + (size_t)cta * 12288, 12288);
            const CUtensorMap* tw = rank ? &tmWv : &tmWk;
            const unsigned char* Kh = g_K + (size_t)team * 32 * 16384 + rank * 16384;
            const unsigned char* Vh = g_V + (size_t)team * 32 * 16384 + rank * 16384;
#pragma unroll 1
            for (int v = 0; v < 2; v++) {
                const int h = team + 16 * v;
#pragma unroll 1
                for (int i = v ? 0 : 3; i < 16; i++) {
                    if (i < 4 && v) load_w(tw, h * 128, i * 128);
                    if (v && i == 3 && lead) mbar_arrive(misc + BAR_PROG + 8);
                    if (v && (i == 3 || i == 7)) dep_wait(D_WAR + (i > 3));
                    acquire();
                    if (lead) tma2d_mc(dst + rank * 16384, &tmC, (i & 3) * 128 + rank * 64, (kv_tile(i >> 2) + k) * 128, fb);
                    if (i == 8 && lead) {
                        tma2d_prefetch(&tmWq, h * 128 + rank * 64, k * 64); tma2d_prefetch(&tmWq, h * 128 + rank * 64, k * 64 + 256);
                        if (k < 2) tma2d_prefetch(&tmWq, h * 128 + rank * 64, k * 64 + 512);
                    }
                }
                int togo = v ? PF_START : 11;
#pragma unroll 1
                for (int r = 0; r < 2; r++) {
                    const int p = r ? b1 : b0, n = 2 * p + 1;
                    if (v == 0) dep_wait(D_LN + r);
                    const int g0 = r ? rank ^ 1 : 3 - rank, g1 = 3 - g0;
                    const unsigned char* x0 = g_xn + (2 * p + (g0 >> 1)) * 163840 + (g0 & 1) * 8192;
                    const unsigned char* x1 = g_xn + (2 * p + (g1 >> 1)) * 163840 + (g1 & 1) * 8192;
#pragma unroll 1
                    for (int kc = 0; kc < 10; kc++) {
                        acquire();
                        if (lead) {
                            tma2d_mc(dst + 16384 + rank * 8192, &tmWq, h * 128 + rank * 64, kc * 64, fb);
                            bulk_load(dst, x0 + kc * 16384, 8192, fb);
                            bulk_load(dst + 8192, x1 + kc * 16384, 8192, fb);
                        }
                    }
                    dep_wait(D_KV + 2 * v + r);
                    load_half(Kh + n * 32768);
#pragma unroll 1
                    for (int j = n - 1; j >= 0; j--) {
                        load_half(Kh + j * 32768); load_half(Vh + (j + 1) * 32768);
                        if (v == 0 && r && j == 7 && lead) mbar_arrive(misc + BAR_PROG);
                        --togo;
                        if (v == 0 && togo == 0 && lead) {
                            tma2d_prefetch(tw, h * 128 + 2048, k * 128); tma2d_prefetch(tw, h * 128 + 2112, k * 128);
                            l2_prefetch(reinterpret_cast<const unsigned char*>(P.c) + (size_t)cta * 16384, 16384);
                        }
                        if (v && togo <= 0 && togo > -OP_PF && lead) op_prefetch(-togo);
                    }
                    load_half(Vh);
                }
            }
            mbar_wait_sleep(misc + BAR_EMPTY + 8 * c.slot, c.ph ^ 1); c.adv();
            int st = 0; uint32_t ph3 = 0;
#pragma unroll 1
            for (int i = 0; i < 32; i++) {
                const int head = op_head(i >> 1, kap);
                if ((i & 1) == 0) dep_wait(D_CTX + (i >> 1));
                if (i < NST3) { mbar_wait_sleep(misc + BAR_EMPTY + 8 * c.slot, c.ph ^ 1); c.adv(); }
                else mbar_wait_sleep(misc + BAR_EMPTY3 + 8 * st, ph3 ^ 1);
                fb = misc + BAR_FULL3 + 8 * st; dst = ring + st * ST3_BYTES;
                if (i == LATE_AT && lead) mbar_arrive(misc + BAR_PROG + 16);
                if (lead) {
                    mbar_expect_tx(fb, ST3_BYTES);
                    const unsigned char* src = g_ctx + (size_t)(head * 32 + 4 * u3 + 2 * rank) * 16384 + (i & 1) * 8192;
                    bulk_load(dst, src, 8192, fb);
                    bulk_load(dst + 8192, src + 16384, 8192, fb);
                    tma3d_mc(dst + 16384 + rank * 10240, &tmWo, 0, head * 128 + (i & 1) * 64 + rank * 32, 5 * s3, fb);
                    if ((i & 1) && (i >> 1) + OP_PF < 16) op_prefetch((i >> 1) + OP_PF);
                }
                if (++st == NST3) { st = 0; ph3 ^= 1; }
            }
        } else {
        if (warp >= 1 && warp <= 3 && lane < 27 && (warp - 1) * 27 + lane < 80) {
            const int ch = (warp - 1) * 27 + lane;
            uint4 u = __ldg(reinterpret_cast<const uint4*>(P.wr) + ch);
            asm volatile("st.shared.v4.b32 [%0], {%1,%2,%3,%4};" ::"r"(misc + MISC_WR + 16 * ch), "r"(u.x), "r"(u.y), "r"(u.z), "r"(u.w) : "memory");
        }
        bar_sync(3, aux ? 384 : 96);
        const int nln = aux ? (warp < 8 ? 3 : 2) : (warp == 3 ? 1 : 3), rstep = aux ? 24 : -512;
        int lrow = aux ? (cta - 128) * 256 + 192 + 2 * warp : (cta >> 5) * 256 + (cta & 31) * 6 + (warp - 1) * 2;
        int lnext = aux ? lrow + 24 : 1536 + cta * 4 + (warp - 1) * 2;
#pragma unroll 1
        for (int t = 0; t < nln; t++) {
            if (t + 1 < nln) {
                const int ll = fresh_lane();
#pragma unroll
                for (int i = 0; i < 3; i++)
                    if (i * 32 + ll < 80) asm volatile("prefetch.global.L2 [%0];" ::"l"(P.x + (size_t)lnext * DM + (i * 32 + ll) * 16));
            }
            ln_rows(P.x, lrow, misc + MISC_WR);
            __syncwarp();
            if (fresh_lane() == 0 && warp < 3 && !aux) {
                if (t) flag_signal(flag_ptr(FL_LN + (lrow >> 8))); else mbar_arrive(misc + BAR_LN);
            }
            lrow = lnext; lnext += rstep;
        }
        if (aux) {
            bar_sync(3, 384);
            if (tid == 320) flag_signal(flag_ptr(FL_LN + cta - 128));
            __syncwarp();
            asm volatile("setmaxnreg.inc.sync.aligned.u32 128;");
            aux_cta(&tmG, &tmU, &tmD, smem_raw, cta - 128);
        } else
        if (warp == 3) {
            const unsigned ep1 = *reinterpret_cast<volatile unsigned*>(&g_epoch) + 1;
            if (lane == 0) {
                asm volatile("st.shared.u32 [%0], %1;" ::"r"(misc + MISC_EPOCH), "r"(ep1) : "memory");
                mbar_wait(misc + BAR_LN, 0);
                flag_signal(flag_ptr(FL_LN + (cta >> 5)));
                flag_wait(flag_ptr(FL_LN + b0), ep1 * 33u);
                mbar_arrive(misc + BAR_DEP + 8 * D_LN);
#pragma unroll 1
                for (int i = 0; i < 4; i++) {
                    mbar_wait(misc + BAR_EV + 8 * (NEV + EV_KV + i), 0);
                    if (i < 2) {
                        mbar_wait(misc + BAR_EV + 8 * (EV_KV + i), 0);
                        asm volatile("red.release.gpu.global.add.u32 [%0], 2;" ::"l"(flag_ptr(FL_KV + team * 8 + i)) : "memory");
                    }
                    if (i == 1) {
                        flag_wait(flag_ptr(FL_LN + b1), ep1 * 128u);
                        mbar_arrive(misc + BAR_DEP + 8 * (D_LN + 1));
                    }
                    flag_wait(flag_ptr(FL_KV + team * 8 + i), ep1 * 16u);
                    mbar_arrive(misc + BAR_DEP + 8 * (D_KV + i));
                    if (i == 1) {
#pragma unroll 1
                        for (int j = 0; j < 2; j++) {
                            mbar_wait(misc + BAR_PROG + 8 * j, 0);
                            asm volatile("red.relaxed.gpu.global.add.u32 [%0], 1;" ::"l"(flag_ptr(FL_WAR + 2 * team + j)) : "memory");
                            flag_wait(flag_ptr(FL_WAR + 2 * team + j), ep1 * 8u);
                            mbar_arrive(misc + BAR_DEP + 8 * (D_WAR + j));
                        }
                    }
                }
                flag_wait(flag_ptr(FL_MOE_DONE), ep1);
                int4 s0 = __ldcg(reinterpret_cast<const int4*>(g_sel)), s1 = __ldcg(reinterpret_cast<const int4*>(g_sel) + 1);
                asm volatile("st.shared.v4.u32 [%0], {%1,%2,%3,%4};" ::"r"(misc + MISC_SEL), "r"(s0.x), "r"(s0.y), "r"(s0.z), "r"(s0.w) : "memory");
                asm volatile("st.shared.v4.u32 [%0], {%1,%2,%3,%4};" ::"r"(misc + MISC_SEL + 16), "r"(s1.x), "r"(s1.y), "r"(s1.z), "r"(s1.w) : "memory");
                mbar_arrive(misc + BAR_SEL);
            }
            __syncwarp();
            const unsigned* cf = flag_ptr(FL_CTX + op_head(lane & 15, kap) * 8 + u3);
#pragma unroll 1
            for (int half = 0; half < 2; half++) {
                if (half) mbar_wait(misc + BAR_EV + 8 * (EV_CTX + 3), 0);
                bool done = (lane >> 3) != half;
                for (int spin = 0; spin < 4000000; spin++) {
                    if (!done) {
                        unsigned v;
                        asm volatile("ld.acquire.gpu.global.u32 %0, [%1];" : "=r"(v) : "l"(cf) : "memory");
                        if ((int)(v - ep1 * 4u) >= 0) { mbar_arrive(misc + BAR_DEP + 8 * (D_CTX + lane)); done = true; }
                    }
                    if (__all_sync(0xffffffffu, done)) break;
                    __nanosleep(64);
                }
            }
        } else {
            const int w = warp - 1;
            if (lane == 0) {
                const uint32_t eb = misc + BAR_EV + w * 8 * NEV;
#pragma unroll 1
                for (int i = 0; i < 6; i++) {
                    const bool kv = (i >> 1) == 1;
                    const int ci = i < 2 ? i : i - 2;
                    mbar_wait(eb + 8 * (kv ? EV_KV + i : EV_CTX + ci), 0);
                    if (i == 1) {
                        asm volatile("cp.async.bulk.global.shared::cta.bulk_group [%0], [%1], 16384;"
                                     ::"l"(g_ctx + (size_t)(team * 32 + 4 * b1 + (w ? 3 - (rank ^ 1) : rank ^ 1)) * 16384),
                                       "r"(ring + slot_of(78) * SLOT_BYTES + w * 16384) : "memory");
                        asm volatile("cp.async.bulk.commit_group;" ::: "memory");
                        asm volatile("cp.async.bulk.wait_group.read 0;" ::: "memory");
                        mbar_arrive_cluster(mapa(misc + BAR_EMPTY + 8 * slot_of(78), 0), 4);
                        mbar_arrive_cluster(mapa(misc + BAR_EMPTY + 8 * slot_of(78), 1), 4);
                        asm volatile("cp.async.bulk.wait_group 0;" ::: "memory");
                        fence_async_global();
                    }
                    flag_signal(flag_ptr(kv ? FL_KV + team * 8 + i : FL_CTX + (team + 16 * (ci >> 1)) * 8 + ((ci & 1) ? b1 : b0)));
                }
            }
            __syncwarp();
            mbar_wait(misc + BAR_PROG + 16, 0);
            const int row = (2 * u3 + rank) * 128 + 64 * w + perm32(16 * (lane >> 3) + 8 * kap + (lane & 7));
#pragma unroll
            for (int i = 0; i < 10; i++) asm volatile("prefetch.global.L2 [%0];" ::"l"(P.x + (size_t)row * DM + 160 * s3 + 16 * i));
            asm volatile("prefetch.global.L2 [%0];" ::"l"(g_stats + row));
            if (lane < 5) asm volatile("prefetch.global.L2 [%0];" ::"l"(g_brow + ((cta & 31) * 10 + w * 5 + lane) * 16));
            mbar_wait(misc + BAR_EV + w * 8 * NEV + 8 * EV_END, 0);
        }
        }
    } else {
        asm volatile("setmaxnreg.inc.sync.aligned.u32 232;");
        Ctx c;
        c.ring = ring; c.misc = misc; c.w = wg - 1; c.warp = __shfl_sync(0xffffffffu, (tid >> 5) & 3, 0); c.lane = tid & 31;
        c.rel = mapa(misc, tid & 1);
        const int w = c.w;
        if (w == 1) bar_arrive(1, 256);
        prefetch_w(2); prefetch_w(3);
        Cur cur = cur_at(0);
        float o[64], inv[2];
        unsigned char* out[2];
        uint32_t wf[128];
        Cur cw = cur;
        auto load_wchunk = [&](auto CH) {
            constexpr int ch = decltype(CH)::value;
            mbar_wait_hot(misc + BAR_FULL + 8 * cw.slot, cw.ph);
            const uint32_t z = load_afrag<8, 32 * ch>(wf, ring + cw.slot * SLOT_BYTES + w * 16384, c);
            release(c, BAR_EMPTY + 8 * cw.slot + z, 1);
            cw.adv(); cw.adv();
        };
#pragma unroll
        for (int i = 32; i < 64; i++) wf[i] = 0u;
        load_wchunk(IC<0>{});
#pragma unroll 1
        for (int v = 0; v < 2; v++) {
        {
            float (&acc)[64] = o;
#pragma unroll
            for (int i = 64; i < 128; i++) wf[i] = 0u;
            cur.adv();
            inv[0] = inv[1] = rank ? 1.0f : SM_SCALE;
#pragma unroll 1
            for (int t = 0; t < 4; t++) {
                uint32_t last = 0;
                token_wait(w);
                undef_regs(acc);
                auto chunk = [&](auto CH) {
                    constexpr int ch = decltype(CH)::value;
                    mbar_wait_hot(misc + BAR_FULL + 8 * cur.slot, cur.ph);
                    uint64_t d = mkdesc(ring + cur.slot * SLOT_BYTES, 16, 1024, 1);
                    wg_fence();
#pragma unroll
                    for (int ks = 0; ks < 8; ks++)
                        wgmma_rs_n128_ta0_tb0(acc, wf[32 * ch + 4 * ks], wf[32 * ch + 4 * ks + 1], wf[32 * ch + 4 * ks + 2], wf[32 * ch + 4 * ks + 3],
                                              d + (ks >> 2) * 1024 + (ks & 3) * 2, (ch | ks) != 0);
                    wg_commit();
                    if (ch == 3 || (ch < 2 && t == 0)) token_pass(w);
                    if constexpr (ch == 0) {
                        if (t == 0) {
                            if (v) {
                                release(c, BAR_EMPTY + 8 * slot_of(76), 1);
                                asm volatile("fence.proxy.async.shared::cta;" ::: "memory");
                                signal_event(c, EV_CTX + 1);
                                load_wchunk(IC<2>{});
                            } else load_wchunk(IC<1>{});
                        }
                    }
                    if constexpr (ch == 1) { if (t == 0 && !v) load_wchunk(IC<2>{}); }
                    if constexpr (ch == 2) { if (t == 0 && !(w | v)) load_wchunk(IC<3>{}); }
                    if (ch > 0) { wg_wait<1>(); release(c, BAR_EMPTY + 8 * last, 1); }
                    last = cur.slot;
                    cur.adv();
                    if (ch < 3 && t == 0) cur.adv();
                    if constexpr (ch == 1) { if (t == 0 && (w | v)) load_wchunk(IC<3>{}); }
                    if (ch < 2 && t == 0) token_wait(w);
                };
                chunk(IC<0>{}); chunk(IC<1>{}); chunk(IC<2>{}); chunk(IC<3>{});
                wg_wait<0>();
                release(c, BAR_EMPTY + 8 * last, 1);
                fence_regs(acc);
                tile_out(out, (rank ? g_V : g_K) + (size_t)(team * 32 + 2 * (kv_tile(t) + k)) * 16384, 64 * w, rank, c);
                if (t == 3 && w) break;
#pragma unroll
                for (int i = 0; i < 4; i++) store_pair(acc, i, out, 8192, inv);
                if (t >= 2) signal_event(c, EV_KV + 2 * v + t - 2);
            }
        }
        {
            uint32_t q[32], p[32];
            float m[2], l[2];
#pragma unroll
            for (int i = 0; i < 32; i++) p[i] = 0u;
            l[0] = l[1] = 1.f;
            int pv_acc = 1, pv_mode = 2;
#pragma unroll 1
            for (int r = 0; r < 2; r++) {
                const int heavy = 1 ^ r ^ w;
                const int half = 1 ^ heavy ^ rank ^ r;
                int left = 2 * (r ? b1 : b0) + 1 + heavy;
                Cur ck, cv = cur;
                {
                    float s[64];
                    if (r) cur.adv();
                    mbar_wait_hot(misc + BAR_FULL + 8 * cv.slot, cv.ph);
                    token_wait(w);
                    issue_pv(o, p, ring + cv.slot * SLOT_BYTES, pv_acc, pv_mode);
                    undef_regs(s);
                    uint32_t prev;
                    auto qchunk = [&](int acc) {
                        mbar_wait_hot(misc + BAR_FULL + 8 * cur.slot, cur.ph);
                        const uint64_t da = mkdesc(ring + cur.slot * SLOT_BYTES + w * 8192, 16, 1024, 1);
                        const uint64_t db = mkdesc(ring + cur.slot * SLOT_BYTES + 16384, 8192, 1024, 1);
                        wg_fence();
#pragma unroll
                        for (int ks = 0; ks < 4; ks++) wgmma_ss_n128_ta0_tb1(s, da + 2 * ks, db + 128 * ks, ks ? 1 : acc);
                        wg_commit();
                    };
                    qchunk(0);
                    prev = cur.slot; cur.adv();
                    token_pass(w);
                    if (r) {
                        row_inv(l, inv);
                        tile_out(out, g_ctx + (size_t)((team + 16 * v) * 32 + 4 * b0 + (w ? rank : 3 - rank)) * 16384, 0, 0, c);
                    }
                    const int epi = r | w, hs = r ? 4096 : 8192;
                    const int hold = heavy ? -10 : half ? 6 : 8;
#pragma unroll
                    for (int kc = 1; kc < 10; kc++) {
                        if (kc >= 6 && (kc == hold || kc == hold + 2)) token_wait(w);
                        qchunk(1);
                        if (kc > 6 && kc == hold + 1) token_pass(w);
                        if (kc == 9 && heavy) { token_wait(w); token_pass(w); }
                        wg_wait<1>();
                        release(c, BAR_EMPTY + 8 * prev, 1);
                        prev = cur.slot; cur.adv();
                        if (kc == 1) { fence_regs(o); if (r) release(c, BAR_EMPTY + 8 * cv.slot, 1); }
                        if (kc <= 4 && epi) {
                            store_pair(o, kc - 1, out, hs, inv);
                            if (kc == 4) signal_event(c, r ? EV_CTX + 2 * v : EV_KV + 2 * v + 1);
                        }
                    }
                    if (!heavy) cur.adv();
                    ck = cur;
                    cur.adv();
                    if (!heavy) cur.adv();
                    wg_wait<0>();
                    release(c, BAR_EMPTY + 8 * prev, 1);
                    fence_regs(s);
#pragma unroll
                    for (int i = 0; i < 32; i++) q[i] = pack_bf16(s[2 * i], s[2 * i + 1]);
                }
                int first = 1, gen = 0;
                uint32_t pv_cnt = 0;
                l[0] = l[1] = m[0] = m[1] = 0.f;
                mbar_wait_hot(misc + BAR_FULL + 8 * ck.slot, ck.ph);
                auto diagonal = [&](auto NJC) {
                    constexpr int NJ = decltype(NJC)::value;
                    if (NJ == 16 || heavy) token_wait(w);
                    float sd[4 * NJ];
                    undef_regs(sd);
                    if constexpr (NJ == 8) issue_qk_half(sd, q, ring + ck.slot * SLOT_BYTES); else issue_qk(sd, q, ring + ck.slot * SLOT_BYTES);
                    token_pass(w);
                    wg_wait<0>();
                    fence_regs(sd);
                    mask_diag<NJ - 8>(sd, c);
                    float l0 = 0.f, l1 = 0.f;
#pragma unroll
                    for (int j = 0; j < NJ; j++) {
#pragma unroll
                        for (int e = 0; e < 4; e++) ex2v(sd[4 * j + e]);
                        l0 += sd[4 * j] + sd[4 * j + 1]; l1 += sd[4 * j + 2] + sd[4 * j + 3];
                    }
#pragma unroll
                    for (int i = 0; i < 2 * NJ; i++) p[i] = pack_bf16(sd[2 * i], sd[2 * i + 1]);
                    const int lim = NJ == 8 ? mask_lim(c) : 0;
                    const bool bad = __any_sync(0xffffffffu, !(l0 <= SAFE_SUM && l1 <= SAFE_SUM && (l0 >= 1.0f / SAFE_SUM || lim < 0) &&
                                                               (l1 >= 1.0f / SAFE_SUM || lim < -2)));
                    if (!bad) { l[0] = l0; l[1] = l1; }
                    return bad;
                };
#pragma unroll 1
                while (true) {
                    float s[64];
                    if (first) {
                        --left;
                        if (half ? diagonal(IC<8>{}) : diagonal(IC<16>{})) goto redo;
                        if (left == 0) goto tail;
                        release(c, BAR_EMPTY + 8 * ck.slot, 1 + heavy);
                        pv_acc = 0; pv_mode = half; pv_cnt = 1 + heavy; first = 0;
                        ck = cur; cur.adv(); cv = cur; cur.adv();
                        mbar_wait_hot(misc + BAR_FULL + 8 * ck.slot, ck.ph);
                    }
#pragma unroll 1
                    while (true) {
                        token_wait(w);
                        undef_regs(s);
                        issue_qk(s, q, ring + ck.slot * SLOT_BYTES);
                        Cur nck = cur, ncv = cur, ncur;
                        ncv.adv(); ncur = ncv; ncur.adv();
                        --left;
                        mbar_wait_hot(misc + BAR_FULL + 8 * cv.slot, cv.ph);
                        issue_pv(o, p, ring + cv.slot * SLOT_BYTES, pv_acc, pv_mode & 1);
                        token_pass(w);
                        wg_wait<1>();
                        fence_regs(s);
                        constexpr int JB = 11;
                        float l0 = l[0], l1 = l[1];
                        if (!gen) {
#pragma unroll
                            for (int j = 0; j < JB; j++) {
#pragma unroll
                                for (int e = 0; e < 4; e++) ex2v(s[4 * j + e]);
                                if (j < JB - 1) { l0 += s[4 * j] + s[4 * j + 1]; l1 += s[4 * j + 2] + s[4 * j + 3]; }
                            }
                        }
                        wg_wait<0>();
                        fence_regs(o);
                        if (gen) goto general;
#pragma unroll
                        for (int j = JB - 1; j < 16; j++) {
                            if (j >= JB) {
#pragma unroll
                                for (int e = 0; e < 4; e++) ex2v(s[4 * j + e]);
                            }
                            l0 += s[4 * j] + s[4 * j + 1]; l1 += s[4 * j + 2] + s[4 * j + 3];
                        }
#pragma unroll
                        for (int i = 0; i < 32; i++) p[i] = pack_bf16(s[2 * i], s[2 * i + 1]);
                        if (__any_sync(0xffffffffu, !(l0 <= SAFE_SUM && l1 <= SAFE_SUM))) goto redo;
                        l[0] = l0; l[1] = l1;
                        if (left == 0) goto tail;
                        release(c, BAR_EMPTY + 8 * ck.slot, 1);
                        release(c, BAR_EMPTY + 8 * cv.slot, pv_cnt);
                        pv_acc = 1; pv_mode = 0; pv_cnt = 1;
                        ck = nck; cv = ncv; cur = ncur;
                        mbar_wait_hot(misc + BAR_FULL + 8 * ck.slot, ck.ph);
                    }
                redo:
                    recompute_scores(s, q, ring + ck.slot * SLOT_BYTES, c);
                    if (first) { mask_any(s, half ^ 1, c); m[0] = m[1] = -INFINITY; }
                    gen = 1;
                general:
                    {
                        float mx[2], alpha[2];
                        row_max<16>(s, mx);
#pragma unroll
                        for (int i = 0; i < 2; i++) {
                            mx[i] = fmaxf(mx[i], m[i]);
                            alpha[i] = ex2(m[i] - mx[i]);
                            m[i] = mx[i];
                            l[i] *= alpha[i];
                        }
                        exp_sum<16, true>(s, m, l[0], l[1]);
#pragma unroll
                        for (int i = 0; i < 64; i++) o[i] *= alpha[(i >> 1) & 1];
#pragma unroll
                        for (int i = 0; i < 32; i++) p[i] = pack_bf16(s[2 * i], s[2 * i + 1]);
                    }
                tail:
                    release(c, BAR_EMPTY + 8 * ck.slot, 1 + (first & heavy));
                    if (pv_cnt) release(c, BAR_EMPTY + 8 * cv.slot, pv_cnt);
                    pv_acc = first ^ 1; pv_mode = first & half; pv_cnt = 1 + (first & heavy); first = 0;
                    if (left == 0) break;
                    ck = cur; cur.adv(); cv = cur; cur.adv();
                    mbar_wait_hot(misc + BAR_FULL + 8 * ck.slot, ck.ph);
                }
            }
            mbar_wait_hot(misc + BAR_FULL + 8 * cur.slot, cur.ph);
            token_wait(w);
            issue_pv(o, p, ring + cur.slot * SLOT_BYTES, 1, 0);
            if (w == 0 || v == 0) token_pass(w);
            const uint32_t vslot = cur.slot;
            cur.adv();
            row_inv(l, inv);
            if (v) {
                wg_wait<0>();
                release(c, BAR_EMPTY + 8 * vslot, 1);
                fence_regs(o);
                tile_out(out, g_ctx + (size_t)((team + 16) * 32 + 4 * b1 + (w ? 3 - (rank ^ 1) : rank ^ 1)) * 16384, 0, 0, c);
#pragma unroll
                for (int i = 0; i < 64; i++) wf[i] = 0u;
                continue;
            }
            cw = cur_at(80);
            mbar_wait_hot(misc + BAR_FULL + 8 * slot_of(76), cur_at(76).ph);
            mbar_wait_hot(misc + BAR_FULL + 8 * slot_of(78), cur_at(78).ph);
            load_afrag<8, 32>(wf, ring + slot_of(78) * SLOT_BYTES + w * 16384, c);
            load_afrag<8, 0>(wf, ring + slot_of(76) * SLOT_BYTES + w * 16384, c);
            asm volatile("{\n.reg .pred p;\nsetp.eq.u32 p, %0, 0;\n@p bar.sync 4, 128;\n@!p bar.sync 5, 128;\n}\n" ::"r"(w) : "memory");
            wg_wait<0>();
            release(c, BAR_EMPTY + 8 * vslot, 1);
            fence_regs(o);
            {
                const uint32_t base = ring + slot_of(78) * SLOT_BYTES + w * 16384 + (16 * c.warp + (c.lane >> 2)) * 64 + (((c.lane ^ (c.lane >> 3)) & 3) << 4);
#pragma unroll
                for (int i = 0; i < 2; i++)
#pragma unroll
                    for (int qq = 0; qq < 4; qq++)
                        asm volatile("st.shared.v4.b32 [%0], {%1,%2,%3,%4};" ::"r"(base + qq * 4096 + i * 512),
                                     "r"(pack_bf16(o[16 * qq + 2 * i] * inv[i], o[16 * qq + 2 * i + 1] * inv[i])),
                                     "r"(pack_bf16(o[16 * qq + 4 + 2 * i] * inv[i], o[16 * qq + 4 + 2 * i + 1] * inv[i])),
                                     "r"(pack_bf16(o[16 * qq + 8 + 2 * i] * inv[i], o[16 * qq + 8 + 2 * i + 1] * inv[i])),
                                     "r"(pack_bf16(o[16 * qq + 12 + 2 * i] * inv[i], o[16 * qq + 12 + 2 * i + 1] * inv[i])) : "memory");
            }
        }
        }
        {
            float acc[80];
            undef_regs(acc);
            int st = 0, prev = 0; uint32_t ph3 = 0;
            auto op_stage = [&](int i) {
                mbar_wait_hot(misc + BAR_FULL3 + 8 * st, ph3);
                uint32_t base = ring + st * ST3_BYTES;
                uint64_t da = mkdesc(base + w * 8192, 16, 512, 2);
                uint64_t db = mkdesc(base + 16384, 2048, 512, 2);
                wg_fence();
#pragma unroll
                for (int k = 0; k < 4; k++) wgmma_ss_n160_ta0_tb1(acc, da + (k >> 1) * 256 + 2 * (k & 1), db + (k >> 1) * 640 + (k & 1) * 64, k ? 1 : i);
                wg_commit();
                if (i > 0) { wg_wait<1>(); if (i <= 32 - NST3) release(c, BAR_EMPTY3 + 8 * prev, 1); }
                prev = st;
                if (++st == NST3) { st = 0; ph3 ^= 1; }
            };
#pragma unroll
            for (int i = 0; i < 4; i++) { op_stage(i); store_pair(o, i, out, 4096, inv); }
            signal_event(c, EV_CTX + 3);
            const int split = w ? 32 - OP_HOLD : RES_AT;
#pragma unroll 1
            for (int i = 4; i < split; i++) op_stage(i);
            mbar_wait(misc + BAR_SEL, 0);
            const uint32_t tag = lds32(misc + MISC_EPOCH) & 1;
            const int g = c.lane >> 2, t = c.lane & 3;
            const int row = (2 * u3 + rank) * 128 + 64 * w + perm32(16 * c.warp + 8 * kap + g);
            const int col = 160 * s3 + 8 * t;
            int sel = -1;
#pragma unroll
            for (int i = 0; i < TOPC; i++) if ((int)lds32(misc + MISC_SEL + 4 * i) == row) sel = i;
            const int t256 = tid - 128;
            uint4* sendp = g_part + (size_t)cta * 2560 + t256;
            if (c.lane >= 30) stg128(sendp + 9 * 256, tag ^ 1, tag ^ 1, tag ^ 1, tag ^ 1);
            uint4 xv[5], bv[5];
#pragma unroll
            for (int i = 0; i < 5; i++) xv[i] = ldg128(P.x + (size_t)row * DM + col + 32 * i);
            uint2 stat;
            asm volatile("ld.global.cg.v2.b32 {%0,%1}, [%2];" : "=r"(stat.x), "=r"(stat.y) : "l"(g_stats + row) : "memory");
#pragma unroll
            for (int i = 0; i < 5; i++) {
                uint32_t xx[4] = {xv[i].x, xv[i].y, xv[i].z, xv[i].w};
#pragma unroll
                for (int e = 0; e < 4; e++) {
                    asm("sub.rn.bf16x2 %0, %0, %1;" : "+r"(xx[e]) : "r"(stat.x));
                    xx[e] = pack_bf16(bf_lo(xx[e]) * __uint_as_float(stat.y), bf_hi(xx[e]) * __uint_as_float(stat.y));
                }
                bv[i] = make_uint4(xx[0], xx[1], xx[2], xx[3]);
            }
            if (sel >= 0) {
#pragma unroll
                for (int i = 0; i < 5; i++) bv[i] = ldg128(g_brow + sel * DM + col + 32 * i);
            }
#pragma unroll
            for (int i = 0; i < 5; i++) asm volatile("" : "+r"(bv[i].x), "+r"(bv[i].y), "+r"(bv[i].z), "+r"(bv[i].w));
            if (w) bar_sync(4, 256);
#pragma unroll 1
            for (int i = split; i < 32; i++) op_stage(i);
            if (!w) bar_arrive(4, 256);
            wg_wait<0>();
            fence_regs(acc);
            float keep[40];
#pragma unroll
            for (int j = 0; j < 10; j++) {
                uint32_t v0 = __float_as_uint(kap ? acc[8 * j + 0] : acc[8 * j + 2]), v1 = __float_as_uint(kap ? acc[8 * j + 1] : acc[8 * j + 3]);
                uint32_t v2 = __float_as_uint(kap ? acc[8 * j + 4] : acc[8 * j + 6]), v3 = __float_as_uint(kap ? acc[8 * j + 5] : acc[8 * j + 7]);
                asm volatile("st.relaxed.gpu.global.v4.b32 [%0], {%1,%2,%3,%4};" ::"l"(sendp + j * 256),
                             "r"((v0 & ~1u) | tag), "r"((v1 & ~1u) | tag), "r"((v2 & ~1u) | tag), "r"((v3 & ~1u) | tag) : "memory");
                keep[4 * j + 0] = kap ? acc[8 * j + 2] : acc[8 * j + 0]; keep[4 * j + 1] = kap ? acc[8 * j + 3] : acc[8 * j + 1];
                keep[4 * j + 2] = kap ? acc[8 * j + 6] : acc[8 * j + 4]; keep[4 * j + 3] = kap ? acc[8 * j + 7] : acc[8 * j + 5];
            }
            signal_event(c, EV_END);
            const uint4* recvp = g_part + (size_t)partner * 2560 + t256;
            uint4 rv[10];
            int spins = 0;
            while (true) {
                uint32_t v;
                asm volatile("ld.relaxed.gpu.global.b32 %0, [%1];" : "=r"(v) : "l"(recvp + 9 * 256 + (31 - c.lane)) : "memory");
                if (__all_sync(0xffffffffu, (v & 1u) == tag) || ++spins > 2000000) break;
            }
            while (true) {
                uint32_t bad = 0u;
#pragma unroll
                for (int j = 0; j < 10; j++) {
                    asm volatile("ld.relaxed.gpu.global.v4.b32 {%0,%1,%2,%3}, [%4];"
                                 : "=r"(rv[j].x), "=r"(rv[j].y), "=r"(rv[j].z), "=r"(rv[j].w) : "l"(recvp + j * 256) : "memory");
                }
#pragma unroll
                for (int j = 0; j < 10; j++) {
                    rv[j].x ^= tag; rv[j].y ^= tag; rv[j].z ^= tag; rv[j].w ^= tag;
                    bad |= rv[j].x | rv[j].y | rv[j].z | rv[j].w;
                }
                if (__all_sync(0xffffffffu, (bad & 1u) == 0) || ++spins > 2000000) break;
            }
            uint32_t pk[20];
#pragma unroll
            for (int j = 0; j < 10; j++) {
                pk[2 * j] = pack_bf16(keep[4 * j] + __uint_as_float(rv[j].x), keep[4 * j + 1] + __uint_as_float(rv[j].y));
                pk[2 * j + 1] = pack_bf16(keep[4 * j + 2] + __uint_as_float(rv[j].z), keep[4 * j + 3] + __uint_as_float(rv[j].w));
            }
#pragma unroll
            for (int i = 0; i < 5; i++) {
                uint32_t a0 = pk[4 * i], a1 = pk[4 * i + 1], a2 = pk[4 * i + 2], a3 = pk[4 * i + 3];
                uint32_t x0 = (t & 1) ? a0 : a1, x1 = (t & 1) ? a2 : a3;
                x0 = __shfl_xor_sync(0xffffffffu, x0, 1); x1 = __shfl_xor_sync(0xffffffffu, x1, 1);
                if (t & 1) { a0 = x0; a2 = x1; } else { a1 = x0; a3 = x1; }
                x0 = (t & 2) ? a0 : a2; x1 = (t & 2) ? a1 : a3;
                x0 = __shfl_xor_sync(0xffffffffu, x0, 2); x1 = __shfl_xor_sync(0xffffffffu, x1, 2);
                if (t & 2) { a0 = x0; a1 = x1; } else { a2 = x0; a3 = x1; }
                uint32_t av[4] = {a0, a1, a2, a3};
                uint32_t xx[4] = {xv[i].x, xv[i].y, xv[i].z, xv[i].w}, bb[4] = {bv[i].x, bv[i].y, bv[i].z, bv[i].w};
                uint32_t ov[4];
#pragma unroll
                for (int e = 0; e < 4; e++) {
                    asm("add.rn.bf16x2 %0, %1, %2;" : "=r"(ov[e]) : "r"(xx[e]), "r"(av[e]));
                    asm("add.rn.bf16x2 %0, %0, %1;" : "+r"(ov[e]) : "r"(bb[e]));
                }
                stg128(P.out + (size_t)row * DM + col + 32 * i, ov[0], ov[1], ov[2], ov[3]);
            }
        }
    }
}

typedef CUresult (*EncodeFn)(CUtensorMap*, CUtensorMapDataType, cuuint32_t, void*, const cuuint64_t*, const cuuint64_t*, const cuuint32_t*,
                             const cuuint32_t*, CUtensorMapInterleave, CUtensorMapSwizzle, CUtensorMapL2promotion, CUtensorMapFloatOOBfill);

void make_map2d(EncodeFn enc, CUtensorMap* tm, const void* p, uint64_t cols, uint64_t rows, uint32_t box_rows = 128) {
    cuuint64_t gd[2] = {cols, rows}, gs[1] = {cols * 2};
    cuuint32_t box[2] = {64, box_rows}, es[2] = {1, 1};
    enc(tm, CU_TENSOR_MAP_DATA_TYPE_BFLOAT16, 2, const_cast<void*>(p), gd, gs, box, es, CU_TENSOR_MAP_INTERLEAVE_NONE,
        CU_TENSOR_MAP_SWIZZLE_128B, CU_TENSOR_MAP_L2_PROMOTION_L2_128B, CU_TENSOR_MAP_FLOAT_OOB_FILL_NONE);
}

void make_map3d(EncodeFn enc, CUtensorMap* tm, const void* p, uint64_t cols, uint64_t rows, uint32_t bw, uint32_t nb) {
    cuuint64_t gd[3] = {bw, rows, cols / bw}, gs[2] = {cols * 2, bw * 2};
    cuuint32_t box[3] = {bw, 32, nb}, es[3] = {1, 1, 1};
    enc(tm, CU_TENSOR_MAP_DATA_TYPE_BFLOAT16, 3, const_cast<void*>(p), gd, gs, box, es, CU_TENSOR_MAP_INTERLEAVE_NONE,
        bw == 64 ? CU_TENSOR_MAP_SWIZZLE_128B : CU_TENSOR_MAP_SWIZZLE_64B, CU_TENSOR_MAP_L2_PROMOTION_L2_128B, CU_TENSOR_MAP_FLOAT_OOB_FILL_NONE);
}

}

extern "C" void kernel_launch(void* const* d_in, const int* in_sizes, int n_in, void* d_out, int out_size) {
    (void)in_sizes; (void)n_in; (void)out_size;
    static EncodeFn enc = nullptr;
    if (!enc) {
        void* fn = nullptr;
        cudaDriverEntryPointQueryResult qr;
        cudaGetDriverEntryPoint("cuTensorMapEncodeTiled", &fn, cudaEnableDefault, &qr);
        enc = (EncodeFn)fn;
        cudaFuncSetAttribute(fused_kernel, cudaFuncAttributeMaxDynamicSharedMemorySize, SMEM_BYTES);
    }
    CUtensorMap tmC, tmWk, tmWv, tmWq, tmWo, tmG, tmU, tmD;
    make_map2d(enc, &tmC, d_in[1], DC, SEQ);
    make_map2d(enc, &tmWq, d_in[2], 4096, DM, 64);
    make_map2d(enc, &tmWk, d_in[3], 4096, DC);
    make_map2d(enc, &tmWv, d_in[4], 4096, DC);
    make_map3d(enc, &tmWo, d_in[5], DM, 4096, 32, 5);
    make_map3d(enc, &tmG, d_in[8], FF, DM, 64, 7);
    make_map3d(enc, &tmU, d_in[9], FF, DM, 64, 7);
    make_map3d(enc, &tmD, d_in[10], DM, FF, 64, 10);
    Params P;
    P.x = (const __nv_bfloat16*)d_in[0];
    P.c = (const __nv_bfloat16*)d_in[1];
    P.wk = (const __nv_bfloat16*)d_in[3];
    P.wv = (const __nv_bfloat16*)d_in[4];
    P.wo = (const __nv_bfloat16*)d_in[5];
    P.wr = (const __nv_bfloat16*)d_in[7];
    P.out = (__nv_bfloat16*)d_out;
    fused_kernel<<<132, 384, SMEM_BYTES>>>(tmC, tmWk, tmWv, tmWq, tmWo, tmG, tmU, tmD, P);
}
```

```cpp
#include <cuda_runtime.h>
#include <cuda_bf16.h>
#include <cuda.h>
#include <stdint.h>

#define MOE_GATE FL_CTX + (18 + a) * 8
#define MOE_CNT 4u
namespace {

constexpr int SEQ = 2048, NH = 32, DM = 640, DC = 512, FF = 1728, TOPC = 8;
constexpr int NSLOT = 7, SLOT_BYTES = 32768;
constexpr int NST3 = 6, ST3_BYTES = 36864;
constexpr int RING_BYTES = NSLOT * SLOT_BYTES;
constexpr int SMEM_BYTES = RING_BYTES + 3072;
constexpr int OP_PF = 8, PF_START = 9, LATE_AT = 18, RES_AT = 23, OP_HOLD = 4;

constexpr int BAR_FULL = 0  , BAR_EMPTY = 64  , BAR_FULL3 = 128  , BAR_EMPTY3 = 192  , BAR_DEP = 256  ,
              BAR_EV = 448  , BAR_PROG = 592  , BAR_SEL = 616, BAR_LN = 624,
              MISC_EPOCH = 640, MISC_SMID = 644  , MISC_SEL = 656, MISC_WR = 1024  ;
constexpr int D_LN = 0  , D_KV = 2  , D_WAR = 6  , D_CTX = 8  ;
constexpr int EV_KV = 0  , EV_CTX = 4  , EV_END = 8, NEV = 9;

constexpr int FL_MOE_CNT = 0, FL_MOE_DONE = 1, FL_LN = 16  , FL_KV = 32  , FL_CTX = 160  , FL_WAR = 416  , FL_TOTAL = 448;

__device__ __align__(1024) unsigned char g_K[16 * 32 * 16384];
__device__ __align__(1024) unsigned char g_V[16 * 32 * 16384];
__device__ __align__(1024) unsigned char g_ctx[NH * 32 * 16384];
__device__ __align__(1024) unsigned char g_xn[16 * 10 * 16384];
__device__ __align__(1024) uint4 g_part[128 * 10 * 256];
__device__ float g_router[SEQ];
__device__ uint2 g_stats[SEQ];
__device__ __align__(16) float g_moe_part[4 * TOPC * DM];
__device__ __align__(16) __nv_bfloat16 g_brow[TOPC * DM];
__device__ __align__(16) int g_sel[TOPC];
__device__ unsigned g_flags[FL_TOTAL * 8];
__device__ unsigned g_epoch;
__device__ unsigned g_roleq[130];
struct Params {
    const __nv_bfloat16 *x, *c, *wr, *wk, *wv, *wo;
    __nv_bfloat16* out;
};

__device__ __forceinline__ uint32_t smem_u32(const void* p) { return (uint32_t)__cvta_generic_to_shared(p); }
__device__ __forceinline__ void mbar_init(uint32_t bar, int cnt) { asm volatile("mbarrier.init.shared::cta.b64 [%0], %1;" ::"r"(bar), "r"(cnt)); }
__device__ __forceinline__ void mbar_expect_tx(uint32_t bar, uint32_t bytes) {
    asm volatile("mbarrier.arrive.expect_tx.shared::cta.b64 _, [%0], %1;" ::"r"(bar), "r"(bytes) : "memory");
}
__device__ __forceinline__ void mbar_arrive(uint32_t bar) { asm volatile("mbarrier.arrive.shared::cta.b64 _, [%0];" ::"r"(bar) : "memory"); }
__device__ __forceinline__ void mbar_arrive_cluster(uint32_t cluster_addr, uint32_t cnt) {
    asm volatile("mbarrier.arrive.shared::cluster.b64 _, [%0], %1;" ::"r"(cluster_addr), "r"(cnt) : "memory");
}
__device__ __forceinline__ uint32_t mapa(uint32_t addr, uint32_t cta) {
    uint32_t r; asm("mapa.shared::cluster.u32 %0, %1, %2;" : "=r"(r) : "r"(addr), "r"(cta)); return r;
}
__device__ __forceinline__ void mbar_wait(uint32_t bar, uint32_t parity) {
    asm volatile(
        "{\n.reg .pred p;\n.reg .u32 n;\n"
        "mov.u32 n, 0;\n"
        "LAB_WAIT:\n"
        "mbarrier.try_wait.parity.shared::cta.b64 p, [%0], %1, 100000;\n"
        "@p bra DONE;\n"
        "add.u32 n, n, 1;\n"
        "setp.lt.u32 p, n, 50000;\n"
        "@p bra LAB_WAIT;\n"
        "trap;\n"
        "DONE:\n}\n" ::"r"(bar), "r"(parity) : "memory");
}
__device__ __forceinline__ void mbar_wait_hot(uint32_t bar, uint32_t parity) {
    asm volatile("{\n.reg .pred p;\nLAB_WAIT:\nmbarrier.try_wait.parity.shared::cta.b64 p, [%0], %1;\n@!p bra LAB_WAIT;\n}\n" ::"r"(bar), "r"(parity) : "memory");
}
__device__ __forceinline__ void mbar_wait_sleep(uint32_t bar, uint32_t parity) {
    asm volatile("{\n.reg .pred p;\nLAB_WAIT:\nmbarrier.try_wait.parity.shared::cta.b64 p, [%0], %1, 100000;\n@!p bra LAB_WAIT;\n}\n" ::"r"(bar), "r"(parity) : "memory");
}
__device__ __forceinline__ void flag_wait(const unsigned* flag, unsigned target) {
    asm volatile(
        "{\n.reg .pred p;\n.reg .u32 n, v;\n.reg .s32 d;\n"
        "mov.u32 n, 0;\n"
        "LAB_WAIT:\n"
        "ld.acquire.gpu.global.u32 v, [%0];\n"
        "sub.s32 d, v, %1;\n"
        "setp.ge.s32 p, d, 0;\n"
        "@p bra DONE;\n"
        "nanosleep.u32 40;\n"
        "add.u32 n, n, 1;\n"
        "setp.lt.u32 p, n, 3000000;\n"
        "@p bra LAB_WAIT;\n"
        "trap;\n"
        "DONE:\n}\n" ::"l"(flag), "r"(target) : "memory");
}
__device__ __forceinline__ void flag_signal(unsigned* flag) {
    asm volatile("red.release.gpu.global.add.u32 [%0], 1;" ::"l"(flag) : "memory");
}
__device__ __forceinline__ void fence_async_global() { asm volatile("fence.proxy.async.global;" ::: "memory"); }
__device__ __forceinline__ unsigned* flag_ptr(int idx) { return g_flags + idx * 8; }

__device__ __forceinline__ uint64_t policy_stream() {
    uint64_t p; asm("createpolicy.fractional.L2::evict_first.b64 %0, 1.0;" : "=l"(p)); return p;
}
__device__ __forceinline__ void bulk_load(uint32_t dst, const void* src, uint32_t bytes, uint32_t bar) {
    asm volatile("cp.async.bulk.shared::cluster.global.mbarrier::complete_tx::bytes [%0], [%1], %2, [%3];"
                 ::"r"(dst), "l"(src), "r"(bytes), "r"(bar) : "memory");
}
__device__ __forceinline__ void bulk_load_mc(uint32_t dst, const void* src, uint32_t bytes, uint32_t bar) {
    asm volatile("cp.async.bulk.shared::cluster.global.mbarrier::complete_tx::bytes.multicast::cluster [%0], [%1], %2, [%3], %4;"
                 ::"r"(dst), "l"(src), "r"(bytes), "r"(bar), "h"((uint16_t)3) : "memory");
}
__device__ __forceinline__ void tma2d(uint32_t dst, const CUtensorMap* tm, int c0, int c1, uint32_t bar) {
    asm volatile("cp.async.bulk.tensor.2d.shared::cluster.global.mbarrier::complete_tx::bytes [%0], [%1, {%3, %4}], [%2];"
                 ::"r"(dst), "l"(tm), "r"(bar), "r"(c0), "r"(c1) : "memory");
}
__device__ __forceinline__ void tma2d_mc(uint32_t dst, const CUtensorMap* tm, int c0, int c1, uint32_t bar) {
    asm volatile("cp.async.bulk.tensor.2d.shared::cluster.global.mbarrier::complete_tx::bytes.multicast::cluster [%0], [%1, {%3, %4}], [%2], %5;"
                 ::"r"(dst), "l"(tm), "r"(bar), "r"(c0), "r"(c1), "h"((uint16_t)3) : "memory");
}
__device__ __forceinline__ void tma3d_mc(uint32_t dst, const CUtensorMap* tm, int c0, int c1, int c2, uint32_t bar) {
    asm volatile("cp.async.bulk.tensor.3d.shared::cluster.global.mbarrier::complete_tx::bytes.multicast::cluster [%0], [%1, {%3, %4, %5}], [%2], %6;"
                 ::"r"(dst), "l"(tm), "r"(bar), "r"(c0), "r"(c1), "r"(c2), "h"((uint16_t)3) : "memory");
}
__device__ __forceinline__ void tma3d(uint32_t dst, const CUtensorMap* tm, int c0, int c1, int c2, uint32_t bar) {
    asm volatile("cp.async.bulk.tensor.3d.shared::cluster.global.mbarrier::complete_tx::bytes.L2::cache_hint [%0], [%1, {%3, %4, %5}], [%2], %6;"
                 ::"r"(dst), "l"(tm), "r"(bar), "r"(c0), "r"(c1), "r"(c2), "l"(policy_stream()) : "memory");
}
__device__ __forceinline__ void tma2d_prefetch(const CUtensorMap* tm, int c0, int c1) {
    asm volatile("cp.async.bulk.prefetch.tensor.2d.L2.global [%0, {%1, %2}];" ::"l"(tm), "r"(c0), "r"(c1) : "memory");
}
__device__ __forceinline__ void tma3d_prefetch(const CUtensorMap* tm, int c0, int c1, int c2) {
    asm volatile("cp.async.bulk.prefetch.tensor.3d.L2.global [%0, {%1, %2, %3}];" ::"l"(tm), "r"(c0), "r"(c1), "r"(c2) : "memory");
}
__device__ __forceinline__ void l2_prefetch(const void* p, uint32_t bytes) {
    asm volatile("cp.async.bulk.prefetch.L2.global [%0], %1;" ::"l"(p), "r"(bytes) : "memory");
}
__device__ __forceinline__ bool elect_one() {
    uint32_t r; asm volatile("{\n.reg .pred p;\nelect.sync _|p, 0xffffffff;\nselp.u32 %0, 1, 0, p;\n}\n" : "=r"(r)); return r != 0;
}
__device__ __forceinline__ void wg_fence() { asm volatile("wgmma.fence.sync.aligned;" ::: "memory"); }
__device__ __forceinline__ void wg_commit() { asm volatile("wgmma.commit_group.sync.aligned;" ::: "memory"); }
template <int N> __device__ __forceinline__ void wg_wait() { asm volatile("wgmma.wait_group.sync.aligned %0;" ::"n"(N) : "memory"); }
__device__ __forceinline__ void bar_sync(int id, int n) { asm volatile("bar.sync %0, %1;" ::"r"(id), "r"(n) : "memory"); }
__device__ __forceinline__ void bar_arrive(int id, int n) { asm volatile("bar.arrive %0, %1;" ::"r"(id), "r"(n) : "memory"); }
__device__ __forceinline__ void token_wait(int w) {
    asm volatile("{\n.reg .pred p;\nsetp.eq.u32 p, %0, 0;\n@p bar.sync 1, 256;\n@!p bar.sync 2, 256;\n}\n" ::"r"(w) : "memory");
}
__device__ __forceinline__ void token_pass(int w) {
    asm volatile("{\n.reg .pred p;\nsetp.eq.u32 p, %0, 0;\n@p bar.arrive 2, 256;\n@!p bar.arrive 1, 256;\n}\n" ::"r"(w) : "memory");
}
template <int N> __device__ __forceinline__ void fence_regs(float (&a)[N]) {
#pragma unroll
    for (int i = 0; i < N; i++) asm volatile("" : "+f"(a[i])::"memory");
}
template <int N> __device__ __forceinline__ void undef_regs(float (&a)[N]) {
#pragma unroll
    for (int i = 0; i < N; i++) asm volatile("" : "=f"(a[i]));
}
__device__ __forceinline__ void ldsm4t(uint32_t& r0, uint32_t& r1, uint32_t& r2, uint32_t& r3, uint32_t addr) {
    asm volatile("ldmatrix.sync.aligned.m8n8.x4.trans.shared.b16 {%0,%1,%2,%3}, [%4];"
                 : "=r"(r0), "=r"(r1), "=r"(r2), "=r"(r3) : "r"(addr) : "memory");
}
__device__ __forceinline__ uint32_t pack_bf16(float lo, float hi) {
    uint32_t r; asm("cvt.rn.bf16x2.f32 %0, %1, %2;" : "=r"(r) : "f"(hi), "f"(lo)); return r;
}
__device__ __forceinline__ float bf_lo(uint32_t v) { return __uint_as_float(v << 16); }
__device__ __forceinline__ float bf_hi(uint32_t v) { return __uint_as_float(v & 0xffff0000u); }
__device__ __forceinline__ float bf_round(float v) { return __bfloat162float(__float2bfloat16_rn(v)); }
__device__ __forceinline__ float ex2(float v) { float r; asm("ex2.approx.ftz.f32 %0, %1;" : "=f"(r) : "f"(v)); return r; }
__device__ __forceinline__ void ex2v(float& v) { asm volatile("ex2.approx.ftz.f32 %0, %0;" : "+f"(v)); }
__device__ __forceinline__ float rcp_fast(float v) { float r; asm("rcp.approx.ftz.f32 %0, %1;" : "=f"(r) : "f"(v)); return r; }
__device__ __forceinline__ float sqrt_fast(float v) { float r; asm("sqrt.approx.ftz.f32 %0, %1;" : "=f"(r) : "f"(v)); return r; }
__device__ __forceinline__ void stg128(void* p, uint32_t a, uint32_t b, uint32_t c, uint32_t d) {
    asm volatile("st.global.v4.b32 [%0], {%1,%2,%3,%4};" ::"l"(p), "r"(a), "r"(b), "r"(c), "r"(d) : "memory");
}
__device__ __forceinline__ uint4 ldg128(const void* p) {
    uint4 v; asm volatile("ld.global.cg.v4.b32 {%0,%1,%2,%3}, [%4];" : "=r"(v.x), "=r"(v.y), "=r"(v.z), "=r"(v.w) : "l"(p) : "memory"); return v;
}
__device__ __forceinline__ uint64_t mkdesc(uint32_t addr, uint32_t lbo, uint32_t sbo, uint32_t swz) {
    uint32_t lo = ((addr & 0x3FFFF) >> 4) | ((lbo >> 4) << 16);
    uint32_t hi = (sbo >> 4) | (swz << 30);
    return ((uint64_t)hi << 32) | lo;
}
__device__ __forceinline__ int perm32(int v) { return (v & ~30) | ((v >> 2) & 6) | ((v << 2) & 24); }

__device__ __forceinline__ void wgmma_rs_n128_ta0_tb0(float (&d)[64], uint32_t a0, uint32_t a1, uint32_t a2, uint32_t a3, uint64_t descB, int scaleD) {
  asm volatile("{\n.reg .pred p;\nsetp.ne.b32 p, %69, 0;\n"
    "wgmma.mma_async.sync.aligned.m64n128k16.f32.bf16.bf16 "
    "{%0, %1, %2, %3, %4, %5, %6, %7, %8, %9, %10, %11, %12, %13, %14, %15, %16, %17, %18, %19, %20, %21, %22, %23, %24, %25, %26, %27, %28, %29, %30, %31, %32, %33, %34, %35, %36, %37, %38, %39, %40, %41, %42, %43, %44, %45, %46, %47, %48, %49, %50, %51, %52, %53, %54, %55, %56, %57, %58, %59, %60, %61, %62, %63}, "
    "{%64, %65, %66, %67}, %68, p, 1, 1, 0;\n}\n"
    : "+f"(d[0]), "+f"(d[1]), "+f"(d[2]), "+f"(d[3]), "+f"(d[4]), "+f"(d[5]), "+f"(d[6]), "+f"(d[7]), "+f"(d[8]), "+f"(d[9]), "+f"(d[10]), "+f"(d[11]), "+f"(d[12]), "+f"(d[13]), "+f"(d[14]), "+f"(d[15]), "+f"(d[16]), "+f"(d[17]), "+f"(d[18]), "+f"(d[19]), "+f"(d[20]), "+f"(d[21]), "+f"(d[22]), "+f"(d[23]), "+f"(d[24]), "+f"(d[25]), "+f"(d[26]), "+f"(d[27]), "+f"(d[28]), "+f"(d[29]), "+f"(d[30]), "+f"(d[31]), "+f"(d[32]), "+f"(d[33]), "+f"(d[34]), "+f"(d[35]), "+f"(d[36]), "+f"(d[37]), "+f"(d[38]), "+f"(d[39]), "+f"(d[40]), "+f"(d[41]), "+f"(d[42]), "+f"(d[43]), "+f"(d[44]), "+f"(d[45]), "+f"(d[46]), "+f"(d[47]), "+f"(d[48]), "+f"(d[49]), "+f"(d[50]), "+f"(d[51]), "+f"(d[52]), "+f"(d[53]), "+f"(d[54]), "+f"(d[55]), "+f"(d[56]), "+f"(d[57]), "+f"(d[58]), "+f"(d[59]), "+f"(d[60]), "+f"(d[61]), "+f"(d[62]), "+f"(d[63])
    : "r"(a0), "r"(a1), "r"(a2), "r"(a3), "l"(descB), "r"(scaleD));
}
__device__ __forceinline__ void wgmma_rs_n128_ta0_tb1(float (&d)[64], uint32_t a0, uint32_t a1, uint32_t a2, uint32_t a3, uint64_t descB, int scaleD) {
  asm volatile("{\n.reg .pred p;\nsetp.ne.b32 p, %69, 0;\n"
    "wgmma.mma_async.sync.aligned.m64n128k16.f32.bf16.bf16 "
    "{%0, %1, %2, %3, %4, %5, %6, %7, %8, %9, %10, %11, %12, %13, %14, %15, %16, %17, %18, %19, %20, %21, %22, %23, %24, %25, %26, %27, %28, %29, %30, %31, %32, %33, %34, %35, %36, %37, %38, %39, %40, %41, %42, %43, %44, %45, %46, %47, %48, %49, %50, %51, %52, %53, %54, %55, %56, %57, %58, %59, %60, %61, %62, %63}, "
    "{%64, %65, %66, %67}, %68, p, 1, 1, 1;\n}\n"
    : "+f"(d[0]), "+f"(d[1]), "+f"(d[2]), "+f"(d[3]), "+f"(d[4]), "+f"(d[5]), "+f"(d[6]), "+f"(d[7]), "+f"(d[8]), "+f"(d[9]), "+f"(d[10]), "+f"(d[11]), "+f"(d[12]), "+f"(d[13]), "+f"(d[14]), "+f"(d[15]), "+f"(d[16]), "+f"(d[17]), "+f"(d[18]), "+f"(d[19]), "+f"(d[20]), "+f"(d[21]), "+f"(d[22]), "+f"(d[23]), "+f"(d[24]), "+f"(d[25]), "+f"(d[26]), "+f"(d[27]), "+f"(d[28]), "+f"(d[29]), "+f"(d[30]), "+f"(d[31]), "+f"(d[32]), "+f"(d[33]), "+f"(d[34]), "+f"(d[35]), "+f"(d[36]), "+f"(d[37]), "+f"(d[38]), "+f"(d[39]), "+f"(d[40]), "+f"(d[41]), "+f"(d[42]), "+f"(d[43]), "+f"(d[44]), "+f"(d[45]), "+f"(d[46]), "+f"(d[47]), "+f"(d[48]), "+f"(d[49]), "+f"(d[50]), "+f"(d[51]), "+f"(d[52]), "+f"(d[53]), "+f"(d[54]), "+f"(d[55]), "+f"(d[56]), "+f"(d[57]), "+f"(d[58]), "+f"(d[59]), "+f"(d[60]), "+f"(d[61]), "+f"(d[62]), "+f"(d[63])
    : "r"(a0), "r"(a1), "r"(a2), "r"(a3), "l"(descB), "r"(scaleD));
}
__device__ __forceinline__ void wgmma_rs_n64_ta0_tb1(float (&d)[32], uint32_t a0, uint32_t a1, uint32_t a2, uint32_t a3, uint64_t descB, int scaleD) {
  asm volatile("{\n.reg .pred p;\nsetp.ne.b32 p, %37, 0;\n"
    "wgmma.mma_async.sync.aligned.m64n64k16.f32.bf16.bf16 "
    "{%0, %1, %2, %3, %4, %5, %6, %7, %8, %9, %10, %11, %12, %13, %14, %15, %16, %17, %18, %19, %20, %21, %22, %23, %24, %25, %26, %27, %28, %29, %30, %31}, "
    "{%32, %33, %34, %35}, %36, p, 1, 1, 1;\n}\n"
    : "+f"(d[0]), "+f"(d[1]), "+f"(d[2]), "+f"(d[3]), "+f"(d[4]), "+f"(d[5]), "+f"(d[6]), "+f"(d[7]), "+f"(d[8]), "+f"(d[9]), "+f"(d[10]), "+f"(d[11]), "+f"(d[12]), "+f"(d[13]), "+f"(d[14]), "+f"(d[15]), "+f"(d[16]), "+f"(d[17]), "+f"(d[18]), "+f"(d[19]), "+f"(d[20]), "+f"(d[21]), "+f"(d[22]), "+f"(d[23]), "+f"(d[24]), "+f"(d[25]), "+f"(d[26]), "+f"(d[27]), "+f"(d[28]), "+f"(d[29]), "+f"(d[30]), "+f"(d[31])
    : "r"(a0), "r"(a1), "r"(a2), "r"(a3), "l"(descB), "r"(scaleD));
}
__device__ __forceinline__ void wgmma_ss_n128_ta0_tb1(float (&d)[64], uint64_t descA, uint64_t descB, int scaleD) {
  asm volatile("{\n.reg .pred p;\nsetp.ne.b32 p, %66, 0;\n"
    "wgmma.mma_async.sync.aligned.m64n128k16.f32.bf16.bf16 "
    "{%0, %1, %2, %3, %4, %5, %6, %7, %8, %9, %10, %11, %12, %13, %14, %15, %16, %17, %18, %19, %20, %21, %22, %23, %24, %25, %26, %27, %28, %29, %30, %31, %32, %33, %34, %35, %36, %37, %38, %39, %40, %41, %42, %43, %44, %45, %46, %47, %48, %49, %50, %51, %52, %53, %54, %55, %56, %57, %58, %59, %60, %61, %62, %63}, "
    "%64, %65, p, 1, 1, 0, 1;\n}\n"
    : "+f"(d[0]), "+f"(d[1]), "+f"(d[2]), "+f"(d[3]), "+f"(d[4]), "+f"(d[5]), "+f"(d[6]), "+f"(d[7]), "+f"(d[8]), "+f"(d[9]), "+f"(d[10]), "+f"(d[11]), "+f"(d[12]), "+f"(d[13]), "+f"(d[14]), "+f"(d[15]), "+f"(d[16]), "+f"(d[17]), "+f"(d[18]), "+f"(d[19]), "+f"(d[20]), "+f"(d[21]), "+f"(d[22]), "+f"(d[23]), "+f"(d[24]), "+f"(d[25]), "+f"(d[26]), "+f"(d[27]), "+f"(d[28]), "+f"(d[29]), "+f"(d[30]), "+f"(d[31]), "+f"(d[32]), "+f"(d[33]), "+f"(d[34]), "+f"(d[35]), "+f"(d[36]), "+f"(d[37]), "+f"(d[38]), "+f"(d[39]), "+f"(d[40]), "+f"(d[41]), "+f"(d[42]), "+f"(d[43]), "+f"(d[44]), "+f"(d[45]), "+f"(d[46]), "+f"(d[47]), "+f"(d[48]), "+f"(d[49]), "+f"(d[50]), "+f"(d[51]), "+f"(d[52]), "+f"(d[53]), "+f"(d[54]), "+f"(d[55]), "+f"(d[56]), "+f"(d[57]), "+f"(d[58]), "+f"(d[59]), "+f"(d[60]), "+f"(d[61]), "+f"(d[62]), "+f"(d[63])
    : "l"(descA), "l"(descB), "r"(scaleD));
}
__device__ __forceinline__ void wgmma_ss_n160_ta0_tb1(float (&d)[80], uint64_t descA, uint64_t descB, int scaleD) {
  asm volatile("{\n.reg .pred p;\nsetp.ne.b32 p, %82, 0;\n"
    "wgmma.mma_async.sync.aligned.m64n160k16.f32.bf16.bf16 "
    "{%0, %1, %2, %3, %4, %5, %6, %7, %8, %9, %10, %11, %12, %13, %14, %15, %16, %17, %18, %19, %20, %21, %22, %23, %24, %25, %26, %27, %28, %29, %30, %31, %32, %33, %34, %35, %36, %37, %38, %39, %40, %41, %42, %43, %44, %45, %46, %47, %48, %49, %50, %51, %52, %53, %54, %55, %56, %57, %58, %59, %60, %61, %62, %63, %64, %65, %66, %67, %68, %69, %70, %71, %72, %73, %74, %75, %76, %77, %78, %79}, "
    "%80, %81, p, 1, 1, 0, 1;\n}\n"
    : "+f"(d[0]), "+f"(d[1]), "+f"(d[2]), "+f"(d[3]), "+f"(d[4]), "+f"(d[5]), "+f"(d[6]), "+f"(d[7]), "+f"(d[8]), "+f"(d[9]), "+f"(d[10]), "+f"(d[11]), "+f"(d[12]), "+f"(d[13]), "+f"(d[14]), "+f"(d[15]), "+f"(d[16]), "+f"(d[17]), "+f"(d[18]), "+f"(d[19]), "+f"(d[20]), "+f"(d[21]), "+f"(d[22]), "+f"(d[23]), "+f"(d[24]), "+f"(d[25]), "+f"(d[26]), "+f"(d[27]), "+f"(d[28]), "+f"(d[29]), "+f"(d[30]), "+f"(d[31]), "+f"(d[32]), "+f"(d[33]), "+f"(d[34]), "+f"(d[35]), "+f"(d[36]), "+f"(d[37]), "+f"(d[38]), "+f"(d[39]), "+f"(d[40]), "+f"(d[41]), "+f"(d[42]), "+f"(d[43]), "+f"(d[44]), "+f"(d[45]), "+f"(d[46]), "+f"(d[47]), "+f"(d[48]), "+f"(d[49]), "+f"(d[50]), "+f"(d[51]), "+f"(d[52]), "+f"(d[53]), "+f"(d[54]), "+f"(d[55]), "+f"(d[56]), "+f"(d[57]), "+f"(d[58]), "+f"(d[59]), "+f"(d[60]), "+f"(d[61]), "+f"(d[62]), "+f"(d[63]), "+f"(d[64]), "+f"(d[65]), "+f"(d[66]), "+f"(d[67]), "+f"(d[68]), "+f"(d[69]), "+f"(d[70]), "+f"(d[71]), "+f"(d[72]), "+f"(d[73]), "+f"(d[74]), "+f"(d[75]), "+f"(d[76]), "+f"(d[77]), "+f"(d[78]), "+f"(d[79])
    : "l"(descA), "l"(descB), "r"(scaleD));
}

template <int N> struct IC { static constexpr int value = N; };
struct Cur {
    uint32_t slot, ph;
    __device__ __forceinline__ void adv() { if (++slot == NSLOT) { slot = 0; ph ^= 1; } }
};
constexpr int E0 = 2;
__host__ __device__ constexpr uint32_t slot_of(int e) { return (e + E0) % NSLOT; }
__device__ __forceinline__ Cur cur_at(int e) { Cur c; c.slot = (e + E0) % NSLOT; c.ph = ((e + E0) / NSLOT) & 1; return c; }

__device__ __forceinline__ int kv_tile(int s) { return (0x804Cu >> (4 * s)) & 15; }
__device__ __forceinline__ int op_head(int i, int kap) { return 8 * kap + (i & 7) + 16 * (i >> 3); }

constexpr float SM_SCALE = 0.08838834764831845f * 1.4426950408889634f;

struct Ctx {
    uint32_t ring, misc;
    uint32_t rel;
    int w, warp, lane;
};
__device__ __forceinline__ void release(const Ctx& c, uint32_t off, uint32_t cnt) {
    if (c.lane < 2) mbar_arrive_cluster(c.rel + off, cnt);
}
__device__ __forceinline__ void signal_event(const Ctx& c, int ev) {
    __syncwarp();
    if (c.lane == 0) mbar_arrive(c.misc + BAR_EV + (c.w * NEV + ev) * 8);
}
template <int NK, int OFF, int N>
__device__ __forceinline__ uint32_t load_afrag(uint32_t (&a)[N], uint32_t base, const Ctx& c) {
    int r = c.lane & 7, mat = c.lane >> 3;
    uint32_t addr = base + (8 * (mat >> 1) + r) * 128 + (((2 * c.warp + (mat & 1)) ^ r) << 4);
#pragma unroll
    for (int k = 0; k < NK; k++) ldsm4t(a[OFF + 4 * k], a[OFF + 4 * k + 1], a[OFF + 4 * k + 2], a[OFF + 4 * k + 3], addr + k * 2048);
    uint32_t dep = 0;
#pragma unroll
    for (int k = 0; k < NK; k++) dep |= a[OFF + 4 * k];
    return dep & blockIdx.y;
}
__device__ __forceinline__ void tile_out(unsigned char* (&out)[2], unsigned char* dst, int row0, int perm, const Ctx& c) {
#pragma unroll
    for (int i = 0; i < 2; i++) {
        int row = row0 + 16 * c.warp + 8 * i + (c.lane >> 2);
        if (perm) row = perm32(row);
        out[i] = dst + row * 64 + (((c.lane ^ (row >> 1)) & 3) << 4);
    }
}
__device__ __forceinline__ void store_pair(const float (&a)[64], int q, unsigned char* const (&out)[2], int quarter_stride, const float (&f)[2]) {
#pragma unroll
    for (int i = 0; i < 2; i++)
        stg128(out[i] + q * quarter_stride,
               pack_bf16(a[16 * q + 2 * i] * f[i], a[16 * q + 2 * i + 1] * f[i]), pack_bf16(a[16 * q + 4 + 2 * i] * f[i], a[16 * q + 4 + 2 * i + 1] * f[i]),
               pack_bf16(a[16 * q + 8 + 2 * i] * f[i], a[16 * q + 8 + 2 * i + 1] * f[i]), pack_bf16(a[16 * q + 12 + 2 * i] * f[i], a[16 * q + 12 + 2 * i + 1] * f[i]));
}

constexpr float SAFE_SUM = 1099511627776.0f;
template <int NJ>
__device__ __forceinline__ void row_max(const float (&s)[4 * NJ], float (&mx)[2]) {
#pragma unroll
    for (int i = 0; i < 2; i++) {
        float a = fmaxf(s[2 * i], s[2 * i + 1]), b = fmaxf(s[4 + 2 * i], s[4 + 2 * i + 1]);
#pragma unroll
        for (int j = 2; j < NJ; j += 2) {
            a = fmaxf(a, fmaxf(s[4 * j + 2 * i], s[4 * j + 2 * i + 1]));
            b = fmaxf(b, fmaxf(s[4 * j + 4 + 2 * i], s[4 * j + 4 + 2 * i + 1]));
        }
        a = fmaxf(a, b);
        a = fmaxf(a, __shfl_xor_sync(0xffffffffu, a, 1));
        mx[i] = fmaxf(a, __shfl_xor_sync(0xffffffffu, a, 2));
    }
}
template <int NJ, bool SHIFT>
__device__ __forceinline__ void exp_sum(float (&s)[4 * NJ], const float (&m)[2], float& l0, float& l1) {
#pragma unroll
    for (int j = 0; j < NJ; j++) {
#pragma unroll
        for (int e = 0; e < 4; e++) s[4 * j + e] = ex2(SHIFT ? s[4 * j + e] - m[e >> 1] : s[4 * j + e]);
        l0 += s[4 * j + 0] + s[4 * j + 1]; l1 += s[4 * j + 2] + s[4 * j + 3];
    }
}
__device__ __forceinline__ void recompute_scores(float (&s)[64], const uint32_t (&q)[32], uint32_t kaddr, const Ctx& c) {
    const int r = c.lane & 7, mat = c.lane >> 3;
    const uint32_t a0 = kaddr + (8 * (mat & 1) + r) * 64 + (((mat >> 1) ^ (r >> 1)) << 4);
#pragma unroll
    for (int i = 0; i < 64; i++) s[i] = 0.f;
#pragma unroll
    for (int jp = 0; jp < 8; jp++) {
#pragma unroll
        for (int k = 0; k < 8; k++) {
            asm volatile(
                "{\n.reg .b32 b0, b1, b2, b3;\n"
                "ldmatrix.sync.aligned.m8n8.x4.trans.shared.b16 {b0,b1,b2,b3}, [%12];\n"
                "mma.sync.aligned.m16n8k16.row.col.f32.bf16.bf16.f32 {%0,%1,%2,%3}, {%8,%9,%10,%11}, {b0,b1}, {%0,%1,%2,%3};\n"
                "mma.sync.aligned.m16n8k16.row.col.f32.bf16.bf16.f32 {%4,%5,%6,%7}, {%8,%9,%10,%11}, {b2,b3}, {%4,%5,%6,%7};\n}\n"
                : "+f"(s[8 * jp]), "+f"(s[8 * jp + 1]), "+f"(s[8 * jp + 2]), "+f"(s[8 * jp + 3]),
                  "+f"(s[8 * jp + 4]), "+f"(s[8 * jp + 5]), "+f"(s[8 * jp + 6]), "+f"(s[8 * jp + 7])
                : "r"(q[4 * k]), "r"(q[4 * k + 1]), "r"(q[4 * k + 2]), "r"(q[4 * k + 3]),
                  "r"((a0 ^ ((jp & 1) << 5)) + (jp >> 1) * 8192 + k * 1024) : "memory");
        }
    }
}
__device__ __forceinline__ int mask_lim(const Ctx& c) { return perm32(16 * c.warp + (c.lane >> 2)) - 8 * (c.lane & 3); }
template <int J0>
__device__ __forceinline__ void mask_diag(float (&s)[4 * J0 + 32], const Ctx& c) {
    const int lim = mask_lim(c);
    if (c.warp < 2) {
#pragma unroll
        for (int x = 0; x < 16; x++) {
            if (2 * (x >> 2) + (x & 1) - (x & 2) > lim) s[4 * J0 + x] = -INFINITY;
            s[4 * J0 + 16 + x] = -INFINITY;
        }
    } else {
#pragma unroll
        for (int x = 0; x < 16; x++)
            if (32 + 2 * (x >> 2) + (x & 1) - (x & 2) > lim) s[4 * J0 + 16 + x] = -INFINITY;
    }
}
__device__ __forceinline__ void mask_any(float (&s)[64], int hh, const Ctx& c) {
    const int lim = mask_lim(c) + 64 * hh;
#pragma unroll
    for (int x = 0; x < 64; x++)
        if (32 * (x >> 4) + 2 * ((x >> 2) & 3) + (x & 1) - (x & 2) > lim) s[x] = -INFINITY;
}
__device__ __forceinline__ void issue_pv(float (&o)[64], const uint32_t (&p)[32], uint32_t vaddr, int acc, int mode  ) {
    uint64_t d = mkdesc(vaddr, 16, 512, 2);
    if (mode == 0) {
        wg_fence();
#pragma unroll
        for (int k = 0; k < 8; k++)
            wgmma_rs_n128_ta0_tb0(o, p[4 * k], p[4 * k + 1], p[4 * k + 2], p[4 * k + 3], d + (k >> 1) * 512 + 2 * (k & 1), k ? 1 : acc);
        wg_commit();
    } else if (mode == 1) {
        wg_fence();
#pragma unroll
        for (int k = 0; k < 4; k++) wgmma_rs_n128_ta0_tb0(o, p[4 * k], p[4 * k + 1], p[4 * k + 2], p[4 * k + 3], d + (k >> 1) * 512 + 2 * (k & 1), k != 0);
        wg_commit();
    } else {
        wg_fence();
        wgmma_rs_n128_ta0_tb0(o, p[0], p[1], p[2], p[3], d, acc);
        wg_commit();
    }
}
__device__ __forceinline__ void issue_qk(float (&s)[64], const uint32_t (&q)[32], uint32_t kaddr) {
    uint64_t d = mkdesc(kaddr, 8192, 512, 2);
    wg_fence();
#pragma unroll
    for (int k = 0; k < 8; k++) wgmma_rs_n128_ta0_tb1(s, q[4 * k], q[4 * k + 1], q[4 * k + 2], q[4 * k + 3], d + 64 * k, k != 0);
    wg_commit();
}
__device__ __forceinline__ void issue_qk_half(float (&s32)[32], const uint32_t (&q)[32], uint32_t kaddr) {
    uint64_t d = mkdesc(kaddr, 8192, 512, 2);
    wg_fence();
#pragma unroll
    for (int k = 0; k < 8; k++) wgmma_rs_n64_ta0_tb1(s32, q[4 * k], q[4 * k + 1], q[4 * k + 2], q[4 * k + 3], d + 64 * k, k != 0);
    wg_commit();
}
__device__ __forceinline__ void row_inv(const float (&l)[2], float (&inv)[2]) {
#pragma unroll
    for (int i = 0; i < 2; i++) {
        float sum = l[i];
        sum += __shfl_xor_sync(0xffffffffu, sum, 1);
        sum += __shfl_xor_sync(0xffffffffu, sum, 2);
        inv[i] = rcp_fast(sum);
    }
}

__device__ __forceinline__ const unsigned char* xn_addr(int row, int col) {
    row = perm32(row);
    return g_xn + ((row >> 7) * 10 + (col >> 6)) * 16384 + (row & 127) * 128 + ((((col & 63) >> 3) ^ (row & 7)) << 4);
}
__device__ __forceinline__ void mma16816(float (&d)[4], uint32_t a0, uint32_t a1, uint32_t a2, uint32_t a3, uint32_t b0, uint32_t b1) {
    asm volatile("mma.sync.aligned.m16n8k16.row.col.f32.bf16.bf16.f32 {%0,%1,%2,%3}, {%4,%5,%6,%7}, {%8,%9}, {%0,%1,%2,%3};"
                 : "+f"(d[0]), "+f"(d[1]), "+f"(d[2]), "+f"(d[3]) : "r"(a0), "r"(a1), "r"(a2), "r"(a3), "r"(b0), "r"(b1));
}
__device__ __forceinline__ uint32_t lds32(uint32_t addr) { uint32_t v; asm volatile("ld.shared.u32 %0, [%1];" : "=r"(v) : "r"(addr)); return v; }

__device__ __forceinline__ int fresh_lane() { int l; asm volatile("mov.u32 %0, %%laneid;" : "=r"(l)); return l; }
__device__ __forceinline__ void ln_rows(const __nv_bfloat16* x, int row0, uint32_t wr_s) {
    int lane = fresh_lane();
    int hl = lane & 15, row = row0 + (lane >> 4);
    uint32_t v[20];
#pragma unroll
    for (int i = 0; i < 5; i++) {
        const uint4 u = __ldg(reinterpret_cast<const uint4*>(x + (size_t)row * DM + 128 * i + 8 * hl));
        v[4 * i] = u.x; v[4 * i + 1] = u.y; v[4 * i + 2] = u.z; v[4 * i + 3] = u.w;
    }
    float mean = 0.f, m2 = 0.f, acc2 = 0.f;
#pragma unroll
    for (int i = 0; i < 20; i++) { mean += bf_lo(v[i]); acc2 += bf_hi(v[i]); }
    mean = (mean + acc2) * (1.0f / 40);
    acc2 = 0.f;
#pragma unroll
    for (int i = 0; i < 20; i++) {
        float d0 = __uint_as_float(__byte_perm(v[i], 0, 0x1044)) - mean, d1 = __uint_as_float(__byte_perm(v[i], 0, 0x3244)) - mean;
        m2 = fmaf(d0, d0, m2); acc2 = fmaf(d1, d1, acc2);
    }
    m2 += acc2;
    acc2 = 0.f;
#pragma unroll
    for (int o = 1; o < 16; o <<= 1) {
        float mo = __shfl_xor_sync(0xffffffffu, mean, o), qo = __shfl_xor_sync(0xffffffffu, m2, o), d = mo - mean;
        m2 = fmaf(d * d, 20.0f * o, m2 + qo);
        mean = 0.5f * (mean + mo);
    }
    const uint32_t mb2 = pack_bf16(mean, mean);
    const float inv = rcp_fast(bf_round(sqrt_fast(bf_round(bf_round(m2 * (1.0f / DM)) + 1e-5f))));
    float dot = 0.f;
    lane = fresh_lane(); hl = lane & 15; row = row0 + (lane >> 4);
    if (hl == 0) g_stats[row] = make_uint2(mb2, __float_as_uint(inv));
    unsigned char* xp = const_cast<unsigned char*>(xn_addr(row, 8 * hl));
#pragma unroll
    for (int i = 0; i < 5; i++) {
        uint32_t ww[4];
        asm volatile("ld.shared.v4.b32 {%0,%1,%2,%3}, [%4];" : "=r"(ww[0]), "=r"(ww[1]), "=r"(ww[2]), "=r"(ww[3]) : "r"(wr_s + 256 * i + 16 * hl) : "memory");
#pragma unroll
        for (int e = 0; e < 4; e++) {
            uint32_t d;
            asm("sub.rn.bf16x2 %0, %1, %2;" : "=r"(d) : "r"(v[4 * i + e]), "r"(mb2));
            d = pack_bf16(bf_lo(d) * inv, bf_hi(d) * inv);
            v[4 * i + e] = d;
            dot = fmaf(bf_lo(d), bf_lo(ww[e]), dot);
            acc2 = fmaf(bf_hi(d), bf_hi(ww[e]), acc2);
        }
        stg128(xp + i * 32768, v[4 * i], v[4 * i + 1], v[4 * i + 2], v[4 * i + 3]);
    }
    dot += acc2;
#pragma unroll
    for (int o = 8; o > 0; o >>= 1) dot += __shfl_xor_sync(0xffffffffu, dot, o);
    lane = fresh_lane();
    if ((lane & 15) == 0) g_router[row0 + (lane >> 4)] = bf_round(dot);
}

__device__ __forceinline__ void aux_cta(const CUtensorMap* tmG, const CUtensorMap* tmU, const CUtensorMap* tmD, unsigned char* sm, int a) {
    constexpr int STG = 57344, XS = 3 * STG, HS = XS + 8 * 1296, KEY = HS + 8 * 912, MI = KEY + 8192;
    const int tid = threadIdx.x, warp = __shfl_sync(0xffffffffu, tid >> 5, 0), lane = tid & 31;
    const uint32_t sb = smem_u32(sm);
    const uint32_t full = sb + MI, empty = sb + MI + 32;
    int* s_sel = reinterpret_cast<int*>(sm + MI + 64);
    float* s_r = reinterpret_cast<float*>(sm + MI + 96);
    volatile unsigned* s_misc = reinterpret_cast<volatile unsigned*>(sm + MI + 128);
    uint32_t* s_key = reinterpret_cast<uint32_t*>(sm + KEY);
    if (tid == 0) {
        for (int i = 0; i < 3; i++) { mbar_init(full + 8 * i, 1); mbar_init(empty + 8 * i, 10); }
        asm volatile("fence.mbarrier_init.release.cluster;" ::: "memory");
    }
    __syncthreads();
    if (warp == 11) {
        if (elect_one()) {
            const unsigned ep1 = *reinterpret_cast<volatile unsigned*>(&g_epoch) + 1;
            __nanosleep(20000);
            flag_wait(flag_ptr(MOE_GATE), ep1 * MOE_CNT);
            int st = 0; uint32_t ph = 0;
#pragma unroll 1
            for (int s = 0; s < 34; s++) {
                mbar_wait(empty + 8 * st, ph ^ 1);
                const uint32_t dst = sb + st * STG, fb = full + 8 * st;
                if (s < 20) {
                    mbar_expect_tx(fb, 57344);
                    tma3d(dst, tmG, 0, 32 * s, 7 * a, fb);
                    tma3d(dst + 28672, tmU, 0, 32 * s, 7 * a, fb);
                } else {
                    mbar_expect_tx(fb, 40960);
                    tma3d(dst, tmD, 0, 448 * a + 32 * (s - 20), 0, fb);
                }
                if (s >= 2) {
#pragma unroll 1
                    for (int f = (s == 2 ? 3 : s + 6); f <= s + 6 && f < 34; f++) {
                        if (f < 20) { tma3d_prefetch(tmG, 0, 32 * f, 7 * a); tma3d_prefetch(tmU, 0, 32 * f, 7 * a); }
                        else tma3d_prefetch(tmD, 0, 448 * a + 32 * (f - 20), 0);
                    }
                }
                if (++st == 3) { st = 0; ph ^= 1; }
            }
        }
        return;
    }
    if (warp == 10) return;
    if (tid < 8) {
        unsigned e = *reinterpret_cast<volatile unsigned*>(&g_epoch);
        if (tid == 0) s_misc[0] = e;
        flag_wait(flag_ptr(FL_LN + tid), (e + 1) * (tid < 4 ? 33u : 128u));
    }
    bar_sync(1, 320);
    const unsigned ep = s_misc[0];
    auto top8 = [&](uint32_t (&key)[8]) {
        uint32_t mine = 0;
#pragma unroll 1
        for (int r = 0; r < TOPC; r++) {
            uint32_t best = 0;
#pragma unroll
            for (int i = 0; i < 8; i++) best = max(best, key[i]);
            best = __reduce_max_sync(0xffffffffu, best);
#pragma unroll
            for (int i = 0; i < 8; i++) if (key[i] == best) key[i] = 0;
            if (lane == r) mine = best;
        }
        return mine;
    };
#pragma unroll 1
    for (int pass = 0; pass < 2; pass++) {
        if (warp < (pass ? 1 : 8)) {
            uint32_t key[8];
#pragma unroll
            for (int i = 0; i < 8; i++) {
                if (pass == 0) {
                    int idx = warp * 256 + i * 32 + lane;
                    uint32_t b = __float_as_uint(__ldcg(g_router + idx)) >> 16;
                    b = (b & 0x8000u) ? (~b & 0xffffu) : (b | 0x8000u);
                    key[i] = (b << 16) | (uint32_t)(0xffff - idx);
                } else key[i] = i < 2 ? s_key[i * 32 + lane] : 0u;
            }
            uint32_t best = top8(key);
            if (lane < TOPC) {
                if (pass == 0) s_key[warp * 8 + lane] = best;
                else {
                    uint32_t b = best >> 16;
                    b = (b & 0x8000u) ? (b & 0x7fffu) : (~b & 0xffffu);
                    s_sel[lane] = 0xffff - (int)(best & 0xffffu);
                    s_r[lane] = bf_round(rcp_fast(1.0f + __expf(fminf(-__uint_as_float(b << 16), 80.f))));
                }
            }
        }
        bar_sync(1, 320);
    }
#pragma unroll 1
    for (int it = 0; it < 2; it++) {
        int i = tid + it * 320, tk = i / 80, ch = i % 80;
        *reinterpret_cast<uint4*>(sm + XS + tk * 1296 + ch * 16) = __ldcg(reinterpret_cast<const uint4*>(xn_addr(s_sel[tk], ch * 8)));
    }
    bar_sync(1, 320);
    const int g = lane >> 2, t = lane & 3;
    const uint32_t woff = warp * 4096 + (8 * (lane >> 4) + (lane & 7)) * 128 + ((((lane >> 3) & 1) ^ (lane & 7)) << 4);
    int st = 0; uint32_t ph = 0;
    float ga[4][4], ua[4][4];
#pragma unroll
    for (int i = 0; i < 4; i++)
#pragma unroll
        for (int e = 0; e < 4; e++) { ga[i][e] = 0.f; ua[i][e] = 0.f; }
#pragma unroll 1
    for (int s = 0; s < 34; s++) {
        if (s == 20) {
            if (warp < 7) {
#pragma unroll 1
                for (int i = 0; i < 4; i++) {
#pragma unroll
                    for (int e = 0; e < 4; e++) {
                        float gv = bf_round(ga[0][e]), uv = bf_round(ua[0][e]);
                        float sg = bf_round(gv * rcp_fast(1.0f + __expf(fminf(-gv, 80.f))));
                        int f = warp * 64 + i * 16 + g + 8 * (e >> 1), tk = 2 * t + (e & 1);
                        *reinterpret_cast<__nv_bfloat16*>(sm + HS + tk * 912 + f * 2) = __float2bfloat16_rn(sg * uv);
                        ga[0][e] = ga[1][e]; ga[1][e] = ga[2][e]; ga[2][e] = ga[3][e]; ga[3][e] = 0.f;
                        ua[0][e] = ua[1][e]; ua[1][e] = ua[2][e]; ua[2][e] = ua[3][e];
                    }
                }
            }
            bar_sync(1, 320);
        }
        mbar_wait(full + 8 * st, ph);
        if (s >= 20 || warp < 7) {
#pragma unroll
            for (int kk = 0; kk < 2; kk++) {
                uint32_t xb = sb + (s < 20 ? XS + g * 1296 + s * 64 : HS + g * 912 + (s - 20) * 64) + 32 * kk + 4 * t;
                uint32_t b0 = lds32(xb), b1 = lds32(xb + 16);
                uint32_t wa = sb + st * STG + woff + kk * 2048;
#pragma unroll
                for (int i = 0; i < 4; i++) {
                    uint32_t a0, a1, a2, a3;
                    ldsm4t(a0, a1, a2, a3, wa ^ (i << 5));
                    mma16816(ga[i], a0, a1, a2, a3, b0, b1);
                    if (s < 20) {
                        ldsm4t(a0, a1, a2, a3, (wa ^ (i << 5)) + 28672);
                        mma16816(ua[i], a0, a1, a2, a3, b0, b1);
                    }
                }
            }
        }
        asm volatile("fence.proxy.async.shared::cta;" ::: "memory");
        __syncwarp();
        if (lane == 0) mbar_arrive(empty + 8 * st);
        if (++st == 3) { st = 0; ph ^= 1; }
    }
#pragma unroll
    for (int i = 0; i < 4; i++)
#pragma unroll
        for (int e = 0; e < 4; e += 2)
            *reinterpret_cast<float2*>(g_moe_part + (a * DM + warp * 64 + i * 16 + g + 4 * e) * 8 + 2 * t) = make_float2(ga[i][e], ga[i][e + 1]);
    bar_sync(1, 320);
    if (tid == 0) {
        __threadfence();
        unsigned old = atomicAdd(flag_ptr(FL_MOE_CNT), 1u);
        s_misc[1] = (old == ep * 4u + 3u);
        __threadfence();
    }
    bar_sync(1, 320);
    if (s_misc[1]) {
        const float4* pp = reinterpret_cast<const float4*>(g_moe_part);
#pragma unroll 1
        for (int i = tid; i < DM * 2; i += 320) {
            float4 v0 = __ldcg(pp + i), v1 = __ldcg(pp + DM * 2 + i), v2 = __ldcg(pp + DM * 4 + i), v3 = __ldcg(pp + DM * 6 + i);
            float y[4] = {v0.x + v1.x + v2.x + v3.x, v0.y + v1.y + v2.y + v3.y, v0.z + v1.z + v2.z + v3.z, v0.w + v1.w + v2.w + v3.w};
#pragma unroll
            for (int e = 0; e < 4; e++) {
                int col = i >> 1, tk = (i & 1) * 4 + e;
                float upd = bf_round(bf_round(y[e]) * s_r[tk]);
                float xn = __bfloat162float(*reinterpret_cast<const __nv_bfloat16*>(sm + XS + tk * 1296 + col * 2));
                g_brow[tk * DM + col] = __float2bfloat16_rn(xn + upd);
            }
        }
        if (tid < TOPC) g_sel[tid] = s_sel[tid];
        bar_sync(1, 320);
        if (tid == 0) {
            flag_signal(flag_ptr(FL_MOE_DONE));
            *reinterpret_cast<volatile unsigned*>(&g_epoch) = ep + 1;
        }
    }
}

__global__ void __cluster_dims__(2, 1, 1) __launch_bounds__(384, 1)
fused_kernel(const __grid_constant__ CUtensorMap tmC, const __grid_constant__ CUtensorMap tmWk, const __grid_constant__ CUtensorMap tmWv,
             const __grid_constant__ CUtensorMap tmWq, const __grid_constant__ CUtensorMap tmWo,
             const __grid_constant__ CUtensorMap tmG, const __grid_constant__ CUtensorMap tmU, const __grid_constant__ CUtensorMap tmD, const Params P) {
    extern __shared__ __align__(1024) unsigned char smem_raw[];
    const uint32_t ring = smem_u32(smem_raw);
    const uint32_t misc = ring + RING_BYTES;
    const int tid = threadIdx.x;
    const int rank = blockIdx.x & 1;
    uint32_t smid, nsm;
    asm("mov.u32 %0, %%smid;" : "=r"(smid));
    asm("mov.u32 %0, %%nsmid;" : "=r"(nsm));
    if (nsm != 132) smid = blockIdx.x;
    auto role_of = [](int tpc) {
        return tpc < 32 ? (tpc & 7) * 8 + (tpc >> 3) : tpc < 60 ? (1 + (tpc - 32) % 7) * 8 + 4 + (tpc - 32) / 7 : tpc < 64 ? tpc - 56 : tpc;
    };
    int mc = role_of(smid >> 1);

    auto prefetch_w = [&](int ch) {
        const int i = tid - 128;
        asm volatile("prefetch.global.L2 [%0];" ::"l"((rank ? P.wv : P.wk) + (size_t)(ch * 128 + (mc & 3) * 32 + (i >> 3)) * 4096 + (mc >> 2) * 128 + (i & 7) * 16));
    };
    if (tid >= 128 && mc < 64) {
        if (tid < 256) asm volatile("prefetch.global.L2 [%0];" ::"l"(P.c + (size_t)((12 + (mc & 3)) * 128 + ((mc >> 2) * 2 + rank) * 4) * DC + (tid - 128) * 16));
        prefetch_w(0);
    }
    auto load_w0 = [&]() {
        const CUtensorMap* tw = rank ? &tmWv : &tmWk;
        mbar_expect_tx(misc + BAR_FULL + 8 * slot_of(0), SLOT_BYTES);
        tma2d(ring + slot_of(0) * SLOT_BYTES, tw, (mc >> 2) * 128, 0, misc + BAR_FULL + 8 * slot_of(0));
        tma2d(ring + slot_of(0) * SLOT_BYTES + 16384, tw, (mc >> 2) * 128 + 64, 0, misc + BAR_FULL + 8 * slot_of(0));
    };
    if (tid == 0) {
#pragma unroll
        for (int i = 0; i < NSLOT; i++) mbar_init(misc + BAR_FULL + 8 * i, 1);
#pragma unroll
        for (int i = 0; i < E0; i++) mbar_arrive(misc + BAR_FULL + 8 * i);
        asm volatile("fence.mbarrier_init.release.cluster;" ::: "memory");
        if (mc < 64) load_w0();
    }
    if (tid == 160) {
        asm volatile("st.shared.u32 [%0], %1;" ::"r"(misc + MISC_SMID), "r"(smid) : "memory");
        asm volatile("fence.release.sync_restrict::shared::cta.cluster;" ::: "memory");
    }
    if (tid == 32) {
        asm volatile("prefetch.tensormap [%0];" ::"l"(&tmC) : "memory");
#pragma unroll
        for (int i = 0; i < NSLOT; i++) mbar_init(misc + BAR_EMPTY + 8 * i, 16);
#pragma unroll
        for (int i = 0; i < E0; i++) mbar_arrive_cluster(misc + BAR_EMPTY + 8 * i, 16);
        asm volatile("fence.mbarrier_init.release.cluster;" ::: "memory");
    }
    if (tid == 64) {
#pragma unroll
        for (int i = 0; i < NST3; i++) { mbar_init(misc + BAR_FULL3 + 8 * i, 1); mbar_init(misc + BAR_EMPTY3 + 8 * i, 16); }
#pragma unroll
        for (int i = 0; i < 4; i++) mbar_init(misc + BAR_PROG + 8 * i, 1);
        mbar_init(misc + BAR_LN, 2);
        asm volatile("fence.mbarrier_init.release.cluster;" ::: "memory");
    }
    if (tid == 96) {
#pragma unroll
        for (int i = 0; i < 24; i++) mbar_init(misc + BAR_DEP + 8 * i, 1);
    }
    if (tid == 128) {
#pragma unroll
        for (int i = 0; i < 2 * NEV; i++) mbar_init(misc + BAR_EV + 8 * i, 4);
    }
    __syncthreads();
    asm volatile("barrier.cluster.arrive.relaxed.aligned;\nbarrier.cluster.wait.aligned;" ::: "memory");
    {
        uint32_t peer;
        asm volatile("{\n.reg .b32 r, a;\nmov.u32 r, %%cluster_ctarank;\nxor.b32 r, r, 1;\nmapa.shared::cluster.u32 a, %1, r;\n"
                     "ld.shared::cluster.u32 %0, [a];\n}\n" : "=r"(peer) : "r"(misc + MISC_SMID) : "memory");
        if ((__shfl_sync(0xffffffffu, peer, 0) ^ smid) != 1) {
            if (tid == 0) {
                const unsigned ep1 = *reinterpret_cast<volatile unsigned*>(&g_epoch) + 1;
                if ((smid & 1) == 0) atomicExch(g_roleq + 2 + (atomicAdd(g_roleq, 1u) & 127), (ep1 << 8) | (smid >> 1));
                if (rank == 0) {
                    unsigned* slot = g_roleq + 2 + (atomicAdd(g_roleq + 1, 1u) & 127);
                    unsigned v = 0;
                    for (int spin = 0; spin < 4000000 && ((v = atomicAdd(slot, 0u)) >> 8) != (ep1 & 0xffffffu); spin++) {}
                    asm volatile("st.shared::cluster.u32 [%0], %1;" ::"r"(mapa(misc + MISC_SMID + 4, 0)), "r"(v & 255) : "memory");
                    asm volatile("st.shared::cluster.u32 [%0], %1;" ::"r"(mapa(misc + MISC_SMID + 4, 1)), "r"(v & 255) : "memory");
                }
                if (mc < 64) {
                    mbar_wait(misc + BAR_FULL + 8 * slot_of(0), 0);
                    asm volatile("mbarrier.inval.shared::cta.b64 [%0];" ::"r"(misc + BAR_FULL + 8 * slot_of(0)) : "memory");
                    mbar_init(misc + BAR_FULL + 8 * slot_of(0), 1);
                    asm volatile("fence.mbarrier_init.release.cluster;" ::: "memory");
                }
            }
            __syncwarp();
            asm volatile("barrier.cluster.arrive.aligned;\nbarrier.cluster.wait.aligned;" ::: "memory");
            mc = role_of(__shfl_sync(0xffffffffu, lds32(misc + MISC_SMID + 4), 0));
            if (tid == 0 && mc < 64) load_w0();
            __syncwarp();
        }
    }
    const int cta = mc * 2 + rank;
    const bool aux = mc >= 64;
    const int team = mc >> 2, k = mc & 3;
    const int u3 = (mc >> 4) * 2 + (team & 1), s3 = k, kap = (mc >> 3) & 1;
    const int partner = cta ^ 16;
    const int b0 = k, b1 = 7 - k;
    if (tid >= 128 && !aux) prefetch_w(1);
    if (tid == 256 && !aux) {
        const CUtensorMap* tw = rank ? &tmWv : &tmWk;
#pragma unroll
        for (int e = 1; e < NSLOT; e++) {
            const uint32_t fb = misc + BAR_FULL + 8 * slot_of(e), dst = ring + slot_of(e) * SLOT_BYTES;
            mbar_expect_tx(fb, SLOT_BYTES);
            if (e & 1) tma2d_mc(dst + rank * 16384, &tmC, (e >> 1) * 128 + rank * 64, (12 + k) * 128, fb);
            else { tma2d(dst, tw, team * 128, e * 64, fb); tma2d(dst + 16384, tw, team * 128 + 64, e * 64, fb); }
        }
    }
    const int wg = __shfl_sync(0xffffffffu, tid >> 7, 0);

    if (wg == 0 || aux) {
        asm volatile("setmaxnreg.dec.sync.aligned.u32 40;");
        const int warp = __shfl_sync(0xffffffffu, tid >> 5, 0), lane = tid & 31;
        if (warp == 0 && !aux) {
            const bool lead = elect_one();
            Cur c = cur_at(NSLOT);
            uint32_t dst, fb;
            auto acquire = [&]() {
                mbar_wait_sleep(misc + BAR_EMPTY + 8 * c.slot, c.ph ^ 1);
                fb = misc + BAR_FULL + 8 * c.slot; dst = ring + c.slot * SLOT_BYTES;
                if (lead) mbar_expect_tx(fb, SLOT_BYTES);
                c.adv();
            };
            auto load_w = [&](const CUtensorMap* tm, int col, int row) {
                acquire();
                if (lead) { tma2d(dst, tm, col, row, fb); tma2d(dst + 16384, tm, col + 64, row, fb); }
            };
            auto load_half = [&](const unsigned char* src) {
                acquire();
                if (lead) bulk_load_mc(dst + rank * 16384, src, 16384, fb);
            };
            auto dep_wait = [&](int d) { mbar_wait_sleep(misc + BAR_DEP + 8 * d, 0); fence_async_global(); };
            auto op_prefetch = [&](int i) {
                const int head = op_head(i, kap);
                l2_prefetch(reinterpret_cast<const unsigned char*>(P.wo) + head * 163840 + (u3 * 8 + s3 * 2 + rank) * 2560, 2560);
                if (i < 8) l2_prefetch(g_ctx + (size_t)(head * 32 + 4 * u3 + 2 * rank) * 16384 + s3 * 8192, 8192);
            };
            if (lead) l2_prefetch(reinterpret_cast<const unsigned char*>(P.c) + (size_t)cta * 12288, 12288);
            const CUtensorMap* tw = rank ? &tmWv : &tmWk;
            const unsigned char* Kh = g_K + (size_t)team * 32 * 16384 + rank * 16384;
            const unsigned char* Vh = g_V + (size_t)team * 32 * 16384 + rank * 16384;
#pragma unroll 1
            for (int v = 0; v < 2; v++) {
                const int h = team + 16 * v;
#pragma unroll 1
                for (int i = v ? 0 : 3; i < 16; i++) {
                    if (i < 4 && v) load_w(tw, h * 128, i * 128);
                    if (v && i == 3 && lead) mbar_arrive(misc + BAR_PROG + 8);
                    if (v && (i == 3 || i == 7)) dep_wait(D_WAR + (i > 3));
                    acquire();
                    if (lead) tma2d_mc(dst + rank * 16384, &tmC, (i & 3) * 128 + rank * 64, (kv_tile(i >> 2) + k) * 128, fb);
                    if (i == 8 && lead) {
                        tma2d_prefetch(&tmWq, h * 128 + rank * 64, k * 64); tma2d_prefetch(&tmWq, h * 128 + rank * 64, k * 64 + 256);
                        if (k < 2) tma2d_prefetch(&tmWq, h * 128 + rank * 64, k * 64 + 512);
                    }
                }
                int togo = v ? PF_START : 11;
#pragma unroll 1
                for (int r = 0; r < 2; r++) {
                    const int p = r ? b1 : b0, n = 2 * p + 1;
                    if (v == 0) dep_wait(D_LN + r);
                    const int g0 = r ? rank ^ 1 : 3 - rank, g1 = 3 - g0;
                    const unsigned char* x0 = g_xn + (2 * p + (g0 >> 1)) * 163840 + (g0 & 1) * 8192;
                    const unsigned char* x1 = g_xn + (2 * p + (g1 >> 1)) * 163840 + (g1 & 1) * 8192;
#pragma unroll 1
                    for (int kc = 0; kc < 10; kc++) {
                        acquire();
                        if (lead) {
                            tma2d_mc(dst + 16384 + rank * 8192, &tmWq, h * 128 + rank * 64, kc * 64, fb);
                            bulk_load(dst, x0 + kc * 16384, 8192, fb);
                            bulk_load(dst + 8192, x1 + kc * 16384, 8192, fb);
                        }
                    }
                    dep_wait(D_KV + 2 * v + r);
                    load_half(Kh + n * 32768);
#pragma unroll 1
                    for (int j = n - 1; j >= 0; j--) {
                        load_half(Kh + j * 32768); load_half(Vh + (j + 1) * 32768);
                        if (v == 0 && r && j == 7 && lead) mbar_arrive(misc + BAR_PROG);
                        --togo;
                        if (v == 0 && togo == 0 && lead) {
                            tma2d_prefetch(tw, h * 128 + 2048, k * 128); tma2d_prefetch(tw, h * 128 + 2112, k * 128);
                            l2_prefetch(reinterpret_cast<const unsigned char*>(P.c) + (size_t)cta * 16384, 16384);
                        }
                        if (v && togo <= 0 && togo > -OP_PF && lead) op_prefetch(-togo);
                    }
                    load_half(Vh);
                }
            }
            mbar_wait_sleep(misc + BAR_EMPTY + 8 * c.slot, c.ph ^ 1); c.adv();
            int st = 0; uint32_t ph3 = 0;
#pragma unroll 1
            for (int i = 0; i < 32; i++) {
                const int head = op_head(i >> 1, kap);
                if ((i & 1) == 0) dep_wait(D_CTX + (i >> 1));
                if (i < NST3) { mbar_wait_sleep(misc + BAR_EMPTY + 8 * c.slot, c.ph ^ 1); c.adv(); }
                else mbar_wait_sleep(misc + BAR_EMPTY3 + 8 * st, ph3 ^ 1);
                fb = misc + BAR_FULL3 + 8 * st; dst = ring + st * ST3_BYTES;
                if (i == LATE_AT && lead) mbar_arrive(misc + BAR_PROG + 16);
                if (lead) {
                    mbar_expect_tx(fb, ST3_BYTES);
                    const unsigned char* src = g_ctx + (size_t)(head * 32 + 4 * u3 + 2 * rank) * 16384 + (i & 1) * 8192;
                    bulk_load(dst, src, 8192, fb);
                    bulk_load(dst + 8192, src + 16384, 8192, fb);
                    tma3d_mc(dst + 16384 + rank * 10240, &tmWo, 0, head * 128 + (i & 1) * 64 + rank * 32, 5 * s3, fb);
                    if ((i & 1) && (i >> 1) + OP_PF < 16) op_prefetch((i >> 1) + OP_PF);
                }
                if (++st == NST3) { st = 0; ph3 ^= 1; }
            }
        } else {
        if (warp >= 1 && warp <= 3 && lane < 27 && (warp - 1) * 27 + lane < 80) {
            const int ch = (warp - 1) * 27 + lane;
            uint4 u = __ldg(reinterpret_cast<const uint4*>(P.wr) + ch);
            asm volatile("st.shared.v4.b32 [%0], {%1,%2,%3,%4};" ::"r"(misc + MISC_WR + 16 * ch), "r"(u.x), "r"(u.y), "r"(u.z), "r"(u.w) : "memory");
        }
        bar_sync(3, aux ? 384 : 96);
        const int nln = aux ? (warp < 8 ? 3 : 2) : (warp == 3 ? 1 : 3), rstep = aux ? 24 : -512;
        int lrow = aux ? (cta - 128) * 256 + 192 + 2 * warp : (cta >> 5) * 256 + (cta & 31) * 6 + (warp - 1) * 2;
        int lnext = aux ? lrow + 24 : 1536 + cta * 4 + (warp - 1) * 2;
#pragma unroll 1
        for (int t = 0; t < nln; t++) {
            if (t + 1 < nln) {
                const int ll = fresh_lane();
#pragma unroll
                for (int i = 0; i < 3; i++)
                    if (i * 32 + ll < 80) asm volatile("prefetch.global.L2 [%0];" ::"l"(P.x + (size_t)lnext * DM + (i * 32 + ll) * 16));
            }
            ln_rows(P.x, lrow, misc + MISC_WR);
            __syncwarp();
            if (fresh_lane() == 0 && warp < 3 && !aux) {
                if (t) flag_signal(flag_ptr(FL_LN + (lrow >> 8))); else mbar_arrive(misc + BAR_LN);
            }
            lrow = lnext; lnext += rstep;
        }
        if (aux) {
            bar_sync(3, 384);
            if (tid == 320) flag_signal(flag_ptr(FL_LN + cta - 128));
            __syncwarp();
            asm volatile("setmaxnreg.inc.sync.aligned.u32 128;");
            aux_cta(&tmG, &tmU, &tmD, smem_raw, cta - 128);
        } else
        if (warp == 3) {
            const unsigned ep1 = *reinterpret_cast<volatile unsigned*>(&g_epoch) + 1;
            if (lane == 0) {
                asm volatile("st.shared.u32 [%0], %1;" ::"r"(misc + MISC_EPOCH), "r"(ep1) : "memory");
                mbar_wait(misc + BAR_LN, 0);
                flag_signal(flag_ptr(FL_LN + (cta >> 5)));
                flag_wait(flag_ptr(FL_LN + b0), ep1 * 33u);
                mbar_arrive(misc + BAR_DEP + 8 * D_LN);
#pragma unroll 1
                for (int i = 0; i < 4; i++) {
                    mbar_wait(misc + BAR_EV + 8 * (NEV + EV_KV + i), 0);
                    if (i < 2) {
                        mbar_wait(misc + BAR_EV + 8 * (EV_KV + i), 0);
                        asm volatile("red.release.gpu.global.add.u32 [%0], 2;" ::"l"(flag_ptr(FL_KV + team * 8 + i)) : "memory");
                    }
                    if (i == 1) {
                        flag_wait(flag_ptr(FL_LN + b1), ep1 * 128u);
                        mbar_arrive(misc + BAR_DEP + 8 * (D_LN + 1));
                    }
                    flag_wait(flag_ptr(FL_KV + team * 8 + i), ep1 * 16u);
                    mbar_arrive(misc + BAR_DEP + 8 * (D_KV + i));
                    if (i == 1) {
#pragma unroll 1
                        for (int j = 0; j < 2; j++) {
                            mbar_wait(misc + BAR_PROG + 8 * j, 0);
                            asm volatile("red.relaxed.gpu.global.add.u32 [%0], 1;" ::"l"(flag_ptr(FL_WAR + 2 * team + j)) : "memory");
                            flag_wait(flag_ptr(FL_WAR + 2 * team + j), ep1 * 8u);
                            mbar_arrive(misc + BAR_DEP + 8 * (D_WAR + j));
                        }
                    }
                }
            }
            __syncwarp();
            const unsigned* cf = flag_ptr(FL_CTX + op_head(lane & 15, kap) * 8 + u3);
#pragma unroll 1
            for (int half = 0; half < 2; half++) {
                if (half) mbar_wait(misc + BAR_EV + 8 * (EV_CTX + 3), 0);
                bool done = (lane >> 3) != half;
                for (int spin = 0; spin < 4000000; spin++) {
                    if (!done) {
                        unsigned v;
                        asm volatile("ld.acquire.gpu.global.u32 %0, [%1];" : "=r"(v) : "l"(cf) : "memory");
                        if ((int)(v - ep1 * 4u) >= 0) { mbar_arrive(misc + BAR_DEP + 8 * (D_CTX + lane)); done = true; }
                    }
                    if (__all_sync(0xffffffffu, done)) break;
                    __nanosleep(64);
                }
            }
            if (lane == 0) {
                flag_wait(flag_ptr(FL_MOE_DONE), ep1);
                int4 s0 = __ldcg(reinterpret_cast<const int4*>(g_sel)), s1 = __ldcg(reinterpret_cast<const int4*>(g_sel) + 1);
                asm volatile("st.shared.v4.u32 [%0], {%1,%2,%3,%4};" ::"r"(misc + MISC_SEL), "r"(s0.x), "r"(s0.y), "r"(s0.z), "r"(s0.w) : "memory");
                asm volatile("st.shared.v4.u32 [%0], {%1,%2,%3,%4};" ::"r"(misc + MISC_SEL + 16), "r"(s1.x), "r"(s1.y), "r"(s1.z), "r"(s1.w) : "memory");
                mbar_arrive(misc + BAR_SEL);
            }
        } else {
            const int w = warp - 1;
            if (lane == 0) {
                const uint32_t eb = misc + BAR_EV + w * 8 * NEV;
#pragma unroll 1
                for (int i = 0; i < 6; i++) {
                    const bool kv = (i >> 1) == 1;
                    const int ci = i < 2 ? i : i - 2;
                    mbar_wait(eb + 8 * (kv ? EV_KV + i : EV_CTX + ci), 0);
                    if (i == 1) {
                        asm volatile("cp.async.bulk.global.shared::cta.bulk_group [%0], [%1], 16384;"
                                     ::"l"(g_ctx + (size_t)(team * 32 + 4 * b1 + (w ? 3 - (rank ^ 1) : rank ^ 1)) * 16384),
                                       "r"(ring + slot_of(78) * SLOT_BYTES + w * 16384) : "memory");
                        asm volatile("cp.async.bulk.commit_group;" ::: "memory");
                        asm volatile("cp.async.bulk.wait_group.read 0;" ::: "memory");
                        mbar_arrive_cluster(mapa(misc + BAR_EMPTY + 8 * slot_of(78), 0), 4);
                        mbar_arrive_cluster(mapa(misc + BAR_EMPTY + 8 * slot_of(78), 1), 4);
                        asm volatile("cp.async.bulk.wait_group 0;" ::: "memory");
                        fence_async_global();
                    }
                    flag_signal(flag_ptr(kv ? FL_KV + team * 8 + i : FL_CTX + (team + 16 * (ci >> 1)) * 8 + ((ci & 1) ? b1 : b0)));
                }
            }
            __syncwarp();
            mbar_wait(misc + BAR_PROG + 16, 0);
            const int row = (2 * u3 + rank) * 128 + 64 * w + perm32(16 * (lane >> 3) + 8 * kap + (lane & 7));
#pragma unroll
            for (int i = 0; i < 10; i++) asm volatile("prefetch.global.L2 [%0];" ::"l"(P.x + (size_t)row * DM + 160 * s3 + 16 * i));
            asm volatile("prefetch.global.L2 [%0];" ::"l"(g_stats + row));
            mbar_wait(misc + BAR_EV + w * 8 * NEV + 8 * EV_END, 0);
        }
        }
    } else {
        asm volatile("setmaxnreg.inc.sync.aligned.u32 232;");
        Ctx c;
        c.ring = ring; c.misc = misc; c.w = wg - 1; c.warp = __shfl_sync(0xffffffffu, (tid >> 5) & 3, 0); c.lane = tid & 31;
        c.rel = mapa(misc, tid & 1);
        const int w = c.w;
        if (w == 1) bar_arrive(1, 256);
        prefetch_w(2); prefetch_w(3);
        Cur cur = cur_at(0);
        float o[64], inv[2];
        unsigned char* out[2];
        uint32_t wf[128];
        Cur cw = cur;
        auto load_wchunk = [&](auto CH) {
            constexpr int ch = decltype(CH)::value;
            mbar_wait_hot(misc + BAR_FULL + 8 * cw.slot, cw.ph);
            const uint32_t z = load_afrag<8, 32 * ch>(wf, ring + cw.slot * SLOT_BYTES + w * 16384, c);
            release(c, BAR_EMPTY + 8 * cw.slot + z, 1);
            cw.adv(); cw.adv();
        };
#pragma unroll
        for (int i = 32; i < 64; i++) wf[i] = 0u;
        load_wchunk(IC<0>{});
#pragma unroll 1
        for (int v = 0; v < 2; v++) {
        {
            float (&acc)[64] = o;
#pragma unroll
            for (int i = 64; i < 128; i++) wf[i] = 0u;
            cur.adv();
            inv[0] = inv[1] = rank ? 1.0f : SM_SCALE;
#pragma unroll 1
            for (int t = 0; t < 4; t++) {
                uint32_t last = 0;
                token_wait(w);
                undef_regs(acc);
                auto chunk = [&](auto CH) {
                    constexpr int ch = decltype(CH)::value;
                    mbar_wait_hot(misc + BAR_FULL + 8 * cur.slot, cur.ph);
                    uint64_t d = mkdesc(ring + cur.slot * SLOT_BYTES, 16, 1024, 1);
                    wg_fence();
#pragma unroll
                    for (int ks = 0; ks < 8; ks++)
                        wgmma_rs_n128_ta0_tb0(acc, wf[32 * ch + 4 * ks], wf[32 * ch + 4 * ks + 1], wf[32 * ch + 4 * ks + 2], wf[32 * ch + 4 * ks + 3],
                                              d + (ks >> 2) * 1024 + (ks & 3) * 2, (ch | ks) != 0);
                    wg_commit();
                    if (ch == 3 || (ch < 2 && t == 0)) token_pass(w);
                    if constexpr (ch == 0) {
                        if (t == 0) {
                            if (v) {
                                release(c, BAR_EMPTY + 8 * slot_of(76), 1);
                                asm volatile("fence.proxy.async.shared::cta;" ::: "memory");
                                signal_event(c, EV_CTX + 1);
                                load_wchunk(IC<2>{});
                            } else load_wchunk(IC<1>{});
                        }
                    }
                    if constexpr (ch == 1) { if (t == 0 && !v) load_wchunk(IC<2>{}); }
                    if constexpr (ch == 2) { if (t == 0 && !(w | v)) load_wchunk(IC<3>{}); }
                    if (ch > 0) { wg_wait<1>(); release(c, BAR_EMPTY + 8 * last, 1); }
                    last = cur.slot;
                    cur.adv();
                    if (ch < 3 && t == 0) cur.adv();
                    if constexpr (ch == 1) { if (t == 0 && (w | v)) load_wchunk(IC<3>{}); }
                    if (ch < 2 && t == 0) token_wait(w);
                };
                chunk(IC<0>{}); chunk(IC<1>{}); chunk(IC<2>{}); chunk(IC<3>{});
                wg_wait<0>();
                release(c, BAR_EMPTY + 8 * last, 1);
                fence_regs(acc);
                tile_out(out, (rank ? g_V : g_K) + (size_t)(team * 32 + 2 * (kv_tile(t) + k)) * 16384, 64 * w, rank, c);
                if (t == 3 && w) break;
#pragma unroll
                for (int i = 0; i < 4; i++) store_pair(acc, i, out, 8192, inv);
                if (t >= 2) signal_event(c, EV_KV + 2 * v + t - 2);
            }
        }
        {
            uint32_t q[32], p[32];
            float m[2], l[2];
#pragma unroll
            for (int i = 0; i < 32; i++) p[i] = 0u;
            l[0] = l[1] = 1.f;
            int pv_acc = 1, pv_mode = 2;
#pragma unroll 1
            for (int r = 0; r < 2; r++) {
                const int heavy = 1 ^ r ^ w;
                const int half = 1 ^ heavy ^ rank ^ r;
                int left = 2 * (r ? b1 : b0) + 1 + heavy;
                Cur ck, cv = cur;
                {
                    float s[64];
                    if (r) cur.adv();
                    mbar_wait_hot(misc + BAR_FULL + 8 * cv.slot, cv.ph);
                    token_wait(w);
                    issue_pv(o, p, ring + cv.slot * SLOT_BYTES, pv_acc, pv_mode);
                    undef_regs(s);
                    uint32_t prev;
                    auto qchunk = [&](int acc) {
                        mbar_wait_hot(misc + BAR_FULL + 8 * cur.slot, cur.ph);
                        const uint64_t da = mkdesc(ring + cur.slot * SLOT_BYTES + w * 8192, 16, 1024, 1);
                        const uint64_t db = mkdesc(ring + cur.slot * SLOT_BYTES + 16384, 8192, 1024, 1);
                        wg_fence();
#pragma unroll
                        for (int ks = 0; ks < 4; ks++) wgmma_ss_n128_ta0_tb1(s, da + 2 * ks, db + 128 * ks, ks ? 1 : acc);
                        wg_commit();
                    };
                    qchunk(0);
                    prev = cur.slot; cur.adv();
                    token_pass(w);
                    if (r) {
                        row_inv(l, inv);
                        tile_out(out, g_ctx + (size_t)((team + 16 * v) * 32 + 4 * b0 + (w ? rank : 3 - rank)) * 16384, 0, 0, c);
                    }
                    const int epi = r | w, hs = r ? 4096 : 8192;
                    const int hold = heavy ? -10 : half ? 6 : 8;
#pragma unroll
                    for (int kc = 1; kc < 10; kc++) {
                        if (kc >= 6 && (kc == hold || kc == hold + 2)) token_wait(w);
                        qchunk(1);
                        if (kc > 6 && kc == hold + 1) token_pass(w);
                        if (kc == 9 && heavy) { token_wait(w); token_pass(w); }
                        wg_wait<1>();
                        release(c, BAR_EMPTY + 8 * prev, 1);
                        prev = cur.slot; cur.adv();
                        if (kc == 1) { fence_regs(o); if (r) release(c, BAR_EMPTY + 8 * cv.slot, 1); }
                        if (kc <= 4 && epi) {
                            store_pair(o, kc - 1, out, hs, inv);
                            if (kc == 4) signal_event(c, r ? EV_CTX + 2 * v : EV_KV + 2 * v + 1);
                        }
                    }
                    if (!heavy) cur.adv();
                    ck = cur;
                    cur.adv();
                    if (!heavy) cur.adv();
                    wg_wait<0>();
                    release(c, BAR_EMPTY + 8 * prev, 1);
                    fence_regs(s);
#pragma unroll
                    for (int i = 0; i < 32; i++) q[i] = pack_bf16(s[2 * i], s[2 * i + 1]);
                }
                int first = 1, gen = 0;
                uint32_t pv_cnt = 0;
                l[0] = l[1] = m[0] = m[1] = 0.f;
                mbar_wait_hot(misc + BAR_FULL + 8 * ck.slot, ck.ph);
                auto diagonal = [&](auto NJC) {
                    constexpr int NJ = decltype(NJC)::value;
                    if (NJ == 16 || heavy) token_wait(w);
                    float sd[4 * NJ];
                    undef_regs(sd);
                    if constexpr (NJ == 8) issue_qk_half(sd, q, ring + ck.slot * SLOT_BYTES); else issue_qk(sd, q, ring + ck.slot * SLOT_BYTES);
                    token_pass(w);
                    wg_wait<0>();
                    fence_regs(sd);
                    mask_diag<NJ - 8>(sd, c);
                    float l0 = 0.f, l1 = 0.f;
#pragma unroll
                    for (int j = 0; j < NJ; j++) {
#pragma unroll
                        for (int e = 0; e < 4; e++) ex2v(sd[4 * j + e]);
                        l0 += sd[4 * j] + sd[4 * j + 1]; l1 += sd[4 * j + 2] + sd[4 * j + 3];
                    }
#pragma unroll
                    for (int i = 0; i < 2 * NJ; i++) p[i] = pack_bf16(sd[2 * i], sd[2 * i + 1]);
                    const int lim = NJ == 8 ? mask_lim(c) : 0;
                    const bool bad = __any_sync(0xffffffffu, !(l0 <= SAFE_SUM && l1 <= SAFE_SUM && (l0 >= 1.0f / SAFE_SUM || lim < 0) &&
                                                               (l1 >= 1.0f / SAFE_SUM || lim < -2)));
                    if (!bad) { l[0] = l0; l[1] = l1; }
                    return bad;
                };
#pragma unroll 1
                while (true) {
                    float s[64];
                    if (first) {
                        --left;
                        if (half ? diagonal(IC<8>{}) : diagonal(IC<16>{})) goto redo;
                        if (left == 0) goto tail;
                        release(c, BAR_EMPTY + 8 * ck.slot, 1 + heavy);
                        pv_acc = 0; pv_mode = half; pv_cnt = 1 + heavy; first = 0;
                        ck = cur; cur.adv(); cv = cur; cur.adv();
                        mbar_wait_hot(misc + BAR_FULL + 8 * ck.slot, ck.ph);
                    }
#pragma unroll 1
                    while (true) {
                        token_wait(w);
                        undef_regs(s);
                        issue_qk(s, q, ring + ck.slot * SLOT_BYTES);
                        Cur nck = cur, ncv = cur, ncur;
                        ncv.adv(); ncur = ncv; ncur.adv();
                        --left;
                        mbar_wait_hot(misc + BAR_FULL + 8 * cv.slot, cv.ph);
                        issue_pv(o, p, ring + cv.slot * SLOT_BYTES, pv_acc, pv_mode & 1);
                        token_pass(w);
                        wg_wait<1>();
                        fence_regs(s);
                        constexpr int JB = 11;
                        float l0 = l[0], l1 = l[1];
                        if (!gen) {
#pragma unroll
                            for (int j = 0; j < JB; j++) {
#pragma unroll
                                for (int e = 0; e < 4; e++) ex2v(s[4 * j + e]);
                                if (j < JB - 1) { l0 += s[4 * j] + s[4 * j + 1]; l1 += s[4 * j + 2] + s[4 * j + 3]; }
                            }
                        }
                        wg_wait<0>();
                        fence_regs(o);
                        if (gen) goto general;
#pragma unroll
                        for (int j = JB - 1; j < 16; j++) {
                            if (j >= JB) {
#pragma unroll
                                for (int e = 0; e < 4; e++) ex2v(s[4 * j + e]);
                            }
                            l0 += s[4 * j] + s[4 * j + 1]; l1 += s[4 * j + 2] + s[4 * j + 3];
                        }
#pragma unroll
                        for (int i = 0; i < 32; i++) p[i] = pack_bf16(s[2 * i], s[2 * i + 1]);
                        if (__any_sync(0xffffffffu, !(l0 <= SAFE_SUM && l1 <= SAFE_SUM))) goto redo;
                        l[0] = l0; l[1] = l1;
                        if (left == 0) goto tail;
                        release(c, BAR_EMPTY + 8 * ck.slot, 1);
                        release(c, BAR_EMPTY + 8 * cv.slot, pv_cnt);
                        pv_acc = 1; pv_mode = 0; pv_cnt = 1;
                        ck = nck; cv = ncv; cur = ncur;
                        mbar_wait_hot(misc + BAR_FULL + 8 * ck.slot, ck.ph);
                    }
                redo:
                    recompute_scores(s, q, ring + ck.slot * SLOT_BYTES, c);
                    if (first) { mask_any(s, half ^ 1, c); m[0] = m[1] = -INFINITY; }
                    gen = 1;
                general:
                    {
                        float mx[2], alpha[2];
                        row_max<16>(s, mx);
#pragma unroll
                        for (int i = 0; i < 2; i++) {
                            mx[i] = fmaxf(mx[i], m[i]);
                            alpha[i] = ex2(m[i] - mx[i]);
                            m[i] = mx[i];
                            l[i] *= alpha[i];
                        }
                        exp_sum<16, true>(s, m, l[0], l[1]);
#pragma unroll
                        for (int i = 0; i < 64; i++) o[i] *= alpha[(i >> 1) & 1];
#pragma unroll
                        for (int i = 0; i < 32; i++) p[i] = pack_bf16(s[2 * i], s[2 * i + 1]);
                    }
                tail:
                    release(c, BAR_EMPTY + 8 * ck.slot, 1 + (first & heavy));
                    if (pv_cnt) release(c, BAR_EMPTY + 8 * cv.slot, pv_cnt);
                    pv_acc = first ^ 1; pv_mode = first & half; pv_cnt = 1 + (first & heavy); first = 0;
                    if (left == 0) break;
                    ck = cur; cur.adv(); cv = cur; cur.adv();
                    mbar_wait_hot(misc + BAR_FULL + 8 * ck.slot, ck.ph);
                }
            }
            mbar_wait_hot(misc + BAR_FULL + 8 * cur.slot, cur.ph);
            token_wait(w);
            issue_pv(o, p, ring + cur.slot * SLOT_BYTES, 1, 0);
            if (w == 0 || v == 0) token_pass(w);
            const uint32_t vslot = cur.slot;
            cur.adv();
            row_inv(l, inv);
            if (v) {
                wg_wait<0>();
                release(c, BAR_EMPTY + 8 * vslot, 1);
                fence_regs(o);
                tile_out(out, g_ctx + (size_t)((team + 16) * 32 + 4 * b1 + (w ? 3 - (rank ^ 1) : rank ^ 1)) * 16384, 0, 0, c);
#pragma unroll
                for (int i = 0; i < 64; i++) wf[i] = 0u;
                continue;
            }
            cw = cur_at(80);
            mbar_wait_hot(misc + BAR_FULL + 8 * slot_of(76), cur_at(76).ph);
            mbar_wait_hot(misc + BAR_FULL + 8 * slot_of(78), cur_at(78).ph);
            load_afrag<8, 32>(wf, ring + slot_of(78) * SLOT_BYTES + w * 16384, c);
            load_afrag<8, 0>(wf, ring + slot_of(76) * SLOT_BYTES + w * 16384, c);
            asm volatile("{\n.reg .pred p;\nsetp.eq.u32 p, %0, 0;\n@p bar.sync 4, 128;\n@!p bar.sync 5, 128;\n}\n" ::"r"(w) : "memory");
            wg_wait<0>();
            release(c, BAR_EMPTY + 8 * vslot, 1);
            fence_regs(o);
            {
                const uint32_t base = ring + slot_of(78) * SLOT_BYTES + w * 16384 + (16 * c.warp + (c.lane >> 2)) * 64 + (((c.lane ^ (c.lane >> 3)) & 3) << 4);
#pragma unroll
                for (int i = 0; i < 2; i++)
#pragma unroll
                    for (int qq = 0; qq < 4; qq++)
                        asm volatile("st.shared.v4.b32 [%0], {%1,%2,%3,%4};" ::"r"(base + qq * 4096 + i * 512),
                                     "r"(pack_bf16(o[16 * qq + 2 * i] * inv[i], o[16 * qq + 2 * i + 1] * inv[i])),
                                     "r"(pack_bf16(o[16 * qq + 4 + 2 * i] * inv[i], o[16 * qq + 4 + 2 * i + 1] * inv[i])),
                                     "r"(pack_bf16(o[16 * qq + 8 + 2 * i] * inv[i], o[16 * qq + 8 + 2 * i + 1] * inv[i])),
                                     "r"(pack_bf16(o[16 * qq + 12 + 2 * i] * inv[i], o[16 * qq + 12 + 2 * i + 1] * inv[i])) : "memory");
            }
        }
        }
        {
            float acc[80];
            undef_regs(acc);
            int st = 0, prev = 0; uint32_t ph3 = 0;
            auto op_stage = [&](int i) {
                mbar_wait_hot(misc + BAR_FULL3 + 8 * st, ph3);
                uint32_t base = ring + st * ST3_BYTES;
                uint64_t da = mkdesc(base + w * 8192, 16, 512, 2);
                uint64_t db = mkdesc(base + 16384, 2048, 512, 2);
                wg_fence();
#pragma unroll
                for (int k = 0; k < 4; k++) wgmma_ss_n160_ta0_tb1(acc, da + (k >> 1) * 256 + 2 * (k & 1), db + (k >> 1) * 640 + (k & 1) * 64, k ? 1 : i);
                wg_commit();
                if (i > 0) { wg_wait<1>(); if (i <= 32 - NST3) release(c, BAR_EMPTY3 + 8 * prev, 1); }
                prev = st;
                if (++st == NST3) { st = 0; ph3 ^= 1; }
            };
#pragma unroll
            for (int i = 0; i < 4; i++) { op_stage(i); store_pair(o, i, out, 4096, inv); }
            signal_event(c, EV_CTX + 3);
            const int split = w ? 32 - OP_HOLD : RES_AT;
#pragma unroll 1
            for (int i = 4; i < split; i++) op_stage(i);
            mbar_wait(misc + BAR_SEL, 0);
            const uint32_t tag = lds32(misc + MISC_EPOCH) & 1;
            const int g = c.lane >> 2, t = c.lane & 3;
            const int row = (2 * u3 + rank) * 128 + 64 * w + perm32(16 * c.warp + 8 * kap + g);
            const int col = 160 * s3 + 8 * t;
            int sel = -1;
#pragma unroll
            for (int i = 0; i < TOPC; i++) if ((int)lds32(misc + MISC_SEL + 4 * i) == row) sel = i;
            const int t256 = tid - 128;
            uint4* sendp = g_part + (size_t)cta * 2560 + t256;
            if (c.lane >= 30) stg128(sendp + 9 * 256, tag ^ 1, tag ^ 1, tag ^ 1, tag ^ 1);
            uint4 xv[5], bv[5];
#pragma unroll
            for (int i = 0; i < 5; i++) xv[i] = ldg128(P.x + (size_t)row * DM + col + 32 * i);
            uint2 stat;
            asm volatile("ld.global.cg.v2.b32 {%0,%1}, [%2];" : "=r"(stat.x), "=r"(stat.y) : "l"(g_stats + row) : "memory");
#pragma unroll
            for (int i = 0; i < 5; i++) {
                uint32_t xx[4] = {xv[i].x, xv[i].y, xv[i].z, xv[i].w};
#pragma unroll
                for (int e = 0; e < 4; e++) {
                    asm("sub.rn.bf16x2 %0, %0, %1;" : "+r"(xx[e]) : "r"(stat.x));
                    xx[e] = pack_bf16(bf_lo(xx[e]) * __uint_as_float(stat.y), bf_hi(xx[e]) * __uint_as_float(stat.y));
                }
                bv[i] = make_uint4(xx[0], xx[1], xx[2], xx[3]);
            }
            if (sel >= 0) {
#pragma unroll
                for (int i = 0; i < 5; i++) bv[i] = ldg128(g_brow + sel * DM + col + 32 * i);
            }
#pragma unroll
            for (int i = 0; i < 5; i++) asm volatile("" : "+r"(bv[i].x), "+r"(bv[i].y), "+r"(bv[i].z), "+r"(bv[i].w));
            if (w) bar_sync(4, 256);
#pragma unroll 1
            for (int i = split; i < 32; i++) op_stage(i);
            if (!w) bar_arrive(4, 256);
            wg_wait<0>();
            fence_regs(acc);
            float keep[40];
#pragma unroll
            for (int j = 0; j < 10; j++) {
                uint32_t v0 = __float_as_uint(kap ? acc[8 * j + 0] : acc[8 * j + 2]), v1 = __float_as_uint(kap ? acc[8 * j + 1] : acc[8 * j + 3]);
                uint32_t v2 = __float_as_uint(kap ? acc[8 * j + 4] : acc[8 * j + 6]), v3 = __float_as_uint(kap ? acc[8 * j + 5] : acc[8 * j + 7]);
                asm volatile("st.relaxed.gpu.global.v4.b32 [%0], {%1,%2,%3,%4};" ::"l"(sendp + j * 256),
                             "r"((v0 & ~1u) | tag), "r"((v1 & ~1u) | tag), "r"((v2 & ~1u) | tag), "r"((v3 & ~1u) | tag) : "memory");
                keep[4 * j + 0] = kap ? acc[8 * j + 2] : acc[8 * j + 0]; keep[4 * j + 1] = kap ? acc[8 * j + 3] : acc[8 * j + 1];
                keep[4 * j + 2] = kap ? acc[8 * j + 6] : acc[8 * j + 4]; keep[4 * j + 3] = kap ? acc[8 * j + 7] : acc[8 * j + 5];
            }
            signal_event(c, EV_END);
            const uint4* recvp = g_part + (size_t)partner * 2560 + t256;
            uint4 rv[10];
            int spins = 0;
            while (true) {
                uint32_t v;
                asm volatile("ld.relaxed.gpu.global.b32 %0, [%1];" : "=r"(v) : "l"(recvp + 9 * 256 + (31 - c.lane)) : "memory");
                if (__all_sync(0xffffffffu, (v & 1u) == tag) || ++spins > 2000000) break;
            }
            while (true) {
                uint32_t bad = 0u;
#pragma unroll
                for (int j = 0; j < 10; j++) {
                    asm volatile("ld.relaxed.gpu.global.v4.b32 {%0,%1,%2,%3}, [%4];"
                                 : "=r"(rv[j].x), "=r"(rv[j].y), "=r"(rv[j].z), "=r"(rv[j].w) : "l"(recvp + j * 256) : "memory");
                }
#pragma unroll
                for (int j = 0; j < 10; j++) {
                    rv[j].x ^= tag; rv[j].y ^= tag; rv[j].z ^= tag; rv[j].w ^= tag;
                    bad |= rv[j].x | rv[j].y | rv[j].z | rv[j].w;
                }
                if (__all_sync(0xffffffffu, (bad & 1u) == 0) || ++spins > 2000000) break;
            }
            uint32_t pk[20];
#pragma unroll
            for (int j = 0; j < 10; j++) {
                pk[2 * j] = pack_bf16(keep[4 * j] + __uint_as_float(rv[j].x), keep[4 * j + 1] + __uint_as_float(rv[j].y));
                pk[2 * j + 1] = pack_bf16(keep[4 * j + 2] + __uint_as_float(rv[j].z), keep[4 * j + 3] + __uint_as_float(rv[j].w));
            }
#pragma unroll
            for (int i = 0; i < 5; i++) {
                uint32_t a0 = pk[4 * i], a1 = pk[4 * i + 1], a2 = pk[4 * i + 2], a3 = pk[4 * i + 3];
                uint32_t x0 = (t & 1) ? a0 : a1, x1 = (t & 1) ? a2 : a3;
                x0 = __shfl_xor_sync(0xffffffffu, x0, 1); x1 = __shfl_xor_sync(0xffffffffu, x1, 1);
                if (t & 1) { a0 = x0; a2 = x1; } else { a1 = x0; a3 = x1; }
                x0 = (t & 2) ? a0 : a2; x1 = (t & 2) ? a1 : a3;
                x0 = __shfl_xor_sync(0xffffffffu, x0, 2); x1 = __shfl_xor_sync(0xffffffffu, x1, 2);
                if (t & 2) { a0 = x0; a1 = x1; } else { a2 = x0; a3 = x1; }
                uint32_t av[4] = {a0, a1, a2, a3};
                uint32_t xx[4] = {xv[i].x, xv[i].y, xv[i].z, xv[i].w}, bb[4] = {bv[i].x, bv[i].y, bv[i].z, bv[i].w};
                uint32_t ov[4];
#pragma unroll
                for (int e = 0; e < 4; e++) {
                    asm("add.rn.bf16x2 %0, %1, %2;" : "=r"(ov[e]) : "r"(xx[e]), "r"(av[e]));
                    asm("add.rn.bf16x2 %0, %0, %1;" : "+r"(ov[e]) : "r"(bb[e]));
                }
                stg128(P.out + (size_t)row * DM + col + 32 * i, ov[0], ov[1], ov[2], ov[3]);
            }
        }
    }
}

typedef CUresult (*EncodeFn)(CUtensorMap*, CUtensorMapDataType, cuuint32_t, void*, const cuuint64_t*, const cuuint64_t*, const cuuint32_t*,
                             const cuuint32_t*, CUtensorMapInterleave, CUtensorMapSwizzle, CUtensorMapL2promotion, CUtensorMapFloatOOBfill);

void make_map2d(EncodeFn enc, CUtensorMap* tm, const void* p, uint64_t cols, uint64_t rows, uint32_t box_rows = 128) {
    cuuint64_t gd[2] = {cols, rows}, gs[1] = {cols * 2};
    cuuint32_t box[2] = {64, box_rows}, es[2] = {1, 1};
    enc(tm, CU_TENSOR_MAP_DATA_TYPE_BFLOAT16, 2, const_cast<void*>(p), gd, gs, box, es, CU_TENSOR_MAP_INTERLEAVE_NONE,
        CU_TENSOR_MAP_SWIZZLE_128B, CU_TENSOR_MAP_L2_PROMOTION_L2_128B, CU_TENSOR_MAP_FLOAT_OOB_FILL_NONE);
}

void make_map3d(EncodeFn enc, CUtensorMap* tm, const void* p, uint64_t cols, uint64_t rows, uint32_t bw, uint32_t nb) {
    cuuint64_t gd[3] = {bw, rows, cols / bw}, gs[2] = {cols * 2, bw * 2};
    cuuint32_t box[3] = {bw, 32, nb}, es[3] = {1, 1, 1};
    enc(tm, CU_TENSOR_MAP_DATA_TYPE_BFLOAT16, 3, const_cast<void*>(p), gd, gs, box, es, CU_TENSOR_MAP_INTERLEAVE_NONE,
        bw == 64 ? CU_TENSOR_MAP_SWIZZLE_128B : CU_TENSOR_MAP_SWIZZLE_64B, CU_TENSOR_MAP_L2_PROMOTION_L2_128B, CU_TENSOR_MAP_FLOAT_OOB_FILL_NONE);
}

}

extern "C" void kernel_launch(void* const* d_in, const int* in_sizes, int n_in, void* d_out, int out_size) {
    (void)in_sizes; (void)n_in; (void)out_size;
    static EncodeFn enc = nullptr;
    if (!enc) {
        void* fn = nullptr;
        cudaDriverEntryPointQueryResult qr;
        cudaGetDriverEntryPoint("cuTensorMapEncodeTiled", &fn, cudaEnableDefault, &qr);
        enc = (EncodeFn)fn;
        cudaFuncSetAttribute(fused_kernel, cudaFuncAttributeMaxDynamicSharedMemorySize, SMEM_BYTES);
    }
    CUtensorMap tmC, tmWk, tmWv, tmWq, tmWo, tmG, tmU, tmD;
    make_map2d(enc, &tmC, d_in[1], DC, SEQ);
    make_map2d(enc, &tmWq, d_in[2], 4096, DM, 64);
    make_map2d(enc, &tmWk, d_in[3], 4096, DC);
    make_map2d(enc, &tmWv, d_in[4], 4096, DC);
    make_map3d(enc, &tmWo, d_in[5], DM, 4096, 32, 5);
    make_map3d(enc, &tmG, d_in[8], FF, DM, 64, 7);
    make_map3d(enc, &tmU, d_in[9], FF, DM, 64, 7);
    make_map3d(enc, &tmD, d_in[10], DM, FF, 64, 10);
    Params P;
    P.x = (const __nv_bfloat16*)d_in[0];
    P.c = (const __nv_bfloat16*)d_in[1];
    P.wk = (const __nv_bfloat16*)d_in[3];
    P.wv = (const __nv_bfloat16*)d_in[4];
    P.wo = (const __nv_bfloat16*)d_in[5];
    P.wr = (const __nv_bfloat16*)d_in[7];
    P.out = (__nv_bfloat16*)d_out;
    fused_kernel<<<132, 384, SMEM_BYTES>>>(tmC, tmWk, tmWv, tmWq, tmWo, tmG, tmU, tmD, P);
}
```

```cpp
#include <cuda_runtime.h>
#include <cuda_bf16.h>
#include <cuda.h>
#include <stdint.h>

namespace {

constexpr int SEQ = 2048, NH = 32, DM = 640, DC = 512, FF = 1728, TOPC = 8;
constexpr int NSLOT = 7, SLOT_BYTES = 32768;
constexpr int NST3 = 6, ST3_BYTES = 36864;
constexpr int RING_BYTES = NSLOT * SLOT_BYTES;
constexpr int SMEM_BYTES = RING_BYTES + 3072;
constexpr int OP_PF = 8, PF_START = 9, LATE_AT = 18, RES_AT = 23, OP_HOLD = 4;

constexpr int BAR_FULL = 0  , BAR_EMPTY = 64  , BAR_FULL3 = 128  , BAR_EMPTY3 = 192  , BAR_DEP = 256  ,
              BAR_EV = 448  , BAR_PROG = 592  , BAR_SEL = 616, BAR_LN = 624,
              MISC_EPOCH = 640, MISC_SMID = 644  , MISC_SEL = 656, MISC_WR = 1024  ;
constexpr int D_LN = 0  , D_KV = 2  , D_WAR = 6  , D_CTX = 8  ;
constexpr int EV_KV = 0  , EV_CTX = 4  , EV_END = 8, NEV = 9;

constexpr int FL_MOE_CNT = 0, FL_MOE_DONE = 1, FL_LN = 16  , FL_KV = 32  , FL_CTX = 160  , FL_WAR = 416  , FL_TOTAL = 448;

__device__ __align__(1024) unsigned char g_K[16 * 32 * 16384];
__device__ __align__(1024) unsigned char g_V[16 * 32 * 16384];
__device__ __align__(1024) unsigned char g_ctx[NH * 32 * 16384];
__device__ __align__(1024) unsigned char g_xn[16 * 10 * 16384];
__device__ __align__(1024) uint4 g_part[128 * 10 * 256];
__device__ float g_router[SEQ];
__device__ uint2 g_stats[SEQ];
__device__ __align__(16) float g_moe_part[4 * TOPC * DM];
__device__ __align__(16) __nv_bfloat16 g_brow[TOPC * DM];
__device__ __align__(16) int g_sel[TOPC];
__device__ unsigned g_flags[FL_TOTAL * 8];
__device__ unsigned g_epoch;
__device__ unsigned g_roleq[130];
struct Params {
    const __nv_bfloat16 *x, *c, *wr, *wk, *wv, *wo;
    __nv_bfloat16* out;
};

__device__ __forceinline__ uint32_t smem_u32(const void* p) { return (uint32_t)__cvta_generic_to_shared(p); }
__device__ __forceinline__ void mbar_init(uint32_t bar, int cnt) { asm volatile("mbarrier.init.shared::cta.b64 [%0], %1;" ::"r"(bar), "r"(cnt)); }
__device__ __forceinline__ void mbar_expect_tx(uint32_t bar, uint32_t bytes) {
    asm volatile("mbarrier.arrive.expect_tx.shared::cta.b64 _, [%0], %1;" ::"r"(bar), "r"(bytes) : "memory");
}
__device__ __forceinline__ void mbar_arrive(uint32_t bar) { asm volatile("mbarrier.arrive.shared::cta.b64 _, [%0];" ::"r"(bar) : "memory"); }
__device__ __forceinline__ void mbar_arrive_cluster(uint32_t cluster_addr, uint32_t cnt) {
    asm volatile("mbarrier.arrive.shared::cluster.b64 _, [%0], %1;" ::"r"(cluster_addr), "r"(cnt) : "memory");
}
__device__ __forceinline__ uint32_t mapa(uint32_t addr, uint32_t cta) {
    uint32_t r; asm("mapa.shared::cluster.u32 %0, %1, %2;" : "=r"(r) : "r"(addr), "r"(cta)); return r;
}
__device__ __forceinline__ void mbar_wait(uint32_t bar, uint32_t parity) {
    asm volatile(
        "{\n.reg .pred p;\n.reg .u32 n;\n"
        "mov.u32 n, 0;\n"
        "LAB_WAIT:\n"
        "mbarrier.try_wait.parity.shared::cta.b64 p, [%0], %1, 100000;\n"
        "@p bra DONE;\n"
        "add.u32 n, n, 1;\n"
        "setp.lt.u32 p, n, 50000;\n"
        "@p bra LAB_WAIT;\n"
        "trap;\n"
        "DONE:\n}\n" ::"r"(bar), "r"(parity) : "memory");
}
__device__ __forceinline__ void mbar_wait_hot(uint32_t bar, uint32_t parity) {
    asm volatile("{\n.reg .pred p;\nLAB_WAIT:\nmbarrier.try_wait.parity.shared::cta.b64 p, [%0], %1;\n@!p bra LAB_WAIT;\n}\n" ::"r"(bar), "r"(parity) : "memory");
}
__device__ __forceinline__ void mbar_wait_sleep(uint32_t bar, uint32_t parity) {
    asm volatile("{\n.reg .pred p;\nLAB_WAIT:\nmbarrier.try_wait.parity.shared::cta.b64 p, [%0], %1, 100000;\n@!p bra LAB_WAIT;\n}\n" ::"r"(bar), "r"(parity) : "memory");
}
__device__ __forceinline__ void flag_wait(const unsigned* flag, unsigned target) {
    asm volatile(
        "{\n.reg .pred p;\n.reg .u32 n, v;\n.reg .s32 d;\n"
        "mov.u32 n, 0;\n"
        "LAB_WAIT:\n"
        "ld.acquire.gpu.global.u32 v, [%0];\n"
        "sub.s32 d, v, %1;\n"
        "setp.ge.s32 p, d, 0;\n"
        "@p bra DONE;\n"
        "nanosleep.u32 40;\n"
        "add.u32 n, n, 1;\n"
        "setp.lt.u32 p, n, 3000000;\n"
        "@p bra LAB_WAIT;\n"
        "trap;\n"
        "DONE:\n}\n" ::"l"(flag), "r"(target) : "memory");
}
__device__ __forceinline__ void flag_signal(unsigned* flag) {
    asm volatile("red.release.gpu.global.add.u32 [%0], 1;" ::"l"(flag) : "memory");
}
__device__ __forceinline__ void fence_async_global() { asm volatile("fence.proxy.async.global;" ::: "memory"); }
__device__ __forceinline__ unsigned* flag_ptr(int idx) { return g_flags + idx * 8; }

__device__ __forceinline__ uint64_t policy_stream() {
    uint64_t p; asm("createpolicy.fractional.L2::evict_first.b64 %0, 1.0;" : "=l"(p)); return p;
}
__device__ __forceinline__ void bulk_load(uint32_t dst, const void* src, uint32_t bytes, uint32_t bar) {
    asm volatile("cp.async.bulk.shared::cluster.global.mbarrier::complete_tx::bytes [%0], [%1], %2, [%3];"
                 ::"r"(dst), "l"(src), "r"(bytes), "r"(bar) : "memory");
}
__device__ __forceinline__ void bulk_load_mc(uint32_t dst, const void* src, uint32_t bytes, uint32_t bar) {
    asm volatile("cp.async.bulk.shared::cluster.global.mbarrier::complete_tx::bytes.multicast::cluster [%0], [%1], %2, [%3], %4;"
                 ::"r"(dst), "l"(src), "r"(bytes), "r"(bar), "h"((uint16_t)3) : "memory");
}
__device__ __forceinline__ void tma2d(uint32_t dst, const CUtensorMap* tm, int c0, int c1, uint32_t bar) {
    asm volatile("cp.async.bulk.tensor.2d.shared::cluster.global.mbarrier::complete_tx::bytes [%0], [%1, {%3, %4}], [%2];"
                 ::"r"(dst), "l"(tm), "r"(bar), "r"(c0), "r"(c1) : "memory");
}
__device__ __forceinline__ void tma2d_mc(uint32_t dst, const CUtensorMap* tm, int c0, int c1, uint32_t bar) {
    asm volatile("cp.async.bulk.tensor.2d.shared::cluster.global.mbarrier::complete_tx::bytes.multicast::cluster [%0], [%1, {%3, %4}], [%2], %5;"
                 ::"r"(dst), "l"(tm), "r"(bar), "r"(c0), "r"(c1), "h"((uint16_t)3) : "memory");
}
__device__ __forceinline__ void tma3d_mc(uint32_t dst, const CUtensorMap* tm, int c0, int c1, int c2, uint32_t bar) {
    asm volatile("cp.async.bulk.tensor.3d.shared::cluster.global.mbarrier::complete_tx::bytes.multicast::cluster [%0], [%1, {%3, %4, %5}], [%2], %6;"
                 ::"r"(dst), "l"(tm), "r"(bar), "r"(c0), "r"(c1), "r"(c2), "h"((uint16_t)3) : "memory");
}
__device__ __forceinline__ void tma3d(uint32_t dst, const CUtensorMap* tm, int c0, int c1, int c2, uint32_t bar) {
    asm volatile("cp.async.bulk.tensor.3d.shared::cluster.global.mbarrier::complete_tx::bytes.L2::cache_hint [%0], [%1, {%3, %4, %5}], [%2], %6;"
                 ::"r"(dst), "l"(tm), "r"(bar), "r"(c0), "r"(c1), "r"(c2), "l"(policy_stream()) : "memory");
}
__device__ __forceinline__ void tma2d_prefetch(const CUtensorMap* tm, int c0, int c1) {
    asm volatile("cp.async.bulk.prefetch.tensor.2d.L2.global [%0, {%1, %2}];" ::"l"(tm), "r"(c0), "r"(c1) : "memory");
}
__device__ __forceinline__ void tma3d_prefetch(const CUtensorMap* tm, int c0, int c1, int c2) {
    asm volatile("cp.async.bulk.prefetch.tensor.3d.L2.global [%0, {%1, %2, %3}];" ::"l"(tm), "r"(c0), "r"(c1), "r"(c2) : "memory");
}
__device__ __forceinline__ void l2_prefetch(const void* p, uint32_t bytes) {
    asm volatile("cp.async.bulk.prefetch.L2.global [%0], %1;" ::"l"(p), "r"(bytes) : "memory");
}
__device__ __forceinline__ bool elect_one() {
    uint32_t r; asm volatile("{\n.reg .pred p;\nelect.sync _|p, 0xffffffff;\nselp.u32 %0, 1, 0, p;\n}\n" : "=r"(r)); return r != 0;
}
__device__ __forceinline__ void wg_fence() { asm volatile("wgmma.fence.sync.aligned;" ::: "memory"); }
__device__ __forceinline__ void wg_commit() { asm volatile("wgmma.commit_group.sync.aligned;" ::: "memory"); }
template <int N> __device__ __forceinline__ void wg_wait() { asm volatile("wgmma.wait_group.sync.aligned %0;" ::"n"(N) : "memory"); }
__device__ __forceinline__ void bar_sync(int id, int n) { asm volatile("bar.sync %0, %1;" ::"r"(id), "r"(n) : "memory"); }
__device__ __forceinline__ void bar_arrive(int id, int n) { asm volatile("bar.arrive %0, %1;" ::"r"(id), "r"(n) : "memory"); }
__device__ __forceinline__ void token_wait(int w) {
    asm volatile("{\n.reg .pred p;\nsetp.eq.u32 p, %0, 0;\n@p bar.sync 1, 256;\n@!p bar.sync 2, 256;\n}\n" ::"r"(w) : "memory");
}
__device__ __forceinline__ void token_pass(int w) {
    asm volatile("{\n.reg .pred p;\nsetp.eq.u32 p, %0, 0;\n@p bar.arrive 2, 256;\n@!p bar.arrive 1, 256;\n}\n" ::"r"(w) : "memory");
}
template <int N> __device__ __forceinline__ void fence_regs(float (&a)[N]) {
#pragma unroll
    for (int i = 0; i < N; i++) asm volatile("" : "+f"(a[i])::"memory");
}
template <int N> __device__ __forceinline__ void undef_regs(float (&a)[N]) {
#pragma unroll
    for (int i = 0; i < N; i++) asm volatile("" : "=f"(a[i]));
}
__device__ __forceinline__ void ldsm4t(uint32_t& r0, uint32_t& r1, uint32_t& r2, uint32_t& r3, uint32_t addr) {
    asm volatile("ldmatrix.sync.aligned.m8n8.x4.trans.shared.b16 {%0,%1,%2,%3}, [%4];"
                 : "=r"(r0), "=r"(r1), "=r"(r2), "=r"(r3) : "r"(addr) : "memory");
}
__device__ __forceinline__ uint32_t pack_bf16(float lo, float hi) {
    uint32_t r; asm("cvt.rn.bf16x2.f32 %0, %1, %2;" : "=r"(r) : "f"(hi), "f"(lo)); return r;
}
__device__ __forceinline__ float bf_lo(uint32_t v) { return __uint_as_float(v << 16); }
__device__ __forceinline__ float bf_hi(uint32_t v) { return __uint_as_float(v & 0xffff0000u); }
__device__ __forceinline__ float bf_round(float v) { return __bfloat162float(__float2bfloat16_rn(v)); }
__device__ __forceinline__ float ex2(float v) { float r; asm("ex2.approx.ftz.f32 %0, %1;" : "=f"(r) : "f"(v)); return r; }
__device__ __forceinline__ void ex2v(float& v) { asm volatile("ex2.approx.ftz.f32 %0, %0;" : "+f"(v)); }
__device__ __forceinline__ float rcp_fast(float v) { float r; asm("rcp.approx.ftz.f32 %0, %1;" : "=f"(r) : "f"(v)); return r; }
__device__ __forceinline__ float sqrt_fast(float v) { float r; asm("sqrt.approx.ftz.f32 %0, %1;" : "=f"(r) : "f"(v)); return r; }
__device__ __forceinline__ void stg128(void* p, uint32_t a, uint32_t b, uint32_t c, uint32_t d) {
    asm volatile("st.global.v4.b32 [%0], {%1,%2,%3,%4};" ::"l"(p), "r"(a), "r"(b), "r"(c), "r"(d) : "memory");
}
__device__ __forceinline__ void stg128_hint(void* p, uint32_t a, uint32_t b, uint32_t c, uint32_t d, uint64_t pol) {
    asm volatile("st.global.L2::cache_hint.v4.b32 [%0], {%1,%2,%3,%4}, %5;" ::"l"(p), "r"(a), "r"(b), "r"(c), "r"(d), "l"(pol) : "memory");
}
__device__ __forceinline__ uint4 ldg128(const void* p) {
    uint4 v; asm volatile("ld.global.cg.v4.b32 {%0,%1,%2,%3}, [%4];" : "=r"(v.x), "=r"(v.y), "=r"(v.z), "=r"(v.w) : "l"(p) : "memory"); return v;
}
__device__ __forceinline__ uint64_t mkdesc(uint32_t addr, uint32_t lbo, uint32_t sbo, uint32_t swz) {
    uint32_t lo = ((addr & 0x3FFFF) >> 4) | ((lbo >> 4) << 16);
    uint32_t hi = (sbo >> 4) | (swz << 30);
    return ((uint64_t)hi << 32) | lo;
}
__device__ __forceinline__ int perm32(int v) { return (v & ~30) | ((v >> 2) & 6) | ((v << 2) & 24); }

__device__ __forceinline__ void wgmma_rs_n128_ta0_tb0(float (&d)[64], uint32_t a0, uint32_t a1, uint32_t a2, uint32_t a3, uint64_t descB, int scaleD) {
  asm volatile("{\n.reg .pred p;\nsetp.ne.b32 p, %69, 0;\n"
    "wgmma.mma_async.sync.aligned.m64n128k16.f32.bf16.bf16 "
    "{%0, %1, %2, %3, %4, %5, %6, %7, %8, %9, %10, %11, %12, %13, %14, %15, %16, %17, %18, %19, %20, %21, %22, %23, %24, %25, %26, %27, %28, %29, %30, %31, %32, %33, %34, %35, %36, %37, %38, %39, %40, %41, %42, %43, %44, %45, %46, %47, %48, %49, %50, %51, %52, %53, %54, %55, %56, %57, %58, %59, %60, %61, %62, %63}, "
    "{%64, %65, %66, %67}, %68, p, 1, 1, 0;\n}\n"
    : "+f"(d[0]), "+f"(d[1]), "+f"(d[2]), "+f"(d[3]), "+f"(d[4]), "+f"(d[5]), "+f"(d[6]), "+f"(d[7]), "+f"(d[8]), "+f"(d[9]), "+f"(d[10]), "+f"(d[11]), "+f"(d[12]), "+f"(d[13]), "+f"(d[14]), "+f"(d[15]), "+f"(d[16]), "+f"(d[17]), "+f"(d[18]), "+f"(d[19]), "+f"(d[20]), "+f"(d[21]), "+f"(d[22]), "+f"(d[23]), "+f"(d[24]), "+f"(d[25]), "+f"(d[26]), "+f"(d[27]), "+f"(d[28]), "+f"(d[29]), "+f"(d[30]), "+f"(d[31]), "+f"(d[32]), "+f"(d[33]), "+f"(d[34]), "+f"(d[35]), "+f"(d[36]), "+f"(d[37]), "+f"(d[38]), "+f"(d[39]), "+f"(d[40]), "+f"(d[41]), "+f"(d[42]), "+f"(d[43]), "+f"(d[44]), "+f"(d[45]), "+f"(d[46]), "+f"(d[47]), "+f"(d[48]), "+f"(d[49]), "+f"(d[50]), "+f"(d[51]), "+f"(d[52]), "+f"(d[53]), "+f"(d[54]), "+f"(d[55]), "+f"(d[56]), "+f"(d[57]), "+f"(d[58]), "+f"(d[59]), "+f"(d[60]), "+f"(d[61]), "+f"(d[62]), "+f"(d[63])
    : "r"(a0), "r"(a1), "r"(a2), "r"(a3), "l"(descB), "r"(scaleD));
}
__device__ __forceinline__ void wgmma_rs_n128_ta0_tb1(float (&d)[64], uint32_t a0, uint32_t a1, uint32_t a2, uint32_t a3, uint64_t descB, int scaleD) {
  asm volatile("{\n.reg .pred p;\nsetp.ne.b32 p, %69, 0;\n"
    "wgmma.mma_async.sync.aligned.m64n128k16.f32.bf16.bf16 "
    "{%0, %1, %2, %3, %4, %5, %6, %7, %8, %9, %10, %11, %12, %13, %14, %15, %16, %17, %18, %19, %20, %21, %22, %23, %24, %25, %26, %27, %28, %29, %30, %31, %32, %33, %34, %35, %36, %37, %38, %39, %40, %41, %42, %43, %44, %45, %46, %47, %48, %49, %50, %51, %52, %53, %54, %55, %56, %57, %58, %59, %60, %61, %62, %63}, "
    "{%64, %65, %66, %67}, %68, p, 1, 1, 1;\n}\n"
    : "+f"(d[0]), "+f"(d[1]), "+f"(d[2]), "+f"(d[3]), "+f"(d[4]), "+f"(d[5]), "+f"(d[6]), "+f"(d[7]), "+f"(d[8]), "+f"(d[9]), "+f"(d[10]), "+f"(d[11]), "+f"(d[12]), "+f"(d[13]), "+f"(d[14]), "+f"(d[15]), "+f"(d[16]), "+f"(d[17]), "+f"(d[18]), "+f"(d[19]), "+f"(d[20]), "+f"(d[21]), "+f"(d[22]), "+f"(d[23]), "+f"(d[24]), "+f"(d[25]), "+f"(d[26]), "+f"(d[27]), "+f"(d[28]), "+f"(d[29]), "+f"(d[30]), "+f"(d[31]), "+f"(d[32]), "+f"(d[33]), "+f"(d[34]), "+f"(d[35]), "+f"(d[36]), "+f"(d[37]), "+f"(d[38]), "+f"(d[39]), "+f"(d[40]), "+f"(d[41]), "+f"(d[42]), "+f"(d[43]), "+f"(d[44]), "+f"(d[45]), "+f"(d[46]), "+f"(d[47]), "+f"(d[48]), "+f"(d[49]), "+f"(d[50]), "+f"(d[51]), "+f"(d[52]), "+f"(d[53]), "+f"(d[54]), "+f"(d[55]), "+f"(d[56]), "+f"(d[57]), "+f"(d[58]), "+f"(d[59]), "+f"(d[60]), "+f"(d[61]), "+f"(d[62]), "+f"(d[63])
    : "r"(a0), "r"(a1), "r"(a2), "r"(a3), "l"(descB), "r"(scaleD));
}
__device__ __forceinline__ void wgmma_rs_n64_ta0_tb1(float (&d)[32], uint32_t a0, uint32_t a1, uint32_t a2, uint32_t a3, uint64_t descB, int scaleD) {
  asm volatile("{\n.reg .pred p;\nsetp.ne.b32 p, %37, 0;\n"
    "wgmma.mma_async.sync.aligned.m64n64k16.f32.bf16.bf16 "
    "{%0, %1, %2, %3, %4, %5, %6, %7, %8, %9, %10, %11, %12, %13, %14, %15, %16, %17, %18, %19, %20, %21, %22, %23, %24, %25, %26, %27, %28, %29, %30, %31}, "
    "{%32, %33, %34, %35}, %36, p, 1, 1, 1;\n}\n"
    : "+f"(d[0]), "+f"(d[1]), "+f"(d[2]), "+f"(d[3]), "+f"(d[4]), "+f"(d[5]), "+f"(d[6]), "+f"(d[7]), "+f"(d[8]), "+f"(d[9]), "+f"(d[10]), "+f"(d[11]), "+f"(d[12]), "+f"(d[13]), "+f"(d[14]), "+f"(d[15]), "+f"(d[16]), "+f"(d[17]), "+f"(d[18]), "+f"(d[19]), "+f"(d[20]), "+f"(d[21]), "+f"(d[22]), "+f"(d[23]), "+f"(d[24]), "+f"(d[25]), "+f"(d[26]), "+f"(d[27]), "+f"(d[28]), "+f"(d[29]), "+f"(d[30]), "+f"(d[31])
    : "r"(a0), "r"(a1), "r"(a2), "r"(a3), "l"(descB), "r"(scaleD));
}
__device__ __forceinline__ void wgmma_ss_n128_ta0_tb1(float (&d)[64], uint64_t descA, uint64_t descB, int scaleD) {
  asm volatile("{\n.reg .pred p;\nsetp.ne.b32 p, %66, 0;\n"
    "wgmma.mma_async.sync.aligned.m64n128k16.f32.bf16.bf16 "
    "{%0, %1, %2, %3, %4, %5, %6, %7, %8, %9, %10, %11, %12, %13, %14, %15, %16, %17, %18, %19, %20, %21, %22, %23, %24, %25, %26, %27, %28, %29, %30, %31, %32, %33, %34, %35, %36, %37, %38, %39, %40, %41, %42, %43, %44, %45, %46, %47, %48, %49, %50, %51, %52, %53, %54, %55, %56, %57, %58, %59, %60, %61, %62, %63}, "
    "%64, %65, p, 1, 1, 0, 1;\n}\n"
    : "+f"(d[0]), "+f"(d[1]), "+f"(d[2]), "+f"(d[3]), "+f"(d[4]), "+f"(d[5]), "+f"(d[6]), "+f"(d[7]), "+f"(d[8]), "+f"(d[9]), "+f"(d[10]), "+f"(d[11]), "+f"(d[12]), "+f"(d[13]), "+f"(d[14]), "+f"(d[15]), "+f"(d[16]), "+f"(d[17]), "+f"(d[18]), "+f"(d[19]), "+f"(d[20]), "+f"(d[21]), "+f"(d[22]), "+f"(d[23]), "+f"(d[24]), "+f"(d[25]), "+f"(d[26]), "+f"(d[27]), "+f"(d[28]), "+f"(d[29]), "+f"(d[30]), "+f"(d[31]), "+f"(d[32]), "+f"(d[33]), "+f"(d[34]), "+f"(d[35]), "+f"(d[36]), "+f"(d[37]), "+f"(d[38]), "+f"(d[39]), "+f"(d[40]), "+f"(d[41]), "+f"(d[42]), "+f"(d[43]), "+f"(d[44]), "+f"(d[45]), "+f"(d[46]), "+f"(d[47]), "+f"(d[48]), "+f"(d[49]), "+f"(d[50]), "+f"(d[51]), "+f"(d[52]), "+f"(d[53]), "+f"(d[54]), "+f"(d[55]), "+f"(d[56]), "+f"(d[57]), "+f"(d[58]), "+f"(d[59]), "+f"(d[60]), "+f"(d[61]), "+f"(d[62]), "+f"(d[63])
    : "l"(descA), "l"(descB), "r"(scaleD));
}
__device__ __forceinline__ void wgmma_ss_n160_ta0_tb1(float (&d)[80], uint64_t descA, uint64_t descB, int scaleD) {
  asm volatile("{\n.reg .pred p;\nsetp.ne.b32 p, %82, 0;\n"
    "wgmma.mma_async.sync.aligned.m64n160k16.f32.bf16.bf16 "
    "{%0, %1, %2, %3, %4, %5, %6, %7, %8, %9, %10, %11, %12, %13, %14, %15, %16, %17, %18, %19, %20, %21, %22, %23, %24, %25, %26, %27, %28, %29, %30, %31, %32, %33, %34, %35, %36, %37, %38, %39, %40, %41, %42, %43, %44, %45, %46, %47, %48, %49, %50, %51, %52, %53, %54, %55, %56, %57, %58, %59, %60, %61, %62, %63, %64, %65, %66, %67, %68, %69, %70, %71, %72, %73, %74, %75, %76, %77, %78, %79}, "
    "%80, %81, p, 1, 1, 0, 1;\n}\n"
    : "+f"(d[0]), "+f"(d[1]), "+f"(d[2]), "+f"(d[3]), "+f"(d[4]), "+f"(d[5]), "+f"(d[6]), "+f"(d[7]), "+f"(d[8]), "+f"(d[9]), "+f"(d[10]), "+f"(d[11]), "+f"(d[12]), "+f"(d[13]), "+f"(d[14]), "+f"(d[15]), "+f"(d[16]), "+f"(d[17]), "+f"(d[18]), "+f"(d[19]), "+f"(d[20]), "+f"(d[21]), "+f"(d[22]), "+f"(d[23]), "+f"(d[24]), "+f"(d[25]), "+f"(d[26]), "+f"(d[27]), "+f"(d[28]), "+f"(d[29]), "+f"(d[30]), "+f"(d[31]), "+f"(d[32]), "+f"(d[33]), "+f"(d[34]), "+f"(d[35]), "+f"(d[36]), "+f"(d[37]), "+f"(d[38]), "+f"(d[39]), "+f"(d[40]), "+f"(d[41]), "+f"(d[42]), "+f"(d[43]), "+f"(d[44]), "+f"(d[45]), "+f"(d[46]), "+f"(d[47]), "+f"(d[48]), "+f"(d[49]), "+f"(d[50]), "+f"(d[51]), "+f"(d[52]), "+f"(d[53]), "+f"(d[54]), "+f"(d[55]), "+f"(d[56]), "+f"(d[57]), "+f"(d[58]), "+f"(d[59]), "+f"(d[60]), "+f"(d[61]), "+f"(d[62]), "+f"(d[63]), "+f"(d[64]), "+f"(d[65]), "+f"(d[66]), "+f"(d[67]), "+f"(d[68]), "+f"(d[69]), "+f"(d[70]), "+f"(d[71]), "+f"(d[72]), "+f"(d[73]), "+f"(d[74]), "+f"(d[75]), "+f"(d[76]), "+f"(d[77]), "+f"(d[78]), "+f"(d[79])
    : "l"(descA), "l"(descB), "r"(scaleD));
}


template <int N> struct IC { static constexpr int value = N; };
struct Cur {
    uint32_t slot, ph;
    __device__ __forceinline__ void adv() { if (++slot == NSLOT) { slot = 0; ph ^= 1; } }
};
constexpr int E0 = 2;
__host__ __device__ constexpr uint32_t slot_of(int e) { return (e + E0) % NSLOT; }
__device__ __forceinline__ Cur cur_at(int e) { Cur c; c.slot = (e + E0) % NSLOT; c.ph = ((e + E0) / NSLOT) & 1; return c; }

__device__ __forceinline__ int kv_tile(int s) { return (0x804Cu >> (4 * s)) & 15; }
__device__ __forceinline__ int op_head(int i, int kap) { return 8 * kap + (i & 7) + 16 * (i >> 3); }

constexpr float SM_SCALE = 0.08838834764831845f * 1.4426950408889634f;

struct Ctx {
    uint32_t ring, misc;
    uint32_t rel;
    int w, warp, lane;
};
__device__ __forceinline__ void release(const Ctx& c, uint32_t off, uint32_t cnt) {
    if (c.lane < 2) mbar_arrive_cluster(c.rel + off, cnt);
}
__device__ __forceinline__ void signal_event(const Ctx& c, int ev) {
    __syncwarp();
    if (c.lane == 0) mbar_arrive(c.misc + BAR_EV + (c.w * NEV + ev) * 8);
}
template <int NK, int OFF, int N>
__device__ __forceinline__ uint32_t load_afrag(uint32_t (&a)[N], uint32_t base, const Ctx& c) {
    int r = c.lane & 7, mat = c.lane >> 3;
    uint32_t addr = base + (8 * (mat >> 1) + r) * 128 + (((2 * c.warp + (mat & 1)) ^ r) << 4);
#pragma unroll
    for (int k = 0; k < NK; k++) ldsm4t(a[OFF + 4 * k], a[OFF + 4 * k + 1], a[OFF + 4 * k + 2], a[OFF + 4 * k + 3], addr + k * 2048);
    uint32_t dep = 0;
#pragma unroll
    for (int k = 0; k < NK; k++) dep |= a[OFF + 4 * k];
    return dep & blockIdx.y;
}
__device__ __forceinline__ void tile_out(unsigned char* (&out)[2], unsigned char* dst, int row0, int perm, const Ctx& c) {
#pragma unroll
    for (int i = 0; i < 2; i++) {
        int row = row0 + 16 * c.warp + 8 * i + (c.lane >> 2);
        if (perm) row = perm32(row);
        out[i] = dst + row * 64 + (((c.lane ^ (row >> 1)) & 3) << 4);
    }
}
__device__ __forceinline__ void store_pair(const float (&a)[64], int q, unsigned char* const (&out)[2], int quarter_stride, const float (&f)[2], bool stream = false) {
    const uint64_t pol = stream ? policy_stream() : 0x1000000000000000ull  ;
#pragma unroll
    for (int i = 0; i < 2; i++)
        stg128_hint(out[i] + q * quarter_stride,
               pack_bf16(a[16 * q + 2 * i] * f[i], a[16 * q + 2 * i + 1] * f[i]), pack_bf16(a[16 * q + 4 + 2 * i] * f[i], a[16 * q + 4 + 2 * i + 1] * f[i]),
               pack_bf16(a[16 * q + 8 + 2 * i] * f[i], a[16 * q + 8 + 2 * i + 1] * f[i]), pack_bf16(a[16 * q + 12 + 2 * i] * f[i], a[16 * q + 12 + 2 * i + 1] * f[i]), pol);
}

constexpr float SAFE_SUM = 1099511627776.0f;
template <int NJ>
__device__ __forceinline__ void row_max(const float (&s)[4 * NJ], float (&mx)[2]) {
#pragma unroll
    for (int i = 0; i < 2; i++) {
        float a = fmaxf(s[2 * i], s[2 * i + 1]), b = fmaxf(s[4 + 2 * i], s[4 + 2 * i + 1]);
#pragma unroll
        for (int j = 2; j < NJ; j += 2) {
            a = fmaxf(a, fmaxf(s[4 * j + 2 * i], s[4 * j + 2 * i + 1]));
            b = fmaxf(b, fmaxf(s[4 * j + 4 + 2 * i], s[4 * j + 4 + 2 * i + 1]));
        }
        a = fmaxf(a, b);
        a = fmaxf(a, __shfl_xor_sync(0xffffffffu, a, 1));
        mx[i] = fmaxf(a, __shfl_xor_sync(0xffffffffu, a, 2));
    }
}
template <int NJ, bool SHIFT>
__device__ __forceinline__ void exp_sum(float (&s)[4 * NJ], const float (&m)[2], float& l0, float& l1) {
#pragma unroll
    for (int j = 0; j < NJ; j++) {
#pragma unroll
        for (int e = 0; e < 4; e++) s[4 * j + e] = ex2(SHIFT ? s[4 * j + e] - m[e >> 1] : s[4 * j + e]);
        l0 += s[4 * j + 0] + s[4 * j + 1]; l1 += s[4 * j + 2] + s[4 * j + 3];
    }
}
__device__ __forceinline__ void recompute_scores(float (&s)[64], const uint32_t (&q)[32], uint32_t kaddr, const Ctx& c) {
    const int r = c.lane & 7, mat = c.lane >> 3;
    const uint32_t a0 = kaddr + (8 * (mat & 1) + r) * 64 + (((mat >> 1) ^ (r >> 1)) << 4);
#pragma unroll
    for (int i = 0; i < 64; i++) s[i] = 0.f;
#pragma unroll
    for (int jp = 0; jp < 8; jp++) {
#pragma unroll
        for (int k = 0; k < 8; k++) {
            asm volatile(
                "{\n.reg .b32 b0, b1, b2, b3;\n"
                "ldmatrix.sync.aligned.m8n8.x4.trans.shared.b16 {b0,b1,b2,b3}, [%12];\n"
                "mma.sync.aligned.m16n8k16.row.col.f32.bf16.bf16.f32 {%0,%1,%2,%3}, {%8,%9,%10,%11}, {b0,b1}, {%0,%1,%2,%3};\n"
                "mma.sync.aligned.m16n8k16.row.col.f32.bf16.bf16.f32 {%4,%5,%6,%7}, {%8,%9,%10,%11}, {b2,b3}, {%4,%5,%6,%7};\n}\n"
                : "+f"(s[8 * jp]), "+f"(s[8 * jp + 1]), "+f"(s[8 * jp + 2]), "+f"(s[8 * jp + 3]),
                  "+f"(s[8 * jp + 4]), "+f"(s[8 * jp + 5]), "+f"(s[8 * jp + 6]), "+f"(s[8 * jp + 7])
                : "r"(q[4 * k]), "r"(q[4 * k + 1]), "r"(q[4 * k + 2]), "r"(q[4 * k + 3]),
                  "r"((a0 ^ ((jp & 1) << 5)) + (jp >> 1) * 8192 + k * 1024) : "memory");
        }
    }
}
__device__ __forceinline__ int mask_lim(const Ctx& c) { return perm32(16 * c.warp + (c.lane >> 2)) - 8 * (c.lane & 3); }
template <int J0>
__device__ __forceinline__ void mask_diag(float (&s)[4 * J0 + 32], const Ctx& c) {
    const int lim = mask_lim(c);
    if (c.warp < 2) {
#pragma unroll
        for (int x = 0; x < 16; x++) {
            if (2 * (x >> 2) + (x & 1) - (x & 2) > lim) s[4 * J0 + x] = -INFINITY;
            s[4 * J0 + 16 + x] = -INFINITY;
        }
    } else {
#pragma unroll
        for (int x = 0; x < 16; x++)
            if (32 + 2 * (x >> 2) + (x & 1) - (x & 2) > lim) s[4 * J0 + 16 + x] = -INFINITY;
    }
}
__device__ __forceinline__ void mask_any(float (&s)[64], int hh, const Ctx& c) {
    const int lim = mask_lim(c) + 64 * hh;
#pragma unroll
    for (int x = 0; x < 64; x++)
        if (32 * (x >> 4) + 2 * ((x >> 2) & 3) + (x & 1) - (x & 2) > lim) s[x] = -INFINITY;
}
__device__ __forceinline__ void issue_pv(float (&o)[64], const uint32_t (&p)[32], uint32_t vaddr, int acc, int mode  ) {
    uint64_t d = mkdesc(vaddr, 16, 512, 2);
    if (mode == 0) {
        wg_fence();
#pragma unroll
        for (int k = 0; k < 8; k++)
            wgmma_rs_n128_ta0_tb0(o, p[4 * k], p[4 * k + 1], p[4 * k + 2], p[4 * k + 3], d + (k >> 1) * 512 + 2 * (k & 1), k ? 1 : acc);
        wg_commit();
    } else if (mode == 1) {
        wg_fence();
#pragma unroll
        for (int k = 0; k < 4; k++) wgmma_rs_n128_ta0_tb0(o, p[4 * k], p[4 * k + 1], p[4 * k + 2], p[4 * k + 3], d + (k >> 1) * 512 + 2 * (k & 1), k != 0);
        wg_commit();
    } else {
        wg_fence();
        wgmma_rs_n128_ta0_tb0(o, p[0], p[1], p[2], p[3], d, acc);
        wg_commit();
    }
}
__device__ __forceinline__ void issue_qk(float (&s)[64], const uint32_t (&q)[32], uint32_t kaddr) {
    uint64_t d = mkdesc(kaddr, 8192, 512, 2);
    wg_fence();
#pragma unroll
    for (int k = 0; k < 8; k++) wgmma_rs_n128_ta0_tb1(s, q[4 * k], q[4 * k + 1], q[4 * k + 2], q[4 * k + 3], d + 64 * k, k != 0);
    wg_commit();
}
__device__ __forceinline__ void issue_qk_half(float (&s32)[32], const uint32_t (&q)[32], uint32_t kaddr) {
    uint64_t d = mkdesc(kaddr, 8192, 512, 2);
    wg_fence();
#pragma unroll
    for (int k = 0; k < 8; k++) wgmma_rs_n64_ta0_tb1(s32, q[4 * k], q[4 * k + 1], q[4 * k + 2], q[4 * k + 3], d + 64 * k, k != 0);
    wg_commit();
}
__device__ __forceinline__ void row_inv(const float (&l)[2], float (&inv)[2]) {
#pragma unroll
    for (int i = 0; i < 2; i++) {
        float sum = l[i];
        sum += __shfl_xor_sync(0xffffffffu, sum, 1);
        sum += __shfl_xor_sync(0xffffffffu, sum, 2);
        inv[i] = rcp_fast(sum);
    }
}

__device__ __forceinline__ const unsigned char* xn_addr(int row, int col) {
    row = perm32(row);
    return g_xn + ((row >> 7) * 10 + (col >> 6)) * 16384 + (row & 127) * 128 + ((((col & 63) >> 3) ^ (row & 7)) << 4);
}
__device__ __forceinline__ void mma16816(float (&d)[4], uint32_t a0, uint32_t a1, uint32_t a2, uint32_t a3, uint32_t b0, uint32_t b1) {
    asm volatile("mma.sync.aligned.m16n8k16.row.col.f32.bf16.bf16.f32 {%0,%1,%2,%3}, {%4,%5,%6,%7}, {%8,%9}, {%0,%1,%2,%3};"
                 : "+f"(d[0]), "+f"(d[1]), "+f"(d[2]), "+f"(d[3]) : "r"(a0), "r"(a1), "r"(a2), "r"(a3), "r"(b0), "r"(b1));
}
__device__ __forceinline__ uint32_t lds32(uint32_t addr) { uint32_t v; asm volatile("ld.shared.u32 %0, [%1];" : "=r"(v) : "r"(addr)); return v; }

__device__ __forceinline__ int fresh_lane() { int l; asm volatile("mov.u32 %0, %%laneid;" : "=r"(l)); return l; }
__device__ __forceinline__ void ln_rows(const __nv_bfloat16* x, int row0, uint32_t wr_s) {
    int lane = fresh_lane();
    int hl = lane & 15, row = row0 + (lane >> 4);
    uint32_t v[20];
#pragma unroll
    for (int i = 0; i < 5; i++) {
        const uint4 u = __ldg(reinterpret_cast<const uint4*>(x + (size_t)row * DM + 128 * i + 8 * hl));
        v[4 * i] = u.x; v[4 * i + 1] = u.y; v[4 * i + 2] = u.z; v[4 * i + 3] = u.w;
    }
    float mean = 0.f, m2 = 0.f, acc2 = 0.f;
#pragma unroll
    for (int i = 0; i < 20; i++) { mean += bf_lo(v[i]); acc2 += bf_hi(v[i]); }
    mean = (mean + acc2) * (1.0f / 40);
    acc2 = 0.f;
#pragma unroll
    for (int i = 0; i < 20; i++) {
        float d0 = __uint_as_float(__byte_perm(v[i], 0, 0x1044)) - mean, d1 = __uint_as_float(__byte_perm(v[i], 0, 0x3244)) - mean;
        m2 = fmaf(d0, d0, m2); acc2 = fmaf(d1, d1, acc2);
    }
    m2 += acc2;
    acc2 = 0.f;
#pragma unroll
    for (int o = 1; o < 16; o <<= 1) {
        float mo = __shfl_xor_sync(0xffffffffu, mean, o), qo = __shfl_xor_sync(0xffffffffu, m2, o), d = mo - mean;
        m2 = fmaf(d * d, 20.0f * o, m2 + qo);
        mean = 0.5f * (mean + mo);
    }
    const uint32_t mb2 = pack_bf16(mean, mean);
    const float inv = rcp_fast(bf_round(sqrt_fast(bf_round(bf_round(m2 * (1.0f / DM)) + 1e-5f))));
    float dot = 0.f;
    lane = fresh_lane(); hl = lane & 15; row = row0 + (lane >> 4);
    if (hl == 0) g_stats[row] = make_uint2(mb2, __float_as_uint(inv));
    unsigned char* xp = const_cast<unsigned char*>(xn_addr(row, 8 * hl));
#pragma unroll
    for (int i = 0; i < 5; i++) {
        uint32_t ww[4];
        asm volatile("ld.shared.v4.b32 {%0,%1,%2,%3}, [%4];" : "=r"(ww[0]), "=r"(ww[1]), "=r"(ww[2]), "=r"(ww[3]) : "r"(wr_s + 256 * i + 16 * hl) : "memory");
#pragma unroll
        for (int e = 0; e < 4; e++) {
            uint32_t d;
            asm("sub.rn.bf16x2 %0, %1, %2;" : "=r"(d) : "r"(v[4 * i + e]), "r"(mb2));
            d = pack_bf16(bf_lo(d) * inv, bf_hi(d) * inv);
            v[4 * i + e] = d;
            dot = fmaf(bf_lo(d), bf_lo(ww[e]), dot);
            acc2 = fmaf(bf_hi(d), bf_hi(ww[e]), acc2);
        }
        stg128(xp + i * 32768, v[4 * i], v[4 * i + 1], v[4 * i + 2], v[4 * i + 3]);
    }
    dot += acc2;
#pragma unroll
    for (int o = 8; o > 0; o >>= 1) dot += __shfl_xor_sync(0xffffffffu, dot, o);
    lane = fresh_lane();
    if ((lane & 15) == 0) g_router[row0 + (lane >> 4)] = bf_round(dot);
}

__device__ __forceinline__ void aux_cta(const CUtensorMap* tmG, const CUtensorMap* tmU, const CUtensorMap* tmD, unsigned char* sm, int a) {
    constexpr int STG = 57344, XS = 3 * STG, HS = XS + 8 * 1296, KEY = HS + 8 * 912, MI = KEY + 8192;
    const int tid = threadIdx.x, warp = __shfl_sync(0xffffffffu, tid >> 5, 0), lane = tid & 31;
    const uint32_t sb = smem_u32(sm);
    const uint32_t full = sb + MI, empty = sb + MI + 32;
    int* s_sel = reinterpret_cast<int*>(sm + MI + 64);
    float* s_r = reinterpret_cast<float*>(sm + MI + 96);
    volatile unsigned* s_misc = reinterpret_cast<volatile unsigned*>(sm + MI + 128);
    uint32_t* s_key = reinterpret_cast<uint32_t*>(sm + KEY);
    if (tid == 0) {
        for (int i = 0; i < 3; i++) { mbar_init(full + 8 * i, 1); mbar_init(empty + 8 * i, 10); }
        asm volatile("fence.mbarrier_init.release.cluster;" ::: "memory");
    }
    __syncthreads();
    if (warp == 11) {
        if (elect_one()) {
            const unsigned ep1 = *reinterpret_cast<volatile unsigned*>(&g_epoch) + 1;
            __nanosleep(20000);
            flag_wait(flag_ptr(FL_CTX + (18 + a) * 8), ep1 * 4u);
            int st = 0; uint32_t ph = 0;
#pragma unroll 1
            for (int s = 0; s < 34; s++) {
                mbar_wait(empty + 8 * st, ph ^ 1);
                const uint32_t dst = sb + st * STG, fb = full + 8 * st;
                if (s < 20) {
                    mbar_expect_tx(fb, 57344);
                    tma3d(dst, tmG, 0, 32 * s, 7 * a, fb);
                    tma3d(dst + 28672, tmU, 0, 32 * s, 7 * a, fb);
                } else {
                    mbar_expect_tx(fb, 40960);
                    tma3d(dst, tmD, 0, 448 * a + 32 * (s - 20), 0, fb);
                }
                if (s >= 2) {
#pragma unroll 1
                    for (int f = (s == 2 ? 3 : s + 6); f <= s + 6 && f < 34; f++) {
                        if (f < 20) { tma3d_prefetch(tmG, 0, 32 * f, 7 * a); tma3d_prefetch(tmU, 0, 32 * f, 7 * a); }
                        else tma3d_prefetch(tmD, 0, 448 * a + 32 * (f - 20), 0);
                    }
                }
                if (++st == 3) { st = 0; ph ^= 1; }
            }
        }
        return;
    }
    if (warp == 10) return;
    if (tid < 8) {
        unsigned e = *reinterpret_cast<volatile unsigned*>(&g_epoch);
        if (tid == 0) s_misc[0] = e;
        flag_wait(flag_ptr(FL_LN + tid), (e + 1) * (tid < 4 ? 33u : 128u));
    }
    bar_sync(1, 320);
    const unsigned ep = s_misc[0];
    auto top8 = [&](uint32_t (&key)[8]) {
        uint32_t mine = 0;
#pragma unroll 1
        for (int r = 0; r < TOPC; r++) {
            uint32_t best = 0;
#pragma unroll
            for (int i = 0; i < 8; i++) best = max(best, key[i]);
            best = __reduce_max_sync(0xffffffffu, best);
#pragma unroll
            for (int i = 0; i < 8; i++) if (key[i] == best) key[i] = 0;
            if (lane == r) mine = best;
        }
        return mine;
    };
#pragma unroll 1
    for (int pass = 0; pass < 2; pass++) {
        if (warp < (pass ? 1 : 8)) {
            uint32_t key[8];
#pragma unroll
            for (int i = 0; i < 8; i++) {
                if (pass == 0) {
                    int idx = warp * 256 + i * 32 + lane;
                    uint32_t b = __float_as_uint(__ldcg(g_router + idx)) >> 16;
                    b = (b & 0x8000u) ? (~b & 0xffffu) : (b | 0x8000u);
                    key[i] = (b << 16) | (uint32_t)(0xffff - idx);
                } else key[i] = i < 2 ? s_key[i * 32 + lane] : 0u;
            }
            uint32_t best = top8(key);
            if (lane < TOPC) {
                if (pass == 0) s_key[warp * 8 + lane] = best;
                else {
                    uint32_t b = best >> 16;
                    b = (b & 0x8000u) ? (b & 0x7fffu) : (~b & 0xffffu);
                    s_sel[lane] = 0xffff - (int)(best & 0xffffu);
                    s_r[lane] = bf_round(rcp_fast(1.0f + __expf(fminf(-__uint_as_float(b << 16), 80.f))));
                }
            }
        }
        bar_sync(1, 320);
    }
#pragma unroll 1
    for (int it = 0; it < 2; it++) {
        int i = tid + it * 320, tk = i / 80, ch = i % 80;
        *reinterpret_cast<uint4*>(sm + XS + tk * 1296 + ch * 16) = __ldcg(reinterpret_cast<const uint4*>(xn_addr(s_sel[tk], ch * 8)));
    }
    bar_sync(1, 320);
    const int g = lane >> 2, t = lane & 3;
    const uint32_t woff = warp * 4096 + (8 * (lane >> 4) + (lane & 7)) * 128 + ((((lane >> 3) & 1) ^ (lane & 7)) << 4);
    int st = 0; uint32_t ph = 0;
    float ga[4][4], ua[4][4];
#pragma unroll
    for (int i = 0; i < 4; i++)
#pragma unroll
        for (int e = 0; e < 4; e++) { ga[i][e] = 0.f; ua[i][e] = 0.f; }
#pragma unroll 1
    for (int s = 0; s < 34; s++) {
        if (s == 20) {
            if (warp < 7) {
#pragma unroll 1
                for (int i = 0; i < 4; i++) {
#pragma unroll
                    for (int e = 0; e < 4; e++) {
                        float gv = bf_round(ga[0][e]), uv = bf_round(ua[0][e]);
                        float sg = bf_round(gv * rcp_fast(1.0f + __expf(fminf(-gv, 80.f))));
                        int f = warp * 64 + i * 16 + g + 8 * (e >> 1), tk = 2 * t + (e & 1);
                        *reinterpret_cast<__nv_bfloat16*>(sm + HS + tk * 912 + f * 2) = __float2bfloat16_rn(sg * uv);
                        ga[0][e] = ga[1][e]; ga[1][e] = ga[2][e]; ga[2][e] = ga[3][e]; ga[3][e] = 0.f;
                        ua[0][e] = ua[1][e]; ua[1][e] = ua[2][e]; ua[2][e] = ua[3][e];
                    }
                }
            }
            bar_sync(1, 320);
        }
        mbar_wait(full + 8 * st, ph);
        if (s >= 20 || warp < 7) {
#pragma unroll
            for (int kk = 0; kk < 2; kk++) {
                uint32_t xb = sb + (s < 20 ? XS + g * 1296 + s * 64 : HS + g * 912 + (s - 20) * 64) + 32 * kk + 4 * t;
                uint32_t b0 = lds32(xb), b1 = lds32(xb + 16);
                uint32_t wa = sb + st * STG + woff + kk * 2048;
#pragma unroll
                for (int i = 0; i < 4; i++) {
                    uint32_t a0, a1, a2, a3;
                    ldsm4t(a0, a1, a2, a3, wa ^ (i << 5));
                    mma16816(ga[i], a0, a1, a2, a3, b0, b1);
                    if (s < 20) {
                        ldsm4t(a0, a1, a2, a3, (wa ^ (i << 5)) + 28672);
                        mma16816(ua[i], a0, a1, a2, a3, b0, b1);
                    }
                }
            }
        }
        asm volatile("fence.proxy.async.shared::cta;" ::: "memory");
        __syncwarp();
        if (lane == 0) mbar_arrive(empty + 8 * st);
        if (++st == 3) { st = 0; ph ^= 1; }
    }
#pragma unroll
    for (int i = 0; i < 4; i++)
#pragma unroll
        for (int e = 0; e < 4; e += 2)
            *reinterpret_cast<float2*>(g_moe_part + (a * DM + warp * 64 + i * 16 + g + 4 * e) * 8 + 2 * t) = make_float2(ga[i][e], ga[i][e + 1]);
    bar_sync(1, 320);
    if (tid == 0) {
        __threadfence();
        unsigned old = atomicAdd(flag_ptr(FL_MOE_CNT), 1u);
        s_misc[1] = (old == ep * 4u + 3u);
        __threadfence();
    }
    bar_sync(1, 320);
    if (s_misc[1]) {
        const float4* pp = reinterpret_cast<const float4*>(g_moe_part);
#pragma unroll 1
        for (int i = tid; i < DM * 2; i += 320) {
            float4 v0 = __ldcg(pp + i), v1 = __ldcg(pp + DM * 2 + i), v2 = __ldcg(pp + DM * 4 + i), v3 = __ldcg(pp + DM * 6 + i);
            float y[4] = {v0.x + v1.x + v2.x + v3.x, v0.y + v1.y + v2.y + v3.y, v0.z + v1.z + v2.z + v3.z, v0.w + v1.w + v2.w + v3.w};
#pragma unroll
            for (int e = 0; e < 4; e++) {
                int col = i >> 1, tk = (i & 1) * 4 + e;
                float upd = bf_round(bf_round(y[e]) * s_r[tk]);
                float xn = __bfloat162float(*reinterpret_cast<const __nv_bfloat16*>(sm + XS + tk * 1296 + col * 2));
                g_brow[tk * DM + col] = __float2bfloat16_rn(xn + upd);
            }
        }
        if (tid < TOPC) g_sel[tid] = s_sel[tid];
        bar_sync(1, 320);
        if (tid == 0) {
            flag_signal(flag_ptr(FL_MOE_DONE));
            *reinterpret_cast<volatile unsigned*>(&g_epoch) = ep + 1;
        }
    }
}

__global__ void __cluster_dims__(2, 1, 1) __launch_bounds__(384, 1)
fused_kernel(const __grid_constant__ CUtensorMap tmC, const __grid_constant__ CUtensorMap tmWk, const __grid_constant__ CUtensorMap tmWv,
             const __grid_constant__ CUtensorMap tmWq, const __grid_constant__ CUtensorMap tmWo,
             const __grid_constant__ CUtensorMap tmG, const __grid_constant__ CUtensorMap tmU, const __grid_constant__ CUtensorMap tmD, const Params P) {
    extern __shared__ __align__(1024) unsigned char smem_raw[];
    const uint32_t ring = smem_u32(smem_raw);
    const uint32_t misc = ring + RING_BYTES;
    const int tid = threadIdx.x;
    const int rank = blockIdx.x & 1;
    uint32_t smid, nsm;
    asm("mov.u32 %0, %%smid;" : "=r"(smid));
    asm("mov.u32 %0, %%nsmid;" : "=r"(nsm));
    if (nsm != 132) smid = blockIdx.x;
    auto role_of = [](int tpc) {
        return tpc < 32 ? (tpc & 7) * 8 + (tpc >> 3) : tpc < 60 ? (1 + (tpc - 32) % 7) * 8 + 4 + (tpc - 32) / 7 : tpc < 62 ? tpc + 4 : tpc - 58;
    };
    int mc = role_of(smid >> 1);

    auto prefetch_w = [&](int ch) {
        const int i = tid - 128;
        asm volatile("prefetch.global.L2 [%0];" ::"l"((rank ? P.wv : P.wk) + (size_t)(ch * 128 + (mc & 3) * 32 + (i >> 3)) * 4096 + (mc >> 2) * 128 + (i & 7) * 16));
    };
    if (tid >= 128 && mc < 64) {
        if (tid < 256) asm volatile("prefetch.global.L2 [%0];" ::"l"(P.c + (size_t)((12 + (mc & 3)) * 128 + ((mc >> 2) * 2 + rank) * 4) * DC + (tid - 128) * 16));
        prefetch_w(0);
    }
    auto load_w0 = [&]() {
        const CUtensorMap* tw = rank ? &tmWv : &tmWk;
        mbar_expect_tx(misc + BAR_FULL + 8 * slot_of(0), SLOT_BYTES);
        tma2d(ring + slot_of(0) * SLOT_BYTES, tw, (mc >> 2) * 128, 0, misc + BAR_FULL + 8 * slot_of(0));
        tma2d(ring + slot_of(0) * SLOT_BYTES + 16384, tw, (mc >> 2) * 128 + 64, 0, misc + BAR_FULL + 8 * slot_of(0));
    };
    if (tid == 0) {
#pragma unroll
        for (int i = 0; i < NSLOT; i++) mbar_init(misc + BAR_FULL + 8 * i, 1);
#pragma unroll
        for (int i = 0; i < E0; i++) mbar_arrive(misc + BAR_FULL + 8 * i);
        asm volatile("fence.mbarrier_init.release.cluster;" ::: "memory");
        if (mc < 64) load_w0();
    }
    if (tid == 160) {
        asm volatile("st.shared.u32 [%0], %1;" ::"r"(misc + MISC_SMID), "r"(smid) : "memory");
        asm volatile("fence.release.sync_restrict::shared::cta.cluster;" ::: "memory");
    }
    if (tid == 32) {
        asm volatile("prefetch.tensormap [%0];" ::"l"(&tmC) : "memory");
#pragma unroll
        for (int i = 0; i < NSLOT; i++) mbar_init(misc + BAR_EMPTY + 8 * i, 16);
#pragma unroll
        for (int i = 0; i < E0; i++) mbar_arrive_cluster(misc + BAR_EMPTY + 8 * i, 16);
        asm volatile("fence.mbarrier_init.release.cluster;" ::: "memory");
    }
    if (tid == 64) {
#pragma unroll
        for (int i = 0; i < NST3; i++) { mbar_init(misc + BAR_FULL3 + 8 * i, 1); mbar_init(misc + BAR_EMPTY3 + 8 * i, 16); }
#pragma unroll
        for (int i = 0; i < 4; i++) mbar_init(misc + BAR_PROG + 8 * i, 1);
        mbar_init(misc + BAR_LN, 2);
        asm volatile("fence.mbarrier_init.release.cluster;" ::: "memory");
    }
    if (tid == 96) {
#pragma unroll
        for (int i = 0; i < 24; i++) mbar_init(misc + BAR_DEP + 8 * i, 1);
    }
    if (tid == 128) {
#pragma unroll
        for (int i = 0; i < 2 * NEV; i++) mbar_init(misc + BAR_EV + 8 * i, 4);
    }
    __syncthreads();
    asm volatile("barrier.cluster.arrive.relaxed.aligned;\nbarrier.cluster.wait.aligned;" ::: "memory");
    {
        uint32_t peer;
        asm volatile("{\n.reg .b32 r, a;\nmov.u32 r, %%cluster_ctarank;\nxor.b32 r, r, 1;\nmapa.shared::cluster.u32 a, %1, r;\n"
                     "ld.shared::cluster.u32 %0, [a];\n}\n" : "=r"(peer) : "r"(misc + MISC_SMID) : "memory");
        if ((__shfl_sync(0xffffffffu, peer, 0) ^ smid) != 1) {
            if (tid == 0) {
                const unsigned ep1 = *reinterpret_cast<volatile unsigned*>(&g_epoch) + 1;
                if ((smid & 1) == 0) atomicExch(g_roleq + 2 + (atomicAdd(g_roleq, 1u) & 127), (ep1 << 8) | (smid >> 1));
                if (rank == 0) {
                    unsigned* slot = g_roleq + 2 + (atomicAdd(g_roleq + 1, 1u) & 127);
                    unsigned v = 0;
                    for (int spin = 0; spin < 4000000 && ((v = atomicAdd(slot, 0u)) >> 8) != (ep1 & 0xffffffu); spin++) {}
                    asm volatile("st.shared::cluster.u32 [%0], %1;" ::"r"(mapa(misc + MISC_SMID + 4, 0)), "r"(v & 255) : "memory");
                    asm volatile("st.shared::cluster.u32 [%0], %1;" ::"r"(mapa(misc + MISC_SMID + 4, 1)), "r"(v & 255) : "memory");
                }
                if (mc < 64) {
                    mbar_wait(misc + BAR_FULL + 8 * slot_of(0), 0);
                    asm volatile("mbarrier.inval.shared::cta.b64 [%0];" ::"r"(misc + BAR_FULL + 8 * slot_of(0)) : "memory");
                    mbar_init(misc + BAR_FULL + 8 * slot_of(0), 1);
                    asm volatile("fence.mbarrier_init.release.cluster;" ::: "memory");
                }
            }
            __syncwarp();
            asm volatile("barrier.cluster.arrive.aligned;\nbarrier.cluster.wait.aligned;" ::: "memory");
            mc = role_of(__shfl_sync(0xffffffffu, lds32(misc + MISC_SMID + 4), 0));
            if (tid == 0 && mc < 64) load_w0();
            __syncwarp();
        }
    }
    const int cta = mc * 2 + rank;
    const bool aux = mc >= 64;
    const int team = mc >> 2, k = mc & 3;
    const int u3 = mc >> 3, s3 = k, kap = team & 1;
    const int partner = cta ^ 8;
    const int b0 = k, b1 = 7 - k;
    if (tid >= 128 && !aux) prefetch_w(1);
    if (tid == 256 && !aux) {
        const CUtensorMap* tw = rank ? &tmWv : &tmWk;
#pragma unroll
        for (int e = 1; e < NSLOT; e++) {
            const uint32_t fb = misc + BAR_FULL + 8 * slot_of(e), dst = ring + slot_of(e) * SLOT_BYTES;
            mbar_expect_tx(fb, SLOT_BYTES);
            if (e & 1) tma2d_mc(dst + rank * 16384, &tmC, (e >> 1) * 128 + rank * 64, (12 + k) * 128, fb);
            else { tma2d(dst, tw, team * 128, e * 64, fb); tma2d(dst + 16384, tw, team * 128 + 64, e * 64, fb); }
        }
    }
    const int wg = __shfl_sync(0xffffffffu, tid >> 7, 0);

    if (wg == 0 || aux) {
        asm volatile("setmaxnreg.dec.sync.aligned.u32 40;");
        const int warp = __shfl_sync(0xffffffffu, tid >> 5, 0), lane = tid & 31;
        if (warp == 0 && !aux) {
            const bool lead = elect_one();
            Cur c = cur_at(NSLOT);
            uint32_t dst, fb;
            auto acquire = [&]() {
                mbar_wait_sleep(misc + BAR_EMPTY + 8 * c.slot, c.ph ^ 1);
                fb = misc + BAR_FULL + 8 * c.slot; dst = ring + c.slot * SLOT_BYTES;
                if (lead) mbar_expect_tx(fb, SLOT_BYTES);
                c.adv();
            };
            auto load_w = [&](const CUtensorMap* tm, int col, int row) {
                acquire();
                if (lead) { tma2d(dst, tm, col, row, fb); tma2d(dst + 16384, tm, col + 64, row, fb); }
            };
            auto load_half = [&](const unsigned char* src) {
                acquire();
                if (lead) bulk_load_mc(dst + rank * 16384, src, 16384, fb);
            };
            auto dep_wait = [&](int d) { mbar_wait_sleep(misc + BAR_DEP + 8 * d, 0); fence_async_global(); };
            auto op_prefetch = [&](int i) {
                const int head = op_head(i, kap);
                l2_prefetch(reinterpret_cast<const unsigned char*>(P.wo) + head * 163840 + (u3 * 8 + s3 * 2 + rank) * 2560, 2560);
                if (i < 8) l2_prefetch(g_ctx + (size_t)(head * 32 + 4 * u3 + 2 * rank) * 16384 + s3 * 8192, 8192);
            };
            if (lead) l2_prefetch(reinterpret_cast<const unsigned char*>(P.c) + (size_t)cta * 12288, 12288);
            const CUtensorMap* tw = rank ? &tmWv : &tmWk;
            const unsigned char* Kh = g_K + (size_t)team * 32 * 16384 + rank * 16384;
            const unsigned char* Vh = g_V + (size_t)team * 32 * 16384 + rank * 16384;
#pragma unroll 1
            for (int v = 0; v < 2; v++) {
                const int h = team + 16 * v;
#pragma unroll 1
                for (int i = v ? 0 : 3; i < 16; i++) {
                    if (i < 4 && v) load_w(tw, h * 128, i * 128);
                    if (v && i == 3 && lead) mbar_arrive(misc + BAR_PROG + 8);
                    if (v && (i == 3 || i == 7)) dep_wait(D_WAR + (i > 3));
                    acquire();
                    if (lead) tma2d_mc(dst + rank * 16384, &tmC, (i & 3) * 128 + rank * 64, (kv_tile(i >> 2) + k) * 128, fb);
                    if (i == 8 && lead) {
                        tma2d_prefetch(&tmWq, h * 128 + rank * 64, k * 64); tma2d_prefetch(&tmWq, h * 128 + rank * 64, k * 64 + 256);
                        if (k < 2) tma2d_prefetch(&tmWq, h * 128 + rank * 64, k * 64 + 512);
                    }
                }
                int togo = v ? PF_START : 11;
#pragma unroll 1
                for (int r = 0; r < 2; r++) {
                    const int p = r ? b1 : b0, n = 2 * p + 1;
                    if (v == 0) dep_wait(D_LN + r);
                    const int g0 = r ? rank ^ 1 : 3 - rank, g1 = 3 - g0;
                    const unsigned char* x0 = g_xn + (2 * p + (g0 >> 1)) * 163840 + (g0 & 1) * 8192;
                    const unsigned char* x1 = g_xn + (2 * p + (g1 >> 1)) * 163840 + (g1 & 1) * 8192;
#pragma unroll 1
                    for (int kc = 0; kc < 10; kc++) {
                        acquire();
                        if (lead) {
                            tma2d_mc(dst + 16384 + rank * 8192, &tmWq, h * 128 + rank * 64, kc * 64, fb);
                            bulk_load(dst, x0 + kc * 16384, 8192, fb);
                            bulk_load(dst + 8192, x1 + kc * 16384, 8192, fb);
                        }
                    }
                    dep_wait(D_KV + 2 * v + r);
                    load_half(Kh + n * 32768);
#pragma unroll 1
                    for (int j = n - 1; j >= 0; j--) {
                        load_half(Kh + j * 32768); load_half(Vh + (j + 1) * 32768);
                        if (v == 0 && r && j == 7 && lead) mbar_arrive(misc + BAR_PROG);
                        --togo;
                        if (v == 0 && togo == 0 && lead) {
                            tma2d_prefetch(tw, h * 128 + 2048, k * 128); tma2d_prefetch(tw, h * 128 + 2112, k * 128);
                            l2_prefetch(reinterpret_cast<const unsigned char*>(P.c) + (size_t)cta * 16384, 16384);
                        }
                        if (v && togo <= 0 && togo > -OP_PF && lead) op_prefetch(-togo);
                    }
                    load_half(Vh);
                }
            }
            mbar_wait_sleep(misc + BAR_EMPTY + 8 * c.slot, c.ph ^ 1); c.adv();
            int st = 0; uint32_t ph3 = 0;
#pragma unroll 1
            for (int i = 0; i < 32; i++) {
                const int head = op_head(i >> 1, kap);
                if ((i & 1) == 0) dep_wait(D_CTX + (i >> 1));
                if (i < NST3) { mbar_wait_sleep(misc + BAR_EMPTY + 8 * c.slot, c.ph ^ 1); c.adv(); }
                else mbar_wait_sleep(misc + BAR_EMPTY3 + 8 * st, ph3 ^ 1);
                fb = misc + BAR_FULL3 + 8 * st; dst = ring + st * ST3_BYTES;
                if (i == LATE_AT && lead) mbar_arrive(misc + BAR_PROG + 16);
                if (lead) {
                    mbar_expect_tx(fb, ST3_BYTES);
                    const unsigned char* src = g_ctx + (size_t)(head * 32 + 4 * u3 + 2 * rank) * 16384 + (i & 1) * 8192;
                    bulk_load(dst, src, 8192, fb);
                    bulk_load(dst + 8192, src + 16384, 8192, fb);
                    tma3d_mc(dst + 16384 + rank * 10240, &tmWo, 0, head * 128 + (i & 1) * 64 + rank * 32, 5 * s3, fb);
                    if ((i & 1) && (i >> 1) + OP_PF < 16) op_prefetch((i >> 1) + OP_PF);
                }
                if (++st == NST3) { st = 0; ph3 ^= 1; }
            }
        } else {
        if (warp >= 1 && warp <= 3 && lane < 27 && (warp - 1) * 27 + lane < 80) {
            const int ch = (warp - 1) * 27 + lane;
            uint4 u = __ldg(reinterpret_cast<const uint4*>(P.wr) + ch);
            asm volatile("st.shared.v4.b32 [%0], {%1,%2,%3,%4};" ::"r"(misc + MISC_WR + 16 * ch), "r"(u.x), "r"(u.y), "r"(u.z), "r"(u.w) : "memory");
        }
        bar_sync(3, aux ? 384 : 96);
        const int lid = (team * 6 + (k - 1) * 2 + rank) * 2 + warp - 1;
        const int nln = aux ? (warp < 8 ? 3 : 2) : (warp == 3 || k == 0) ? 1 : lid < 128 ? 4 : 3, rstep = aux ? 24 : -384;
        int lrow = aux ? (cta - 128) * 256 + 192 + 2 * warp : (cta >> 5) * 256 + (cta & 31) * 6 + (warp - 1) * 2;
        int lnext = aux ? lrow + 24 : 2046 - 2 * lid;
#pragma unroll 1
        for (int t = 0; t < nln; t++) {
            if (t + 1 < nln) {
                const int ll = fresh_lane();
#pragma unroll
                for (int i = 0; i < 3; i++)
                    if (i * 32 + ll < 80) asm volatile("prefetch.global.L2 [%0];" ::"l"(P.x + (size_t)lnext * DM + (i * 32 + ll) * 16));
            }
            ln_rows(P.x, lrow, misc + MISC_WR);
            __syncwarp();
            if (fresh_lane() == 0 && warp < 3 && !aux) {
                if (t) flag_signal(flag_ptr(FL_LN + (lrow >> 8))); else mbar_arrive(misc + BAR_LN);
            }
            lrow = lnext; lnext += rstep;
        }
        if (aux) {
            bar_sync(3, 384);
            if (tid == 320) flag_signal(flag_ptr(FL_LN + cta - 128));
            __syncwarp();
            asm volatile("setmaxnreg.inc.sync.aligned.u32 128;");
            aux_cta(&tmG, &tmU, &tmD, smem_raw, cta - 128);
        } else
        if (warp == 3) {
            const unsigned ep1 = *reinterpret_cast<volatile unsigned*>(&g_epoch) + 1;
            if (lane == 0) {
                asm volatile("st.shared.u32 [%0], %1;" ::"r"(misc + MISC_EPOCH), "r"(ep1) : "memory");
                mbar_wait(misc + BAR_LN, 0);
                flag_signal(flag_ptr(FL_LN + (cta >> 5)));
                flag_wait(flag_ptr(FL_LN + b0), ep1 * 33u);
                mbar_arrive(misc + BAR_DEP + 8 * D_LN);
#pragma unroll 1
                for (int i = 0; i < 4; i++) {
                    mbar_wait(misc + BAR_EV + 8 * (NEV + EV_KV + i), 0);
                    if (i < 2) {
                        mbar_wait(misc + BAR_EV + 8 * (EV_KV + i), 0);
                        asm volatile("red.release.gpu.global.add.u32 [%0], 2;" ::"l"(flag_ptr(FL_KV + team * 8 + i)) : "memory");
                    }
                    flag_wait(flag_ptr(FL_KV + team * 8 + i), ep1 * 16u);
                    mbar_arrive(misc + BAR_DEP + 8 * (D_KV + i));
                    if (i == (k >> 1)) {
                        flag_wait(flag_ptr(FL_LN + b1), ep1 * 128u);
                        mbar_arrive(misc + BAR_DEP + 8 * (D_LN + 1));
                    }
                    if (i == 1) {
#pragma unroll 1
                        for (int j = 0; j < 2; j++) {
                            mbar_wait(misc + BAR_PROG + 8 * j, 0);
                            asm volatile("red.relaxed.gpu.global.add.u32 [%0], 1;" ::"l"(flag_ptr(FL_WAR + 2 * team + j)) : "memory");
                            flag_wait(flag_ptr(FL_WAR + 2 * team + j), ep1 * 8u);
                            mbar_arrive(misc + BAR_DEP + 8 * (D_WAR + j));
                        }
                    }
                }
                flag_wait(flag_ptr(FL_LN + u3), ep1 * (u3 < 4 ? 33u : 128u));
            }
            __syncwarp();
            const unsigned* cf = flag_ptr(FL_CTX + op_head(lane & 15, kap) * 8 + u3);
#pragma unroll 1
            for (int half = 0; half < 2; half++) {
                if (half) mbar_wait(misc + BAR_EV + 8 * (EV_CTX + 3), 0);
                bool done = (lane >> 3) != half;
                for (int spin = 0; spin < 4000000; spin++) {
                    if (!done) {
                        unsigned v;
                        asm volatile("ld.acquire.gpu.global.u32 %0, [%1];" : "=r"(v) : "l"(cf) : "memory");
                        if ((int)(v - ep1 * 4u) >= 0) { mbar_arrive(misc + BAR_DEP + 8 * (D_CTX + lane)); done = true; }
                    }
                    if (__all_sync(0xffffffffu, done)) break;
                    __nanosleep(64);
                }
            }
            if (lane == 0) {
                flag_wait(flag_ptr(FL_MOE_DONE), ep1);
                int4 s0 = __ldcg(reinterpret_cast<const int4*>(g_sel)), s1 = __ldcg(reinterpret_cast<const int4*>(g_sel) + 1);
                asm volatile("st.shared.v4.u32 [%0], {%1,%2,%3,%4};" ::"r"(misc + MISC_SEL), "r"(s0.x), "r"(s0.y), "r"(s0.z), "r"(s0.w) : "memory");
                asm volatile("st.shared.v4.u32 [%0], {%1,%2,%3,%4};" ::"r"(misc + MISC_SEL + 16), "r"(s1.x), "r"(s1.y), "r"(s1.z), "r"(s1.w) : "memory");
                mbar_arrive(misc + BAR_SEL);
            }
        } else {
            const int w = warp - 1;
            if (lane == 0) {
                const uint32_t eb = misc + BAR_EV + w * 8 * NEV;
#pragma unroll 1
                for (int i = 0; i < 6; i++) {
                    const bool kv = (i >> 1) == 1;
                    const int ci = i < 2 ? i : i - 2;
                    mbar_wait(eb + 8 * (kv ? EV_KV + i : EV_CTX + ci), 0);
                    if (i == 1) {
                        asm volatile("cp.async.bulk.global.shared::cta.bulk_group.L2::cache_hint [%0], [%1], 16384, %2;"
                                     ::"l"(g_ctx + (size_t)(team * 32 + 4 * b1 + (w ? 3 - (rank ^ 1) : rank ^ 1)) * 16384),
                                       "r"(ring + slot_of(78) * SLOT_BYTES + w * 16384), "l"(policy_stream()) : "memory");
                        asm volatile("cp.async.bulk.commit_group;" ::: "memory");
                        asm volatile("cp.async.bulk.wait_group.read 0;" ::: "memory");
                        mbar_arrive_cluster(mapa(misc + BAR_EMPTY + 8 * slot_of(78), 0), 4);
                        mbar_arrive_cluster(mapa(misc + BAR_EMPTY + 8 * slot_of(78), 1), 4);
                        asm volatile("cp.async.bulk.wait_group 0;" ::: "memory");
                        fence_async_global();
                    }
                    flag_signal(flag_ptr(kv ? FL_KV + team * 8 + i : FL_CTX + (team + 16 * (ci >> 1)) * 8 + ((ci & 1) ? b1 : b0)));
                }
            }
            __syncwarp();
            mbar_wait(misc + BAR_PROG + 16, 0);
            const int row = (2 * u3 + rank) * 128 + 64 * w + perm32(16 * (lane >> 3) + 8 * kap + (lane & 7));
#pragma unroll
            for (int i = 0; i < 10; i++) asm volatile("prefetch.global.L2 [%0];" ::"l"(P.x + (size_t)row * DM + 160 * s3 + 16 * i));
            asm volatile("prefetch.global.L2 [%0];" ::"l"(g_stats + row));
            mbar_wait(misc + BAR_EV + w * 8 * NEV + 8 * EV_END, 0);
        }
        }
    } else {
        asm volatile("setmaxnreg.inc.sync.aligned.u32 232;");
        Ctx c;
        c.ring = ring; c.misc = misc; c.w = wg - 1; c.warp = __shfl_sync(0xffffffffu, (tid >> 5) & 3, 0); c.lane = tid & 31;
        c.rel = mapa(misc, tid & 1);
        const int w = c.w;
        if (w == 1) bar_arrive(1, 256);
        prefetch_w(2); prefetch_w(3);
        Cur cur = cur_at(0);
        float o[64], inv[2];
        unsigned char* out[2];
        uint32_t wf[128];
        Cur cw = cur;
        auto load_wchunk = [&](auto CH) {
            constexpr int ch = decltype(CH)::value;
            mbar_wait_hot(misc + BAR_FULL + 8 * cw.slot, cw.ph);
            const uint32_t z = load_afrag<8, 32 * ch>(wf, ring + cw.slot * SLOT_BYTES + w * 16384, c);
            release(c, BAR_EMPTY + 8 * cw.slot + z, 1);
            cw.adv(); cw.adv();
        };
#pragma unroll
        for (int i = 32; i < 64; i++) wf[i] = 0u;
        load_wchunk(IC<0>{});
#pragma unroll 1
        for (int v = 0; v < 2; v++) {
        {
            float (&acc)[64] = o;
#pragma unroll
            for (int i = 64; i < 128; i++) wf[i] = 0u;
            cur.adv();
            inv[0] = inv[1] = rank ? 1.0f : SM_SCALE;
#pragma unroll 1
            for (int t = 0; t < 4; t++) {
                uint32_t last = 0;
                token_wait(w);
                undef_regs(acc);
                auto chunk = [&](auto CH) {
                    constexpr int ch = decltype(CH)::value;
                    mbar_wait_hot(misc + BAR_FULL + 8 * cur.slot, cur.ph);
                    uint64_t d = mkdesc(ring + cur.slot * SLOT_BYTES, 16, 1024, 1);
                    wg_fence();
#pragma unroll
                    for (int ks = 0; ks < 8; ks++)
                        wgmma_rs_n128_ta0_tb0(acc, wf[32 * ch + 4 * ks], wf[32 * ch + 4 * ks + 1], wf[32 * ch + 4 * ks + 2], wf[32 * ch + 4 * ks + 3],
                                              d + (ks >> 2) * 1024 + (ks & 3) * 2, (ch | ks) != 0);
                    wg_commit();
                    if (ch == 3 || (ch < 2 && t == 0)) token_pass(w);
                    if constexpr (ch == 0) {
                        if (t == 0) {
                            if (v) {
                                release(c, BAR_EMPTY + 8 * slot_of(76), 1);
                                asm volatile("fence.proxy.async.shared::cta;" ::: "memory");
                                signal_event(c, EV_CTX + 1);
                                load_wchunk(IC<2>{});
                            } else load_wchunk(IC<1>{});
                        }
                    }
                    if constexpr (ch == 1) { if (t == 0 && !v) load_wchunk(IC<2>{}); }
                    if constexpr (ch == 2) { if (t == 0 && !(w | v)) load_wchunk(IC<3>{}); }
                    if (ch > 0) { wg_wait<1>(); release(c, BAR_EMPTY + 8 * last, 1); }
                    last = cur.slot;
                    cur.adv();
                    if (ch < 3 && t == 0) cur.adv();
                    if constexpr (ch == 1) { if (t == 0 && (w | v)) load_wchunk(IC<3>{}); }
                    if (ch < 2 && t == 0) token_wait(w);
                };
                chunk(IC<0>{}); chunk(IC<1>{}); chunk(IC<2>{}); chunk(IC<3>{});
                wg_wait<0>();
                release(c, BAR_EMPTY + 8 * last, 1);
                fence_regs(acc);
                tile_out(out, (rank ? g_V : g_K) + (size_t)(team * 32 + 2 * (kv_tile(t) + k)) * 16384, 64 * w, rank, c);
                if (t == 3 && w) break;
#pragma unroll
                for (int i = 0; i < 4; i++) store_pair(acc, i, out, 8192, inv);
                if (t >= 2) signal_event(c, EV_KV + 2 * v + t - 2);
            }
        }
        {
            uint32_t q[32], p[32];
            float m[2], l[2];
#pragma unroll
            for (int i = 0; i < 32; i++) p[i] = 0u;
            l[0] = l[1] = 1.f;
            int pv_acc = 1, pv_mode = 2;
#pragma unroll 1
            for (int r = 0; r < 2; r++) {
                const int heavy = 1 ^ r ^ w;
                const int half = 1 ^ heavy ^ rank ^ r;
                int left = 2 * (r ? b1 : b0) + 1 + heavy;
                Cur ck, cv = cur;
                {
                    float s[64];
                    if (r) cur.adv();
                    mbar_wait_hot(misc + BAR_FULL + 8 * cv.slot, cv.ph);
                    token_wait(w);
                    issue_pv(o, p, ring + cv.slot * SLOT_BYTES, pv_acc, pv_mode);
                    undef_regs(s);
                    uint32_t prev;
                    auto qchunk = [&](int acc) {
                        mbar_wait_hot(misc + BAR_FULL + 8 * cur.slot, cur.ph);
                        const uint64_t da = mkdesc(ring + cur.slot * SLOT_BYTES + w * 8192, 16, 1024, 1);
                        const uint64_t db = mkdesc(ring + cur.slot * SLOT_BYTES + 16384, 8192, 1024, 1);
                        wg_fence();
#pragma unroll
                        for (int ks = 0; ks < 4; ks++) wgmma_ss_n128_ta0_tb1(s, da + 2 * ks, db + 128 * ks, ks ? 1 : acc);
                        wg_commit();
                    };
                    qchunk(0);
                    prev = cur.slot; cur.adv();
                    token_pass(w);
                    if (r) {
                        row_inv(l, inv);
                        tile_out(out, g_ctx + (size_t)((team + 16 * v) * 32 + 4 * b0 + (w ? rank : 3 - rank)) * 16384, 0, 0, c);
                    }
                    const int epi = r | w, hs = r ? 4096 : 8192;
                    const int hold = heavy ? -10 : half ? 6 : 8;
#pragma unroll
                    for (int kc = 1; kc < 10; kc++) {
                        if (kc >= 6 && (kc == hold || kc == hold + 2)) token_wait(w);
                        qchunk(1);
                        if (kc > 6 && kc == hold + 1) token_pass(w);
                        if (kc == 9 && heavy) { token_wait(w); token_pass(w); }
                        wg_wait<1>();
                        release(c, BAR_EMPTY + 8 * prev, 1);
                        prev = cur.slot; cur.adv();
                        if (kc == 1) { fence_regs(o); if (r) release(c, BAR_EMPTY + 8 * cv.slot, 1); }
                        if (kc <= 4 && epi) {
                            store_pair(o, kc - 1, out, hs, inv, r > v);
                            if (kc == 4) signal_event(c, r ? EV_CTX + 2 * v : EV_KV + 2 * v + 1);
                        }
                    }
                    if (!heavy) cur.adv();
                    ck = cur;
                    cur.adv();
                    if (!heavy) cur.adv();
                    wg_wait<0>();
                    release(c, BAR_EMPTY + 8 * prev, 1);
                    fence_regs(s);
#pragma unroll
                    for (int i = 0; i < 32; i++) q[i] = pack_bf16(s[2 * i], s[2 * i + 1]);
                }
                int first = 1, gen = 0;
                uint32_t pv_cnt = 0;
                l[0] = l[1] = m[0] = m[1] = 0.f;
                mbar_wait_hot(misc + BAR_FULL + 8 * ck.slot, ck.ph);
                auto diagonal = [&](auto NJC) {
                    constexpr int NJ = decltype(NJC)::value;
                    if (NJ == 16 || heavy) token_wait(w);
                    float sd[4 * NJ];
                    undef_regs(sd);
                    if constexpr (NJ == 8) issue_qk_half(sd, q, ring + ck.slot * SLOT_BYTES); else issue_qk(sd, q, ring + ck.slot * SLOT_BYTES);
                    token_pass(w);
                    wg_wait<0>();
                    fence_regs(sd);
                    mask_diag<NJ - 8>(sd, c);
                    float l0 = 0.f, l1 = 0.f;
#pragma unroll
                    for (int j = 0; j < NJ; j++) {
#pragma unroll
                        for (int e = 0; e < 4; e++) ex2v(sd[4 * j + e]);
                        l0 += sd[4 * j] + sd[4 * j + 1]; l1 += sd[4 * j + 2] + sd[4 * j + 3];
                    }
#pragma unroll
                    for (int i = 0; i < 2 * NJ; i++) p[i] = pack_bf16(sd[2 * i], sd[2 * i + 1]);
                    const int lim = NJ == 8 ? mask_lim(c) : 0;
                    const bool bad = __any_sync(0xffffffffu, !(l0 <= SAFE_SUM && l1 <= SAFE_SUM && (l0 >= 1.0f / SAFE_SUM || lim < 0) &&
                                                               (l1 >= 1.0f / SAFE_SUM || lim < -2)));
                    if (!bad) { l[0] = l0; l[1] = l1; }
                    return bad;
                };
#pragma unroll 1
                while (true) {
                    float s[64];
                    if (first) {
                        --left;
                        if (half ? diagonal(IC<8>{}) : diagonal(IC<16>{})) goto redo;
                        if (left == 0) goto tail;
                        release(c, BAR_EMPTY + 8 * ck.slot, 1 + heavy);
                        pv_acc = 0; pv_mode = half; pv_cnt = 1 + heavy; first = 0;
                        ck = cur; cur.adv(); cv = cur; cur.adv();
                        mbar_wait_hot(misc + BAR_FULL + 8 * ck.slot, ck.ph);
                    }
#pragma unroll 1
                    while (true) {
                        token_wait(w);
                        undef_regs(s);
                        issue_qk(s, q, ring + ck.slot * SLOT_BYTES);
                        Cur nck = cur, ncv = cur, ncur;
                        ncv.adv(); ncur = ncv; ncur.adv();
                        --left;
                        mbar_wait_hot(misc + BAR_FULL + 8 * cv.slot, cv.ph);
                        issue_pv(o, p, ring + cv.slot * SLOT_BYTES, pv_acc, pv_mode & 1);
                        token_pass(w);
                        wg_wait<1>();
                        fence_regs(s);
                        constexpr int JB = 11;
                        float l0 = l[0], l1 = l[1];
                        if (!gen) {
#pragma unroll
                            for (int j = 0; j < JB; j++) {
#pragma unroll
                                for (int e = 0; e < 4; e++) ex2v(s[4 * j + e]);
                                if (j < JB - 1) { l0 += s[4 * j] + s[4 * j + 1]; l1 += s[4 * j + 2] + s[4 * j + 3]; }
                            }
                        }
                        wg_wait<0>();
                        fence_regs(o);
                        if (gen) goto general;
#pragma unroll
                        for (int j = JB - 1; j < 16; j++) {
                            if (j >= JB) {
#pragma unroll
                                for (int e = 0; e < 4; e++) ex2v(s[4 * j + e]);
                            }
                            l0 += s[4 * j] + s[4 * j + 1]; l1 += s[4 * j + 2] + s[4 * j + 3];
                        }
#pragma unroll
                        for (int i = 0; i < 32; i++) p[i] = pack_bf16(s[2 * i], s[2 * i + 1]);
                        if (__any_sync(0xffffffffu, !(l0 <= SAFE_SUM && l1 <= SAFE_SUM))) goto redo;
                        l[0] = l0; l[1] = l1;
                        if (left == 0) goto tail;
                        release(c, BAR_EMPTY + 8 * ck.slot, 1);
                        release(c, BAR_EMPTY + 8 * cv.slot, pv_cnt);
                        pv_acc = 1; pv_mode = 0; pv_cnt = 1;
                        ck = nck; cv = ncv; cur = ncur;
                        mbar_wait_hot(misc + BAR_FULL + 8 * ck.slot, ck.ph);
                    }
                redo:
                    recompute_scores(s, q, ring + ck.slot * SLOT_BYTES, c);
                    if (first) { mask_any(s, half ^ 1, c); m[0] = m[1] = -INFINITY; }
                    gen = 1;
                general:
                    {
                        float mx[2], alpha[2];
                        row_max<16>(s, mx);
#pragma unroll
                        for (int i = 0; i < 2; i++) {
                            mx[i] = fmaxf(mx[i], m[i]);
                            alpha[i] = ex2(m[i] - mx[i]);
                            m[i] = mx[i];
                            l[i] *= alpha[i];
                        }
                        exp_sum<16, true>(s, m, l[0], l[1]);
#pragma unroll
                        for (int i = 0; i < 64; i++) o[i] *= alpha[(i >> 1) & 1];
#pragma unroll
                        for (int i = 0; i < 32; i++) p[i] = pack_bf16(s[2 * i], s[2 * i + 1]);
                    }
                tail:
                    release(c, BAR_EMPTY + 8 * ck.slot, 1 + (first & heavy));
                    if (pv_cnt) release(c, BAR_EMPTY + 8 * cv.slot, pv_cnt);
                    pv_acc = first ^ 1; pv_mode = first & half; pv_cnt = 1 + (first & heavy); first = 0;
                    if (left == 0) break;
                    ck = cur; cur.adv(); cv = cur; cur.adv();
                    mbar_wait_hot(misc + BAR_FULL + 8 * ck.slot, ck.ph);
                }
            }
            mbar_wait_hot(misc + BAR_FULL + 8 * cur.slot, cur.ph);
            token_wait(w);
            issue_pv(o, p, ring + cur.slot * SLOT_BYTES, 1, 0);
            if (w == 0 || v == 0) token_pass(w);
            const uint32_t vslot = cur.slot;
            cur.adv();
            row_inv(l, inv);
            if (v) {
                wg_wait<0>();
                release(c, BAR_EMPTY + 8 * vslot, 1);
                fence_regs(o);
                tile_out(out, g_ctx + (size_t)((team + 16) * 32 + 4 * b1 + (w ? 3 - (rank ^ 1) : rank ^ 1)) * 16384, 0, 0, c);
#pragma unroll
                for (int i = 0; i < 64; i++) wf[i] = 0u;
                continue;
            }
            cw = cur_at(80);
            mbar_wait_hot(misc + BAR_FULL + 8 * slot_of(76), cur_at(76).ph);
            mbar_wait_hot(misc + BAR_FULL + 8 * slot_of(78), cur_at(78).ph);
            load_afrag<8, 32>(wf, ring + slot_of(78) * SLOT_BYTES + w * 16384, c);
            load_afrag<8, 0>(wf, ring + slot_of(76) * SLOT_BYTES + w * 16384, c);
            asm volatile("{\n.reg .pred p;\nsetp.eq.u32 p, %0, 0;\n@p bar.sync 4, 128;\n@!p bar.sync 5, 128;\n}\n" ::"r"(w) : "memory");
            wg_wait<0>();
            release(c, BAR_EMPTY + 8 * vslot, 1);
            fence_regs(o);
            {
                const uint32_t base = ring + slot_of(78) * SLOT_BYTES + w * 16384 + (16 * c.warp + (c.lane >> 2)) * 64 + (((c.lane ^ (c.lane >> 3)) & 3) << 4);
#pragma unroll
                for (int i = 0; i < 2; i++)
#pragma unroll
                    for (int qq = 0; qq < 4; qq++)
                        asm volatile("st.shared.v4.b32 [%0], {%1,%2,%3,%4};" ::"r"(base + qq * 4096 + i * 512),
                                     "r"(pack_bf16(o[16 * qq + 2 * i] * inv[i], o[16 * qq + 2 * i + 1] * inv[i])),
                                     "r"(pack_bf16(o[16 * qq + 4 + 2 * i] * inv[i], o[16 * qq + 4 + 2 * i + 1] * inv[i])),
                                     "r"(pack_bf16(o[16 * qq + 8 + 2 * i] * inv[i], o[16 * qq + 8 + 2 * i + 1] * inv[i])),
                                     "r"(pack_bf16(o[16 * qq + 12 + 2 * i] * inv[i], o[16 * qq + 12 + 2 * i + 1] * inv[i])) : "memory");
            }
        }
        }
        {
            float acc[80];
            undef_regs(acc);
            int st = 0, prev = 0; uint32_t ph3 = 0;
            auto op_stage = [&](int i) {
                mbar_wait_hot(misc + BAR_FULL3 + 8 * st, ph3);
                uint32_t base = ring + st * ST3_BYTES;
                uint64_t da = mkdesc(base + w * 8192, 16, 512, 2);
                uint64_t db = mkdesc(base + 16384, 2048, 512, 2);
                wg_fence();
#pragma unroll
                for (int k = 0; k < 4; k++) wgmma_ss_n160_ta0_tb1(acc, da + (k >> 1) * 256 + 2 * (k & 1), db + (k >> 1) * 640 + (k & 1) * 64, k ? 1 : i);
                wg_commit();
                if (i > 0 && i <= 32 - NST3) { wg_wait<1>(); release(c, BAR_EMPTY3 + 8 * prev, 1); }
                prev = st;
                if (++st == NST3) { st = 0; ph3 ^= 1; }
            };
#pragma unroll
            for (int i = 0; i < 4; i++) { op_stage(i); store_pair(o, i, out, 4096, inv); }
            signal_event(c, EV_CTX + 3);
            const int split = w ? 32 - OP_HOLD : RES_AT;
#pragma unroll 1
            for (int i = 4; i < split; i++) op_stage(i);
            const uint32_t tag = lds32(misc + MISC_EPOCH) & 1;
            const int g = c.lane >> 2, t = c.lane & 3;
            const int row = (2 * u3 + rank) * 128 + 64 * w + perm32(16 * c.warp + 8 * kap + g);
            const int col = 160 * s3 + 8 * t;
            const int t256 = tid - 128;
            uint4* sendp = g_part + (size_t)cta * 2560 + t256;
            if (c.lane >= 30) stg128(sendp + 9 * 256, tag ^ 1, tag ^ 1, tag ^ 1, tag ^ 1);
            uint4 xv[5], bv[5];
#pragma unroll
            for (int i = 0; i < 5; i++) xv[i] = ldg128(P.x + (size_t)row * DM + col + 32 * i);
            uint2 stat;
            asm volatile("ld.global.cg.v2.b32 {%0,%1}, [%2];" : "=r"(stat.x), "=r"(stat.y) : "l"(g_stats + row) : "memory");
#pragma unroll
            for (int i = 0; i < 5; i++) {
                uint32_t xx[4] = {xv[i].x, xv[i].y, xv[i].z, xv[i].w};
#pragma unroll
                for (int e = 0; e < 4; e++) {
                    asm("sub.rn.bf16x2 %0, %0, %1;" : "+r"(xx[e]) : "r"(stat.x));
                    xx[e] = pack_bf16(bf_lo(xx[e]) * __uint_as_float(stat.y), bf_hi(xx[e]) * __uint_as_float(stat.y));
                }
                bv[i] = make_uint4(xx[0], xx[1], xx[2], xx[3]);
            }
#pragma unroll
            for (int i = 0; i < 5; i++) asm volatile("" : "+r"(bv[i].x), "+r"(bv[i].y), "+r"(bv[i].z), "+r"(bv[i].w));
            if (w) bar_sync(4, 256);
#pragma unroll 1
            for (int i = split; i < 32; i++) op_stage(i);
            if (!w) bar_arrive(4, 256);
            wg_wait<0>();
            fence_regs(acc);
            float keep[40];
#pragma unroll
            for (int j = 0; j < 10; j++) {
                uint32_t v0 = __float_as_uint(kap ? acc[8 * j + 0] : acc[8 * j + 2]), v1 = __float_as_uint(kap ? acc[8 * j + 1] : acc[8 * j + 3]);
                uint32_t v2 = __float_as_uint(kap ? acc[8 * j + 4] : acc[8 * j + 6]), v3 = __float_as_uint(kap ? acc[8 * j + 5] : acc[8 * j + 7]);
                asm volatile("st.relaxed.gpu.global.v4.b32 [%0], {%1,%2,%3,%4};" ::"l"(sendp + j * 256),
                             "r"((v0 & ~1u) | tag), "r"((v1 & ~1u) | tag), "r"((v2 & ~1u) | tag), "r"((v3 & ~1u) | tag) : "memory");
                keep[4 * j + 0] = kap ? acc[8 * j + 2] : acc[8 * j + 0]; keep[4 * j + 1] = kap ? acc[8 * j + 3] : acc[8 * j + 1];
                keep[4 * j + 2] = kap ? acc[8 * j + 6] : acc[8 * j + 4]; keep[4 * j + 3] = kap ? acc[8 * j + 7] : acc[8 * j + 5];
            }
            signal_event(c, EV_END);
            mbar_wait(misc + BAR_SEL, 0);
            int sel = -1;
#pragma unroll
            for (int i = 0; i < TOPC; i++) if ((int)lds32(misc + MISC_SEL + 4 * i) == row) sel = i;
            if (sel >= 0) {
#pragma unroll
                for (int i = 0; i < 5; i++) bv[i] = ldg128(g_brow + sel * DM + col + 32 * i);
            }
            const uint4* recvp = g_part + (size_t)partner * 2560 + t256;
            uint4 rv[10];
            int spins = 0;
            while (true) {
                uint32_t v;
                asm volatile("ld.relaxed.gpu.global.b32 %0, [%1];" : "=r"(v) : "l"(recvp + 9 * 256 + (31 - c.lane)) : "memory");
                if (__all_sync(0xffffffffu, (v & 1u) == tag) || ++spins > 2000000) break;
            }
            while (true) {
                uint32_t bad = 0u;
#pragma unroll
                for (int j = 0; j < 10; j++) {
                    asm volatile("ld.relaxed.gpu.global.v4.b32 {%0,%1,%2,%3}, [%4];"
                                 : "=r"(rv[j].x), "=r"(rv[j].y), "=r"(rv[j].z), "=r"(rv[j].w) : "l"(recvp + j * 256) : "memory");
                }
#pragma unroll
                for (int j = 0; j < 10; j++) {
                    rv[j].x ^= tag; rv[j].y ^= tag; rv[j].z ^= tag; rv[j].w ^= tag;
                    bad |= rv[j].x | rv[j].y | rv[j].z | rv[j].w;
                }
                if (__all_sync(0xffffffffu, (bad & 1u) == 0) || ++spins > 2000000) break;
            }
            uint32_t pk[20];
#pragma unroll
            for (int j = 0; j < 10; j++) {
                pk[2 * j] = pack_bf16(keep[4 * j] + __uint_as_float(rv[j].x), keep[4 * j + 1] + __uint_as_float(rv[j].y));
                pk[2 * j + 1] = pack_bf16(keep[4 * j + 2] + __uint_as_float(rv[j].z), keep[4 * j + 3] + __uint_as_float(rv[j].w));
            }
#pragma unroll
            for (int i = 0; i < 5; i++) {
                uint32_t a0 = pk[4 * i], a1 = pk[4 * i + 1], a2 = pk[4 * i + 2], a3 = pk[4 * i + 3];
                uint32_t x0 = (t & 1) ? a0 : a1, x1 = (t & 1) ? a2 : a3;
                x0 = __shfl_xor_sync(0xffffffffu, x0, 1); x1 = __shfl_xor_sync(0xffffffffu, x1, 1);
                if (t & 1) { a0 = x0; a2 = x1; } else { a1 = x0; a3 = x1; }
                x0 = (t & 2) ? a0 : a2; x1 = (t & 2) ? a1 : a3;
                x0 = __shfl_xor_sync(0xffffffffu, x0, 2); x1 = __shfl_xor_sync(0xffffffffu, x1, 2);
                if (t & 2) { a0 = x0; a1 = x1; } else { a2 = x0; a3 = x1; }
                uint32_t av[4] = {a0, a1, a2, a3};
                uint32_t xx[4] = {xv[i].x, xv[i].y, xv[i].z, xv[i].w}, bb[4] = {bv[i].x, bv[i].y, bv[i].z, bv[i].w};
                uint32_t ov[4];
#pragma unroll
                for (int e = 0; e < 4; e++) {
                    asm("add.rn.bf16x2 %0, %1, %2;" : "=r"(ov[e]) : "r"(xx[e]), "r"(av[e]));
                    asm("add.rn.bf16x2 %0, %0, %1;" : "+r"(ov[e]) : "r"(bb[e]));
                }
                stg128(P.out + (size_t)row * DM + col + 32 * i, ov[0], ov[1], ov[2], ov[3]);
            }
        }
    }
}

typedef CUresult (*EncodeFn)(CUtensorMap*, CUtensorMapDataType, cuuint32_t, void*, const cuuint64_t*, const cuuint64_t*, const cuuint32_t*,
                             const cuuint32_t*, CUtensorMapInterleave, CUtensorMapSwizzle, CUtensorMapL2promotion, CUtensorMapFloatOOBfill);

void make_map2d(EncodeFn enc, CUtensorMap* tm, const void* p, uint64_t cols, uint64_t rows, uint32_t box_rows = 128) {
    cuuint64_t gd[2] = {cols, rows}, gs[1] = {cols * 2};
    cuuint32_t box[2] = {64, box_rows}, es[2] = {1, 1};
    enc(tm, CU_TENSOR_MAP_DATA_TYPE_BFLOAT16, 2, const_cast<void*>(p), gd, gs, box, es, CU_TENSOR_MAP_INTERLEAVE_NONE,
        CU_TENSOR_MAP_SWIZZLE_128B, CU_TENSOR_MAP_L2_PROMOTION_L2_128B, CU_TENSOR_MAP_FLOAT_OOB_FILL_NONE);
}

void make_map3d(EncodeFn enc, CUtensorMap* tm, const void* p, uint64_t cols, uint64_t rows, uint32_t bw, uint32_t nb) {
    cuuint64_t gd[3] = {bw, rows, cols / bw}, gs[2] = {cols * 2, bw * 2};
    cuuint32_t box[3] = {bw, 32, nb}, es[3] = {1, 1, 1};
    enc(tm, CU_TENSOR_MAP_DATA_TYPE_BFLOAT16, 3, const_cast<void*>(p), gd, gs, box, es, CU_TENSOR_MAP_INTERLEAVE_NONE,
        bw == 64 ? CU_TENSOR_MAP_SWIZZLE_128B : CU_TENSOR_MAP_SWIZZLE_64B, CU_TENSOR_MAP_L2_PROMOTION_L2_128B, CU_TENSOR_MAP_FLOAT_OOB_FILL_NONE);
}

}

extern "C" void kernel_launch(void* const* d_in, const int* in_sizes, int n_in, void* d_out, int out_size) {
    (void)in_sizes; (void)n_in; (void)out_size;
    static EncodeFn enc = nullptr;
    if (!enc) {
        void* fn = nullptr;
        cudaDriverEntryPointQueryResult qr;
        cudaGetDriverEntryPoint("cuTensorMapEncodeTiled", &fn, cudaEnableDefault, &qr);
        enc = (EncodeFn)fn;
        cudaFuncSetAttribute(fused_kernel, cudaFuncAttributeMaxDynamicSharedMemorySize, SMEM_BYTES);
    }
    CUtensorMap tmC, tmWk, tmWv, tmWq, tmWo, tmG, tmU, tmD;
    make_map2d(enc, &tmC, d_in[1], DC, SEQ);
    make_map2d(enc, &tmWq, d_in[2], 4096, DM, 64);
    make_map2d(enc, &tmWk, d_in[3], 4096, DC);
    make_map2d(enc, &tmWv, d_in[4], 4096, DC);
    make_map3d(enc, &tmWo, d_in[5], DM, 4096, 32, 5);
    make_map3d(enc, &tmG, d_in[8], FF, DM, 64, 7);
    make_map3d(enc, &tmU, d_in[9], FF, DM, 64, 7);
    make_map3d(enc, &tmD, d_in[10], DM, FF, 64, 10);
    Params P;
    P.x = (const __nv_bfloat16*)d_in[0];
    P.c = (const __nv_bfloat16*)d_in[1];
    P.wk = (const __nv_bfloat16*)d_in[3];
    P.wv = (const __nv_bfloat16*)d_in[4];
    P.wo = (const __nv_bfloat16*)d_in[5];
    P.wr = (const __nv_bfloat16*)d_in[7];
    P.out = (__nv_bfloat16*)d_out;
    fused_kernel<<<132, 384, SMEM_BYTES>>>(tmC, tmWk, tmWv, tmWq, tmWo, tmG, tmU, tmD, P);
}
```

```cpp
#include <cuda_runtime.h>
#include <cuda_bf16.h>
#include <cuda.h>
#include <stdint.h>

namespace {

constexpr int SEQ = 2048, NH = 32, DM = 640, DC = 512, FF = 1728, TOPC = 8;
constexpr int NSLOT = 7, SLOT_BYTES = 32768;
constexpr int NST3 = 6, ST3_BYTES = 36864;
constexpr int RING_BYTES = NSLOT * SLOT_BYTES;
constexpr int SMEM_BYTES = RING_BYTES + 3072;
constexpr int OP_PF = 8, PF_START = 9, LATE_AT = 18, RES_AT = 23, OP_HOLD = 4;

constexpr int BAR_FULL = 0  , BAR_EMPTY = 64  , BAR_FULL3 = 128  , BAR_EMPTY3 = 192  , BAR_DEP = 256  ,
              BAR_EV = 448  , BAR_PROG = 592  , BAR_SEL = 616, BAR_LN = 624,
              MISC_EPOCH = 640, MISC_SMID = 644  , MISC_SEL = 656, MISC_WR = 1024  ;
constexpr int D_LN = 0  , D_KV = 2  , D_WAR = 6  , D_CTX = 8  ;
constexpr int EV_KV = 0  , EV_CTX = 4  , EV_END = 8, NEV = 9;

constexpr int FL_MOE_CNT = 0, FL_MOE_DONE = 1, FL_LN = 16  , FL_KV = 32  , FL_CTX = 160  , FL_WAR = 416  , FL_TOTAL = 448;

__device__ __align__(1024) unsigned char g_K[16 * 32 * 16384];
__device__ __align__(1024) unsigned char g_V[16 * 32 * 16384];
__device__ __align__(1024) unsigned char g_ctx[NH * 32 * 16384];
__device__ __align__(1024) unsigned char g_xn[16 * 10 * 16384];
__device__ __align__(1024) uint4 g_part[128 * 10 * 256];
__device__ float g_router[SEQ];
__device__ uint2 g_stats[SEQ];
__device__ __align__(16) float g_moe_part[4 * TOPC * DM];
__device__ __align__(16) __nv_bfloat16 g_brow[TOPC * DM];
__device__ __align__(16) int g_sel[TOPC];
__device__ unsigned g_flags[FL_TOTAL * 8];
__device__ unsigned g_epoch;
__device__ unsigned g_roleq[130];
struct Params {
    const __nv_bfloat16 *x, *c, *wr, *wk, *wv, *wo;
    __nv_bfloat16* out;
};

__device__ __forceinline__ uint32_t smem_u32(const void* p) { return (uint32_t)__cvta_generic_to_shared(p); }
__device__ __forceinline__ void mbar_init(uint32_t bar, int cnt) { asm volatile("mbarrier.init.shared::cta.b64 [%0], %1;" ::"r"(bar), "r"(cnt)); }
__device__ __forceinline__ void mbar_expect_tx(uint32_t bar, uint32_t bytes) {
    asm volatile("mbarrier.arrive.expect_tx.shared::cta.b64 _, [%0], %1;" ::"r"(bar), "r"(bytes) : "memory");
}
__device__ __forceinline__ void mbar_arrive(uint32_t bar) { asm volatile("mbarrier.arrive.shared::cta.b64 _, [%0];" ::"r"(bar) : "memory"); }
__device__ __forceinline__ void mbar_arrive_cluster(uint32_t cluster_addr, uint32_t cnt) {
    asm volatile("mbarrier.arrive.shared::cluster.b64 _, [%0], %1;" ::"r"(cluster_addr), "r"(cnt) : "memory");
}
__device__ __forceinline__ uint32_t mapa(uint32_t addr, uint32_t cta) {
    uint32_t r; asm("mapa.shared::cluster.u32 %0, %1, %2;" : "=r"(r) : "r"(addr), "r"(cta)); return r;
}
__device__ __forceinline__ void mbar_wait(uint32_t bar, uint32_t parity) {
    asm volatile(
        "{\n.reg .pred p;\n.reg .u32 n;\n"
        "mov.u32 n, 0;\n"
        "LAB_WAIT:\n"
        "mbarrier.try_wait.parity.shared::cta.b64 p, [%0], %1, 100000;\n"
        "@p bra DONE;\n"
        "add.u32 n, n, 1;\n"
        "setp.lt.u32 p, n, 50000;\n"
        "@p bra LAB_WAIT;\n"
        "trap;\n"
        "DONE:\n}\n" ::"r"(bar), "r"(parity) : "memory");
}
__device__ __forceinline__ void mbar_wait_hot(uint32_t bar, uint32_t parity) {
    asm volatile("{\n.reg .pred p;\nLAB_WAIT:\nmbarrier.try_wait.parity.shared::cta.b64 p, [%0], %1;\n@!p bra LAB_WAIT;\n}\n" ::"r"(bar), "r"(parity) : "memory");
}
__device__ __forceinline__ void mbar_wait_sleep(uint32_t bar, uint32_t parity) {
    asm volatile("{\n.reg .pred p;\nLAB_WAIT:\nmbarrier.try_wait.parity.shared::cta.b64 p, [%0], %1, 100000;\n@!p bra LAB_WAIT;\n}\n" ::"r"(bar), "r"(parity) : "memory");
}
__device__ __forceinline__ void flag_wait(const unsigned* flag, unsigned target) {
    asm volatile(
        "{\n.reg .pred p;\n.reg .u32 n, v;\n.reg .s32 d;\n"
        "mov.u32 n, 0;\n"
        "LAB_WAIT:\n"
        "ld.acquire.gpu.global.u32 v, [%0];\n"
        "sub.s32 d, v, %1;\n"
        "setp.ge.s32 p, d, 0;\n"
        "@p bra DONE;\n"
        "nanosleep.u32 40;\n"
        "add.u32 n, n, 1;\n"
        "setp.lt.u32 p, n, 3000000;\n"
        "@p bra LAB_WAIT;\n"
        "trap;\n"
        "DONE:\n}\n" ::"l"(flag), "r"(target) : "memory");
}
__device__ __forceinline__ void flag_signal(unsigned* flag) {
    asm volatile("red.release.gpu.global.add.u32 [%0], 1;" ::"l"(flag) : "memory");
}
__device__ __forceinline__ void fence_async_global() { asm volatile("fence.proxy.async.global;" ::: "memory"); }
__device__ __forceinline__ unsigned* flag_ptr(int idx) { return g_flags + idx * 8; }

__device__ __forceinline__ uint64_t policy_stream() {
    uint64_t p; asm("createpolicy.fractional.L2::evict_first.b64 %0, 1.0;" : "=l"(p)); return p;
}
__device__ __forceinline__ void bulk_load(uint32_t dst, const void* src, uint32_t bytes, uint32_t bar) {
    asm volatile("cp.async.bulk.shared::cluster.global.mbarrier::complete_tx::bytes [%0], [%1], %2, [%3];"
                 ::"r"(dst), "l"(src), "r"(bytes), "r"(bar) : "memory");
}
__device__ __forceinline__ void bulk_load_mc(uint32_t dst, const void* src, uint32_t bytes, uint32_t bar) {
    asm volatile("cp.async.bulk.shared::cluster.global.mbarrier::complete_tx::bytes.multicast::cluster [%0], [%1], %2, [%3], %4;"
                 ::"r"(dst), "l"(src), "r"(bytes), "r"(bar), "h"((uint16_t)3) : "memory");
}
__device__ __forceinline__ void tma2d(uint32_t dst, const CUtensorMap* tm, int c0, int c1, uint32_t bar) {
    asm volatile("cp.async.bulk.tensor.2d.shared::cluster.global.mbarrier::complete_tx::bytes [%0], [%1, {%3, %4}], [%2];"
                 ::"r"(dst), "l"(tm), "r"(bar), "r"(c0), "r"(c1) : "memory");
}
__device__ __forceinline__ void tma2d_mc(uint32_t dst, const CUtensorMap* tm, int c0, int c1, uint32_t bar) {
    asm volatile("cp.async.bulk.tensor.2d.shared::cluster.global.mbarrier::complete_tx::bytes.multicast::cluster [%0], [%1, {%3, %4}], [%2], %5;"
                 ::"r"(dst), "l"(tm), "r"(bar), "r"(c0), "r"(c1), "h"((uint16_t)3) : "memory");
}
__device__ __forceinline__ void tma3d_mc(uint32_t dst, const CUtensorMap* tm, int c0, int c1, int c2, uint32_t bar) {
    asm volatile("cp.async.bulk.tensor.3d.shared::cluster.global.mbarrier::complete_tx::bytes.multicast::cluster [%0], [%1, {%3, %4, %5}], [%2], %6;"
                 ::"r"(dst), "l"(tm), "r"(bar), "r"(c0), "r"(c1), "r"(c2), "h"((uint16_t)3) : "memory");
}
__device__ __forceinline__ void tma3d(uint32_t dst, const CUtensorMap* tm, int c0, int c1, int c2, uint32_t bar) {
    asm volatile("cp.async.bulk.tensor.3d.shared::cluster.global.mbarrier::complete_tx::bytes.L2::cache_hint [%0], [%1, {%3, %4, %5}], [%2], %6;"
                 ::"r"(dst), "l"(tm), "r"(bar), "r"(c0), "r"(c1), "r"(c2), "l"(policy_stream()) : "memory");
}
__device__ __forceinline__ void tma2d_prefetch(const CUtensorMap* tm, int c0, int c1) {
    asm volatile("cp.async.bulk.prefetch.tensor.2d.L2.global [%0, {%1, %2}];" ::"l"(tm), "r"(c0), "r"(c1) : "memory");
}
__device__ __forceinline__ void tma3d_prefetch(const CUtensorMap* tm, int c0, int c1, int c2) {
    asm volatile("cp.async.bulk.prefetch.tensor.3d.L2.global [%0, {%1, %2, %3}];" ::"l"(tm), "r"(c0), "r"(c1), "r"(c2) : "memory");
}
__device__ __forceinline__ void l2_prefetch(const void* p, uint32_t bytes) {
    asm volatile("cp.async.bulk.prefetch.L2.global [%0], %1;" ::"l"(p), "r"(bytes) : "memory");
}
__device__ __forceinline__ bool elect_one() {
    uint32_t r; asm volatile("{\n.reg .pred p;\nelect.sync _|p, 0xffffffff;\nselp.u32 %0, 1, 0, p;\n}\n" : "=r"(r)); return r != 0;
}
__device__ __forceinline__ void wg_fence() { asm volatile("wgmma.fence.sync.aligned;" ::: "memory"); }
__device__ __forceinline__ void wg_commit() { asm volatile("wgmma.commit_group.sync.aligned;" ::: "memory"); }
template <int N> __device__ __forceinline__ void wg_wait() { asm volatile("wgmma.wait_group.sync.aligned %0;" ::"n"(N) : "memory"); }
__device__ __forceinline__ void bar_sync(int id, int n) { asm volatile("bar.sync %0, %1;" ::"r"(id), "r"(n) : "memory"); }
__device__ __forceinline__ void bar_arrive(int id, int n) { asm volatile("bar.arrive %0, %1;" ::"r"(id), "r"(n) : "memory"); }
__device__ __forceinline__ void token_wait(int w) {
    asm volatile("{\n.reg .pred p;\nsetp.eq.u32 p, %0, 0;\n@p bar.sync 1, 256;\n@!p bar.sync 2, 256;\n}\n" ::"r"(w) : "memory");
}
__device__ __forceinline__ void token_pass(int w) {
    asm volatile("{\n.reg .pred p;\nsetp.eq.u32 p, %0, 0;\n@p bar.arrive 2, 256;\n@!p bar.arrive 1, 256;\n}\n" ::"r"(w) : "memory");
}
template <int N> __device__ __forceinline__ void fence_regs(float (&a)[N]) {
#pragma unroll
    for (int i = 0; i < N; i++) asm volatile("" : "+f"(a[i])::"memory");
}
template <int N> __device__ __forceinline__ void undef_regs(float (&a)[N]) {
#pragma unroll
    for (int i = 0; i < N; i++) asm volatile("" : "=f"(a[i]));
}
__device__ __forceinline__ void ldsm4t(uint32_t& r0, uint32_t& r1, uint32_t& r2, uint32_t& r3, uint32_t addr) {
    asm volatile("ldmatrix.sync.aligned.m8n8.x4.trans.shared.b16 {%0,%1,%2,%3}, [%4];"
                 : "=r"(r0), "=r"(r1), "=r"(r2), "=r"(r3) : "r"(addr) : "memory");
}
__device__ __forceinline__ uint32_t pack_bf16(float lo, float hi) {
    uint32_t r; asm("cvt.rn.bf16x2.f32 %0, %1, %2;" : "=r"(r) : "f"(hi), "f"(lo)); return r;
}
__device__ __forceinline__ float bf_lo(uint32_t v) { return __uint_as_float(v << 16); }
__device__ __forceinline__ float bf_hi(uint32_t v) { return __uint_as_float(v & 0xffff0000u); }
__device__ __forceinline__ float bf_round(float v) { return __bfloat162float(__float2bfloat16_rn(v)); }
__device__ __forceinline__ float ex2(float v) { float r; asm("ex2.approx.ftz.f32 %0, %1;" : "=f"(r) : "f"(v)); return r; }
__device__ __forceinline__ void ex2v(float& v) { asm volatile("ex2.approx.ftz.f32 %0, %0;" : "+f"(v)); }
__device__ __forceinline__ float rcp_fast(float v) { float r; asm("rcp.approx.ftz.f32 %0, %1;" : "=f"(r) : "f"(v)); return r; }
__device__ __forceinline__ float sqrt_fast(float v) { float r; asm("sqrt.approx.ftz.f32 %0, %1;" : "=f"(r) : "f"(v)); return r; }
__device__ __forceinline__ void stg128(void* p, uint32_t a, uint32_t b, uint32_t c, uint32_t d) {
    asm volatile("st.global.v4.b32 [%0], {%1,%2,%3,%4};" ::"l"(p), "r"(a), "r"(b), "r"(c), "r"(d) : "memory");
}
__device__ __forceinline__ void stg128_hint(void* p, uint32_t a, uint32_t b, uint32_t c, uint32_t d, uint64_t pol) {
    asm volatile("st.global.L2::cache_hint.v4.b32 [%0], {%1,%2,%3,%4}, %5;" ::"l"(p), "r"(a), "r"(b), "r"(c), "r"(d), "l"(pol) : "memory");
}
__device__ __forceinline__ uint4 ldg128(const void* p) {
    uint4 v; asm volatile("ld.global.cg.v4.b32 {%0,%1,%2,%3}, [%4];" : "=r"(v.x), "=r"(v.y), "=r"(v.z), "=r"(v.w) : "l"(p) : "memory"); return v;
}
__device__ __forceinline__ uint64_t mkdesc(uint32_t addr, uint32_t lbo, uint32_t sbo, uint32_t swz) {
    uint32_t lo = ((addr & 0x3FFFF) >> 4) | ((lbo >> 4) << 16);
    uint32_t hi = (sbo >> 4) | (swz << 30);
    return ((uint64_t)hi << 32) | lo;
}
__device__ __forceinline__ int perm32(int v) { return (v & ~30) | ((v >> 2) & 6) | ((v << 2) & 24); }

__device__ __forceinline__ void wgmma_rs_n128_ta0_tb0(float (&d)[64], uint32_t a0, uint32_t a1, uint32_t a2, uint32_t a3, uint64_t descB, int scaleD) {
  asm volatile("{\n.reg .pred p;\nsetp.ne.b32 p, %69, 0;\n"
    "wgmma.mma_async.sync.aligned.m64n128k16.f32.bf16.bf16 "
    "{%0, %1, %2, %3, %4, %5, %6, %7, %8, %9, %10, %11, %12, %13, %14, %15, %16, %17, %18, %19, %20, %21, %22, %23, %24, %25, %26, %27, %28, %29, %30, %31, %32, %33, %34, %35, %36, %37, %38, %39, %40, %41, %42, %43, %44, %45, %46, %47, %48, %49, %50, %51, %52, %53, %54, %55, %56, %57, %58, %59, %60, %61, %62, %63}, "
    "{%64, %65, %66, %67}, %68, p, 1, 1, 0;\n}\n"
    : "+f"(d[0]), "+f"(d[1]), "+f"(d[2]), "+f"(d[3]), "+f"(d[4]), "+f"(d[5]), "+f"(d[6]), "+f"(d[7]), "+f"(d[8]), "+f"(d[9]), "+f"(d[10]), "+f"(d[11]), "+f"(d[12]), "+f"(d[13]), "+f"(d[14]), "+f"(d[15]), "+f"(d[16]), "+f"(d[17]), "+f"(d[18]), "+f"(d[19]), "+f"(d[20]), "+f"(d[21]), "+f"(d[22]), "+f"(d[23]), "+f"(d[24]), "+f"(d[25]), "+f"(d[26]), "+f"(d[27]), "+f"(d[28]), "+f"(d[29]), "+f"(d[30]), "+f"(d[31]), "+f"(d[32]), "+f"(d[33]), "+f"(d[34]), "+f"(d[35]), "+f"(d[36]), "+f"(d[37]), "+f"(d[38]), "+f"(d[39]), "+f"(d[40]), "+f"(d[41]), "+f"(d[42]), "+f"(d[43]), "+f"(d[44]), "+f"(d[45]), "+f"(d[46]), "+f"(d[47]), "+f"(d[48]), "+f"(d[49]), "+f"(d[50]), "+f"(d[51]), "+f"(d[52]), "+f"(d[53]), "+f"(d[54]), "+f"(d[55]), "+f"(d[56]), "+f"(d[57]), "+f"(d[58]), "+f"(d[59]), "+f"(d[60]), "+f"(d[61]), "+f"(d[62]), "+f"(d[63])
    : "r"(a0), "r"(a1), "r"(a2), "r"(a3), "l"(descB), "r"(scaleD));
}
__device__ __forceinline__ void wgmma_rs_n128_ta0_tb1(float (&d)[64], uint32_t a0, uint32_t a1, uint32_t a2, uint32_t a3, uint64_t descB, int scaleD) {
  asm volatile("{\n.reg .pred p;\nsetp.ne.b32 p, %69, 0;\n"
    "wgmma.mma_async.sync.aligned.m64n128k16.f32.bf16.bf16 "
    "{%0, %1, %2, %3, %4, %5, %6, %7, %8, %9, %10, %11, %12, %13, %14, %15, %16, %17, %18, %19, %20, %21, %22, %23, %24, %25, %26, %27, %28, %29, %30, %31, %32, %33, %34, %35, %36, %37, %38, %39, %40, %41, %42, %43, %44, %45, %46, %47, %48, %49, %50, %51, %52, %53, %54, %55, %56, %57, %58, %59, %60, %61, %62, %63}, "
    "{%64, %65, %66, %67}, %68, p, 1, 1, 1;\n}\n"
    : "+f"(d[0]), "+f"(d[1]), "+f"(d[2]), "+f"(d[3]), "+f"(d[4]), "+f"(d[5]), "+f"(d[6]), "+f"(d[7]), "+f"(d[8]), "+f"(d[9]), "+f"(d[10]), "+f"(d[11]), "+f"(d[12]), "+f"(d[13]), "+f"(d[14]), "+f"(d[15]), "+f"(d[16]), "+f"(d[17]), "+f"(d[18]), "+f"(d[19]), "+f"(d[20]), "+f"(d[21]), "+f"(d[22]), "+f"(d[23]), "+f"(d[24]), "+f"(d[25]), "+f"(d[26]), "+f"(d[27]), "+f"(d[28]), "+f"(d[29]), "+f"(d[30]), "+f"(d[31]), "+f"(d[32]), "+f"(d[33]), "+f"(d[34]), "+f"(d[35]), "+f"(d[36]), "+f"(d[37]), "+f"(d[38]), "+f"(d[39]), "+f"(d[40]), "+f"(d[41]), "+f"(d[42]), "+f"(d[43]), "+f"(d[44]), "+f"(d[45]), "+f"(d[46]), "+f"(d[47]), "+f"(d[48]), "+f"(d[49]), "+f"(d[50]), "+f"(d[51]), "+f"(d[52]), "+f"(d[53]), "+f"(d[54]), "+f"(d[55]), "+f"(d[56]), "+f"(d[57]), "+f"(d[58]), "+f"(d[59]), "+f"(d[60]), "+f"(d[61]), "+f"(d[62]), "+f"(d[63])
    : "r"(a0), "r"(a1), "r"(a2), "r"(a3), "l"(descB), "r"(scaleD));
}
__device__ __forceinline__ void wgmma_rs_n64_ta0_tb1(float (&d)[32], uint32_t a0, uint32_t a1, uint32_t a2, uint32_t a3, uint64_t descB, int scaleD) {
  asm volatile("{\n.reg .pred p;\nsetp.ne.b32 p, %37, 0;\n"
    "wgmma.mma_async.sync.aligned.m64n64k16.f32.bf16.bf16 "
    "{%0, %1, %2, %3, %4, %5, %6, %7, %8, %9, %10, %11, %12, %13, %14, %15, %16, %17, %18, %19, %20, %21, %22, %23, %24, %25, %26, %27, %28, %29, %30, %31}, "
    "{%32, %33, %34, %35}, %36, p, 1, 1, 1;\n}\n"
    : "+f"(d[0]), "+f"(d[1]), "+f"(d[2]), "+f"(d[3]), "+f"(d[4]), "+f"(d[5]), "+f"(d[6]), "+f"(d[7]), "+f"(d[8]), "+f"(d[9]), "+f"(d[10]), "+f"(d[11]), "+f"(d[12]), "+f"(d[13]), "+f"(d[14]), "+f"(d[15]), "+f"(d[16]), "+f"(d[17]), "+f"(d[18]), "+f"(d[19]), "+f"(d[20]), "+f"(d[21]), "+f"(d[22]), "+f"(d[23]), "+f"(d[24]), "+f"(d[25]), "+f"(d[26]), "+f"(d[27]), "+f"(d[28]), "+f"(d[29]), "+f"(d[30]), "+f"(d[31])
    : "r"(a0), "r"(a1), "r"(a2), "r"(a3), "l"(descB), "r"(scaleD));
}
__device__ __forceinline__ void wgmma_ss_n128_ta0_tb1(float (&d)[64], uint64_t descA, uint64_t descB, int scaleD) {
  asm volatile("{\n.reg .pred p;\nsetp.ne.b32 p, %66, 0;\n"
    "wgmma.mma_async.sync.aligned.m64n128k16.f32.bf16.bf16 "
    "{%0, %1, %2, %3, %4, %5, %6, %7, %8, %9, %10, %11, %12, %13, %14, %15, %16, %17, %18, %19, %20, %21, %22, %23, %24, %25, %26, %27, %28, %29, %30, %31, %32, %33, %34, %35, %36, %37, %38, %39, %40, %41, %42, %43, %44, %45, %46, %47, %48, %49, %50, %51, %52, %53, %54, %55, %56, %57, %58, %59, %60, %61, %62, %63}, "
    "%64, %65, p, 1, 1, 0, 1;\n}\n"
    : "+f"(d[0]), "+f"(d[1]), "+f"(d[2]), "+f"(d[3]), "+f"(d[4]), "+f"(d[5]), "+f"(d[6]), "+f"(d[7]), "+f"(d[8]), "+f"(d[9]), "+f"(d[10]), "+f"(d[11]), "+f"(d[12]), "+f"(d[13]), "+f"(d[14]), "+f"(d[15]), "+f"(d[16]), "+f"(d[17]), "+f"(d[18]), "+f"(d[19]), "+f"(d[20]), "+f"(d[21]), "+f"(d[22]), "+f"(d[23]), "+f"(d[24]), "+f"(d[25]), "+f"(d[26]), "+f"(d[27]), "+f"(d[28]), "+f"(d[29]), "+f"(d[30]), "+f"(d[31]), "+f"(d[32]), "+f"(d[33]), "+f"(d[34]), "+f"(d[35]), "+f"(d[36]), "+f"(d[37]), "+f"(d[38]), "+f"(d[39]), "+f"(d[40]), "+f"(d[41]), "+f"(d[42]), "+f"(d[43]), "+f"(d[44]), "+f"(d[45]), "+f"(d[46]), "+f"(d[47]), "+f"(d[48]), "+f"(d[49]), "+f"(d[50]), "+f"(d[51]), "+f"(d[52]), "+f"(d[53]), "+f"(d[54]), "+f"(d[55]), "+f"(d[56]), "+f"(d[57]), "+f"(d[58]), "+f"(d[59]), "+f"(d[60]), "+f"(d[61]), "+f"(d[62]), "+f"(d[63])
    : "l"(descA), "l"(descB), "r"(scaleD));
}
__device__ __forceinline__ void wgmma_ss_n160_ta0_tb1(float (&d)[80], uint64_t descA, uint64_t descB, int scaleD) {
  asm volatile("{\n.reg .pred p;\nsetp.ne.b32 p, %82, 0;\n"
    "wgmma.mma_async.sync.aligned.m64n160k16.f32.bf16.bf16 "
    "{%0, %1, %2, %3, %4, %5, %6, %7, %8, %9, %10, %11, %12, %13, %14, %15, %16, %17, %18, %19, %20, %21, %22, %23, %24, %25, %26, %27, %28, %29, %30, %31, %32, %33, %34, %35, %36, %37, %38, %39, %40, %41, %42, %43, %44, %45, %46, %47, %48, %49, %50, %51, %52, %53, %54, %55, %56, %57, %58, %59, %60, %61, %62, %63, %64, %65, %66, %67, %68, %69, %70, %71, %72, %73, %74, %75, %76, %77, %78, %79}, "
    "%80, %81, p, 1, 1, 0, 1;\n}\n"
    : "+f"(d[0]), "+f"(d[1]), "+f"(d[2]), "+f"(d[3]), "+f"(d[4]), "+f"(d[5]), "+f"(d[6]), "+f"(d[7]), "+f"(d[8]), "+f"(d[9]), "+f"(d[10]), "+f"(d[11]), "+f"(d[12]), "+f"(d[13]), "+f"(d[14]), "+f"(d[15]), "+f"(d[16]), "+f"(d[17]), "+f"(d[18]), "+f"(d[19]), "+f"(d[20]), "+f"(d[21]), "+f"(d[22]), "+f"(d[23]), "+f"(d[24]), "+f"(d[25]), "+f"(d[26]), "+f"(d[27]), "+f"(d[28]), "+f"(d[29]), "+f"(d[30]), "+f"(d[31]), "+f"(d[32]), "+f"(d[33]), "+f"(d[34]), "+f"(d[35]), "+f"(d[36]), "+f"(d[37]), "+f"(d[38]), "+f"(d[39]), "+f"(d[40]), "+f"(d[41]), "+f"(d[42]), "+f"(d[43]), "+f"(d[44]), "+f"(d[45]), "+f"(d[46]), "+f"(d[47]), "+f"(d[48]), "+f"(d[49]), "+f"(d[50]), "+f"(d[51]), "+f"(d[52]), "+f"(d[53]), "+f"(d[54]), "+f"(d[55]), "+f"(d[56]), "+f"(d[57]), "+f"(d[58]), "+f"(d[59]), "+f"(d[60]), "+f"(d[61]), "+f"(d[62]), "+f"(d[63]), "+f"(d[64]), "+f"(d[65]), "+f"(d[66]), "+f"(d[67]), "+f"(d[68]), "+f"(d[69]), "+f"(d[70]), "+f"(d[71]), "+f"(d[72]), "+f"(d[73]), "+f"(d[74]), "+f"(d[75]), "+f"(d[76]), "+f"(d[77]), "+f"(d[78]), "+f"(d[79])
    : "l"(descA), "l"(descB), "r"(scaleD));
}


template <int N> struct IC { static constexpr int value = N; };
struct Cur {
    uint32_t slot, ph;
    __device__ __forceinline__ void adv() { if (++slot == NSLOT) { slot = 0; ph ^= 1; } }
};
constexpr int E0 = 2;
__host__ __device__ constexpr uint32_t slot_of(int e) { return (e + E0) % NSLOT; }
__device__ __forceinline__ Cur cur_at(int e) { Cur c; c.slot = (e + E0) % NSLOT; c.ph = ((e + E0) / NSLOT) & 1; return c; }

__device__ __forceinline__ int kv_tile(int s) { return (0x804Cu >> (4 * s)) & 15; }
__device__ __forceinline__ int op_head(int i, int kap) { return 8 * kap + (i & 7) + 16 * (i >> 3); }

constexpr float SM_SCALE = 0.08838834764831845f * 1.4426950408889634f;

struct Ctx {
    uint32_t ring, misc;
    uint32_t rel;
    int w, warp, lane;
};
__device__ __forceinline__ void release(const Ctx& c, uint32_t off, uint32_t cnt) {
    if (c.lane < 2) mbar_arrive_cluster(c.rel + off, cnt);
}
__device__ __forceinline__ void signal_event(const Ctx& c, int ev) {
    __syncwarp();
    if (c.lane == 0) mbar_arrive(c.misc + BAR_EV + (c.w * NEV + ev) * 8);
}
template <int NK, int OFF, int N>
__device__ __forceinline__ uint32_t load_afrag(uint32_t (&a)[N], uint32_t base, const Ctx& c) {
    int r = c.lane & 7, mat = c.lane >> 3;
    uint32_t addr = base + (8 * (mat >> 1) + r) * 128 + (((2 * c.warp + (mat & 1)) ^ r) << 4);
#pragma unroll
    for (int k = 0; k < NK; k++) ldsm4t(a[OFF + 4 * k], a[OFF + 4 * k + 1], a[OFF + 4 * k + 2], a[OFF + 4 * k + 3], addr + k * 2048);
    uint32_t dep = 0;
#pragma unroll
    for (int k = 0; k < NK; k++) dep |= a[OFF + 4 * k];
    return dep & blockIdx.y;
}
__device__ __forceinline__ void tile_out(unsigned char* (&out)[2], unsigned char* dst, int row0, int perm, const Ctx& c) {
#pragma unroll
    for (int i = 0; i < 2; i++) {
        int row = row0 + 16 * c.warp + 8 * i + (c.lane >> 2);
        if (perm) row = perm32(row);
        out[i] = dst + row * 64 + (((c.lane ^ (row >> 1)) & 3) << 4);
    }
}
__device__ __forceinline__ void store_pair(const float (&a)[64], int q, unsigned char* const (&out)[2], int quarter_stride, const float (&f)[2], bool stream = false) {
    const uint64_t pol = stream ? policy_stream() : 0x1000000000000000ull  ;
#pragma unroll
    for (int i = 0; i < 2; i++)
        stg128_hint(out[i] + q * quarter_stride,
               pack_bf16(a[16 * q + 2 * i] * f[i], a[16 * q + 2 * i + 1] * f[i]), pack_bf16(a[16 * q + 4 + 2 * i] * f[i], a[16 * q + 4 + 2 * i + 1] * f[i]),
               pack_bf16(a[16 * q + 8 + 2 * i] * f[i], a[16 * q + 8 + 2 * i + 1] * f[i]), pack_bf16(a[16 * q + 12 + 2 * i] * f[i], a[16 * q + 12 + 2 * i + 1] * f[i]), pol);
}

constexpr float SAFE_SUM = 1099511627776.0f;
template <int NJ>
__device__ __forceinline__ void row_max(const float (&s)[4 * NJ], float (&mx)[2]) {
#pragma unroll
    for (int i = 0; i < 2; i++) {
        float a = fmaxf(s[2 * i], s[2 * i + 1]), b = fmaxf(s[4 + 2 * i], s[4 + 2 * i + 1]);
#pragma unroll
        for (int j = 2; j < NJ; j += 2) {
            a = fmaxf(a, fmaxf(s[4 * j + 2 * i], s[4 * j + 2 * i + 1]));
            b = fmaxf(b, fmaxf(s[4 * j + 4 + 2 * i], s[4 * j + 4 + 2 * i + 1]));
        }
        a = fmaxf(a, b);
        a = fmaxf(a, __shfl_xor_sync(0xffffffffu, a, 1));
        mx[i] = fmaxf(a, __shfl_xor_sync(0xffffffffu, a, 2));
    }
}
template <int NJ, bool SHIFT>
__device__ __forceinline__ void exp_sum(float (&s)[4 * NJ], const float (&m)[2], float& l0, float& l1) {
#pragma unroll
    for (int j = 0; j < NJ; j++) {
#pragma unroll
        for (int e = 0; e < 4; e++) s[4 * j + e] = ex2(SHIFT ? s[4 * j + e] - m[e >> 1] : s[4 * j + e]);
        l0 += s[4 * j + 0] + s[4 * j + 1]; l1 += s[4 * j + 2] + s[4 * j + 3];
    }
}
__device__ __forceinline__ void recompute_scores(float (&s)[64], const uint32_t (&q)[32], uint32_t kaddr, const Ctx& c) {
    const int r = c.lane & 7, mat = c.lane >> 3;
    const uint32_t a0 = kaddr + (8 * (mat & 1) + r) * 64 + (((mat >> 1) ^ (r >> 1)) << 4);
#pragma unroll
    for (int i = 0; i < 64; i++) s[i] = 0.f;
#pragma unroll
    for (int jp = 0; jp < 8; jp++) {
#pragma unroll
        for (int k = 0; k < 8; k++) {
            asm volatile(
                "{\n.reg .b32 b0, b1, b2, b3;\n"
                "ldmatrix.sync.aligned.m8n8.x4.trans.shared.b16 {b0,b1,b2,b3}, [%12];\n"
                "mma.sync.aligned.m16n8k16.row.col.f32.bf16.bf16.f32 {%0,%1,%2,%3}, {%8,%9,%10,%11}, {b0,b1}, {%0,%1,%2,%3};\n"
                "mma.sync.aligned.m16n8k16.row.col.f32.bf16.bf16.f32 {%4,%5,%6,%7}, {%8,%9,%10,%11}, {b2,b3}, {%4,%5,%6,%7};\n}\n"
                : "+f"(s[8 * jp]), "+f"(s[8 * jp + 1]), "+f"(s[8 * jp + 2]), "+f"(s[8 * jp + 3]),
                  "+f"(s[8 * jp + 4]), "+f"(s[8 * jp + 5]), "+f"(s[8 * jp + 6]), "+f"(s[8 * jp + 7])
                : "r"(q[4 * k]), "r"(q[4 * k + 1]), "r"(q[4 * k + 2]), "r"(q[4 * k + 3]),
                  "r"((a0 ^ ((jp & 1) << 5)) + (jp >> 1) * 8192 + k * 1024) : "memory");
        }
    }
}
__device__ __forceinline__ int mask_lim(const Ctx& c) { return perm32(16 * c.warp + (c.lane >> 2)) - 8 * (c.lane & 3); }
template <int J0>
__device__ __forceinline__ void mask_diag(float (&s)[4 * J0 + 32], const Ctx& c) {
    const int lim = mask_lim(c);
    if (c.warp < 2) {
#pragma unroll
        for (int x = 0; x < 16; x++) {
            if (2 * (x >> 2) + (x & 1) - (x & 2) > lim) s[4 * J0 + x] = -INFINITY;
            s[4 * J0 + 16 + x] = -INFINITY;
        }
    } else {
#pragma unroll
        for (int x = 0; x < 16; x++)
            if (32 + 2 * (x >> 2) + (x & 1) - (x & 2) > lim) s[4 * J0 + 16 + x] = -INFINITY;
    }
}
__device__ __forceinline__ void mask_any(float (&s)[64], int hh, const Ctx& c) {
    const int lim = mask_lim(c) + 64 * hh;
#pragma unroll
    for (int x = 0; x < 64; x++)
        if (32 * (x >> 4) + 2 * ((x >> 2) & 3) + (x & 1) - (x & 2) > lim) s[x] = -INFINITY;
}
__device__ __forceinline__ void issue_pv(float (&o)[64], const uint32_t (&p)[32], uint32_t vaddr, int acc, int mode  ) {
    uint64_t d = mkdesc(vaddr, 16, 512, 2);
    if (mode == 0) {
        wg_fence();
#pragma unroll
        for (int k = 0; k < 8; k++)
            wgmma_rs_n128_ta0_tb0(o, p[4 * k], p[4 * k + 1], p[4 * k + 2], p[4 * k + 3], d + (k >> 1) * 512 + 2 * (k & 1), k ? 1 : acc);
        wg_commit();
    } else if (mode == 1) {
        wg_fence();
#pragma unroll
        for (int k = 0; k < 4; k++) wgmma_rs_n128_ta0_tb0(o, p[4 * k], p[4 * k + 1], p[4 * k + 2], p[4 * k + 3], d + (k >> 1) * 512 + 2 * (k & 1), k != 0);
        wg_commit();
    } else {
        wg_fence();
        wgmma_rs_n128_ta0_tb0(o, p[0], p[1], p[2], p[3], d, acc);
        wg_commit();
    }
}
__device__ __forceinline__ void issue_qk(float (&s)[64], const uint32_t (&q)[32], uint32_t kaddr) {
    uint64_t d = mkdesc(kaddr, 8192, 512, 2);
    wg_fence();
#pragma unroll
    for (int k = 0; k < 8; k++) wgmma_rs_n128_ta0_tb1(s, q[4 * k], q[4 * k + 1], q[4 * k + 2], q[4 * k + 3], d + 64 * k, k != 0);
    wg_commit();
}
__device__ __forceinline__ void issue_qk_half(float (&s32)[32], const uint32_t (&q)[32], uint32_t kaddr) {
    uint64_t d = mkdesc(kaddr, 8192, 512, 2);
    wg_fence();
#pragma unroll
    for (int k = 0; k < 8; k++) wgmma_rs_n64_ta0_tb1(s32, q[4 * k], q[4 * k + 1], q[4 * k + 2], q[4 * k + 3], d + 64 * k, k != 0);
    wg_commit();
}
__device__ __forceinline__ void row_inv(const float (&l)[2], float (&inv)[2]) {
#pragma unroll
    for (int i = 0; i < 2; i++) {
        float sum = l[i];
        sum += __shfl_xor_sync(0xffffffffu, sum, 1);
        sum += __shfl_xor_sync(0xffffffffu, sum, 2);
        inv[i] = rcp_fast(sum);
    }
}

__device__ __forceinline__ const unsigned char* xn_addr(int row, int col) {
    row = perm32(row);
    return g_xn + ((row >> 7) * 10 + (col >> 6)) * 16384 + (row & 127) * 128 + ((((col & 63) >> 3) ^ (row & 7)) << 4);
}
__device__ __forceinline__ void mma16816(float (&d)[4], uint32_t a0, uint32_t a1, uint32_t a2, uint32_t a3, uint32_t b0, uint32_t b1) {
    asm volatile("mma.sync.aligned.m16n8k16.row.col.f32.bf16.bf16.f32 {%0,%1,%2,%3}, {%4,%5,%6,%7}, {%8,%9}, {%0,%1,%2,%3};"
                 : "+f"(d[0]), "+f"(d[1]), "+f"(d[2]), "+f"(d[3]) : "r"(a0), "r"(a1), "r"(a2), "r"(a3), "r"(b0), "r"(b1));
}
__device__ __forceinline__ uint32_t lds32(uint32_t addr) { uint32_t v; asm volatile("ld.shared.u32 %0, [%1];" : "=r"(v) : "r"(addr)); return v; }

__device__ __forceinline__ int fresh_lane() { int l; asm volatile("mov.u32 %0, %%laneid;" : "=r"(l)); return l; }
__device__ __forceinline__ void ln_rows(const __nv_bfloat16* x, int row0, uint32_t wr_s) {
    int lane = fresh_lane();
    int hl = lane & 15, row = row0 + (lane >> 4);
    uint32_t v[20];
#pragma unroll
    for (int i = 0; i < 5; i++) {
        const uint4 u = __ldg(reinterpret_cast<const uint4*>(x + (size_t)row * DM + 128 * i + 8 * hl));
        v[4 * i] = u.x; v[4 * i + 1] = u.y; v[4 * i + 2] = u.z; v[4 * i + 3] = u.w;
    }
    float mean = 0.f, m2 = 0.f, acc2 = 0.f;
#pragma unroll
    for (int i = 0; i < 20; i++) { mean += bf_lo(v[i]); acc2 += bf_hi(v[i]); }
    mean = (mean + acc2) * (1.0f / 40);
    acc2 = 0.f;
#pragma unroll
    for (int i = 0; i < 20; i++) {
        float d0 = __uint_as_float(__byte_perm(v[i], 0, 0x1044)) - mean, d1 = __uint_as_float(__byte_perm(v[i], 0, 0x3244)) - mean;
        m2 = fmaf(d0, d0, m2); acc2 = fmaf(d1, d1, acc2);
    }
    m2 += acc2;
    acc2 = 0.f;
#pragma unroll
    for (int o = 1; o < 16; o <<= 1) {
        float mo = __shfl_xor_sync(0xffffffffu, mean, o), qo = __shfl_xor_sync(0xffffffffu, m2, o), d = mo - mean;
        m2 = fmaf(d * d, 20.0f * o, m2 + qo);
        mean = 0.5f * (mean + mo);
    }
    const uint32_t mb2 = pack_bf16(mean, mean);
    const float inv = rcp_fast(bf_round(sqrt_fast(bf_round(bf_round(m2 * (1.0f / DM)) + 1e-5f))));
    float dot = 0.f;
    lane = fresh_lane(); hl = lane & 15; row = row0 + (lane >> 4);
    if (hl == 0) g_stats[row] = make_uint2(mb2, __float_as_uint(inv));
    unsigned char* xp = const_cast<unsigned char*>(xn_addr(row, 8 * hl));
#pragma unroll
    for (int i = 0; i < 5; i++) {
        uint32_t ww[4];
        asm volatile("ld.shared.v4.b32 {%0,%1,%2,%3}, [%4];" : "=r"(ww[0]), "=r"(ww[1]), "=r"(ww[2]), "=r"(ww[3]) : "r"(wr_s + 256 * i + 16 * hl) : "memory");
#pragma unroll
        for (int e = 0; e < 4; e++) {
            uint32_t d;
            asm("sub.rn.bf16x2 %0, %1, %2;" : "=r"(d) : "r"(v[4 * i + e]), "r"(mb2));
            d = pack_bf16(bf_lo(d) * inv, bf_hi(d) * inv);
            v[4 * i + e] = d;
            dot = fmaf(bf_lo(d), bf_lo(ww[e]), dot);
            acc2 = fmaf(bf_hi(d), bf_hi(ww[e]), acc2);
        }
        stg128(xp + i * 32768, v[4 * i], v[4 * i + 1], v[4 * i + 2], v[4 * i + 3]);
    }
    dot += acc2;
#pragma unroll
    for (int o = 8; o > 0; o >>= 1) dot += __shfl_xor_sync(0xffffffffu, dot, o);
    lane = fresh_lane();
    if ((lane & 15) == 0) g_router[row0 + (lane >> 4)] = bf_round(dot);
}

__device__ __forceinline__ void aux_cta(const CUtensorMap* tmG, const CUtensorMap* tmU, const CUtensorMap* tmD, unsigned char* sm, int a) {
    constexpr int STG = 57344, XS = 3 * STG, HS = XS + 8 * 1296, KEY = HS + 8 * 912, MI = KEY + 8192;
    const int tid = threadIdx.x, warp = __shfl_sync(0xffffffffu, tid >> 5, 0), lane = tid & 31;
    const uint32_t sb = smem_u32(sm);
    const uint32_t full = sb + MI, empty = sb + MI + 32;
    int* s_sel = reinterpret_cast<int*>(sm + MI + 64);
    float* s_r = reinterpret_cast<float*>(sm + MI + 96);
    volatile unsigned* s_misc = reinterpret_cast<volatile unsigned*>(sm + MI + 128);
    uint32_t* s_key = reinterpret_cast<uint32_t*>(sm + KEY);
    if (tid == 0) {
        for (int i = 0; i < 3; i++) { mbar_init(full + 8 * i, 1); mbar_init(empty + 8 * i, 10); }
        asm volatile("fence.mbarrier_init.release.cluster;" ::: "memory");
    }
    __syncthreads();
    if (warp == 11) {
        if (elect_one()) {
            const unsigned ep1 = *reinterpret_cast<volatile unsigned*>(&g_epoch) + 1;
            __nanosleep(20000);
            flag_wait(flag_ptr(FL_CTX + (18 + a) * 8), ep1 * 4u);
            int st = 0; uint32_t ph = 0;
#pragma unroll 1
            for (int s = 0; s < 34; s++) {
                mbar_wait(empty + 8 * st, ph ^ 1);
                const uint32_t dst = sb + st * STG, fb = full + 8 * st;
                if (s < 20) {
                    mbar_expect_tx(fb, 57344);
                    tma3d(dst, tmG, 0, 32 * s, 7 * a, fb);
                    tma3d(dst + 28672, tmU, 0, 32 * s, 7 * a, fb);
                } else {
                    mbar_expect_tx(fb, 40960);
                    tma3d(dst, tmD, 0, 448 * a + 32 * (s - 20), 0, fb);
                }
                if (s >= 2) {
#pragma unroll 1
                    for (int f = (s == 2 ? 3 : s + 6); f <= s + 6 && f < 34; f++) {
                        if (f < 20) { tma3d_prefetch(tmG, 0, 32 * f, 7 * a); tma3d_prefetch(tmU, 0, 32 * f, 7 * a); }
                        else tma3d_prefetch(tmD, 0, 448 * a + 32 * (f - 20), 0);
                    }
                }
                if (++st == 3) { st = 0; ph ^= 1; }
            }
        }
        return;
    }
    if (warp == 10) return;
    if (tid < 8) {
        unsigned e = *reinterpret_cast<volatile unsigned*>(&g_epoch);
        if (tid == 0) s_misc[0] = e;
        flag_wait(flag_ptr(FL_LN + tid), (e + 1) * (tid < 4 ? 64u : 128u));
    }
    bar_sync(1, 320);
    const unsigned ep = s_misc[0];
    auto top8 = [&](uint32_t (&key)[8]) {
        uint32_t mine = 0;
#pragma unroll 1
        for (int r = 0; r < TOPC; r++) {
            uint32_t best = 0;
#pragma unroll
            for (int i = 0; i < 8; i++) best = max(best, key[i]);
            best = __reduce_max_sync(0xffffffffu, best);
#pragma unroll
            for (int i = 0; i < 8; i++) if (key[i] == best) key[i] = 0;
            if (lane == r) mine = best;
        }
        return mine;
    };
#pragma unroll 1
    for (int pass = 0; pass < 2; pass++) {
        if (warp < (pass ? 1 : 8)) {
            uint32_t key[8];
#pragma unroll
            for (int i = 0; i < 8; i++) {
                if (pass == 0) {
                    int idx = warp * 256 + i * 32 + lane;
                    uint32_t b = __float_as_uint(__ldcg(g_router + idx)) >> 16;
                    b = (b & 0x8000u) ? (~b & 0xffffu) : (b | 0x8000u);
                    key[i] = (b << 16) | (uint32_t)(0xffff - idx);
                } else key[i] = i < 2 ? s_key[i * 32 + lane] : 0u;
            }
            uint32_t best = top8(key);
            if (lane < TOPC) {
                if (pass == 0) s_key[warp * 8 + lane] = best;
                else {
                    uint32_t b = best >> 16;
                    b = (b & 0x8000u) ? (b & 0x7fffu) : (~b & 0xffffu);
                    s_sel[lane] = 0xffff - (int)(best & 0xffffu);
                    s_r[lane] = bf_round(rcp_fast(1.0f + __expf(fminf(-__uint_as_float(b << 16), 80.f))));
                }
            }
        }
        bar_sync(1, 320);
    }
#pragma unroll 1
    for (int it = 0; it < 2; it++) {
        int i = tid + it * 320, tk = i / 80, ch = i % 80;
        *reinterpret_cast<uint4*>(sm + XS + tk * 1296 + ch * 16) = __ldcg(reinterpret_cast<const uint4*>(xn_addr(s_sel[tk], ch * 8)));
    }
    bar_sync(1, 320);
    const int g = lane >> 2, t = lane & 3;
    const uint32_t woff = warp * 4096 + (8 * (lane >> 4) + (lane & 7)) * 128 + ((((lane >> 3) & 1) ^ (lane & 7)) << 4);
    int st = 0; uint32_t ph = 0;
    float ga[4][4], ua[4][4];
#pragma unroll
    for (int i = 0; i < 4; i++)
#pragma unroll
        for (int e = 0; e < 4; e++) { ga[i][e] = 0.f; ua[i][e] = 0.f; }
#pragma unroll 1
    for (int s = 0; s < 34; s++) {
        if (s == 20) {
            if (warp < 7) {
#pragma unroll 1
                for (int i = 0; i < 4; i++) {
#pragma unroll
                    for (int e = 0; e < 4; e++) {
                        float gv = bf_round(ga[0][e]), uv = bf_round(ua[0][e]);
                        float sg = bf_round(gv * rcp_fast(1.0f + __expf(fminf(-gv, 80.f))));
                        int f = warp * 64 + i * 16 + g + 8 * (e >> 1), tk = 2 * t + (e & 1);
                        *reinterpret_cast<__nv_bfloat16*>(sm + HS + tk * 912 + f * 2) = __float2bfloat16_rn(sg * uv);
                        ga[0][e] = ga[1][e]; ga[1][e] = ga[2][e]; ga[2][e] = ga[3][e]; ga[3][e] = 0.f;
                        ua[0][e] = ua[1][e]; ua[1][e] = ua[2][e]; ua[2][e] = ua[3][e];
                    }
                }
            }
            bar_sync(1, 320);
        }
        mbar_wait(full + 8 * st, ph);
        if (s >= 20 || warp < 7) {
#pragma unroll
            for (int kk = 0; kk < 2; kk++) {
                uint32_t xb = sb + (s < 20 ? XS + g * 1296 + s * 64 : HS + g * 912 + (s - 20) * 64) + 32 * kk + 4 * t;
                uint32_t b0 = lds32(xb), b1 = lds32(xb + 16);
                uint32_t wa = sb + st * STG + woff + kk * 2048;
#pragma unroll
                for (int i = 0; i < 4; i++) {
                    uint32_t a0, a1, a2, a3;
                    ldsm4t(a0, a1, a2, a3, wa ^ (i << 5));
                    mma16816(ga[i], a0, a1, a2, a3, b0, b1);
                    if (s < 20) {
                        ldsm4t(a0, a1, a2, a3, (wa ^ (i << 5)) + 28672);
                        mma16816(ua[i], a0, a1, a2, a3, b0, b1);
                    }
                }
            }
        }
        asm volatile("fence.proxy.async.shared::cta;" ::: "memory");
        __syncwarp();
        if (lane == 0) mbar_arrive(empty + 8 * st);
        if (++st == 3) { st = 0; ph ^= 1; }
    }
#pragma unroll
    for (int i = 0; i < 4; i++)
#pragma unroll
        for (int e = 0; e < 4; e += 2)
            *reinterpret_cast<float2*>(g_moe_part + (a * DM + warp * 64 + i * 16 + g + 4 * e) * 8 + 2 * t) = make_float2(ga[i][e], ga[i][e + 1]);
    bar_sync(1, 320);
    if (tid == 0) {
        __threadfence();
        unsigned old = atomicAdd(flag_ptr(FL_MOE_CNT), 1u);
        s_misc[1] = (old == ep * 4u + 3u);
        __threadfence();
    }
    bar_sync(1, 320);
    if (s_misc[1]) {
        const float4* pp = reinterpret_cast<const float4*>(g_moe_part);
#pragma unroll 1
        for (int i = tid; i < DM * 2; i += 320) {
            float4 v0 = __ldcg(pp + i), v1 = __ldcg(pp + DM * 2 + i), v2 = __ldcg(pp + DM * 4 + i), v3 = __ldcg(pp + DM * 6 + i);
            float y[4] = {v0.x + v1.x + v2.x + v3.x, v0.y + v1.y + v2.y + v3.y, v0.z + v1.z + v2.z + v3.z, v0.w + v1.w + v2.w + v3.w};
#pragma unroll
            for (int e = 0; e < 4; e++) {
                int col = i >> 1, tk = (i & 1) * 4 + e;
                float upd = bf_round(bf_round(y[e]) * s_r[tk]);
                float xn = __bfloat162float(*reinterpret_cast<const __nv_bfloat16*>(sm + XS + tk * 1296 + col * 2));
                g_brow[tk * DM + col] = __float2bfloat16_rn(xn + upd);
            }
        }
        if (tid < TOPC) g_sel[tid] = s_sel[tid];
        bar_sync(1, 320);
        if (tid == 0) {
            flag_signal(flag_ptr(FL_MOE_DONE));
            *reinterpret_cast<volatile unsigned*>(&g_epoch) = ep + 1;
        }
    }
}

__global__ void __cluster_dims__(2, 1, 1) __launch_bounds__(384, 1)
fused_kernel(const __grid_constant__ CUtensorMap tmC, const __grid_constant__ CUtensorMap tmWk, const __grid_constant__ CUtensorMap tmWv,
             const __grid_constant__ CUtensorMap tmWq, const __grid_constant__ CUtensorMap tmWo,
             const __grid_constant__ CUtensorMap tmG, const __grid_constant__ CUtensorMap tmU, const __grid_constant__ CUtensorMap tmD, const Params P) {
    extern __shared__ __align__(1024) unsigned char smem_raw[];
    const uint32_t ring = smem_u32(smem_raw);
    const uint32_t misc = ring + RING_BYTES;
    const int tid = threadIdx.x;
    const int rank = blockIdx.x & 1;
    uint32_t smid, nsm;
    asm("mov.u32 %0, %%smid;" : "=r"(smid));
    asm("mov.u32 %0, %%nsmid;" : "=r"(nsm));
    if (nsm != 132) smid = blockIdx.x;
    auto role_of = [](int tpc) {
        return tpc < 32 ? (tpc & 7) * 8 + (tpc >> 3) : tpc < 60 ? (1 + (tpc - 32) % 7) * 8 + 4 + (tpc - 32) / 7 : tpc < 62 ? tpc + 4 : tpc - 58;
    };
    int mc = role_of(smid >> 1);

    auto prefetch_w = [&](int ch) {
        const int i = tid - 128;
        asm volatile("prefetch.global.L2 [%0];" ::"l"((rank ? P.wv : P.wk) + (size_t)(ch * 128 + (mc & 3) * 32 + (i >> 3)) * 4096 + (mc >> 2) * 128 + (i & 7) * 16));
    };
    if (tid >= 128 && mc < 64) {
        if (tid < 256) asm volatile("prefetch.global.L2 [%0];" ::"l"(P.c + (size_t)((12 + (mc & 3)) * 128 + ((mc >> 2) * 2 + rank) * 4) * DC + (tid - 128) * 16));
        prefetch_w(0);
    }
    auto load_w0 = [&]() {
        const CUtensorMap* tw = rank ? &tmWv : &tmWk;
        mbar_expect_tx(misc + BAR_FULL + 8 * slot_of(0), SLOT_BYTES);
        tma2d(ring + slot_of(0) * SLOT_BYTES, tw, (mc >> 2) * 128, 0, misc + BAR_FULL + 8 * slot_of(0));
        tma2d(ring + slot_of(0) * SLOT_BYTES + 16384, tw, (mc >> 2) * 128 + 64, 0, misc + BAR_FULL + 8 * slot_of(0));
    };
    if (tid == 0) {
#pragma unroll
        for (int i = 0; i < NSLOT; i++) mbar_init(misc + BAR_FULL + 8 * i, 1);
#pragma unroll
        for (int i = 0; i < E0; i++) mbar_arrive(misc + BAR_FULL + 8 * i);
        asm volatile("fence.mbarrier_init.release.cluster;" ::: "memory");
        if (mc < 64) load_w0();
    }
    if (tid == 160) {
        asm volatile("st.shared.u32 [%0], %1;" ::"r"(misc + MISC_SMID), "r"(smid) : "memory");
        asm volatile("fence.release.sync_restrict::shared::cta.cluster;" ::: "memory");
    }
    if (tid == 32) {
        asm volatile("prefetch.tensormap [%0];" ::"l"(&tmC) : "memory");
#pragma unroll
        for (int i = 0; i < NSLOT; i++) mbar_init(misc + BAR_EMPTY + 8 * i, 16);
#pragma unroll
        for (int i = 0; i < E0; i++) mbar_arrive_cluster(misc + BAR_EMPTY + 8 * i, 16);
        asm volatile("fence.mbarrier_init.release.cluster;" ::: "memory");
    }
    if (tid == 64) {
#pragma unroll
        for (int i = 0; i < NST3; i++) { mbar_init(misc + BAR_FULL3 + 8 * i, 1); mbar_init(misc + BAR_EMPTY3 + 8 * i, 16); }
#pragma unroll
        for (int i = 0; i < 4; i++) mbar_init(misc + BAR_PROG + 8 * i, 1);
        mbar_init(misc + BAR_LN, 2);
        asm volatile("fence.mbarrier_init.release.cluster;" ::: "memory");
    }
    if (tid == 96) {
#pragma unroll
        for (int i = 0; i < 24; i++) mbar_init(misc + BAR_DEP + 8 * i, 1);
    }
    if (tid == 128) {
#pragma unroll
        for (int i = 0; i < 2 * NEV; i++) mbar_init(misc + BAR_EV + 8 * i, 4);
    }
    __syncthreads();
    asm volatile("barrier.cluster.arrive.relaxed.aligned;\nbarrier.cluster.wait.aligned;" ::: "memory");
    {
        uint32_t peer;
        asm volatile("{\n.reg .b32 r, a;\nmov.u32 r, %%cluster_ctarank;\nxor.b32 r, r, 1;\nmapa.shared::cluster.u32 a, %1, r;\n"
                     "ld.shared::cluster.u32 %0, [a];\n}\n" : "=r"(peer) : "r"(misc + MISC_SMID) : "memory");
        if ((__shfl_sync(0xffffffffu, peer, 0) ^ smid) != 1) {
            if (tid == 0) {
                const unsigned ep1 = *reinterpret_cast<volatile unsigned*>(&g_epoch) + 1;
                if ((smid & 1) == 0) atomicExch(g_roleq + 2 + (atomicAdd(g_roleq, 1u) & 127), (ep1 << 8) | (smid >> 1));
                if (rank == 0) {
                    unsigned* slot = g_roleq + 2 + (atomicAdd(g_roleq + 1, 1u) & 127);
                    unsigned v = 0;
                    for (int spin = 0; spin < 4000000 && ((v = atomicAdd(slot, 0u)) >> 8) != (ep1 & 0xffffffu); spin++) {}
                    asm volatile("st.shared::cluster.u32 [%0], %1;" ::"r"(mapa(misc + MISC_SMID + 4, 0)), "r"(v & 255) : "memory");
                    asm volatile("st.shared::cluster.u32 [%0], %1;" ::"r"(mapa(misc + MISC_SMID + 4, 1)), "r"(v & 255) : "memory");
                }
                if (mc < 64) {
                    mbar_wait(misc + BAR_FULL + 8 * slot_of(0), 0);
                    asm volatile("mbarrier.inval.shared::cta.b64 [%0];" ::"r"(misc + BAR_FULL + 8 * slot_of(0)) : "memory");
                    mbar_init(misc + BAR_FULL + 8 * slot_of(0), 1);
                    asm volatile("fence.mbarrier_init.release.cluster;" ::: "memory");
                }
            }
            __syncwarp();
            asm volatile("barrier.cluster.arrive.aligned;\nbarrier.cluster.wait.aligned;" ::: "memory");
            mc = role_of(__shfl_sync(0xffffffffu, lds32(misc + MISC_SMID + 4), 0));
            if (tid == 0 && mc < 64) load_w0();
            __syncwarp();
        }
    }
    const int cta = mc * 2 + rank;
    const bool aux = mc >= 64;
    const int team = mc >> 2, k = mc & 3;
    const int u3 = mc >> 3, s3 = k, kap = team & 1;
    const int partner = cta ^ 8;
    const int b0 = k, b1 = 7 - k;
    if (tid >= 128 && !aux) prefetch_w(1);
    if (tid == 256 && !aux) {
        const CUtensorMap* tw = rank ? &tmWv : &tmWk;
#pragma unroll
        for (int e = 1; e < NSLOT; e++) {
            const uint32_t fb = misc + BAR_FULL + 8 * slot_of(e), dst = ring + slot_of(e) * SLOT_BYTES;
            mbar_expect_tx(fb, SLOT_BYTES);
            if (e & 1) tma2d_mc(dst + rank * 16384, &tmC, (e >> 1) * 128 + rank * 64, (12 + k) * 128, fb);
            else { tma2d(dst, tw, team * 128, e * 64, fb); tma2d(dst + 16384, tw, team * 128 + 64, e * 64, fb); }
        }
    }
    const int wg = __shfl_sync(0xffffffffu, tid >> 7, 0);

    if (wg == 0 || aux) {
        asm volatile("setmaxnreg.dec.sync.aligned.u32 40;");
        const int warp = __shfl_sync(0xffffffffu, tid >> 5, 0), lane = tid & 31;
        if (warp == 0 && !aux) {
            const bool lead = elect_one();
            Cur c = cur_at(NSLOT);
            uint32_t dst, fb;
            auto acquire = [&]() {
                mbar_wait_sleep(misc + BAR_EMPTY + 8 * c.slot, c.ph ^ 1);
                fb = misc + BAR_FULL + 8 * c.slot; dst = ring + c.slot * SLOT_BYTES;
                if (lead) mbar_expect_tx(fb, SLOT_BYTES);
                c.adv();
            };
            auto load_w = [&](const CUtensorMap* tm, int col, int row) {
                acquire();
                if (lead) { tma2d(dst, tm, col, row, fb); tma2d(dst + 16384, tm, col + 64, row, fb); }
            };
            auto load_half = [&](const unsigned char* src) {
                acquire();
                if (lead) bulk_load_mc(dst + rank * 16384, src, 16384, fb);
            };
            auto dep_wait = [&](int d) { mbar_wait_sleep(misc + BAR_DEP + 8 * d, 0); fence_async_global(); };
            auto op_prefetch = [&](int i) {
                const int head = op_head(i, kap);
                l2_prefetch(reinterpret_cast<const unsigned char*>(P.wo) + head * 163840 + (u3 * 8 + s3 * 2 + rank) * 2560, 2560);
                if (i < 8) l2_prefetch(g_ctx + (size_t)(head * 32 + 4 * u3 + 2 * rank) * 16384 + s3 * 8192, 8192);
            };
            if (lead) l2_prefetch(reinterpret_cast<const unsigned char*>(P.c) + (size_t)cta * 12288, 12288);
            const CUtensorMap* tw = rank ? &tmWv : &tmWk;
            const unsigned char* Kh = g_K + (size_t)team * 32 * 16384 + rank * 16384;
            const unsigned char* Vh = g_V + (size_t)team * 32 * 16384 + rank * 16384;
#pragma unroll 1
            for (int v = 0; v < 2; v++) {
                const int h = team + 16 * v;
#pragma unroll 1
                for (int i = v ? 0 : 3; i < 16; i++) {
                    if (i < 4 && v) load_w(tw, h * 128, i * 128);
                    if (v && i == 3 && lead) mbar_arrive(misc + BAR_PROG + 8);
                    if (v && (i == 3 || i == 7)) dep_wait(D_WAR + (i > 3));
                    acquire();
                    if (lead) tma2d_mc(dst + rank * 16384, &tmC, (i & 3) * 128 + rank * 64, (kv_tile(i >> 2) + k) * 128, fb);
                    if (i == 8 && lead) {
                        tma2d_prefetch(&tmWq, h * 128 + rank * 64, k * 64); tma2d_prefetch(&tmWq, h * 128 + rank * 64, k * 64 + 256);
                        if (k < 2) tma2d_prefetch(&tmWq, h * 128 + rank * 64, k * 64 + 512);
                    }
                }
                int togo = v ? PF_START : 11;
#pragma unroll 1
                for (int r = 0; r < 2; r++) {
                    const int p = r ? b1 : b0, n = 2 * p + 1;
                    if (v == 0) dep_wait(D_LN + r);
                    const int g0 = r ? rank ^ 1 : 3 - rank, g1 = 3 - g0;
                    const unsigned char* x0 = g_xn + (2 * p + (g0 >> 1)) * 163840 + (g0 & 1) * 8192;
                    const unsigned char* x1 = g_xn + (2 * p + (g1 >> 1)) * 163840 + (g1 & 1) * 8192;
#pragma unroll 1
                    for (int kc = 0; kc < 10; kc++) {
                        acquire();
                        if (lead) {
                            tma2d_mc(dst + 16384 + rank * 8192, &tmWq, h * 128 + rank * 64, kc * 64, fb);
                            bulk_load(dst, x0 + kc * 16384, 8192, fb);
                            bulk_load(dst + 8192, x1 + kc * 16384, 8192, fb);
                        }
                    }
                    dep_wait(D_KV + 2 * v + r);
                    load_half(Kh + n * 32768);
#pragma unroll 1
                    for (int j = n - 1; j >= 0; j--) {
                        load_half(Kh + j * 32768); load_half(Vh + (j + 1) * 32768);
                        if (v == 0 && r && j == 7 && lead) mbar_arrive(misc + BAR_PROG);
                        --togo;
                        if (v == 0 && togo == 0 && lead) {
                            tma2d_prefetch(tw, h * 128 + 2048, k * 128); tma2d_prefetch(tw, h * 128 + 2112, k * 128);
                            l2_prefetch(reinterpret_cast<const unsigned char*>(P.c) + (size_t)cta * 16384, 16384);
                        }
                        if (v && togo <= 0 && togo > -OP_PF && lead) op_prefetch(-togo);
                    }
                    load_half(Vh);
                }
            }
            mbar_wait_sleep(misc + BAR_EMPTY + 8 * c.slot, c.ph ^ 1); c.adv();
            int st = 0; uint32_t ph3 = 0;
#pragma unroll 1
            for (int i = 0; i < 32; i++) {
                const int head = op_head(i >> 1, kap);
                if ((i & 1) == 0) dep_wait(D_CTX + (i >> 1));
                if (i < NST3) { mbar_wait_sleep(misc + BAR_EMPTY + 8 * c.slot, c.ph ^ 1); c.adv(); }
                else mbar_wait_sleep(misc + BAR_EMPTY3 + 8 * st, ph3 ^ 1);
                fb = misc + BAR_FULL3 + 8 * st; dst = ring + st * ST3_BYTES;
                if (i == LATE_AT && lead) mbar_arrive(misc + BAR_PROG + 16);
                if (lead) {
                    mbar_expect_tx(fb, ST3_BYTES);
                    const unsigned char* src = g_ctx + (size_t)(head * 32 + 4 * u3 + 2 * rank) * 16384 + (i & 1) * 8192;
                    bulk_load(dst, src, 8192, fb);
                    bulk_load(dst + 8192, src + 16384, 8192, fb);
                    tma3d_mc(dst + 16384 + rank * 10240, &tmWo, 0, head * 128 + (i & 1) * 64 + rank * 32, 5 * s3, fb);
                    if ((i & 1) && (i >> 1) + OP_PF < 16) op_prefetch((i >> 1) + OP_PF);
                }
                if (++st == NST3) { st = 0; ph3 ^= 1; }
            }
        } else {
        if (warp >= 1 && warp <= 3 && lane < 27 && (warp - 1) * 27 + lane < 80) {
            const int ch = (warp - 1) * 27 + lane;
            uint4 u = __ldg(reinterpret_cast<const uint4*>(P.wr) + ch);
            asm volatile("st.shared.v4.b32 [%0], {%1,%2,%3,%4};" ::"r"(misc + MISC_WR + 16 * ch), "r"(u.x), "r"(u.y), "r"(u.z), "r"(u.w) : "memory");
        }
        bar_sync(3, aux ? 384 : 96);
        const int nln = aux ? (warp < 4 ? 6 : 5) : (warp == 3 || k == 0) ? 1 : 3;
        auto ln_row = [&](int t) {
            const int id = warp + 12 * t, a = cta - 128;
            return aux ? (id < 32 ? a * 256 + 192 : 960 + a * 64) + 2 * id
                       : t ? 2430 - 384 * t - 4 * (team * 6 + (k - 1) * 2 + rank) - 2 * (warp - 1) : (cta >> 5) * 256 + (cta & 31) * 6 + (warp - 1) * 2;
        };
        int done = 0;
#pragma unroll 1
        for (int t = 0; t < nln; t++) {
            const int lrow = ln_row(t), lnext = t + 1 < nln ? ln_row(t + 1) : -1;
            if (lnext >= 0) {
                const int ll = fresh_lane();
#pragma unroll
                for (int i = 0; i < 3; i++)
                    if (i * 32 + ll < 80) asm volatile("prefetch.global.L2 [%0];" ::"l"(P.x + (size_t)lnext * DM + (i * 32 + ll) * 16));
            }
            ln_rows(P.x, lrow, misc + MISC_WR);
            __syncwarp();
            done++;
            if ((lnext >> 8) != (lrow >> 8)) {
                if (fresh_lane() == 0) {
                    if (aux || t) asm volatile("red.release.gpu.global.add.u32 [%0], %1;" ::"l"(flag_ptr(FL_LN + (lrow >> 8))), "r"(done) : "memory");
                    else if (warp < 3) mbar_arrive(misc + BAR_LN);
                }
                done = 0;
            }
        }
        if (aux) {
            __syncwarp();
            asm volatile("setmaxnreg.inc.sync.aligned.u32 128;");
            aux_cta(&tmG, &tmU, &tmD, smem_raw, cta - 128);
        } else
        if (warp == 3) {
            const unsigned ep1 = *reinterpret_cast<volatile unsigned*>(&g_epoch) + 1;
            if (lane == 0) {
                asm volatile("st.shared.u32 [%0], %1;" ::"r"(misc + MISC_EPOCH), "r"(ep1) : "memory");
                mbar_wait(misc + BAR_LN, 0);
                flag_signal(flag_ptr(FL_LN + (cta >> 5)));
                flag_wait(flag_ptr(FL_LN + b0), ep1 * 64u);
                mbar_arrive(misc + BAR_DEP + 8 * D_LN);
#pragma unroll 1
                for (int i = 0; i < 4; i++) {
                    mbar_wait(misc + BAR_EV + 8 * (NEV + EV_KV + i), 0);
                    if (i < 2) {
                        mbar_wait(misc + BAR_EV + 8 * (EV_KV + i), 0);
                        asm volatile("red.release.gpu.global.add.u32 [%0], 2;" ::"l"(flag_ptr(FL_KV + team * 8 + i)) : "memory");
                    }
                    flag_wait(flag_ptr(FL_KV + team * 8 + i), ep1 * 16u);
                    mbar_arrive(misc + BAR_DEP + 8 * (D_KV + i));
                    if (i == (k >> 1)) {
                        flag_wait(flag_ptr(FL_LN + b1), ep1 * 128u);
                        mbar_arrive(misc + BAR_DEP + 8 * (D_LN + 1));
                    }
                    if (i == 1) {
#pragma unroll 1
                        for (int j = 0; j < 2; j++) {
                            mbar_wait(misc + BAR_PROG + 8 * j, 0);
                            asm volatile("red.relaxed.gpu.global.add.u32 [%0], 1;" ::"l"(flag_ptr(FL_WAR + 2 * team + j)) : "memory");
                            flag_wait(flag_ptr(FL_WAR + 2 * team + j), ep1 * 8u);
                            mbar_arrive(misc + BAR_DEP + 8 * (D_WAR + j));
                        }
                    }
                }
                flag_wait(flag_ptr(FL_LN + u3), ep1 * (u3 < 4 ? 64u : 128u));
            }
            __syncwarp();
            const unsigned* cf = flag_ptr(FL_CTX + op_head(lane & 15, kap) * 8 + u3);
#pragma unroll 1
            for (int half = 0; half < 2; half++) {
                if (half) mbar_wait(misc + BAR_EV + 8 * (EV_CTX + 3), 0);
                bool done = (lane >> 3) != half;
                for (int spin = 0; spin < 4000000; spin++) {
                    if (!done) {
                        unsigned v;
                        asm volatile("ld.acquire.gpu.global.u32 %0, [%1];" : "=r"(v) : "l"(cf) : "memory");
                        if ((int)(v - ep1 * 4u) >= 0) { mbar_arrive(misc + BAR_DEP + 8 * (D_CTX + lane)); done = true; }
                    }
                    if (__all_sync(0xffffffffu, done)) break;
                    __nanosleep(64);
                }
            }
            if (lane == 0) {
                flag_wait(flag_ptr(FL_MOE_DONE), ep1);
                int4 s0 = __ldcg(reinterpret_cast<const int4*>(g_sel)), s1 = __ldcg(reinterpret_cast<const int4*>(g_sel) + 1);
                asm volatile("st.shared.v4.u32 [%0], {%1,%2,%3,%4};" ::"r"(misc + MISC_SEL), "r"(s0.x), "r"(s0.y), "r"(s0.z), "r"(s0.w) : "memory");
                asm volatile("st.shared.v4.u32 [%0], {%1,%2,%3,%4};" ::"r"(misc + MISC_SEL + 16), "r"(s1.x), "r"(s1.y), "r"(s1.z), "r"(s1.w) : "memory");
                mbar_arrive(misc + BAR_SEL);
            }
        } else {
            const int w = warp - 1;
            if (lane == 0) {
                const uint32_t eb = misc + BAR_EV + w * 8 * NEV;
#pragma unroll 1
                for (int i = 0; i < 6; i++) {
                    const bool kv = (i >> 1) == 1;
                    const int ci = i < 2 ? i : i - 2;
                    mbar_wait(eb + 8 * (kv ? EV_KV + i : EV_CTX + ci), 0);
                    if (i == 1) {
                        asm volatile("cp.async.bulk.global.shared::cta.bulk_group.L2::cache_hint [%0], [%1], 16384, %2;"
                                     ::"l"(g_ctx + (size_t)(team * 32 + 4 * b1 + (w ? 3 - (rank ^ 1) : rank ^ 1)) * 16384),
                                       "r"(ring + slot_of(78) * SLOT_BYTES + w * 16384), "l"(policy_stream()) : "memory");
                        asm volatile("cp.async.bulk.commit_group;" ::: "memory");
                        asm volatile("cp.async.bulk.wait_group.read 0;" ::: "memory");
                        mbar_arrive_cluster(mapa(misc + BAR_EMPTY + 8 * slot_of(78), 0), 4);
                        mbar_arrive_cluster(mapa(misc + BAR_EMPTY + 8 * slot_of(78), 1), 4);
                        asm volatile("cp.async.bulk.wait_group 0;" ::: "memory");
                        fence_async_global();
                    }
                    flag_signal(flag_ptr(kv ? FL_KV + team * 8 + i : FL_CTX + (team + 16 * (ci >> 1)) * 8 + ((ci & 1) ? b1 : b0)));
                }
            }
            __syncwarp();
            mbar_wait(misc + BAR_PROG + 16, 0);
            const int row = (2 * u3 + rank) * 128 + 64 * w + perm32(16 * (lane >> 3) + 8 * kap + (lane & 7));
#pragma unroll
            for (int i = 0; i < 10; i++) asm volatile("prefetch.global.L2 [%0];" ::"l"(P.x + (size_t)row * DM + 160 * s3 + 16 * i));
            asm volatile("prefetch.global.L2 [%0];" ::"l"(g_stats + row));
            mbar_wait(misc + BAR_EV + w * 8 * NEV + 8 * EV_END, 0);
        }
        }
    } else {
        asm volatile("setmaxnreg.inc.sync.aligned.u32 232;");
        Ctx c;
        c.ring = ring; c.misc = misc; c.w = wg - 1; c.warp = __shfl_sync(0xffffffffu, (tid >> 5) & 3, 0); c.lane = tid & 31;
        c.rel = mapa(misc, tid & 1);
        const int w = c.w;
        if (w == 1) bar_arrive(1, 256);
        prefetch_w(2); prefetch_w(3);
        Cur cur = cur_at(0);
        float o[64], inv[2];
        unsigned char* out[2];
        uint32_t wf[128];
        Cur cw = cur;
        auto load_wchunk = [&](auto CH) {
            constexpr int ch = decltype(CH)::value;
            mbar_wait_hot(misc + BAR_FULL + 8 * cw.slot, cw.ph);
            const uint32_t z = load_afrag<8, 32 * ch>(wf, ring + cw.slot * SLOT_BYTES + w * 16384, c);
            release(c, BAR_EMPTY + 8 * cw.slot + z, 1);
            cw.adv(); cw.adv();
        };
#pragma unroll
        for (int i = 32; i < 64; i++) wf[i] = 0u;
        load_wchunk(IC<0>{});
#pragma unroll 1
        for (int v = 0; v < 2; v++) {
        {
            float (&acc)[64] = o;
#pragma unroll
            for (int i = 64; i < 128; i++) wf[i] = 0u;
            cur.adv();
            inv[0] = inv[1] = rank ? 1.0f : SM_SCALE;
#pragma unroll 1
            for (int t = 0; t < 4; t++) {
                uint32_t last = 0;
                token_wait(w);
                undef_regs(acc);
                auto chunk = [&](auto CH) {
                    constexpr int ch = decltype(CH)::value;
                    mbar_wait_hot(misc + BAR_FULL + 8 * cur.slot, cur.ph);
                    uint64_t d = mkdesc(ring + cur.slot * SLOT_BYTES, 16, 1024, 1);
                    wg_fence();
#pragma unroll
                    for (int ks = 0; ks < 8; ks++)
                        wgmma_rs_n128_ta0_tb0(acc, wf[32 * ch + 4 * ks], wf[32 * ch + 4 * ks + 1], wf[32 * ch + 4 * ks + 2], wf[32 * ch + 4 * ks + 3],
                                              d + (ks >> 2) * 1024 + (ks & 3) * 2, (ch | ks) != 0);
                    wg_commit();
                    if (ch == 3 || (ch < 2 && t == 0)) token_pass(w);
                    if constexpr (ch == 0) {
                        if (t == 0) {
                            if (v) {
                                release(c, BAR_EMPTY + 8 * slot_of(76), 1);
                                asm volatile("fence.proxy.async.shared::cta;" ::: "memory");
                                signal_event(c, EV_CTX + 1);
                                load_wchunk(IC<2>{});
                            } else load_wchunk(IC<1>{});
                        }
                    }
                    if constexpr (ch == 1) { if (t == 0 && !v) load_wchunk(IC<2>{}); }
                    if constexpr (ch == 2) { if (t == 0 && !(w | v)) load_wchunk(IC<3>{}); }
                    if (ch > 0) { wg_wait<1>(); release(c, BAR_EMPTY + 8 * last, 1); }
                    last = cur.slot;
                    cur.adv();
                    if (ch < 3 && t == 0) cur.adv();
                    if constexpr (ch == 1) { if (t == 0 && (w | v)) load_wchunk(IC<3>{}); }
                    if (ch < 2 && t == 0) token_wait(w);
                };
                chunk(IC<0>{}); chunk(IC<1>{}); chunk(IC<2>{}); chunk(IC<3>{});
                wg_wait<0>();
                release(c, BAR_EMPTY + 8 * last, 1);
                fence_regs(acc);
                tile_out(out, (rank ? g_V : g_K) + (size_t)(team * 32 + 2 * (kv_tile(t) + k)) * 16384, 64 * w, rank, c);
                if (t == 3 && w) break;
#pragma unroll
                for (int i = 0; i < 4; i++) store_pair(acc, i, out, 8192, inv);
                if (t >= 2) signal_event(c, EV_KV + 2 * v + t - 2);
            }
        }
        {
            uint32_t q[32], p[32];
            float m[2], l[2];
#pragma unroll
            for (int i = 0; i < 32; i++) p[i] = 0u;
            l[0] = l[1] = 1.f;
            int pv_acc = 1, pv_mode = 2;
#pragma unroll 1
            for (int r = 0; r < 2; r++) {
                const int heavy = 1 ^ r ^ w;
                const int half = 1 ^ heavy ^ rank ^ r;
                int left = 2 * (r ? b1 : b0) + 1 + heavy;
                Cur ck, cv = cur;
                {
                    float s[64];
                    if (r) cur.adv();
                    mbar_wait_hot(misc + BAR_FULL + 8 * cv.slot, cv.ph);
                    token_wait(w);
                    issue_pv(o, p, ring + cv.slot * SLOT_BYTES, pv_acc, pv_mode);
                    undef_regs(s);
                    uint32_t prev;
                    auto qchunk = [&](int acc) {
                        mbar_wait_hot(misc + BAR_FULL + 8 * cur.slot, cur.ph);
                        const uint64_t da = mkdesc(ring + cur.slot * SLOT_BYTES + w * 8192, 16, 1024, 1);
                        const uint64_t db = mkdesc(ring + cur.slot * SLOT_BYTES + 16384, 8192, 1024, 1);
                        wg_fence();
#pragma unroll
                        for (int ks = 0; ks < 4; ks++) wgmma_ss_n128_ta0_tb1(s, da + 2 * ks, db + 128 * ks, ks ? 1 : acc);
                        wg_commit();
                    };
                    qchunk(0);
                    prev = cur.slot; cur.adv();
                    token_pass(w);
                    if (r) {
                        row_inv(l, inv);
                        tile_out(out, g_ctx + (size_t)((team + 16 * v) * 32 + 4 * b0 + (w ? rank : 3 - rank)) * 16384, 0, 0, c);
                    }
                    const int epi = r | w, hs = r ? 4096 : 8192;
                    const int hold = heavy ? -10 : half ? 6 : 8;
#pragma unroll
                    for (int kc = 1; kc < 10; kc++) {
                        if (kc >= 6 && (kc == hold || kc == hold + 2)) token_wait(w);
                        qchunk(1);
                        if (kc > 6 && kc == hold + 1) token_pass(w);
                        if (kc == 9 && heavy) { token_wait(w); token_pass(w); }
                        wg_wait<1>();
                        release(c, BAR_EMPTY + 8 * prev, 1);
                        prev = cur.slot; cur.adv();
                        if (kc == 1) { fence_regs(o); if (r) release(c, BAR_EMPTY + 8 * cv.slot, 1); }
                        if (kc <= 4 && epi) {
                            store_pair(o, kc - 1, out, hs, inv, r > v);
                            if (kc == 4) signal_event(c, r ? EV_CTX + 2 * v : EV_KV + 2 * v + 1);
                        }
                    }
                    if (!heavy) cur.adv();
                    ck = cur;
                    cur.adv();
                    if (!heavy) cur.adv();
                    wg_wait<0>();
                    release(c, BAR_EMPTY + 8 * prev, 1);
                    fence_regs(s);
#pragma unroll
                    for (int i = 0; i < 32; i++) q[i] = pack_bf16(s[2 * i], s[2 * i + 1]);
                }
                int first = 1, gen = 0;
                uint32_t pv_cnt = 0;
                l[0] = l[1] = m[0] = m[1] = 0.f;
                mbar_wait_hot(misc + BAR_FULL + 8 * ck.slot, ck.ph);
                auto diagonal = [&](auto NJC) {
                    constexpr int NJ = decltype(NJC)::value;
                    if (NJ == 16 || heavy) token_wait(w);
                    float sd[4 * NJ];
                    undef_regs(sd);
                    if constexpr (NJ == 8) issue_qk_half(sd, q, ring + ck.slot * SLOT_BYTES); else issue_qk(sd, q, ring + ck.slot * SLOT_BYTES);
                    token_pass(w);
                    wg_wait<0>();
                    fence_regs(sd);
                    mask_diag<NJ - 8>(sd, c);
                    float l0 = 0.f, l1 = 0.f;
#pragma unroll
                    for (int j = 0; j < NJ; j++) {
#pragma unroll
                        for (int e = 0; e < 4; e++) ex2v(sd[4 * j + e]);
                        l0 += sd[4 * j] + sd[4 * j + 1]; l1 += sd[4 * j + 2] + sd[4 * j + 3];
                    }
#pragma unroll
                    for (int i = 0; i < 2 * NJ; i++) p[i] = pack_bf16(sd[2 * i], sd[2 * i + 1]);
                    const int lim = NJ == 8 ? mask_lim(c) : 0;
                    const bool bad = __any_sync(0xffffffffu, !(l0 <= SAFE_SUM && l1 <= SAFE_SUM && (l0 >= 1.0f / SAFE_SUM || lim < 0) &&
                                                               (l1 >= 1.0f / SAFE_SUM || lim < -2)));
                    if (!bad) { l[0] = l0; l[1] = l1; }
                    return bad;
                };
#pragma unroll 1
                while (true) {
                    float s[64];
                    if (first) {
                        --left;
                        if (half ? diagonal(IC<8>{}) : diagonal(IC<16>{})) goto redo;
                        if (left == 0) goto tail;
                        release(c, BAR_EMPTY + 8 * ck.slot, 1 + heavy);
                        pv_acc = 0; pv_mode = half; pv_cnt = 1 + heavy; first = 0;
                        ck = cur; cur.adv(); cv = cur; cur.adv();
                        mbar_wait_hot(misc + BAR_FULL + 8 * ck.slot, ck.ph);
                    }
#pragma unroll 1
                    while (true) {
                        token_wait(w);
                        undef_regs(s);
                        issue_qk(s, q, ring + ck.slot * SLOT_BYTES);
                        Cur nck = cur, ncv = cur, ncur;
                        ncv.adv(); ncur = ncv; ncur.adv();
                        --left;
                        mbar_wait_hot(misc + BAR_FULL + 8 * cv.slot, cv.ph);
                        issue_pv(o, p, ring + cv.slot * SLOT_BYTES, pv_acc, pv_mode & 1);
                        token_pass(w);
                        wg_wait<1>();
                        fence_regs(s);
                        constexpr int JB = 11;
                        float l0 = l[0], l1 = l[1];
                        if (!gen) {
#pragma unroll
                            for (int j = 0; j < JB; j++) {
#pragma unroll
                                for (int e = 0; e < 4; e++) ex2v(s[4 * j + e]);
                                if (j < JB - 1) { l0 += s[4 * j] + s[4 * j + 1]; l1 += s[4 * j + 2] + s[4 * j + 3]; }
                            }
                        }
                        wg_wait<0>();
                        fence_regs(o);
                        if (gen) goto general;
#pragma unroll
                        for (int j = JB - 1; j < 16; j++) {
                            if (j >= JB) {
#pragma unroll
                                for (int e = 0; e < 4; e++) ex2v(s[4 * j + e]);
                            }
                            l0 += s[4 * j] + s[4 * j + 1]; l1 += s[4 * j + 2] + s[4 * j + 3];
                        }
#pragma unroll
                        for (int i = 0; i < 32; i++) p[i] = pack_bf16(s[2 * i], s[2 * i + 1]);
                        if (__any_sync(0xffffffffu, !(l0 <= SAFE_SUM && l1 <= SAFE_SUM))) goto redo;
                        l[0] = l0; l[1] = l1;
                        if (left == 0) goto tail;
                        release(c, BAR_EMPTY + 8 * ck.slot, 1);
                        release(c, BAR_EMPTY + 8 * cv.slot, pv_cnt);
                        pv_acc = 1; pv_mode = 0; pv_cnt = 1;
                        ck = nck; cv = ncv; cur = ncur;
                        mbar_wait_hot(misc + BAR_FULL + 8 * ck.slot, ck.ph);
                    }
                redo:
                    recompute_scores(s, q, ring + ck.slot * SLOT_BYTES, c);
                    if (first) { mask_any(s, half ^ 1, c); m[0] = m[1] = -INFINITY; }
                    gen = 1;
                general:
                    {
                        float mx[2], alpha[2];
                        row_max<16>(s, mx);
#pragma unroll
                        for (int i = 0; i < 2; i++) {
                            mx[i] = fmaxf(mx[i], m[i]);
                            alpha[i] = ex2(m[i] - mx[i]);
                            m[i] = mx[i];
                            l[i] *= alpha[i];
                        }
                        exp_sum<16, true>(s, m, l[0], l[1]);
#pragma unroll
                        for (int i = 0; i < 64; i++) o[i] *= alpha[(i >> 1) & 1];
#pragma unroll
                        for (int i = 0; i < 32; i++) p[i] = pack_bf16(s[2 * i], s[2 * i + 1]);
                    }
                tail:
                    release(c, BAR_EMPTY + 8 * ck.slot, 1 + (first & heavy));
                    if (pv_cnt) release(c, BAR_EMPTY + 8 * cv.slot, pv_cnt);
                    pv_acc = first ^ 1; pv_mode = first & half; pv_cnt = 1 + (first & heavy); first = 0;
                    if (left == 0) break;
                    ck = cur; cur.adv(); cv = cur; cur.adv();
                    mbar_wait_hot(misc + BAR_FULL + 8 * ck.slot, ck.ph);
                }
            }
            mbar_wait_hot(misc + BAR_FULL + 8 * cur.slot, cur.ph);
            token_wait(w);
            issue_pv(o, p, ring + cur.slot * SLOT_BYTES, 1, 0);
            if (w == 0 || v == 0) token_pass(w);
            const uint32_t vslot = cur.slot;
            cur.adv();
            row_inv(l, inv);
            if (v) {
                wg_wait<0>();
                release(c, BAR_EMPTY + 8 * vslot, 1);
                fence_regs(o);
                tile_out(out, g_ctx + (size_t)((team + 16) * 32 + 4 * b1 + (w ? 3 - (rank ^ 1) : rank ^ 1)) * 16384, 0, 0, c);
#pragma unroll
                for (int i = 0; i < 64; i++) wf[i] = 0u;
                continue;
            }
            cw = cur_at(80);
            mbar_wait_hot(misc + BAR_FULL + 8 * slot_of(76), cur_at(76).ph);
            mbar_wait_hot(misc + BAR_FULL + 8 * slot_of(78), cur_at(78).ph);
            load_afrag<8, 32>(wf, ring + slot_of(78) * SLOT_BYTES + w * 16384, c);
            load_afrag<8, 0>(wf, ring + slot_of(76) * SLOT_BYTES + w * 16384, c);
            asm volatile("{\n.reg .pred p;\nsetp.eq.u32 p, %0, 0;\n@p bar.sync 4, 128;\n@!p bar.sync 5, 128;\n}\n" ::"r"(w) : "memory");
            wg_wait<0>();
            release(c, BAR_EMPTY + 8 * vslot, 1);
            fence_regs(o);
            {
                const uint32_t base = ring + slot_of(78) * SLOT_BYTES + w * 16384 + (16 * c.warp + (c.lane >> 2)) * 64 + (((c.lane ^ (c.lane >> 3)) & 3) << 4);
#pragma unroll
                for (int i = 0; i < 2; i++)
#pragma unroll
                    for (int qq = 0; qq < 4; qq++)
                        asm volatile("st.shared.v4.b32 [%0], {%1,%2,%3,%4};" ::"r"(base + qq * 4096 + i * 512),
                                     "r"(pack_bf16(o[16 * qq + 2 * i] * inv[i], o[16 * qq + 2 * i + 1] * inv[i])),
                                     "r"(pack_bf16(o[16 * qq + 4 + 2 * i] * inv[i], o[16 * qq + 4 + 2 * i + 1] * inv[i])),
                                     "r"(pack_bf16(o[16 * qq + 8 + 2 * i] * inv[i], o[16 * qq + 8 + 2 * i + 1] * inv[i])),
                                     "r"(pack_bf16(o[16 * qq + 12 + 2 * i] * inv[i], o[16 * qq + 12 + 2 * i + 1] * inv[i])) : "memory");
            }
        }
        }
        {
            float acc[80];
            undef_regs(acc);
            int st = 0, prev = 0; uint32_t ph3 = 0;
            auto op_stage = [&](int i) {
                mbar_wait_hot(misc + BAR_FULL3 + 8 * st, ph3);
                uint32_t base = ring + st * ST3_BYTES;
                uint64_t da = mkdesc(base + w * 8192, 16, 512, 2);
                uint64_t db = mkdesc(base + 16384, 2048, 512, 2);
                wg_fence();
#pragma unroll
                for (int k = 0; k < 4; k++) wgmma_ss_n160_ta0_tb1(acc, da + (k >> 1) * 256 + 2 * (k & 1), db + (k >> 1) * 640 + (k & 1) * 64, k ? 1 : i);
                wg_commit();
                if (i > 0 && i <= 32 - NST3) { wg_wait<1>(); release(c, BAR_EMPTY3 + 8 * prev, 1); }
                prev = st;
                if (++st == NST3) { st = 0; ph3 ^= 1; }
            };
#pragma unroll
            for (int i = 0; i < 4; i++) { op_stage(i); store_pair(o, i, out, 4096, inv); }
            signal_event(c, EV_CTX + 3);
            const int split = w ? 32 - OP_HOLD : RES_AT;
#pragma unroll 1
            for (int i = 4; i < split; i++) op_stage(i);
            const uint32_t tag = lds32(misc + MISC_EPOCH) & 1;
            const int g = c.lane >> 2, t = c.lane & 3;
            const int row = (2 * u3 + rank) * 128 + 64 * w + perm32(16 * c.warp + 8 * kap + g);
            const int col = 160 * s3 + 8 * t;
            const int t256 = tid - 128;
            uint4* sendp = g_part + (size_t)cta * 2560 + t256;
            if (c.lane >= 30) stg128(sendp + 9 * 256, tag ^ 1, tag ^ 1, tag ^ 1, tag ^ 1);
            uint4 xv[5], bv[5];
#pragma unroll
            for (int i = 0; i < 5; i++) xv[i] = ldg128(P.x + (size_t)row * DM + col + 32 * i);
            uint2 stat;
            asm volatile("ld.global.cg.v2.b32 {%0,%1}, [%2];" : "=r"(stat.x), "=r"(stat.y) : "l"(g_stats + row) : "memory");
#pragma unroll
            for (int i = 0; i < 5; i++) {
                uint32_t xx[4] = {xv[i].x, xv[i].y, xv[i].z, xv[i].w};
#pragma unroll
                for (int e = 0; e < 4; e++) {
                    asm("sub.rn.bf16x2 %0, %0, %1;" : "+r"(xx[e]) : "r"(stat.x));
                    xx[e] = pack_bf16(bf_lo(xx[e]) * __uint_as_float(stat.y), bf_hi(xx[e]) * __uint_as_float(stat.y));
                }
                bv[i] = make_uint4(xx[0], xx[1], xx[2], xx[3]);
            }
#pragma unroll
            for (int i = 0; i < 5; i++) asm volatile("" : "+r"(bv[i].x), "+r"(bv[i].y), "+r"(bv[i].z), "+r"(bv[i].w));
            if (w) bar_sync(4, 256);
#pragma unroll 1
            for (int i = split; i < 32; i++) op_stage(i);
            if (!w) bar_arrive(4, 256);
            wg_wait<0>();
            fence_regs(acc);
            float keep[40];
#pragma unroll
            for (int j = 0; j < 10; j++) {
                uint32_t v0 = __float_as_uint(kap ? acc[8 * j + 0] : acc[8 * j + 2]), v1 = __float_as_uint(kap ? acc[8 * j + 1] : acc[8 * j + 3]);
                uint32_t v2 = __float_as_uint(kap ? acc[8 * j + 4] : acc[8 * j + 6]), v3 = __float_as_uint(kap ? acc[8 * j + 5] : acc[8 * j + 7]);
                asm volatile("st.relaxed.gpu.global.v4.b32 [%0], {%1,%2,%3,%4};" ::"l"(sendp + j * 256),
                             "r"((v0 & ~1u) | tag), "r"((v1 & ~1u) | tag), "r"((v2 & ~1u) | tag), "r"((v3 & ~1u) | tag) : "memory");
                keep[4 * j + 0] = kap ? acc[8 * j + 2] : acc[8 * j + 0]; keep[4 * j + 1] = kap ? acc[8 * j + 3] : acc[8 * j + 1];
                keep[4 * j + 2] = kap ? acc[8 * j + 6] : acc[8 * j + 4]; keep[4 * j + 3] = kap ? acc[8 * j + 7] : acc[8 * j + 5];
            }
            signal_event(c, EV_END);
            mbar_wait(misc + BAR_SEL, 0);
            int sel = -1;
#pragma unroll
            for (int i = 0; i < TOPC; i++) if ((int)lds32(misc + MISC_SEL + 4 * i) == row) sel = i;
            if (sel >= 0) {
#pragma unroll
                for (int i = 0; i < 5; i++) bv[i] = ldg128(g_brow + sel * DM + col + 32 * i);
            }
            const uint4* recvp = g_part + (size_t)partner * 2560 + t256;
            uint4 rv[10];
            int spins = 0;
            while (true) {
                uint32_t v;
                asm volatile("ld.relaxed.gpu.global.b32 %0, [%1];" : "=r"(v) : "l"(recvp + 9 * 256 + (31 - c.lane)) : "memory");
                if (__all_sync(0xffffffffu, (v & 1u) == tag) || ++spins > 2000000) break;
            }
            while (true) {
                uint32_t bad = 0u;
#pragma unroll
                for (int j = 0; j < 10; j++) {
                    asm volatile("ld.relaxed.gpu.global.v4.b32 {%0,%1,%2,%3}, [%4];"
                                 : "=r"(rv[j].x), "=r"(rv[j].y), "=r"(rv[j].z), "=r"(rv[j].w) : "l"(recvp + j * 256) : "memory");
                }
#pragma unroll
                for (int j = 0; j < 10; j++) {
                    rv[j].x ^= tag; rv[j].y ^= tag; rv[j].z ^= tag; rv[j].w ^= tag;
                    bad |= rv[j].x | rv[j].y | rv[j].z | rv[j].w;
                }
                if (__all_sync(0xffffffffu, (bad & 1u) == 0) || ++spins > 2000000) break;
            }
            uint32_t pk[20];
#pragma unroll
            for (int j = 0; j < 10; j++) {
                pk[2 * j] = pack_bf16(keep[4 * j] + __uint_as_float(rv[j].x), keep[4 * j + 1] + __uint_as_float(rv[j].y));
                pk[2 * j + 1] = pack_bf16(keep[4 * j + 2] + __uint_as_float(rv[j].z), keep[4 * j + 3] + __uint_as_float(rv[j].w));
            }
#pragma unroll
            for (int i = 0; i < 5; i++) {
                uint32_t a0 = pk[4 * i], a1 = pk[4 * i + 1], a2 = pk[4 * i + 2], a3 = pk[4 * i + 3];
                uint32_t x0 = (t & 1) ? a0 : a1, x1 = (t & 1) ? a2 : a3;
                x0 = __shfl_xor_sync(0xffffffffu, x0, 1); x1 = __shfl_xor_sync(0xffffffffu, x1, 1);
                if (t & 1) { a0 = x0; a2 = x1; } else { a1 = x0; a3 = x1; }
                x0 = (t & 2) ? a0 : a2; x1 = (t & 2) ? a1 : a3;
                x0 = __shfl_xor_sync(0xffffffffu, x0, 2); x1 = __shfl_xor_sync(0xffffffffu, x1, 2);
                if (t & 2) { a0 = x0; a1 = x1; } else { a2 = x0; a3 = x1; }
                uint32_t av[4] = {a0, a1, a2, a3};
                uint32_t xx[4] = {xv[i].x, xv[i].y, xv[i].z, xv[i].w}, bb[4] = {bv[i].x, bv[i].y, bv[i].z, bv[i].w};
                uint32_t ov[4];
#pragma unroll
                for (int e = 0; e < 4; e++) {
                    asm("add.rn.bf16x2 %0, %1, %2;" : "=r"(ov[e]) : "r"(xx[e]), "r"(av[e]));
                    asm("add.rn.bf16x2 %0, %0, %1;" : "+r"(ov[e]) : "r"(bb[e]));
                }
                stg128(P.out + (size_t)row * DM + col + 32 * i, ov[0], ov[1], ov[2], ov[3]);
            }
        }
    }
}

typedef CUresult (*EncodeFn)(CUtensorMap*, CUtensorMapDataType, cuuint32_t, void*, const cuuint64_t*, const cuuint64_t*, const cuuint32_t*,
                             const cuuint32_t*, CUtensorMapInterleave, CUtensorMapSwizzle, CUtensorMapL2promotion, CUtensorMapFloatOOBfill);

void make_map2d(EncodeFn enc, CUtensorMap* tm, const void* p, uint64_t cols, uint64_t rows, uint32_t box_rows = 128) {
    cuuint64_t gd[2] = {cols, rows}, gs[1] = {cols * 2};
    cuuint32_t box[2] = {64, box_rows}, es[2] = {1, 1};
    enc(tm, CU_TENSOR_MAP_DATA_TYPE_BFLOAT16, 2, const_cast<void*>(p), gd, gs, box, es, CU_TENSOR_MAP_INTERLEAVE_NONE,
        CU_TENSOR_MAP_SWIZZLE_128B, CU_TENSOR_MAP_L2_PROMOTION_L2_128B, CU_TENSOR_MAP_FLOAT_OOB_FILL_NONE);
}

void make_map3d(EncodeFn enc, CUtensorMap* tm, const void* p, uint64_t cols, uint64_t rows, uint32_t bw, uint32_t nb) {
    cuuint64_t gd[3] = {bw, rows, cols / bw}, gs[2] = {cols * 2, bw * 2};
    cuuint32_t box[3] = {bw, 32, nb}, es[3] = {1, 1, 1};
    enc(tm, CU_TENSOR_MAP_DATA_TYPE_BFLOAT16, 3, const_cast<void*>(p), gd, gs, box, es, CU_TENSOR_MAP_INTERLEAVE_NONE,
        bw == 64 ? CU_TENSOR_MAP_SWIZZLE_128B : CU_TENSOR_MAP_SWIZZLE_64B, CU_TENSOR_MAP_L2_PROMOTION_L2_128B, CU_TENSOR_MAP_FLOAT_OOB_FILL_NONE);
}

}

extern "C" void kernel_launch(void* const* d_in, const int* in_sizes, int n_in, void* d_out, int out_size) {
    (void)in_sizes; (void)n_in; (void)out_size;
    static EncodeFn enc = nullptr;
    if (!enc) {
        void* fn = nullptr;
        cudaDriverEntryPointQueryResult qr;
        cudaGetDriverEntryPoint("cuTensorMapEncodeTiled", &fn, cudaEnableDefault, &qr);
        enc = (EncodeFn)fn;
        cudaFuncSetAttribute(fused_kernel, cudaFuncAttributeMaxDynamicSharedMemorySize, SMEM_BYTES);
    }
    CUtensorMap tmC, tmWk, tmWv, tmWq, tmWo, tmG, tmU, tmD;
    make_map2d(enc, &tmC, d_in[1], DC, SEQ);
    make_map2d(enc, &tmWq, d_in[2], 4096, DM, 64);
    make_map2d(enc, &tmWk, d_in[3], 4096, DC);
    make_map2d(enc, &tmWv, d_in[4], 4096, DC);
    make_map3d(enc, &tmWo, d_in[5], DM, 4096, 32, 5);
    make_map3d(enc, &tmG, d_in[8], FF, DM, 64, 7);
    make_map3d(enc, &tmU, d_in[9], FF, DM, 64, 7);
    make_map3d(enc, &tmD, d_in[10], DM, FF, 64, 10);
    Params P;
    P.x = (const __nv_bfloat16*)d_in[0];
    P.c = (const __nv_bfloat16*)d_in[1];
    P.wk = (const __nv_bfloat16*)d_in[3];
    P.wv = (const __nv_bfloat16*)d_in[4];
    P.wo = (const __nv_bfloat16*)d_in[5];
    P.wr = (const __nv_bfloat16*)d_in[7];
    P.out = (__nv_bfloat16*)d_out;
    fused_kernel<<<132, 384, SMEM_BYTES>>>(tmC, tmWk, tmWv, tmWq, tmWo, tmG, tmU, tmD, P);
}
```

```cpp
#include <cuda_runtime.h>
#include <cuda_bf16.h>
#include <cuda.h>
#include <stdint.h>

namespace {

constexpr int SEQ = 2048, NH = 32, DM = 640, DC = 512, FF = 1728, TOPC = 8;
constexpr int NSLOT = 7, SLOT_BYTES = 32768;
constexpr int NST3 = 6, ST3_BYTES = 36864;
constexpr int RING_BYTES = NSLOT * SLOT_BYTES;
constexpr int SMEM_BYTES = RING_BYTES + 3072;
constexpr int OP_PF = 8, PF_START = 9, LATE_AT = 18, RES_AT = 23, OP_HOLD = 4;

constexpr int BAR_FULL = 0  , BAR_EMPTY = 64  , BAR_FULL3 = 128  , BAR_EMPTY3 = 192  , BAR_DEP = 256  ,
              BAR_EV = 448  , BAR_PROG = 592  , BAR_SEL = 616, BAR_LN = 624,
              MISC_EPOCH = 640, MISC_SMID = 644  , MISC_SEL = 656, MISC_WR = 1024  ;
constexpr int D_LN = 0  , D_KV = 2  , D_WAR = 6  , D_CTX = 8  ;
constexpr int EV_KV = 0  , EV_CTX = 4  , EV_END = 8, NEV = 9;

constexpr int FL_MOE_CNT = 0, FL_MOE_DONE = 1, FL_LN = 16  , FL_KV = 32  , FL_CTX = 160  , FL_WAR = 416  , FL_TOTAL = 448;

__device__ __align__(1024) unsigned char g_K[16 * 32 * 16384];
__device__ __align__(1024) unsigned char g_V[16 * 32 * 16384];
__device__ __align__(1024) unsigned char g_ctx[NH * 32 * 16384];
__device__ __align__(1024) unsigned char g_xn[16 * 10 * 16384];
__device__ __align__(1024) uint4 g_part[128 * 10 * 256];
__device__ float g_router[SEQ];
__device__ uint2 g_stats[SEQ];
__device__ __align__(16) float g_moe_part[4 * TOPC * DM];
__device__ __align__(16) __nv_bfloat16 g_brow[TOPC * DM];
__device__ __align__(16) int g_sel[TOPC];
__device__ unsigned g_flags[FL_TOTAL * 8];
__device__ unsigned g_epoch;
__device__ unsigned g_roleq[130];
struct Params {
    const __nv_bfloat16 *x, *c, *wr, *wk, *wv, *wo;
    __nv_bfloat16* out;
};

__device__ __forceinline__ uint32_t smem_u32(const void* p) { return (uint32_t)__cvta_generic_to_shared(p); }
__device__ __forceinline__ void mbar_init(uint32_t bar, int cnt) { asm volatile("mbarrier.init.shared::cta.b64 [%0], %1;" ::"r"(bar), "r"(cnt)); }
__device__ __forceinline__ void mbar_expect_tx(uint32_t bar, uint32_t bytes) {
    asm volatile("mbarrier.arrive.expect_tx.shared::cta.b64 _, [%0], %1;" ::"r"(bar), "r"(bytes) : "memory");
}
__device__ __forceinline__ void mbar_arrive(uint32_t bar) { asm volatile("mbarrier.arrive.shared::cta.b64 _, [%0];" ::"r"(bar) : "memory"); }
__device__ __forceinline__ void mbar_arrive_cluster(uint32_t cluster_addr, uint32_t cnt) {
    asm volatile("mbarrier.arrive.shared::cluster.b64 _, [%0], %1;" ::"r"(cluster_addr), "r"(cnt) : "memory");
}
__device__ __forceinline__ uint32_t mapa(uint32_t addr, uint32_t cta) {
    uint32_t r; asm("mapa.shared::cluster.u32 %0, %1, %2;" : "=r"(r) : "r"(addr), "r"(cta)); return r;
}
__device__ __forceinline__ void mbar_wait(uint32_t bar, uint32_t parity) {
    asm volatile(
        "{\n.reg .pred p;\n.reg .u32 n;\n"
        "mov.u32 n, 0;\n"
        "LAB_WAIT:\n"
        "mbarrier.try_wait.parity.shared::cta.b64 p, [%0], %1, 100000;\n"
        "@p bra DONE;\n"
        "add.u32 n, n, 1;\n"
        "setp.lt.u32 p, n, 50000;\n"
        "@p bra LAB_WAIT;\n"
        "trap;\n"
        "DONE:\n}\n" ::"r"(bar), "r"(parity) : "memory");
}
__device__ __forceinline__ void mbar_wait_hot(uint32_t bar, uint32_t parity) {
    asm volatile("{\n.reg .pred p;\nLAB_WAIT:\nmbarrier.try_wait.parity.shared::cta.b64 p, [%0], %1;\n@!p bra LAB_WAIT;\n}\n" ::"r"(bar), "r"(parity) : "memory");
}
__device__ __forceinline__ void mbar_wait_sleep(uint32_t bar, uint32_t parity) {
    asm volatile("{\n.reg .pred p;\nLAB_WAIT:\nmbarrier.try_wait.parity.shared::cta.b64 p, [%0], %1, 100000;\n@!p bra LAB_WAIT;\n}\n" ::"r"(bar), "r"(parity) : "memory");
}
__device__ __forceinline__ void flag_wait(const unsigned* flag, unsigned target) {
    asm volatile(
        "{\n.reg .pred p;\n.reg .u32 n, v;\n.reg .s32 d;\n"
        "mov.u32 n, 0;\n"
        "LAB_WAIT:\n"
        "ld.acquire.gpu.global.u32 v, [%0];\n"
        "sub.s32 d, v, %1;\n"
        "setp.ge.s32 p, d, 0;\n"
        "@p bra DONE;\n"
        "nanosleep.u32 40;\n"
        "add.u32 n, n, 1;\n"
        "setp.lt.u32 p, n, 3000000;\n"
        "@p bra LAB_WAIT;\n"
        "trap;\n"
        "DONE:\n}\n" ::"l"(flag), "r"(target) : "memory");
}
__device__ __forceinline__ void flag_signal(unsigned* flag) {
    asm volatile("red.release.gpu.global.add.u32 [%0], 1;" ::"l"(flag) : "memory");
}
__device__ __forceinline__ void fence_async_global() { asm volatile("fence.proxy.async.global;" ::: "memory"); }
__device__ __forceinline__ unsigned* flag_ptr(int idx) { return g_flags + idx * 8; }

__device__ __forceinline__ uint64_t policy_stream() {
    uint64_t p; asm("createpolicy.fractional.L2::evict_first.b64 %0, 1.0;" : "=l"(p)); return p;
}
__device__ __forceinline__ void bulk_load(uint32_t dst, const void* src, uint32_t bytes, uint32_t bar) {
    asm volatile("cp.async.bulk.shared::cluster.global.mbarrier::complete_tx::bytes [%0], [%1], %2, [%3];"
                 ::"r"(dst), "l"(src), "r"(bytes), "r"(bar) : "memory");
}
__device__ __forceinline__ void bulk_load_mc(uint32_t dst, const void* src, uint32_t bytes, uint32_t bar) {
    asm volatile("cp.async.bulk.shared::cluster.global.mbarrier::complete_tx::bytes.multicast::cluster [%0], [%1], %2, [%3], %4;"
                 ::"r"(dst), "l"(src), "r"(bytes), "r"(bar), "h"((uint16_t)3) : "memory");
}
__device__ __forceinline__ void tma2d(uint32_t dst, const CUtensorMap* tm, int c0, int c1, uint32_t bar) {
    asm volatile("cp.async.bulk.tensor.2d.shared::cluster.global.mbarrier::complete_tx::bytes [%0], [%1, {%3, %4}], [%2];"
                 ::"r"(dst), "l"(tm), "r"(bar), "r"(c0), "r"(c1) : "memory");
}
__device__ __forceinline__ void tma2d_mc(uint32_t dst, const CUtensorMap* tm, int c0, int c1, uint32_t bar) {
    asm volatile("cp.async.bulk.tensor.2d.shared::cluster.global.mbarrier::complete_tx::bytes.multicast::cluster [%0], [%1, {%3, %4}], [%2], %5;"
                 ::"r"(dst), "l"(tm), "r"(bar), "r"(c0), "r"(c1), "h"((uint16_t)3) : "memory");
}
__device__ __forceinline__ void tma3d_mc(uint32_t dst, const CUtensorMap* tm, int c0, int c1, int c2, uint32_t bar) {
    asm volatile("cp.async.bulk.tensor.3d.shared::cluster.global.mbarrier::complete_tx::bytes.multicast::cluster [%0], [%1, {%3, %4, %5}], [%2], %6;"
                 ::"r"(dst), "l"(tm), "r"(bar), "r"(c0), "r"(c1), "r"(c2), "h"((uint16_t)3) : "memory");
}
__device__ __forceinline__ void tma3d(uint32_t dst, const CUtensorMap* tm, int c0, int c1, int c2, uint32_t bar) {
    asm volatile("cp.async.bulk.tensor.3d.shared::cluster.global.mbarrier::complete_tx::bytes.L2::cache_hint [%0], [%1, {%3, %4, %5}], [%2], %6;"
                 ::"r"(dst), "l"(tm), "r"(bar), "r"(c0), "r"(c1), "r"(c2), "l"(policy_stream()) : "memory");
}
__device__ __forceinline__ void tma2d_prefetch(const CUtensorMap* tm, int c0, int c1) {
    asm volatile("cp.async.bulk.prefetch.tensor.2d.L2.global [%0, {%1, %2}];" ::"l"(tm), "r"(c0), "r"(c1) : "memory");
}
__device__ __forceinline__ void tma3d_prefetch(const CUtensorMap* tm, int c0, int c1, int c2) {
    asm volatile("cp.async.bulk.prefetch.tensor.3d.L2.global [%0, {%1, %2, %3}];" ::"l"(tm), "r"(c0), "r"(c1), "r"(c2) : "memory");
}
__device__ __forceinline__ void l2_prefetch(const void* p, uint32_t bytes) {
    asm volatile("cp.async.bulk.prefetch.L2.global [%0], %1;" ::"l"(p), "r"(bytes) : "memory");
}
__device__ __forceinline__ bool elect_one() {
    uint32_t r; asm volatile("{\n.reg .pred p;\nelect.sync _|p, 0xffffffff;\nselp.u32 %0, 1, 0, p;\n}\n" : "=r"(r)); return r != 0;
}
__device__ __forceinline__ void wg_fence() { asm volatile("wgmma.fence.sync.aligned;" ::: "memory"); }
__device__ __forceinline__ void wg_commit() { asm volatile("wgmma.commit_group.sync.aligned;" ::: "memory"); }
template <int N> __device__ __forceinline__ void wg_wait() { asm volatile("wgmma.wait_group.sync.aligned %0;" ::"n"(N) : "memory"); }
__device__ __forceinline__ void bar_sync(int id, int n) { asm volatile("bar.sync %0, %1;" ::"r"(id), "r"(n) : "memory"); }
__device__ __forceinline__ void bar_arrive(int id, int n) { asm volatile("bar.arrive %0, %1;" ::"r"(id), "r"(n) : "memory"); }
__device__ __forceinline__ void token_wait(int w) {
    asm volatile("{\n.reg .pred p;\nsetp.eq.u32 p, %0, 0;\n@p bar.sync 1, 256;\n@!p bar.sync 2, 256;\n}\n" ::"r"(w) : "memory");
}
__device__ __forceinline__ void token_pass(int w) {
    asm volatile("{\n.reg .pred p;\nsetp.eq.u32 p, %0, 0;\n@p bar.arrive 2, 256;\n@!p bar.arrive 1, 256;\n}\n" ::"r"(w) : "memory");
}
template <int N> __device__ __forceinline__ void fence_regs(float (&a)[N]) {
#pragma unroll
    for (int i = 0; i < N; i++) asm volatile("" : "+f"(a[i])::"memory");
}
template <int N> __device__ __forceinline__ void undef_regs(float (&a)[N]) {
#pragma unroll
    for (int i = 0; i < N; i++) asm volatile("" : "=f"(a[i]));
}
__device__ __forceinline__ void ldsm4t(uint32_t& r0, uint32_t& r1, uint32_t& r2, uint32_t& r3, uint32_t addr) {
    asm volatile("ldmatrix.sync.aligned.m8n8.x4.trans.shared.b16 {%0,%1,%2,%3}, [%4];"
                 : "=r"(r0), "=r"(r1), "=r"(r2), "=r"(r3) : "r"(addr) : "memory");
}
__device__ __forceinline__ uint32_t pack_bf16(float lo, float hi) {
    uint32_t r; asm("cvt.rn.bf16x2.f32 %0, %1, %2;" : "=r"(r) : "f"(hi), "f"(lo)); return r;
}
__device__ __forceinline__ float bf_lo(uint32_t v) { return __uint_as_float(v << 16); }
__device__ __forceinline__ float bf_hi(uint32_t v) { return __uint_as_float(v & 0xffff0000u); }
__device__ __forceinline__ float bf_round(float v) { return __bfloat162float(__float2bfloat16_rn(v)); }
__device__ __forceinline__ float ex2(float v) { float r; asm("ex2.approx.ftz.f32 %0, %1;" : "=f"(r) : "f"(v)); return r; }
__device__ __forceinline__ void ex2v(float& v) { asm volatile("ex2.approx.ftz.f32 %0, %0;" : "+f"(v)); }
__device__ __forceinline__ float rcp_fast(float v) { float r; asm("rcp.approx.ftz.f32 %0, %1;" : "=f"(r) : "f"(v)); return r; }
__device__ __forceinline__ float sqrt_fast(float v) { float r; asm("sqrt.approx.ftz.f32 %0, %1;" : "=f"(r) : "f"(v)); return r; }
__device__ __forceinline__ void stg128(void* p, uint32_t a, uint32_t b, uint32_t c, uint32_t d) {
    asm volatile("st.global.v4.b32 [%0], {%1,%2,%3,%4};" ::"l"(p), "r"(a), "r"(b), "r"(c), "r"(d) : "memory");
}
__device__ __forceinline__ void stg128_hint(void* p, uint32_t a, uint32_t b, uint32_t c, uint32_t d, uint64_t pol) {
    asm volatile("st.global.L2::cache_hint.v4.b32 [%0], {%1,%2,%3,%4}, %5;" ::"l"(p), "r"(a), "r"(b), "r"(c), "r"(d), "l"(pol) : "memory");
}
__device__ __forceinline__ uint4 ldg128(const void* p) {
    uint4 v; asm volatile("ld.global.cg.v4.b32 {%0,%1,%2,%3}, [%4];" : "=r"(v.x), "=r"(v.y), "=r"(v.z), "=r"(v.w) : "l"(p) : "memory"); return v;
}
__device__ __forceinline__ uint64_t mkdesc(uint32_t addr, uint32_t lbo, uint32_t sbo, uint32_t swz) {
    uint64_t d;
    asm("mad.wide.u32 %0, %1, 1, %2;" : "=l"(d) : "r"((addr & 0x3FFFF) >> 4), "l"(((uint64_t)((sbo >> 4) | (swz << 30)) << 32) | ((lbo >> 4) << 16)));
    return d;
}
__device__ __forceinline__ int perm32(int v) { return (v & ~30) | ((v >> 2) & 6) | ((v << 2) & 24); }

__device__ __forceinline__ void wgmma_rs_n128_ta0_tb0(float (&d)[64], uint32_t a0, uint32_t a1, uint32_t a2, uint32_t a3, uint64_t descB, int scaleD) {
  asm volatile("{\n.reg .pred p;\nsetp.ne.b32 p, %69, 0;\n"
    "wgmma.mma_async.sync.aligned.m64n128k16.f32.bf16.bf16 "
    "{%0, %1, %2, %3, %4, %5, %6, %7, %8, %9, %10, %11, %12, %13, %14, %15, %16, %17, %18, %19, %20, %21, %22, %23, %24, %25, %26, %27, %28, %29, %30, %31, %32, %33, %34, %35, %36, %37, %38, %39, %40, %41, %42, %43, %44, %45, %46, %47, %48, %49, %50, %51, %52, %53, %54, %55, %56, %57, %58, %59, %60, %61, %62, %63}, "
    "{%64, %65, %66, %67}, %68, p, 1, 1, 0;\n}\n"
    : "+f"(d[0]), "+f"(d[1]), "+f"(d[2]), "+f"(d[3]), "+f"(d[4]), "+f"(d[5]), "+f"(d[6]), "+f"(d[7]), "+f"(d[8]), "+f"(d[9]), "+f"(d[10]), "+f"(d[11]), "+f"(d[12]), "+f"(d[13]), "+f"(d[14]), "+f"(d[15]), "+f"(d[16]), "+f"(d[17]), "+f"(d[18]), "+f"(d[19]), "+f"(d[20]), "+f"(d[21]), "+f"(d[22]), "+f"(d[23]), "+f"(d[24]), "+f"(d[25]), "+f"(d[26]), "+f"(d[27]), "+f"(d[28]), "+f"(d[29]), "+f"(d[30]), "+f"(d[31]), "+f"(d[32]), "+f"(d[33]), "+f"(d[34]), "+f"(d[35]), "+f"(d[36]), "+f"(d[37]), "+f"(d[38]), "+f"(d[39]), "+f"(d[40]), "+f"(d[41]), "+f"(d[42]), "+f"(d[43]), "+f"(d[44]), "+f"(d[45]), "+f"(d[46]), "+f"(d[47]), "+f"(d[48]), "+f"(d[49]), "+f"(d[50]), "+f"(d[51]), "+f"(d[52]), "+f"(d[53]), "+f"(d[54]), "+f"(d[55]), "+f"(d[56]), "+f"(d[57]), "+f"(d[58]), "+f"(d[59]), "+f"(d[60]), "+f"(d[61]), "+f"(d[62]), "+f"(d[63])
    : "r"(a0), "r"(a1), "r"(a2), "r"(a3), "l"(descB), "r"(scaleD));
}
__device__ __forceinline__ void wgmma_rs_n128_ta0_tb1(float (&d)[64], uint32_t a0, uint32_t a1, uint32_t a2, uint32_t a3, uint64_t descB, int scaleD) {
  asm volatile("{\n.reg .pred p;\nsetp.ne.b32 p, %69, 0;\n"
    "wgmma.mma_async.sync.aligned.m64n128k16.f32.bf16.bf16 "
    "{%0, %1, %2, %3, %4, %5, %6, %7, %8, %9, %10, %11, %12, %13, %14, %15, %16, %17, %18, %19, %20, %21, %22, %23, %24, %25, %26, %27, %28, %29, %30, %31, %32, %33, %34, %35, %36, %37, %38, %39, %40, %41, %42, %43, %44, %45, %46, %47, %48, %49, %50, %51, %52, %53, %54, %55, %56, %57, %58, %59, %60, %61, %62, %63}, "
    "{%64, %65, %66, %67}, %68, p, 1, 1, 1;\n}\n"
    : "+f"(d[0]), "+f"(d[1]), "+f"(d[2]), "+f"(d[3]), "+f"(d[4]), "+f"(d[5]), "+f"(d[6]), "+f"(d[7]), "+f"(d[8]), "+f"(d[9]), "+f"(d[10]), "+f"(d[11]), "+f"(d[12]), "+f"(d[13]), "+f"(d[14]), "+f"(d[15]), "+f"(d[16]), "+f"(d[17]), "+f"(d[18]), "+f"(d[19]), "+f"(d[20]), "+f"(d[21]), "+f"(d[22]), "+f"(d[23]), "+f"(d[24]), "+f"(d[25]), "+f"(d[26]), "+f"(d[27]), "+f"(d[28]), "+f"(d[29]), "+f"(d[30]), "+f"(d[31]), "+f"(d[32]), "+f"(d[33]), "+f"(d[34]), "+f"(d[35]), "+f"(d[36]), "+f"(d[37]), "+f"(d[38]), "+f"(d[39]), "+f"(d[40]), "+f"(d[41]), "+f"(d[42]), "+f"(d[43]), "+f"(d[44]), "+f"(d[45]), "+f"(d[46]), "+f"(d[47]), "+f"(d[48]), "+f"(d[49]), "+f"(d[50]), "+f"(d[51]), "+f"(d[52]), "+f"(d[53]), "+f"(d[54]), "+f"(d[55]), "+f"(d[56]), "+f"(d[57]), "+f"(d[58]), "+f"(d[59]), "+f"(d[60]), "+f"(d[61]), "+f"(d[62]), "+f"(d[63])
    : "r"(a0), "r"(a1), "r"(a2), "r"(a3), "l"(descB), "r"(scaleD));
}
__device__ __forceinline__ void wgmma_rs_n64_ta0_tb1(float (&d)[32], uint32_t a0, uint32_t a1, uint32_t a2, uint32_t a3, uint64_t descB, int scaleD) {
  asm volatile("{\n.reg .pred p;\nsetp.ne.b32 p, %37, 0;\n"
    "wgmma.mma_async.sync.aligned.m64n64k16.f32.bf16.bf16 "
    "{%0, %1, %2, %3, %4, %5, %6, %7, %8, %9, %10, %11, %12, %13, %14, %15, %16, %17, %18, %19, %20, %21, %22, %23, %24, %25, %26, %27, %28, %29, %30, %31}, "
    "{%32, %33, %34, %35}, %36, p, 1, 1, 1;\n}\n"
    : "+f"(d[0]), "+f"(d[1]), "+f"(d[2]), "+f"(d[3]), "+f"(d[4]), "+f"(d[5]), "+f"(d[6]), "+f"(d[7]), "+f"(d[8]), "+f"(d[9]), "+f"(d[10]), "+f"(d[11]), "+f"(d[12]), "+f"(d[13]), "+f"(d[14]), "+f"(d[15]), "+f"(d[16]), "+f"(d[17]), "+f"(d[18]), "+f"(d[19]), "+f"(d[20]), "+f"(d[21]), "+f"(d[22]), "+f"(d[23]), "+f"(d[24]), "+f"(d[25]), "+f"(d[26]), "+f"(d[27]), "+f"(d[28]), "+f"(d[29]), "+f"(d[30]), "+f"(d[31])
    : "r"(a0), "r"(a1), "r"(a2), "r"(a3), "l"(descB), "r"(scaleD));
}
__device__ __forceinline__ void wgmma_ss_n128_ta0_tb1(float (&d)[64], uint64_t descA, uint64_t descB, int scaleD) {
  asm volatile("{\n.reg .pred p;\nsetp.ne.b32 p, %66, 0;\n"
    "wgmma.mma_async.sync.aligned.m64n128k16.f32.bf16.bf16 "
    "{%0, %1, %2, %3, %4, %5, %6, %7, %8, %9, %10, %11, %12, %13, %14, %15, %16, %17, %18, %19, %20, %21, %22, %23, %24, %25, %26, %27, %28, %29, %30, %31, %32, %33, %34, %35, %36, %37, %38, %39, %40, %41, %42, %43, %44, %45, %46, %47, %48, %49, %50, %51, %52, %53, %54, %55, %56, %57, %58, %59, %60, %61, %62, %63}, "
    "%64, %65, p, 1, 1, 0, 1;\n}\n"
    : "+f"(d[0]), "+f"(d[1]), "+f"(d[2]), "+f"(d[3]), "+f"(d[4]), "+f"(d[5]), "+f"(d[6]), "+f"(d[7]), "+f"(d[8]), "+f"(d[9]), "+f"(d[10]), "+f"(d[11]), "+f"(d[12]), "+f"(d[13]), "+f"(d[14]), "+f"(d[15]), "+f"(d[16]), "+f"(d[17]), "+f"(d[18]), "+f"(d[19]), "+f"(d[20]), "+f"(d[21]), "+f"(d[22]), "+f"(d[23]), "+f"(d[24]), "+f"(d[25]), "+f"(d[26]), "+f"(d[27]), "+f"(d[28]), "+f"(d[29]), "+f"(d[30]), "+f"(d[31]), "+f"(d[32]), "+f"(d[33]), "+f"(d[34]), "+f"(d[35]), "+f"(d[36]), "+f"(d[37]), "+f"(d[38]), "+f"(d[39]), "+f"(d[40]), "+f"(d[41]), "+f"(d[42]), "+f"(d[43]), "+f"(d[44]), "+f"(d[45]), "+f"(d[46]), "+f"(d[47]), "+f"(d[48]), "+f"(d[49]), "+f"(d[50]), "+f"(d[51]), "+f"(d[52]), "+f"(d[53]), "+f"(d[54]), "+f"(d[55]), "+f"(d[56]), "+f"(d[57]), "+f"(d[58]), "+f"(d[59]), "+f"(d[60]), "+f"(d[61]), "+f"(d[62]), "+f"(d[63])
    : "l"(descA), "l"(descB), "r"(scaleD));
}
__device__ __forceinline__ void wgmma_ss_n160_ta0_tb1(float (&d)[80], uint64_t descA, uint64_t descB, int scaleD) {
  asm volatile("{\n.reg .pred p;\nsetp.ne.b32 p, %82, 0;\n"
    "wgmma.mma_async.sync.aligned.m64n160k16.f32.bf16.bf16 "
    "{%0, %1, %2, %3, %4, %5, %6, %7, %8, %9, %10, %11, %12, %13, %14, %15, %16, %17, %18, %19, %20, %21, %22, %23, %24, %25, %26, %27, %28, %29, %30, %31, %32, %33, %34, %35, %36, %37, %38, %39, %40, %41, %42, %43, %44, %45, %46, %47, %48, %49, %50, %51, %52, %53, %54, %55, %56, %57, %58, %59, %60, %61, %62, %63, %64, %65, %66, %67, %68, %69, %70, %71, %72, %73, %74, %75, %76, %77, %78, %79}, "
    "%80, %81, p, 1, 1, 0, 1;\n}\n"
    : "+f"(d[0]), "+f"(d[1]), "+f"(d[2]), "+f"(d[3]), "+f"(d[4]), "+f"(d[5]), "+f"(d[6]), "+f"(d[7]), "+f"(d[8]), "+f"(d[9]), "+f"(d[10]), "+f"(d[11]), "+f"(d[12]), "+f"(d[13]), "+f"(d[14]), "+f"(d[15]), "+f"(d[16]), "+f"(d[17]), "+f"(d[18]), "+f"(d[19]), "+f"(d[20]), "+f"(d[21]), "+f"(d[22]), "+f"(d[23]), "+f"(d[24]), "+f"(d[25]), "+f"(d[26]), "+f"(d[27]), "+f"(d[28]), "+f"(d[29]), "+f"(d[30]), "+f"(d[31]), "+f"(d[32]), "+f"(d[33]), "+f"(d[34]), "+f"(d[35]), "+f"(d[36]), "+f"(d[37]), "+f"(d[38]), "+f"(d[39]), "+f"(d[40]), "+f"(d[41]), "+f"(d[42]), "+f"(d[43]), "+f"(d[44]), "+f"(d[45]), "+f"(d[46]), "+f"(d[47]), "+f"(d[48]), "+f"(d[49]), "+f"(d[50]), "+f"(d[51]), "+f"(d[52]), "+f"(d[53]), "+f"(d[54]), "+f"(d[55]), "+f"(d[56]), "+f"(d[57]), "+f"(d[58]), "+f"(d[59]), "+f"(d[60]), "+f"(d[61]), "+f"(d[62]), "+f"(d[63]), "+f"(d[64]), "+f"(d[65]), "+f"(d[66]), "+f"(d[67]), "+f"(d[68]), "+f"(d[69]), "+f"(d[70]), "+f"(d[71]), "+f"(d[72]), "+f"(d[73]), "+f"(d[74]), "+f"(d[75]), "+f"(d[76]), "+f"(d[77]), "+f"(d[78]), "+f"(d[79])
    : "l"(descA), "l"(descB), "r"(scaleD));
}


template <int N> struct IC { static constexpr int value = N; };
struct Cur {
    uint32_t slot, ph;
    __device__ __forceinline__ void adv() { if (++slot == NSLOT) { slot = 0; ph ^= 1; } }
};
constexpr int E0 = 2;
__host__ __device__ constexpr uint32_t slot_of(int e) { return (e + E0) % NSLOT; }
__device__ __forceinline__ Cur cur_at(int e) { Cur c; c.slot = (e + E0) % NSLOT; c.ph = ((e + E0) / NSLOT) & 1; return c; }

__device__ __forceinline__ int kv_tile(int s) { return (0x804Cu >> (4 * s)) & 15; }
__device__ __forceinline__ int op_head(int i, int kap) { return 8 * kap + (i & 7) + 16 * (i >> 3); }

constexpr float V_SCALE = 0.125f, X_SCALE = 0.5f;
constexpr float SM_SCALE = 0.08838834764831845f * 1.4426950408889634f;

struct Ctx {
    uint32_t ring, misc;
    uint32_t rel;
    int w, warp, lane;
};
__device__ __forceinline__ void release(const Ctx& c, uint32_t off, uint32_t cnt) {
    if (c.lane < 2) mbar_arrive_cluster(c.rel + off, cnt);
}
__device__ __forceinline__ void signal_event(const Ctx& c, int ev) {
    __syncwarp();
    if (c.lane == 0) mbar_arrive(c.misc + BAR_EV + (c.w * NEV + ev) * 8);
}
template <int NK, int OFF, int N>
__device__ __forceinline__ uint32_t load_afrag(uint32_t (&a)[N], uint32_t base, const Ctx& c) {
    int r = c.lane & 7, mat = c.lane >> 3;
    uint32_t addr = base + (8 * (mat >> 1) + r) * 128 + (((2 * c.warp + (mat & 1)) ^ r) << 4);
#pragma unroll
    for (int k = 0; k < NK; k++) ldsm4t(a[OFF + 4 * k], a[OFF + 4 * k + 1], a[OFF + 4 * k + 2], a[OFF + 4 * k + 3], addr + k * 2048);
    uint32_t dep = 0;
#pragma unroll
    for (int k = 0; k < NK; k++) dep |= a[OFF + 4 * k];
    return dep & blockIdx.y;
}
__device__ __forceinline__ void tile_out(unsigned char* (&out)[2], unsigned char* dst, int row0, int perm, const Ctx& c) {
#pragma unroll
    for (int i = 0; i < 2; i++) {
        int row = row0 + 16 * c.warp + 8 * i + (c.lane >> 2);
        if (perm) row = perm32(row);
        out[i] = dst + row * 64 + (((c.lane ^ (row >> 1)) & 3) << 4);
    }
}
__device__ __forceinline__ void store_pair(const float (&a)[64], int q, unsigned char* const (&out)[2], int quarter_stride, const float (&f)[2], bool stream = false) {
    const uint64_t pol = stream ? policy_stream() : 0x1000000000000000ull  ;
#pragma unroll
    for (int i = 0; i < 2; i++)
        stg128_hint(out[i] + q * quarter_stride,
               pack_bf16(a[16 * q + 2 * i] * f[i], a[16 * q + 2 * i + 1] * f[i]), pack_bf16(a[16 * q + 4 + 2 * i] * f[i], a[16 * q + 4 + 2 * i + 1] * f[i]),
               pack_bf16(a[16 * q + 8 + 2 * i] * f[i], a[16 * q + 8 + 2 * i + 1] * f[i]), pack_bf16(a[16 * q + 12 + 2 * i] * f[i], a[16 * q + 12 + 2 * i + 1] * f[i]), pol);
}

constexpr float SAFE_SUM = 1099511627776.0f;
template <int NJ>
__device__ __forceinline__ void row_max(const float (&s)[4 * NJ], float (&mx)[2]) {
#pragma unroll
    for (int i = 0; i < 2; i++) {
        float a = fmaxf(s[2 * i], s[2 * i + 1]), b = fmaxf(s[4 + 2 * i], s[4 + 2 * i + 1]);
#pragma unroll
        for (int j = 2; j < NJ; j += 2) {
            a = fmaxf(a, fmaxf(s[4 * j + 2 * i], s[4 * j + 2 * i + 1]));
            b = fmaxf(b, fmaxf(s[4 * j + 4 + 2 * i], s[4 * j + 4 + 2 * i + 1]));
        }
        a = fmaxf(a, b);
        a = fmaxf(a, __shfl_xor_sync(0xffffffffu, a, 1));
        mx[i] = fmaxf(a, __shfl_xor_sync(0xffffffffu, a, 2));
    }
}
template <int NJ, bool SHIFT>
__device__ __forceinline__ void exp_sum(float (&s)[4 * NJ], const float (&m)[2], float& l0, float& l1) {
#pragma unroll
    for (int j = 0; j < NJ; j++) {
#pragma unroll
        for (int e = 0; e < 4; e++) s[4 * j + e] = ex2(SHIFT ? s[4 * j + e] - m[e >> 1] : s[4 * j + e]);
        l0 += s[4 * j + 0] + s[4 * j + 1]; l1 += s[4 * j + 2] + s[4 * j + 3];
    }
}
__device__ __forceinline__ void recompute_scores(float (&s)[64], const uint32_t (&q)[32], uint32_t kaddr, const Ctx& c) {
    const int r = c.lane & 7, mat = c.lane >> 3;
    const uint32_t a0 = kaddr + (8 * (mat & 1) + r) * 64 + (((mat >> 1) ^ (r >> 1)) << 4);
#pragma unroll
    for (int i = 0; i < 64; i++) s[i] = 0.f;
#pragma unroll
    for (int jp = 0; jp < 8; jp++) {
#pragma unroll
        for (int k = 0; k < 8; k++) {
            asm volatile(
                "{\n.reg .b32 b0, b1, b2, b3;\n"
                "ldmatrix.sync.aligned.m8n8.x4.trans.shared.b16 {b0,b1,b2,b3}, [%12];\n"
                "mma.sync.aligned.m16n8k16.row.col.f32.bf16.bf16.f32 {%0,%1,%2,%3}, {%8,%9,%10,%11}, {b0,b1}, {%0,%1,%2,%3};\n"
                "mma.sync.aligned.m16n8k16.row.col.f32.bf16.bf16.f32 {%4,%5,%6,%7}, {%8,%9,%10,%11}, {b2,b3}, {%4,%5,%6,%7};\n}\n"
                : "+f"(s[8 * jp]), "+f"(s[8 * jp + 1]), "+f"(s[8 * jp + 2]), "+f"(s[8 * jp + 3]),
                  "+f"(s[8 * jp + 4]), "+f"(s[8 * jp + 5]), "+f"(s[8 * jp + 6]), "+f"(s[8 * jp + 7])
                : "r"(q[4 * k]), "r"(q[4 * k + 1]), "r"(q[4 * k + 2]), "r"(q[4 * k + 3]),
                  "r"((a0 ^ ((jp & 1) << 5)) + (jp >> 1) * 8192 + k * 1024) : "memory");
        }
    }
}
__device__ __forceinline__ int mask_lim(const Ctx& c) { return perm32(16 * c.warp + (c.lane >> 2)) - 8 * (c.lane & 3); }
__device__ __forceinline__ void mask_diag(float (&s)[32], const Ctx& c) {
    const int lim = mask_lim(c);
    if (c.warp < 2) {
#pragma unroll
        for (int x = 0; x < 16; x++) {
            if (2 * (x >> 2) + (x & 1) - (x & 2) > lim) s[x] = -INFINITY;
            s[16 + x] = -INFINITY;
        }
    } else {
#pragma unroll
        for (int x = 0; x < 16; x++)
            if (32 + 2 * (x >> 2) + (x & 1) - (x & 2) > lim) s[16 + x] = -INFINITY;
    }
}
__device__ __forceinline__ void mask_any(float (&s)[64], int hh, const Ctx& c) {
    const int lim = mask_lim(c) + 64 * hh;
#pragma unroll
    for (int x = 0; x < 64; x++)
        if (32 * (x >> 4) + 2 * ((x >> 2) & 3) + (x & 1) - (x & 2) > lim) s[x] = -INFINITY;
}
__device__ __forceinline__ void issue_pv(float (&o)[64], const uint32_t (&p)[32], uint32_t vaddr, int acc, int mode  ) {
    uint64_t d = mkdesc(vaddr, 16, 512, 2);
    if (mode == 0) {
        wg_fence();
#pragma unroll
        for (int k = 0; k < 8; k++)
            wgmma_rs_n128_ta0_tb0(o, p[4 * k], p[4 * k + 1], p[4 * k + 2], p[4 * k + 3], d + (k >> 1) * 512 + 2 * (k & 1), k ? 1 : acc);
        wg_commit();
    } else if (mode == 1) {
        wg_fence();
#pragma unroll
        for (int k = 0; k < 4; k++) wgmma_rs_n128_ta0_tb0(o, p[4 * k], p[4 * k + 1], p[4 * k + 2], p[4 * k + 3], d + (k >> 1) * 512 + 2 * (k & 1), k != 0);
        wg_commit();
    } else {
        wg_fence();
        wgmma_rs_n128_ta0_tb0(o, p[0], p[1], p[2], p[3], d, acc);
        wg_commit();
    }
}
__device__ __forceinline__ void issue_qk(float (&s)[64], const uint32_t (&q)[32], uint32_t kaddr) {
    uint64_t d = mkdesc(kaddr, 8192, 512, 2);
    wg_fence();
#pragma unroll
    for (int k = 0; k < 8; k++) wgmma_rs_n128_ta0_tb1(s, q[4 * k], q[4 * k + 1], q[4 * k + 2], q[4 * k + 3], d + 64 * k, k != 0);
    wg_commit();
}
__device__ __forceinline__ void issue_qk_half(float (&s32)[32], const uint32_t (&q)[32], uint32_t kaddr) {
    uint64_t d = mkdesc(kaddr, 8192, 512, 2);
    wg_fence();
#pragma unroll
    for (int k = 0; k < 8; k++) wgmma_rs_n64_ta0_tb1(s32, q[4 * k], q[4 * k + 1], q[4 * k + 2], q[4 * k + 3], d + 64 * k, k != 0);
    wg_commit();
}
__device__ __forceinline__ void row_inv(const float (&l)[2], float (&inv)[2]) {
#pragma unroll
    for (int i = 0; i < 2; i++) {
        float sum = l[i];
        sum += __shfl_xor_sync(0xffffffffu, sum, 1);
        sum += __shfl_xor_sync(0xffffffffu, sum, 2);
        inv[i] = rcp_fast(sum * V_SCALE);
    }
}

__device__ __forceinline__ const unsigned char* xn_addr(int row, int col) {
    row = perm32(row);
    return g_xn + ((row >> 7) * 10 + (col >> 6)) * 16384 + (row & 127) * 128 + ((((col & 63) >> 3) ^ (row & 7)) << 4);
}
__device__ __forceinline__ void mma16816(float (&d)[4], uint32_t a0, uint32_t a1, uint32_t a2, uint32_t a3, uint32_t b0, uint32_t b1) {
    asm volatile("mma.sync.aligned.m16n8k16.row.col.f32.bf16.bf16.f32 {%0,%1,%2,%3}, {%4,%5,%6,%7}, {%8,%9}, {%0,%1,%2,%3};"
                 : "+f"(d[0]), "+f"(d[1]), "+f"(d[2]), "+f"(d[3]) : "r"(a0), "r"(a1), "r"(a2), "r"(a3), "r"(b0), "r"(b1));
}
__device__ __forceinline__ uint32_t lds32(uint32_t addr) { uint32_t v; asm volatile("ld.shared.u32 %0, [%1];" : "=r"(v) : "r"(addr)); return v; }

__device__ __forceinline__ int fresh_lane() { int l; asm volatile("mov.u32 %0, %%laneid;" : "=r"(l)); return l; }
__device__ __forceinline__ void ln_rows(const __nv_bfloat16* x, int row0, uint32_t wr_s) {
    int lane = fresh_lane();
    int hl = lane & 15, row = row0 + (lane >> 4);
    uint32_t v[20];
#pragma unroll
    for (int i = 0; i < 5; i++) {
        const uint4 u = __ldg(reinterpret_cast<const uint4*>(x + (size_t)row * DM + 128 * i + 8 * hl));
        v[4 * i] = u.x; v[4 * i + 1] = u.y; v[4 * i + 2] = u.z; v[4 * i + 3] = u.w;
    }
    float mean = 0.f, m2 = 0.f, acc2 = 0.f;
#pragma unroll
    for (int i = 0; i < 20; i++) { mean += bf_lo(v[i]); acc2 += bf_hi(v[i]); }
    mean = (mean + acc2) * (1.0f / 40);
    acc2 = 0.f;
#pragma unroll
    for (int i = 0; i < 20; i++) {
        float d0 = __uint_as_float(__byte_perm(v[i], 0, 0x1044)) - mean, d1 = __uint_as_float(__byte_perm(v[i], 0, 0x3244)) - mean;
        m2 = fmaf(d0, d0, m2); acc2 = fmaf(d1, d1, acc2);
    }
    m2 += acc2;
    acc2 = 0.f;
#pragma unroll
    for (int o = 1; o < 16; o <<= 1) {
        float mo = __shfl_xor_sync(0xffffffffu, mean, o), qo = __shfl_xor_sync(0xffffffffu, m2, o), d = mo - mean;
        m2 = fmaf(d * d, 20.0f * o, m2 + qo);
        mean = 0.5f * (mean + mo);
    }
    const uint32_t mb2 = pack_bf16(mean, mean);
    const float inv = rcp_fast(bf_round(sqrt_fast(bf_round(bf_round(m2 * (1.0f / DM)) + 1e-5f))));
    float dot = 0.f;
    lane = fresh_lane(); hl = lane & 15; row = row0 + (lane >> 4);
    if (hl == 0) g_stats[row] = make_uint2(mb2, __float_as_uint(inv));
    unsigned char* xp = const_cast<unsigned char*>(xn_addr(row, 8 * hl));
    const float invs = inv * X_SCALE;
#pragma unroll
    for (int i = 0; i < 5; i++) {
        uint32_t ww[4];
        asm volatile("ld.shared.v4.b32 {%0,%1,%2,%3}, [%4];" : "=r"(ww[0]), "=r"(ww[1]), "=r"(ww[2]), "=r"(ww[3]) : "r"(wr_s + 256 * i + 16 * hl) : "memory");
#pragma unroll
        for (int e = 0; e < 4; e++) {
            uint32_t d;
            asm("sub.rn.bf16x2 %0, %1, %2;" : "=r"(d) : "r"(v[4 * i + e]), "r"(mb2));
            d = pack_bf16(bf_lo(d) * invs, bf_hi(d) * invs);
            v[4 * i + e] = d;
            dot = fmaf(bf_lo(d), bf_lo(ww[e]), dot);
            acc2 = fmaf(bf_hi(d), bf_hi(ww[e]), acc2);
        }
        stg128(xp + i * 32768, v[4 * i], v[4 * i + 1], v[4 * i + 2], v[4 * i + 3]);
    }
    dot += acc2;
#pragma unroll
    for (int o = 8; o > 0; o >>= 1) dot += __shfl_xor_sync(0xffffffffu, dot, o);
    lane = fresh_lane();
    if ((lane & 15) == 0) g_router[row0 + (lane >> 4)] = bf_round(dot * (1.0f / X_SCALE));
}

__device__ __forceinline__ void aux_cta(const CUtensorMap* tmG, const CUtensorMap* tmU, const CUtensorMap* tmD, unsigned char* sm, int a) {
    constexpr int STG = 57344, XS = 3 * STG, HS = XS + 8 * 1296, KEY = HS + 8 * 912, MI = KEY + 8192;
    const int tid = threadIdx.x, warp = __shfl_sync(0xffffffffu, tid >> 5, 0), lane = tid & 31;
    const uint32_t sb = smem_u32(sm);
    const uint32_t full = sb + MI, empty = sb + MI + 32;
    int* s_sel = reinterpret_cast<int*>(sm + MI + 64);
    float* s_r = reinterpret_cast<float*>(sm + MI + 96);
    volatile unsigned* s_misc = reinterpret_cast<volatile unsigned*>(sm + MI + 128);
    uint32_t* s_key = reinterpret_cast<uint32_t*>(sm + KEY);
    if (tid == 0) {
        for (int i = 0; i < 3; i++) { mbar_init(full + 8 * i, 1); mbar_init(empty + 8 * i, 10); }
        asm volatile("fence.mbarrier_init.release.cluster;" ::: "memory");
    }
    __syncthreads();
    if (warp == 11) {
        if (elect_one()) {
            const unsigned ep1 = *reinterpret_cast<volatile unsigned*>(&g_epoch) + 1;
            __nanosleep(20000);
            flag_wait(flag_ptr(FL_CTX + (18 + a) * 8), ep1 * 4u);
            int st = 0; uint32_t ph = 0;
#pragma unroll 1
            for (int s = 0; s < 34; s++) {
                mbar_wait(empty + 8 * st, ph ^ 1);
                const uint32_t dst = sb + st * STG, fb = full + 8 * st;
                if (s < 20) {
                    mbar_expect_tx(fb, 57344);
                    tma3d(dst, tmG, 0, 32 * s, 7 * a, fb);
                    tma3d(dst + 28672, tmU, 0, 32 * s, 7 * a, fb);
                } else {
                    mbar_expect_tx(fb, 40960);
                    tma3d(dst, tmD, 0, 448 * a + 32 * (s - 20), 0, fb);
                }
                if (s >= 2) {
#pragma unroll 1
                    for (int f = (s == 2 ? 3 : s + 6); f <= s + 6 && f < 34; f++) {
                        if (f < 20) { tma3d_prefetch(tmG, 0, 32 * f, 7 * a); tma3d_prefetch(tmU, 0, 32 * f, 7 * a); }
                        else tma3d_prefetch(tmD, 0, 448 * a + 32 * (f - 20), 0);
                    }
                }
                if (++st == 3) { st = 0; ph ^= 1; }
            }
        }
        return;
    }
    if (warp == 10) return;
    if (tid < 8) {
        unsigned e = *reinterpret_cast<volatile unsigned*>(&g_epoch);
        if (tid == 0) s_misc[0] = e;
        flag_wait(flag_ptr(FL_LN + tid), (e + 1) * (tid < 4 ? 64u : 128u));
    }
    bar_sync(1, 320);
    const unsigned ep = s_misc[0];
    auto top8 = [&](uint32_t (&key)[8]) {
        uint32_t mine = 0;
#pragma unroll 1
        for (int r = 0; r < TOPC; r++) {
            uint32_t best = 0;
#pragma unroll
            for (int i = 0; i < 8; i++) best = max(best, key[i]);
            best = __reduce_max_sync(0xffffffffu, best);
#pragma unroll
            for (int i = 0; i < 8; i++) if (key[i] == best) key[i] = 0;
            if (lane == r) mine = best;
        }
        return mine;
    };
#pragma unroll 1
    for (int pass = 0; pass < 2; pass++) {
        if (warp < (pass ? 1 : 8)) {
            uint32_t key[8];
#pragma unroll
            for (int i = 0; i < 8; i++) {
                if (pass == 0) {
                    int idx = warp * 256 + i * 32 + lane;
                    uint32_t b = __float_as_uint(__ldcg(g_router + idx)) >> 16;
                    b = (b & 0x8000u) ? (~b & 0xffffu) : (b | 0x8000u);
                    key[i] = (b << 16) | (uint32_t)(0xffff - idx);
                } else key[i] = i < 2 ? s_key[i * 32 + lane] : 0u;
            }
            uint32_t best = top8(key);
            if (lane < TOPC) {
                if (pass == 0) s_key[warp * 8 + lane] = best;
                else {
                    uint32_t b = best >> 16;
                    b = (b & 0x8000u) ? (b & 0x7fffu) : (~b & 0xffffu);
                    s_sel[lane] = 0xffff - (int)(best & 0xffffu);
                    s_r[lane] = bf_round(rcp_fast(1.0f + __expf(fminf(-__uint_as_float(b << 16), 80.f))));
                }
            }
        }
        bar_sync(1, 320);
    }
#pragma unroll 1
    for (int it = 0; it < 2; it++) {
        int i = tid + it * 320, tk = i / 80, ch = i % 80;
        uint4 u = __ldcg(reinterpret_cast<const uint4*>(xn_addr(s_sel[tk], ch * 8)));
        const uint32_t un = pack_bf16(1.0f / X_SCALE, 1.0f / X_SCALE);
        asm("mul.rn.bf16x2 %0, %0, %1;" : "+r"(u.x) : "r"(un)); asm("mul.rn.bf16x2 %0, %0, %1;" : "+r"(u.y) : "r"(un));
        asm("mul.rn.bf16x2 %0, %0, %1;" : "+r"(u.z) : "r"(un)); asm("mul.rn.bf16x2 %0, %0, %1;" : "+r"(u.w) : "r"(un));
        *reinterpret_cast<uint4*>(sm + XS + tk * 1296 + ch * 16) = u;
    }
    bar_sync(1, 320);
    const int g = lane >> 2, t = lane & 3;
    const uint32_t woff = warp * 4096 + (8 * (lane >> 4) + (lane & 7)) * 128 + ((((lane >> 3) & 1) ^ (lane & 7)) << 4);
    int st = 0; uint32_t ph = 0;
    float ga[4][4], ua[4][4];
#pragma unroll
    for (int i = 0; i < 4; i++)
#pragma unroll
        for (int e = 0; e < 4; e++) { ga[i][e] = 0.f; ua[i][e] = 0.f; }
#pragma unroll 1
    for (int s = 0; s < 34; s++) {
        if (s == 20) {
            if (warp < 7) {
#pragma unroll 1
                for (int i = 0; i < 4; i++) {
#pragma unroll
                    for (int e = 0; e < 4; e++) {
                        float gv = bf_round(ga[0][e]), uv = bf_round(ua[0][e]);
                        float sg = bf_round(gv * rcp_fast(1.0f + __expf(fminf(-gv, 80.f))));
                        int f = warp * 64 + i * 16 + g + 8 * (e >> 1), tk = 2 * t + (e & 1);
                        *reinterpret_cast<__nv_bfloat16*>(sm + HS + tk * 912 + f * 2) = __float2bfloat16_rn(sg * uv);
                        ga[0][e] = ga[1][e]; ga[1][e] = ga[2][e]; ga[2][e] = ga[3][e]; ga[3][e] = 0.f;
                        ua[0][e] = ua[1][e]; ua[1][e] = ua[2][e]; ua[2][e] = ua[3][e];
                    }
                }
            }
            bar_sync(1, 320);
        }
        mbar_wait(full + 8 * st, ph);
        if (s >= 20 || warp < 7) {
#pragma unroll
            for (int kk = 0; kk < 2; kk++) {
                uint32_t xb = sb + (s < 20 ? XS + g * 1296 + s * 64 : HS + g * 912 + (s - 20) * 64) + 32 * kk + 4 * t;
                uint32_t b0 = lds32(xb), b1 = lds32(xb + 16);
                uint32_t wa = sb + st * STG + woff + kk * 2048;
#pragma unroll
                for (int i = 0; i < 4; i++) {
                    uint32_t a0, a1, a2, a3;
                    ldsm4t(a0, a1, a2, a3, wa ^ (i << 5));
                    mma16816(ga[i], a0, a1, a2, a3, b0, b1);
                    if (s < 20) {
                        ldsm4t(a0, a1, a2, a3, (wa ^ (i << 5)) + 28672);
                        mma16816(ua[i], a0, a1, a2, a3, b0, b1);
                    }
                }
            }
        }
        asm volatile("fence.proxy.async.shared::cta;" ::: "memory");
        __syncwarp();
        if (lane == 0) mbar_arrive(empty + 8 * st);
        if (++st == 3) { st = 0; ph ^= 1; }
    }
#pragma unroll
    for (int i = 0; i < 4; i++)
#pragma unroll
        for (int e = 0; e < 4; e += 2)
            *reinterpret_cast<float2*>(g_moe_part + (a * DM + warp * 64 + i * 16 + g + 4 * e) * 8 + 2 * t) = make_float2(ga[i][e], ga[i][e + 1]);
    bar_sync(1, 320);
    if (tid == 0) {
        __threadfence();
        unsigned old = atomicAdd(flag_ptr(FL_MOE_CNT), 1u);
        s_misc[1] = (old == ep * 4u + 3u);
        __threadfence();
    }
    bar_sync(1, 320);
    if (s_misc[1]) {
        const float4* pp = reinterpret_cast<const float4*>(g_moe_part);
#pragma unroll 1
        for (int i = tid; i < DM * 2; i += 320) {
            float4 v0 = __ldcg(pp + i), v1 = __ldcg(pp + DM * 2 + i), v2 = __ldcg(pp + DM * 4 + i), v3 = __ldcg(pp + DM * 6 + i);
            float y[4] = {v0.x + v1.x + v2.x + v3.x, v0.y + v1.y + v2.y + v3.y, v0.z + v1.z + v2.z + v3.z, v0.w + v1.w + v2.w + v3.w};
#pragma unroll
            for (int e = 0; e < 4; e++) {
                int col = i >> 1, tk = (i & 1) * 4 + e;
                float upd = bf_round(bf_round(y[e]) * s_r[tk]);
                float xn = __bfloat162float(*reinterpret_cast<const __nv_bfloat16*>(sm + XS + tk * 1296 + col * 2));
                g_brow[tk * DM + col] = __float2bfloat16_rn(xn + upd);
            }
        }
        if (tid < TOPC) g_sel[tid] = s_sel[tid];
        bar_sync(1, 320);
        if (tid == 0) {
            flag_signal(flag_ptr(FL_MOE_DONE));
            *reinterpret_cast<volatile unsigned*>(&g_epoch) = ep + 1;
        }
    }
}

__global__ void __cluster_dims__(2, 1, 1) __launch_bounds__(384, 1)
fused_kernel(const __grid_constant__ CUtensorMap tmC, const __grid_constant__ CUtensorMap tmWk, const __grid_constant__ CUtensorMap tmWv,
             const __grid_constant__ CUtensorMap tmWq, const __grid_constant__ CUtensorMap tmWo,
             const __grid_constant__ CUtensorMap tmG, const __grid_constant__ CUtensorMap tmU, const __grid_constant__ CUtensorMap tmD, const Params P) {
    extern __shared__ __align__(1024) unsigned char smem_raw[];
    const uint32_t ring = smem_u32(smem_raw);
    const uint32_t misc = ring + RING_BYTES;
    const int tid = threadIdx.x;
    const int rank = blockIdx.x & 1;
    uint32_t smid, nsm;
    asm volatile("mov.u32 %0, %%smid;" : "=r"(smid));
    asm("mov.u32 %0, %%nsmid;" : "=r"(nsm));
    if (nsm != 132) smid = blockIdx.x;
    auto role_of = [](int tpc) {
        return tpc < 32 ? (tpc & 7) * 8 + (tpc >> 3) : tpc < 60 ? (1 + (tpc - 32) % 7) * 8 + 4 + (tpc - 32) / 7 : tpc < 62 ? tpc + 4 : tpc - 58;
    };
    int mc = role_of(smid >> 1);

    auto prefetch_w = [&](int ch) {
        const int i = tid - 128;
        asm volatile("prefetch.global.L2 [%0];" ::"l"((rank ? P.wv : P.wk) + (size_t)(ch * 128 + (mc & 3) * 32 + (i >> 3)) * 4096 + (mc >> 2) * 128 + (i & 7) * 16));
    };
    if (tid >= 128 && mc < 64) {
        if (tid < 256) asm volatile("prefetch.global.L2 [%0];" ::"l"(P.c + (size_t)((12 + (mc & 3)) * 128 + ((mc >> 2) * 2 + rank) * 4) * DC + (tid - 128) * 16));
        prefetch_w(0);
    }
    auto load_w0 = [&]() {
        const CUtensorMap* tw = rank ? &tmWv : &tmWk;
        mbar_expect_tx(misc + BAR_FULL + 8 * slot_of(0), SLOT_BYTES);
        tma2d(ring + slot_of(0) * SLOT_BYTES, tw, (mc >> 2) * 128, 0, misc + BAR_FULL + 8 * slot_of(0));
        tma2d(ring + slot_of(0) * SLOT_BYTES + 16384, tw, (mc >> 2) * 128 + 64, 0, misc + BAR_FULL + 8 * slot_of(0));
    };
    if (tid == 0) {
#pragma unroll
        for (int i = 0; i < NSLOT; i++) mbar_init(misc + BAR_FULL + 8 * i, 1);
#pragma unroll
        for (int i = 0; i < E0; i++) mbar_arrive(misc + BAR_FULL + 8 * i);
        asm volatile("fence.mbarrier_init.release.cluster;" ::: "memory");
        if (mc < 64) load_w0();
    }
    if (tid == 160) {
        asm volatile("st.shared.u32 [%0], %1;" ::"r"(misc + MISC_SMID), "r"(smid) : "memory");
        asm volatile("fence.release.sync_restrict::shared::cta.cluster;" ::: "memory");
    }
    if (tid == 32) {
        asm volatile("prefetch.tensormap [%0];" ::"l"(&tmC) : "memory");
#pragma unroll
        for (int i = 0; i < NSLOT; i++) mbar_init(misc + BAR_EMPTY + 8 * i, 16);
#pragma unroll
        for (int i = 0; i < E0; i++) mbar_arrive_cluster(misc + BAR_EMPTY + 8 * i, 16);
        asm volatile("fence.mbarrier_init.release.cluster;" ::: "memory");
    }
    if (tid == 64) {
#pragma unroll
        for (int i = 0; i < NST3; i++) { mbar_init(misc + BAR_FULL3 + 8 * i, 1); mbar_init(misc + BAR_EMPTY3 + 8 * i, 16); }
#pragma unroll
        for (int i = 0; i < 4; i++) mbar_init(misc + BAR_PROG + 8 * i, 1);
        mbar_init(misc + BAR_LN, 2);
        asm volatile("fence.mbarrier_init.release.cluster;" ::: "memory");
    }
    if (tid == 96) {
#pragma unroll
        for (int i = 0; i < 24; i++) mbar_init(misc + BAR_DEP + 8 * i, 1);
    }
    if (tid == 128) {
#pragma unroll
        for (int i = 0; i < 2 * NEV; i++) mbar_init(misc + BAR_EV + 8 * i, 4);
    }
    __syncthreads();
    asm volatile("barrier.cluster.arrive.relaxed.aligned;\nbarrier.cluster.wait.aligned;" ::: "memory");
    {
        uint32_t peer;
        asm volatile("{\n.reg .b32 r, a;\nmov.u32 r, %%cluster_ctarank;\nxor.b32 r, r, 1;\nmapa.shared::cluster.u32 a, %1, r;\n"
                     "ld.shared::cluster.u32 %0, [a];\n}\n" : "=r"(peer) : "r"(misc + MISC_SMID) : "memory");
        if ((__shfl_sync(0xffffffffu, peer, 0) ^ smid) != 1) {
            if (tid == 0) {
                const unsigned ep1 = *reinterpret_cast<volatile unsigned*>(&g_epoch) + 1;
                if ((smid & 1) == 0) atomicExch(g_roleq + 2 + (atomicAdd(g_roleq, 1u) & 127), (ep1 << 8) | (smid >> 1));
                if (rank == 0) {
                    unsigned* slot = g_roleq + 2 + (atomicAdd(g_roleq + 1, 1u) & 127);
                    unsigned v = 0;
                    for (int spin = 0; spin < 4000000 && ((v = atomicAdd(slot, 0u)) >> 8) != (ep1 & 0xffffffu); spin++) {}
                    asm volatile("st.shared::cluster.u32 [%0], %1;" ::"r"(mapa(misc + MISC_SMID + 4, 0)), "r"(v & 255) : "memory");
                    asm volatile("st.shared::cluster.u32 [%0], %1;" ::"r"(mapa(misc + MISC_SMID + 4, 1)), "r"(v & 255) : "memory");
                }
                if (mc < 64) {
                    mbar_wait(misc + BAR_FULL + 8 * slot_of(0), 0);
                    asm volatile("mbarrier.inval.shared::cta.b64 [%0];" ::"r"(misc + BAR_FULL + 8 * slot_of(0)) : "memory");
                    mbar_init(misc + BAR_FULL + 8 * slot_of(0), 1);
                    asm volatile("fence.mbarrier_init.release.cluster;" ::: "memory");
                }
            }
            __syncwarp();
            asm volatile("barrier.cluster.arrive.aligned;\nbarrier.cluster.wait.aligned;" ::: "memory");
            mc = role_of(__shfl_sync(0xffffffffu, lds32(misc + MISC_SMID + 4), 0));
            if (tid == 0 && mc < 64) load_w0();
            __syncwarp();
        }
    }
    const int cta = mc * 2 + rank;
    const bool aux = mc >= 64;
    const int team = mc >> 2, k = mc & 3;
    const int u3 = mc >> 3, s3 = k, kap = team & 1;
    const int partner = cta ^ 8;
    const int b0 = k, b1 = 7 - k;
    if (tid >= 128 && !aux) prefetch_w(1);
    if (tid == 256 && !aux) {
        const CUtensorMap* tw = rank ? &tmWv : &tmWk;
#pragma unroll
        for (int e = 1; e < NSLOT; e++) {
            const uint32_t fb = misc + BAR_FULL + 8 * slot_of(e), dst = ring + slot_of(e) * SLOT_BYTES;
            mbar_expect_tx(fb, SLOT_BYTES);
            if (e & 1) tma2d_mc(dst + rank * 16384, &tmC, (e >> 1) * 128 + rank * 64, (12 + k) * 128, fb);
            else { tma2d(dst, tw, team * 128, e * 64, fb); tma2d(dst + 16384, tw, team * 128 + 64, e * 64, fb); }
        }
    }
    const int wg = __shfl_sync(0xffffffffu, tid >> 7, 0);

    if (wg == 0 || aux) {
        asm volatile("setmaxnreg.dec.sync.aligned.u32 40;");
        const int warp = __shfl_sync(0xffffffffu, tid >> 5, 0), lane = tid & 31;
        if (warp == 0 && !aux) {
            const bool lead = elect_one();
            Cur c = cur_at(NSLOT);
            uint32_t dst, fb;
            auto acquire = [&]() {
                mbar_wait_sleep(misc + BAR_EMPTY + 8 * c.slot, c.ph ^ 1);
                fb = misc + BAR_FULL + 8 * c.slot; dst = ring + c.slot * SLOT_BYTES;
                if (lead) mbar_expect_tx(fb, SLOT_BYTES);
                c.adv();
            };
            auto load_w = [&](const CUtensorMap* tm, int col, int row) {
                acquire();
                if (lead) { tma2d(dst, tm, col, row, fb); tma2d(dst + 16384, tm, col + 64, row, fb); }
            };
            auto load_half = [&](const unsigned char* src) {
                acquire();
                if (lead) bulk_load_mc(dst + rank * 16384, src, 16384, fb);
            };
            auto dep_wait = [&](int d) { mbar_wait_sleep(misc + BAR_DEP + 8 * d, 0); fence_async_global(); };
            auto op_prefetch = [&](int i) {
                const int head = op_head(i, kap);
                l2_prefetch(reinterpret_cast<const unsigned char*>(P.wo) + head * 163840 + (u3 * 8 + s3 * 2 + rank) * 2560, 2560);
                if (i < 8) l2_prefetch(g_ctx + (size_t)(head * 32 + 4 * u3 + 2 * rank) * 16384 + s3 * 8192, 8192);
            };
            if (lead) l2_prefetch(reinterpret_cast<const unsigned char*>(P.c) + (size_t)cta * 12288, 12288);
            const CUtensorMap* tw = rank ? &tmWv : &tmWk;
            const unsigned char* Kh = g_K + (size_t)team * 32 * 16384 + rank * 16384;
            const unsigned char* Vh = g_V + (size_t)team * 32 * 16384 + rank * 16384;
#pragma unroll 1
            for (int v = 0; v < 2; v++) {
                const int h = team + 16 * v;
#pragma unroll 1
                for (int i = v ? 0 : 3; i < 16; i++) {
                    if (i < 4 && v) load_w(tw, h * 128, i * 128);
                    if (v && i == 3 && lead) mbar_arrive(misc + BAR_PROG + 8);
                    if (v && (i == 3 || i == 7)) dep_wait(D_WAR + (i > 3));
                    acquire();
                    if (lead) tma2d_mc(dst + rank * 16384, &tmC, (i & 3) * 128 + rank * 64, (kv_tile(i >> 2) + k) * 128, fb);
                    if (i == 8 && lead) {
                        tma2d_prefetch(&tmWq, h * 128 + rank * 64, k * 64); tma2d_prefetch(&tmWq, h * 128 + rank * 64, k * 64 + 256);
                        if (k < 2) tma2d_prefetch(&tmWq, h * 128 + rank * 64, k * 64 + 512);
                    }
                }
                int togo = v ? PF_START : 11;
#pragma unroll 1
                for (int r = 0; r < 2; r++) {
                    const int p = r ? b1 : b0, n = 2 * p + 1;
                    if (v == 0) dep_wait(D_LN + r);
                    const int g0 = r ? rank ^ 1 : 3 - rank, g1 = 3 - g0;
                    const unsigned char* x0 = g_xn + (2 * p + (g0 >> 1)) * 163840 + (g0 & 1) * 8192;
                    const unsigned char* x1 = g_xn + (2 * p + (g1 >> 1)) * 163840 + (g1 & 1) * 8192;
#pragma unroll 1
                    for (int kc = 0; kc < 10; kc++) {
                        acquire();
                        if (lead) {
                            tma2d_mc(dst + 16384 + rank * 8192, &tmWq, h * 128 + rank * 64, kc * 64, fb);
                            bulk_load(dst, x0 + kc * 16384, 8192, fb);
                            bulk_load(dst + 8192, x1 + kc * 16384, 8192, fb);
                        }
                    }
                    dep_wait(D_KV + 2 * v + r);
                    load_half(Kh + n * 32768);
#pragma unroll 1
                    for (int j = n - 1; j >= 0; j--) {
                        load_half(Kh + j * 32768); load_half(Vh + (j + 1) * 32768);
                        if (v == 0 && r && j == 7 && lead) mbar_arrive(misc + BAR_PROG);
                        --togo;
                        if (v == 0 && togo == 0 && lead) {
                            tma2d_prefetch(tw, h * 128 + 2048, k * 128); tma2d_prefetch(tw, h * 128 + 2112, k * 128);
                            l2_prefetch(reinterpret_cast<const unsigned char*>(P.c) + (size_t)cta * 16384, 16384);
                        }
                        if (v && togo <= 0 && togo > -OP_PF && lead) op_prefetch(-togo);
                    }
                    load_half(Vh);
                }
            }
            mbar_wait_sleep(misc + BAR_EMPTY + 8 * c.slot, c.ph ^ 1); c.adv();
            int st = 0; uint32_t ph3 = 0;
#pragma unroll 1
            for (int i = 0; i < 32; i++) {
                const int head = op_head(i >> 1, kap);
                if ((i & 1) == 0) dep_wait(D_CTX + (i >> 1));
                if (i < NST3) { mbar_wait_sleep(misc + BAR_EMPTY + 8 * c.slot, c.ph ^ 1); c.adv(); }
                else mbar_wait_sleep(misc + BAR_EMPTY3 + 8 * st, ph3 ^ 1);
                fb = misc + BAR_FULL3 + 8 * st; dst = ring + st * ST3_BYTES;
                if (i == LATE_AT && lead) mbar_arrive(misc + BAR_PROG + 16);
                if (lead) {
                    mbar_expect_tx(fb, ST3_BYTES);
                    const unsigned char* src = g_ctx + (size_t)(head * 32 + 4 * u3 + 2 * rank) * 16384 + (i & 1) * 8192;
                    bulk_load(dst, src, 8192, fb);
                    bulk_load(dst + 8192, src + 16384, 8192, fb);
                    tma3d_mc(dst + 16384 + rank * 10240, &tmWo, 0, head * 128 + (i & 1) * 64 + rank * 32, 5 * s3, fb);
                    if ((i & 1) && (i >> 1) + OP_PF < 16) op_prefetch((i >> 1) + OP_PF);
                }
                if (++st == NST3) { st = 0; ph3 ^= 1; }
            }
        } else {
        if (warp >= 1 && warp <= 3 && lane < 27 && (warp - 1) * 27 + lane < 80) {
            const int ch = (warp - 1) * 27 + lane;
            uint4 u = __ldg(reinterpret_cast<const uint4*>(P.wr) + ch);
            asm volatile("st.shared.v4.b32 [%0], {%1,%2,%3,%4};" ::"r"(misc + MISC_WR + 16 * ch), "r"(u.x), "r"(u.y), "r"(u.z), "r"(u.w) : "memory");
        }
        bar_sync(3, aux ? 384 : 96);
        const int nln = aux ? (warp < 4 ? 6 : 5) : (warp == 3 || k == 0) ? 1 : 3;
        auto ln_row = [&](int t) {
            const int id = warp + 12 * t, a = cta - 128;
            return aux ? (id < 32 ? a * 256 + 192 : 960 + a * 64) + 2 * id
                       : t ? 2430 - 384 * t - 4 * (team * 6 + (k - 1) * 2 + rank) - 2 * (warp - 1) : (cta >> 5) * 256 + (cta & 31) * 6 + (warp - 1) * 2;
        };
        int done = 0;
#pragma unroll 1
        for (int t = 0; t < nln; t++) {
            const int lrow = ln_row(t), lnext = t + 1 < nln ? ln_row(t + 1) : -1;
            if (lnext >= 0) {
                const int ll = fresh_lane();
#pragma unroll
                for (int i = 0; i < 3; i++)
                    if (i * 32 + ll < 80) asm volatile("prefetch.global.L2 [%0];" ::"l"(P.x + (size_t)lnext * DM + (i * 32 + ll) * 16));
            }
            ln_rows(P.x, lrow, misc + MISC_WR);
            __syncwarp();
            done++;
            if ((lnext >> 8) != (lrow >> 8)) {
                if (fresh_lane() == 0) {
                    if (aux || t) asm volatile("red.release.gpu.global.add.u32 [%0], %1;" ::"l"(flag_ptr(FL_LN + (lrow >> 8))), "r"(done) : "memory");
                    else if (warp < 3) mbar_arrive(misc + BAR_LN);
                }
                done = 0;
            }
        }
        if (aux) {
            __syncwarp();
            asm volatile("setmaxnreg.inc.sync.aligned.u32 128;");
            aux_cta(&tmG, &tmU, &tmD, smem_raw, cta - 128);
        } else
        if (warp == 3) {
            const unsigned ep1 = *reinterpret_cast<volatile unsigned*>(&g_epoch) + 1;
            if (lane == 0) {
                asm volatile("st.shared.u32 [%0], %1;" ::"r"(misc + MISC_EPOCH), "r"(ep1) : "memory");
                mbar_wait(misc + BAR_LN, 0);
                flag_signal(flag_ptr(FL_LN + (cta >> 5)));
                flag_wait(flag_ptr(FL_LN + b0), ep1 * 64u);
                mbar_arrive(misc + BAR_DEP + 8 * D_LN);
#pragma unroll 1
                for (int i = 0; i < 4; i++) {
                    mbar_wait(misc + BAR_EV + 8 * (NEV + EV_KV + i), 0);
                    if (i < 2) {
                        mbar_wait(misc + BAR_EV + 8 * (EV_KV + i), 0);
                        asm volatile("red.release.gpu.global.add.u32 [%0], 2;" ::"l"(flag_ptr(FL_KV + team * 8 + i)) : "memory");
                    }
                    flag_wait(flag_ptr(FL_KV + team * 8 + i), ep1 * 16u);
                    mbar_arrive(misc + BAR_DEP + 8 * (D_KV + i));
                    if (i == (k >> 1)) {
                        flag_wait(flag_ptr(FL_LN + b1), ep1 * 128u);
                        mbar_arrive(misc + BAR_DEP + 8 * (D_LN + 1));
                    }
                    if (i == 1) {
#pragma unroll 1
                        for (int j = 0; j < 2; j++) {
                            mbar_wait(misc + BAR_PROG + 8 * j, 0);
                            asm volatile("red.relaxed.gpu.global.add.u32 [%0], 1;" ::"l"(flag_ptr(FL_WAR + 2 * team + j)) : "memory");
                            flag_wait(flag_ptr(FL_WAR + 2 * team + j), ep1 * 8u);
                            mbar_arrive(misc + BAR_DEP + 8 * (D_WAR + j));
                        }
                    }
                }
                flag_wait(flag_ptr(FL_LN + u3), ep1 * (u3 < 4 ? 64u : 128u));
            }
            __syncwarp();
            const unsigned* cf = flag_ptr(FL_CTX + op_head(lane & 15, kap) * 8 + u3);
#pragma unroll 1
            for (int half = 0; half < 2; half++) {
                if (half) mbar_wait(misc + BAR_EV + 8 * (EV_CTX + 3), 0);
                bool done = (lane >> 3) != half;
                for (int spin = 0; spin < 4000000; spin++) {
                    if (!done) {
                        unsigned v;
                        asm volatile("ld.acquire.gpu.global.u32 %0, [%1];" : "=r"(v) : "l"(cf) : "memory");
                        if ((int)(v - ep1 * 4u) >= 0) { mbar_arrive(misc + BAR_DEP + 8 * (D_CTX + lane)); done = true; }
                    }
                    if (__all_sync(0xffffffffu, done)) break;
                    __nanosleep(64);
                }
            }
            if (lane == 0) {
                flag_wait(flag_ptr(FL_MOE_DONE), ep1);
                int4 s0 = __ldcg(reinterpret_cast<const int4*>(g_sel)), s1 = __ldcg(reinterpret_cast<const int4*>(g_sel) + 1);
                asm volatile("st.shared.v4.u32 [%0], {%1,%2,%3,%4};" ::"r"(misc + MISC_SEL), "r"(s0.x), "r"(s0.y), "r"(s0.z), "r"(s0.w) : "memory");
                asm volatile("st.shared.v4.u32 [%0], {%1,%2,%3,%4};" ::"r"(misc + MISC_SEL + 16), "r"(s1.x), "r"(s1.y), "r"(s1.z), "r"(s1.w) : "memory");
                mbar_arrive(misc + BAR_SEL);
            }
        } else {
            const int w = warp - 1;
            if (lane == 0) {
                const uint32_t eb = misc + BAR_EV + w * 8 * NEV;
#pragma unroll 1
                for (int i = 0; i < 6; i++) {
                    const bool kv = (i >> 1) == 1;
                    const int ci = i < 2 ? i : i - 2;
                    mbar_wait(eb + 8 * (kv ? EV_KV + i : EV_CTX + ci), 0);
                    if (i == 1) {
                        asm volatile("cp.async.bulk.global.shared::cta.bulk_group.L2::cache_hint [%0], [%1], 16384, %2;"
                                     ::"l"(g_ctx + (size_t)(team * 32 + 4 * b1 + (w ? 3 - (rank ^ 1) : rank ^ 1)) * 16384),
                                       "r"(ring + slot_of(78) * SLOT_BYTES + w * 16384), "l"(policy_stream()) : "memory");
                        asm volatile("cp.async.bulk.commit_group;" ::: "memory");
                        asm volatile("cp.async.bulk.wait_group.read 0;" ::: "memory");
                        mbar_arrive_cluster(mapa(misc + BAR_EMPTY + 8 * slot_of(78), 0), 4);
                        mbar_arrive_cluster(mapa(misc + BAR_EMPTY + 8 * slot_of(78), 1), 4);
                        asm volatile("cp.async.bulk.wait_group 0;" ::: "memory");
                        fence_async_global();
                    }
                    flag_signal(flag_ptr(kv ? FL_KV + team * 8 + i : FL_CTX + (team + 16 * (ci >> 1)) * 8 + ((ci & 1) ? b1 : b0)));
                }
            }
            __syncwarp();
            mbar_wait(misc + BAR_PROG + 16, 0);
            const int row = (2 * u3 + rank) * 128 + 64 * w + perm32(16 * (lane >> 3) + 8 * kap + (lane & 7));
#pragma unroll
            for (int i = 0; i < 10; i++) asm volatile("prefetch.global.L2 [%0];" ::"l"(P.x + (size_t)row * DM + 160 * s3 + 16 * i));
            asm volatile("prefetch.global.L2 [%0];" ::"l"(g_stats + row));
            mbar_wait(misc + BAR_EV + w * 8 * NEV + 8 * EV_END, 0);
        }
        }
    } else {
        asm volatile("setmaxnreg.inc.sync.aligned.u32 232;");
        Ctx c;
        c.ring = ring; c.misc = misc; c.w = wg - 1; c.warp = __shfl_sync(0xffffffffu, (tid >> 5) & 3, 0); c.lane = tid & 31;
        c.rel = mapa(misc, tid & 1);
        const int w = c.w;
        if (w == 1) bar_arrive(1, 256);
        prefetch_w(2); prefetch_w(3);
        Cur cur = cur_at(0);
        float o[64], inv[2];
        unsigned char* out[2];
        uint32_t wf[128];
        Cur cw = cur;
        auto load_wchunk = [&](auto CH) {
            constexpr int ch = decltype(CH)::value;
            mbar_wait_hot(misc + BAR_FULL + 8 * cw.slot, cw.ph);
            const uint32_t z = load_afrag<8, 32 * ch>(wf, ring + cw.slot * SLOT_BYTES + w * 16384, c);
            release(c, BAR_EMPTY + 8 * cw.slot + z, 1);
            cw.adv(); cw.adv();
        };
#pragma unroll
        for (int i = 32; i < 64; i++) wf[i] = 0u;
        load_wchunk(IC<0>{});
#pragma unroll 1
        for (int v = 0; v < 2; v++) {
        {
            float (&acc)[64] = o;
#pragma unroll
            for (int i = 64; i < 128; i++) wf[i] = 0u;
            cur.adv();
            inv[0] = inv[1] = rank ? V_SCALE : SM_SCALE / X_SCALE;
#pragma unroll 1
            for (int t = 0; t < 4; t++) {
                uint32_t last = 0;
                token_wait(w);
                undef_regs(acc);
                auto chunk = [&](auto CH) {
                    constexpr int ch = decltype(CH)::value;
                    mbar_wait_hot(misc + BAR_FULL + 8 * cur.slot, cur.ph);
                    uint64_t d = mkdesc(ring + cur.slot * SLOT_BYTES, 16, 1024, 1);
                    wg_fence();
#pragma unroll
                    for (int ks = 0; ks < 8; ks++)
                        wgmma_rs_n128_ta0_tb0(acc, wf[32 * ch + 4 * ks], wf[32 * ch + 4 * ks + 1], wf[32 * ch + 4 * ks + 2], wf[32 * ch + 4 * ks + 3],
                                              d + (ks >> 2) * 1024 + (ks & 3) * 2, (ch | ks) != 0);
                    wg_commit();
                    if (ch == 3 || (ch < 2 && t == 0)) token_pass(w);
                    if constexpr (ch == 0) {
                        if (t == 0) {
                            if (v) {
                                release(c, BAR_EMPTY + 8 * slot_of(76), 1);
                                asm volatile("fence.proxy.async.shared::cta;" ::: "memory");
                                signal_event(c, EV_CTX + 1);
                                load_wchunk(IC<2>{});
                            } else load_wchunk(IC<1>{});
                        }
                    }
                    if constexpr (ch == 1) { if (t == 0 && !v) load_wchunk(IC<2>{}); }
                    if constexpr (ch == 2) { if (t == 0 && !(w | v)) load_wchunk(IC<3>{}); }
                    if (ch > 0) { wg_wait<1>(); release(c, BAR_EMPTY + 8 * last, 1); }
                    last = cur.slot;
                    cur.adv();
                    if (ch < 3 && t == 0) cur.adv();
                    if constexpr (ch == 1) { if (t == 0 && (w | v)) load_wchunk(IC<3>{}); }
                    if (ch < 2 && t == 0) token_wait(w);
                };
                chunk(IC<0>{}); chunk(IC<1>{}); chunk(IC<2>{}); chunk(IC<3>{});
                wg_wait<0>();
                release(c, BAR_EMPTY + 8 * last, 1);
                fence_regs(acc);
                tile_out(out, (rank ? g_V : g_K) + (size_t)(team * 32 + 2 * (kv_tile(t) + k)) * 16384, 64 * w, rank, c);
                if (t == 3 && w) break;
#pragma unroll
                for (int i = 0; i < 4; i++) store_pair(acc, i, out, 8192, inv);
                if (t >= 2) signal_event(c, EV_KV + 2 * v + t - 2);
            }
        }
        {
            uint32_t q[32], p[32];
            float m[2], l[2];
#pragma unroll
            for (int i = 0; i < 32; i++) p[i] = 0u;
            l[0] = l[1] = 1.f;
            int pv_acc = 1, pv_mode = 2;
#pragma unroll 1
            for (int r = 0; r < 2; r++) {
                const int heavy = 1 ^ r ^ w;
                const int half = 1 ^ heavy ^ rank ^ r;
                int left = 2 * (r ? b1 : b0) + 1 + heavy;
                Cur ck, cv = cur;
                {
                    float s[64];
                    if (r) cur.adv();
                    mbar_wait_hot(misc + BAR_FULL + 8 * cv.slot, cv.ph);
                    token_wait(w);
                    issue_pv(o, p, ring + cv.slot * SLOT_BYTES, pv_acc, pv_mode);
                    undef_regs(s);
                    uint32_t prev;
                    auto qchunk = [&](int acc) {
                        mbar_wait_hot(misc + BAR_FULL + 8 * cur.slot, cur.ph);
                        const uint64_t da = mkdesc(ring + cur.slot * SLOT_BYTES + w * 8192, 16, 1024, 1);
                        const uint64_t db = mkdesc(ring + cur.slot * SLOT_BYTES + 16384, 8192, 1024, 1);
                        wg_fence();
#pragma unroll
                        for (int ks = 0; ks < 4; ks++) wgmma_ss_n128_ta0_tb1(s, da + 2 * ks, db + 128 * ks, ks ? 1 : acc);
                        wg_commit();
                    };
                    qchunk(0);
                    prev = cur.slot; cur.adv();
                    token_pass(w);
                    if (r) {
                        row_inv(l, inv);
                        tile_out(out, g_ctx + (size_t)((team + 16 * v) * 32 + 4 * b0 + (w ? rank : 3 - rank)) * 16384, 0, 0, c);
                    }
                    const int epi = r | w, hs = r ? 4096 : 8192;
                    const int hold = heavy ? -10 : half ? 6 : 8;
#pragma unroll
                    for (int kc = 1; kc < 10; kc++) {
                        if (kc >= 6 && (kc == hold || kc == hold + 2)) token_wait(w);
                        qchunk(1);
                        if (kc > 6 && kc == hold + 1) token_pass(w);
                        if (kc == 9 && heavy) { token_wait(w); token_pass(w); }
                        wg_wait<1>();
                        release(c, BAR_EMPTY + 8 * prev, 1);
                        prev = cur.slot; cur.adv();
                        if (kc == 1) { fence_regs(o); if (r) release(c, BAR_EMPTY + 8 * cv.slot, 1); }
                        if (kc <= 4 && epi) {
                            store_pair(o, kc - 1, out, hs, inv, r > v);
                            if (kc == 4) signal_event(c, r ? EV_CTX + 2 * v : EV_KV + 2 * v + 1);
                        }
                    }
                    if (!heavy) cur.adv();
                    ck = cur;
                    cur.adv();
                    if (!heavy) cur.adv();
                    wg_wait<0>();
                    release(c, BAR_EMPTY + 8 * prev, 1);
                    fence_regs(s);
#pragma unroll
                    for (int i = 0; i < 32; i++) q[i] = pack_bf16(s[2 * i], s[2 * i + 1]);
                }
                int first = 1, gen = 0;
                uint32_t pv_cnt = 0;
                l[0] = l[1] = m[0] = m[1] = 0.f;
                mbar_wait_hot(misc + BAR_FULL + 8 * ck.slot, ck.ph);
                auto diagonal = [&](auto NJC) {
                    constexpr int NJ = decltype(NJC)::value;
                    if (NJ == 16 || heavy) token_wait(w);
                    float sd[4 * NJ];
                    undef_regs(sd);
                    if constexpr (NJ == 8) issue_qk_half(sd, q, ring + ck.slot * SLOT_BYTES); else issue_qk(sd, q, ring + ck.slot * SLOT_BYTES);
                    token_pass(w);
                    wg_wait<0>();
                    fence_regs(sd);
                    if constexpr (NJ == 8) mask_diag(sd, c);
                    else {
                        const int lm = mask_lim(c);
#pragma unroll
                        for (int x = 0; x < 32; x++)
                            if (32 * (x >> 4) + 2 * ((x >> 2) & 3) + (x & 1) - (x & 2) > lm) sd[32 + x] = -INFINITY;
                    }
                    float l0 = 0.f, l1 = 0.f;
#pragma unroll
                    for (int j = 0; j < NJ; j++) {
#pragma unroll
                        for (int e = 0; e < 4; e++) ex2v(sd[4 * j + e]);
                        l0 += sd[4 * j] + sd[4 * j + 1]; l1 += sd[4 * j + 2] + sd[4 * j + 3];
                    }
#pragma unroll
                    for (int i = 0; i < 2 * NJ; i++) p[i] = pack_bf16(sd[2 * i], sd[2 * i + 1]);
                    const int lim = NJ == 8 ? mask_lim(c) : 0;
                    const bool bad = __any_sync(0xffffffffu, !(l0 <= SAFE_SUM && l1 <= SAFE_SUM && (l0 >= 1.0f / SAFE_SUM || lim < 0) &&
                                                               (l1 >= 1.0f / SAFE_SUM || lim < -2)));
                    if (!bad) { l[0] = l0; l[1] = l1; }
                    return bad;
                };
#pragma unroll 1
                while (true) {
                    float s[64];
                    if (first) {
                        --left;
                        if (half ? diagonal(IC<8>{}) : diagonal(IC<16>{})) goto redo;
                        if (left == 0) goto tail;
                        release(c, BAR_EMPTY + 8 * ck.slot, 1 + heavy);
                        pv_acc = 0; pv_mode = half; pv_cnt = 1 + heavy; first = 0;
                        ck = cur; cur.adv(); cv = cur; cur.adv();
                        mbar_wait_hot(misc + BAR_FULL + 8 * ck.slot, ck.ph);
                    }
#pragma unroll 1
                    while (true) {
                        token_wait(w);
                        undef_regs(s);
                        issue_qk(s, q, ring + ck.slot * SLOT_BYTES);
                        Cur nck = cur, ncv = cur, ncur;
                        ncv.adv(); ncur = ncv; ncur.adv();
                        --left;
                        mbar_wait_hot(misc + BAR_FULL + 8 * cv.slot, cv.ph);
                        issue_pv(o, p, ring + cv.slot * SLOT_BYTES, pv_acc, pv_mode & 1);
                        token_pass(w);
                        wg_wait<1>();
                        fence_regs(s);
                        constexpr int JB = 11;
                        float l0 = l[0], l1 = l[1];
                        if (!gen) {
#pragma unroll
                            for (int j = 0; j < JB; j++) {
#pragma unroll
                                for (int e = 0; e < 4; e++) ex2v(s[4 * j + e]);
                                if (j < JB - 1) { l0 += s[4 * j] + s[4 * j + 1]; l1 += s[4 * j + 2] + s[4 * j + 3]; }
                            }
                        }
                        wg_wait<0>();
                        fence_regs(o);
                        if (gen) goto general;
#pragma unroll
                        for (int j = JB - 1; j < 16; j++) {
                            if (j >= JB) {
#pragma unroll
                                for (int e = 0; e < 4; e++) ex2v(s[4 * j + e]);
                            }
                            l0 += s[4 * j] + s[4 * j + 1]; l1 += s[4 * j + 2] + s[4 * j + 3];
                        }
#pragma unroll
                        for (int i = 0; i < 32; i++) p[i] = pack_bf16(s[2 * i], s[2 * i + 1]);
                        if (__any_sync(0xffffffffu, !(l0 <= SAFE_SUM && l1 <= SAFE_SUM))) goto redo;
                        l[0] = l0; l[1] = l1;
                        if (left == 0) goto tail;
                        release(c, BAR_EMPTY + 8 * ck.slot, 1);
                        release(c, BAR_EMPTY + 8 * cv.slot, pv_cnt);
                        pv_acc = 1; pv_mode = 0; pv_cnt = 1;
                        ck = nck; cv = ncv; cur = ncur;
                        mbar_wait_hot(misc + BAR_FULL + 8 * ck.slot, ck.ph);
                    }
                redo:
                    recompute_scores(s, q, ring + ck.slot * SLOT_BYTES, c);
                    if (first) { mask_any(s, half ^ 1, c); m[0] = m[1] = -INFINITY; }
                    gen = 1;
                general:
                    {
                        float mx[2], alpha[2];
                        row_max<16>(s, mx);
#pragma unroll
                        for (int i = 0; i < 2; i++) {
                            mx[i] = fmaxf(mx[i], m[i]);
                            alpha[i] = ex2(m[i] - mx[i]);
                            m[i] = mx[i];
                            l[i] *= alpha[i];
                        }
                        exp_sum<16, true>(s, m, l[0], l[1]);
#pragma unroll
                        for (int i = 0; i < 64; i++) o[i] *= alpha[(i >> 1) & 1];
#pragma unroll
                        for (int i = 0; i < 32; i++) p[i] = pack_bf16(s[2 * i], s[2 * i + 1]);
                    }
                tail:
                    release(c, BAR_EMPTY + 8 * ck.slot, 1 + (first & heavy));
                    if (pv_cnt) release(c, BAR_EMPTY + 8 * cv.slot, pv_cnt);
                    pv_acc = first ^ 1; pv_mode = first & half; pv_cnt = 1 + (first & heavy); first = 0;
                    if (left == 0) break;
                    ck = cur; cur.adv(); cv = cur; cur.adv();
                    mbar_wait_hot(misc + BAR_FULL + 8 * ck.slot, ck.ph);
                }
            }
            mbar_wait_hot(misc + BAR_FULL + 8 * cur.slot, cur.ph);
            token_wait(w);
            issue_pv(o, p, ring + cur.slot * SLOT_BYTES, 1, 0);
            if (w == 0 || v == 0) token_pass(w);
            const uint32_t vslot = cur.slot;
            cur.adv();
            row_inv(l, inv);
            if (v) {
                wg_wait<0>();
                release(c, BAR_EMPTY + 8 * vslot, 1);
                fence_regs(o);
                tile_out(out, g_ctx + (size_t)((team + 16) * 32 + 4 * b1 + (w ? 3 - (rank ^ 1) : rank ^ 1)) * 16384, 0, 0, c);
#pragma unroll
                for (int i = 0; i < 64; i++) wf[i] = 0u;
                continue;
            }
            cw = cur_at(80);
            mbar_wait_hot(misc + BAR_FULL + 8 * slot_of(76), cur_at(76).ph);
            mbar_wait_hot(misc + BAR_FULL + 8 * slot_of(78), cur_at(78).ph);
            load_afrag<8, 32>(wf, ring + slot_of(78) * SLOT_BYTES + w * 16384, c);
            load_afrag<8, 0>(wf, ring + slot_of(76) * SLOT_BYTES + w * 16384, c);
            asm volatile("{\n.reg .pred p;\nsetp.eq.u32 p, %0, 0;\n@p bar.sync 4, 128;\n@!p bar.sync 5, 128;\n}\n" ::"r"(w) : "memory");
            wg_wait<0>();
            release(c, BAR_EMPTY + 8 * vslot, 1);
            fence_regs(o);
            {
                const uint32_t base = ring + slot_of(78) * SLOT_BYTES + w * 16384 + (16 * c.warp + (c.lane >> 2)) * 64 + (((c.lane ^ (c.lane >> 3)) & 3) << 4);
#pragma unroll
                for (int i = 0; i < 2; i++)
#pragma unroll
                    for (int qq = 0; qq < 4; qq++)
                        asm volatile("st.shared.v4.b32 [%0], {%1,%2,%3,%4};" ::"r"(base + qq * 4096 + i * 512),
                                     "r"(pack_bf16(o[16 * qq + 2 * i] * inv[i], o[16 * qq + 2 * i + 1] * inv[i])),
                                     "r"(pack_bf16(o[16 * qq + 4 + 2 * i] * inv[i], o[16 * qq + 4 + 2 * i + 1] * inv[i])),
                                     "r"(pack_bf16(o[16 * qq + 8 + 2 * i] * inv[i], o[16 * qq + 8 + 2 * i + 1] * inv[i])),
                                     "r"(pack_bf16(o[16 * qq + 12 + 2 * i] * inv[i], o[16 * qq + 12 + 2 * i + 1] * inv[i])) : "memory");
            }
        }
        }
        {
            float acc[80];
            undef_regs(acc);
            int st = 0, prev = 0; uint32_t ph3 = 0;
            auto op_stage = [&](int i) {
                mbar_wait_hot(misc + BAR_FULL3 + 8 * st, ph3);
                uint32_t base = ring + st * ST3_BYTES;
                uint64_t da = mkdesc(base + w * 8192, 16, 512, 2);
                uint64_t db = mkdesc(base + 16384, 2048, 512, 2);
                wg_fence();
#pragma unroll
                for (int k = 0; k < 4; k++) wgmma_ss_n160_ta0_tb1(acc, da + (k >> 1) * 256 + 2 * (k & 1), db + (k >> 1) * 640 + (k & 1) * 64, k ? 1 : i);
                wg_commit();
                if (i > 0 && i <= 32 - NST3) { wg_wait<1>(); release(c, BAR_EMPTY3 + 8 * prev, 1); }
                prev = st;
                if (++st == NST3) { st = 0; ph3 ^= 1; }
            };
#pragma unroll
            for (int i = 0; i < 4; i++) { op_stage(i); store_pair(o, i, out, 4096, inv); }
            signal_event(c, EV_CTX + 3);
            const int split = w ? 32 - OP_HOLD : RES_AT;
#pragma unroll 1
            for (int i = 4; i < split; i++) op_stage(i);
            const uint32_t tag = lds32(misc + MISC_EPOCH) & 1;
            const int g = c.lane >> 2, t = c.lane & 3;
            const int row = (2 * u3 + rank) * 128 + 64 * w + perm32(16 * c.warp + 8 * kap + g);
            const int col = 160 * s3 + 8 * t;
            const int t256 = tid - 128;
            uint4* sendp = g_part + (size_t)cta * 2560 + t256;
            if (c.lane >= 30) stg128(sendp + 9 * 256, tag ^ 1, tag ^ 1, tag ^ 1, tag ^ 1);
            uint4 xv[5], bv[5];
#pragma unroll
            for (int i = 0; i < 5; i++) xv[i] = ldg128(P.x + (size_t)row * DM + col + 32 * i);
            uint2 stat;
            asm volatile("ld.global.cg.v2.b32 {%0,%1}, [%2];" : "=r"(stat.x), "=r"(stat.y) : "l"(g_stats + row) : "memory");
#pragma unroll
            for (int i = 0; i < 5; i++) {
                uint32_t xx[4] = {xv[i].x, xv[i].y, xv[i].z, xv[i].w};
#pragma unroll
                for (int e = 0; e < 4; e++) {
                    asm("sub.rn.bf16x2 %0, %0, %1;" : "+r"(xx[e]) : "r"(stat.x));
                    xx[e] = pack_bf16(bf_lo(xx[e]) * __uint_as_float(stat.y), bf_hi(xx[e]) * __uint_as_float(stat.y));
                }
                bv[i] = make_uint4(xx[0], xx[1], xx[2], xx[3]);
            }
#pragma unroll
            for (int i = 0; i < 5; i++) asm volatile("" : "+r"(bv[i].x), "+r"(bv[i].y), "+r"(bv[i].z), "+r"(bv[i].w));
            if (w) bar_sync(4, 256);
#pragma unroll 1
            for (int i = split; i < 32; i++) op_stage(i);
            if (!w) bar_arrive(4, 256);
            wg_wait<0>();
            fence_regs(acc);
            float keep[40];
#pragma unroll
            for (int j = 0; j < 10; j++) {
                uint32_t v0 = __float_as_uint(kap ? acc[8 * j + 0] : acc[8 * j + 2]), v1 = __float_as_uint(kap ? acc[8 * j + 1] : acc[8 * j + 3]);
                uint32_t v2 = __float_as_uint(kap ? acc[8 * j + 4] : acc[8 * j + 6]), v3 = __float_as_uint(kap ? acc[8 * j + 5] : acc[8 * j + 7]);
                asm volatile("st.relaxed.gpu.global.v4.b32 [%0], {%1,%2,%3,%4};" ::"l"(sendp + j * 256),
                             "r"((v0 & ~1u) | tag), "r"((v1 & ~1u) | tag), "r"((v2 & ~1u) | tag), "r"((v3 & ~1u) | tag) : "memory");
                keep[4 * j + 0] = kap ? acc[8 * j + 2] : acc[8 * j + 0]; keep[4 * j + 1] = kap ? acc[8 * j + 3] : acc[8 * j + 1];
                keep[4 * j + 2] = kap ? acc[8 * j + 6] : acc[8 * j + 4]; keep[4 * j + 3] = kap ? acc[8 * j + 7] : acc[8 * j + 5];
            }
            signal_event(c, EV_END);
            mbar_wait(misc + BAR_SEL, 0);
            int sel = -1;
#pragma unroll
            for (int i = 0; i < TOPC; i++) if ((int)lds32(misc + MISC_SEL + 4 * i) == row) sel = i;
            if (sel >= 0) {
#pragma unroll
                for (int i = 0; i < 5; i++) bv[i] = ldg128(g_brow + sel * DM + col + 32 * i);
            }
            const uint4* recvp = g_part + (size_t)partner * 2560 + t256;
            uint4 rv[10];
            int spins = 0;
            while (true) {
                uint32_t v;
                asm volatile("ld.relaxed.gpu.global.b32 %0, [%1];" : "=r"(v) : "l"(recvp + 9 * 256 + (31 - c.lane)) : "memory");
                if (__all_sync(0xffffffffu, (v & 1u) == tag) || ++spins > 2000000) break;
            }
            while (true) {
                uint32_t bad = 0u;
#pragma unroll
                for (int j = 0; j < 10; j++) {
                    asm volatile("ld.relaxed.gpu.global.v4.b32 {%0,%1,%2,%3}, [%4];"
                                 : "=r"(rv[j].x), "=r"(rv[j].y), "=r"(rv[j].z), "=r"(rv[j].w) : "l"(recvp + j * 256) : "memory");
                }
#pragma unroll
                for (int j = 0; j < 10; j++) {
                    rv[j].x ^= tag; rv[j].y ^= tag; rv[j].z ^= tag; rv[j].w ^= tag;
                    bad |= rv[j].x | rv[j].y | rv[j].z | rv[j].w;
                }
                if (__all_sync(0xffffffffu, (bad & 1u) == 0) || ++spins > 2000000) break;
            }
            uint32_t pk[20];
#pragma unroll
            for (int j = 0; j < 10; j++) {
                pk[2 * j] = pack_bf16(keep[4 * j] + __uint_as_float(rv[j].x), keep[4 * j + 1] + __uint_as_float(rv[j].y));
                pk[2 * j + 1] = pack_bf16(keep[4 * j + 2] + __uint_as_float(rv[j].z), keep[4 * j + 3] + __uint_as_float(rv[j].w));
            }
#pragma unroll
            for (int i = 0; i < 5; i++) {
                uint32_t a0 = pk[4 * i], a1 = pk[4 * i + 1], a2 = pk[4 * i + 2], a3 = pk[4 * i + 3];
                uint32_t x0 = (t & 1) ? a0 : a1, x1 = (t & 1) ? a2 : a3;
                x0 = __shfl_xor_sync(0xffffffffu, x0, 1); x1 = __shfl_xor_sync(0xffffffffu, x1, 1);
                if (t & 1) { a0 = x0; a2 = x1; } else { a1 = x0; a3 = x1; }
                x0 = (t & 2) ? a0 : a2; x1 = (t & 2) ? a1 : a3;
                x0 = __shfl_xor_sync(0xffffffffu, x0, 2); x1 = __shfl_xor_sync(0xffffffffu, x1, 2);
                if (t & 2) { a0 = x0; a1 = x1; } else { a2 = x0; a3 = x1; }
                uint32_t av[4] = {a0, a1, a2, a3};
                uint32_t xx[4] = {xv[i].x, xv[i].y, xv[i].z, xv[i].w}, bb[4] = {bv[i].x, bv[i].y, bv[i].z, bv[i].w};
                uint32_t ov[4];
#pragma unroll
                for (int e = 0; e < 4; e++) {
                    asm("add.rn.bf16x2 %0, %1, %2;" : "=r"(ov[e]) : "r"(xx[e]), "r"(av[e]));
                    asm("add.rn.bf16x2 %0, %0, %1;" : "+r"(ov[e]) : "r"(bb[e]));
                }
                stg128(P.out + (size_t)row * DM + col + 32 * i, ov[0], ov[1], ov[2], ov[3]);
            }
        }
    }
}

typedef CUresult (*EncodeFn)(CUtensorMap*, CUtensorMapDataType, cuuint32_t, void*, const cuuint64_t*, const cuuint64_t*, const cuuint32_t*,
                             const cuuint32_t*, CUtensorMapInterleave, CUtensorMapSwizzle, CUtensorMapL2promotion, CUtensorMapFloatOOBfill);

void make_map2d(EncodeFn enc, CUtensorMap* tm, const void* p, uint64_t cols, uint64_t rows, uint32_t box_rows = 128) {
    cuuint64_t gd[2] = {cols, rows}, gs[1] = {cols * 2};
    cuuint32_t box[2] = {64, box_rows}, es[2] = {1, 1};
    enc(tm, CU_TENSOR_MAP_DATA_TYPE_BFLOAT16, 2, const_cast<void*>(p), gd, gs, box, es, CU_TENSOR_MAP_INTERLEAVE_NONE,
        CU_TENSOR_MAP_SWIZZLE_128B, CU_TENSOR_MAP_L2_PROMOTION_L2_128B, CU_TENSOR_MAP_FLOAT_OOB_FILL_NONE);
}

void make_map3d(EncodeFn enc, CUtensorMap* tm, const void* p, uint64_t cols, uint64_t rows, uint32_t bw, uint32_t nb) {
    cuuint64_t gd[3] = {bw, rows, cols / bw}, gs[2] = {cols * 2, bw * 2};
    cuuint32_t box[3] = {bw, 32, nb}, es[3] = {1, 1, 1};
    enc(tm, CU_TENSOR_MAP_DATA_TYPE_BFLOAT16, 3, const_cast<void*>(p), gd, gs, box, es, CU_TENSOR_MAP_INTERLEAVE_NONE,
        bw == 64 ? CU_TENSOR_MAP_SWIZZLE_128B : CU_TENSOR_MAP_SWIZZLE_64B, CU_TENSOR_MAP_L2_PROMOTION_L2_128B, CU_TENSOR_MAP_FLOAT_OOB_FILL_NONE);
}

}

extern "C" void kernel_launch(void* const* d_in, const int* in_sizes, int n_in, void* d_out, int out_size) {
    (void)in_sizes; (void)n_in; (void)out_size;
    static EncodeFn enc = nullptr;
    if (!enc) {
        void* fn = nullptr;
        cudaDriverEntryPointQueryResult qr;
        cudaGetDriverEntryPoint("cuTensorMapEncodeTiled", &fn, cudaEnableDefault, &qr);
        enc = (EncodeFn)fn;
        cudaFuncSetAttribute(fused_kernel, cudaFuncAttributeMaxDynamicSharedMemorySize, SMEM_BYTES);
    }
    CUtensorMap tmC, tmWk, tmWv, tmWq, tmWo, tmG, tmU, tmD;
    make_map2d(enc, &tmC, d_in[1], DC, SEQ);
    make_map2d(enc, &tmWq, d_in[2], 4096, DM, 64);
    make_map2d(enc, &tmWk, d_in[3], 4096, DC);
    make_map2d(enc, &tmWv, d_in[4], 4096, DC);
    make_map3d(enc, &tmWo, d_in[5], DM, 4096, 32, 5);
    make_map3d(enc, &tmG, d_in[8], FF, DM, 64, 7);
    make_map3d(enc, &tmU, d_in[9], FF, DM, 64, 7);
    make_map3d(enc, &tmD, d_in[10], DM, FF, 64, 10);
    Params P;
    P.x = (const __nv_bfloat16*)d_in[0];
    P.c = (const __nv_bfloat16*)d_in[1];
    P.wk = (const __nv_bfloat16*)d_in[3];
    P.wv = (const __nv_bfloat16*)d_in[4];
    P.wo = (const __nv_bfloat16*)d_in[5];
    P.wr = (const __nv_bfloat16*)d_in[7];
    P.out = (__nv_bfloat16*)d_out;
    fused_kernel<<<132, 384, SMEM_BYTES>>>(tmC, tmWk, tmWv, tmWq, tmWo, tmG, tmU, tmD, P);
}
```
